```python
import torch

def _softmax(x, axis=-1):
    return torch.softmax(x, dim=axis)
def _gelu(x):
    return torch.nn.functional.gelu(x, approximate="tanh")
def _silu(x):
    return torch.nn.functional.silu(x)
def _sigmoid(x):
    return torch.sigmoid(x)
def _layernorm(x, axis=-1, eps=1e-5):
    m = x.mean(dim=axis, keepdim=True)
    v = x.var(dim=axis, keepdim=True, unbiased=False)
    return (x - m) / torch.sqrt(v + eps)
def _scatter_add(tgt, idx, src, axis=0):
    return tgt.clone().index_add_(axis, idx, src)
def _segment_sum(src, seg, n):
    out = torch.zeros((n,) + src.shape[1:], dtype=src.dtype)
    return out.index_add_(0, seg, src)
def _pad(x, pw):
    flat = tuple(v for pair in reversed(pw) for v in pair)
    return torch.nn.functional.pad(x, flat)

kernel_name = 'standalone__self_sup_conv_stem_wavlm__speech'

def setup_inputs():

    _w = (lambda a: (lambda t: t.to(torch.bfloat16) if t.is_floating_point() else t)(torch.as_tensor(a)))
    B, T, D, K = 2, 16000, 512, 31
    scale = (K * D) ** -0.5
    return {
        "x": _w((lambda *s: torch.randn(*s, dtype=torch.bfloat16) * 0.05)(B, T, D)),
        "w": _w((lambda *s: torch.randn(*s, dtype=torch.bfloat16) * 0.05)(K, D, D) * scale),
        "gn_gamma": _w((lambda *s: torch.randn(*s, dtype=torch.bfloat16) * 0.05)(D) * 0.1 + 1.0),
        "gn_beta": _w((lambda *s: torch.randn(*s, dtype=torch.bfloat16) * 0.05)(D) * 0.1),
    }

def reference(x, w, gn_gamma, gn_beta):
    B, T, D = x.shape
    K = w.shape[0]
    s = 2
    L = (T - K) // s + 1
    h = torch.einsum('blc,cd->bld', x[:, 0:s * L:s, :], w[0])
    for i in range(1, K):
        h = h + torch.einsum('blc,cd->bld', x[:, i:i + s * L:s, :], w[i])
    mu = torch.einsum('bld->bd', h)[:, None, :] / L
    var = torch.einsum('bld->bd', (h - mu) ** 2)[:, None, :] / L
    h = (h - mu) / torch.sqrt(var + 1e-5)
    h = h * gn_gamma[None, None, :] + gn_beta[None, None, :]
    return _gelu(h)
```

```cpp
#include <cuda_runtime.h>
#include <cuda_bf16.h>
#include <cuda.h>
#include <stdint.h>

namespace {

constexpr int LOUT = 7985;
constexpr int MT = 48;
constexpr int NT = 168;
constexpr int XBLK = NT * 128;
constexpr int WBLK = 16384;

__device__ __align__(1024) uint8_t g_X[32ull * 2 * 32 * XBLK];
__device__ __align__(1024) uint8_t g_W[32ull * 4 * 32 * WBLK];
__device__ __align__(1024) uint8_t g_Y[16ull * NT * 8192];
__device__ float g_part[16 * 8 * 128];
__device__ unsigned g_cnt[16];

__device__ const uint16_t g_cos_tab[128] = {
  0x3f80, 0x3f80, 0x3f7f, 0x3f7d, 0x3f7b, 0x3f78, 0x3f75, 0x3f71, 0x3f6d, 0x3f67, 0x3f62, 0x3f5c, 0x3f55, 0x3f4e, 0x3f46, 0x3f3e,
  0x3f35, 0x3f2c, 0x3f22, 0x3f18, 0x3f0e, 0x3f04, 0x3ef1, 0x3edb, 0x3ec4, 0x3eac, 0x3e95, 0x3e79, 0x3e48, 0x3e16, 0x3dc9, 0x3d49,
  0x0000, 0xbd49, 0xbdc9, 0xbe16, 0xbe48, 0xbe79, 0xbe95, 0xbeac, 0xbec4, 0xbedb, 0xbef1, 0xbf04, 0xbf0e, 0xbf18, 0xbf22, 0xbf2c,
  0xbf35, 0xbf3e, 0xbf46, 0xbf4e, 0xbf55, 0xbf5c, 0xbf62, 0xbf67, 0xbf6d, 0xbf71, 0xbf75, 0xbf78, 0xbf7b, 0xbf7d, 0xbf7f, 0xbf80,
  0xbf80, 0xbf80, 0xbf7f, 0xbf7d, 0xbf7b, 0xbf78, 0xbf75, 0xbf71, 0xbf6d, 0xbf67, 0xbf62, 0xbf5c, 0xbf55, 0xbf4e, 0xbf46, 0xbf3e,
  0xbf35, 0xbf2c, 0xbf22, 0xbf18, 0xbf0e, 0xbf04, 0xbef1, 0xbedb, 0xbec4, 0xbeac, 0xbe95, 0xbe79, 0xbe48, 0xbe16, 0xbdc9, 0xbd49,
  0x0000, 0x3d49, 0x3dc9, 0x3e16, 0x3e48, 0x3e79, 0x3e95, 0x3eac, 0x3ec4, 0x3edb, 0x3ef1, 0x3f04, 0x3f0e, 0x3f18, 0x3f22, 0x3f2c,
  0x3f35, 0x3f3e, 0x3f46, 0x3f4e, 0x3f55, 0x3f5c, 0x3f62, 0x3f67, 0x3f6d, 0x3f71, 0x3f75, 0x3f78, 0x3f7b, 0x3f7d, 0x3f7f, 0x3f80,
};

template<int SA>
__device__ __forceinline__ void wgmma_ss_n168(float (&d)[84], uint64_t da, uint64_t db, int sd) {
  asm volatile("{\n.reg .pred p;\nsetp.ne.b32 p, %86, 0;\n"
    "wgmma.mma_async.sync.aligned.m64n168k16.f32.bf16.bf16 "
    "{%0, %1, %2, %3, %4, %5, %6, %7, %8, %9, %10, %11, %12, %13, %14, %15, %16, %17, %18, %19, %20, %21, %22, %23, %24, %25, %26, %27, %28, %29, %30, %31, %32, %33, %34, %35, %36, %37, %38, %39, %40, %41, %42, %43, %44, %45, %46, %47, %48, %49, %50, %51, %52, %53, %54, %55, %56, %57, %58, %59, %60, %61, %62, %63, %64, %65, %66, %67, %68, %69, %70, %71, %72, %73, %74, %75, %76, %77, %78, %79, %80, %81, %82, %83}, %84, %85, p, %87, 1, 1, 0;\n}\n"
    : "+f"(d[0]), "+f"(d[1]), "+f"(d[2]), "+f"(d[3]), "+f"(d[4]), "+f"(d[5]), "+f"(d[6]), "+f"(d[7]), "+f"(d[8]), "+f"(d[9]), "+f"(d[10]), "+f"(d[11]), "+f"(d[12]), "+f"(d[13]), "+f"(d[14]), "+f"(d[15]), "+f"(d[16]), "+f"(d[17]), "+f"(d[18]), "+f"(d[19]), "+f"(d[20]), "+f"(d[21]), "+f"(d[22]), "+f"(d[23]), "+f"(d[24]), "+f"(d[25]), "+f"(d[26]), "+f"(d[27]), "+f"(d[28]), "+f"(d[29]), "+f"(d[30]), "+f"(d[31]), "+f"(d[32]), "+f"(d[33]), "+f"(d[34]), "+f"(d[35]), "+f"(d[36]), "+f"(d[37]), "+f"(d[38]), "+f"(d[39]), "+f"(d[40]), "+f"(d[41]), "+f"(d[42]), "+f"(d[43]), "+f"(d[44]), "+f"(d[45]), "+f"(d[46]), "+f"(d[47]), "+f"(d[48]), "+f"(d[49]), "+f"(d[50]), "+f"(d[51]), "+f"(d[52]), "+f"(d[53]), "+f"(d[54]), "+f"(d[55]), "+f"(d[56]), "+f"(d[57]), "+f"(d[58]), "+f"(d[59]), "+f"(d[60]), "+f"(d[61]), "+f"(d[62]), "+f"(d[63]), "+f"(d[64]), "+f"(d[65]), "+f"(d[66]), "+f"(d[67]), "+f"(d[68]), "+f"(d[69]), "+f"(d[70]), "+f"(d[71]), "+f"(d[72]), "+f"(d[73]), "+f"(d[74]), "+f"(d[75]), "+f"(d[76]), "+f"(d[77]), "+f"(d[78]), "+f"(d[79]), "+f"(d[80]), "+f"(d[81]), "+f"(d[82]), "+f"(d[83])
    : "l"(da), "l"(db), "r"(sd), "n"(SA));
}
__device__ __forceinline__ void wgmma_rs_n128(float (&d)[64], const uint32_t (&a)[4], uint64_t db, int sd) {
  asm volatile("{\n.reg .pred p;\nsetp.ne.b32 p, %69, 0;\n"
    "wgmma.mma_async.sync.aligned.m64n128k16.f32.bf16.bf16 "
    "{%0, %1, %2, %3, %4, %5, %6, %7, %8, %9, %10, %11, %12, %13, %14, %15, %16, %17, %18, %19, %20, %21, %22, %23, %24, %25, %26, %27, %28, %29, %30, %31, %32, %33, %34, %35, %36, %37, %38, %39, %40, %41, %42, %43, %44, %45, %46, %47, %48, %49, %50, %51, %52, %53, %54, %55, %56, %57, %58, %59, %60, %61, %62, %63}, {%64, %65, %66, %67}, %68, p, 1, 1, 1;\n}\n"
    : "+f"(d[0]), "+f"(d[1]), "+f"(d[2]), "+f"(d[3]), "+f"(d[4]), "+f"(d[5]), "+f"(d[6]), "+f"(d[7]), "+f"(d[8]), "+f"(d[9]), "+f"(d[10]), "+f"(d[11]), "+f"(d[12]), "+f"(d[13]), "+f"(d[14]), "+f"(d[15]), "+f"(d[16]), "+f"(d[17]), "+f"(d[18]), "+f"(d[19]), "+f"(d[20]), "+f"(d[21]), "+f"(d[22]), "+f"(d[23]), "+f"(d[24]), "+f"(d[25]), "+f"(d[26]), "+f"(d[27]), "+f"(d[28]), "+f"(d[29]), "+f"(d[30]), "+f"(d[31]), "+f"(d[32]), "+f"(d[33]), "+f"(d[34]), "+f"(d[35]), "+f"(d[36]), "+f"(d[37]), "+f"(d[38]), "+f"(d[39]), "+f"(d[40]), "+f"(d[41]), "+f"(d[42]), "+f"(d[43]), "+f"(d[44]), "+f"(d[45]), "+f"(d[46]), "+f"(d[47]), "+f"(d[48]), "+f"(d[49]), "+f"(d[50]), "+f"(d[51]), "+f"(d[52]), "+f"(d[53]), "+f"(d[54]), "+f"(d[55]), "+f"(d[56]), "+f"(d[57]), "+f"(d[58]), "+f"(d[59]), "+f"(d[60]), "+f"(d[61]), "+f"(d[62]), "+f"(d[63])
    : "r"(a[0]), "r"(a[1]), "r"(a[2]), "r"(a[3]), "l"(db), "r"(sd));
}
__device__ __forceinline__ void wgmma_rs_n64(float (&d)[32], const uint32_t (&a)[4], uint64_t db, int sd) {
  asm volatile("{\n.reg .pred p;\nsetp.ne.b32 p, %37, 0;\n"
    "wgmma.mma_async.sync.aligned.m64n64k16.f32.bf16.bf16 "
    "{%0, %1, %2, %3, %4, %5, %6, %7, %8, %9, %10, %11, %12, %13, %14, %15, %16, %17, %18, %19, %20, %21, %22, %23, %24, %25, %26, %27, %28, %29, %30, %31}, {%32, %33, %34, %35}, %36, p, 1, 1, 1;\n}\n"
    : "+f"(d[0]), "+f"(d[1]), "+f"(d[2]), "+f"(d[3]), "+f"(d[4]), "+f"(d[5]), "+f"(d[6]), "+f"(d[7]), "+f"(d[8]), "+f"(d[9]), "+f"(d[10]), "+f"(d[11]), "+f"(d[12]), "+f"(d[13]), "+f"(d[14]), "+f"(d[15]), "+f"(d[16]), "+f"(d[17]), "+f"(d[18]), "+f"(d[19]), "+f"(d[20]), "+f"(d[21]), "+f"(d[22]), "+f"(d[23]), "+f"(d[24]), "+f"(d[25]), "+f"(d[26]), "+f"(d[27]), "+f"(d[28]), "+f"(d[29]), "+f"(d[30]), "+f"(d[31])
    : "r"(a[0]), "r"(a[1]), "r"(a[2]), "r"(a[3]), "l"(db), "r"(sd));
}


__device__ __forceinline__ uint32_t s2u(const void* p) { return (uint32_t)__cvta_generic_to_shared(p); }
__device__ __forceinline__ void mbar_init(uint32_t a, int c) { asm volatile("mbarrier.init.shared::cta.b64 [%0], %1;" ::"r"(a), "r"(c)); }
__device__ __forceinline__ void mbar_expect(uint32_t a, int b) { asm volatile("mbarrier.arrive.expect_tx.shared::cta.b64 _, [%0], %1;" ::"r"(a), "r"(b) : "memory"); }
__device__ __forceinline__ void mbar_arrive(uint32_t a) { asm volatile("mbarrier.arrive.shared::cta.b64 _, [%0];" ::"r"(a) : "memory"); }
__device__ __forceinline__ void mbar_arrive_cluster(uint32_t a, uint32_t cta, uint32_t cnt) {
  asm volatile("{\n.reg .b32 r;\nmapa.shared::cluster.u32 r, %0, %1;\nmbarrier.arrive.release.cluster.shared::cluster.b64 _, [r], %2;\n}" ::"r"(a), "r"(cta), "r"(cnt) : "memory");
}
__device__ __forceinline__ void mbar_wait(uint32_t a, int ph) {
  asm volatile("{\n.reg .pred p;\n.reg .u32 c;\nmov.u32 c, 0;\nWAIT:\n"
               "mbarrier.try_wait.parity.shared::cta.b64 p, [%0], %1;\n@p bra DONE;\n"
               "add.u32 c, c, 1;\nsetp.lt.u32 p, c, 0x400000;\n@p bra WAIT;\ntrap;\nDONE:\n}" ::"r"(a), "r"(ph) : "memory");
}
__device__ __forceinline__ void mbar_wait_cluster(uint32_t a, int ph) {
  asm volatile("{\n.reg .pred p;\n.reg .u32 c;\nmov.u32 c, 0;\nWAIT:\n"
               "mbarrier.try_wait.parity.acquire.cluster.shared::cta.b64 p, [%0], %1;\n@p bra DONE;\n"
               "add.u32 c, c, 1;\nsetp.lt.u32 p, c, 0x400000;\n@p bra WAIT;\ntrap;\nDONE:\n}" ::"r"(a), "r"(ph) : "memory");
}
__device__ __forceinline__ void bulk_ld(uint32_t dst, const void* src, int bytes, uint32_t bar) {
  asm volatile("cp.async.bulk.shared::cluster.global.mbarrier::complete_tx::bytes [%0], [%1], %2, [%3];" ::"r"(dst), "l"(src), "r"(bytes), "r"(bar) : "memory");
}
__device__ __forceinline__ void bulk_ld_mc(uint32_t dst, const void* src, int bytes, uint32_t bar, uint16_t mask) {
  asm volatile("cp.async.bulk.shared::cluster.global.mbarrier::complete_tx::bytes.multicast::cluster [%0], [%1], %2, [%3], %4;" ::"r"(dst), "l"(src), "r"(bytes), "r"(bar), "h"(mask) : "memory");
}
__device__ __forceinline__ void tma_ld2(uint32_t dst, const CUtensorMap* tm, int c0, int c1, uint32_t bar) {
  asm volatile("cp.async.bulk.tensor.2d.shared::cluster.global.mbarrier::complete_tx::bytes [%0], [%1, {%3,%4}], [%2];" ::"r"(dst), "l"(tm), "r"(bar), "r"(c0), "r"(c1) : "memory");
}
__device__ __forceinline__ void tma_ld3(uint32_t dst, const CUtensorMap* tm, int c0, int c1, int c2, uint32_t bar) {
  asm volatile("cp.async.bulk.tensor.3d.shared::cluster.global.mbarrier::complete_tx::bytes [%0], [%1, {%3,%4,%5}], [%2];" ::"r"(dst), "l"(tm), "r"(bar), "r"(c0), "r"(c1), "r"(c2) : "memory");
}
__device__ __forceinline__ void tma_st4(const CUtensorMap* tm, uint32_t src, int c0, int c1, int c2, int c3) {
  asm volatile("cp.async.bulk.tensor.4d.global.shared::cta.bulk_group [%0, {%2,%3,%4,%5}], [%1];" ::"l"(tm), "r"(src), "r"(c0), "r"(c1), "r"(c2), "r"(c3) : "memory");
}
__device__ __forceinline__ void wg_fence() { asm volatile("wgmma.fence.sync.aligned;" ::: "memory"); }
__device__ __forceinline__ void wg_commit() { asm volatile("wgmma.commit_group.sync.aligned;" ::: "memory"); }
template <int N> __device__ __forceinline__ void wg_wait() { asm volatile("wgmma.wait_group.sync.aligned %0;" ::"n"(N) : "memory"); }
template <int R> __device__ __forceinline__ void fence_regs(float (&d)[R]) {
#pragma unroll
  for (int i = 0; i < R; i++) asm volatile("" : "+f"(d[i])::"memory");
}
__device__ __forceinline__ uint64_t mk_desc(uint32_t addr, uint32_t lbo, uint32_t sbo) {
  return (uint64_t)((addr & 0x3FFFF) >> 4) | ((uint64_t)(lbo >> 4) << 16) | ((uint64_t)(sbo >> 4) << 32) | (1ull << 62);
}
__device__ __forceinline__ uint32_t pack2(float lo, float hi) {
  uint32_t r;
  asm("cvt.rn.bf16x2.f32 %0, %1, %2;" : "=r"(r) : "f"(hi), "f"(lo));
  return r;
}
__device__ __forceinline__ void stg128(void* p, uint32_t a, uint32_t b, uint32_t c, uint32_t d) {
  asm volatile("st.global.v4.b32 [%0], {%1,%2,%3,%4};" ::"l"(p), "r"(a), "r"(b), "r"(c), "r"(d) : "memory");
}
__device__ __forceinline__ uint32_t tw2(int m0, int m1) {
  return (uint32_t)g_cos_tab[m0 & 127] | ((uint32_t)g_cos_tab[m1 & 127] << 16);
}

constexpr int K1_BOX = 208 * 128;
constexpr int K1_STAGE = 2 * K1_BOX;
constexpr int K1_NST = 4;
constexpr int K1_ITEMS = 8 * 212;
constexpr int K1_SMEM = K1_NST * K1_STAGE + 1024;

__device__ __forceinline__ void k1_decode(int item, bool& isx, int& cg, int& idx) {
  cg = item / 212;
  int r = item - cg * 212;
  int nx = (r * 84) / 212;
  isx = ((r + 1) * 84) / 212 > nx;
  idx = isx ? nx : r - nx;
}

__global__ void __launch_bounds__(288, 1)
k1_transform(const __grid_constant__ CUtensorMap tmX, const __grid_constant__ CUtensorMap tmWe, const __grid_constant__ CUtensorMap tmWo) {
  extern __shared__ uint8_t smem_raw[];
  __shared__ uint64_t bars[2 * K1_NST];
  const uint32_t sbase = (s2u(smem_raw) + 1023) & ~1023u;
  const uint32_t full = s2u(bars), empty = full + 8 * K1_NST;
  const int warp = threadIdx.x >> 5, lane = threadIdx.x & 31;
  if (threadIdx.x == 0) {
    for (int i = 0; i < K1_NST; i++) { mbar_init(full + 8 * i, 1); mbar_init(empty + 8 * i, 1); }
    asm volatile("fence.mbarrier_init.release.cluster;" ::: "memory");
  }
  if (blockIdx.x == 0 && threadIdx.x < 16) g_cnt[threadIdx.x] = 0;
  __syncthreads();
  if (warp == 8) {
    if (lane == 0) {
      int k = 0;
      for (int item = blockIdx.x; item < K1_ITEMS; item += gridDim.x, k++) {
        const int s = k % K1_NST;
        bool isx; int cg, idx;
        k1_decode(item, isx, cg, idx);
        mbar_wait(empty + 8 * s, ((k / K1_NST) & 1) ^ 1);
        const uint32_t dst = sbase + s * K1_STAGE;
        if (isx) {
          const int b = idx / 42, tg = idx - b * 42;
          mbar_expect(full + 8 * s, K1_STAGE);
          tma_ld3(dst, &tmX, cg * 128, tg * 192, b, full + 8 * s);
          tma_ld3(dst + K1_BOX, &tmX, cg * 128 + 64, tg * 192, b, full + 8 * s);
        } else {
          const int cp = cg * 128 + idx;
          mbar_expect(full + 8 * s, 16384);
          tma_ld3(dst, cp < 512 ? &tmWe : &tmWo, 0, 0, (cp & 511) * 8, full + 8 * s);
        }
      }
    }
  } else {
    const int wg = warp >> 2, w = warp & 3, a = lane & 3;
    const int u = 8 * w + (lane >> 2);
    uint32_t fa[4][4];
#pragma unroll
    for (int kk = 0; kk < 4; kk++) {
      const int n0 = 16 * kk + 2 * a, f = 2 * u + 1;
      fa[kk][0] = tw2(f * n0, f * (n0 + 1));
      fa[kk][1] = tw2(f * n0 + 32, f * (n0 + 1) + 32);
      fa[kk][2] = tw2(f * (n0 + 8), f * (n0 + 9));
      fa[kk][3] = tw2(f * (n0 + 8) + 32, f * (n0 + 9) + 32);
    }
    float acc[64];
    int k = wg;
    for (int item = blockIdx.x + wg * gridDim.x; item < K1_ITEMS; item += 2 * gridDim.x, k += 2) {
      const int s = k % K1_NST;
      bool isx; int cg, idx;
      k1_decode(item, isx, cg, idx);
      mbar_wait(full + 8 * s, (k / K1_NST) & 1);
      const uint32_t src = sbase + s * K1_STAGE;
      if (isx) {
        const int b = idx / 42, tg = idx - b * 42;
        uint8_t* base = g_X + (size_t)((u * 2 + b) * 32 + cg * 4) * XBLK;
#pragma unroll 1
        for (int tt = 0; tt < 4; tt++) {
          wg_fence();
#pragma unroll
          for (int kk = 0; kk < 4; kk++) wgmma_rs_n128(acc, fa[kk], mk_desc(src + (48 * tt + 16 * kk) * 128, K1_BOX, 1024), kk);
          wg_commit();
          wg_wait<0>();
          fence_regs(acc);
          if (tt == 3 && (threadIdx.x & 127) == 0) mbar_arrive(empty + 8 * s);
          const int t = tg * 4 + tt;
          uint8_t* p = base + t * 128;
          const int o0 = (a ^ (t & 7)) << 4, o1 = o0 ^ 64;
#pragma unroll
          for (int g = 0; g < 4; g++) {
            const float* c = acc + 16 * g;
            stg128(p + g * XBLK + o0, pack2(c[0], c[1]), pack2(c[4], c[5]), pack2(c[8], c[9]), pack2(c[12], c[13]));
            stg128(p + g * XBLK + o1, pack2(c[2], c[3]), pack2(c[6], c[7]), pack2(c[10], c[11]), pack2(c[14], c[15]));
          }
        }
      } else {
        const int cp = cg * 128 + idx;
        const int ks = cp >> 5, cl = cp & 31;
        const int kap = 8 * ((cl >> 1) & 3) + 2 * (cl >> 3) + (cl & 1);
        uint8_t* base = g_W + (size_t)(u * 4 * 32 + ks) * WBLK + kap * 128;
        const int o0 = (a ^ (kap & 7)) << 4;
#pragma unroll 1
        for (int dt = 0; dt < 4; dt++) {
          wg_fence();
          wgmma_rs_n128(acc, fa[0], mk_desc(src + dt * 4096, 2048, 1024), 0);
          wg_commit();
          wg_wait<0>();
          fence_regs(acc);
          if (dt == 3 && (threadIdx.x & 127) == 0) mbar_arrive(empty + 8 * s);
          uint8_t* p = base + (size_t)dt * 32 * WBLK;
#pragma unroll
          for (int g = 0; g < 4; g++) {
            const float* c = acc + 16 * g;
            uint8_t* q = p + (g >> 1) * 8192 + (o0 ^ ((g & 1) * 64));
            stg128(q, pack2(c[0], c[1]), pack2(c[4], c[5]), pack2(c[8], c[9]), pack2(c[12], c[13]));
            stg128(q + 4096, pack2(c[2], c[3]), pack2(c[6], c[7]), pack2(c[10], c[11]), pack2(c[14], c[15]));
          }
        }
      }
    }
  }
}

constexpr int K2_STAGE = WBLK + XBLK;
constexpr int K2_NST = 6;
constexpr int K2_SMEM = K2_NST * K2_STAGE + 1024;
constexpr int K2_USES = 35;

__global__ void __cluster_dims__(2, 1, 1) __launch_bounds__(384, 1)
k2_gemm(const __grid_constant__ CUtensorMap tmYst) {
  extern __shared__ uint8_t smem_raw[];
  __shared__ uint64_t bars[2 * K2_NST + 1];
  const uint32_t sbase = (s2u(smem_raw) + 1023) & ~1023u;
  const uint32_t full = s2u(bars), empty = full + 8 * K2_NST, stg_ready = empty + 8 * K2_NST;
  const int warp = threadIdx.x >> 5, lane = threadIdx.x & 31;
  const uint32_t rank = blockIdx.x & 1;
  const int pr = blockIdx.x >> 1;
  const int dt = (pr & 1) * 2 + rank, b = (pr >> 1) & 1, ul = pr >> 2;
  if (threadIdx.x == 0) {
    for (int i = 0; i < K2_NST; i++) { mbar_init(full + 8 * i, 1); mbar_init(empty + 8 * i, 4); }
    mbar_init(stg_ready, 256);
    asm volatile("fence.mbarrier_init.release.cluster;" ::: "memory");
  }
  __syncthreads();
  asm volatile("barrier.cluster.arrive.aligned;\nbarrier.cluster.wait.aligned;" ::: "memory");
  if (warp >= 8) {
    asm volatile("setmaxnreg.dec.sync.aligned.u32 40;");
    if (warp == 8 && lane == 0) {
      int s = 0, ph = 1;
      for (int pass = 0; pass < 2; pass++) {
        const int u = pass * 16 + ul;
        const uint8_t* xs = g_X + (size_t)((u * 2 + b) * 32) * XBLK + rank * (XBLK / 2);
        const uint8_t* ws = g_W + (size_t)((u * 4 + dt) * 32) * WBLK;
        for (int i = 0; i < K2_USES; i++) {
          mbar_wait_cluster(empty + 8 * s, ph);
          if (i < 32) {
            const int ks = 31 - i;
            const uint32_t dst = sbase + s * K2_STAGE;
            mbar_expect(full + 8 * s, K2_STAGE);
            bulk_ld(dst, ws + (size_t)ks * WBLK, WBLK, full + 8 * s);
            bulk_ld_mc(dst + WBLK + rank * (XBLK / 2), xs + (size_t)ks * XBLK, XBLK / 2, full + 8 * s, 3);
          } else {
            mbar_arrive(full + 8 * s);
          }
          if (++s == K2_NST) { s = 0; ph ^= 1; }
        }
      }
    } else if (warp == 9 && lane == 0) {
      for (int pass = 0; pass < 2; pass++) {
        const int u = pass * 16 + ul;
        const int s0 = (pass * K2_USES + 32) % K2_NST;
        mbar_wait(stg_ready, pass);
        const uint32_t src = sbase + s0 * K2_STAGE;
        tma_st4(&tmYst, src, 0, 0, 2 * u, b * 8 + dt * 2);
        tma_st4(&tmYst, src + 2 * XBLK, 0, 0, 2 * u, b * 8 + dt * 2 + 1);
        asm volatile("cp.async.bulk.commit_group;" ::: "memory");
        if (pass == 0) {
          asm volatile("cp.async.bulk.wait_group.read 0;" ::: "memory");
          for (int i = 0; i < 3; i++) {
            mbar_arrive_cluster(empty + 8 * (s0 + i), 0, 2);
            mbar_arrive_cluster(empty + 8 * (s0 + i), 1, 2);
          }
        } else {
          asm volatile("cp.async.bulk.wait_group 0;" ::: "memory");
        }
      }
    }
    asm volatile("barrier.cluster.arrive;\nbarrier.cluster.wait;" ::: "memory");
  } else {
    asm volatile("setmaxnreg.inc.sync.aligned.u32 232;");
    const int wg = warp >> 2, w = warp & 3;
    float yr[84], yi[84];
    int s = 0, ph = 0;
    for (int pass = 0; pass < 2; pass++) {
      int sprev = 0;
#pragma unroll 1
      for (int i = 0; i < 32; i++) {
        mbar_wait(full + 8 * s, ph);
        const uint32_t st = sbase + s * K2_STAGE;
        const uint64_t dwr = mk_desc(st + wg * 8192, 1024, 1024), dx = mk_desc(st + WBLK, 16, 1024);
        wg_fence();
#pragma unroll
        for (int kk = 0; kk < 2; kk++) {
          const uint64_t wr = dwr + kk * (2048 >> 4), wi = wr + (4096 >> 4);
          const uint64_t xr = dx + kk * 2, xi = xr + 4;
          const int sd = (i | kk) != 0;
          wgmma_ss_n168<1>(yr, wr, xr, sd);
          wgmma_ss_n168<1>(yi, wr, xi, sd);
          wgmma_ss_n168<1>(yr, wi, xi, 1);
          wgmma_ss_n168<-1>(yi, wi, xr, 1);
        }
        wg_commit();
        if (i > 0) {
          wg_wait<1>();
          if (w == 0 && lane < 2) mbar_arrive_cluster(empty + 8 * sprev, lane, 1);
        }
        sprev = s;
        if (++s == K2_NST) { s = 0; ph ^= 1; }
      }
      wg_wait<0>();
      fence_regs(yr);
      fence_regs(yi);
      if (w == 0 && lane < 2) mbar_arrive_cluster(empty + 8 * sprev, lane, 1);
      const uint32_t stg = sbase + s * K2_STAGE + wg * 2 * XBLK;
#pragma unroll 1
      for (int i = 0; i < 3; i++) {
        mbar_wait(full + 8 * s, ph);
        if (++s == K2_NST) { s = 0; ph ^= 1; }
      }
      const int m = lane >> 3, r = lane & 7;
      const uint32_t ad = stg + (m >> 1) * XBLK + r * 128 + (((2 * w + (m & 1)) ^ r) << 4);
#pragma unroll
      for (int j = 0; j < 21; j++) {
        asm volatile("stmatrix.sync.aligned.m8n8.x4.trans.shared.b16 [%0], {%1,%2,%3,%4};" ::"r"(ad + j * 1024),
                     "r"(pack2(yr[4 * j], yr[4 * j + 1])), "r"(pack2(yr[4 * j + 2], yr[4 * j + 3])),
                     "r"(pack2(yi[4 * j], yi[4 * j + 1])), "r"(pack2(yi[4 * j + 2], yi[4 * j + 3]))
                     : "memory");
      }
      asm volatile("fence.proxy.async.shared::cta;" ::: "memory");
      mbar_arrive(stg_ready);
    }
    asm volatile("barrier.cluster.arrive.aligned;\nbarrier.cluster.wait.aligned;" ::: "memory");
  }
}

constexpr int K3_TILES = 21;
constexpr int K3_SMEM = K3_TILES * 8192 + 1024;

__global__ void __launch_bounds__(512, 1)
k3_inverse(const __grid_constant__ CUtensorMap tmYld, const __nv_bfloat16* __restrict__ gamma, const __nv_bfloat16* __restrict__ beta,
           __nv_bfloat16* __restrict__ out) {
  extern __shared__ uint8_t smem_raw[];
  __shared__ uint64_t bars[7];
  __shared__ float s_red[16][128];
  __shared__ float s_par[128];
  const uint32_t sbase = (s2u(smem_raw) + 1023) & ~1023u;
  const uint32_t full = s2u(bars);
  const int warp = threadIdx.x >> 5, lane = threadIdx.x & 31;
  const int grp = blockIdx.x >> 3, tr = blockIdx.x & 7;
  const int b = grp >> 3, d64 = grp & 7;
  const int t0 = tr * K3_TILES;
  if (threadIdx.x == 0) {
    for (int i = 0; i < 7; i++) mbar_init(full + 8 * i, 1);
    asm volatile("fence.mbarrier_init.release.cluster;" ::: "memory");
  }
  __syncthreads();
  if (lane == 0 && warp < 7) {
    mbar_expect(full + 8 * warp, 3 * 8192);
    tma_ld2(sbase + warp * 3 * 8192, &tmYld, 0, (grp * NT + t0 + warp * 3) * 64, full + 8 * warp);
  }
  const int wg = warp >> 2, w = warp & 3, a = lane & 3;
  const bool active = (w != wg);
  const int mb = w < wg ? w : w - 1;
  const int p0 = 16 * mb + (lane >> 2);
  uint32_t ga[4][4];
#pragma unroll
  for (int kk = 0; kk < 4; kk++) {
    const int f0 = 2 * (8 * kk + a) + 1, f1 = f0 + 8;
    ga[kk][0] = active ? tw2(f0 * p0, f0 * p0 + 32) : 0u;
    ga[kk][1] = active ? tw2(f0 * (p0 + 8), f0 * (p0 + 8) + 32) : 0u;
    ga[kk][2] = active ? tw2(f1 * p0, f1 * p0 + 32) : 0u;
    ga[kk][3] = active ? tw2(f1 * (p0 + 8), f1 * (p0 + 8) + 32) : 0u;
  }
  float acc[32];
  float s1[16], s2[16];
#pragma unroll
  for (int i = 0; i < 16; i++) { s1[i] = 0.f; s2[i] = 0.f; }
#pragma unroll 1
  for (int tl = wg; tl < K3_TILES; tl += 4) {
    mbar_wait(full + 8 * (tl / 3), 0);
    wg_fence();
#pragma unroll
    for (int kk = 0; kk < 4; kk++) wgmma_rs_n64(acc, ga[kk], mk_desc(sbase + tl * 8192 + kk * 2048, 1024, 1024), kk);
    wg_commit();
    wg_wait<0>();
    fence_regs(acc);
    if (active) {
      const int l0 = (t0 + tl) * MT + p0;
      const bool v0 = l0 < LOUT, v1 = l0 + 8 < LOUT;
#pragma unroll
      for (int j = 0; j < 8; j++) {
#pragma unroll
        for (int e = 0; e < 2; e++) {
          const float x0 = v0 ? acc[4 * j + e] : 0.f, x1 = v1 ? acc[4 * j + 2 + e] : 0.f;
          s1[2 * j + e] += x0 + x1;
          s2[2 * j + e] = fmaf(x0, x0, fmaf(x1, x1, s2[2 * j + e]));
        }
      }
    }
  }
#pragma unroll
  for (int i = 0; i < 16; i++) {
#pragma unroll
    for (int o = 4; o < 32; o <<= 1) {
      s1[i] += __shfl_xor_sync(0xffffffffu, s1[i], o);
      s2[i] += __shfl_xor_sync(0xffffffffu, s2[i], o);
    }
  }
  if (lane < 4) {
#pragma unroll
    for (int i = 0; i < 16; i++) {
      const int d = 32 * (i >> 3) + 8 * a + (i & 7);
      s_red[warp][d] = s1[i];
      s_red[warp][64 + d] = s2[i];
    }
  }
  __syncthreads();
  if (threadIdx.x < 128) {
    float t = 0.f;
#pragma unroll
    for (int i = 0; i < 16; i++) t += s_red[i][threadIdx.x];
    g_part[(grp * 8 + tr) * 128 + threadIdx.x] = t;
    __threadfence();
    asm volatile("bar.sync 1, 128;" ::: "memory");
    if (threadIdx.x == 0) {
      asm volatile("red.release.gpu.global.add.u32 [%0], 1;" ::"l"(&g_cnt[grp]) : "memory");
      unsigned v;
      int it = 0;
      do {
        asm volatile("ld.acquire.gpu.global.u32 %0, [%1];" : "=r"(v) : "l"(&g_cnt[grp]) : "memory");
        if (++it > (1 << 22)) __trap();
      } while (v < 8);
    }
    asm volatile("bar.sync 1, 128;" ::: "memory");
    if (threadIdx.x < 64) {
      float a1 = 0.f, a2 = 0.f;
#pragma unroll
      for (int i = 0; i < 8; i++) {
        a1 += __ldcg(&g_part[(grp * 8 + i) * 128 + threadIdx.x]);
        a2 += __ldcg(&g_part[(grp * 8 + i) * 128 + 64 + threadIdx.x]);
      }
      const float sc = 1.f / 32.f;
      const float mu = a1 * (sc / LOUT);
      const float var = fmaxf(a2 * (sc * sc / LOUT) - mu * mu, 0.f);
      const float g = __bfloat162float(gamma[d64 * 64 + threadIdx.x]) / sqrtf(var + 1e-5f);
      s_par[threadIdx.x] = g * sc;
      s_par[64 + threadIdx.x] = __bfloat162float(beta[d64 * 64 + threadIdx.x]) - mu * g;
    }
  }
  __syncthreads();
#pragma unroll
  for (int i = 0; i < 16; i++) {
    const int d = 32 * (i >> 3) + 8 * a + (i & 7);
    s1[i] = s_par[d];
    s2[i] = s_par[64 + d];
  }
#pragma unroll 1
  for (int tl = wg; tl < K3_TILES; tl += 4) {
    wg_fence();
#pragma unroll
    for (int kk = 0; kk < 4; kk++) wgmma_rs_n64(acc, ga[kk], mk_desc(sbase + tl * 8192 + kk * 2048, 1024, 1024), kk);
    wg_commit();
    wg_wait<0>();
    fence_regs(acc);
    if (active) {
      const int l0 = (t0 + tl) * MT + p0;
#pragma unroll
      for (int i = 0; i < 32; i++) {
        const int c = 2 * (i >> 2) + (i & 1);
        const float z = fmaf(acc[i], s1[c], s2[c]);
        const float in = z * fmaf(z * z, 0.044715f * 0.7978845608028654f, 0.7978845608028654f);
        float th;
        asm("tanh.approx.f32 %0, %1;" : "=f"(th) : "f"(in));
        const float hz = 0.5f * z;
        acc[i] = fmaf(hz, th, hz);
      }
      uint8_t* p = (uint8_t*)out + ((size_t)b * LOUT + l0) * 1024 + d64 * 128 + a * 16;
#pragma unroll
      for (int h = 0; h < 2; h++) {
        const float* c = acc + 16 * h;
        if (l0 < LOUT) stg128(p + h * 64, pack2(c[0], c[1]), pack2(c[4], c[5]), pack2(c[8], c[9]), pack2(c[12], c[13]));
        if (l0 + 8 < LOUT) stg128(p + 8 * 1024 + h * 64, pack2(c[2], c[3]), pack2(c[6], c[7]), pack2(c[10], c[11]), pack2(c[14], c[15]));
      }
    }
  }
}

typedef CUresult (*EncFn)(CUtensorMap*, CUtensorMapDataType, cuuint32_t, void*, const cuuint64_t*, const cuuint64_t*, const cuuint32_t*,
                          const cuuint32_t*, CUtensorMapInterleave, CUtensorMapSwizzle, CUtensorMapL2promotion, CUtensorMapFloatOOBfill);

struct Maps { CUtensorMap x, we, wo, yst, yld; };

void encode(EncFn fn, CUtensorMap* m, int rank, void* base, const cuuint64_t* dims, const cuuint64_t* strides, const cuuint32_t* box,
            CUtensorMapL2promotion promo) {
  cuuint32_t es[5] = {1, 1, 1, 1, 1};
  fn(m, CU_TENSOR_MAP_DATA_TYPE_BFLOAT16, rank, base, dims, strides, box, es, CU_TENSOR_MAP_INTERLEAVE_NONE, CU_TENSOR_MAP_SWIZZLE_128B, promo,
     CU_TENSOR_MAP_FLOAT_OOB_FILL_NONE);
}

}

extern "C" void kernel_launch(void* const* d_in, const int* in_sizes, int n_in, void* d_out, int out_size) {
  (void)in_sizes; (void)n_in; (void)out_size;
  const __nv_bfloat16* x = (const __nv_bfloat16*)d_in[0];
  const __nv_bfloat16* w = (const __nv_bfloat16*)d_in[1];
  const __nv_bfloat16* gamma = (const __nv_bfloat16*)d_in[2];
  const __nv_bfloat16* beta = (const __nv_bfloat16*)d_in[3];
  void* fnp = nullptr;
  cudaDriverEntryPointQueryResult qr;
  cudaGetDriverEntryPoint("cuTensorMapEncodeTiled", &fnp, cudaEnableDefault, &qr);
  EncFn fn = (EncFn)fnp;
  void* yptr = nullptr;
  cudaGetSymbolAddress(&yptr, g_Y);
  Maps m;
  {
    cuuint64_t d[3] = {1024, 8000, 2}, s[2] = {2048, 8000ull * 2048};
    cuuint32_t bx[3] = {64, 208, 1};
    encode(fn, &m.x, 3, (void*)x, d, s, bx, CU_TENSOR_MAP_L2_PROMOTION_L2_256B);
  }
  for (int ph = 0; ph < 2; ph++) {
    cuuint64_t d[3] = {64, (cuuint64_t)(16 - ph), 4096}, s[2] = {2ull * 262144 * 2, 128};
    cuuint32_t bx[3] = {64, 16, 8};
    encode(fn, ph ? &m.wo : &m.we, 3, (void*)(w + (size_t)ph * 262144), d, s, bx, CU_TENSOR_MAP_L2_PROMOTION_L2_256B);
  }
  {
    cuuint64_t d[4] = {64, NT, 64, 16}, s[3] = {8192, 128, (cuuint64_t)NT * 8192};
    cuuint32_t bx[4] = {64, NT, 2, 1};
    encode(fn, &m.yst, 4, yptr, d, s, bx, CU_TENSOR_MAP_L2_PROMOTION_NONE);
  }
  {
    cuuint64_t d[2] = {64, 16ull * NT * 64}, s[1] = {128};
    cuuint32_t bx[2] = {64, 192};
    encode(fn, &m.yld, 2, yptr, d, s, bx, CU_TENSOR_MAP_L2_PROMOTION_L2_256B);
  }
  cudaFuncSetAttribute(k1_transform, cudaFuncAttributeMaxDynamicSharedMemorySize, K1_SMEM);
  cudaFuncSetAttribute(k2_gemm, cudaFuncAttributeMaxDynamicSharedMemorySize, K2_SMEM);
  cudaFuncSetAttribute(k3_inverse, cudaFuncAttributeMaxDynamicSharedMemorySize, K3_SMEM);
  k1_transform<<<132, 288, K1_SMEM>>>(m.x, m.we, m.wo);
  k2_gemm<<<128, 384, K2_SMEM>>>(m.yst);
  k3_inverse<<<128, 512, K3_SMEM>>>(m.yld, gamma, beta, (__nv_bfloat16*)d_out);
}
```

```cpp
#include <cuda_runtime.h>
#include <cuda_bf16.h>
#include <cuda.h>
#include <stdint.h>

namespace {

constexpr int LOUT = 7985;
constexpr int MT = 48;
constexpr int NT = 168;
constexpr int XBLK = NT * 128;
constexpr int WBLK = 16384;

__device__ __align__(1024) uint8_t g_X[32ull * 2 * 32 * XBLK];
__device__ __align__(1024) uint8_t g_W[32ull * 4 * 32 * WBLK];
__device__ __align__(1024) uint8_t g_Y[16ull * NT * 8192];
__device__ float g_part[16 * 8 * 128];
__device__ unsigned g_cnt[16];

__device__ const uint16_t g_cos_tab[128] = {
  0x3f80, 0x3f80, 0x3f7f, 0x3f7d, 0x3f7b, 0x3f78, 0x3f75, 0x3f71, 0x3f6d, 0x3f67, 0x3f62, 0x3f5c, 0x3f55, 0x3f4e, 0x3f46, 0x3f3e,
  0x3f35, 0x3f2c, 0x3f22, 0x3f18, 0x3f0e, 0x3f04, 0x3ef1, 0x3edb, 0x3ec4, 0x3eac, 0x3e95, 0x3e79, 0x3e48, 0x3e16, 0x3dc9, 0x3d49,
  0x0000, 0xbd49, 0xbdc9, 0xbe16, 0xbe48, 0xbe79, 0xbe95, 0xbeac, 0xbec4, 0xbedb, 0xbef1, 0xbf04, 0xbf0e, 0xbf18, 0xbf22, 0xbf2c,
  0xbf35, 0xbf3e, 0xbf46, 0xbf4e, 0xbf55, 0xbf5c, 0xbf62, 0xbf67, 0xbf6d, 0xbf71, 0xbf75, 0xbf78, 0xbf7b, 0xbf7d, 0xbf7f, 0xbf80,
  0xbf80, 0xbf80, 0xbf7f, 0xbf7d, 0xbf7b, 0xbf78, 0xbf75, 0xbf71, 0xbf6d, 0xbf67, 0xbf62, 0xbf5c, 0xbf55, 0xbf4e, 0xbf46, 0xbf3e,
  0xbf35, 0xbf2c, 0xbf22, 0xbf18, 0xbf0e, 0xbf04, 0xbef1, 0xbedb, 0xbec4, 0xbeac, 0xbe95, 0xbe79, 0xbe48, 0xbe16, 0xbdc9, 0xbd49,
  0x0000, 0x3d49, 0x3dc9, 0x3e16, 0x3e48, 0x3e79, 0x3e95, 0x3eac, 0x3ec4, 0x3edb, 0x3ef1, 0x3f04, 0x3f0e, 0x3f18, 0x3f22, 0x3f2c,
  0x3f35, 0x3f3e, 0x3f46, 0x3f4e, 0x3f55, 0x3f5c, 0x3f62, 0x3f67, 0x3f6d, 0x3f71, 0x3f75, 0x3f78, 0x3f7b, 0x3f7d, 0x3f7f, 0x3f80,
};

template<int SA>
__device__ __forceinline__ void wgmma_ss_n168(float (&d)[84], uint64_t da, uint64_t db, int sd) {
  asm volatile("{\n.reg .pred p;\nsetp.ne.b32 p, %86, 0;\n"
    "wgmma.mma_async.sync.aligned.m64n168k16.f32.bf16.bf16 "
    "{%0, %1, %2, %3, %4, %5, %6, %7, %8, %9, %10, %11, %12, %13, %14, %15, %16, %17, %18, %19, %20, %21, %22, %23, %24, %25, %26, %27, %28, %29, %30, %31, %32, %33, %34, %35, %36, %37, %38, %39, %40, %41, %42, %43, %44, %45, %46, %47, %48, %49, %50, %51, %52, %53, %54, %55, %56, %57, %58, %59, %60, %61, %62, %63, %64, %65, %66, %67, %68, %69, %70, %71, %72, %73, %74, %75, %76, %77, %78, %79, %80, %81, %82, %83}, %84, %85, p, %87, 1, 1, 0;\n}\n"
    : "+f"(d[0]), "+f"(d[1]), "+f"(d[2]), "+f"(d[3]), "+f"(d[4]), "+f"(d[5]), "+f"(d[6]), "+f"(d[7]), "+f"(d[8]), "+f"(d[9]), "+f"(d[10]), "+f"(d[11]), "+f"(d[12]), "+f"(d[13]), "+f"(d[14]), "+f"(d[15]), "+f"(d[16]), "+f"(d[17]), "+f"(d[18]), "+f"(d[19]), "+f"(d[20]), "+f"(d[21]), "+f"(d[22]), "+f"(d[23]), "+f"(d[24]), "+f"(d[25]), "+f"(d[26]), "+f"(d[27]), "+f"(d[28]), "+f"(d[29]), "+f"(d[30]), "+f"(d[31]), "+f"(d[32]), "+f"(d[33]), "+f"(d[34]), "+f"(d[35]), "+f"(d[36]), "+f"(d[37]), "+f"(d[38]), "+f"(d[39]), "+f"(d[40]), "+f"(d[41]), "+f"(d[42]), "+f"(d[43]), "+f"(d[44]), "+f"(d[45]), "+f"(d[46]), "+f"(d[47]), "+f"(d[48]), "+f"(d[49]), "+f"(d[50]), "+f"(d[51]), "+f"(d[52]), "+f"(d[53]), "+f"(d[54]), "+f"(d[55]), "+f"(d[56]), "+f"(d[57]), "+f"(d[58]), "+f"(d[59]), "+f"(d[60]), "+f"(d[61]), "+f"(d[62]), "+f"(d[63]), "+f"(d[64]), "+f"(d[65]), "+f"(d[66]), "+f"(d[67]), "+f"(d[68]), "+f"(d[69]), "+f"(d[70]), "+f"(d[71]), "+f"(d[72]), "+f"(d[73]), "+f"(d[74]), "+f"(d[75]), "+f"(d[76]), "+f"(d[77]), "+f"(d[78]), "+f"(d[79]), "+f"(d[80]), "+f"(d[81]), "+f"(d[82]), "+f"(d[83])
    : "l"(da), "l"(db), "r"(sd), "n"(SA));
}
__device__ __forceinline__ void wgmma_rs_n128(float (&d)[64], const uint32_t (&a)[4], uint64_t db, int sd) {
  asm volatile("{\n.reg .pred p;\nsetp.ne.b32 p, %69, 0;\n"
    "wgmma.mma_async.sync.aligned.m64n128k16.f32.bf16.bf16 "
    "{%0, %1, %2, %3, %4, %5, %6, %7, %8, %9, %10, %11, %12, %13, %14, %15, %16, %17, %18, %19, %20, %21, %22, %23, %24, %25, %26, %27, %28, %29, %30, %31, %32, %33, %34, %35, %36, %37, %38, %39, %40, %41, %42, %43, %44, %45, %46, %47, %48, %49, %50, %51, %52, %53, %54, %55, %56, %57, %58, %59, %60, %61, %62, %63}, {%64, %65, %66, %67}, %68, p, 1, 1, 1;\n}\n"
    : "+f"(d[0]), "+f"(d[1]), "+f"(d[2]), "+f"(d[3]), "+f"(d[4]), "+f"(d[5]), "+f"(d[6]), "+f"(d[7]), "+f"(d[8]), "+f"(d[9]), "+f"(d[10]), "+f"(d[11]), "+f"(d[12]), "+f"(d[13]), "+f"(d[14]), "+f"(d[15]), "+f"(d[16]), "+f"(d[17]), "+f"(d[18]), "+f"(d[19]), "+f"(d[20]), "+f"(d[21]), "+f"(d[22]), "+f"(d[23]), "+f"(d[24]), "+f"(d[25]), "+f"(d[26]), "+f"(d[27]), "+f"(d[28]), "+f"(d[29]), "+f"(d[30]), "+f"(d[31]), "+f"(d[32]), "+f"(d[33]), "+f"(d[34]), "+f"(d[35]), "+f"(d[36]), "+f"(d[37]), "+f"(d[38]), "+f"(d[39]), "+f"(d[40]), "+f"(d[41]), "+f"(d[42]), "+f"(d[43]), "+f"(d[44]), "+f"(d[45]), "+f"(d[46]), "+f"(d[47]), "+f"(d[48]), "+f"(d[49]), "+f"(d[50]), "+f"(d[51]), "+f"(d[52]), "+f"(d[53]), "+f"(d[54]), "+f"(d[55]), "+f"(d[56]), "+f"(d[57]), "+f"(d[58]), "+f"(d[59]), "+f"(d[60]), "+f"(d[61]), "+f"(d[62]), "+f"(d[63])
    : "r"(a[0]), "r"(a[1]), "r"(a[2]), "r"(a[3]), "l"(db), "r"(sd));
}
__device__ __forceinline__ void wgmma_rs_n64(float (&d)[32], const uint32_t (&a)[4], uint64_t db, int sd) {
  asm volatile("{\n.reg .pred p;\nsetp.ne.b32 p, %37, 0;\n"
    "wgmma.mma_async.sync.aligned.m64n64k16.f32.bf16.bf16 "
    "{%0, %1, %2, %3, %4, %5, %6, %7, %8, %9, %10, %11, %12, %13, %14, %15, %16, %17, %18, %19, %20, %21, %22, %23, %24, %25, %26, %27, %28, %29, %30, %31}, {%32, %33, %34, %35}, %36, p, 1, 1, 1;\n}\n"
    : "+f"(d[0]), "+f"(d[1]), "+f"(d[2]), "+f"(d[3]), "+f"(d[4]), "+f"(d[5]), "+f"(d[6]), "+f"(d[7]), "+f"(d[8]), "+f"(d[9]), "+f"(d[10]), "+f"(d[11]), "+f"(d[12]), "+f"(d[13]), "+f"(d[14]), "+f"(d[15]), "+f"(d[16]), "+f"(d[17]), "+f"(d[18]), "+f"(d[19]), "+f"(d[20]), "+f"(d[21]), "+f"(d[22]), "+f"(d[23]), "+f"(d[24]), "+f"(d[25]), "+f"(d[26]), "+f"(d[27]), "+f"(d[28]), "+f"(d[29]), "+f"(d[30]), "+f"(d[31])
    : "r"(a[0]), "r"(a[1]), "r"(a[2]), "r"(a[3]), "l"(db), "r"(sd));
}


__device__ __forceinline__ uint32_t s2u(const void* p) { return (uint32_t)__cvta_generic_to_shared(p); }
__device__ __forceinline__ void mbar_init(uint32_t a, int c) { asm volatile("mbarrier.init.shared::cta.b64 [%0], %1;" ::"r"(a), "r"(c)); }
__device__ __forceinline__ void mbar_expect(uint32_t a, int b) { asm volatile("mbarrier.arrive.expect_tx.shared::cta.b64 _, [%0], %1;" ::"r"(a), "r"(b) : "memory"); }
__device__ __forceinline__ void mbar_arrive(uint32_t a) { asm volatile("mbarrier.arrive.shared::cta.b64 _, [%0];" ::"r"(a) : "memory"); }
__device__ __forceinline__ void mbar_arrive_cluster(uint32_t a, uint32_t cta, uint32_t cnt) {
  asm volatile("{\n.reg .b32 r;\nmapa.shared::cluster.u32 r, %0, %1;\nmbarrier.arrive.shared::cluster.b64 _, [r], %2;\n}" ::"r"(a), "r"(cta), "r"(cnt) : "memory");
}
__device__ __forceinline__ void mbar_wait(uint32_t a, int ph) {
  asm volatile("{\n.reg .pred p;\n.reg .u32 c;\nmov.u32 c, 0;\nWAIT:\n"
               "mbarrier.try_wait.parity.shared::cta.b64 p, [%0], %1;\n@p bra DONE;\n"
               "add.u32 c, c, 1;\nsetp.lt.u32 p, c, 0x400000;\n@p bra WAIT;\ntrap;\nDONE:\n}" ::"r"(a), "r"(ph) : "memory");
}
__device__ __forceinline__ bool elect_one() {
  uint32_t p;
  asm volatile("{\n.reg .pred P;\nelect.sync _|P, 0xffffffff;\nselp.u32 %0, 1, 0, P;\n}" : "=r"(p));
  return p != 0;
}
__device__ __forceinline__ void bulk_ld(uint32_t dst, const void* src, int bytes, uint32_t bar) {
  asm volatile("cp.async.bulk.shared::cluster.global.mbarrier::complete_tx::bytes [%0], [%1], %2, [%3];" ::"r"(dst), "l"(src), "r"(bytes), "r"(bar) : "memory");
}
__device__ __forceinline__ void bulk_ld_mc(uint32_t dst, const void* src, int bytes, uint32_t bar, uint16_t mask) {
  asm volatile("cp.async.bulk.shared::cluster.global.mbarrier::complete_tx::bytes.multicast::cluster [%0], [%1], %2, [%3], %4;" ::"r"(dst), "l"(src), "r"(bytes), "r"(bar), "h"(mask) : "memory");
}
__device__ __forceinline__ void tma_ld2(uint32_t dst, const CUtensorMap* tm, int c0, int c1, uint32_t bar) {
  asm volatile("cp.async.bulk.tensor.2d.shared::cluster.global.mbarrier::complete_tx::bytes [%0], [%1, {%3,%4}], [%2];" ::"r"(dst), "l"(tm), "r"(bar), "r"(c0), "r"(c1) : "memory");
}
__device__ __forceinline__ void tma_ld3(uint32_t dst, const CUtensorMap* tm, int c0, int c1, int c2, uint32_t bar) {
  asm volatile("cp.async.bulk.tensor.3d.shared::cluster.global.mbarrier::complete_tx::bytes [%0], [%1, {%3,%4,%5}], [%2];" ::"r"(dst), "l"(tm), "r"(bar), "r"(c0), "r"(c1), "r"(c2) : "memory");
}
__device__ __forceinline__ void tma_st4(const CUtensorMap* tm, uint32_t src, int c0, int c1, int c2, int c3) {
  asm volatile("cp.async.bulk.tensor.4d.global.shared::cta.bulk_group [%0, {%2,%3,%4,%5}], [%1];" ::"l"(tm), "r"(src), "r"(c0), "r"(c1), "r"(c2), "r"(c3) : "memory");
}
__device__ __forceinline__ void wg_fence() { asm volatile("wgmma.fence.sync.aligned;" ::: "memory"); }
__device__ __forceinline__ void wg_commit() { asm volatile("wgmma.commit_group.sync.aligned;" ::: "memory"); }
template <int N> __device__ __forceinline__ void wg_wait() { asm volatile("wgmma.wait_group.sync.aligned %0;" ::"n"(N) : "memory"); }
template <int R> __device__ __forceinline__ void fence_regs(float (&d)[R]) {
#pragma unroll
  for (int i = 0; i < R; i++) asm volatile("" : "+f"(d[i])::"memory");
}
__device__ __forceinline__ uint64_t mk_desc(uint32_t addr, uint32_t lbo, uint32_t sbo) {
  return (uint64_t)((addr & 0x3FFFF) >> 4) | ((uint64_t)(lbo >> 4) << 16) | ((uint64_t)(sbo >> 4) << 32) | (1ull << 62);
}
__device__ __forceinline__ uint32_t pack2(float lo, float hi) {
  uint32_t r;
  asm("cvt.rn.bf16x2.f32 %0, %1, %2;" : "=r"(r) : "f"(hi), "f"(lo));
  return r;
}
__device__ __forceinline__ void stg128(void* p, uint32_t a, uint32_t b, uint32_t c, uint32_t d) {
  asm volatile("st.global.v4.b32 [%0], {%1,%2,%3,%4};" ::"l"(p), "r"(a), "r"(b), "r"(c), "r"(d) : "memory");
}
__device__ __forceinline__ uint32_t tw2(int m0, int m1) {
  return (uint32_t)g_cos_tab[m0 & 127] | ((uint32_t)g_cos_tab[m1 & 127] << 16);
}

constexpr int K1_BOX = 208 * 128;
constexpr int K1_STAGE = 2 * K1_BOX;
constexpr int K1_NST = 4;
constexpr int K1_ITEMS = 8 * 212;
constexpr int K1_SMEM = K1_NST * K1_STAGE + 1024;

__device__ __forceinline__ void k1_decode(int item, bool& isx, int& cg, int& idx) {
  cg = item / 212;
  int r = item - cg * 212;
  int nx = (r * 84) / 212;
  isx = ((r + 1) * 84) / 212 > nx;
  idx = isx ? nx : r - nx;
}

__global__ void __launch_bounds__(288, 1)
k1_transform(const __grid_constant__ CUtensorMap tmX, const __grid_constant__ CUtensorMap tmWe, const __grid_constant__ CUtensorMap tmWo) {
  extern __shared__ uint8_t smem_raw[];
  __shared__ uint64_t bars[2 * K1_NST];
  const uint32_t sbase = (s2u(smem_raw) + 1023) & ~1023u;
  const uint32_t full = s2u(bars), empty = full + 8 * K1_NST;
  const int warp = __shfl_sync(0xffffffffu, threadIdx.x >> 5, 0), lane = threadIdx.x & 31;
  if (threadIdx.x == 0) {
    for (int i = 0; i < K1_NST; i++) { mbar_init(full + 8 * i, 1); mbar_init(empty + 8 * i, 1); }
    asm volatile("fence.mbarrier_init.release.cluster;" ::: "memory");
  }
  if (blockIdx.x == 0 && threadIdx.x < 16) g_cnt[threadIdx.x] = 0;
  __syncthreads();
  if (warp == 8) {
    if (elect_one()) {
      int k = 0;
      for (int item = blockIdx.x; item < K1_ITEMS; item += gridDim.x, k++) {
        const int s = k % K1_NST;
        bool isx; int cg, idx;
        k1_decode(item, isx, cg, idx);
        mbar_wait(empty + 8 * s, ((k / K1_NST) & 1) ^ 1);
        const uint32_t dst = sbase + s * K1_STAGE;
        if (isx) {
          const int b = idx / 42, tg = idx - b * 42;
          mbar_expect(full + 8 * s, K1_STAGE);
          tma_ld3(dst, &tmX, cg * 128, tg * 192, b, full + 8 * s);
          tma_ld3(dst + K1_BOX, &tmX, cg * 128 + 64, tg * 192, b, full + 8 * s);
        } else {
          const int cp = cg * 128 + idx;
          mbar_expect(full + 8 * s, 16384);
          tma_ld3(dst, cp < 512 ? &tmWe : &tmWo, 0, 0, (cp & 511) * 8, full + 8 * s);
        }
      }
    }
  } else {
    const int wg = warp >> 2, w = warp & 3, a = lane & 3;
    const int u = 8 * w + (lane >> 2);
    uint32_t fa[4][4];
#pragma unroll
    for (int kk = 0; kk < 4; kk++) {
      const int n0 = 16 * kk + 2 * a, f = 2 * u + 1;
      fa[kk][0] = tw2(f * n0, f * (n0 + 1));
      fa[kk][1] = tw2(f * n0 + 32, f * (n0 + 1) + 32);
      fa[kk][2] = tw2(f * (n0 + 8), f * (n0 + 9));
      fa[kk][3] = tw2(f * (n0 + 8) + 32, f * (n0 + 9) + 32);
    }
    float acc[64];
    int k = wg;
    for (int item = blockIdx.x + wg * gridDim.x; item < K1_ITEMS; item += 2 * gridDim.x, k += 2) {
      const int s = k % K1_NST;
      bool isx; int cg, idx;
      k1_decode(item, isx, cg, idx);
      mbar_wait(full + 8 * s, (k / K1_NST) & 1);
      const uint32_t src = sbase + s * K1_STAGE;
      if (isx) {
        const int b = idx / 42, tg = idx - b * 42;
        uint8_t* base = g_X + (size_t)((u * 2 + b) * 32 + cg * 4) * XBLK;
#pragma unroll 1
        for (int tt = 0; tt < 4; tt++) {
          wg_fence();
#pragma unroll
          for (int kk = 0; kk < 4; kk++) wgmma_rs_n128(acc, fa[kk], mk_desc(src + (48 * tt + 16 * kk) * 128, K1_BOX, 1024), kk);
          wg_commit();
          wg_wait<0>();
          fence_regs(acc);
          if (tt == 3 && (threadIdx.x & 127) == 0) mbar_arrive(empty + 8 * s);
          const int t = tg * 4 + tt;
          uint8_t* p = base + t * 128;
          const int o0 = (a ^ (t & 7)) << 4, o1 = o0 ^ 64;
#pragma unroll
          for (int g = 0; g < 4; g++) {
            const float* c = acc + 16 * g;
            stg128(p + g * XBLK + o0, pack2(c[0], c[1]), pack2(c[4], c[5]), pack2(c[8], c[9]), pack2(c[12], c[13]));
            stg128(p + g * XBLK + o1, pack2(c[2], c[3]), pack2(c[6], c[7]), pack2(c[10], c[11]), pack2(c[14], c[15]));
          }
        }
      } else {
        const int cp = cg * 128 + idx;
        const int ks = cp >> 5, cl = cp & 31;
        const int kap = 8 * ((cl >> 1) & 3) + 2 * (cl >> 3) + (cl & 1);
        uint8_t* base = g_W + (size_t)(u * 4 * 32 + ks) * WBLK + kap * 128;
        const int o0 = (a ^ (kap & 7)) << 4;
#pragma unroll 1
        for (int dt = 0; dt < 4; dt++) {
          wg_fence();
          wgmma_rs_n128(acc, fa[0], mk_desc(src + dt * 4096, 2048, 1024), 0);
          wg_commit();
          wg_wait<0>();
          fence_regs(acc);
          if (dt == 3 && (threadIdx.x & 127) == 0) mbar_arrive(empty + 8 * s);
          uint8_t* p = base + (size_t)dt * 32 * WBLK;
#pragma unroll
          for (int g = 0; g < 4; g++) {
            const float* c = acc + 16 * g;
            uint8_t* q = p + (g >> 1) * 8192 + (o0 ^ ((g & 1) * 64));
            stg128(q, pack2(c[0], c[1]), pack2(c[4], c[5]), pack2(c[8], c[9]), pack2(c[12], c[13]));
            stg128(q + 4096, pack2(c[2], c[3]), pack2(c[6], c[7]), pack2(c[10], c[11]), pack2(c[14], c[15]));
          }
        }
      }
    }
  }
}

constexpr int K2_STAGE = WBLK + XBLK;
constexpr int K2_NST = 6;
constexpr int K2_SMEM = K2_NST * K2_STAGE + 1024;
constexpr int K2_USES = 35;

__global__ void __cluster_dims__(2, 1, 1) __launch_bounds__(384, 1)
k2_gemm(const __grid_constant__ CUtensorMap tmYst) {
  extern __shared__ uint8_t smem_raw[];
  __shared__ uint64_t bars[2 * K2_NST + 1];
  const uint32_t sbase = (s2u(smem_raw) + 1023) & ~1023u;
  const uint32_t full = s2u(bars), empty = full + 8 * K2_NST, stg_ready = empty + 8 * K2_NST;
  const int warp = __shfl_sync(0xffffffffu, threadIdx.x >> 5, 0), lane = threadIdx.x & 31;
  const uint32_t rank = blockIdx.x & 1;
  const int pr = blockIdx.x >> 1;
  const int dt = (pr & 1) * 2 + rank, b = (pr >> 1) & 1, ul = pr >> 2;
  if (threadIdx.x == 0) {
    for (int i = 0; i < K2_NST; i++) { mbar_init(full + 8 * i, 1); mbar_init(empty + 8 * i, 4); }
    mbar_init(stg_ready, 256);
    asm volatile("fence.mbarrier_init.release.cluster;" ::: "memory");
  }
  __syncthreads();
  asm volatile("barrier.cluster.arrive.aligned;\nbarrier.cluster.wait.aligned;" ::: "memory");
  if (warp >= 8) {
    asm volatile("setmaxnreg.dec.sync.aligned.u32 40;");
    if (warp == 8) { if (elect_one()) {
      int s = 0, ph = 1;
      for (int pass = 0; pass < 2; pass++) {
        const int u = pass * 16 + ul;
        const uint8_t* xs = g_X + (size_t)((u * 2 + b) * 32) * XBLK + rank * (XBLK / 2);
        const uint8_t* ws = g_W + (size_t)((u * 4 + dt) * 32) * WBLK;
        for (int i = 0; i < K2_USES; i++) {
          mbar_wait(empty + 8 * s, ph);
          if (i < 32) {
            const int ks = 31 - i;
            const uint32_t dst = sbase + s * K2_STAGE;
            mbar_expect(full + 8 * s, K2_STAGE);
            bulk_ld(dst, ws + (size_t)ks * WBLK, WBLK, full + 8 * s);
            bulk_ld_mc(dst + WBLK + rank * (XBLK / 2), xs + (size_t)ks * XBLK, XBLK / 2, full + 8 * s, 3);
          } else {
            mbar_arrive(full + 8 * s);
          }
          if (++s == K2_NST) { s = 0; ph ^= 1; }
        }
      } }
    } else if (warp == 9 && elect_one()) {
      for (int pass = 0; pass < 2; pass++) {
        const int u = pass * 16 + ul;
        const int s0 = (pass * K2_USES + 32) % K2_NST;
        mbar_wait(stg_ready, pass);
        const uint32_t src = sbase + s0 * K2_STAGE;
        tma_st4(&tmYst, src, 0, 0, 2 * u, b * 8 + dt * 2);
        tma_st4(&tmYst, src + 2 * XBLK, 0, 0, 2 * u, b * 8 + dt * 2 + 1);
        asm volatile("cp.async.bulk.commit_group;" ::: "memory");
        if (pass == 0) {
          asm volatile("cp.async.bulk.wait_group.read 0;" ::: "memory");
          for (int i = 0; i < 3; i++) {
            mbar_arrive_cluster(empty + 8 * (s0 + i), 0, 2);
            mbar_arrive_cluster(empty + 8 * (s0 + i), 1, 2);
          }
        } else {
          asm volatile("cp.async.bulk.wait_group 0;" ::: "memory");
        }
      }
    }
    asm volatile("barrier.cluster.arrive;\nbarrier.cluster.wait;" ::: "memory");
  } else {
    asm volatile("setmaxnreg.inc.sync.aligned.u32 232;");
    const int wg = warp >> 2, w = warp & 3;
    float yr[84], yi[84];
    int s = 0, ph = 0;
    for (int pass = 0; pass < 2; pass++) {
      int sprev = 0;
#pragma unroll 1
      for (int i = 0; i < 32; i++) {
        mbar_wait(full + 8 * s, ph);
        const uint32_t st = sbase + s * K2_STAGE;
        const uint64_t dwr = mk_desc(st + wg * 8192, 1024, 1024), dx = mk_desc(st + WBLK, 16, 1024);
        wg_fence();
#pragma unroll
        for (int kk = 0; kk < 2; kk++) {
          const uint64_t wr = dwr + kk * (2048 >> 4), wi = wr + (4096 >> 4);
          const uint64_t xr = dx + kk * 2, xi = xr + 4;
          const int sd = (i | kk) != 0;
          wgmma_ss_n168<1>(yr, wr, xr, sd);
          wgmma_ss_n168<1>(yi, wr, xi, sd);
          wgmma_ss_n168<1>(yr, wi, xi, 1);
          wgmma_ss_n168<-1>(yi, wi, xr, 1);
        }
        wg_commit();
        if (i > 0) {
          wg_wait<1>();
          if (w == 0 && lane < 2) mbar_arrive_cluster(empty + 8 * sprev, lane, 1);
        }
        sprev = s;
        if (++s == K2_NST) { s = 0; ph ^= 1; }
      }
      wg_wait<0>();
      fence_regs(yr);
      fence_regs(yi);
      if (w == 0 && lane < 2) mbar_arrive_cluster(empty + 8 * sprev, lane, 1);
      const uint32_t stg = sbase + s * K2_STAGE + wg * 2 * XBLK;
#pragma unroll 1
      for (int i = 0; i < 3; i++) {
        mbar_wait(full + 8 * s, ph);
        if (++s == K2_NST) { s = 0; ph ^= 1; }
      }
      const int m = lane >> 3, r = lane & 7;
      const uint32_t ad = stg + (m >> 1) * XBLK + r * 128 + (((2 * w + (m & 1)) ^ r) << 4);
#pragma unroll
      for (int j = 0; j < 21; j++) {
        asm volatile("stmatrix.sync.aligned.m8n8.x4.trans.shared.b16 [%0], {%1,%2,%3,%4};" ::"r"(ad + j * 1024),
                     "r"(pack2(yr[4 * j], yr[4 * j + 1])), "r"(pack2(yr[4 * j + 2], yr[4 * j + 3])),
                     "r"(pack2(yi[4 * j], yi[4 * j + 1])), "r"(pack2(yi[4 * j + 2], yi[4 * j + 3]))
                     : "memory");
      }
      asm volatile("fence.proxy.async.shared::cta;" ::: "memory");
      mbar_arrive(stg_ready);
    }
    asm volatile("barrier.cluster.arrive.aligned;\nbarrier.cluster.wait.aligned;" ::: "memory");
  }
}

constexpr int K3_TILES = 21;
constexpr int K3_SMEM = K3_TILES * 8192 + 1024;

__global__ void __launch_bounds__(512, 1)
k3_inverse(const __grid_constant__ CUtensorMap tmYld, const __nv_bfloat16* __restrict__ gamma, const __nv_bfloat16* __restrict__ beta,
           __nv_bfloat16* __restrict__ out) {
  extern __shared__ uint8_t smem_raw[];
  __shared__ uint64_t bars[7];
  __shared__ float s_red[16][128];
  __shared__ float s_par[128];
  const uint32_t sbase = (s2u(smem_raw) + 1023) & ~1023u;
  const uint32_t full = s2u(bars);
  const int warp = __shfl_sync(0xffffffffu, threadIdx.x >> 5, 0), lane = threadIdx.x & 31;
  const int grp = blockIdx.x >> 3, tr = blockIdx.x & 7;
  const int b = grp >> 3, d64 = grp & 7;
  const int t0 = tr * K3_TILES;
  if (threadIdx.x == 0) {
    for (int i = 0; i < 7; i++) mbar_init(full + 8 * i, 1);
    asm volatile("fence.mbarrier_init.release.cluster;" ::: "memory");
  }
  __syncthreads();
  if (warp < 7 && elect_one()) {
    mbar_expect(full + 8 * warp, 3 * 8192);
    tma_ld2(sbase + warp * 3 * 8192, &tmYld, 0, (grp * NT + t0 + warp * 3) * 64, full + 8 * warp);
  }
  const int wg = warp >> 2, w = warp & 3, a = lane & 3;
  const bool active = (w != wg);
  const int mb = w < wg ? w : w - 1;
  const int p0 = 16 * mb + (lane >> 2);
  uint32_t ga[4][4];
#pragma unroll
  for (int kk = 0; kk < 4; kk++) {
    const int f0 = 2 * (8 * kk + a) + 1, f1 = f0 + 8;
    ga[kk][0] = active ? tw2(f0 * p0, f0 * p0 + 32) : 0u;
    ga[kk][1] = active ? tw2(f0 * (p0 + 8), f0 * (p0 + 8) + 32) : 0u;
    ga[kk][2] = active ? tw2(f1 * p0, f1 * p0 + 32) : 0u;
    ga[kk][3] = active ? tw2(f1 * (p0 + 8), f1 * (p0 + 8) + 32) : 0u;
  }
  float acc[32];
  float s1[16], s2[16];
#pragma unroll
  for (int i = 0; i < 16; i++) { s1[i] = 0.f; s2[i] = 0.f; }
#pragma unroll 1
  for (int tl = wg; tl < K3_TILES; tl += 4) {
    mbar_wait(full + 8 * (tl / 3), 0);
    wg_fence();
#pragma unroll
    for (int kk = 0; kk < 4; kk++) wgmma_rs_n64(acc, ga[kk], mk_desc(sbase + tl * 8192 + kk * 2048, 1024, 1024), kk);
    wg_commit();
    wg_wait<0>();
    fence_regs(acc);
    if (active) {
      const int l0 = (t0 + tl) * MT + p0;
      const bool v0 = l0 < LOUT, v1 = l0 + 8 < LOUT;
#pragma unroll
      for (int j = 0; j < 8; j++) {
#pragma unroll
        for (int e = 0; e < 2; e++) {
          const float x0 = v0 ? acc[4 * j + e] : 0.f, x1 = v1 ? acc[4 * j + 2 + e] : 0.f;
          s1[2 * j + e] += x0 + x1;
          s2[2 * j + e] = fmaf(x0, x0, fmaf(x1, x1, s2[2 * j + e]));
        }
      }
    }
  }
#pragma unroll
  for (int i = 0; i < 16; i++) {
#pragma unroll
    for (int o = 4; o < 32; o <<= 1) {
      s1[i] += __shfl_xor_sync(0xffffffffu, s1[i], o);
      s2[i] += __shfl_xor_sync(0xffffffffu, s2[i], o);
    }
  }
  if (lane < 4) {
#pragma unroll
    for (int i = 0; i < 16; i++) {
      const int d = 32 * (i >> 3) + 8 * a + (i & 7);
      s_red[warp][d] = s1[i];
      s_red[warp][64 + d] = s2[i];
    }
  }
  __syncthreads();
  if (threadIdx.x < 128) {
    float t = 0.f;
#pragma unroll
    for (int i = 0; i < 16; i++) t += s_red[i][threadIdx.x];
    g_part[(grp * 8 + tr) * 128 + threadIdx.x] = t;
    __threadfence();
    asm volatile("bar.sync 1, 128;" ::: "memory");
    if (threadIdx.x == 0) {
      asm volatile("red.release.gpu.global.add.u32 [%0], 1;" ::"l"(&g_cnt[grp]) : "memory");
      unsigned v;
      int it = 0;
      do {
        asm volatile("ld.acquire.gpu.global.u32 %0, [%1];" : "=r"(v) : "l"(&g_cnt[grp]) : "memory");
        if (++it > (1 << 22)) __trap();
      } while (v < 8);
    }
    asm volatile("bar.sync 1, 128;" ::: "memory");
    if (threadIdx.x < 64) {
      float a1 = 0.f, a2 = 0.f;
#pragma unroll
      for (int i = 0; i < 8; i++) {
        a1 += __ldcg(&g_part[(grp * 8 + i) * 128 + threadIdx.x]);
        a2 += __ldcg(&g_part[(grp * 8 + i) * 128 + 64 + threadIdx.x]);
      }
      const float sc = 1.f / 32.f;
      const float mu = a1 * (sc / LOUT);
      const float var = fmaxf(a2 * (sc * sc / LOUT) - mu * mu, 0.f);
      const float g = __bfloat162float(gamma[d64 * 64 + threadIdx.x]) / sqrtf(var + 1e-5f);
      s_par[threadIdx.x] = g * sc;
      s_par[64 + threadIdx.x] = __bfloat162float(beta[d64 * 64 + threadIdx.x]) - mu * g;
    }
  }
  __syncthreads();
#pragma unroll
  for (int i = 0; i < 16; i++) {
    const int d = 32 * (i >> 3) + 8 * a + (i & 7);
    s1[i] = s_par[d];
    s2[i] = s_par[64 + d];
  }
#pragma unroll 1
  for (int tl = wg; tl < K3_TILES; tl += 4) {
    wg_fence();
#pragma unroll
    for (int kk = 0; kk < 4; kk++) wgmma_rs_n64(acc, ga[kk], mk_desc(sbase + tl * 8192 + kk * 2048, 1024, 1024), kk);
    wg_commit();
    wg_wait<0>();
    fence_regs(acc);
    if (active) {
      const int l0 = (t0 + tl) * MT + p0;
#pragma unroll
      for (int i = 0; i < 32; i++) {
        const int c = 2 * (i >> 2) + (i & 1);
        const float z = fmaf(acc[i], s1[c], s2[c]);
        const float in = z * fmaf(z * z, 0.044715f * 0.7978845608028654f, 0.7978845608028654f);
        float th;
        asm("tanh.approx.f32 %0, %1;" : "=f"(th) : "f"(in));
        const float hz = 0.5f * z;
        acc[i] = fmaf(hz, th, hz);
      }
      uint8_t* p = (uint8_t*)out + ((size_t)b * LOUT + l0) * 1024 + d64 * 128 + a * 16;
#pragma unroll
      for (int h = 0; h < 2; h++) {
        const float* c = acc + 16 * h;
        if (l0 < LOUT) stg128(p + h * 64, pack2(c[0], c[1]), pack2(c[4], c[5]), pack2(c[8], c[9]), pack2(c[12], c[13]));
        if (l0 + 8 < LOUT) stg128(p + 8 * 1024 + h * 64, pack2(c[2], c[3]), pack2(c[6], c[7]), pack2(c[10], c[11]), pack2(c[14], c[15]));
      }
    }
  }
}

typedef CUresult (*EncFn)(CUtensorMap*, CUtensorMapDataType, cuuint32_t, void*, const cuuint64_t*, const cuuint64_t*, const cuuint32_t*,
                          const cuuint32_t*, CUtensorMapInterleave, CUtensorMapSwizzle, CUtensorMapL2promotion, CUtensorMapFloatOOBfill);

struct Maps { CUtensorMap x, we, wo, yst, yld; };

void encode(EncFn fn, CUtensorMap* m, int rank, void* base, const cuuint64_t* dims, const cuuint64_t* strides, const cuuint32_t* box,
            CUtensorMapL2promotion promo) {
  cuuint32_t es[5] = {1, 1, 1, 1, 1};
  fn(m, CU_TENSOR_MAP_DATA_TYPE_BFLOAT16, rank, base, dims, strides, box, es, CU_TENSOR_MAP_INTERLEAVE_NONE, CU_TENSOR_MAP_SWIZZLE_128B, promo,
     CU_TENSOR_MAP_FLOAT_OOB_FILL_NONE);
}

}

extern "C" void kernel_launch(void* const* d_in, const int* in_sizes, int n_in, void* d_out, int out_size) {
  (void)in_sizes; (void)n_in; (void)out_size;
  const __nv_bfloat16* x = (const __nv_bfloat16*)d_in[0];
  const __nv_bfloat16* w = (const __nv_bfloat16*)d_in[1];
  const __nv_bfloat16* gamma = (const __nv_bfloat16*)d_in[2];
  const __nv_bfloat16* beta = (const __nv_bfloat16*)d_in[3];
  void* fnp = nullptr;
  cudaDriverEntryPointQueryResult qr;
  cudaGetDriverEntryPoint("cuTensorMapEncodeTiled", &fnp, cudaEnableDefault, &qr);
  EncFn fn = (EncFn)fnp;
  void* yptr = nullptr;
  cudaGetSymbolAddress(&yptr, g_Y);
  Maps m;
  {
    cuuint64_t d[3] = {1024, 8000, 2}, s[2] = {2048, 8000ull * 2048};
    cuuint32_t bx[3] = {64, 208, 1};
    encode(fn, &m.x, 3, (void*)x, d, s, bx, CU_TENSOR_MAP_L2_PROMOTION_L2_256B);
  }
  for (int ph = 0; ph < 2; ph++) {
    cuuint64_t d[3] = {64, (cuuint64_t)(16 - ph), 4096}, s[2] = {2ull * 262144 * 2, 128};
    cuuint32_t bx[3] = {64, 16, 8};
    encode(fn, ph ? &m.wo : &m.we, 3, (void*)(w + (size_t)ph * 262144), d, s, bx, CU_TENSOR_MAP_L2_PROMOTION_L2_256B);
  }
  {
    cuuint64_t d[4] = {64, NT, 64, 16}, s[3] = {8192, 128, (cuuint64_t)NT * 8192};
    cuuint32_t bx[4] = {64, NT, 2, 1};
    encode(fn, &m.yst, 4, yptr, d, s, bx, CU_TENSOR_MAP_L2_PROMOTION_NONE);
  }
  {
    cuuint64_t d[2] = {64, 16ull * NT * 64}, s[1] = {128};
    cuuint32_t bx[2] = {64, 192};
    encode(fn, &m.yld, 2, yptr, d, s, bx, CU_TENSOR_MAP_L2_PROMOTION_L2_256B);
  }
  cudaFuncSetAttribute(k1_transform, cudaFuncAttributeMaxDynamicSharedMemorySize, K1_SMEM);
  cudaFuncSetAttribute(k2_gemm, cudaFuncAttributeMaxDynamicSharedMemorySize, K2_SMEM);
  cudaFuncSetAttribute(k3_inverse, cudaFuncAttributeMaxDynamicSharedMemorySize, K3_SMEM);
  k1_transform<<<132, 288, K1_SMEM>>>(m.x, m.we, m.wo);
  k2_gemm<<<128, 384, K2_SMEM>>>(m.yst);
  k3_inverse<<<128, 512, K3_SMEM>>>(m.yld, gamma, beta, (__nv_bfloat16*)d_out);
}
```

```cpp
#include <cuda_runtime.h>
#include <cuda_bf16.h>
#include <cuda.h>
#include <stdint.h>

namespace {

constexpr int LOUT = 7985;
constexpr int MT = 48;
constexpr int NT = 168;
constexpr int XBLK = NT * 128;
constexpr int WBLK = 16384;
constexpr int LEAD = 3;
constexpr int WR = 8;
constexpr int WCHUNK = 32 * 4 * WBLK;

__device__ __align__(1024) uint8_t g_X[32ull * 2 * 32 * XBLK];
__device__ __align__(1024) uint8_t g_W[(size_t)WR * WCHUNK];
__device__ __align__(1024) uint8_t g_Y[16ull * NT * 8192];
__device__ float g_part[16 * 8 * 128];
__device__ unsigned g_cnt[16 * 32];
__device__ unsigned g_flag[32 * 32];
#define PROF_T(i)

__device__ __align__(128) const uint32_t g_Fimg[2048] = {
 0x3f803f80,0x3f7d3f7f,0x3f783f7b,0x3f713f75,0x3f673f6d,0x3f5c3f62,0x3f4e3f55,0x3f3e3f46,0x3f2c3f35,0x3f183f22,0x3f043f0e,0x3edb3ef1,0x3eac3ec4,0x3e793e95,0x3e163e48,0x3d493dc9,
 0xbd490000,0xbe16bdc9,0xbe79be48,0xbeacbe95,0xbedbbec4,0xbf04bef1,0xbf18bf0e,0xbf2cbf22,0xbf3ebf35,0xbf4ebf46,0xbf5cbf55,0xbf67bf62,0xbf71bf6d,0xbf78bf75,0xbf7dbf7b,0xbf80bf7f,
 0x3e793ec4,0xbd493dc9,0xbeacbe48,0xbf18bef1,0x3f7d3f80,0x3f673f75,0x3f3e3f55,0x3f043f22,0xbf5cbf6d,0xbf2cbf46,0xbedbbf0e,0xbe16be95,0xbf4ebf35,0xbf71bf62,0xbf80bf7b,0xbf78bf7f,
 0x3f783f6d,0x3f803f7f,0x3f713f7b,0x3f4e3f62,0x3e160000,0x3edb3e95,0x3f2c3f0e,0x3f5c3f46,0xbf04bec4,0xbf3ebf22,0xbf67bf55,0xbf7dbf75,0x3f183f35,0x3eac3ef1,0x3d493e48,0xbe79bdc9,
 0xbf04bf35,0xbd49be95,0x3edb3e48,0x3f4e3f22,0x3f7d3f6d,0x3f713f7f,0x3f2c3f55,0x3e793ef1,0x3f783f80,0x3f3e3f62,0x3eac3f0e,0xbe163dc9,0xbf18bec4,0xbf67bf46,0xbf80bf7b,0xbf5cbf75,
 0x3f5c3f35,0x3f803f75,0x3f673f7b,0x3f183f46,0x3e163ec4,0xbeacbdc9,0xbf3ebf0e,0xbf78bf62,0xbe790000,0xbf2cbef1,0xbf71bf55,0xbf7dbf7f,0xbf4ebf6d,0xbedbbf22,0x3d49be48,0x3f043e95,
 0xbf2cbec4,0xbf7dbf62,0xbf5cbf7b,0xbeacbf22,0x3f673f35,0x3f783f7f,0x3f183f55,0xbd493e95,0xbf80bf6d,0xbf4ebf75,0xbe79bf0e,0x3edb3dc9,0x3f713f80,0x3f043f46,0xbe163e48,0xbf3ebef1,
 0x3f3e3f6d,0x3e163ef1,0xbf04be48,0xbf71bf46,0xbedbbf35,0x3e79bdc9,0x3f4e3f0e,0x3f803f75,0x3d493ec4,0xbf18be95,0xbf78bf55,0xbf67bf7f,0x3eac0000,0x3f5c3f22,0x3f7d3f7b,0x3f2c3f62,
 0xbedb0000,0xbf78bf46,0xbf4ebf7b,0xbd49bef1,0x3f3e3ec4,0x3f7d3f75,0x3f043f55,0xbeac3dc9,0xbf71bf35,0xbf5cbf7f,0xbe16bf0e,0x3f2c3e95,0x3f803f6d,0x3f183f62,0xbe793e48,0xbf67bf22,
 0x3f673f80,0x3e793f22,0xbf18be48,0xbf80bf62,0xbf2cbf6d,0x3e16be95,0x3f5c3f0e,0x3f713f7f,0x3eac3f35,0xbf04bdc9,0xbf7dbf55,0xbf3ebf75,0x3d49bec4,0x3f4e3ef1,0x3f783f7b,0x3edb3f46,
 0xbf7dbf6d,0xbeacbf46,0x3f2c3e48,0x3f783f75,0x3f040000,0x3f803f62,0x3edb3f55,0xbf18bdc9,0x3f4e3ec4,0x3f673f7f,0x3d493f0e,0xbf5cbef1,0x3e793f35,0xbf3ebe95,0xbf71bf7b,0xbe16bf22,
 0x3e16bec4,0x3f713f22,0x3f3e3f7b,0xbe793e95,0x3f5c3f80,0xbd493ef1,0xbf67bf0e,0xbf4ebf7f,0x3f183f6d,0xbedb3dc9,0xbf80bf55,0xbf04bf62,0xbf78bf35,0xbf2cbf75,0x3eacbe48,0x3f7d3f46,
 0x3f7d3f35,0x3edb3f62,0xbf3ebe48,0xbf5cbf7f,0x3e79bec4,0x3f803f46,0x3eac3f55,0xbf4ebe95,0xbf180000,0xbf71bf75,0x3d49bf0e,0x3f783f22,0x3f043f6d,0xbf2cbdc9,0xbf67bf7b,0x3e16bef1,
 0xbe16bf35,0x3f673ef1,0x3f2c3f7b,0xbf043dc9,0xbf78bf6d,0xbd49bf22,0x3f713f0e,0x3f183f75,0x3f4e3f80,0xbeac3e95,0xbf80bf55,0xbe79bf46,0x3f5c3ec4,0x3f3e3f7f,0xbedb3e48,0xbf7dbf62,
 0xbedbbf6d,0x3f5c3e95,0x3f183f7b,0xbf3ebdc9,0xbd49bf35,0x3f7d3f22,0x3e793f55,0xbf71bef1,0x3eacbec4,0x3f783f62,0xbe163f0e,0xbf80bf46,0x3f2c0000,0x3f4e3f7f,0xbf043e48,0xbf67bf75,
 0x3f673ec4,0x3f043f75,0xbf4ebe48,0xbf2cbf7f,0x3f803f35,0x3e163f46,0xbf78bf0e,0xbeacbf62,0x3f713f6d,0xbe793ef1,0xbf7dbf55,0x3d49bf22,0x3f3e3f80,0xbf183dc9,0xbf5cbf7b,0x3edbbe95,
 0xbd490000,0xbe16bdc9,0xbe79be48,0xbeacbe95,0xbedbbec4,0xbf04bef1,0xbf18bf0e,0xbf2cbf22,0xbf3ebf35,0xbf4ebf46,0xbf5cbf55,0xbf67bf62,0xbf71bf6d,0xbf78bf75,0xbf7dbf7b,0xbf80bf7f,
 0xbf80bf80,0xbf7dbf7f,0xbf78bf7b,0xbf71bf75,0xbf67bf6d,0xbf5cbf62,0xbf4ebf55,0xbf3ebf46,0xbf2cbf35,0xbf18bf22,0xbf04bf0e,0xbedbbef1,0xbeacbec4,0xbe79be95,0xbe16be48,0xbd49bdc9,
 0xbf78bf6d,0xbf80bf7f,0xbf71bf7b,0xbf4ebf62,0xbe160000,0xbedbbe95,0xbf2cbf0e,0xbf5cbf46,0x3f043ec4,0x3f3e3f22,0x3f673f55,0x3f7d3f75,0xbf18bf35,0xbeacbef1,0xbd49be48,0x3e793dc9,
 0x3e793ec4,0xbd493dc9,0xbeacbe48,0xbf18bef1,0x3f7d3f80,0x3f673f75,0x3f3e3f55,0x3f043f22,0xbf5cbf6d,0xbf2cbf46,0xbedbbf0e,0xbe16be95,0xbf4ebf35,0xbf71bf62,0xbf80bf7b,0xbf78bf7f,
 0x3f5c3f35,0x3f803f75,0x3f673f7b,0x3f183f46,0x3e163ec4,0xbeacbdc9,0xbf3ebf0e,0xbf78bf62,0xbe790000,0xbf2cbef1,0xbf71bf55,0xbf7dbf7f,0xbf4ebf6d,0xbedbbf22,0x3d49be48,0x3f043e95,
 0x3f043f35,0x3d493e95,0xbedbbe48,0xbf4ebf22,0xbf7dbf6d,0xbf71bf7f,0xbf2cbf55,0xbe79bef1,0xbf78bf80,0xbf3ebf62,0xbeacbf0e,0x3e16bdc9,0x3f183ec4,0x3f673f46,0x3f803f7b,0x3f5c3f75,
 0xbf3ebf6d,0xbe16bef1,0x3f043e48,0x3f713f46,0x3edb3f35,0xbe793dc9,0xbf4ebf0e,0xbf80bf75,0xbd49bec4,0x3f183e95,0x3f783f55,0x3f673f7f,0xbeac0000,0xbf5cbf22,0xbf7dbf7b,0xbf2cbf62,
 0xbf2cbec4,0xbf7dbf62,0xbf5cbf7b,0xbeacbf22,0x3f673f35,0x3f783f7f,0x3f183f55,0xbd493e95,0xbf80bf6d,0xbf4ebf75,0xbe79bf0e,0x3edb3dc9,0x3f713f80,0x3f043f46,0xbe163e48,0xbf3ebef1,
 0xbf67bf80,0xbe79bf22,0x3f183e48,0x3f803f62,0x3f2c3f6d,0xbe163e95,0xbf5cbf0e,0xbf71bf7f,0xbeacbf35,0x3f043dc9,0x3f7d3f55,0x3f3e3f75,0xbd493ec4,0xbf4ebef1,0xbf78bf7b,0xbedbbf46,
 0xbedb0000,0xbf78bf46,0xbf4ebf7b,0xbd49bef1,0x3f3e3ec4,0x3f7d3f75,0x3f043f55,0xbeac3dc9,0xbf71bf35,0xbf5cbf7f,0xbe16bf0e,0x3f2c3e95,0x3f803f6d,0x3f183f62,0xbe793e48,0xbf67bf22,
 0x3e16bec4,0x3f713f22,0x3f3e3f7b,0xbe793e95,0x3f5c3f80,0xbd493ef1,0xbf67bf0e,0xbf4ebf7f,0x3f183f6d,0xbedb3dc9,0xbf80bf55,0xbf04bf62,0xbf78bf35,0xbf2cbf75,0x3eacbe48,0x3f7d3f46,
 0x3f7d3f6d,0x3eac3f46,0xbf2cbe48,0xbf78bf75,0xbf040000,0xbf80bf62,0xbedbbf55,0x3f183dc9,0xbf4ebec4,0xbf67bf7f,0xbd49bf0e,0x3f5c3ef1,0xbe79bf35,0x3f3e3e95,0x3f713f7b,0x3e163f22,
 0x3e163f35,0xbf67bef1,0xbf2cbf7b,0x3f04bdc9,0x3f783f6d,0x3d493f22,0xbf71bf0e,0xbf18bf75,0xbf4ebf80,0x3eacbe95,0x3f803f55,0x3e793f46,0xbf5cbec4,0xbf3ebf7f,0x3edbbe48,0x3f7d3f62,
 0x3f7d3f35,0x3edb3f62,0xbf3ebe48,0xbf5cbf7f,0x3e79bec4,0x3f803f46,0x3eac3f55,0xbf4ebe95,0xbf180000,0xbf71bf75,0x3d49bf0e,0x3f783f22,0x3f043f6d,0xbf2cbdc9,0xbf67bf7b,0x3e16bef1,
 0x3f673ec4,0x3f043f75,0xbf4ebe48,0xbf2cbf7f,0x3f803f35,0x3e163f46,0xbf78bf0e,0xbeacbf62,0x3f713f6d,0xbe793ef1,0xbf7dbf55,0x3d49bf22,0x3f3e3f80,0xbf183dc9,0xbf5cbf7b,0x3edbbe95,
 0x3edb3f6d,0xbf5cbe95,0xbf18bf7b,0x3f3e3dc9,0x3d493f35,0xbf7dbf22,0xbe79bf55,0x3f713ef1,0xbeac3ec4,0xbf78bf62,0x3e16bf0e,0x3f803f46,0xbf2c0000,0xbf4ebf7f,0x3f04be48,0x3f673f75,
 0x3f2c3f80,0xbf4ebdc9,0xbf04bf7b,0x3f673e95,0x3eac3f6d,0xbf78bef1,0xbe16bf55,0x3f803f22,0xbd493f35,0xbf7dbf46,0x3e79bf0e,0x3f713f62,0xbedb3ec4,0xbf5cbf75,0x3f18be48,0x3f3e3f7f,
 0xbf3e0000,0xbf18bf7f,0x3f5c3e48,0x3edb3f75,0xbf71bec4,0xbe79bf62,0x3f7d3f0e,0x3d493f46,0xbf80bf35,0x3e16bf22,0x3f783f55,0xbeac3ef1,0xbf67bf6d,0x3f04be95,0x3f4e3f7b,0xbf2c3dc9,
 0xbf043ec4,0xbf2cbf7f,0x3f673e48,0x3e163f62,0x3f183f80,0xbf71be95,0xbd49bf55,0x3f783f46,0xbe79bf6d,0x3f803f22,0xbeac3f0e,0xbf4ebf75,0xbf7dbf35,0x3edbbef1,0x3f3e3f7b,0xbf5cbdc9,
 0x3f5c3f6d,0xbf3e3dc9,0xbedbbf7b,0x3f7d3ef1,0x3f4e0000,0x3eac3f75,0xbf80bf0e,0x3e79bf22,0xbf78bec4,0x3d49bf46,0x3f713f55,0xbf183e95,0xbe163f35,0xbf67bf62,0x3f2cbe48,0x3f043f7f,
 0x3e79bf35,0x3f3e3f75,0xbf71be48,0x3e16bf46,0x3f4e3f6d,0xbf67bdc9,0x3d49bf55,0x3f5c3f62,0x3f043f80,0xbf80bef1,0x3edbbf0e,0x3f183f7f,0xbf7dbec4,0x3eacbf22,0x3f2c3f7b,0xbf78be95,
 0x3f783f35,0xbf2c3e95,0xbeacbf7b,0x3f7d3f22,0xbf183ec4,0xbedbbf7f,0x3f803f0e,0xbf043ef1,0xbf5c0000,0xbd49bf62,0x3f673f55,0xbf4e3dc9,0xbe16bf6d,0x3f713f46,0xbf3e3e48,0xbe79bf75,
 0xbf80bec4,0x3f18bef1,0x3e793f7b,0xbf67bf46,0x3f713f35,0xbf5c3dc9,0x3e16bf55,0x3f2c3f75,0xbf3ebf6d,0x3f7d3e95,0xbf043f0e,0xbeacbf7f,0x3edb3f80,0xbf78bf22,0x3f4ebe48,0xbd493f62,
 0x3d493f6d,0xbf4ebf62,0x3f783e48,0xbedb3f22,0x3eacbf35,0x3f043f7f,0xbf7dbf0e,0x3f3ebe95,0xbf2c3ec4,0xbe16bf75,0x3f5c3f55,0xbf71bdc9,0x3f670000,0xbe793f46,0xbf18bf7b,0x3f803ef1,
 0xbf710000,0x3f04bf22,0x3e163f7b,0xbf3ebf62,0x3f803ec4,0xbf4e3e95,0x3e79bf55,0x3edb3f7f,0xbf67bf35,0x3f783dc9,0xbf183f0e,0xbd49bf75,0x3f2c3f6d,0xbf7dbef1,0x3f5cbe48,0xbeac3f46,
 0x3eac3f80,0xbf5cbf46,0x3f7d3e48,0xbf2c3ef1,0x3d49bf6d,0x3f183f75,0xbf78bf0e,0x3f67bdc9,0xbedb3f35,0xbe79bf7f,0x3f4e3f55,0xbf80be95,0x3f3ebec4,0xbe163f62,0xbf04bf7b,0x3f713f22,
 0xbf18bf6d,0x3f673f22,0xbf80be48,0x3f5cbe95,0x3f780000,0xbf3e3ef1,0x3eacbf55,0x3e163f7f,0x3f7d3ec4,0xbf713dc9,0x3f2cbf0e,0xbe793f62,0xbf043f35,0x3d49bf75,0x3edb3f7b,0xbf4ebf46,
 0x3f4ebec4,0xbedb3f46,0xbd49bf7b,0x3f043f75,0x3e793f80,0xbf2cbf62,0x3f713f0e,0xbf7dbdc9,0xbe163f6d,0xbeacbf7f,0x3f3e3f55,0xbf78bef1,0xbf5cbf35,0x3f803e95,0xbf673e48,0x3f18bf22,
 0x3f4e3f35,0xbf71bef1,0x3f803e48,0xbf783dc9,0x3f5cbec4,0xbf2c3f22,0x3edbbf55,0xbe163f75,0xbf7d0000,0x3f67be95,0xbf3e3f0e,0x3f04bf46,0xbe793f6d,0xbd49bf7f,0x3eac3f7b,0xbf18bf62,
 0x3f18bf35,0xbeac3f62,0x3d49bf7b,0x3e793f7f,0xbf04bf6d,0x3f3e3f46,0xbf67bf0e,0x3f7d3e95,0x3e163f80,0xbedbbf75,0x3f2c3f55,0xbf5cbf22,0x3f783ec4,0xbf80bdc9,0x3f71be48,0xbf4e3ef1,
 0x3eacbf6d,0xbe793f75,0x3e16bf7b,0xbd493f7f,0x3f2cbf35,0xbf183f46,0x3f04bf55,0xbedb3f62,0x3f67bec4,0xbf5c3ef1,0x3f4ebf0e,0xbf3e3f22,0x3f800000,0xbf7d3dc9,0x3f78be48,0xbf713e95,
 0x3f713ec4,0xbf78be95,0x3f7d3e48,0xbf80bdc9,0x3f3e3f35,0xbf4ebf22,0x3f5c3f0e,0xbf67bef1,0x3edb3f6d,0xbf04bf62,0x3f183f55,0xbf2cbf46,0x3d493f80,0xbe16bf7f,0x3e793f7b,0xbeacbf75,
 0xbf3e0000,0xbf18bf7f,0x3f5c3e48,0x3edb3f75,0xbf71bec4,0xbe79bf62,0x3f7d3f0e,0x3d493f46,0xbf80bf35,0x3e16bf22,0x3f783f55,0xbeac3ef1,0xbf67bf6d,0x3f04be95,0x3f4e3f7b,0xbf2c3dc9,
 0xbf2cbf80,0x3f4e3dc9,0x3f043f7b,0xbf67be95,0xbeacbf6d,0x3f783ef1,0x3e163f55,0xbf80bf22,0x3d49bf35,0x3f7d3f46,0xbe793f0e,0xbf71bf62,0x3edbbec4,0x3f5c3f75,0xbf183e48,0xbf3ebf7f,
 0xbf5cbf6d,0x3f3ebdc9,0x3edb3f7b,0xbf7dbef1,0xbf4e0000,0xbeacbf75,0x3f803f0e,0xbe793f22,0x3f783ec4,0xbd493f46,0xbf71bf55,0x3f18be95,0x3e16bf35,0x3f673f62,0xbf2c3e48,0xbf04bf7f,
 0xbf043ec4,0xbf2cbf7f,0x3f673e48,0x3e163f62,0x3f183f80,0xbf71be95,0xbd49bf55,0x3f783f46,0xbe79bf6d,0x3f803f22,0xbeac3f0e,0xbf4ebf75,0xbf7dbf35,0x3edbbef1,0x3f3e3f7b,0xbf5cbdc9,
 0x3f783f35,0xbf2c3e95,0xbeacbf7b,0x3f7d3f22,0xbf183ec4,0xbedbbf7f,0x3f803f0e,0xbf043ef1,0xbf5c0000,0xbd49bf62,0x3f673f55,0xbf4e3dc9,0xbe16bf6d,0x3f713f46,0xbf3e3e48,0xbe79bf75,
 0xbe793f35,0xbf3ebf75,0x3f713e48,0xbe163f46,0xbf4ebf6d,0x3f673dc9,0xbd493f55,0xbf5cbf62,0xbf04bf80,0x3f803ef1,0xbedb3f0e,0xbf18bf7f,0x3f7d3ec4,0xbeac3f22,0xbf2cbf7b,0x3f783e95,
 0xbd49bf6d,0x3f4e3f62,0xbf78be48,0x3edbbf22,0xbeac3f35,0xbf04bf7f,0x3f7d3f0e,0xbf3e3e95,0x3f2cbec4,0x3e163f75,0xbf5cbf55,0x3f713dc9,0xbf670000,0x3e79bf46,0x3f183f7b,0xbf80bef1,
 0xbf80bec4,0x3f18bef1,0x3e793f7b,0xbf67bf46,0x3f713f35,0xbf5c3dc9,0x3e16bf55,0x3f2c3f75,0xbf3ebf6d,0x3f7d3e95,0xbf043f0e,0xbeacbf7f,0x3edb3f80,0xbf78bf22,0x3f4ebe48,0xbd493f62,
 0xbeacbf80,0x3f5c3f46,0xbf7dbe48,0x3f2cbef1,0xbd493f6d,0xbf18bf75,0x3f783f0e,0xbf673dc9,0x3edbbf35,0x3e793f7f,0xbf4ebf55,0x3f803e95,0xbf3e3ec4,0x3e16bf62,0x3f043f7b,0xbf71bf22,
 0xbf710000,0x3f04bf22,0x3e163f7b,0xbf3ebf62,0x3f803ec4,0xbf4e3e95,0x3e79bf55,0x3edb3f7f,0xbf67bf35,0x3f783dc9,0xbf183f0e,0xbd49bf75,0x3f2c3f6d,0xbf7dbef1,0x3f5cbe48,0xbeac3f46,
 0x3f4ebec4,0xbedb3f46,0xbd49bf7b,0x3f043f75,0x3e793f80,0xbf2cbf62,0x3f713f0e,0xbf7dbdc9,0xbe163f6d,0xbeacbf7f,0x3f3e3f55,0xbf78bef1,0xbf5cbf35,0x3f803e95,0xbf673e48,0x3f18bf22,
 0x3f183f6d,0xbf67bf22,0x3f803e48,0xbf5c3e95,0xbf780000,0x3f3ebef1,0xbeac3f55,0xbe16bf7f,0xbf7dbec4,0x3f71bdc9,0xbf2c3f0e,0x3e79bf62,0x3f04bf35,0xbd493f75,0xbedbbf7b,0x3f4e3f46,
 0xbf183f35,0x3eacbf62,0xbd493f7b,0xbe79bf7f,0x3f043f6d,0xbf3ebf46,0x3f673f0e,0xbf7dbe95,0xbe16bf80,0x3edb3f75,0xbf2cbf55,0x3f5c3f22,0xbf78bec4,0x3f803dc9,0xbf713e48,0x3f4ebef1,
 0x3f4e3f35,0xbf71bef1,0x3f803e48,0xbf783dc9,0x3f5cbec4,0xbf2c3f22,0x3edbbf55,0xbe163f75,0xbf7d0000,0x3f67be95,0xbf3e3f0e,0x3f04bf46,0xbe793f6d,0xbd49bf7f,0x3eac3f7b,0xbf18bf62,
 0x3f713ec4,0xbf78be95,0x3f7d3e48,0xbf80bdc9,0x3f3e3f35,0xbf4ebf22,0x3f5c3f0e,0xbf67bef1,0x3edb3f6d,0xbf04bf62,0x3f183f55,0xbf2cbf46,0x3d493f80,0xbe16bf7f,0x3e793f7b,0xbeacbf75,
 0xbeac3f6d,0x3e79bf75,0xbe163f7b,0x3d49bf7f,0xbf2c3f35,0x3f18bf46,0xbf043f55,0x3edbbf62,0xbf673ec4,0x3f5cbef1,0xbf4e3f0e,0x3f3ebf22,0xbf800000,0x3f7dbdc9,0xbf783e48,0x3f71be95,
 0xbd493f80,0x3e16bf7f,0xbe793f7b,0x3eacbf75,0xbedb3f6d,0x3f04bf62,0xbf183f55,0x3f2cbf46,0xbf3e3f35,0x3f4ebf22,0xbf5c3f0e,0x3f67bef1,0xbf713ec4,0x3f78be95,0xbf7d3e48,0x3f80bdc9,
 0xbf800000,0x3f7d3dc9,0xbf78be48,0x3f713e95,0xbf67bec4,0x3f5c3ef1,0xbf4ebf0e,0x3f3e3f22,0xbf2cbf35,0x3f183f46,0xbf04bf55,0x3edb3f62,0xbeacbf6d,0x3e793f75,0xbe16bf7b,0x3d493f7f,
 0xbf783ec4,0x3f80bdc9,0xbf71be48,0x3f4e3ef1,0xbe163f80,0x3edbbf75,0xbf2c3f55,0x3f5cbf22,0x3f04bf6d,0xbf3e3f46,0x3f67bf0e,0xbf7d3e95,0xbf18bf35,0x3eac3f62,0xbd49bf7b,0xbe793f7f,
 0x3e793f6d,0x3d49bf7f,0xbeac3f7b,0x3f18bf62,0x3f7d0000,0xbf67be95,0x3f3e3f0e,0xbf04bf46,0xbf5cbec4,0x3f2c3f22,0xbedbbf55,0x3e163f75,0xbf4e3f35,0x3f71bef1,0xbf803e48,0x3f783dc9,
 0x3f5cbf35,0xbf803e95,0x3f673e48,0xbf18bf22,0x3e163f6d,0x3eacbf7f,0xbf3e3f55,0x3f78bef1,0xbe793f80,0x3f2cbf62,0xbf713f0e,0x3f7dbdc9,0xbf4ebec4,0x3edb3f46,0x3d49bf7b,0xbf043f75,
 0x3f043f35,0xbd49bf75,0xbedb3f7b,0x3f4ebf46,0xbf7d3ec4,0x3f713dc9,0xbf2cbf0e,0x3e793f62,0xbf780000,0x3f3e3ef1,0xbeacbf55,0xbe163f7f,0x3f18bf6d,0xbf673f22,0x3f80be48,0xbf5cbe95,
 0xbf3ebec4,0x3e163f62,0x3f04bf7b,0xbf713f22,0x3edb3f35,0x3e79bf7f,0xbf4e3f55,0x3f80be95,0xbd49bf6d,0xbf183f75,0x3f78bf0e,0xbf67bdc9,0xbeac3f80,0x3f5cbf46,0xbf7d3e48,0x3f2c3ef1,
 0xbf2c3f6d,0x3f7dbef1,0xbf5cbe48,0x3eac3f46,0x3f67bf35,0xbf783dc9,0x3f183f0e,0x3d49bf75,0xbf803ec4,0x3f4e3e95,0xbe79bf55,0xbedb3f7f,0x3f710000,0xbf04bf22,0xbe163f7b,0x3f3ebf62,
 0xbf670000,0x3e793f46,0x3f18bf7b,0xbf803ef1,0x3f2c3ec4,0x3e16bf75,0xbf5c3f55,0x3f71bdc9,0xbeacbf35,0xbf043f7f,0x3f7dbf0e,0xbf3ebe95,0xbd493f6d,0x3f4ebf62,0xbf783e48,0x3edb3f22,
 0xbedb3f80,0x3f78bf22,0xbf4ebe48,0x3d493f62,0x3f3ebf6d,0xbf7d3e95,0x3f043f0e,0x3eacbf7f,0xbf713f35,0x3f5c3dc9,0xbe16bf55,0xbf2c3f75,0x3f80bec4,0xbf18bef1,0xbe793f7b,0x3f67bf46,
 0x3e16bf6d,0xbf713f46,0x3f3e3e48,0x3e79bf75,0x3f5c0000,0x3d49bf62,0xbf673f55,0x3f4e3dc9,0x3f183ec4,0x3edbbf7f,0xbf803f0e,0x3f043ef1,0xbf783f35,0x3f2c3e95,0x3eacbf7b,0xbf7d3f22,
 0x3f7dbec4,0xbeacbf22,0xbf2c3f7b,0x3f78be95,0xbf043f80,0x3f80bef1,0xbedbbf0e,0xbf183f7f,0xbf4e3f6d,0x3f67bdc9,0xbd49bf55,0xbf5c3f62,0xbe79bf35,0xbf3e3f75,0x3f71be48,0xbe16bf46,
 0x3e163f35,0x3f67bf62,0xbf2cbe48,0xbf043f7f,0x3f78bec4,0xbd49bf46,0xbf713f55,0x3f183e95,0xbf4e0000,0xbeac3f75,0x3f80bf0e,0xbe79bf22,0xbf5c3f6d,0x3f3e3dc9,0x3edbbf7b,0xbf7d3ef1,
 0x3f7dbf35,0xbedbbef1,0xbf3e3f7b,0x3f5cbdc9,0x3e79bf6d,0xbf803f22,0x3eac3f0e,0x3f4ebf75,0xbf183f80,0x3f71be95,0x3d49bf55,0xbf783f46,0x3f043ec4,0x3f2cbf7f,0xbf673e48,0xbe163f62,
 0x3f67bf6d,0xbf04be95,0xbf4e3f7b,0x3f2c3dc9,0x3f80bf35,0xbe16bf22,0xbf783f55,0x3eac3ef1,0x3f71bec4,0x3e79bf62,0xbf7d3f0e,0xbd493f46,0x3f3e0000,0x3f18bf7f,0xbf5c3e48,0xbedb3f75,
 0x3edb3ec4,0x3f5cbf75,0xbf18be48,0xbf3e3f7f,0x3d493f35,0x3f7dbf46,0xbe79bf0e,0xbf713f62,0xbeac3f6d,0x3f78bef1,0x3e16bf55,0xbf803f22,0xbf2c3f80,0x3f4ebdc9,0x3f04bf7b,0xbf673e95,
 0xbf800000,0x3f7d3dc9,0xbf78be48,0x3f713e95,0xbf67bec4,0x3f5c3ef1,0xbf4ebf0e,0x3f3e3f22,0xbf2cbf35,0x3f183f46,0xbf04bf55,0x3edb3f62,0xbeacbf6d,0x3e793f75,0xbe16bf7b,0x3d493f7f,
 0x3d49bf80,0xbe163f7f,0x3e79bf7b,0xbeac3f75,0x3edbbf6d,0xbf043f62,0x3f18bf55,0xbf2c3f46,0x3f3ebf35,0xbf4e3f22,0x3f5cbf0e,0xbf673ef1,0x3f71bec4,0xbf783e95,0x3f7dbe48,0xbf803dc9,
 0xbe79bf6d,0xbd493f7f,0x3eacbf7b,0xbf183f62,0xbf7d0000,0x3f673e95,0xbf3ebf0e,0x3f043f46,0x3f5c3ec4,0xbf2cbf22,0x3edb3f55,0xbe16bf75,0x3f4ebf35,0xbf713ef1,0x3f80be48,0xbf78bdc9,
 0xbf783ec4,0x3f80bdc9,0xbf71be48,0x3f4e3ef1,0xbe163f80,0x3edbbf75,0xbf2c3f55,0x3f5cbf22,0x3f04bf6d,0xbf3e3f46,0x3f67bf0e,0xbf7d3e95,0xbf18bf35,0x3eac3f62,0xbd49bf7b,0xbe793f7f,
 0x3f043f35,0xbd49bf75,0xbedb3f7b,0x3f4ebf46,0xbf7d3ec4,0x3f713dc9,0xbf2cbf0e,0x3e793f62,0xbf780000,0x3f3e3ef1,0xbeacbf55,0xbe163f7f,0x3f18bf6d,0xbf673f22,0x3f80be48,0xbf5cbe95,
 0xbf5c3f35,0x3f80be95,0xbf67be48,0x3f183f22,0xbe16bf6d,0xbeac3f7f,0x3f3ebf55,0xbf783ef1,0x3e79bf80,0xbf2c3f62,0x3f71bf0e,0xbf7d3dc9,0x3f4e3ec4,0xbedbbf46,0xbd493f7b,0x3f04bf75,
 0x3f2cbf6d,0xbf7d3ef1,0x3f5c3e48,0xbeacbf46,0xbf673f35,0x3f78bdc9,0xbf18bf0e,0xbd493f75,0x3f80bec4,0xbf4ebe95,0x3e793f55,0x3edbbf7f,0xbf710000,0x3f043f22,0x3e16bf7b,0xbf3e3f62,
 0xbf3ebec4,0x3e163f62,0x3f04bf7b,0xbf713f22,0x3edb3f35,0x3e79bf7f,0xbf4e3f55,0x3f80be95,0xbd49bf6d,0xbf183f75,0x3f78bf0e,0xbf67bdc9,0xbeac3f80,0x3f5cbf46,0xbf7d3e48,0x3f2c3ef1,
 0x3edbbf80,0xbf783f22,0x3f4e3e48,0xbd49bf62,0xbf3e3f6d,0x3f7dbe95,0xbf04bf0e,0xbeac3f7f,0x3f71bf35,0xbf5cbdc9,0x3e163f55,0x3f2cbf75,0xbf803ec4,0x3f183ef1,0x3e79bf7b,0xbf673f46,
 0xbf670000,0x3e793f46,0x3f18bf7b,0xbf803ef1,0x3f2c3ec4,0x3e16bf75,0xbf5c3f55,0x3f71bdc9,0xbeacbf35,0xbf043f7f,0x3f7dbf0e,0xbf3ebe95,0xbd493f6d,0x3f4ebf62,0xbf783e48,0x3edb3f22,
 0x3f7dbec4,0xbeacbf22,0xbf2c3f7b,0x3f78be95,0xbf043f80,0x3f80bef1,0xbedbbf0e,0xbf183f7f,0xbf4e3f6d,0x3f67bdc9,0xbd49bf55,0xbf5c3f62,0xbe79bf35,0xbf3e3f75,0x3f71be48,0xbe16bf46,
 0xbe163f6d,0x3f71bf46,0xbf3ebe48,0xbe793f75,0xbf5c0000,0xbd493f62,0x3f67bf55,0xbf4ebdc9,0xbf18bec4,0xbedb3f7f,0x3f80bf0e,0xbf04bef1,0x3f78bf35,0xbf2cbe95,0xbeac3f7b,0x3f7dbf22,
 0xbf7d3f35,0x3edb3ef1,0x3f3ebf7b,0xbf5c3dc9,0xbe793f6d,0x3f80bf22,0xbeacbf0e,0xbf4e3f75,0x3f18bf80,0xbf713e95,0xbd493f55,0x3f78bf46,0xbf04bec4,0xbf2c3f7f,0x3f67be48,0x3e16bf62,
 0x3e163f35,0x3f67bf62,0xbf2cbe48,0xbf043f7f,0x3f78bec4,0xbd49bf46,0xbf713f55,0x3f183e95,0xbf4e0000,0xbeac3f75,0x3f80bf0e,0xbe79bf22,0xbf5c3f6d,0x3f3e3dc9,0x3edbbf7b,0xbf7d3ef1,
 0x3edb3ec4,0x3f5cbf75,0xbf18be48,0xbf3e3f7f,0x3d493f35,0x3f7dbf46,0xbe79bf0e,0xbf713f62,0xbeac3f6d,0x3f78bef1,0x3e16bf55,0xbf803f22,0xbf2c3f80,0x3f4ebdc9,0x3f04bf7b,0xbf673e95,
 0xbf673f6d,0x3f043e95,0x3f4ebf7b,0xbf2cbdc9,0xbf803f35,0x3e163f22,0x3f78bf55,0xbeacbef1,0xbf713ec4,0xbe793f62,0x3f7dbf0e,0x3d49bf46,0xbf3e0000,0xbf183f7f,0x3f5cbe48,0x3edbbf75,
 0xbf3e3f80,0x3f183dc9,0x3f5cbf7b,0xbedbbe95,0xbf713f6d,0x3e793ef1,0x3f7dbf55,0xbd49bf22,0xbf803f35,0xbe163f46,0x3f78bf0e,0x3eacbf62,0xbf673ec4,0xbf043f75,0x3f4ebe48,0x3f2cbf7f,
 0xbf2c0000,0xbf4e3f7f,0x3f043e48,0x3f67bf75,0xbeacbec4,0xbf783f62,0x3e163f0e,0x3f80bf46,0x3d49bf35,0xbf7d3f22,0xbe793f55,0x3f71bef1,0x3edbbf6d,0xbf5c3e95,0xbf183f7b,0x3f3ebdc9,
 0xbf5c3ec4,0xbf3e3f7f,0x3edb3e48,0x3f7dbf62,0xbf4e3f80,0x3eac3e95,0x3f80bf55,0x3e79bf46,0x3f78bf6d,0x3d49bf22,0xbf713f0e,0xbf183f75,0x3e16bf35,0xbf673ef1,0xbf2c3f7b,0x3f043dc9,
 0xbf043f6d,0x3f2cbdc9,0x3f67bf7b,0xbe16bef1,0x3f180000,0x3f71bf75,0xbd49bf0e,0xbf783f22,0xbe79bec4,0xbf803f46,0xbeac3f55,0x3f4ebe95,0xbf7d3f35,0xbedb3f62,0x3f3ebe48,0x3f5cbf7f,
 0x3f78bf35,0x3f2cbf75,0xbeacbe48,0xbf7d3f46,0xbf183f6d,0x3edb3dc9,0x3f80bf55,0x3f04bf62,0xbf5c3f80,0x3d493ef1,0x3f67bf0e,0x3f4ebf7f,0xbe16bec4,0xbf713f22,0xbf3e3f7b,0x3e793e95,
 0xbe793f35,0x3f3ebe95,0x3f71bf7b,0x3e16bf22,0xbf4e3ec4,0xbf673f7f,0xbd493f0e,0x3f5cbef1,0xbf040000,0xbf803f62,0xbedb3f55,0x3f18bdc9,0x3f7dbf6d,0x3eacbf46,0xbf2c3e48,0xbf783f75,
 0xbd49bec4,0xbf4e3ef1,0xbf783f7b,0xbedb3f46,0xbeac3f35,0x3f04bdc9,0x3f7dbf55,0x3f3ebf75,0x3f2cbf6d,0xbe16be95,0xbf5c3f0e,0xbf713f7f,0xbf673f80,0xbe793f22,0x3f18be48,0x3f80bf62,
 0xbf803f6d,0xbf183f62,0x3e793e48,0x3f67bf22,0x3f71bf35,0x3f5cbf7f,0x3e16bf0e,0xbf2c3e95,0xbf3e3ec4,0xbf7d3f75,0xbf043f55,0x3eac3dc9,0x3edb0000,0x3f78bf46,0x3f4ebf7b,0x3d49bef1,
 0xbeac0000,0xbf5c3f22,0xbf7d3f7b,0xbf2c3f62,0xbd493ec4,0x3f18be95,0x3f78bf55,0x3f67bf7f,0x3edbbf35,0xbe79bdc9,0xbf4e3f0e,0xbf803f75,0xbf3e3f6d,0xbe163ef1,0x3f04be48,0x3f71bf46,
 0xbf713f80,0xbf043f46,0x3e163e48,0x3f3ebef1,0x3f80bf6d,0x3f4ebf75,0x3e79bf0e,0xbedb3dc9,0xbf673f35,0xbf783f7f,0xbf183f55,0x3d493e95,0x3f2cbec4,0x3f7dbf62,0x3f5cbf7b,0x3eacbf22,
 0x3f4ebf6d,0x3edbbf22,0xbd49be48,0xbf043e95,0x3e790000,0x3f2cbef1,0x3f71bf55,0x3f7dbf7f,0xbe163ec4,0x3eacbdc9,0x3f3ebf0e,0x3f78bf62,0xbf5c3f35,0xbf803f75,0xbf673f7b,0xbf183f46,
 0x3f18bec4,0x3f67bf46,0x3f80bf7b,0x3f5cbf75,0xbf783f80,0xbf3e3f62,0xbeac3f0e,0x3e163dc9,0xbf7d3f6d,0xbf713f7f,0xbf2c3f55,0xbe793ef1,0x3f04bf35,0x3d49be95,0xbedb3e48,0xbf4e3f22,
 0xbf183f35,0xbeac3ef1,0xbd493e48,0x3e79bdc9,0x3f04bec4,0x3f3ebf22,0x3f67bf55,0x3f7dbf75,0xbe160000,0xbedb3e95,0xbf2c3f0e,0xbf5c3f46,0xbf783f6d,0xbf803f7f,0xbf713f7b,0xbf4e3f62,
 0x3f4ebf35,0x3f71bf62,0x3f80bf7b,0x3f78bf7f,0x3f5cbf6d,0x3f2cbf46,0x3edbbf0e,0x3e16be95,0xbf7d3f80,0xbf673f75,0xbf3e3f55,0xbf043f22,0xbe793ec4,0x3d493dc9,0x3eacbe48,0x3f18bef1,
 0x3f71bf6d,0x3f78bf75,0x3f7dbf7b,0x3f80bf7f,0x3f3ebf35,0x3f4ebf46,0x3f5cbf55,0x3f67bf62,0x3edbbec4,0x3f04bef1,0x3f18bf0e,0x3f2cbf22,0x3d490000,0x3e16bdc9,0x3e79be48,0x3eacbe95,
 0xbeac3ec4,0xbe793e95,0xbe163e48,0xbd493dc9,0xbf2c3f35,0xbf183f22,0xbf043f0e,0xbedb3ef1,0xbf673f6d,0xbf5c3f62,0xbf4e3f55,0xbf3e3f46,0xbf803f80,0xbf7d3f7f,0xbf783f7b,0xbf713f75,
 0xbf2c0000,0xbf4e3f7f,0x3f043e48,0x3f67bf75,0xbeacbec4,0xbf783f62,0x3e163f0e,0x3f80bf46,0x3d49bf35,0xbf7d3f22,0xbe793f55,0x3f71bef1,0x3edbbf6d,0xbf5c3e95,0xbf183f7b,0x3f3ebdc9,
 0x3f3ebf80,0xbf18bdc9,0xbf5c3f7b,0x3edb3e95,0x3f71bf6d,0xbe79bef1,0xbf7d3f55,0x3d493f22,0x3f80bf35,0x3e16bf46,0xbf783f0e,0xbeac3f62,0x3f67bec4,0x3f04bf75,0xbf4e3e48,0xbf2c3f7f,
 0x3f04bf6d,0xbf2c3dc9,0xbf673f7b,0x3e163ef1,0xbf180000,0xbf713f75,0x3d493f0e,0x3f78bf22,0x3e793ec4,0x3f80bf46,0x3eacbf55,0xbf4e3e95,0x3f7dbf35,0x3edbbf62,0xbf3e3e48,0xbf5c3f7f,
 0xbf5c3ec4,0xbf3e3f7f,0x3edb3e48,0x3f7dbf62,0xbf4e3f80,0x3eac3e95,0x3f80bf55,0x3e79bf46,0x3f78bf6d,0x3d49bf22,0xbf713f0e,0xbf183f75,0x3e16bf35,0xbf673ef1,0xbf2c3f7b,0x3f043dc9,
 0xbe793f35,0x3f3ebe95,0x3f71bf7b,0x3e16bf22,0xbf4e3ec4,0xbf673f7f,0xbd493f0e,0x3f5cbef1,0xbf040000,0xbf803f62,0xbedb3f55,0x3f18bdc9,0x3f7dbf6d,0x3eacbf46,0xbf2c3e48,0xbf783f75,
 0xbf783f35,0xbf2c3f75,0x3eac3e48,0x3f7dbf46,0x3f18bf6d,0xbedbbdc9,0xbf803f55,0xbf043f62,0x3f5cbf80,0xbd49bef1,0xbf673f0e,0xbf4e3f7f,0x3e163ec4,0x3f71bf22,0x3f3ebf7b,0xbe79be95,
 0x3f80bf6d,0x3f18bf62,0xbe79be48,0xbf673f22,0xbf713f35,0xbf5c3f7f,0xbe163f0e,0x3f2cbe95,0x3f3ebec4,0x3f7dbf75,0x3f04bf55,0xbeacbdc9,0xbedb0000,0xbf783f46,0xbf4e3f7b,0xbd493ef1,
 0xbd49bec4,0xbf4e3ef1,0xbf783f7b,0xbedb3f46,0xbeac3f35,0x3f04bdc9,0x3f7dbf55,0x3f3ebf75,0x3f2cbf6d,0xbe16be95,0xbf5c3f0e,0xbf713f7f,0xbf673f80,0xbe793f22,0x3f18be48,0x3f80bf62,
 0x3f71bf80,0x3f04bf46,0xbe16be48,0xbf3e3ef1,0xbf803f6d,0xbf4e3f75,0xbe793f0e,0x3edbbdc9,0x3f67bf35,0x3f78bf7f,0x3f18bf55,0xbd49be95,0xbf2c3ec4,0xbf7d3f62,0xbf5c3f7b,0xbeac3f22,
 0xbeac0000,0xbf5c3f22,0xbf7d3f7b,0xbf2c3f62,0xbd493ec4,0x3f18be95,0x3f78bf55,0x3f67bf7f,0x3edbbf35,0xbe79bdc9,0xbf4e3f0e,0xbf803f75,0xbf3e3f6d,0xbe163ef1,0x3f04be48,0x3f71bf46,
 0x3f18bec4,0x3f67bf46,0x3f80bf7b,0x3f5cbf75,0xbf783f80,0xbf3e3f62,0xbeac3f0e,0x3e163dc9,0xbf7d3f6d,0xbf713f7f,0xbf2c3f55,0xbe793ef1,0x3f04bf35,0x3d49be95,0xbedb3e48,0xbf4e3f22,
 0xbf4e3f6d,0xbedb3f22,0x3d493e48,0x3f04be95,0xbe790000,0xbf2c3ef1,0xbf713f55,0xbf7d3f7f,0x3e16bec4,0xbeac3dc9,0xbf3e3f0e,0xbf783f62,0x3f5cbf35,0x3f80bf75,0x3f67bf7b,0x3f18bf46,
 0xbf4e3f35,0xbf713f62,0xbf803f7b,0xbf783f7f,0xbf5c3f6d,0xbf2c3f46,0xbedb3f0e,0xbe163e95,0x3f7dbf80,0x3f67bf75,0x3f3ebf55,0x3f04bf22,0x3e79bec4,0xbd49bdc9,0xbeac3e48,0xbf183ef1,
 0xbf183f35,0xbeac3ef1,0xbd493e48,0x3e79bdc9,0x3f04bec4,0x3f3ebf22,0x3f67bf55,0x3f7dbf75,0xbe160000,0xbedb3e95,0xbf2c3f0e,0xbf5c3f46,0xbf783f6d,0xbf803f7f,0xbf713f7b,0xbf4e3f62,
 0xbeac3ec4,0xbe793e95,0xbe163e48,0xbd493dc9,0xbf2c3f35,0xbf183f22,0xbf043f0e,0xbedb3ef1,0xbf673f6d,0xbf5c3f62,0xbf4e3f55,0xbf3e3f46,0xbf803f80,0xbf7d3f7f,0xbf783f7b,0xbf713f75,
 0xbf713f6d,0xbf783f75,0xbf7d3f7b,0xbf803f7f,0xbf3e3f35,0xbf4e3f46,0xbf5c3f55,0xbf673f62,0xbedb3ec4,0xbf043ef1,0xbf183f0e,0xbf2c3f22,0xbd490000,0xbe163dc9,0xbe793e48,0xbeac3e95,
};
__device__ __align__(128) const uint32_t g_Gimg[1536] = {
 0x00003d00,0x00003d00,0x00003d00,0x00003d00,0x00003d00,0x00003d00,0x00003d00,0x00003d00,0x00003d00,0x00003d00,0x00003d00,0x00003d00,0x00003d00,0x00003d00,0x00003d00,0x00003d00,
 0x00003d00,0x00003d00,0x00003d00,0x00003d00,0x00003d00,0x00003d00,0x00003d00,0x00003d00,0x00003d00,0x00003d00,0x00003d00,0x00003d00,0x00003d00,0x00003d00,0x00003d00,0x00003d00,
 0xbc5b3ce7,0xbc843cdc,0xbc983cce,0xbcac3cbe,0xbac93d00,0xbb963cfd,0xbbf93cf8,0xbc2c3cf1,0xbcf13c2c,0xbcf83bf9,0xbcfd3b96,0xbd003ac9,0xbcbe3cac,0xbcce3c98,0xbcdc3c84,0xbce73c5b,
 0xbce7bc5b,0xbcdcbc84,0xbccebc98,0xbcbebcac,0xbd00bac9,0xbcfdbb96,0xbcf8bbf9,0xbcf1bc2c,0xbc2cbcf1,0xbbf9bcf8,0xbb96bcfd,0xbac9bd00,0xbcacbcbe,0xbc98bcce,0xbc84bcdc,0xbc5bbce7,
 0xbcffbb49,0xbcf5bc15,0xbce2bc71,0xbcc6bca2,0xbca2bcc6,0xbc71bce2,0xbc15bcf5,0xbb49bcff,0xbb493cff,0xbc153cf5,0xbc713ce2,0xbca23cc6,0xbcc63ca2,0xbce23c71,0xbcf53c15,0xbcff3b49,
 0x3cff3b49,0x3cf53c15,0x3ce23c71,0x3cc63ca2,0x3ca23cc6,0x3c713ce2,0x3c153cf5,0x3b493cff,0x3b49bcff,0x3c15bcf5,0x3c71bce2,0x3ca2bcc6,0x3cc6bca2,0x3ce2bc71,0x3cf5bc15,0x3cffbb49,
 0x3c84bcdc,0x3cbebcac,0x3ce7bc5b,0x3cfdbb96,0xbc98bcce,0xbc2cbcf1,0xbac9bd00,0x3bf9bcf8,0xbcf83bf9,0xbd00bac9,0xbcf1bc2c,0xbccebc98,0xbb963cfd,0xbc5b3ce7,0xbcac3cbe,0xbcdc3c84,
 0xbcdcbc84,0xbcacbcbe,0xbc5bbce7,0xbb96bcfd,0xbcce3c98,0xbcf13c2c,0xbd003ac9,0xbcf8bbf9,0x3bf93cf8,0xbac93d00,0xbc2c3cf1,0xbc983cce,0x3cfd3b96,0x3ce73c5b,0x3cbe3cac,0x3c843cdc,
 0xbbc83cfb,0xbc8e3cd5,0xbcd53c8e,0xbcfb3bc8,0xbcfbbbc8,0xbcd5bc8e,0xbc8ebcd5,0xbbc8bcfb,0x3bc8bcfb,0x3c8ebcd5,0x3cd5bc8e,0x3cfbbbc8,0x3cfb3bc8,0x3cd53c8e,0x3c8e3cd5,0x3bc83cfb,
 0xbbc83cfb,0xbc8e3cd5,0xbcd53c8e,0xbcfb3bc8,0xbcfbbbc8,0xbcd5bc8e,0xbc8ebcd5,0xbbc8bcfb,0x3bc8bcfb,0x3c8ebcd5,0x3cd5bc8e,0x3cfbbbc8,0x3cfb3bc8,0x3cd53c8e,0x3c8e3cd5,0x3bc83cfb,
 0x3c98bcce,0x3ce7bc5b,0x3d003ac9,0x3cdc3c84,0xbcf8bbf9,0xbcbebcac,0xbc2cbcf1,0x3b96bcfd,0xbcfd3b96,0xbcf1bc2c,0xbcacbcbe,0xbbf9bcf8,0x3c843cdc,0x3ac93d00,0xbc5b3ce7,0xbcce3c98,
 0xbccebc98,0xbc5bbce7,0x3ac9bd00,0x3c84bcdc,0xbbf93cf8,0xbcac3cbe,0xbcf13c2c,0xbcfdbb96,0x3b963cfd,0xbc2c3cf1,0xbcbe3cac,0xbcf83bf9,0x3cdcbc84,0x3d00bac9,0x3ce73c5b,0x3c983cce,
 0xbcf5bc15,0xbca2bcc6,0xbb49bcff,0x3c71bce2,0x3ce2bc71,0x3cff3b49,0x3cc63ca2,0x3c153cf5,0x3c15bcf5,0x3cc6bca2,0x3cffbb49,0x3ce23c71,0x3c713ce2,0xbb493cff,0xbca23cc6,0xbcf53c15,
 0x3cf53c15,0x3ca23cc6,0x3b493cff,0xbc713ce2,0xbce23c71,0xbcffbb49,0xbcc6bca2,0xbc15bcf5,0xbc153cf5,0xbcc63ca2,0xbcff3b49,0xbce2bc71,0xbc71bce2,0x3b49bcff,0x3ca2bcc6,0x3cf5bc15,
 0xbcac3cbe,0xbcfd3b96,0xbcdcbc84,0xbc2cbcf1,0x3ce7bc5b,0x3cf83bf9,0x3c983cce,0xbac93d00,0xbd003ac9,0xbccebc98,0xbbf9bcf8,0x3c5bbce7,0x3cf13c2c,0x3c843cdc,0xbb963cfd,0xbcbe3cac,
 0xbcbebcac,0xbb96bcfd,0x3c84bcdc,0x3cf1bc2c,0x3c5b3ce7,0xbbf93cf8,0xbcce3c98,0xbd00bac9,0xbac9bd00,0x3c98bcce,0x3cf8bbf9,0x3ce73c5b,0xbc2c3cf1,0xbcdc3c84,0xbcfdbb96,0xbcacbcbe,
 0xbc443ced,0xbced3c44,0xbcedbc44,0xbc44bced,0x3c44bced,0x3cedbc44,0x3ced3c44,0x3c443ced,0xbc443ced,0xbced3c44,0xbcedbc44,0xbc44bced,0x3c44bced,0x3cedbc44,0x3ced3c44,0x3c443ced,
 0xbc443ced,0xbced3c44,0xbcedbc44,0xbc44bced,0x3c44bced,0x3cedbc44,0x3ced3c44,0x3c443ced,0xbc443ced,0xbced3c44,0xbcedbc44,0xbc44bced,0x3c44bced,0x3cedbc44,0x3ced3c44,0x3c443ced,
 0x3cbebcac,0x3cfd3b96,0x3c843cdc,0xbc2c3cf1,0xbc5b3ce7,0xbcf83bf9,0xbccebc98,0xbac9bd00,0x3d003ac9,0x3c983cce,0xbbf93cf8,0xbce73c5b,0xbcf13c2c,0xbcdcbc84,0xbb96bcfd,0x3cacbcbe,
 0x3cac3cbe,0xbb963cfd,0xbcdc3c84,0xbcf1bc2c,0xbce7bc5b,0xbbf9bcf8,0x3c98bcce,0x3d00bac9,0xbac93d00,0xbcce3c98,0xbcf8bbf9,0xbc5bbce7,0xbc2cbcf1,0x3c84bcdc,0x3cfdbb96,0x3cbe3cac,
 0xbce2bc71,0xbb49bcff,0x3cc6bca2,0x3cf53c15,0x3c153cf5,0xbca23cc6,0xbcffbb49,0xbc71bce2,0xbc713ce2,0xbcff3b49,0xbca2bcc6,0x3c15bcf5,0x3cf5bc15,0x3cc63ca2,0xbb493cff,0xbce23c71,
 0x3ce23c71,0x3b493cff,0xbcc63ca2,0xbcf5bc15,0xbc15bcf5,0x3ca2bcc6,0x3cff3b49,0x3c713ce2,0x3c71bce2,0x3cffbb49,0x3ca23cc6,0xbc153cf5,0xbcf53c15,0xbcc6bca2,0x3b49bcff,0x3ce2bc71,
 0xbcce3c98,0xbce7bc5b,0xbac9bd00,0x3cdcbc84,0xbbf9bcf8,0x3cbebcac,0x3cf13c2c,0x3b963cfd,0x3cfd3b96,0x3c2c3cf1,0xbcac3cbe,0xbcf8bbf9,0xbc843cdc,0xbd00bac9,0xbc5bbce7,0x3c98bcce,
 0x3c983cce,0xbc5b3ce7,0xbd003ac9,0xbc84bcdc,0xbcf83bf9,0xbcacbcbe,0x3c2cbcf1,0x3cfdbb96,0x3b96bcfd,0x3cf1bc2c,0x3cbe3cac,0xbbf93cf8,0x3cdc3c84,0xbac93d00,0xbce73c5b,0xbccebc98,
 0xbc8e3cd5,0xbcfbbbc8,0xbbc8bcfb,0x3cd5bc8e,0x3cd53c8e,0xbbc83cfb,0xbcfb3bc8,0xbc8ebcd5,0x3c8ebcd5,0x3cfb3bc8,0x3bc83cfb,0xbcd53c8e,0xbcd5bc8e,0x3bc8bcfb,0x3cfbbbc8,0x3c8e3cd5,
 0xbc8e3cd5,0xbcfbbbc8,0xbbc8bcfb,0x3cd5bc8e,0x3cd53c8e,0xbbc83cfb,0xbcfb3bc8,0xbc8ebcd5,0x3c8ebcd5,0x3cfb3bc8,0x3bc83cfb,0xbcd53c8e,0xbcd5bc8e,0x3bc8bcfb,0x3cfbbbc8,0x3c8e3cd5,
 0xbcdc3c84,0xbcbebcac,0x3c5bbce7,0x3cfd3b96,0xbccebc98,0x3c2cbcf1,0x3d003ac9,0x3bf93cf8,0x3cf83bf9,0x3ac93d00,0xbcf13c2c,0xbc98bcce,0x3b963cfd,0xbce73c5b,0xbcacbcbe,0x3c84bcdc,
 0x3c843cdc,0xbcac3cbe,0xbce7bc5b,0x3b96bcfd,0xbc983cce,0xbcf1bc2c,0x3ac9bd00,0x3cf8bbf9,0x3bf9bcf8,0x3d00bac9,0x3c2c3cf1,0xbcce3c98,0x3cfdbb96,0x3c5b3ce7,0xbcbe3cac,0xbcdcbc84,
 0xbcc6bca2,0x3c71bce2,0x3cf53c15,0xbb493cff,0xbcff3b49,0xbc15bcf5,0x3ce2bc71,0x3ca23cc6,0x3ca2bcc6,0x3ce23c71,0xbc153cf5,0xbcffbb49,0xbb49bcff,0x3cf5bc15,0x3c713ce2,0xbcc63ca2,
 0x3cc63ca2,0xbc713ce2,0xbcf5bc15,0x3b49bcff,0x3cffbb49,0x3c153cf5,0xbce23c71,0xbca2bcc6,0xbca23cc6,0xbce2bc71,0x3c15bcf5,0x3cff3b49,0x3b493cff,0xbcf53c15,0xbc71bce2,0x3cc6bca2,
 0x3ce7bc5b,0x3c843cdc,0xbcce3c98,0xbcacbcbe,0x3d00bac9,0x3b963cfd,0xbcf83bf9,0xbc2cbcf1,0x3cf13c2c,0xbbf93cf8,0xbcfdbb96,0x3ac9bd00,0x3cbe3cac,0xbc983cce,0xbcdcbc84,0x3c5bbce7,
 0x3c5b3ce7,0xbcdc3c84,0xbc98bcce,0x3cbebcac,0x3ac93d00,0xbcfd3b96,0xbbf9bcf8,0x3cf1bc2c,0xbc2c3cf1,0xbcf8bbf9,0x3b96bcfd,0x3d003ac9,0xbcac3cbe,0xbccebc98,0x3c84bcdc,0x3ce73c5b,
 0xbcb53cb5,0xbcb5bcb5,0x3cb5bcb5,0x3cb53cb5,0xbcb53cb5,0xbcb5bcb5,0x3cb5bcb5,0x3cb53cb5,0xbcb53cb5,0xbcb5bcb5,0x3cb5bcb5,0x3cb53cb5,0xbcb53cb5,0xbcb5bcb5,0x3cb5bcb5,0x3cb53cb5,
 0xbcb53cb5,0xbcb5bcb5,0x3cb5bcb5,0x3cb53cb5,0xbcb53cb5,0xbcb5bcb5,0x3cb5bcb5,0x3cb53cb5,0xbcb53cb5,0xbcb5bcb5,0x3cb5bcb5,0x3cb53cb5,0xbcb53cb5,0xbcb5bcb5,0x3cb5bcb5,0x3cb53cb5,
 0xbcf13c2c,0xbbf9bcf8,0x3cfdbb96,0x3ac93d00,0xbcbe3cac,0xbc98bcce,0x3cdcbc84,0x3c5b3ce7,0xbce7bc5b,0x3c84bcdc,0x3cce3c98,0xbcac3cbe,0xbd00bac9,0x3b96bcfd,0x3cf83bf9,0xbc2c3cf1,
 0xbc2cbcf1,0x3cf8bbf9,0x3b963cfd,0xbd003ac9,0xbcacbcbe,0x3ccebc98,0x3c843cdc,0xbce73c5b,0x3c5bbce7,0x3cdc3c84,0xbc983cce,0xbcbebcac,0x3ac9bd00,0x3cfd3b96,0xbbf93cf8,0xbcf1bc2c,
 0xbca2bcc6,0x3ce2bc71,0x3c153cf5,0xbcff3b49,0x3b49bcff,0x3cf53c15,0xbc713ce2,0xbcc6bca2,0xbcc63ca2,0xbc71bce2,0x3cf5bc15,0x3b493cff,0xbcffbb49,0x3c15bcf5,0x3ce23c71,0xbca23cc6,
 0x3ca23cc6,0xbce23c71,0xbc15bcf5,0x3cffbb49,0xbb493cff,0xbcf5bc15,0x3c71bce2,0x3cc63ca2,0x3cc6bca2,0x3c713ce2,0xbcf53c15,0xbb49bcff,0x3cff3b49,0xbc153cf5,0xbce2bc71,0x3ca2bcc6,
 0x3cf8bbf9,0xbac93d00,0xbcf1bc2c,0x3c98bcce,0x3b96bcfd,0x3ce73c5b,0xbcac3cbe,0xbc84bcdc,0xbcdcbc84,0x3cbebcac,0x3c5b3ce7,0xbcfd3b96,0xbcce3c98,0xbc2cbcf1,0x3d00bac9,0xbbf93cf8,
 0xbbf9bcf8,0x3d003ac9,0xbc2c3cf1,0xbccebc98,0xbcfdbb96,0x3c5bbce7,0x3cbe3cac,0xbcdc3c84,0xbc843cdc,0xbcacbcbe,0x3ce7bc5b,0x3b963cfd,0x3c983cce,0xbcf13c2c,0xbac9bd00,0x3cf83bf9,
 0xbcd53c8e,0xbbc8bcfb,0x3cfb3bc8,0xbc8e3cd5,0xbc8ebcd5,0x3cfbbbc8,0xbbc83cfb,0xbcd5bc8e,0x3cd5bc8e,0x3bc83cfb,0xbcfbbbc8,0x3c8ebcd5,0x3c8e3cd5,0xbcfb3bc8,0x3bc8bcfb,0x3cd53c8e,
 0xbcd53c8e,0xbbc8bcfb,0x3cfb3bc8,0xbc8e3cd5,0xbc8ebcd5,0x3cfbbbc8,0xbbc83cfb,0xbcd5bc8e,0x3cd5bc8e,0x3bc83cfb,0xbcfbbbc8,0x3c8ebcd5,0x3c8e3cd5,0xbcfb3bc8,0x3bc8bcfb,0x3cd53c8e,
 0x3cfdbb96,0xbc2c3cf1,0xbcacbcbe,0x3cf8bbf9,0xbc84bcdc,0x3d00bac9,0xbc5b3ce7,0xbc98bcce,0xbccebc98,0x3ce7bc5b,0xbac93d00,0xbcdcbc84,0xbbf93cf8,0xbcbebcac,0x3cf1bc2c,0xbb963cfd,
 0xbb96bcfd,0x3cf13c2c,0xbcbe3cac,0xbbf9bcf8,0xbcdc3c84,0xbac9bd00,0x3ce73c5b,0xbcce3c98,0xbc983cce,0xbc5bbce7,0x3d003ac9,0xbc843cdc,0x3cf83bf9,0xbcac3cbe,0xbc2cbcf1,0x3cfd3b96,
 0xbc71bce2,0x3cff3b49,0xbca23cc6,0xbc15bcf5,0x3cf53c15,0xbcc63ca2,0xbb49bcff,0x3ce23c71,0x3ce2bc71,0xbb493cff,0xbcc6bca2,0x3cf5bc15,0xbc153cf5,0xbca2bcc6,0x3cffbb49,0xbc713ce2,
 0x3c713ce2,0xbcffbb49,0x3ca2bcc6,0x3c153cf5,0xbcf5bc15,0x3cc6bca2,0x3b493cff,0xbce2bc71,0xbce23c71,0x3b49bcff,0x3cc63ca2,0xbcf53c15,0x3c15bcf5,0x3ca23cc6,0xbcff3b49,0x3c71bce2,
 0xbd003ac9,0x3c98bcce,0x3bf93cf8,0xbce7bc5b,0x3cf13c2c,0xbcdc3c84,0x3b96bcfd,0x3cac3cbe,0xbcbebcac,0x3cfdbb96,0xbc843cdc,0xbc2cbcf1,0x3c5b3ce7,0xbcf8bbf9,0x3ccebc98,0xbac93d00,
 0xbac9bd00,0x3cce3c98,0xbcf83bf9,0x3c5bbce7,0xbc2c3cf1,0xbc84bcdc,0x3cfd3b96,0xbcbe3cac,0x3cacbcbe,0x3b963cfd,0xbcdcbc84,0x3cf1bc2c,0xbce73c5b,0x3bf9bcf8,0x3c983cce,0xbd00bac9,
 0xbced3c44,0x3c44bced,0x3c443ced,0xbcedbc44,0x3cedbc44,0xbc443ced,0xbc44bced,0x3ced3c44,0xbced3c44,0x3c44bced,0x3c443ced,0xbcedbc44,0x3cedbc44,0xbc443ced,0xbc44bced,0x3ced3c44,
 0xbced3c44,0x3c44bced,0x3c443ced,0xbcedbc44,0x3cedbc44,0xbc443ced,0xbc44bced,0x3ced3c44,0xbced3c44,0x3c44bced,0x3c443ced,0xbcedbc44,0x3cedbc44,0xbc443ced,0xbc44bced,0x3ced3c44,
 0x3d003ac9,0xbcce3c98,0x3bf9bcf8,0x3c5b3ce7,0xbcf13c2c,0x3c84bcdc,0x3b963cfd,0xbcbebcac,0x3cac3cbe,0xbcfdbb96,0x3cdcbc84,0xbc2c3cf1,0xbce7bc5b,0x3cf8bbf9,0xbc983cce,0xbac9bd00,
 0xbac93d00,0xbc98bcce,0x3cf83bf9,0xbce73c5b,0xbc2cbcf1,0x3cdc3c84,0xbcfd3b96,0x3cacbcbe,0xbcbe3cac,0x3b96bcfd,0x3c843cdc,0xbcf1bc2c,0x3c5bbce7,0x3bf93cf8,0xbccebc98,0x3d00bac9,
 0xbc15bcf5,0x3cc63ca2,0xbcffbb49,0x3ce2bc71,0xbc713ce2,0xbb49bcff,0x3ca23cc6,0xbcf5bc15,0xbcf53c15,0x3ca2bcc6,0xbb493cff,0xbc71bce2,0x3ce23c71,0xbcff3b49,0x3cc6bca2,0xbc153cf5,
 0x3c153cf5,0xbcc6bca2,0x3cff3b49,0xbce23c71,0x3c71bce2,0x3b493cff,0xbca2bcc6,0x3cf53c15,0x3cf5bc15,0xbca23cc6,0x3b49bcff,0x3c713ce2,0xbce2bc71,0x3cffbb49,0xbcc63ca2,0x3c15bcf5,
 0xbcfdbb96,0x3cf1bc2c,0xbcac3cbe,0x3bf9bcf8,0x3c84bcdc,0xbac93d00,0xbc5bbce7,0x3cce3c98,0x3c983cce,0xbce7bc5b,0x3d00bac9,0xbcdc3c84,0xbcf83bf9,0x3cbebcac,0xbc2c3cf1,0xbb96bcfd,
 0xbb963cfd,0xbc2cbcf1,0x3cbe3cac,0xbcf8bbf9,0xbcdcbc84,0x3d003ac9,0xbce73c5b,0x3c98bcce,0x3ccebc98,0xbc5b3ce7,0xbac9bd00,0x3c843cdc,0x3bf93cf8,0xbcacbcbe,0x3cf13c2c,0xbcfd3b96,
 0xbcfb3bc8,0x3cd5bc8e,0xbc8e3cd5,0x3bc8bcfb,0x3bc83cfb,0xbc8ebcd5,0x3cd53c8e,0xbcfbbbc8,0x3cfbbbc8,0xbcd53c8e,0x3c8ebcd5,0xbbc83cfb,0xbbc8bcfb,0x3c8e3cd5,0xbcd5bc8e,0x3cfb3bc8,
 0xbcfb3bc8,0x3cd5bc8e,0xbc8e3cd5,0x3bc8bcfb,0x3bc83cfb,0xbc8ebcd5,0x3cd53c8e,0xbcfbbbc8,0x3cfbbbc8,0xbcd53c8e,0x3c8ebcd5,0xbbc83cfb,0xbbc8bcfb,0x3c8e3cd5,0xbcd5bc8e,0x3cfb3bc8,
 0xbcf8bbf9,0x3d00bac9,0xbcf13c2c,0x3ccebc98,0xbb96bcfd,0x3c5b3ce7,0xbcacbcbe,0x3cdc3c84,0x3c843cdc,0xbcbebcac,0x3ce73c5b,0xbcfdbb96,0xbc983cce,0x3c2cbcf1,0xbac93d00,0xbbf9bcf8,
 0xbbf93cf8,0xbac9bd00,0x3c2c3cf1,0xbc98bcce,0xbcfd3b96,0x3ce7bc5b,0xbcbe3cac,0x3c84bcdc,0x3cdcbc84,0xbcac3cbe,0x3c5bbce7,0xbb963cfd,0x3cce3c98,0xbcf1bc2c,0x3d003ac9,0xbcf83bf9,
 0xbb49bcff,0x3c153cf5,0xbc71bce2,0x3ca23cc6,0xbcc6bca2,0x3ce23c71,0xbcf5bc15,0x3cff3b49,0x3cffbb49,0xbcf53c15,0x3ce2bc71,0xbcc63ca2,0x3ca2bcc6,0xbc713ce2,0x3c15bcf5,0xbb493cff,
 0x3b493cff,0xbc15bcf5,0x3c713ce2,0xbca2bcc6,0x3cc63ca2,0xbce2bc71,0x3cf53c15,0xbcffbb49,0xbcff3b49,0x3cf5bc15,0xbce23c71,0x3cc6bca2,0xbca23cc6,0x3c71bce2,0xbc153cf5,0x3b49bcff,
 0x3cf13c2c,0xbcf8bbf9,0x3cfd3b96,0xbd00bac9,0x3cbe3cac,0xbccebc98,0x3cdc3c84,0xbce7bc5b,0x3c5b3ce7,0xbc84bcdc,0x3c983cce,0xbcacbcbe,0x3ac93d00,0xbb96bcfd,0x3bf93cf8,0xbc2cbcf1,
 0xbc2c3cf1,0x3bf9bcf8,0xbb963cfd,0x3ac9bd00,0xbcac3cbe,0x3c98bcce,0xbc843cdc,0x3c5bbce7,0xbce73c5b,0x3cdcbc84,0xbcce3c98,0x3cbebcac,0xbd003ac9,0x3cfdbb96,0xbcf83bf9,0x3cf1bc2c,
 0xbd000000,0x3d000000,0xbd000000,0x3d000000,0xbd000000,0x3d000000,0xbd000000,0x3d000000,0xbd000000,0x3d000000,0xbd000000,0x3d000000,0xbd000000,0x3d000000,0xbd000000,0x3d000000,
 0xbd000000,0x3d000000,0xbd000000,0x3d000000,0xbd000000,0x3d000000,0xbd000000,0x3d000000,0xbd000000,0x3d000000,0xbd000000,0x3d000000,0xbd000000,0x3d000000,0xbd000000,0x3d000000,
 0xbce7bc5b,0x3cdc3c84,0xbccebc98,0x3cbe3cac,0xbd00bac9,0x3cfd3b96,0xbcf8bbf9,0x3cf13c2c,0xbc2cbcf1,0x3bf93cf8,0xbb96bcfd,0x3ac93d00,0xbcacbcbe,0x3c983cce,0xbc84bcdc,0x3c5b3ce7,
 0x3c5bbce7,0xbc843cdc,0x3c98bcce,0xbcac3cbe,0x3ac9bd00,0xbb963cfd,0x3bf9bcf8,0xbc2c3cf1,0x3cf1bc2c,0xbcf83bf9,0x3cfdbb96,0xbd003ac9,0x3cbebcac,0xbcce3c98,0x3cdcbc84,0xbce73c5b,
 0x3b49bcff,0xbc153cf5,0x3c71bce2,0xbca23cc6,0x3cc6bca2,0xbce23c71,0x3cf5bc15,0xbcff3b49,0xbcffbb49,0x3cf53c15,0xbce2bc71,0x3cc63ca2,0xbca2bcc6,0x3c713ce2,0xbc15bcf5,0x3b493cff,
 0xbb493cff,0x3c15bcf5,0xbc713ce2,0x3ca2bcc6,0xbcc63ca2,0x3ce2bc71,0xbcf53c15,0x3cffbb49,0x3cff3b49,0xbcf5bc15,0x3ce23c71,0xbcc6bca2,0x3ca23cc6,0xbc71bce2,0x3c153cf5,0xbb49bcff,
 0x3cdc3c84,0xbcacbcbe,0x3c5b3ce7,0xbb96bcfd,0x3ccebc98,0xbcf13c2c,0x3d00bac9,0xbcf8bbf9,0xbbf9bcf8,0xbac93d00,0x3c2cbcf1,0xbc983cce,0xbcfdbb96,0x3ce73c5b,0xbcbebcac,0x3c843cdc,
 0x3c84bcdc,0xbcbe3cac,0x3ce7bc5b,0xbcfd3b96,0xbc98bcce,0x3c2c3cf1,0xbac9bd00,0xbbf93cf8,0xbcf83bf9,0x3d003ac9,0xbcf1bc2c,0x3cce3c98,0xbb963cfd,0x3c5bbce7,0xbcac3cbe,0x3cdcbc84,
 0xbcfbbbc8,0x3cd53c8e,0xbc8ebcd5,0x3bc83cfb,0x3bc8bcfb,0xbc8e3cd5,0x3cd5bc8e,0xbcfb3bc8,0x3cfb3bc8,0xbcd5bc8e,0x3c8e3cd5,0xbbc8bcfb,0xbbc83cfb,0x3c8ebcd5,0xbcd53c8e,0x3cfbbbc8,
 0xbcfbbbc8,0x3cd53c8e,0xbc8ebcd5,0x3bc83cfb,0x3bc8bcfb,0xbc8e3cd5,0x3cd5bc8e,0xbcfb3bc8,0x3cfb3bc8,0xbcd5bc8e,0x3c8e3cd5,0xbbc8bcfb,0xbbc83cfb,0x3c8ebcd5,0xbcd53c8e,0x3cfbbbc8,
 0x3cce3c98,0xbc5bbce7,0xbac93d00,0x3c84bcdc,0x3bf9bcf8,0xbcac3cbe,0x3cf1bc2c,0xbcfdbb96,0xbb96bcfd,0xbc2c3cf1,0x3cbebcac,0xbcf83bf9,0xbcdc3c84,0x3d00bac9,0xbce7bc5b,0x3c983cce,
 0x3c98bcce,0xbce73c5b,0x3d003ac9,0xbcdcbc84,0xbcf8bbf9,0x3cbe3cac,0xbc2cbcf1,0xbb963cfd,0xbcfd3b96,0x3cf13c2c,0xbcacbcbe,0x3bf93cf8,0x3c843cdc,0xbac9bd00,0xbc5b3ce7,0x3ccebc98,
 0x3c15bcf5,0xbcc63ca2,0x3cffbb49,0xbce2bc71,0x3c713ce2,0x3b49bcff,0xbca23cc6,0x3cf5bc15,0x3cf53c15,0xbca2bcc6,0x3b493cff,0x3c71bce2,0xbce23c71,0x3cff3b49,0xbcc6bca2,0x3c153cf5,
 0xbc153cf5,0x3cc6bca2,0xbcff3b49,0x3ce23c71,0xbc71bce2,0xbb493cff,0x3ca2bcc6,0xbcf53c15,0xbcf5bc15,0x3ca23cc6,0xbb49bcff,0xbc713ce2,0x3ce2bc71,0xbcffbb49,0x3cc63ca2,0xbc15bcf5,
 0xbcbebcac,0x3b963cfd,0x3c84bcdc,0xbcf13c2c,0x3c5b3ce7,0x3bf9bcf8,0xbcce3c98,0x3d003ac9,0xbac9bd00,0xbc983cce,0x3cf8bbf9,0xbce7bc5b,0xbc2c3cf1,0x3cdcbc84,0xbcfdbb96,0x3cac3cbe,
 0x3cacbcbe,0xbcfd3b96,0x3cdc3c84,0xbc2cbcf1,0xbce73c5b,0x3cf83bf9,0xbc98bcce,0xbac93d00,0x3d00bac9,0xbccebc98,0x3bf93cf8,0x3c5bbce7,0xbcf1bc2c,0x3c843cdc,0x3b96bcfd,0xbcbe3cac,
 0xbcedbc44,0x3c443ced,0x3c44bced,0xbced3c44,0x3ced3c44,0xbc44bced,0xbc443ced,0x3cedbc44,0xbcedbc44,0x3c443ced,0x3c44bced,0xbced3c44,0x3ced3c44,0xbc44bced,0xbc443ced,0x3cedbc44,
 0xbcedbc44,0x3c443ced,0x3c44bced,0xbced3c44,0x3ced3c44,0xbc44bced,0xbc443ced,0x3cedbc44,0xbcedbc44,0x3c443ced,0x3c44bced,0xbced3c44,0x3ced3c44,0xbc44bced,0xbc443ced,0x3cedbc44,
 0x3cac3cbe,0x3b96bcfd,0xbcdc3c84,0x3cf13c2c,0xbce7bc5b,0x3bf93cf8,0x3c98bcce,0xbd003ac9,0xbac93d00,0x3ccebc98,0xbcf8bbf9,0x3c5b3ce7,0xbc2cbcf1,0xbc843cdc,0x3cfdbb96,0xbcbebcac,
 0xbcbe3cac,0x3cfd3b96,0xbc84bcdc,0xbc2c3cf1,0x3c5bbce7,0xbcf83bf9,0x3cce3c98,0xbac9bd00,0xbd00bac9,0x3c983cce,0x3bf9bcf8,0xbce73c5b,0x3cf1bc2c,0xbcdcbc84,0x3b963cfd,0x3cacbcbe,
 0x3c71bce2,0xbcff3b49,0x3ca23cc6,0x3c15bcf5,0xbcf53c15,0x3cc63ca2,0x3b49bcff,0xbce23c71,0xbce2bc71,0x3b493cff,0x3cc6bca2,0xbcf5bc15,0x3c153cf5,0x3ca2bcc6,0xbcffbb49,0x3c713ce2,
 0xbc713ce2,0x3cffbb49,0xbca2bcc6,0xbc153cf5,0x3cf5bc15,0xbcc6bca2,0xbb493cff,0x3ce2bc71,0x3ce23c71,0xbb49bcff,0xbcc63ca2,0x3cf53c15,0xbc15bcf5,0xbca23cc6,0x3cff3b49,0xbc71bce2,
 0xbc98bcce,0xbc5b3ce7,0x3d00bac9,0xbc84bcdc,0x3cf8bbf9,0xbcacbcbe,0xbc2c3cf1,0x3cfdbb96,0xbb963cfd,0x3cf1bc2c,0xbcbebcac,0xbbf93cf8,0xbcdcbc84,0xbac93d00,0x3ce7bc5b,0xbccebc98,
 0xbcce3c98,0x3ce73c5b,0xbac9bd00,0xbcdc3c84,0xbbf9bcf8,0xbcbe3cac,0x3cf13c2c,0xbb96bcfd,0x3cfd3b96,0xbc2cbcf1,0xbcac3cbe,0x3cf83bf9,0xbc843cdc,0x3d003ac9,0xbc5bbce7,0xbc983cce,
 0xbcd5bc8e,0xbbc83cfb,0x3cfbbbc8,0xbc8ebcd5,0xbc8e3cd5,0x3cfb3bc8,0xbbc8bcfb,0xbcd53c8e,0x3cd53c8e,0x3bc8bcfb,0xbcfb3bc8,0x3c8e3cd5,0x3c8ebcd5,0xbcfbbbc8,0x3bc83cfb,0x3cd5bc8e,
 0xbcd5bc8e,0xbbc83cfb,0x3cfbbbc8,0xbc8ebcd5,0xbc8e3cd5,0x3cfb3bc8,0xbbc8bcfb,0xbcd53c8e,0x3cd53c8e,0x3bc8bcfb,0xbcfb3bc8,0x3c8e3cd5,0x3c8ebcd5,0xbcfbbbc8,0x3bc83cfb,0x3cd5bc8e,
 0xbc84bcdc,0xbcac3cbe,0x3ce73c5b,0x3b96bcfd,0x3c98bcce,0xbcf1bc2c,0xbac93d00,0x3cf8bbf9,0xbbf93cf8,0x3d00bac9,0xbc2cbcf1,0xbcce3c98,0xbcfd3b96,0x3c5b3ce7,0x3cbebcac,0xbcdcbc84,
 0xbcdc3c84,0x3cbe3cac,0x3c5bbce7,0xbcfdbb96,0xbccebc98,0xbc2c3cf1,0x3d003ac9,0xbbf9bcf8,0x3cf83bf9,0xbac9bd00,0xbcf13c2c,0x3c983cce,0x3b963cfd,0x3ce7bc5b,0xbcacbcbe,0xbc843cdc,
 0x3ca2bcc6,0xbce2bc71,0xbc153cf5,0x3cff3b49,0xbb49bcff,0xbcf53c15,0x3c713ce2,0x3cc6bca2,0x3cc63ca2,0x3c71bce2,0xbcf5bc15,0xbb493cff,0x3cffbb49,0xbc15bcf5,0xbce23c71,0x3ca23cc6,
 0xbca23cc6,0x3ce23c71,0x3c15bcf5,0xbcffbb49,0x3b493cff,0x3cf5bc15,0xbc71bce2,0xbcc63ca2,0xbcc6bca2,0xbc713ce2,0x3cf53c15,0x3b49bcff,0xbcff3b49,0x3c153cf5,0x3ce2bc71,0xbca2bcc6,
 0x3c5b3ce7,0x3cdcbc84,0xbc98bcce,0xbcbe3cac,0x3ac93d00,0x3cfdbb96,0xbbf9bcf8,0xbcf13c2c,0xbc2c3cf1,0x3cf83bf9,0x3b96bcfd,0xbd00bac9,0xbcac3cbe,0x3cce3c98,0x3c84bcdc,0xbce7bc5b,
 0xbce73c5b,0x3c843cdc,0x3ccebc98,0xbcacbcbe,0xbd003ac9,0x3b963cfd,0x3cf8bbf9,0xbc2cbcf1,0xbcf1bc2c,0xbbf93cf8,0x3cfd3b96,0x3ac9bd00,0xbcbebcac,0xbc983cce,0x3cdc3c84,0x3c5bbce7,
};

template<int SA>
__device__ __forceinline__ void wgmma_main(float (&d)[84], uint64_t da, uint64_t db, int sd) {
  asm volatile("{\n.reg .pred p;\nsetp.ne.b32 p, %86, 0;\n"
    "wgmma.mma_async.sync.aligned.m64n168k16.f32.bf16.bf16 "
    "{%0, %1, %2, %3, %4, %5, %6, %7, %8, %9, %10, %11, %12, %13, %14, %15, %16, %17, %18, %19, %20, %21, %22, %23, %24, %25, %26, %27, %28, %29, %30, %31, %32, %33, %34, %35, %36, %37, %38, %39, %40, %41, %42, %43, %44, %45, %46, %47, %48, %49, %50, %51, %52, %53, %54, %55, %56, %57, %58, %59, %60, %61, %62, %63, %64, %65, %66, %67, %68, %69, %70, %71, %72, %73, %74, %75, %76, %77, %78, %79, %80, %81, %82, %83}, %84, %85, p, %87, 1, 1, 0;\n}\n"
    : "+f"(d[0]), "+f"(d[1]), "+f"(d[2]), "+f"(d[3]), "+f"(d[4]), "+f"(d[5]), "+f"(d[6]), "+f"(d[7]), "+f"(d[8]), "+f"(d[9]), "+f"(d[10]), "+f"(d[11]), "+f"(d[12]), "+f"(d[13]), "+f"(d[14]), "+f"(d[15]), "+f"(d[16]), "+f"(d[17]), "+f"(d[18]), "+f"(d[19]), "+f"(d[20]), "+f"(d[21]), "+f"(d[22]), "+f"(d[23]), "+f"(d[24]), "+f"(d[25]), "+f"(d[26]), "+f"(d[27]), "+f"(d[28]), "+f"(d[29]), "+f"(d[30]), "+f"(d[31]), "+f"(d[32]), "+f"(d[33]), "+f"(d[34]), "+f"(d[35]), "+f"(d[36]), "+f"(d[37]), "+f"(d[38]), "+f"(d[39]), "+f"(d[40]), "+f"(d[41]), "+f"(d[42]), "+f"(d[43]), "+f"(d[44]), "+f"(d[45]), "+f"(d[46]), "+f"(d[47]), "+f"(d[48]), "+f"(d[49]), "+f"(d[50]), "+f"(d[51]), "+f"(d[52]), "+f"(d[53]), "+f"(d[54]), "+f"(d[55]), "+f"(d[56]), "+f"(d[57]), "+f"(d[58]), "+f"(d[59]), "+f"(d[60]), "+f"(d[61]), "+f"(d[62]), "+f"(d[63]), "+f"(d[64]), "+f"(d[65]), "+f"(d[66]), "+f"(d[67]), "+f"(d[68]), "+f"(d[69]), "+f"(d[70]), "+f"(d[71]), "+f"(d[72]), "+f"(d[73]), "+f"(d[74]), "+f"(d[75]), "+f"(d[76]), "+f"(d[77]), "+f"(d[78]), "+f"(d[79]), "+f"(d[80]), "+f"(d[81]), "+f"(d[82]), "+f"(d[83])
    : "l"(da), "l"(db), "r"(sd), "n"(SA));
}
template<int SA>
__device__ __forceinline__ void wgmma_fwd(float (&d)[32], uint64_t da, uint64_t db, int sd) {
  asm volatile("{\n.reg .pred p;\nsetp.ne.b32 p, %34, 0;\n"
    "wgmma.mma_async.sync.aligned.m64n64k16.f32.bf16.bf16 "
    "{%0, %1, %2, %3, %4, %5, %6, %7, %8, %9, %10, %11, %12, %13, %14, %15, %16, %17, %18, %19, %20, %21, %22, %23, %24, %25, %26, %27, %28, %29, %30, %31}, %32, %33, p, %35, 1, 0, 1;\n}\n"
    : "+f"(d[0]), "+f"(d[1]), "+f"(d[2]), "+f"(d[3]), "+f"(d[4]), "+f"(d[5]), "+f"(d[6]), "+f"(d[7]), "+f"(d[8]), "+f"(d[9]), "+f"(d[10]), "+f"(d[11]), "+f"(d[12]), "+f"(d[13]), "+f"(d[14]), "+f"(d[15]), "+f"(d[16]), "+f"(d[17]), "+f"(d[18]), "+f"(d[19]), "+f"(d[20]), "+f"(d[21]), "+f"(d[22]), "+f"(d[23]), "+f"(d[24]), "+f"(d[25]), "+f"(d[26]), "+f"(d[27]), "+f"(d[28]), "+f"(d[29]), "+f"(d[30]), "+f"(d[31])
    : "l"(da), "l"(db), "r"(sd), "n"(SA));
}
template<int SA>
__device__ __forceinline__ void wgmma_inv(float (&d)[24], uint64_t da, uint64_t db, int sd) {
  asm volatile("{\n.reg .pred p;\nsetp.ne.b32 p, %26, 0;\n"
    "wgmma.mma_async.sync.aligned.m64n48k16.f32.bf16.bf16 "
    "{%0, %1, %2, %3, %4, %5, %6, %7, %8, %9, %10, %11, %12, %13, %14, %15, %16, %17, %18, %19, %20, %21, %22, %23}, %24, %25, p, %27, 1, 1, 0;\n}\n"
    : "+f"(d[0]), "+f"(d[1]), "+f"(d[2]), "+f"(d[3]), "+f"(d[4]), "+f"(d[5]), "+f"(d[6]), "+f"(d[7]), "+f"(d[8]), "+f"(d[9]), "+f"(d[10]), "+f"(d[11]), "+f"(d[12]), "+f"(d[13]), "+f"(d[14]), "+f"(d[15]), "+f"(d[16]), "+f"(d[17]), "+f"(d[18]), "+f"(d[19]), "+f"(d[20]), "+f"(d[21]), "+f"(d[22]), "+f"(d[23])
    : "l"(da), "l"(db), "r"(sd), "n"(SA));
}

__device__ __forceinline__ uint32_t s2u(const void* p) { return (uint32_t)__cvta_generic_to_shared(p); }
__device__ __forceinline__ void mbar_init(uint32_t a, int c) { asm volatile("mbarrier.init.shared::cta.b64 [%0], %1;" ::"r"(a), "r"(c)); }
__device__ __forceinline__ void mbar_expect(uint32_t a, int b) { asm volatile("mbarrier.arrive.expect_tx.shared::cta.b64 _, [%0], %1;" ::"r"(a), "r"(b) : "memory"); }
__device__ __forceinline__ void mbar_arrive(uint32_t a) { asm volatile("mbarrier.arrive.shared::cta.b64 _, [%0];" ::"r"(a) : "memory"); }
__device__ __forceinline__ void mbar_arrive_cluster(uint32_t a, uint32_t cta, uint32_t cnt) {
  asm volatile("{\n.reg .b32 r;\nmapa.shared::cluster.u32 r, %0, %1;\nmbarrier.arrive.shared::cluster.b64 _, [r], %2;\n}" ::"r"(a), "r"(cta), "r"(cnt) : "memory");
}
__device__ __forceinline__ void mbar_wait(uint32_t a, int ph) {
  asm volatile("{\n.reg .pred p;\n.reg .u32 c;\nmov.u32 c, 0;\nWAIT:\n"
               "mbarrier.try_wait.parity.shared::cta.b64 p, [%0], %1;\n@p bra DONE;\n"
               "add.u32 c, c, 1;\nsetp.lt.u32 p, c, 0x400000;\n@p bra WAIT;\ntrap;\nDONE:\n}" ::"r"(a), "r"(ph) : "memory");
}
__device__ __forceinline__ void flag_wait(const unsigned* p, unsigned target) {
  asm volatile("{\n.reg .pred p;\n.reg .u32 c, v;\nmov.u32 c, 0;\nWAIT:\n"
               "ld.acquire.gpu.global.u32 v, [%0];\nsetp.ge.u32 p, v, %1;\n@p bra DONE;\n"
               "add.u32 c, c, 1;\nsetp.lt.u32 p, c, 0x400000;\n@p bra WAIT;\ntrap;\nDONE:\n}" ::"l"(p), "r"(target) : "memory");
}
__device__ __forceinline__ void flag_add(unsigned* p) { asm volatile("red.release.gpu.global.add.u32 [%0], 1;" ::"l"(p) : "memory"); }
__device__ __forceinline__ bool elect_one() {
  uint32_t p;
  asm volatile("{\n.reg .pred P;\nelect.sync _|P, 0xffffffff;\nselp.u32 %0, 1, 0, P;\n}" : "=r"(p));
  return p != 0;
}
__device__ __forceinline__ void bulk_ld(uint32_t dst, const void* src, int bytes, uint32_t bar) {
  asm volatile("cp.async.bulk.shared::cluster.global.mbarrier::complete_tx::bytes [%0], [%1], %2, [%3];" ::"r"(dst), "l"(src), "r"(bytes), "r"(bar) : "memory");
}
__device__ __forceinline__ void bulk_ld_mc(uint32_t dst, const void* src, int bytes, uint32_t bar, uint16_t mask) {
  asm volatile("cp.async.bulk.shared::cluster.global.mbarrier::complete_tx::bytes.multicast::cluster [%0], [%1], %2, [%3], %4;" ::"r"(dst), "l"(src), "r"(bytes), "r"(bar), "h"(mask) : "memory");
}
__device__ __forceinline__ void tma_ld2(uint32_t dst, const CUtensorMap* tm, int c0, int c1, uint32_t bar) {
  asm volatile("cp.async.bulk.tensor.2d.shared::cluster.global.mbarrier::complete_tx::bytes [%0], [%1, {%3,%4}], [%2];" ::"r"(dst), "l"(tm), "r"(bar), "r"(c0), "r"(c1) : "memory");
}
__device__ __forceinline__ void tma_ld3(uint32_t dst, const CUtensorMap* tm, int c0, int c1, int c2, uint32_t bar) {
  asm volatile("cp.async.bulk.tensor.3d.shared::cluster.global.mbarrier::complete_tx::bytes [%0], [%1, {%3,%4,%5}], [%2];" ::"r"(dst), "l"(tm), "r"(bar), "r"(c0), "r"(c1), "r"(c2) : "memory");
}
__device__ __forceinline__ void tma_pf3(const CUtensorMap* tm, int c0, int c1, int c2) {
  asm volatile("cp.async.bulk.prefetch.tensor.3d.L2.global [%0, {%1,%2,%3}];" ::"l"(tm), "r"(c0), "r"(c1), "r"(c2) : "memory");
}
__device__ __forceinline__ void tma_st3(const CUtensorMap* tm, uint32_t src, int c0, int c1, int c2) {
  asm volatile("cp.async.bulk.tensor.3d.global.shared::cta.bulk_group [%0, {%2,%3,%4}], [%1];" ::"l"(tm), "r"(src), "r"(c0), "r"(c1), "r"(c2) : "memory");
}
__device__ __forceinline__ void tma_st4(const CUtensorMap* tm, uint32_t src, int c0, int c1, int c2, int c3) {
  asm volatile("cp.async.bulk.tensor.4d.global.shared::cta.bulk_group [%0, {%2,%3,%4,%5}], [%1];" ::"l"(tm), "r"(src), "r"(c0), "r"(c1), "r"(c2), "r"(c3) : "memory");
}
__device__ __forceinline__ void bulk_commit() { asm volatile("cp.async.bulk.commit_group;" ::: "memory"); }
template <int N> __device__ __forceinline__ void bulk_wait_read() { asm volatile("cp.async.bulk.wait_group.read %0;" ::"n"(N) : "memory"); }
template <int N> __device__ __forceinline__ void bulk_wait() { asm volatile("cp.async.bulk.wait_group %0;" ::"n"(N) : "memory"); }
__device__ __forceinline__ void fence_async_smem() { asm volatile("fence.proxy.async.shared::cta;" ::: "memory"); }
__device__ __forceinline__ void wg_fence() { asm volatile("wgmma.fence.sync.aligned;" ::: "memory"); }
__device__ __forceinline__ void wg_commit() { asm volatile("wgmma.commit_group.sync.aligned;" ::: "memory"); }
template <int N> __device__ __forceinline__ void wg_wait() { asm volatile("wgmma.wait_group.sync.aligned %0;" ::"n"(N) : "memory"); }
template <int R> __device__ __forceinline__ void fence_regs(float (&d)[R]) {
#pragma unroll
  for (int i = 0; i < R; i++) asm volatile("" : "+f"(d[i])::"memory");
}
__device__ __forceinline__ uint64_t mk_desc(uint32_t addr) {
  return (uint64_t)((addr & 0x3FFFF) >> 4) | (1ull << 16) | (64ull << 32) | (1ull << 62);
}
__device__ __forceinline__ uint32_t pack2(float lo, float hi) {
  uint32_t r;
  asm("cvt.rn.bf16x2.f32 %0, %1, %2;" : "=r"(r) : "f"(hi), "f"(lo));
  return r;
}
__device__ __forceinline__ void stsm4(uint32_t ad, uint32_t a, uint32_t b, uint32_t c, uint32_t d) {
  asm volatile("stmatrix.sync.aligned.m8n8.x4.shared.b16 [%0], {%1,%2,%3,%4};" ::"r"(ad), "r"(a), "r"(b), "r"(c), "r"(d) : "memory");
}
__device__ __forceinline__ void stsm4t(uint32_t ad, uint32_t a, uint32_t b, uint32_t c, uint32_t d) {
  asm volatile("stmatrix.sync.aligned.m8n8.x4.trans.shared.b16 [%0], {%1,%2,%3,%4};" ::"r"(ad), "r"(a), "r"(b), "r"(c), "r"(d) : "memory");
}

constexpr int GST = 4;
constexpr int G_STAGE = WBLK + XBLK;
constexpr int NR = 8;
constexpr int OFF_RING = GST * G_STAGE;
constexpr int OFF_F = OFF_RING + NR * 8192;
constexpr int OFF_BAR = OFF_F + 8192;
constexpr int K1_SMEM = OFF_BAR + 512;
constexpr int B_FULL = 0, B_EMPTY = 32, B_RAWF = 64, B_STG = 128, B_RAWE = 192, B_Y = 256, B_F = 272;

struct K1Maps { CUtensorMap x, we, wo, xst, wst, yst; };

__device__ __forceinline__ int chunk_of(int n) { return n < 16 ? n : 31 - n; }
__device__ __forceinline__ int x2_of(int cta, int n) { return (cta + 80 * n) & 127; }

template <bool ISX>
__device__ __forceinline__ void t_issue(float (&t)[32], uint32_t sb, int seq) {
  const int sl = seq & (NR - 1);
  mbar_wait(sb + OFF_BAR + B_RAWF + 8 * sl, (seq >> 3) & 1);
  const uint64_t da = mk_desc(sb + OFF_F), db = mk_desc(sb + OFF_RING + sl * 8192);
  wg_fence();
#pragma unroll
  for (int kk = 0; kk < (ISX ? 4 : 1); kk++) wgmma_fwd<1>(t, da + 2 * kk, db + 128 * kk, kk);
  wg_commit();
}
template <bool ISX>
__device__ __forceinline__ void t_finish(float (&t)[32], uint32_t sb, int seq, int sw, int wg, int w, int lane) {
  const int sl = seq & (NR - 1);
  fence_regs(t);
  asm volatile("bar.sync %0, 128;" ::"r"(1 + wg) : "memory");
  const int m = lane >> 3, r = lane & 7;
  uint32_t ad = sb + OFF_RING + sl * 8192 + (8 * w + r) * 128;
  if (ISX) ad += ((((m & 1) * 4 + (m >> 1)) ^ sw ^ r) << 4);
  else ad += (m & 1) * 4096 + (((m >> 1) ^ sw ^ r) << 4);
#pragma unroll
  for (int i = 0; i < 4; i++) {
    const uint32_t a = ISX ? ((ad ^ ((i & 1) * 32)) + (i >> 1) * 4096) : (ad ^ (i * 32));
    stsm4(a, pack2(t[8 * i], t[8 * i + 1]), pack2(t[8 * i + 2], t[8 * i + 3]), pack2(t[8 * i + 4], t[8 * i + 5]), pack2(t[8 * i + 6], t[8 * i + 7]));
  }
  fence_async_smem();
  __syncwarp();
  if (lane == 0) mbar_arrive(sb + OFF_BAR + B_STG + 8 * sl);
}
__device__ __forceinline__ void main_issue(float (&yr)[84], float (&yi)[84], uint32_t st, int wg, int kk, int sd) {
  const uint64_t wr = mk_desc(st + wg * 8192) + kk * 128, wi = wr + 256;
  const uint64_t xr = mk_desc(st + WBLK) + kk * 2, xi = xr + 4;
  wg_fence();
  wgmma_main<1>(yr, wr, xr, sd);
  wgmma_main<1>(yi, wr, xi, sd);
  wgmma_main<1>(yr, wi, xi, 1);
  wgmma_main<-1>(yi, wi, xr, 1);
  wg_commit();
}

__global__ void __cluster_dims__(2, 1, 1) __launch_bounds__(384, 1)
k1_main(const __grid_constant__ K1Maps tm) {
  extern __shared__ __align__(1024) uint8_t smem_raw[];
  const uint32_t sb = s2u(smem_raw);
  const uint32_t bar = sb + OFF_BAR;
  const int warp = __shfl_sync(0xffffffffu, threadIdx.x >> 5, 0), lane = threadIdx.x & 31;
  const int cta = blockIdx.x;
  const uint32_t rank = cta & 1;
  const int b = (cta >> 1) & 1, u = cta >> 2;
  if (threadIdx.x == 0) {
    PROF_T(0);
    for (int i = 0; i < GST; i++) { mbar_init(bar + B_FULL + 8 * i, 1); mbar_init(bar + B_EMPTY + 8 * i, 4); }
    for (int i = 0; i < NR; i++) { mbar_init(bar + B_RAWF + 8 * i, 1); mbar_init(bar + B_STG + 8 * i, 4); mbar_init(bar + B_RAWE + 8 * i, 1); }
    mbar_init(bar + B_Y, 4);
    mbar_init(bar + B_Y + 8, 4);
    mbar_init(bar + B_F, 1);
    asm volatile("fence.mbarrier_init.release.cluster;" ::: "memory");
  }
  if (cta == 0 && threadIdx.x < 16) g_cnt[threadIdx.x * 32] = 0;
  __syncthreads();
  asm volatile("barrier.cluster.arrive.relaxed.aligned;" ::: "memory");
  asm volatile("griddepcontrol.launch_dependents;" ::: "memory");
  if (warp >= 8) {
    asm volatile("setmaxnreg.dec.sync.aligned.u32 40;");
    if (warp == 9) {
      if (elect_one()) {
        mbar_expect(bar + B_F, 8192);
        bulk_ld(sb + OFF_F, g_Fimg, 8192, bar + B_F);
        int seq = 0;
        for (int n = 0; n < 32; n++) {
          const int c = chunk_of(n);
          const int r2 = x2_of(cta, n);
          const int nit = n < 16 ? (r2 < 80 ? 5 : 4) : 2;
          for (int j = 0; j < nit; j++, seq++) {
            const int sl = seq & (NR - 1);
            const int jj = n < 16 ? j : j + 2;
            const uint32_t dst = sb + OFF_RING + sl * 8192, fb = bar + B_RAWF + 8 * sl;
            mbar_wait(bar + B_RAWE + 8 * sl, ((seq >> 3) & 1) ^ 1);
            if (jj == 2 || jj == 3) {
              const int cp = c * 64 + (cta >> 1);
              const int d64 = (n >> 4) * 4 + (cta & 1) * 2 + (jj - 2);
              mbar_expect(fb, 2048);
              tma_ld3(dst, cp < 512 ? &tm.we : &tm.wo, 0, 0, (cp & 511) * 8 + d64, fb);
            } else {
              const int wi = jj == 4 ? 256 + r2 : 2 * cta + jj;
              const int bb = wi >= NT, t = wi - bb * NT;
              mbar_expect(fb, 8192);
              tma_ld3(dst, &tm.x, c * 64, t * MT, bb, fb);
            }
          }
        }
      }
      __syncwarp();
      asm volatile("barrier.cluster.wait.aligned;" ::: "memory");
    } else if (warp >= 10) {
      if (elect_one()) {
        int seq = 0;
        for (int n = 0; n < 32; n++) {
          const int c = chunk_of(n);
          const int r2 = x2_of(cta, n);
          const int nit = n < 16 ? (r2 < 80 ? 5 : 4) : 2;
          if ((n & 1) != (warp & 1)) { seq += nit; continue; }
          for (int j = 0; j < nit; j++, seq++) {
            const int sl = seq & (NR - 1);
            const int jj = n < 16 ? j : j + 2;
            const uint32_t src = sb + OFF_RING + sl * 8192;
            mbar_wait(bar + B_STG + 8 * sl, (seq >> 3) & 1);
            if (jj == 2 || jj == 3) {
              const int cl = cta >> 1;
              const int row = (n & (WR - 1)) * (WCHUNK / 128) + ((cta & 1) * 2 + (cl >> 5)) * 128 + (jj - 2) * 64 + (cl & 31);
              tma_st4(&tm.wst, src, 0, 0, 0, row);
            } else {
              const int wi = jj == 4 ? 256 + r2 : 2 * cta + jj;
              const int bb = wi >= NT, t = wi - bb * NT;
              tma_st4(&tm.xst, src, 0, 0, 0, (bb * 32 + 2 * c) * NT + t);
            }
            bulk_commit();
            if (j > 0) {
              bulk_wait_read<1>();
              mbar_arrive(bar + B_RAWE + 8 * ((seq - 1) & (NR - 1)));
            }
          }
          bulk_wait_read<0>();
          mbar_arrive(bar + B_RAWE + 8 * ((seq - 1) & (NR - 1)));
          bulk_wait<0>();
          flag_add(&g_flag[n * 32]);
          PROF_T(64 + n);
        }
      }
      __syncwarp();
      asm volatile("barrier.cluster.wait.aligned;" ::: "memory");
    } else {
      asm volatile("barrier.cluster.wait.aligned;" ::: "memory");
      if (elect_one()) {
        int s = 0, ph = 1;
        const uint8_t* xs = g_X + (size_t)((u * 2 + b) * 32) * XBLK + rank * (XBLK / 2);
        const uint8_t* ws = g_W + (size_t)(u * 2 + rank) * 2 * WBLK;
        for (int n = 0; n < 32; n++) {
          const int c = chunk_of(n);
          if (n == 16) {
            for (int i = 0; i < 3; i++) {
              mbar_wait(bar + B_EMPTY + 8 * s, ph);
              mbar_arrive(bar + B_FULL + 8 * s);
              s++;
            }
          }
          flag_wait(&g_flag[n * 32], 128);
          asm volatile("fence.proxy.async.global;" ::: "memory");
          PROF_T(32 + n);
          for (int h = 0; h < 2; h++) {
            mbar_wait(bar + B_EMPTY + 8 * s, ph);
            const uint32_t dst = sb + s * G_STAGE, fb = bar + B_FULL + 8 * s;
            mbar_expect(fb, G_STAGE);
            bulk_ld(dst, ws + (size_t)(n & (WR - 1)) * WCHUNK + h * WBLK, WBLK, fb);
            bulk_ld_mc(dst + WBLK + rank * (XBLK / 2), xs + (size_t)(2 * c + h) * XBLK, XBLK / 2, fb, 3);
            if (++s == GST) { s = 0; ph ^= 1; }
            if (n == 16 && h == 0) {
              for (int g = 0; g < 2; g++) {
                mbar_wait(bar + B_Y + 8 * g, 0);
                tma_st4(&tm.yst, sb + g * 2 * XBLK, 0, 0, 2 * u, b * 8 + rank * 2 + g);
                bulk_commit();
              }
              bulk_wait_read<1>();
              mbar_arrive_cluster(bar + B_EMPTY, 0, 2);
              mbar_arrive_cluster(bar + B_EMPTY, 1, 2);
              bulk_wait_read<0>();
              for (int i = 1; i < 3; i++) {
                mbar_arrive_cluster(bar + B_EMPTY + 8 * i, 0, 2);
                mbar_arrive_cluster(bar + B_EMPTY + 8 * i, 1, 2);
              }
            }
          }
        }
        for (int g = 0; g < 2; g++) {
          mbar_wait(bar + B_Y + 8 * g, 1);
          tma_st4(&tm.yst, sb + g * 2 * XBLK, 0, 0, 2 * u, b * 8 + 4 + rank * 2 + g);
          bulk_commit();
        }
        bulk_wait<0>();
        PROF_T(1);
      }
      __syncwarp();
    }
    asm volatile("barrier.cluster.arrive.relaxed.aligned;\nbarrier.cluster.wait.aligned;" ::: "memory");
  } else {
    asm volatile("setmaxnreg.inc.sync.aligned.u32 232;");
    asm volatile("barrier.cluster.wait.aligned;" ::: "memory");
    const int wg = warp >> 2, w = warp & 3;
    float yr[84], yi[84], t[32];
    const int swx = (2 * cta + wg) & 7, sww = (cta >> 1) & 7;
    int seq = 0;
    mbar_wait(bar + B_F, 0);
#pragma unroll 1
    for (int m = 0; m < LEAD; m++) {
      const int r2 = x2_of(cta, m);
      t_issue<true>(t, sb, seq + wg);
      wg_wait<0>();
      t_finish<true>(t, sb, seq + wg, swx, wg, w, lane);
      t_issue<false>(t, sb, seq + 2 + wg);
      wg_wait<0>();
      t_finish<false>(t, sb, seq + 2 + wg, sww, wg, w, lane);
      if (r2 < 80 && (m & 1) == wg) {
        t_issue<true>(t, sb, seq + 4);
        wg_wait<0>();
        t_finish<true>(t, sb, seq + 4, r2 & 7, wg, w, lane);
      }
      seq += r2 < 80 ? 5 : 4;
    }
    int s = 0, ph = 0;
#pragma unroll 1
    for (int pass = 0; pass < 2; pass++) {
      int sprev = -1;
#pragma unroll 1
      for (int i = 0; i < 16; i++) {
        const int m = pass * 16 + i + LEAD;
        const int r2 = x2_of(cta, m);
        const bool hx = m < 16, hw = m < 32, hx2 = hx && r2 < 80 && (m & 1) == wg;
        const int sw_ = hx ? seq + 2 + wg : seq + wg;
        mbar_wait(bar + B_FULL + 8 * s, ph);
        if (threadIdx.x == 0) PROF_T(96 + pass * 16 + i);
        uint32_t st = sb + s * G_STAGE;
        if (hx) t_issue<true>(t, sb, seq + wg);
        main_issue(yr, yi, st, wg, 0, i != 0);
        wg_wait<1>();
        if (sprev >= 0 && w == 0 && lane < 2) mbar_arrive_cluster(bar + B_EMPTY + 8 * sprev, lane, 1);
        if (hx) t_finish<true>(t, sb, seq + wg, swx, wg, w, lane);
        if (hw) t_issue<false>(t, sb, sw_);
        main_issue(yr, yi, st, wg, 1, 1);
        wg_wait<1>();
        if (hw) t_finish<false>(t, sb, sw_, sww, wg, w, lane);
        sprev = s;
        if (++s == GST) { s = 0; ph ^= 1; }
        mbar_wait(bar + B_FULL + 8 * s, ph);
        st = sb + s * G_STAGE;
        if (hx2) t_issue<true>(t, sb, seq + 4);
        main_issue(yr, yi, st, wg, 0, 1);
        wg_wait<1>();
        if (w == 0 && lane < 2) mbar_arrive_cluster(bar + B_EMPTY + 8 * sprev, lane, 1);
        if (hx2) t_finish<true>(t, sb, seq + 4, r2 & 7, wg, w, lane);
        main_issue(yr, yi, st, wg, 1, 1);
        sprev = s;
        if (++s == GST) { s = 0; ph ^= 1; }
        seq += hx ? (r2 < 80 ? 5 : 4) : 2;
      }
      wg_wait<0>();
      fence_regs(yr);
      fence_regs(yi);
      if (w == 0 && lane < 2) mbar_arrive_cluster(bar + B_EMPTY + 8 * sprev, lane, 1);
      if (pass == 0) {
#pragma unroll 1
        for (int i = 0; i < 3; i++) mbar_wait(bar + B_FULL + 8 * (s++), ph);
      } else {
        asm volatile("bar.sync 3, 256;" ::: "memory");
      }
      const int m = lane >> 3, r = lane & 7;
      const uint32_t ad = sb + wg * 2 * XBLK + (m >> 1) * XBLK + r * 128 + (((2 * w + (m & 1)) ^ r) << 4);
#pragma unroll
      for (int j = 0; j < 21; j++)
        stsm4t(ad + j * 1024, pack2(yr[4 * j], yr[4 * j + 1]), pack2(yr[4 * j + 2], yr[4 * j + 3]), pack2(yi[4 * j], yi[4 * j + 1]),
               pack2(yi[4 * j + 2], yi[4 * j + 3]));
      fence_async_smem();
      __syncwarp();
      if (lane == 0) mbar_arrive(bar + B_Y + 8 * wg);
      if (threadIdx.x == 0) PROF_T(2 + pass);
    }
    asm volatile("barrier.cluster.arrive.relaxed.aligned;\nbarrier.cluster.wait.aligned;" ::: "memory");
  }
}

constexpr int K2_TILES = 21;
constexpr int K2_OFF_G = K2_TILES * 8192;
constexpr int K2_OFF_RED = K2_OFF_G + 6144;
constexpr int K2_OFF_PAR = K2_OFF_RED + 2048;
constexpr int K2_OFF_BAR = K2_OFF_PAR + 512;
constexpr int K2_SMEM = K2_OFF_BAR + 128;

struct K2Maps { CUtensorMap yld, out; };

__device__ __forceinline__ void inv_issue(float (&acc)[24], uint32_t sb, int tl) {
  const uint64_t da = mk_desc(sb + tl * 8192), db = mk_desc(sb + K2_OFF_G);
#pragma unroll
  for (int kk = 0; kk < 4; kk++) wgmma_inv<1>(acc, da + 128 * kk, db + 2 * kk, kk);
}

__global__ void __launch_bounds__(512, 1)
k2_tail(const __grid_constant__ K2Maps tm, const __nv_bfloat16* __restrict__ gamma, const __nv_bfloat16* __restrict__ beta) {
  extern __shared__ __align__(1024) uint8_t smem_raw[];
  const uint32_t sb = s2u(smem_raw);
  float* s_red = (float*)(smem_raw + K2_OFF_RED);
  float* s_par = (float*)(smem_raw + K2_OFF_PAR);
  const uint32_t full = sb + K2_OFF_BAR;
  const int warp = __shfl_sync(0xffffffffu, threadIdx.x >> 5, 0), lane = threadIdx.x & 31;
  const int grp = blockIdx.x >> 3, tr = blockIdx.x & 7;
  const int b = grp >> 3, d64 = grp & 7;
  const int t0 = tr * K2_TILES;
  if (threadIdx.x == 0) {
    for (int i = 0; i < 8; i++) mbar_init(full + 8 * i, 1);
    asm volatile("fence.mbarrier_init.release.cluster;" ::: "memory");
  }
  __syncthreads();
  if (warp == 7 && elect_one()) {
    mbar_expect(full + 56, 6144);
    bulk_ld(sb + K2_OFF_G, g_Gimg, 6144, full + 56);
  }
  float gam = 0.f, bet = 0.f;
  if (threadIdx.x < 64) {
    gam = __bfloat162float(gamma[d64 * 64 + threadIdx.x]);
    bet = __bfloat162float(beta[d64 * 64 + threadIdx.x]);
  }
  asm volatile("griddepcontrol.wait;" ::: "memory");
  if (threadIdx.x == 0) PROF_T(4);
  if (warp < 7 && elect_one()) {
    mbar_expect(full + 8 * warp, 3 * 8192);
    tma_ld2(sb + warp * 3 * 8192, &tm.yld, 0, (grp * NT + t0 + warp * 3) * 64, full + 8 * warp);
  }
  if (blockIdx.x == 0 && warp == 8) g_flag[lane * 32] = 0;
  const int wg = warp >> 2, w = warp & 3, a = lane & 3;
  float acc[24];
  float s1[2] = {0.f, 0.f}, s2[2] = {0.f, 0.f};
  mbar_wait(full + 56, 0);
#pragma unroll 1
  for (int tl = wg; tl < K2_TILES; tl += 4) {
    mbar_wait(full + 8 * (tl / 3), 0);
    wg_fence();
    inv_issue(acc, sb, tl);
    wg_commit();
    wg_wait<0>();
    fence_regs(acc);
    const int nv = LOUT - (t0 + tl) * MT - 2 * a;
    if (nv < 48) {
#pragma unroll
      for (int i = 0; i < 24; i++)
        if (8 * (i >> 2) + (i & 1) >= nv) acc[i] = 0.f;
    }
#pragma unroll
    for (int i = 0; i < 24; i++) {
      s1[(i >> 1) & 1] += acc[i];
      s2[(i >> 1) & 1] = fmaf(acc[i], acc[i], s2[(i >> 1) & 1]);
    }
  }
#pragma unroll
  for (int i = 0; i < 2; i++) {
#pragma unroll
    for (int o = 1; o < 4; o <<= 1) {
      s1[i] += __shfl_xor_sync(0xffffffffu, s1[i], o);
      s2[i] += __shfl_xor_sync(0xffffffffu, s2[i], o);
    }
  }
  const int d0 = 16 * w + (lane >> 2);
  if (a == 0) {
    s_red[wg * 128 + d0] = s1[0];
    s_red[wg * 128 + d0 + 8] = s1[1];
    s_red[wg * 128 + 64 + d0] = s2[0];
    s_red[wg * 128 + 64 + d0 + 8] = s2[1];
  }
  __syncthreads();
  if (threadIdx.x == 0) PROF_T(5);
  if (threadIdx.x < 128) {
    const float tsum = (s_red[threadIdx.x] + s_red[128 + threadIdx.x]) + (s_red[256 + threadIdx.x] + s_red[384 + threadIdx.x]);
    __stcg(&g_part[(grp * 8 + tr) * 128 + threadIdx.x], tsum);
    asm volatile("bar.sync 1, 128;" ::: "memory");
    if (threadIdx.x == 0) {
      flag_add(&g_cnt[grp * 32]);
      flag_wait(&g_cnt[grp * 32], 8);
    }
    asm volatile("bar.sync 1, 128;" ::: "memory");
    if (threadIdx.x < 64) {
      float a1 = 0.f, a2 = 0.f;
#pragma unroll
      for (int i = 0; i < 8; i++) {
        a1 += __ldcg(&g_part[(grp * 8 + i) * 128 + threadIdx.x]);
        a2 += __ldcg(&g_part[(grp * 8 + i) * 128 + 64 + threadIdx.x]);
      }
      const float mu = a1 * (1.f / LOUT);
      const float var = fmaxf(a2 * (1.f / LOUT) - mu * mu, 0.f);
      const float g = gam / sqrtf(var + 1e-5f);
      s_par[threadIdx.x] = g;
      s_par[64 + threadIdx.x] = bet - mu * g;
    }
  }
  __syncthreads();
  if (threadIdx.x == 0) PROF_T(6);
  s1[0] = s_par[d0]; s1[1] = s_par[d0 + 8];
  s2[0] = s_par[64 + d0]; s2[1] = s_par[64 + d0 + 8];
  const int m = lane >> 3, r = lane & 7;
  const uint32_t ad = sb + ((m >> 1) * 8 + r) * 128 + (((2 * w + (m & 1)) ^ r) << 4);
#pragma unroll 1
  for (int tl = wg; tl < K2_TILES; tl += 4) {
    if ((t0 + tl) * MT >= LOUT) break;
    wg_fence();
    inv_issue(acc, sb, tl);
    wg_commit();
    wg_wait<0>();
    fence_regs(acc);
#pragma unroll
    for (int i = 0; i < 24; i++) {
      const float z = fmaf(acc[i], s1[(i >> 1) & 1], s2[(i >> 1) & 1]);
      const float in = z * fmaf(z * z, 0.044715f * 0.7978845608028654f, 0.7978845608028654f);
      float th;
      asm("tanh.approx.f32 %0, %1;" : "=f"(th) : "f"(in));
      const float hz = 0.5f * z;
      acc[i] = fmaf(hz, th, hz);
    }
    asm volatile("bar.sync %0, 128;" ::"r"(2 + wg) : "memory");
#pragma unroll
    for (int jj = 0; jj < 3; jj++) {
      const float* c = acc + 8 * jj;
      stsm4t(ad + tl * 8192 + jj * 2048, pack2(c[0], c[1]), pack2(c[2], c[3]), pack2(c[4], c[5]), pack2(c[6], c[7]));
    }
    fence_async_smem();
    asm volatile("bar.sync %0, 128;" ::"r"(2 + wg) : "memory");
    if (w == 0 && elect_one()) {
      tma_st3(&tm.out, sb + tl * 8192, d64 * 64, (t0 + tl) * MT, b);
      bulk_commit();
    }
  }
  if (w == 0) bulk_wait_read<0>();
  if (threadIdx.x == 0) PROF_T(7);
}

typedef CUresult (*EncFn)(CUtensorMap*, CUtensorMapDataType, cuuint32_t, void*, const cuuint64_t*, const cuuint64_t*, const cuuint32_t*,
                          const cuuint32_t*, CUtensorMapInterleave, CUtensorMapSwizzle, CUtensorMapL2promotion, CUtensorMapFloatOOBfill);

void encode(EncFn fn, CUtensorMap* m, int rank, void* base, const cuuint64_t* dims, const cuuint64_t* strides, const cuuint32_t* box,
            CUtensorMapL2promotion promo) {
  cuuint32_t es[5] = {1, 1, 1, 1, 1};
  fn(m, CU_TENSOR_MAP_DATA_TYPE_BFLOAT16, rank, base, dims, strides, box, es, CU_TENSOR_MAP_INTERLEAVE_NONE, CU_TENSOR_MAP_SWIZZLE_128B, promo,
     CU_TENSOR_MAP_FLOAT_OOB_FILL_NONE);
}

}

extern "C" void kernel_launch(void* const* d_in, const int* in_sizes, int n_in, void* d_out, int out_size) {
  (void)in_sizes; (void)n_in; (void)out_size;
  const __nv_bfloat16* x = (const __nv_bfloat16*)d_in[0];
  const __nv_bfloat16* w = (const __nv_bfloat16*)d_in[1];
  const __nv_bfloat16* gamma = (const __nv_bfloat16*)d_in[2];
  const __nv_bfloat16* beta = (const __nv_bfloat16*)d_in[3];
  void* fnp = nullptr;
  cudaDriverEntryPointQueryResult qr;
  cudaGetDriverEntryPoint("cuTensorMapEncodeTiled", &fnp, cudaEnableDefault, &qr);
  EncFn fn = (EncFn)fnp;
  void *xptr = nullptr, *wptr = nullptr, *yptr = nullptr;
  cudaGetSymbolAddress(&xptr, g_X);
  cudaGetSymbolAddress(&wptr, g_W);
  cudaGetSymbolAddress(&yptr, g_Y);
  K1Maps m1;
  K2Maps m2;
  {
    cuuint64_t d[3] = {1024, 8000, 2}, s[2] = {2048, 8000ull * 2048};
    cuuint32_t bx[3] = {64, 64, 1};
    encode(fn, &m1.x, 3, (void*)x, d, s, bx, CU_TENSOR_MAP_L2_PROMOTION_L2_256B);
  }
  for (int ph = 0; ph < 2; ph++) {
    cuuint64_t d[3] = {64, (cuuint64_t)(16 - ph), 4096}, s[2] = {2ull * 262144 * 2, 128};
    cuuint32_t bx[3] = {64, 16, 1};
    encode(fn, ph ? &m1.wo : &m1.we, 3, (void*)(w + (size_t)ph * 262144), d, s, bx, CU_TENSOR_MAP_L2_PROMOTION_L2_256B);
  }
  {
    cuuint64_t d[4] = {64, 32, 2, 64 * NT}, s[3] = {64ull * XBLK, XBLK, 128};
    cuuint32_t bx[4] = {64, 32, 2, 1};
    encode(fn, &m1.xst, 4, xptr, d, s, bx, CU_TENSOR_MAP_L2_PROMOTION_NONE);
  }
  {
    cuuint64_t d[4] = {64, 32, 2, (cuuint64_t)WR * WCHUNK / 128}, s[3] = {4ull * WBLK, 4096, 128};
    cuuint32_t bx[4] = {64, 32, 2, 1};
    encode(fn, &m1.wst, 4, wptr, d, s, bx, CU_TENSOR_MAP_L2_PROMOTION_NONE);
  }
  {
    cuuint64_t d[4] = {64, NT, 64, 16}, s[3] = {8192, 128, (cuuint64_t)NT * 8192};
    cuuint32_t bx[4] = {64, NT, 2, 1};
    encode(fn, &m1.yst, 4, yptr, d, s, bx, CU_TENSOR_MAP_L2_PROMOTION_NONE);
  }
  {
    cuuint64_t d[2] = {64, 16ull * NT * 64}, s[1] = {128};
    cuuint32_t bx[2] = {64, 192};
    encode(fn, &m2.yld, 2, yptr, d, s, bx, CU_TENSOR_MAP_L2_PROMOTION_L2_256B);
  }
  {
    cuuint64_t d[3] = {512, LOUT, 2}, s[2] = {1024, (cuuint64_t)LOUT * 1024};
    cuuint32_t bx[3] = {64, MT, 1};
    encode(fn, &m2.out, 3, d_out, d, s, bx, CU_TENSOR_MAP_L2_PROMOTION_NONE);
  }
  cudaFuncSetAttribute(k1_main, cudaFuncAttributeMaxDynamicSharedMemorySize, K1_SMEM);
  cudaFuncSetAttribute(k2_tail, cudaFuncAttributeMaxDynamicSharedMemorySize, K2_SMEM);
  k1_main<<<128, 384, K1_SMEM>>>(m1);
  cudaLaunchConfig_t cfg = {};
  cfg.gridDim = dim3(128);
  cfg.blockDim = dim3(512);
  cfg.dynamicSmemBytes = K2_SMEM;
  cfg.stream = cudaStreamPerThread;
  cudaLaunchAttribute at[1];
  at[0].id = cudaLaunchAttributeProgrammaticStreamSerialization;
  at[0].val.programmaticStreamSerializationAllowed = 1;
  cfg.attrs = at;
  cfg.numAttrs = 1;
  cudaLaunchKernelEx(&cfg, k2_tail, m2, gamma, beta);
}
```

```cpp
#include <cuda_runtime.h>
#include <cuda_bf16.h>
#include <cuda.h>
#include <stdint.h>

namespace {

constexpr int LOUT = 7985;
constexpr int MT = 48;
constexpr int NT = 168;
constexpr int XBLK = NT * 128;
constexpr int WBLK = 16384;
#define LEAD_ 3
#define WR_ 8
constexpr int LEAD = LEAD_;
constexpr int WR = WR_;
constexpr int WCHUNK = 32 * 4 * WBLK;

__device__ __align__(1024) uint8_t g_X[32ull * 2 * 32 * XBLK];
__device__ __align__(1024) uint8_t g_W[(size_t)WR * WCHUNK];
__device__ __align__(1024) uint8_t g_Y[16ull * NT * 8192];
__device__ float g_part[16 * 8 * 128];
__device__ unsigned g_cnt[16 * 32];
__device__ unsigned g_flag[32 * 32];
#define PROF_T(i)

__device__ __align__(128) const uint32_t g_Fimg[2048] = {
 0x3f803f80,0x3f7d3f7f,0x3f783f7b,0x3f713f75,0x3f673f6d,0x3f5c3f62,0x3f4e3f55,0x3f3e3f46,0x3f2c3f35,0x3f183f22,0x3f043f0e,0x3edb3ef1,0x3eac3ec4,0x3e793e95,0x3e163e48,0x3d493dc9,
 0xbd490000,0xbe16bdc9,0xbe79be48,0xbeacbe95,0xbedbbec4,0xbf04bef1,0xbf18bf0e,0xbf2cbf22,0xbf3ebf35,0xbf4ebf46,0xbf5cbf55,0xbf67bf62,0xbf71bf6d,0xbf78bf75,0xbf7dbf7b,0xbf80bf7f,
 0x3e793ec4,0xbd493dc9,0xbeacbe48,0xbf18bef1,0x3f7d3f80,0x3f673f75,0x3f3e3f55,0x3f043f22,0xbf5cbf6d,0xbf2cbf46,0xbedbbf0e,0xbe16be95,0xbf4ebf35,0xbf71bf62,0xbf80bf7b,0xbf78bf7f,
 0x3f783f6d,0x3f803f7f,0x3f713f7b,0x3f4e3f62,0x3e160000,0x3edb3e95,0x3f2c3f0e,0x3f5c3f46,0xbf04bec4,0xbf3ebf22,0xbf67bf55,0xbf7dbf75,0x3f183f35,0x3eac3ef1,0x3d493e48,0xbe79bdc9,
 0xbf04bf35,0xbd49be95,0x3edb3e48,0x3f4e3f22,0x3f7d3f6d,0x3f713f7f,0x3f2c3f55,0x3e793ef1,0x3f783f80,0x3f3e3f62,0x3eac3f0e,0xbe163dc9,0xbf18bec4,0xbf67bf46,0xbf80bf7b,0xbf5cbf75,
 0x3f5c3f35,0x3f803f75,0x3f673f7b,0x3f183f46,0x3e163ec4,0xbeacbdc9,0xbf3ebf0e,0xbf78bf62,0xbe790000,0xbf2cbef1,0xbf71bf55,0xbf7dbf7f,0xbf4ebf6d,0xbedbbf22,0x3d49be48,0x3f043e95,
 0xbf2cbec4,0xbf7dbf62,0xbf5cbf7b,0xbeacbf22,0x3f673f35,0x3f783f7f,0x3f183f55,0xbd493e95,0xbf80bf6d,0xbf4ebf75,0xbe79bf0e,0x3edb3dc9,0x3f713f80,0x3f043f46,0xbe163e48,0xbf3ebef1,
 0x3f3e3f6d,0x3e163ef1,0xbf04be48,0xbf71bf46,0xbedbbf35,0x3e79bdc9,0x3f4e3f0e,0x3f803f75,0x3d493ec4,0xbf18be95,0xbf78bf55,0xbf67bf7f,0x3eac0000,0x3f5c3f22,0x3f7d3f7b,0x3f2c3f62,
 0xbedb0000,0xbf78bf46,0xbf4ebf7b,0xbd49bef1,0x3f3e3ec4,0x3f7d3f75,0x3f043f55,0xbeac3dc9,0xbf71bf35,0xbf5cbf7f,0xbe16bf0e,0x3f2c3e95,0x3f803f6d,0x3f183f62,0xbe793e48,0xbf67bf22,
 0x3f673f80,0x3e793f22,0xbf18be48,0xbf80bf62,0xbf2cbf6d,0x3e16be95,0x3f5c3f0e,0x3f713f7f,0x3eac3f35,0xbf04bdc9,0xbf7dbf55,0xbf3ebf75,0x3d49bec4,0x3f4e3ef1,0x3f783f7b,0x3edb3f46,
 0xbf7dbf6d,0xbeacbf46,0x3f2c3e48,0x3f783f75,0x3f040000,0x3f803f62,0x3edb3f55,0xbf18bdc9,0x3f4e3ec4,0x3f673f7f,0x3d493f0e,0xbf5cbef1,0x3e793f35,0xbf3ebe95,0xbf71bf7b,0xbe16bf22,
 0x3e16bec4,0x3f713f22,0x3f3e3f7b,0xbe793e95,0x3f5c3f80,0xbd493ef1,0xbf67bf0e,0xbf4ebf7f,0x3f183f6d,0xbedb3dc9,0xbf80bf55,0xbf04bf62,0xbf78bf35,0xbf2cbf75,0x3eacbe48,0x3f7d3f46,
 0x3f7d3f35,0x3edb3f62,0xbf3ebe48,0xbf5cbf7f,0x3e79bec4,0x3f803f46,0x3eac3f55,0xbf4ebe95,0xbf180000,0xbf71bf75,0x3d49bf0e,0x3f783f22,0x3f043f6d,0xbf2cbdc9,0xbf67bf7b,0x3e16bef1,
 0xbe16bf35,0x3f673ef1,0x3f2c3f7b,0xbf043dc9,0xbf78bf6d,0xbd49bf22,0x3f713f0e,0x3f183f75,0x3f4e3f80,0xbeac3e95,0xbf80bf55,0xbe79bf46,0x3f5c3ec4,0x3f3e3f7f,0xbedb3e48,0xbf7dbf62,
 0xbedbbf6d,0x3f5c3e95,0x3f183f7b,0xbf3ebdc9,0xbd49bf35,0x3f7d3f22,0x3e793f55,0xbf71bef1,0x3eacbec4,0x3f783f62,0xbe163f0e,0xbf80bf46,0x3f2c0000,0x3f4e3f7f,0xbf043e48,0xbf67bf75,
 0x3f673ec4,0x3f043f75,0xbf4ebe48,0xbf2cbf7f,0x3f803f35,0x3e163f46,0xbf78bf0e,0xbeacbf62,0x3f713f6d,0xbe793ef1,0xbf7dbf55,0x3d49bf22,0x3f3e3f80,0xbf183dc9,0xbf5cbf7b,0x3edbbe95,
 0xbd490000,0xbe16bdc9,0xbe79be48,0xbeacbe95,0xbedbbec4,0xbf04bef1,0xbf18bf0e,0xbf2cbf22,0xbf3ebf35,0xbf4ebf46,0xbf5cbf55,0xbf67bf62,0xbf71bf6d,0xbf78bf75,0xbf7dbf7b,0xbf80bf7f,
 0xbf80bf80,0xbf7dbf7f,0xbf78bf7b,0xbf71bf75,0xbf67bf6d,0xbf5cbf62,0xbf4ebf55,0xbf3ebf46,0xbf2cbf35,0xbf18bf22,0xbf04bf0e,0xbedbbef1,0xbeacbec4,0xbe79be95,0xbe16be48,0xbd49bdc9,
 0xbf78bf6d,0xbf80bf7f,0xbf71bf7b,0xbf4ebf62,0xbe160000,0xbedbbe95,0xbf2cbf0e,0xbf5cbf46,0x3f043ec4,0x3f3e3f22,0x3f673f55,0x3f7d3f75,0xbf18bf35,0xbeacbef1,0xbd49be48,0x3e793dc9,
 0x3e793ec4,0xbd493dc9,0xbeacbe48,0xbf18bef1,0x3f7d3f80,0x3f673f75,0x3f3e3f55,0x3f043f22,0xbf5cbf6d,0xbf2cbf46,0xbedbbf0e,0xbe16be95,0xbf4ebf35,0xbf71bf62,0xbf80bf7b,0xbf78bf7f,
 0x3f5c3f35,0x3f803f75,0x3f673f7b,0x3f183f46,0x3e163ec4,0xbeacbdc9,0xbf3ebf0e,0xbf78bf62,0xbe790000,0xbf2cbef1,0xbf71bf55,0xbf7dbf7f,0xbf4ebf6d,0xbedbbf22,0x3d49be48,0x3f043e95,
 0x3f043f35,0x3d493e95,0xbedbbe48,0xbf4ebf22,0xbf7dbf6d,0xbf71bf7f,0xbf2cbf55,0xbe79bef1,0xbf78bf80,0xbf3ebf62,0xbeacbf0e,0x3e16bdc9,0x3f183ec4,0x3f673f46,0x3f803f7b,0x3f5c3f75,
 0xbf3ebf6d,0xbe16bef1,0x3f043e48,0x3f713f46,0x3edb3f35,0xbe793dc9,0xbf4ebf0e,0xbf80bf75,0xbd49bec4,0x3f183e95,0x3f783f55,0x3f673f7f,0xbeac0000,0xbf5cbf22,0xbf7dbf7b,0xbf2cbf62,
 0xbf2cbec4,0xbf7dbf62,0xbf5cbf7b,0xbeacbf22,0x3f673f35,0x3f783f7f,0x3f183f55,0xbd493e95,0xbf80bf6d,0xbf4ebf75,0xbe79bf0e,0x3edb3dc9,0x3f713f80,0x3f043f46,0xbe163e48,0xbf3ebef1,
 0xbf67bf80,0xbe79bf22,0x3f183e48,0x3f803f62,0x3f2c3f6d,0xbe163e95,0xbf5cbf0e,0xbf71bf7f,0xbeacbf35,0x3f043dc9,0x3f7d3f55,0x3f3e3f75,0xbd493ec4,0xbf4ebef1,0xbf78bf7b,0xbedbbf46,
 0xbedb0000,0xbf78bf46,0xbf4ebf7b,0xbd49bef1,0x3f3e3ec4,0x3f7d3f75,0x3f043f55,0xbeac3dc9,0xbf71bf35,0xbf5cbf7f,0xbe16bf0e,0x3f2c3e95,0x3f803f6d,0x3f183f62,0xbe793e48,0xbf67bf22,
 0x3e16bec4,0x3f713f22,0x3f3e3f7b,0xbe793e95,0x3f5c3f80,0xbd493ef1,0xbf67bf0e,0xbf4ebf7f,0x3f183f6d,0xbedb3dc9,0xbf80bf55,0xbf04bf62,0xbf78bf35,0xbf2cbf75,0x3eacbe48,0x3f7d3f46,
 0x3f7d3f6d,0x3eac3f46,0xbf2cbe48,0xbf78bf75,0xbf040000,0xbf80bf62,0xbedbbf55,0x3f183dc9,0xbf4ebec4,0xbf67bf7f,0xbd49bf0e,0x3f5c3ef1,0xbe79bf35,0x3f3e3e95,0x3f713f7b,0x3e163f22,
 0x3e163f35,0xbf67bef1,0xbf2cbf7b,0x3f04bdc9,0x3f783f6d,0x3d493f22,0xbf71bf0e,0xbf18bf75,0xbf4ebf80,0x3eacbe95,0x3f803f55,0x3e793f46,0xbf5cbec4,0xbf3ebf7f,0x3edbbe48,0x3f7d3f62,
 0x3f7d3f35,0x3edb3f62,0xbf3ebe48,0xbf5cbf7f,0x3e79bec4,0x3f803f46,0x3eac3f55,0xbf4ebe95,0xbf180000,0xbf71bf75,0x3d49bf0e,0x3f783f22,0x3f043f6d,0xbf2cbdc9,0xbf67bf7b,0x3e16bef1,
 0x3f673ec4,0x3f043f75,0xbf4ebe48,0xbf2cbf7f,0x3f803f35,0x3e163f46,0xbf78bf0e,0xbeacbf62,0x3f713f6d,0xbe793ef1,0xbf7dbf55,0x3d49bf22,0x3f3e3f80,0xbf183dc9,0xbf5cbf7b,0x3edbbe95,
 0x3edb3f6d,0xbf5cbe95,0xbf18bf7b,0x3f3e3dc9,0x3d493f35,0xbf7dbf22,0xbe79bf55,0x3f713ef1,0xbeac3ec4,0xbf78bf62,0x3e16bf0e,0x3f803f46,0xbf2c0000,0xbf4ebf7f,0x3f04be48,0x3f673f75,
 0x3f2c3f80,0xbf4ebdc9,0xbf04bf7b,0x3f673e95,0x3eac3f6d,0xbf78bef1,0xbe16bf55,0x3f803f22,0xbd493f35,0xbf7dbf46,0x3e79bf0e,0x3f713f62,0xbedb3ec4,0xbf5cbf75,0x3f18be48,0x3f3e3f7f,
 0xbf3e0000,0xbf18bf7f,0x3f5c3e48,0x3edb3f75,0xbf71bec4,0xbe79bf62,0x3f7d3f0e,0x3d493f46,0xbf80bf35,0x3e16bf22,0x3f783f55,0xbeac3ef1,0xbf67bf6d,0x3f04be95,0x3f4e3f7b,0xbf2c3dc9,
 0xbf043ec4,0xbf2cbf7f,0x3f673e48,0x3e163f62,0x3f183f80,0xbf71be95,0xbd49bf55,0x3f783f46,0xbe79bf6d,0x3f803f22,0xbeac3f0e,0xbf4ebf75,0xbf7dbf35,0x3edbbef1,0x3f3e3f7b,0xbf5cbdc9,
 0x3f5c3f6d,0xbf3e3dc9,0xbedbbf7b,0x3f7d3ef1,0x3f4e0000,0x3eac3f75,0xbf80bf0e,0x3e79bf22,0xbf78bec4,0x3d49bf46,0x3f713f55,0xbf183e95,0xbe163f35,0xbf67bf62,0x3f2cbe48,0x3f043f7f,
 0x3e79bf35,0x3f3e3f75,0xbf71be48,0x3e16bf46,0x3f4e3f6d,0xbf67bdc9,0x3d49bf55,0x3f5c3f62,0x3f043f80,0xbf80bef1,0x3edbbf0e,0x3f183f7f,0xbf7dbec4,0x3eacbf22,0x3f2c3f7b,0xbf78be95,
 0x3f783f35,0xbf2c3e95,0xbeacbf7b,0x3f7d3f22,0xbf183ec4,0xbedbbf7f,0x3f803f0e,0xbf043ef1,0xbf5c0000,0xbd49bf62,0x3f673f55,0xbf4e3dc9,0xbe16bf6d,0x3f713f46,0xbf3e3e48,0xbe79bf75,
 0xbf80bec4,0x3f18bef1,0x3e793f7b,0xbf67bf46,0x3f713f35,0xbf5c3dc9,0x3e16bf55,0x3f2c3f75,0xbf3ebf6d,0x3f7d3e95,0xbf043f0e,0xbeacbf7f,0x3edb3f80,0xbf78bf22,0x3f4ebe48,0xbd493f62,
 0x3d493f6d,0xbf4ebf62,0x3f783e48,0xbedb3f22,0x3eacbf35,0x3f043f7f,0xbf7dbf0e,0x3f3ebe95,0xbf2c3ec4,0xbe16bf75,0x3f5c3f55,0xbf71bdc9,0x3f670000,0xbe793f46,0xbf18bf7b,0x3f803ef1,
 0xbf710000,0x3f04bf22,0x3e163f7b,0xbf3ebf62,0x3f803ec4,0xbf4e3e95,0x3e79bf55,0x3edb3f7f,0xbf67bf35,0x3f783dc9,0xbf183f0e,0xbd49bf75,0x3f2c3f6d,0xbf7dbef1,0x3f5cbe48,0xbeac3f46,
 0x3eac3f80,0xbf5cbf46,0x3f7d3e48,0xbf2c3ef1,0x3d49bf6d,0x3f183f75,0xbf78bf0e,0x3f67bdc9,0xbedb3f35,0xbe79bf7f,0x3f4e3f55,0xbf80be95,0x3f3ebec4,0xbe163f62,0xbf04bf7b,0x3f713f22,
 0xbf18bf6d,0x3f673f22,0xbf80be48,0x3f5cbe95,0x3f780000,0xbf3e3ef1,0x3eacbf55,0x3e163f7f,0x3f7d3ec4,0xbf713dc9,0x3f2cbf0e,0xbe793f62,0xbf043f35,0x3d49bf75,0x3edb3f7b,0xbf4ebf46,
 0x3f4ebec4,0xbedb3f46,0xbd49bf7b,0x3f043f75,0x3e793f80,0xbf2cbf62,0x3f713f0e,0xbf7dbdc9,0xbe163f6d,0xbeacbf7f,0x3f3e3f55,0xbf78bef1,0xbf5cbf35,0x3f803e95,0xbf673e48,0x3f18bf22,
 0x3f4e3f35,0xbf71bef1,0x3f803e48,0xbf783dc9,0x3f5cbec4,0xbf2c3f22,0x3edbbf55,0xbe163f75,0xbf7d0000,0x3f67be95,0xbf3e3f0e,0x3f04bf46,0xbe793f6d,0xbd49bf7f,0x3eac3f7b,0xbf18bf62,
 0x3f18bf35,0xbeac3f62,0x3d49bf7b,0x3e793f7f,0xbf04bf6d,0x3f3e3f46,0xbf67bf0e,0x3f7d3e95,0x3e163f80,0xbedbbf75,0x3f2c3f55,0xbf5cbf22,0x3f783ec4,0xbf80bdc9,0x3f71be48,0xbf4e3ef1,
 0x3eacbf6d,0xbe793f75,0x3e16bf7b,0xbd493f7f,0x3f2cbf35,0xbf183f46,0x3f04bf55,0xbedb3f62,0x3f67bec4,0xbf5c3ef1,0x3f4ebf0e,0xbf3e3f22,0x3f800000,0xbf7d3dc9,0x3f78be48,0xbf713e95,
 0x3f713ec4,0xbf78be95,0x3f7d3e48,0xbf80bdc9,0x3f3e3f35,0xbf4ebf22,0x3f5c3f0e,0xbf67bef1,0x3edb3f6d,0xbf04bf62,0x3f183f55,0xbf2cbf46,0x3d493f80,0xbe16bf7f,0x3e793f7b,0xbeacbf75,
 0xbf3e0000,0xbf18bf7f,0x3f5c3e48,0x3edb3f75,0xbf71bec4,0xbe79bf62,0x3f7d3f0e,0x3d493f46,0xbf80bf35,0x3e16bf22,0x3f783f55,0xbeac3ef1,0xbf67bf6d,0x3f04be95,0x3f4e3f7b,0xbf2c3dc9,
 0xbf2cbf80,0x3f4e3dc9,0x3f043f7b,0xbf67be95,0xbeacbf6d,0x3f783ef1,0x3e163f55,0xbf80bf22,0x3d49bf35,0x3f7d3f46,0xbe793f0e,0xbf71bf62,0x3edbbec4,0x3f5c3f75,0xbf183e48,0xbf3ebf7f,
 0xbf5cbf6d,0x3f3ebdc9,0x3edb3f7b,0xbf7dbef1,0xbf4e0000,0xbeacbf75,0x3f803f0e,0xbe793f22,0x3f783ec4,0xbd493f46,0xbf71bf55,0x3f18be95,0x3e16bf35,0x3f673f62,0xbf2c3e48,0xbf04bf7f,
 0xbf043ec4,0xbf2cbf7f,0x3f673e48,0x3e163f62,0x3f183f80,0xbf71be95,0xbd49bf55,0x3f783f46,0xbe79bf6d,0x3f803f22,0xbeac3f0e,0xbf4ebf75,0xbf7dbf35,0x3edbbef1,0x3f3e3f7b,0xbf5cbdc9,
 0x3f783f35,0xbf2c3e95,0xbeacbf7b,0x3f7d3f22,0xbf183ec4,0xbedbbf7f,0x3f803f0e,0xbf043ef1,0xbf5c0000,0xbd49bf62,0x3f673f55,0xbf4e3dc9,0xbe16bf6d,0x3f713f46,0xbf3e3e48,0xbe79bf75,
 0xbe793f35,0xbf3ebf75,0x3f713e48,0xbe163f46,0xbf4ebf6d,0x3f673dc9,0xbd493f55,0xbf5cbf62,0xbf04bf80,0x3f803ef1,0xbedb3f0e,0xbf18bf7f,0x3f7d3ec4,0xbeac3f22,0xbf2cbf7b,0x3f783e95,
 0xbd49bf6d,0x3f4e3f62,0xbf78be48,0x3edbbf22,0xbeac3f35,0xbf04bf7f,0x3f7d3f0e,0xbf3e3e95,0x3f2cbec4,0x3e163f75,0xbf5cbf55,0x3f713dc9,0xbf670000,0x3e79bf46,0x3f183f7b,0xbf80bef1,
 0xbf80bec4,0x3f18bef1,0x3e793f7b,0xbf67bf46,0x3f713f35,0xbf5c3dc9,0x3e16bf55,0x3f2c3f75,0xbf3ebf6d,0x3f7d3e95,0xbf043f0e,0xbeacbf7f,0x3edb3f80,0xbf78bf22,0x3f4ebe48,0xbd493f62,
 0xbeacbf80,0x3f5c3f46,0xbf7dbe48,0x3f2cbef1,0xbd493f6d,0xbf18bf75,0x3f783f0e,0xbf673dc9,0x3edbbf35,0x3e793f7f,0xbf4ebf55,0x3f803e95,0xbf3e3ec4,0x3e16bf62,0x3f043f7b,0xbf71bf22,
 0xbf710000,0x3f04bf22,0x3e163f7b,0xbf3ebf62,0x3f803ec4,0xbf4e3e95,0x3e79bf55,0x3edb3f7f,0xbf67bf35,0x3f783dc9,0xbf183f0e,0xbd49bf75,0x3f2c3f6d,0xbf7dbef1,0x3f5cbe48,0xbeac3f46,
 0x3f4ebec4,0xbedb3f46,0xbd49bf7b,0x3f043f75,0x3e793f80,0xbf2cbf62,0x3f713f0e,0xbf7dbdc9,0xbe163f6d,0xbeacbf7f,0x3f3e3f55,0xbf78bef1,0xbf5cbf35,0x3f803e95,0xbf673e48,0x3f18bf22,
 0x3f183f6d,0xbf67bf22,0x3f803e48,0xbf5c3e95,0xbf780000,0x3f3ebef1,0xbeac3f55,0xbe16bf7f,0xbf7dbec4,0x3f71bdc9,0xbf2c3f0e,0x3e79bf62,0x3f04bf35,0xbd493f75,0xbedbbf7b,0x3f4e3f46,
 0xbf183f35,0x3eacbf62,0xbd493f7b,0xbe79bf7f,0x3f043f6d,0xbf3ebf46,0x3f673f0e,0xbf7dbe95,0xbe16bf80,0x3edb3f75,0xbf2cbf55,0x3f5c3f22,0xbf78bec4,0x3f803dc9,0xbf713e48,0x3f4ebef1,
 0x3f4e3f35,0xbf71bef1,0x3f803e48,0xbf783dc9,0x3f5cbec4,0xbf2c3f22,0x3edbbf55,0xbe163f75,0xbf7d0000,0x3f67be95,0xbf3e3f0e,0x3f04bf46,0xbe793f6d,0xbd49bf7f,0x3eac3f7b,0xbf18bf62,
 0x3f713ec4,0xbf78be95,0x3f7d3e48,0xbf80bdc9,0x3f3e3f35,0xbf4ebf22,0x3f5c3f0e,0xbf67bef1,0x3edb3f6d,0xbf04bf62,0x3f183f55,0xbf2cbf46,0x3d493f80,0xbe16bf7f,0x3e793f7b,0xbeacbf75,
 0xbeac3f6d,0x3e79bf75,0xbe163f7b,0x3d49bf7f,0xbf2c3f35,0x3f18bf46,0xbf043f55,0x3edbbf62,0xbf673ec4,0x3f5cbef1,0xbf4e3f0e,0x3f3ebf22,0xbf800000,0x3f7dbdc9,0xbf783e48,0x3f71be95,
 0xbd493f80,0x3e16bf7f,0xbe793f7b,0x3eacbf75,0xbedb3f6d,0x3f04bf62,0xbf183f55,0x3f2cbf46,0xbf3e3f35,0x3f4ebf22,0xbf5c3f0e,0x3f67bef1,0xbf713ec4,0x3f78be95,0xbf7d3e48,0x3f80bdc9,
 0xbf800000,0x3f7d3dc9,0xbf78be48,0x3f713e95,0xbf67bec4,0x3f5c3ef1,0xbf4ebf0e,0x3f3e3f22,0xbf2cbf35,0x3f183f46,0xbf04bf55,0x3edb3f62,0xbeacbf6d,0x3e793f75,0xbe16bf7b,0x3d493f7f,
 0xbf783ec4,0x3f80bdc9,0xbf71be48,0x3f4e3ef1,0xbe163f80,0x3edbbf75,0xbf2c3f55,0x3f5cbf22,0x3f04bf6d,0xbf3e3f46,0x3f67bf0e,0xbf7d3e95,0xbf18bf35,0x3eac3f62,0xbd49bf7b,0xbe793f7f,
 0x3e793f6d,0x3d49bf7f,0xbeac3f7b,0x3f18bf62,0x3f7d0000,0xbf67be95,0x3f3e3f0e,0xbf04bf46,0xbf5cbec4,0x3f2c3f22,0xbedbbf55,0x3e163f75,0xbf4e3f35,0x3f71bef1,0xbf803e48,0x3f783dc9,
 0x3f5cbf35,0xbf803e95,0x3f673e48,0xbf18bf22,0x3e163f6d,0x3eacbf7f,0xbf3e3f55,0x3f78bef1,0xbe793f80,0x3f2cbf62,0xbf713f0e,0x3f7dbdc9,0xbf4ebec4,0x3edb3f46,0x3d49bf7b,0xbf043f75,
 0x3f043f35,0xbd49bf75,0xbedb3f7b,0x3f4ebf46,0xbf7d3ec4,0x3f713dc9,0xbf2cbf0e,0x3e793f62,0xbf780000,0x3f3e3ef1,0xbeacbf55,0xbe163f7f,0x3f18bf6d,0xbf673f22,0x3f80be48,0xbf5cbe95,
 0xbf3ebec4,0x3e163f62,0x3f04bf7b,0xbf713f22,0x3edb3f35,0x3e79bf7f,0xbf4e3f55,0x3f80be95,0xbd49bf6d,0xbf183f75,0x3f78bf0e,0xbf67bdc9,0xbeac3f80,0x3f5cbf46,0xbf7d3e48,0x3f2c3ef1,
 0xbf2c3f6d,0x3f7dbef1,0xbf5cbe48,0x3eac3f46,0x3f67bf35,0xbf783dc9,0x3f183f0e,0x3d49bf75,0xbf803ec4,0x3f4e3e95,0xbe79bf55,0xbedb3f7f,0x3f710000,0xbf04bf22,0xbe163f7b,0x3f3ebf62,
 0xbf670000,0x3e793f46,0x3f18bf7b,0xbf803ef1,0x3f2c3ec4,0x3e16bf75,0xbf5c3f55,0x3f71bdc9,0xbeacbf35,0xbf043f7f,0x3f7dbf0e,0xbf3ebe95,0xbd493f6d,0x3f4ebf62,0xbf783e48,0x3edb3f22,
 0xbedb3f80,0x3f78bf22,0xbf4ebe48,0x3d493f62,0x3f3ebf6d,0xbf7d3e95,0x3f043f0e,0x3eacbf7f,0xbf713f35,0x3f5c3dc9,0xbe16bf55,0xbf2c3f75,0x3f80bec4,0xbf18bef1,0xbe793f7b,0x3f67bf46,
 0x3e16bf6d,0xbf713f46,0x3f3e3e48,0x3e79bf75,0x3f5c0000,0x3d49bf62,0xbf673f55,0x3f4e3dc9,0x3f183ec4,0x3edbbf7f,0xbf803f0e,0x3f043ef1,0xbf783f35,0x3f2c3e95,0x3eacbf7b,0xbf7d3f22,
 0x3f7dbec4,0xbeacbf22,0xbf2c3f7b,0x3f78be95,0xbf043f80,0x3f80bef1,0xbedbbf0e,0xbf183f7f,0xbf4e3f6d,0x3f67bdc9,0xbd49bf55,0xbf5c3f62,0xbe79bf35,0xbf3e3f75,0x3f71be48,0xbe16bf46,
 0x3e163f35,0x3f67bf62,0xbf2cbe48,0xbf043f7f,0x3f78bec4,0xbd49bf46,0xbf713f55,0x3f183e95,0xbf4e0000,0xbeac3f75,0x3f80bf0e,0xbe79bf22,0xbf5c3f6d,0x3f3e3dc9,0x3edbbf7b,0xbf7d3ef1,
 0x3f7dbf35,0xbedbbef1,0xbf3e3f7b,0x3f5cbdc9,0x3e79bf6d,0xbf803f22,0x3eac3f0e,0x3f4ebf75,0xbf183f80,0x3f71be95,0x3d49bf55,0xbf783f46,0x3f043ec4,0x3f2cbf7f,0xbf673e48,0xbe163f62,
 0x3f67bf6d,0xbf04be95,0xbf4e3f7b,0x3f2c3dc9,0x3f80bf35,0xbe16bf22,0xbf783f55,0x3eac3ef1,0x3f71bec4,0x3e79bf62,0xbf7d3f0e,0xbd493f46,0x3f3e0000,0x3f18bf7f,0xbf5c3e48,0xbedb3f75,
 0x3edb3ec4,0x3f5cbf75,0xbf18be48,0xbf3e3f7f,0x3d493f35,0x3f7dbf46,0xbe79bf0e,0xbf713f62,0xbeac3f6d,0x3f78bef1,0x3e16bf55,0xbf803f22,0xbf2c3f80,0x3f4ebdc9,0x3f04bf7b,0xbf673e95,
 0xbf800000,0x3f7d3dc9,0xbf78be48,0x3f713e95,0xbf67bec4,0x3f5c3ef1,0xbf4ebf0e,0x3f3e3f22,0xbf2cbf35,0x3f183f46,0xbf04bf55,0x3edb3f62,0xbeacbf6d,0x3e793f75,0xbe16bf7b,0x3d493f7f,
 0x3d49bf80,0xbe163f7f,0x3e79bf7b,0xbeac3f75,0x3edbbf6d,0xbf043f62,0x3f18bf55,0xbf2c3f46,0x3f3ebf35,0xbf4e3f22,0x3f5cbf0e,0xbf673ef1,0x3f71bec4,0xbf783e95,0x3f7dbe48,0xbf803dc9,
 0xbe79bf6d,0xbd493f7f,0x3eacbf7b,0xbf183f62,0xbf7d0000,0x3f673e95,0xbf3ebf0e,0x3f043f46,0x3f5c3ec4,0xbf2cbf22,0x3edb3f55,0xbe16bf75,0x3f4ebf35,0xbf713ef1,0x3f80be48,0xbf78bdc9,
 0xbf783ec4,0x3f80bdc9,0xbf71be48,0x3f4e3ef1,0xbe163f80,0x3edbbf75,0xbf2c3f55,0x3f5cbf22,0x3f04bf6d,0xbf3e3f46,0x3f67bf0e,0xbf7d3e95,0xbf18bf35,0x3eac3f62,0xbd49bf7b,0xbe793f7f,
 0x3f043f35,0xbd49bf75,0xbedb3f7b,0x3f4ebf46,0xbf7d3ec4,0x3f713dc9,0xbf2cbf0e,0x3e793f62,0xbf780000,0x3f3e3ef1,0xbeacbf55,0xbe163f7f,0x3f18bf6d,0xbf673f22,0x3f80be48,0xbf5cbe95,
 0xbf5c3f35,0x3f80be95,0xbf67be48,0x3f183f22,0xbe16bf6d,0xbeac3f7f,0x3f3ebf55,0xbf783ef1,0x3e79bf80,0xbf2c3f62,0x3f71bf0e,0xbf7d3dc9,0x3f4e3ec4,0xbedbbf46,0xbd493f7b,0x3f04bf75,
 0x3f2cbf6d,0xbf7d3ef1,0x3f5c3e48,0xbeacbf46,0xbf673f35,0x3f78bdc9,0xbf18bf0e,0xbd493f75,0x3f80bec4,0xbf4ebe95,0x3e793f55,0x3edbbf7f,0xbf710000,0x3f043f22,0x3e16bf7b,0xbf3e3f62,
 0xbf3ebec4,0x3e163f62,0x3f04bf7b,0xbf713f22,0x3edb3f35,0x3e79bf7f,0xbf4e3f55,0x3f80be95,0xbd49bf6d,0xbf183f75,0x3f78bf0e,0xbf67bdc9,0xbeac3f80,0x3f5cbf46,0xbf7d3e48,0x3f2c3ef1,
 0x3edbbf80,0xbf783f22,0x3f4e3e48,0xbd49bf62,0xbf3e3f6d,0x3f7dbe95,0xbf04bf0e,0xbeac3f7f,0x3f71bf35,0xbf5cbdc9,0x3e163f55,0x3f2cbf75,0xbf803ec4,0x3f183ef1,0x3e79bf7b,0xbf673f46,
 0xbf670000,0x3e793f46,0x3f18bf7b,0xbf803ef1,0x3f2c3ec4,0x3e16bf75,0xbf5c3f55,0x3f71bdc9,0xbeacbf35,0xbf043f7f,0x3f7dbf0e,0xbf3ebe95,0xbd493f6d,0x3f4ebf62,0xbf783e48,0x3edb3f22,
 0x3f7dbec4,0xbeacbf22,0xbf2c3f7b,0x3f78be95,0xbf043f80,0x3f80bef1,0xbedbbf0e,0xbf183f7f,0xbf4e3f6d,0x3f67bdc9,0xbd49bf55,0xbf5c3f62,0xbe79bf35,0xbf3e3f75,0x3f71be48,0xbe16bf46,
 0xbe163f6d,0x3f71bf46,0xbf3ebe48,0xbe793f75,0xbf5c0000,0xbd493f62,0x3f67bf55,0xbf4ebdc9,0xbf18bec4,0xbedb3f7f,0x3f80bf0e,0xbf04bef1,0x3f78bf35,0xbf2cbe95,0xbeac3f7b,0x3f7dbf22,
 0xbf7d3f35,0x3edb3ef1,0x3f3ebf7b,0xbf5c3dc9,0xbe793f6d,0x3f80bf22,0xbeacbf0e,0xbf4e3f75,0x3f18bf80,0xbf713e95,0xbd493f55,0x3f78bf46,0xbf04bec4,0xbf2c3f7f,0x3f67be48,0x3e16bf62,
 0x3e163f35,0x3f67bf62,0xbf2cbe48,0xbf043f7f,0x3f78bec4,0xbd49bf46,0xbf713f55,0x3f183e95,0xbf4e0000,0xbeac3f75,0x3f80bf0e,0xbe79bf22,0xbf5c3f6d,0x3f3e3dc9,0x3edbbf7b,0xbf7d3ef1,
 0x3edb3ec4,0x3f5cbf75,0xbf18be48,0xbf3e3f7f,0x3d493f35,0x3f7dbf46,0xbe79bf0e,0xbf713f62,0xbeac3f6d,0x3f78bef1,0x3e16bf55,0xbf803f22,0xbf2c3f80,0x3f4ebdc9,0x3f04bf7b,0xbf673e95,
 0xbf673f6d,0x3f043e95,0x3f4ebf7b,0xbf2cbdc9,0xbf803f35,0x3e163f22,0x3f78bf55,0xbeacbef1,0xbf713ec4,0xbe793f62,0x3f7dbf0e,0x3d49bf46,0xbf3e0000,0xbf183f7f,0x3f5cbe48,0x3edbbf75,
 0xbf3e3f80,0x3f183dc9,0x3f5cbf7b,0xbedbbe95,0xbf713f6d,0x3e793ef1,0x3f7dbf55,0xbd49bf22,0xbf803f35,0xbe163f46,0x3f78bf0e,0x3eacbf62,0xbf673ec4,0xbf043f75,0x3f4ebe48,0x3f2cbf7f,
 0xbf2c0000,0xbf4e3f7f,0x3f043e48,0x3f67bf75,0xbeacbec4,0xbf783f62,0x3e163f0e,0x3f80bf46,0x3d49bf35,0xbf7d3f22,0xbe793f55,0x3f71bef1,0x3edbbf6d,0xbf5c3e95,0xbf183f7b,0x3f3ebdc9,
 0xbf5c3ec4,0xbf3e3f7f,0x3edb3e48,0x3f7dbf62,0xbf4e3f80,0x3eac3e95,0x3f80bf55,0x3e79bf46,0x3f78bf6d,0x3d49bf22,0xbf713f0e,0xbf183f75,0x3e16bf35,0xbf673ef1,0xbf2c3f7b,0x3f043dc9,
 0xbf043f6d,0x3f2cbdc9,0x3f67bf7b,0xbe16bef1,0x3f180000,0x3f71bf75,0xbd49bf0e,0xbf783f22,0xbe79bec4,0xbf803f46,0xbeac3f55,0x3f4ebe95,0xbf7d3f35,0xbedb3f62,0x3f3ebe48,0x3f5cbf7f,
 0x3f78bf35,0x3f2cbf75,0xbeacbe48,0xbf7d3f46,0xbf183f6d,0x3edb3dc9,0x3f80bf55,0x3f04bf62,0xbf5c3f80,0x3d493ef1,0x3f67bf0e,0x3f4ebf7f,0xbe16bec4,0xbf713f22,0xbf3e3f7b,0x3e793e95,
 0xbe793f35,0x3f3ebe95,0x3f71bf7b,0x3e16bf22,0xbf4e3ec4,0xbf673f7f,0xbd493f0e,0x3f5cbef1,0xbf040000,0xbf803f62,0xbedb3f55,0x3f18bdc9,0x3f7dbf6d,0x3eacbf46,0xbf2c3e48,0xbf783f75,
 0xbd49bec4,0xbf4e3ef1,0xbf783f7b,0xbedb3f46,0xbeac3f35,0x3f04bdc9,0x3f7dbf55,0x3f3ebf75,0x3f2cbf6d,0xbe16be95,0xbf5c3f0e,0xbf713f7f,0xbf673f80,0xbe793f22,0x3f18be48,0x3f80bf62,
 0xbf803f6d,0xbf183f62,0x3e793e48,0x3f67bf22,0x3f71bf35,0x3f5cbf7f,0x3e16bf0e,0xbf2c3e95,0xbf3e3ec4,0xbf7d3f75,0xbf043f55,0x3eac3dc9,0x3edb0000,0x3f78bf46,0x3f4ebf7b,0x3d49bef1,
 0xbeac0000,0xbf5c3f22,0xbf7d3f7b,0xbf2c3f62,0xbd493ec4,0x3f18be95,0x3f78bf55,0x3f67bf7f,0x3edbbf35,0xbe79bdc9,0xbf4e3f0e,0xbf803f75,0xbf3e3f6d,0xbe163ef1,0x3f04be48,0x3f71bf46,
 0xbf713f80,0xbf043f46,0x3e163e48,0x3f3ebef1,0x3f80bf6d,0x3f4ebf75,0x3e79bf0e,0xbedb3dc9,0xbf673f35,0xbf783f7f,0xbf183f55,0x3d493e95,0x3f2cbec4,0x3f7dbf62,0x3f5cbf7b,0x3eacbf22,
 0x3f4ebf6d,0x3edbbf22,0xbd49be48,0xbf043e95,0x3e790000,0x3f2cbef1,0x3f71bf55,0x3f7dbf7f,0xbe163ec4,0x3eacbdc9,0x3f3ebf0e,0x3f78bf62,0xbf5c3f35,0xbf803f75,0xbf673f7b,0xbf183f46,
 0x3f18bec4,0x3f67bf46,0x3f80bf7b,0x3f5cbf75,0xbf783f80,0xbf3e3f62,0xbeac3f0e,0x3e163dc9,0xbf7d3f6d,0xbf713f7f,0xbf2c3f55,0xbe793ef1,0x3f04bf35,0x3d49be95,0xbedb3e48,0xbf4e3f22,
 0xbf183f35,0xbeac3ef1,0xbd493e48,0x3e79bdc9,0x3f04bec4,0x3f3ebf22,0x3f67bf55,0x3f7dbf75,0xbe160000,0xbedb3e95,0xbf2c3f0e,0xbf5c3f46,0xbf783f6d,0xbf803f7f,0xbf713f7b,0xbf4e3f62,
 0x3f4ebf35,0x3f71bf62,0x3f80bf7b,0x3f78bf7f,0x3f5cbf6d,0x3f2cbf46,0x3edbbf0e,0x3e16be95,0xbf7d3f80,0xbf673f75,0xbf3e3f55,0xbf043f22,0xbe793ec4,0x3d493dc9,0x3eacbe48,0x3f18bef1,
 0x3f71bf6d,0x3f78bf75,0x3f7dbf7b,0x3f80bf7f,0x3f3ebf35,0x3f4ebf46,0x3f5cbf55,0x3f67bf62,0x3edbbec4,0x3f04bef1,0x3f18bf0e,0x3f2cbf22,0x3d490000,0x3e16bdc9,0x3e79be48,0x3eacbe95,
 0xbeac3ec4,0xbe793e95,0xbe163e48,0xbd493dc9,0xbf2c3f35,0xbf183f22,0xbf043f0e,0xbedb3ef1,0xbf673f6d,0xbf5c3f62,0xbf4e3f55,0xbf3e3f46,0xbf803f80,0xbf7d3f7f,0xbf783f7b,0xbf713f75,
 0xbf2c0000,0xbf4e3f7f,0x3f043e48,0x3f67bf75,0xbeacbec4,0xbf783f62,0x3e163f0e,0x3f80bf46,0x3d49bf35,0xbf7d3f22,0xbe793f55,0x3f71bef1,0x3edbbf6d,0xbf5c3e95,0xbf183f7b,0x3f3ebdc9,
 0x3f3ebf80,0xbf18bdc9,0xbf5c3f7b,0x3edb3e95,0x3f71bf6d,0xbe79bef1,0xbf7d3f55,0x3d493f22,0x3f80bf35,0x3e16bf46,0xbf783f0e,0xbeac3f62,0x3f67bec4,0x3f04bf75,0xbf4e3e48,0xbf2c3f7f,
 0x3f04bf6d,0xbf2c3dc9,0xbf673f7b,0x3e163ef1,0xbf180000,0xbf713f75,0x3d493f0e,0x3f78bf22,0x3e793ec4,0x3f80bf46,0x3eacbf55,0xbf4e3e95,0x3f7dbf35,0x3edbbf62,0xbf3e3e48,0xbf5c3f7f,
 0xbf5c3ec4,0xbf3e3f7f,0x3edb3e48,0x3f7dbf62,0xbf4e3f80,0x3eac3e95,0x3f80bf55,0x3e79bf46,0x3f78bf6d,0x3d49bf22,0xbf713f0e,0xbf183f75,0x3e16bf35,0xbf673ef1,0xbf2c3f7b,0x3f043dc9,
 0xbe793f35,0x3f3ebe95,0x3f71bf7b,0x3e16bf22,0xbf4e3ec4,0xbf673f7f,0xbd493f0e,0x3f5cbef1,0xbf040000,0xbf803f62,0xbedb3f55,0x3f18bdc9,0x3f7dbf6d,0x3eacbf46,0xbf2c3e48,0xbf783f75,
 0xbf783f35,0xbf2c3f75,0x3eac3e48,0x3f7dbf46,0x3f18bf6d,0xbedbbdc9,0xbf803f55,0xbf043f62,0x3f5cbf80,0xbd49bef1,0xbf673f0e,0xbf4e3f7f,0x3e163ec4,0x3f71bf22,0x3f3ebf7b,0xbe79be95,
 0x3f80bf6d,0x3f18bf62,0xbe79be48,0xbf673f22,0xbf713f35,0xbf5c3f7f,0xbe163f0e,0x3f2cbe95,0x3f3ebec4,0x3f7dbf75,0x3f04bf55,0xbeacbdc9,0xbedb0000,0xbf783f46,0xbf4e3f7b,0xbd493ef1,
 0xbd49bec4,0xbf4e3ef1,0xbf783f7b,0xbedb3f46,0xbeac3f35,0x3f04bdc9,0x3f7dbf55,0x3f3ebf75,0x3f2cbf6d,0xbe16be95,0xbf5c3f0e,0xbf713f7f,0xbf673f80,0xbe793f22,0x3f18be48,0x3f80bf62,
 0x3f71bf80,0x3f04bf46,0xbe16be48,0xbf3e3ef1,0xbf803f6d,0xbf4e3f75,0xbe793f0e,0x3edbbdc9,0x3f67bf35,0x3f78bf7f,0x3f18bf55,0xbd49be95,0xbf2c3ec4,0xbf7d3f62,0xbf5c3f7b,0xbeac3f22,
 0xbeac0000,0xbf5c3f22,0xbf7d3f7b,0xbf2c3f62,0xbd493ec4,0x3f18be95,0x3f78bf55,0x3f67bf7f,0x3edbbf35,0xbe79bdc9,0xbf4e3f0e,0xbf803f75,0xbf3e3f6d,0xbe163ef1,0x3f04be48,0x3f71bf46,
 0x3f18bec4,0x3f67bf46,0x3f80bf7b,0x3f5cbf75,0xbf783f80,0xbf3e3f62,0xbeac3f0e,0x3e163dc9,0xbf7d3f6d,0xbf713f7f,0xbf2c3f55,0xbe793ef1,0x3f04bf35,0x3d49be95,0xbedb3e48,0xbf4e3f22,
 0xbf4e3f6d,0xbedb3f22,0x3d493e48,0x3f04be95,0xbe790000,0xbf2c3ef1,0xbf713f55,0xbf7d3f7f,0x3e16bec4,0xbeac3dc9,0xbf3e3f0e,0xbf783f62,0x3f5cbf35,0x3f80bf75,0x3f67bf7b,0x3f18bf46,
 0xbf4e3f35,0xbf713f62,0xbf803f7b,0xbf783f7f,0xbf5c3f6d,0xbf2c3f46,0xbedb3f0e,0xbe163e95,0x3f7dbf80,0x3f67bf75,0x3f3ebf55,0x3f04bf22,0x3e79bec4,0xbd49bdc9,0xbeac3e48,0xbf183ef1,
 0xbf183f35,0xbeac3ef1,0xbd493e48,0x3e79bdc9,0x3f04bec4,0x3f3ebf22,0x3f67bf55,0x3f7dbf75,0xbe160000,0xbedb3e95,0xbf2c3f0e,0xbf5c3f46,0xbf783f6d,0xbf803f7f,0xbf713f7b,0xbf4e3f62,
 0xbeac3ec4,0xbe793e95,0xbe163e48,0xbd493dc9,0xbf2c3f35,0xbf183f22,0xbf043f0e,0xbedb3ef1,0xbf673f6d,0xbf5c3f62,0xbf4e3f55,0xbf3e3f46,0xbf803f80,0xbf7d3f7f,0xbf783f7b,0xbf713f75,
 0xbf713f6d,0xbf783f75,0xbf7d3f7b,0xbf803f7f,0xbf3e3f35,0xbf4e3f46,0xbf5c3f55,0xbf673f62,0xbedb3ec4,0xbf043ef1,0xbf183f0e,0xbf2c3f22,0xbd490000,0xbe163dc9,0xbe793e48,0xbeac3e95,
};
__device__ __align__(128) const uint32_t g_Gimg[1536] = {
 0x00003d00,0x00003d00,0x00003d00,0x00003d00,0x00003d00,0x00003d00,0x00003d00,0x00003d00,0x00003d00,0x00003d00,0x00003d00,0x00003d00,0x00003d00,0x00003d00,0x00003d00,0x00003d00,
 0x00003d00,0x00003d00,0x00003d00,0x00003d00,0x00003d00,0x00003d00,0x00003d00,0x00003d00,0x00003d00,0x00003d00,0x00003d00,0x00003d00,0x00003d00,0x00003d00,0x00003d00,0x00003d00,
 0xbc5b3ce7,0xbc843cdc,0xbc983cce,0xbcac3cbe,0xbac93d00,0xbb963cfd,0xbbf93cf8,0xbc2c3cf1,0xbcf13c2c,0xbcf83bf9,0xbcfd3b96,0xbd003ac9,0xbcbe3cac,0xbcce3c98,0xbcdc3c84,0xbce73c5b,
 0xbce7bc5b,0xbcdcbc84,0xbccebc98,0xbcbebcac,0xbd00bac9,0xbcfdbb96,0xbcf8bbf9,0xbcf1bc2c,0xbc2cbcf1,0xbbf9bcf8,0xbb96bcfd,0xbac9bd00,0xbcacbcbe,0xbc98bcce,0xbc84bcdc,0xbc5bbce7,
 0xbcffbb49,0xbcf5bc15,0xbce2bc71,0xbcc6bca2,0xbca2bcc6,0xbc71bce2,0xbc15bcf5,0xbb49bcff,0xbb493cff,0xbc153cf5,0xbc713ce2,0xbca23cc6,0xbcc63ca2,0xbce23c71,0xbcf53c15,0xbcff3b49,
 0x3cff3b49,0x3cf53c15,0x3ce23c71,0x3cc63ca2,0x3ca23cc6,0x3c713ce2,0x3c153cf5,0x3b493cff,0x3b49bcff,0x3c15bcf5,0x3c71bce2,0x3ca2bcc6,0x3cc6bca2,0x3ce2bc71,0x3cf5bc15,0x3cffbb49,
 0x3c84bcdc,0x3cbebcac,0x3ce7bc5b,0x3cfdbb96,0xbc98bcce,0xbc2cbcf1,0xbac9bd00,0x3bf9bcf8,0xbcf83bf9,0xbd00bac9,0xbcf1bc2c,0xbccebc98,0xbb963cfd,0xbc5b3ce7,0xbcac3cbe,0xbcdc3c84,
 0xbcdcbc84,0xbcacbcbe,0xbc5bbce7,0xbb96bcfd,0xbcce3c98,0xbcf13c2c,0xbd003ac9,0xbcf8bbf9,0x3bf93cf8,0xbac93d00,0xbc2c3cf1,0xbc983cce,0x3cfd3b96,0x3ce73c5b,0x3cbe3cac,0x3c843cdc,
 0xbbc83cfb,0xbc8e3cd5,0xbcd53c8e,0xbcfb3bc8,0xbcfbbbc8,0xbcd5bc8e,0xbc8ebcd5,0xbbc8bcfb,0x3bc8bcfb,0x3c8ebcd5,0x3cd5bc8e,0x3cfbbbc8,0x3cfb3bc8,0x3cd53c8e,0x3c8e3cd5,0x3bc83cfb,
 0xbbc83cfb,0xbc8e3cd5,0xbcd53c8e,0xbcfb3bc8,0xbcfbbbc8,0xbcd5bc8e,0xbc8ebcd5,0xbbc8bcfb,0x3bc8bcfb,0x3c8ebcd5,0x3cd5bc8e,0x3cfbbbc8,0x3cfb3bc8,0x3cd53c8e,0x3c8e3cd5,0x3bc83cfb,
 0x3c98bcce,0x3ce7bc5b,0x3d003ac9,0x3cdc3c84,0xbcf8bbf9,0xbcbebcac,0xbc2cbcf1,0x3b96bcfd,0xbcfd3b96,0xbcf1bc2c,0xbcacbcbe,0xbbf9bcf8,0x3c843cdc,0x3ac93d00,0xbc5b3ce7,0xbcce3c98,
 0xbccebc98,0xbc5bbce7,0x3ac9bd00,0x3c84bcdc,0xbbf93cf8,0xbcac3cbe,0xbcf13c2c,0xbcfdbb96,0x3b963cfd,0xbc2c3cf1,0xbcbe3cac,0xbcf83bf9,0x3cdcbc84,0x3d00bac9,0x3ce73c5b,0x3c983cce,
 0xbcf5bc15,0xbca2bcc6,0xbb49bcff,0x3c71bce2,0x3ce2bc71,0x3cff3b49,0x3cc63ca2,0x3c153cf5,0x3c15bcf5,0x3cc6bca2,0x3cffbb49,0x3ce23c71,0x3c713ce2,0xbb493cff,0xbca23cc6,0xbcf53c15,
 0x3cf53c15,0x3ca23cc6,0x3b493cff,0xbc713ce2,0xbce23c71,0xbcffbb49,0xbcc6bca2,0xbc15bcf5,0xbc153cf5,0xbcc63ca2,0xbcff3b49,0xbce2bc71,0xbc71bce2,0x3b49bcff,0x3ca2bcc6,0x3cf5bc15,
 0xbcac3cbe,0xbcfd3b96,0xbcdcbc84,0xbc2cbcf1,0x3ce7bc5b,0x3cf83bf9,0x3c983cce,0xbac93d00,0xbd003ac9,0xbccebc98,0xbbf9bcf8,0x3c5bbce7,0x3cf13c2c,0x3c843cdc,0xbb963cfd,0xbcbe3cac,
 0xbcbebcac,0xbb96bcfd,0x3c84bcdc,0x3cf1bc2c,0x3c5b3ce7,0xbbf93cf8,0xbcce3c98,0xbd00bac9,0xbac9bd00,0x3c98bcce,0x3cf8bbf9,0x3ce73c5b,0xbc2c3cf1,0xbcdc3c84,0xbcfdbb96,0xbcacbcbe,
 0xbc443ced,0xbced3c44,0xbcedbc44,0xbc44bced,0x3c44bced,0x3cedbc44,0x3ced3c44,0x3c443ced,0xbc443ced,0xbced3c44,0xbcedbc44,0xbc44bced,0x3c44bced,0x3cedbc44,0x3ced3c44,0x3c443ced,
 0xbc443ced,0xbced3c44,0xbcedbc44,0xbc44bced,0x3c44bced,0x3cedbc44,0x3ced3c44,0x3c443ced,0xbc443ced,0xbced3c44,0xbcedbc44,0xbc44bced,0x3c44bced,0x3cedbc44,0x3ced3c44,0x3c443ced,
 0x3cbebcac,0x3cfd3b96,0x3c843cdc,0xbc2c3cf1,0xbc5b3ce7,0xbcf83bf9,0xbccebc98,0xbac9bd00,0x3d003ac9,0x3c983cce,0xbbf93cf8,0xbce73c5b,0xbcf13c2c,0xbcdcbc84,0xbb96bcfd,0x3cacbcbe,
 0x3cac3cbe,0xbb963cfd,0xbcdc3c84,0xbcf1bc2c,0xbce7bc5b,0xbbf9bcf8,0x3c98bcce,0x3d00bac9,0xbac93d00,0xbcce3c98,0xbcf8bbf9,0xbc5bbce7,0xbc2cbcf1,0x3c84bcdc,0x3cfdbb96,0x3cbe3cac,
 0xbce2bc71,0xbb49bcff,0x3cc6bca2,0x3cf53c15,0x3c153cf5,0xbca23cc6,0xbcffbb49,0xbc71bce2,0xbc713ce2,0xbcff3b49,0xbca2bcc6,0x3c15bcf5,0x3cf5bc15,0x3cc63ca2,0xbb493cff,0xbce23c71,
 0x3ce23c71,0x3b493cff,0xbcc63ca2,0xbcf5bc15,0xbc15bcf5,0x3ca2bcc6,0x3cff3b49,0x3c713ce2,0x3c71bce2,0x3cffbb49,0x3ca23cc6,0xbc153cf5,0xbcf53c15,0xbcc6bca2,0x3b49bcff,0x3ce2bc71,
 0xbcce3c98,0xbce7bc5b,0xbac9bd00,0x3cdcbc84,0xbbf9bcf8,0x3cbebcac,0x3cf13c2c,0x3b963cfd,0x3cfd3b96,0x3c2c3cf1,0xbcac3cbe,0xbcf8bbf9,0xbc843cdc,0xbd00bac9,0xbc5bbce7,0x3c98bcce,
 0x3c983cce,0xbc5b3ce7,0xbd003ac9,0xbc84bcdc,0xbcf83bf9,0xbcacbcbe,0x3c2cbcf1,0x3cfdbb96,0x3b96bcfd,0x3cf1bc2c,0x3cbe3cac,0xbbf93cf8,0x3cdc3c84,0xbac93d00,0xbce73c5b,0xbccebc98,
 0xbc8e3cd5,0xbcfbbbc8,0xbbc8bcfb,0x3cd5bc8e,0x3cd53c8e,0xbbc83cfb,0xbcfb3bc8,0xbc8ebcd5,0x3c8ebcd5,0x3cfb3bc8,0x3bc83cfb,0xbcd53c8e,0xbcd5bc8e,0x3bc8bcfb,0x3cfbbbc8,0x3c8e3cd5,
 0xbc8e3cd5,0xbcfbbbc8,0xbbc8bcfb,0x3cd5bc8e,0x3cd53c8e,0xbbc83cfb,0xbcfb3bc8,0xbc8ebcd5,0x3c8ebcd5,0x3cfb3bc8,0x3bc83cfb,0xbcd53c8e,0xbcd5bc8e,0x3bc8bcfb,0x3cfbbbc8,0x3c8e3cd5,
 0xbcdc3c84,0xbcbebcac,0x3c5bbce7,0x3cfd3b96,0xbccebc98,0x3c2cbcf1,0x3d003ac9,0x3bf93cf8,0x3cf83bf9,0x3ac93d00,0xbcf13c2c,0xbc98bcce,0x3b963cfd,0xbce73c5b,0xbcacbcbe,0x3c84bcdc,
 0x3c843cdc,0xbcac3cbe,0xbce7bc5b,0x3b96bcfd,0xbc983cce,0xbcf1bc2c,0x3ac9bd00,0x3cf8bbf9,0x3bf9bcf8,0x3d00bac9,0x3c2c3cf1,0xbcce3c98,0x3cfdbb96,0x3c5b3ce7,0xbcbe3cac,0xbcdcbc84,
 0xbcc6bca2,0x3c71bce2,0x3cf53c15,0xbb493cff,0xbcff3b49,0xbc15bcf5,0x3ce2bc71,0x3ca23cc6,0x3ca2bcc6,0x3ce23c71,0xbc153cf5,0xbcffbb49,0xbb49bcff,0x3cf5bc15,0x3c713ce2,0xbcc63ca2,
 0x3cc63ca2,0xbc713ce2,0xbcf5bc15,0x3b49bcff,0x3cffbb49,0x3c153cf5,0xbce23c71,0xbca2bcc6,0xbca23cc6,0xbce2bc71,0x3c15bcf5,0x3cff3b49,0x3b493cff,0xbcf53c15,0xbc71bce2,0x3cc6bca2,
 0x3ce7bc5b,0x3c843cdc,0xbcce3c98,0xbcacbcbe,0x3d00bac9,0x3b963cfd,0xbcf83bf9,0xbc2cbcf1,0x3cf13c2c,0xbbf93cf8,0xbcfdbb96,0x3ac9bd00,0x3cbe3cac,0xbc983cce,0xbcdcbc84,0x3c5bbce7,
 0x3c5b3ce7,0xbcdc3c84,0xbc98bcce,0x3cbebcac,0x3ac93d00,0xbcfd3b96,0xbbf9bcf8,0x3cf1bc2c,0xbc2c3cf1,0xbcf8bbf9,0x3b96bcfd,0x3d003ac9,0xbcac3cbe,0xbccebc98,0x3c84bcdc,0x3ce73c5b,
 0xbcb53cb5,0xbcb5bcb5,0x3cb5bcb5,0x3cb53cb5,0xbcb53cb5,0xbcb5bcb5,0x3cb5bcb5,0x3cb53cb5,0xbcb53cb5,0xbcb5bcb5,0x3cb5bcb5,0x3cb53cb5,0xbcb53cb5,0xbcb5bcb5,0x3cb5bcb5,0x3cb53cb5,
 0xbcb53cb5,0xbcb5bcb5,0x3cb5bcb5,0x3cb53cb5,0xbcb53cb5,0xbcb5bcb5,0x3cb5bcb5,0x3cb53cb5,0xbcb53cb5,0xbcb5bcb5,0x3cb5bcb5,0x3cb53cb5,0xbcb53cb5,0xbcb5bcb5,0x3cb5bcb5,0x3cb53cb5,
 0xbcf13c2c,0xbbf9bcf8,0x3cfdbb96,0x3ac93d00,0xbcbe3cac,0xbc98bcce,0x3cdcbc84,0x3c5b3ce7,0xbce7bc5b,0x3c84bcdc,0x3cce3c98,0xbcac3cbe,0xbd00bac9,0x3b96bcfd,0x3cf83bf9,0xbc2c3cf1,
 0xbc2cbcf1,0x3cf8bbf9,0x3b963cfd,0xbd003ac9,0xbcacbcbe,0x3ccebc98,0x3c843cdc,0xbce73c5b,0x3c5bbce7,0x3cdc3c84,0xbc983cce,0xbcbebcac,0x3ac9bd00,0x3cfd3b96,0xbbf93cf8,0xbcf1bc2c,
 0xbca2bcc6,0x3ce2bc71,0x3c153cf5,0xbcff3b49,0x3b49bcff,0x3cf53c15,0xbc713ce2,0xbcc6bca2,0xbcc63ca2,0xbc71bce2,0x3cf5bc15,0x3b493cff,0xbcffbb49,0x3c15bcf5,0x3ce23c71,0xbca23cc6,
 0x3ca23cc6,0xbce23c71,0xbc15bcf5,0x3cffbb49,0xbb493cff,0xbcf5bc15,0x3c71bce2,0x3cc63ca2,0x3cc6bca2,0x3c713ce2,0xbcf53c15,0xbb49bcff,0x3cff3b49,0xbc153cf5,0xbce2bc71,0x3ca2bcc6,
 0x3cf8bbf9,0xbac93d00,0xbcf1bc2c,0x3c98bcce,0x3b96bcfd,0x3ce73c5b,0xbcac3cbe,0xbc84bcdc,0xbcdcbc84,0x3cbebcac,0x3c5b3ce7,0xbcfd3b96,0xbcce3c98,0xbc2cbcf1,0x3d00bac9,0xbbf93cf8,
 0xbbf9bcf8,0x3d003ac9,0xbc2c3cf1,0xbccebc98,0xbcfdbb96,0x3c5bbce7,0x3cbe3cac,0xbcdc3c84,0xbc843cdc,0xbcacbcbe,0x3ce7bc5b,0x3b963cfd,0x3c983cce,0xbcf13c2c,0xbac9bd00,0x3cf83bf9,
 0xbcd53c8e,0xbbc8bcfb,0x3cfb3bc8,0xbc8e3cd5,0xbc8ebcd5,0x3cfbbbc8,0xbbc83cfb,0xbcd5bc8e,0x3cd5bc8e,0x3bc83cfb,0xbcfbbbc8,0x3c8ebcd5,0x3c8e3cd5,0xbcfb3bc8,0x3bc8bcfb,0x3cd53c8e,
 0xbcd53c8e,0xbbc8bcfb,0x3cfb3bc8,0xbc8e3cd5,0xbc8ebcd5,0x3cfbbbc8,0xbbc83cfb,0xbcd5bc8e,0x3cd5bc8e,0x3bc83cfb,0xbcfbbbc8,0x3c8ebcd5,0x3c8e3cd5,0xbcfb3bc8,0x3bc8bcfb,0x3cd53c8e,
 0x3cfdbb96,0xbc2c3cf1,0xbcacbcbe,0x3cf8bbf9,0xbc84bcdc,0x3d00bac9,0xbc5b3ce7,0xbc98bcce,0xbccebc98,0x3ce7bc5b,0xbac93d00,0xbcdcbc84,0xbbf93cf8,0xbcbebcac,0x3cf1bc2c,0xbb963cfd,
 0xbb96bcfd,0x3cf13c2c,0xbcbe3cac,0xbbf9bcf8,0xbcdc3c84,0xbac9bd00,0x3ce73c5b,0xbcce3c98,0xbc983cce,0xbc5bbce7,0x3d003ac9,0xbc843cdc,0x3cf83bf9,0xbcac3cbe,0xbc2cbcf1,0x3cfd3b96,
 0xbc71bce2,0x3cff3b49,0xbca23cc6,0xbc15bcf5,0x3cf53c15,0xbcc63ca2,0xbb49bcff,0x3ce23c71,0x3ce2bc71,0xbb493cff,0xbcc6bca2,0x3cf5bc15,0xbc153cf5,0xbca2bcc6,0x3cffbb49,0xbc713ce2,
 0x3c713ce2,0xbcffbb49,0x3ca2bcc6,0x3c153cf5,0xbcf5bc15,0x3cc6bca2,0x3b493cff,0xbce2bc71,0xbce23c71,0x3b49bcff,0x3cc63ca2,0xbcf53c15,0x3c15bcf5,0x3ca23cc6,0xbcff3b49,0x3c71bce2,
 0xbd003ac9,0x3c98bcce,0x3bf93cf8,0xbce7bc5b,0x3cf13c2c,0xbcdc3c84,0x3b96bcfd,0x3cac3cbe,0xbcbebcac,0x3cfdbb96,0xbc843cdc,0xbc2cbcf1,0x3c5b3ce7,0xbcf8bbf9,0x3ccebc98,0xbac93d00,
 0xbac9bd00,0x3cce3c98,0xbcf83bf9,0x3c5bbce7,0xbc2c3cf1,0xbc84bcdc,0x3cfd3b96,0xbcbe3cac,0x3cacbcbe,0x3b963cfd,0xbcdcbc84,0x3cf1bc2c,0xbce73c5b,0x3bf9bcf8,0x3c983cce,0xbd00bac9,
 0xbced3c44,0x3c44bced,0x3c443ced,0xbcedbc44,0x3cedbc44,0xbc443ced,0xbc44bced,0x3ced3c44,0xbced3c44,0x3c44bced,0x3c443ced,0xbcedbc44,0x3cedbc44,0xbc443ced,0xbc44bced,0x3ced3c44,
 0xbced3c44,0x3c44bced,0x3c443ced,0xbcedbc44,0x3cedbc44,0xbc443ced,0xbc44bced,0x3ced3c44,0xbced3c44,0x3c44bced,0x3c443ced,0xbcedbc44,0x3cedbc44,0xbc443ced,0xbc44bced,0x3ced3c44,
 0x3d003ac9,0xbcce3c98,0x3bf9bcf8,0x3c5b3ce7,0xbcf13c2c,0x3c84bcdc,0x3b963cfd,0xbcbebcac,0x3cac3cbe,0xbcfdbb96,0x3cdcbc84,0xbc2c3cf1,0xbce7bc5b,0x3cf8bbf9,0xbc983cce,0xbac9bd00,
 0xbac93d00,0xbc98bcce,0x3cf83bf9,0xbce73c5b,0xbc2cbcf1,0x3cdc3c84,0xbcfd3b96,0x3cacbcbe,0xbcbe3cac,0x3b96bcfd,0x3c843cdc,0xbcf1bc2c,0x3c5bbce7,0x3bf93cf8,0xbccebc98,0x3d00bac9,
 0xbc15bcf5,0x3cc63ca2,0xbcffbb49,0x3ce2bc71,0xbc713ce2,0xbb49bcff,0x3ca23cc6,0xbcf5bc15,0xbcf53c15,0x3ca2bcc6,0xbb493cff,0xbc71bce2,0x3ce23c71,0xbcff3b49,0x3cc6bca2,0xbc153cf5,
 0x3c153cf5,0xbcc6bca2,0x3cff3b49,0xbce23c71,0x3c71bce2,0x3b493cff,0xbca2bcc6,0x3cf53c15,0x3cf5bc15,0xbca23cc6,0x3b49bcff,0x3c713ce2,0xbce2bc71,0x3cffbb49,0xbcc63ca2,0x3c15bcf5,
 0xbcfdbb96,0x3cf1bc2c,0xbcac3cbe,0x3bf9bcf8,0x3c84bcdc,0xbac93d00,0xbc5bbce7,0x3cce3c98,0x3c983cce,0xbce7bc5b,0x3d00bac9,0xbcdc3c84,0xbcf83bf9,0x3cbebcac,0xbc2c3cf1,0xbb96bcfd,
 0xbb963cfd,0xbc2cbcf1,0x3cbe3cac,0xbcf8bbf9,0xbcdcbc84,0x3d003ac9,0xbce73c5b,0x3c98bcce,0x3ccebc98,0xbc5b3ce7,0xbac9bd00,0x3c843cdc,0x3bf93cf8,0xbcacbcbe,0x3cf13c2c,0xbcfd3b96,
 0xbcfb3bc8,0x3cd5bc8e,0xbc8e3cd5,0x3bc8bcfb,0x3bc83cfb,0xbc8ebcd5,0x3cd53c8e,0xbcfbbbc8,0x3cfbbbc8,0xbcd53c8e,0x3c8ebcd5,0xbbc83cfb,0xbbc8bcfb,0x3c8e3cd5,0xbcd5bc8e,0x3cfb3bc8,
 0xbcfb3bc8,0x3cd5bc8e,0xbc8e3cd5,0x3bc8bcfb,0x3bc83cfb,0xbc8ebcd5,0x3cd53c8e,0xbcfbbbc8,0x3cfbbbc8,0xbcd53c8e,0x3c8ebcd5,0xbbc83cfb,0xbbc8bcfb,0x3c8e3cd5,0xbcd5bc8e,0x3cfb3bc8,
 0xbcf8bbf9,0x3d00bac9,0xbcf13c2c,0x3ccebc98,0xbb96bcfd,0x3c5b3ce7,0xbcacbcbe,0x3cdc3c84,0x3c843cdc,0xbcbebcac,0x3ce73c5b,0xbcfdbb96,0xbc983cce,0x3c2cbcf1,0xbac93d00,0xbbf9bcf8,
 0xbbf93cf8,0xbac9bd00,0x3c2c3cf1,0xbc98bcce,0xbcfd3b96,0x3ce7bc5b,0xbcbe3cac,0x3c84bcdc,0x3cdcbc84,0xbcac3cbe,0x3c5bbce7,0xbb963cfd,0x3cce3c98,0xbcf1bc2c,0x3d003ac9,0xbcf83bf9,
 0xbb49bcff,0x3c153cf5,0xbc71bce2,0x3ca23cc6,0xbcc6bca2,0x3ce23c71,0xbcf5bc15,0x3cff3b49,0x3cffbb49,0xbcf53c15,0x3ce2bc71,0xbcc63ca2,0x3ca2bcc6,0xbc713ce2,0x3c15bcf5,0xbb493cff,
 0x3b493cff,0xbc15bcf5,0x3c713ce2,0xbca2bcc6,0x3cc63ca2,0xbce2bc71,0x3cf53c15,0xbcffbb49,0xbcff3b49,0x3cf5bc15,0xbce23c71,0x3cc6bca2,0xbca23cc6,0x3c71bce2,0xbc153cf5,0x3b49bcff,
 0x3cf13c2c,0xbcf8bbf9,0x3cfd3b96,0xbd00bac9,0x3cbe3cac,0xbccebc98,0x3cdc3c84,0xbce7bc5b,0x3c5b3ce7,0xbc84bcdc,0x3c983cce,0xbcacbcbe,0x3ac93d00,0xbb96bcfd,0x3bf93cf8,0xbc2cbcf1,
 0xbc2c3cf1,0x3bf9bcf8,0xbb963cfd,0x3ac9bd00,0xbcac3cbe,0x3c98bcce,0xbc843cdc,0x3c5bbce7,0xbce73c5b,0x3cdcbc84,0xbcce3c98,0x3cbebcac,0xbd003ac9,0x3cfdbb96,0xbcf83bf9,0x3cf1bc2c,
 0xbd000000,0x3d000000,0xbd000000,0x3d000000,0xbd000000,0x3d000000,0xbd000000,0x3d000000,0xbd000000,0x3d000000,0xbd000000,0x3d000000,0xbd000000,0x3d000000,0xbd000000,0x3d000000,
 0xbd000000,0x3d000000,0xbd000000,0x3d000000,0xbd000000,0x3d000000,0xbd000000,0x3d000000,0xbd000000,0x3d000000,0xbd000000,0x3d000000,0xbd000000,0x3d000000,0xbd000000,0x3d000000,
 0xbce7bc5b,0x3cdc3c84,0xbccebc98,0x3cbe3cac,0xbd00bac9,0x3cfd3b96,0xbcf8bbf9,0x3cf13c2c,0xbc2cbcf1,0x3bf93cf8,0xbb96bcfd,0x3ac93d00,0xbcacbcbe,0x3c983cce,0xbc84bcdc,0x3c5b3ce7,
 0x3c5bbce7,0xbc843cdc,0x3c98bcce,0xbcac3cbe,0x3ac9bd00,0xbb963cfd,0x3bf9bcf8,0xbc2c3cf1,0x3cf1bc2c,0xbcf83bf9,0x3cfdbb96,0xbd003ac9,0x3cbebcac,0xbcce3c98,0x3cdcbc84,0xbce73c5b,
 0x3b49bcff,0xbc153cf5,0x3c71bce2,0xbca23cc6,0x3cc6bca2,0xbce23c71,0x3cf5bc15,0xbcff3b49,0xbcffbb49,0x3cf53c15,0xbce2bc71,0x3cc63ca2,0xbca2bcc6,0x3c713ce2,0xbc15bcf5,0x3b493cff,
 0xbb493cff,0x3c15bcf5,0xbc713ce2,0x3ca2bcc6,0xbcc63ca2,0x3ce2bc71,0xbcf53c15,0x3cffbb49,0x3cff3b49,0xbcf5bc15,0x3ce23c71,0xbcc6bca2,0x3ca23cc6,0xbc71bce2,0x3c153cf5,0xbb49bcff,
 0x3cdc3c84,0xbcacbcbe,0x3c5b3ce7,0xbb96bcfd,0x3ccebc98,0xbcf13c2c,0x3d00bac9,0xbcf8bbf9,0xbbf9bcf8,0xbac93d00,0x3c2cbcf1,0xbc983cce,0xbcfdbb96,0x3ce73c5b,0xbcbebcac,0x3c843cdc,
 0x3c84bcdc,0xbcbe3cac,0x3ce7bc5b,0xbcfd3b96,0xbc98bcce,0x3c2c3cf1,0xbac9bd00,0xbbf93cf8,0xbcf83bf9,0x3d003ac9,0xbcf1bc2c,0x3cce3c98,0xbb963cfd,0x3c5bbce7,0xbcac3cbe,0x3cdcbc84,
 0xbcfbbbc8,0x3cd53c8e,0xbc8ebcd5,0x3bc83cfb,0x3bc8bcfb,0xbc8e3cd5,0x3cd5bc8e,0xbcfb3bc8,0x3cfb3bc8,0xbcd5bc8e,0x3c8e3cd5,0xbbc8bcfb,0xbbc83cfb,0x3c8ebcd5,0xbcd53c8e,0x3cfbbbc8,
 0xbcfbbbc8,0x3cd53c8e,0xbc8ebcd5,0x3bc83cfb,0x3bc8bcfb,0xbc8e3cd5,0x3cd5bc8e,0xbcfb3bc8,0x3cfb3bc8,0xbcd5bc8e,0x3c8e3cd5,0xbbc8bcfb,0xbbc83cfb,0x3c8ebcd5,0xbcd53c8e,0x3cfbbbc8,
 0x3cce3c98,0xbc5bbce7,0xbac93d00,0x3c84bcdc,0x3bf9bcf8,0xbcac3cbe,0x3cf1bc2c,0xbcfdbb96,0xbb96bcfd,0xbc2c3cf1,0x3cbebcac,0xbcf83bf9,0xbcdc3c84,0x3d00bac9,0xbce7bc5b,0x3c983cce,
 0x3c98bcce,0xbce73c5b,0x3d003ac9,0xbcdcbc84,0xbcf8bbf9,0x3cbe3cac,0xbc2cbcf1,0xbb963cfd,0xbcfd3b96,0x3cf13c2c,0xbcacbcbe,0x3bf93cf8,0x3c843cdc,0xbac9bd00,0xbc5b3ce7,0x3ccebc98,
 0x3c15bcf5,0xbcc63ca2,0x3cffbb49,0xbce2bc71,0x3c713ce2,0x3b49bcff,0xbca23cc6,0x3cf5bc15,0x3cf53c15,0xbca2bcc6,0x3b493cff,0x3c71bce2,0xbce23c71,0x3cff3b49,0xbcc6bca2,0x3c153cf5,
 0xbc153cf5,0x3cc6bca2,0xbcff3b49,0x3ce23c71,0xbc71bce2,0xbb493cff,0x3ca2bcc6,0xbcf53c15,0xbcf5bc15,0x3ca23cc6,0xbb49bcff,0xbc713ce2,0x3ce2bc71,0xbcffbb49,0x3cc63ca2,0xbc15bcf5,
 0xbcbebcac,0x3b963cfd,0x3c84bcdc,0xbcf13c2c,0x3c5b3ce7,0x3bf9bcf8,0xbcce3c98,0x3d003ac9,0xbac9bd00,0xbc983cce,0x3cf8bbf9,0xbce7bc5b,0xbc2c3cf1,0x3cdcbc84,0xbcfdbb96,0x3cac3cbe,
 0x3cacbcbe,0xbcfd3b96,0x3cdc3c84,0xbc2cbcf1,0xbce73c5b,0x3cf83bf9,0xbc98bcce,0xbac93d00,0x3d00bac9,0xbccebc98,0x3bf93cf8,0x3c5bbce7,0xbcf1bc2c,0x3c843cdc,0x3b96bcfd,0xbcbe3cac,
 0xbcedbc44,0x3c443ced,0x3c44bced,0xbced3c44,0x3ced3c44,0xbc44bced,0xbc443ced,0x3cedbc44,0xbcedbc44,0x3c443ced,0x3c44bced,0xbced3c44,0x3ced3c44,0xbc44bced,0xbc443ced,0x3cedbc44,
 0xbcedbc44,0x3c443ced,0x3c44bced,0xbced3c44,0x3ced3c44,0xbc44bced,0xbc443ced,0x3cedbc44,0xbcedbc44,0x3c443ced,0x3c44bced,0xbced3c44,0x3ced3c44,0xbc44bced,0xbc443ced,0x3cedbc44,
 0x3cac3cbe,0x3b96bcfd,0xbcdc3c84,0x3cf13c2c,0xbce7bc5b,0x3bf93cf8,0x3c98bcce,0xbd003ac9,0xbac93d00,0x3ccebc98,0xbcf8bbf9,0x3c5b3ce7,0xbc2cbcf1,0xbc843cdc,0x3cfdbb96,0xbcbebcac,
 0xbcbe3cac,0x3cfd3b96,0xbc84bcdc,0xbc2c3cf1,0x3c5bbce7,0xbcf83bf9,0x3cce3c98,0xbac9bd00,0xbd00bac9,0x3c983cce,0x3bf9bcf8,0xbce73c5b,0x3cf1bc2c,0xbcdcbc84,0x3b963cfd,0x3cacbcbe,
 0x3c71bce2,0xbcff3b49,0x3ca23cc6,0x3c15bcf5,0xbcf53c15,0x3cc63ca2,0x3b49bcff,0xbce23c71,0xbce2bc71,0x3b493cff,0x3cc6bca2,0xbcf5bc15,0x3c153cf5,0x3ca2bcc6,0xbcffbb49,0x3c713ce2,
 0xbc713ce2,0x3cffbb49,0xbca2bcc6,0xbc153cf5,0x3cf5bc15,0xbcc6bca2,0xbb493cff,0x3ce2bc71,0x3ce23c71,0xbb49bcff,0xbcc63ca2,0x3cf53c15,0xbc15bcf5,0xbca23cc6,0x3cff3b49,0xbc71bce2,
 0xbc98bcce,0xbc5b3ce7,0x3d00bac9,0xbc84bcdc,0x3cf8bbf9,0xbcacbcbe,0xbc2c3cf1,0x3cfdbb96,0xbb963cfd,0x3cf1bc2c,0xbcbebcac,0xbbf93cf8,0xbcdcbc84,0xbac93d00,0x3ce7bc5b,0xbccebc98,
 0xbcce3c98,0x3ce73c5b,0xbac9bd00,0xbcdc3c84,0xbbf9bcf8,0xbcbe3cac,0x3cf13c2c,0xbb96bcfd,0x3cfd3b96,0xbc2cbcf1,0xbcac3cbe,0x3cf83bf9,0xbc843cdc,0x3d003ac9,0xbc5bbce7,0xbc983cce,
 0xbcd5bc8e,0xbbc83cfb,0x3cfbbbc8,0xbc8ebcd5,0xbc8e3cd5,0x3cfb3bc8,0xbbc8bcfb,0xbcd53c8e,0x3cd53c8e,0x3bc8bcfb,0xbcfb3bc8,0x3c8e3cd5,0x3c8ebcd5,0xbcfbbbc8,0x3bc83cfb,0x3cd5bc8e,
 0xbcd5bc8e,0xbbc83cfb,0x3cfbbbc8,0xbc8ebcd5,0xbc8e3cd5,0x3cfb3bc8,0xbbc8bcfb,0xbcd53c8e,0x3cd53c8e,0x3bc8bcfb,0xbcfb3bc8,0x3c8e3cd5,0x3c8ebcd5,0xbcfbbbc8,0x3bc83cfb,0x3cd5bc8e,
 0xbc84bcdc,0xbcac3cbe,0x3ce73c5b,0x3b96bcfd,0x3c98bcce,0xbcf1bc2c,0xbac93d00,0x3cf8bbf9,0xbbf93cf8,0x3d00bac9,0xbc2cbcf1,0xbcce3c98,0xbcfd3b96,0x3c5b3ce7,0x3cbebcac,0xbcdcbc84,
 0xbcdc3c84,0x3cbe3cac,0x3c5bbce7,0xbcfdbb96,0xbccebc98,0xbc2c3cf1,0x3d003ac9,0xbbf9bcf8,0x3cf83bf9,0xbac9bd00,0xbcf13c2c,0x3c983cce,0x3b963cfd,0x3ce7bc5b,0xbcacbcbe,0xbc843cdc,
 0x3ca2bcc6,0xbce2bc71,0xbc153cf5,0x3cff3b49,0xbb49bcff,0xbcf53c15,0x3c713ce2,0x3cc6bca2,0x3cc63ca2,0x3c71bce2,0xbcf5bc15,0xbb493cff,0x3cffbb49,0xbc15bcf5,0xbce23c71,0x3ca23cc6,
 0xbca23cc6,0x3ce23c71,0x3c15bcf5,0xbcffbb49,0x3b493cff,0x3cf5bc15,0xbc71bce2,0xbcc63ca2,0xbcc6bca2,0xbc713ce2,0x3cf53c15,0x3b49bcff,0xbcff3b49,0x3c153cf5,0x3ce2bc71,0xbca2bcc6,
 0x3c5b3ce7,0x3cdcbc84,0xbc98bcce,0xbcbe3cac,0x3ac93d00,0x3cfdbb96,0xbbf9bcf8,0xbcf13c2c,0xbc2c3cf1,0x3cf83bf9,0x3b96bcfd,0xbd00bac9,0xbcac3cbe,0x3cce3c98,0x3c84bcdc,0xbce7bc5b,
 0xbce73c5b,0x3c843cdc,0x3ccebc98,0xbcacbcbe,0xbd003ac9,0x3b963cfd,0x3cf8bbf9,0xbc2cbcf1,0xbcf1bc2c,0xbbf93cf8,0x3cfd3b96,0x3ac9bd00,0xbcbebcac,0xbc983cce,0x3cdc3c84,0x3c5bbce7,
};

template<int SA>
__device__ __forceinline__ void wgmma_main(float (&d)[84], uint64_t da, uint64_t db, int sd) {
  asm volatile("{\n.reg .pred p;\nsetp.ne.b32 p, %86, 0;\n"
    "wgmma.mma_async.sync.aligned.m64n168k16.f32.bf16.bf16 "
    "{%0, %1, %2, %3, %4, %5, %6, %7, %8, %9, %10, %11, %12, %13, %14, %15, %16, %17, %18, %19, %20, %21, %22, %23, %24, %25, %26, %27, %28, %29, %30, %31, %32, %33, %34, %35, %36, %37, %38, %39, %40, %41, %42, %43, %44, %45, %46, %47, %48, %49, %50, %51, %52, %53, %54, %55, %56, %57, %58, %59, %60, %61, %62, %63, %64, %65, %66, %67, %68, %69, %70, %71, %72, %73, %74, %75, %76, %77, %78, %79, %80, %81, %82, %83}, %84, %85, p, %87, 1, 1, 0;\n}\n"
    : "+f"(d[0]), "+f"(d[1]), "+f"(d[2]), "+f"(d[3]), "+f"(d[4]), "+f"(d[5]), "+f"(d[6]), "+f"(d[7]), "+f"(d[8]), "+f"(d[9]), "+f"(d[10]), "+f"(d[11]), "+f"(d[12]), "+f"(d[13]), "+f"(d[14]), "+f"(d[15]), "+f"(d[16]), "+f"(d[17]), "+f"(d[18]), "+f"(d[19]), "+f"(d[20]), "+f"(d[21]), "+f"(d[22]), "+f"(d[23]), "+f"(d[24]), "+f"(d[25]), "+f"(d[26]), "+f"(d[27]), "+f"(d[28]), "+f"(d[29]), "+f"(d[30]), "+f"(d[31]), "+f"(d[32]), "+f"(d[33]), "+f"(d[34]), "+f"(d[35]), "+f"(d[36]), "+f"(d[37]), "+f"(d[38]), "+f"(d[39]), "+f"(d[40]), "+f"(d[41]), "+f"(d[42]), "+f"(d[43]), "+f"(d[44]), "+f"(d[45]), "+f"(d[46]), "+f"(d[47]), "+f"(d[48]), "+f"(d[49]), "+f"(d[50]), "+f"(d[51]), "+f"(d[52]), "+f"(d[53]), "+f"(d[54]), "+f"(d[55]), "+f"(d[56]), "+f"(d[57]), "+f"(d[58]), "+f"(d[59]), "+f"(d[60]), "+f"(d[61]), "+f"(d[62]), "+f"(d[63]), "+f"(d[64]), "+f"(d[65]), "+f"(d[66]), "+f"(d[67]), "+f"(d[68]), "+f"(d[69]), "+f"(d[70]), "+f"(d[71]), "+f"(d[72]), "+f"(d[73]), "+f"(d[74]), "+f"(d[75]), "+f"(d[76]), "+f"(d[77]), "+f"(d[78]), "+f"(d[79]), "+f"(d[80]), "+f"(d[81]), "+f"(d[82]), "+f"(d[83])
    : "l"(da), "l"(db), "r"(sd), "n"(SA));
}
template<int SA>
__device__ __forceinline__ void wgmma_fwd(float (&d)[32], uint64_t da, uint64_t db, int sd) {
  asm volatile("{\n.reg .pred p;\nsetp.ne.b32 p, %34, 0;\n"
    "wgmma.mma_async.sync.aligned.m64n64k16.f32.bf16.bf16 "
    "{%0, %1, %2, %3, %4, %5, %6, %7, %8, %9, %10, %11, %12, %13, %14, %15, %16, %17, %18, %19, %20, %21, %22, %23, %24, %25, %26, %27, %28, %29, %30, %31}, %32, %33, p, %35, 1, 0, 1;\n}\n"
    : "+f"(d[0]), "+f"(d[1]), "+f"(d[2]), "+f"(d[3]), "+f"(d[4]), "+f"(d[5]), "+f"(d[6]), "+f"(d[7]), "+f"(d[8]), "+f"(d[9]), "+f"(d[10]), "+f"(d[11]), "+f"(d[12]), "+f"(d[13]), "+f"(d[14]), "+f"(d[15]), "+f"(d[16]), "+f"(d[17]), "+f"(d[18]), "+f"(d[19]), "+f"(d[20]), "+f"(d[21]), "+f"(d[22]), "+f"(d[23]), "+f"(d[24]), "+f"(d[25]), "+f"(d[26]), "+f"(d[27]), "+f"(d[28]), "+f"(d[29]), "+f"(d[30]), "+f"(d[31])
    : "l"(da), "l"(db), "r"(sd), "n"(SA));
}
template<int SA>
__device__ __forceinline__ void wgmma_inv(float (&d)[24], uint64_t da, uint64_t db, int sd) {
  asm volatile("{\n.reg .pred p;\nsetp.ne.b32 p, %26, 0;\n"
    "wgmma.mma_async.sync.aligned.m64n48k16.f32.bf16.bf16 "
    "{%0, %1, %2, %3, %4, %5, %6, %7, %8, %9, %10, %11, %12, %13, %14, %15, %16, %17, %18, %19, %20, %21, %22, %23}, %24, %25, p, %27, 1, 1, 0;\n}\n"
    : "+f"(d[0]), "+f"(d[1]), "+f"(d[2]), "+f"(d[3]), "+f"(d[4]), "+f"(d[5]), "+f"(d[6]), "+f"(d[7]), "+f"(d[8]), "+f"(d[9]), "+f"(d[10]), "+f"(d[11]), "+f"(d[12]), "+f"(d[13]), "+f"(d[14]), "+f"(d[15]), "+f"(d[16]), "+f"(d[17]), "+f"(d[18]), "+f"(d[19]), "+f"(d[20]), "+f"(d[21]), "+f"(d[22]), "+f"(d[23])
    : "l"(da), "l"(db), "r"(sd), "n"(SA));
}

__device__ __forceinline__ uint32_t s2u(const void* p) { return (uint32_t)__cvta_generic_to_shared(p); }
__device__ __forceinline__ void mbar_init(uint32_t a, int c) { asm volatile("mbarrier.init.shared::cta.b64 [%0], %1;" ::"r"(a), "r"(c)); }
__device__ __forceinline__ void mbar_expect(uint32_t a, int b) { asm volatile("mbarrier.arrive.expect_tx.shared::cta.b64 _, [%0], %1;" ::"r"(a), "r"(b) : "memory"); }
__device__ __forceinline__ void mbar_arrive(uint32_t a) { asm volatile("mbarrier.arrive.shared::cta.b64 _, [%0];" ::"r"(a) : "memory"); }
__device__ __forceinline__ void mbar_arrive_cluster(uint32_t a, uint32_t cta, uint32_t cnt) {
  asm volatile("{\n.reg .b32 r;\nmapa.shared::cluster.u32 r, %0, %1;\nmbarrier.arrive.shared::cluster.b64 _, [r], %2;\n}" ::"r"(a), "r"(cta), "r"(cnt) : "memory");
}
__device__ __forceinline__ void mbar_wait(uint32_t a, int ph) {
  asm volatile("{\n.reg .pred p;\n.reg .u32 c;\nmov.u32 c, 0;\nWAIT:\n"
               "mbarrier.try_wait.parity.shared::cta.b64 p, [%0], %1;\n@p bra DONE;\n"
               "add.u32 c, c, 1;\nsetp.lt.u32 p, c, 0x400000;\n@p bra WAIT;\ntrap;\nDONE:\n}" ::"r"(a), "r"(ph) : "memory");
}
__device__ __forceinline__ void flag_wait(const unsigned* p, unsigned target) {
  asm volatile("{\n.reg .pred p;\n.reg .u32 c, v;\nmov.u32 c, 0;\nWAIT:\n"
               "ld.acquire.gpu.global.u32 v, [%0];\nsetp.ge.u32 p, v, %1;\n@p bra DONE;\n"
               "add.u32 c, c, 1;\nsetp.lt.u32 p, c, 0x400000;\n@p bra WAIT;\ntrap;\nDONE:\n}" ::"l"(p), "r"(target) : "memory");
}
__device__ __forceinline__ void flag_add(unsigned* p) { asm volatile("red.release.gpu.global.add.u32 [%0], 1;" ::"l"(p) : "memory"); }
__device__ __forceinline__ bool elect_one() {
  uint32_t p;
  asm volatile("{\n.reg .pred P;\nelect.sync _|P, 0xffffffff;\nselp.u32 %0, 1, 0, P;\n}" : "=r"(p));
  return p != 0;
}
__device__ __forceinline__ void bulk_ld(uint32_t dst, const void* src, int bytes, uint32_t bar) {
  asm volatile("cp.async.bulk.shared::cluster.global.mbarrier::complete_tx::bytes [%0], [%1], %2, [%3];" ::"r"(dst), "l"(src), "r"(bytes), "r"(bar) : "memory");
}
__device__ __forceinline__ void bulk_ld_mc(uint32_t dst, const void* src, int bytes, uint32_t bar, uint16_t mask) {
  asm volatile("cp.async.bulk.shared::cluster.global.mbarrier::complete_tx::bytes.multicast::cluster [%0], [%1], %2, [%3], %4;" ::"r"(dst), "l"(src), "r"(bytes), "r"(bar), "h"(mask) : "memory");
}
__device__ __forceinline__ void tma_ld2(uint32_t dst, const CUtensorMap* tm, int c0, int c1, uint32_t bar) {
  asm volatile("cp.async.bulk.tensor.2d.shared::cluster.global.mbarrier::complete_tx::bytes [%0], [%1, {%3,%4}], [%2];" ::"r"(dst), "l"(tm), "r"(bar), "r"(c0), "r"(c1) : "memory");
}
__device__ __forceinline__ void tma_ld3(uint32_t dst, const CUtensorMap* tm, int c0, int c1, int c2, uint32_t bar) {
  asm volatile("cp.async.bulk.tensor.3d.shared::cluster.global.mbarrier::complete_tx::bytes [%0], [%1, {%3,%4,%5}], [%2];" ::"r"(dst), "l"(tm), "r"(bar), "r"(c0), "r"(c1), "r"(c2) : "memory");
}
__device__ __forceinline__ void tma_pf3(const CUtensorMap* tm, int c0, int c1, int c2) {
  asm volatile("cp.async.bulk.prefetch.tensor.3d.L2.global [%0, {%1,%2,%3}];" ::"l"(tm), "r"(c0), "r"(c1), "r"(c2) : "memory");
}
__device__ __forceinline__ void tma_st3(const CUtensorMap* tm, uint32_t src, int c0, int c1, int c2) {
  asm volatile("cp.async.bulk.tensor.3d.global.shared::cta.bulk_group [%0, {%2,%3,%4}], [%1];" ::"l"(tm), "r"(src), "r"(c0), "r"(c1), "r"(c2) : "memory");
}
__device__ __forceinline__ void tma_st4(const CUtensorMap* tm, uint32_t src, int c0, int c1, int c2, int c3) {
  asm volatile("cp.async.bulk.tensor.4d.global.shared::cta.bulk_group [%0, {%2,%3,%4,%5}], [%1];" ::"l"(tm), "r"(src), "r"(c0), "r"(c1), "r"(c2), "r"(c3) : "memory");
}
__device__ __forceinline__ void bulk_commit() { asm volatile("cp.async.bulk.commit_group;" ::: "memory"); }
template <int N> __device__ __forceinline__ void bulk_wait_read() { asm volatile("cp.async.bulk.wait_group.read %0;" ::"n"(N) : "memory"); }
template <int N> __device__ __forceinline__ void bulk_wait() { asm volatile("cp.async.bulk.wait_group %0;" ::"n"(N) : "memory"); }
__device__ __forceinline__ void fence_async_smem() { asm volatile("fence.proxy.async.shared::cta;" ::: "memory"); }
__device__ __forceinline__ void wg_fence() { asm volatile("wgmma.fence.sync.aligned;" ::: "memory"); }
__device__ __forceinline__ void wg_commit() { asm volatile("wgmma.commit_group.sync.aligned;" ::: "memory"); }
template <int N> __device__ __forceinline__ void wg_wait() { asm volatile("wgmma.wait_group.sync.aligned %0;" ::"n"(N) : "memory"); }
template <int R> __device__ __forceinline__ void fence_regs(float (&d)[R]) {
#pragma unroll
  for (int i = 0; i < R; i++) asm volatile("" : "+f"(d[i])::"memory");
}
__device__ __forceinline__ uint64_t mk_desc(uint32_t addr) {
  return (uint64_t)((addr & 0x3FFFF) >> 4) | (1ull << 16) | (64ull << 32) | (1ull << 62);
}
__device__ __forceinline__ uint32_t pack2(float lo, float hi) {
  uint32_t r;
  asm("cvt.rn.bf16x2.f32 %0, %1, %2;" : "=r"(r) : "f"(hi), "f"(lo));
  return r;
}
__device__ __forceinline__ void stsm4(uint32_t ad, uint32_t a, uint32_t b, uint32_t c, uint32_t d) {
  asm volatile("stmatrix.sync.aligned.m8n8.x4.shared.b16 [%0], {%1,%2,%3,%4};" ::"r"(ad), "r"(a), "r"(b), "r"(c), "r"(d) : "memory");
}
__device__ __forceinline__ void stsm4t(uint32_t ad, uint32_t a, uint32_t b, uint32_t c, uint32_t d) {
  asm volatile("stmatrix.sync.aligned.m8n8.x4.trans.shared.b16 [%0], {%1,%2,%3,%4};" ::"r"(ad), "r"(a), "r"(b), "r"(c), "r"(d) : "memory");
}

constexpr int GST = 4;
constexpr int G_STAGE = WBLK + XBLK;
constexpr int NR = 8;
constexpr int OFF_RING = GST * G_STAGE;
constexpr int OFF_F = OFF_RING + NR * 8192;
constexpr int OFF_BAR = OFF_F + 8192;
constexpr int K1_SMEM = OFF_BAR + 1024;
constexpr int B_FULL = 0, B_EMPTY = 32, B_RAWF = 64, B_STG = 128, B_RAWE = 192, B_Y = 256, B_F = 272, B_DONE = 280;

struct K1Maps { CUtensorMap x, we, wo, xst, wst, yst; };

__device__ __forceinline__ int chunk_of(int n) { return n < 16 ? n : 31 - n; }
__device__ __forceinline__ int x2_of(int cta, int n) { return (cta + 80 * n) & 127; }

template <bool ISX>
__device__ __forceinline__ void t_issue(float (&t)[32], uint32_t sb, int seq, int wg) {
  const int sl = wg * 4 + (seq & 3);
  mbar_wait(sb + OFF_BAR + B_RAWF + 8 * sl, (seq >> 2) & 1);
  const uint64_t da = mk_desc(sb + OFF_F), db = mk_desc(sb + OFF_RING + sl * 8192);
  wg_fence();
#pragma unroll
  for (int kk = 0; kk < (ISX ? 4 : 1); kk++) wgmma_fwd<1>(t, da + 2 * kk, db + 128 * kk, kk);
  wg_commit();
}
template <bool ISX>
__device__ __forceinline__ void t_finish(float (&t)[32], uint32_t sb, int seq, int sw, int wg, int w, int lane) {
  const int sl = wg * 4 + (seq & 3);
  fence_regs(t);
  asm volatile("bar.sync %0, 128;" ::"r"(1 + wg) : "memory");
  const int m = lane >> 3, r = lane & 7;
  uint32_t ad = sb + OFF_RING + sl * 8192 + (8 * w + r) * 128;
  if (ISX) ad += ((((m & 1) * 4 + (m >> 1)) ^ sw ^ r) << 4);
  else ad += (m & 1) * 4096 + (((m >> 1) ^ sw ^ r) << 4);
#pragma unroll
  for (int i = 0; i < 4; i++) {
    const uint32_t a = ISX ? ((ad ^ ((i & 1) * 32)) + (i >> 1) * 4096) : (ad ^ (i * 32));
    stsm4(a, pack2(t[8 * i], t[8 * i + 1]), pack2(t[8 * i + 2], t[8 * i + 3]), pack2(t[8 * i + 4], t[8 * i + 5]), pack2(t[8 * i + 6], t[8 * i + 7]));
  }
  fence_async_smem();
  __syncwarp();
  if (lane == 0) mbar_arrive(sb + OFF_BAR + B_STG + 8 * sl);
}
__device__ __forceinline__ void main_issue(float (&yr)[84], float (&yi)[84], uint32_t st, int wg, int kk, int sd) {
  const uint64_t wr = mk_desc(st + wg * 8192) + kk * 128, wi = wr + 256;
  const uint64_t xr = mk_desc(st + WBLK) + kk * 2, xi = xr + 4;
  wg_fence();
  wgmma_main<1>(yr, wr, xr, sd);
  wgmma_main<1>(yi, wr, xi, sd);
  wgmma_main<1>(yr, wi, xi, 1);
  wgmma_main<-1>(yi, wi, xr, 1);
  wg_commit();
}

__global__ void __cluster_dims__(2, 1, 1) __launch_bounds__(384, 1)
k1_main(const __grid_constant__ K1Maps tm) {
  extern __shared__ __align__(1024) uint8_t smem_raw[];
  const uint32_t sb = s2u(smem_raw);
  const uint32_t bar = sb + OFF_BAR;
  const int warp = __shfl_sync(0xffffffffu, threadIdx.x >> 5, 0), lane = threadIdx.x & 31;
  const int cta = blockIdx.x;
  const uint32_t rank = cta & 1;
  const int b = (cta >> 1) & 1, u = cta >> 2;
  if (threadIdx.x == 0) {
    PROF_T(0);
    for (int i = 0; i < GST; i++) { mbar_init(bar + B_FULL + 8 * i, 1); mbar_init(bar + B_EMPTY + 8 * i, 4); }
    for (int i = 0; i < NR; i++) { mbar_init(bar + B_RAWF + 8 * i, 1); mbar_init(bar + B_STG + 8 * i, 4); mbar_init(bar + B_RAWE + 8 * i, 1); }
    mbar_init(bar + B_Y, 4);
    mbar_init(bar + B_Y + 8, 4);
    mbar_init(bar + B_F, 1);
    for (int i = 0; i < 32; i++) mbar_init(bar + B_DONE + 8 * i, 1);
    asm volatile("fence.mbarrier_init.release.cluster;" ::: "memory");
  }
  if (cta == 0 && threadIdx.x < 16) g_cnt[threadIdx.x * 32] = 0;
  __syncthreads();
  asm volatile("barrier.cluster.arrive.relaxed.aligned;" ::: "memory");
  asm volatile("griddepcontrol.launch_dependents;" ::: "memory");
  if (warp >= 8) {
    asm volatile("setmaxnreg.dec.sync.aligned.u32 40;");
    if (warp == 9) {
      if (elect_one()) {
        mbar_expect(bar + B_F, 8192);
        bulk_ld(sb + OFF_F, g_Fimg, 8192, bar + B_F);
        int k0 = 0, k1 = 0;
        for (int n = 0; n < 32; n++) {
          const int c = chunk_of(n);
          const int r2 = x2_of(cta, n);
          const int nit = n < 16 ? (r2 < 80 ? 5 : 4) : 2;
          for (int j = 0; j < nit; j++) {
            const int jj = n < 16 ? j : j + 2;
            const int g = jj == 4 ? (n & 1) : (jj & 1);
            const int k = g ? k1++ : k0++;
            const int sl = g * 4 + (k & 3);
            const uint32_t dst = sb + OFF_RING + sl * 8192, fb = bar + B_RAWF + 8 * sl;
            mbar_wait(bar + B_RAWE + 8 * sl, ((k >> 2) & 1) ^ 1);
            if (jj == 2 || jj == 3) {
              const int cp = c * 64 + (cta >> 1);
              const int d64 = (n >> 4) * 4 + (cta & 1) * 2 + (jj - 2);
              mbar_expect(fb, 2048);
              tma_ld3(dst, cp < 512 ? &tm.we : &tm.wo, 0, 0, (cp & 511) * 8 + d64, fb);
            } else {
              const int wi = jj == 4 ? 256 + r2 : 2 * cta + jj;
              const int bb = wi >= NT, t = wi - bb * NT;
              mbar_expect(fb, 8192);
              tma_ld3(dst, &tm.x, c * 64, t * MT, bb, fb);
            }
          }
        }
      }
      __syncwarp();
      asm volatile("barrier.cluster.wait.aligned;" ::: "memory");
    } else if (warp == 10) {
      if (elect_one()) {
        int k0 = 0, k1 = 0;
        for (int n = 0; n < 32; n++) {
          const int c = chunk_of(n);
          const int r2 = x2_of(cta, n);
          const int nit = n < 16 ? (r2 < 80 ? 5 : 4) : 2;
          int slprev = 0;
          for (int j = 0; j < nit; j++) {
            const int jj = n < 16 ? j : j + 2;
            const int g = jj == 4 ? (n & 1) : (jj & 1);
            const int k = g ? k1++ : k0++;
            const int sl = g * 4 + (k & 3);
            const uint32_t src = sb + OFF_RING + sl * 8192;
            mbar_wait(bar + B_STG + 8 * sl, (k >> 2) & 1);
            if (jj == 2 || jj == 3) {
              const int cl = cta >> 1;
              const int row = (n % WR) * (WCHUNK / 128) + ((cta & 1) * 2 + (cl >> 5)) * 128 + (jj - 2) * 64 + (cl & 31);
              tma_st4(&tm.wst, src, 0, 0, 0, row);
            } else {
              const int wi = jj == 4 ? 256 + r2 : 2 * cta + jj;
              const int bb = wi >= NT, t = wi - bb * NT;
              tma_st4(&tm.xst, src, 0, 0, 0, (c * 128 + bb * 2) * NT + t);
            }
            bulk_commit();
            if (j > 0) {
              bulk_wait_read<1>();
              mbar_arrive(bar + B_RAWE + 8 * slprev);
            }
            slprev = sl;
          }
          PROF_T(128 + n);
          bulk_wait<0>();
          mbar_arrive(bar + B_RAWE + 8 * slprev);
          mbar_arrive(bar + B_DONE + 8 * n);
          PROF_T(160 + n);
        }
      }
      __syncwarp();
      asm volatile("barrier.cluster.wait.aligned;" ::: "memory");
    } else if (warp == 11) {
      if (elect_one()) {
        for (int n = 0; n < 32; n++) {
          mbar_wait(bar + B_DONE + 8 * n, 0);
          PROF_T(192 + n);
          flag_add(&g_flag[n * 32]);
          PROF_T(64 + n);
        }
      }
      __syncwarp();
      asm volatile("barrier.cluster.wait.aligned;" ::: "memory");
    } else {
      asm volatile("barrier.cluster.wait.aligned;" ::: "memory");
      if (elect_one()) {
        int s = 0, ph = 1;
        const uint8_t* xs = g_X + (size_t)((u * 2 + b) * 2) * XBLK + rank * (XBLK / 2);
        const uint8_t* ws = g_W + (size_t)(u * 2 + rank) * 2 * WBLK;
        for (int n = 0; n < 32; n++) {
          const int c = chunk_of(n);
          if (n == 16) {
            for (int i = 0; i < 3; i++) {
              mbar_wait(bar + B_EMPTY + 8 * s, ph);
              mbar_arrive(bar + B_FULL + 8 * s);
              s++;
            }
          }
          flag_wait(&g_flag[n * 32], 128);
          asm volatile("fence.proxy.async.global;" ::: "memory");
          PROF_T(32 + n);
          for (int h = 0; h < 2; h++) {
            mbar_wait(bar + B_EMPTY + 8 * s, ph);
            const uint32_t dst = sb + s * G_STAGE, fb = bar + B_FULL + 8 * s;
            mbar_expect(fb, G_STAGE);
            bulk_ld(dst, ws + (size_t)(n % WR) * WCHUNK + h * WBLK, WBLK, fb);
            bulk_ld_mc(dst + WBLK + rank * (XBLK / 2), xs + (size_t)(128 * c + h) * XBLK, XBLK / 2, fb, 3);
            if (++s == GST) { s = 0; ph ^= 1; }
            if (n == 16 && h == 0) {
              for (int g = 0; g < 2; g++) {
                mbar_wait(bar + B_Y + 8 * g, 0);
                tma_st4(&tm.yst, sb + g * 2 * XBLK, 0, 0, 2 * u, b * 8 + rank * 2 + g);
                bulk_commit();
              }
              bulk_wait_read<1>();
              mbar_arrive_cluster(bar + B_EMPTY, 0, 2);
              mbar_arrive_cluster(bar + B_EMPTY, 1, 2);
              bulk_wait_read<0>();
              for (int i = 1; i < 3; i++) {
                mbar_arrive_cluster(bar + B_EMPTY + 8 * i, 0, 2);
                mbar_arrive_cluster(bar + B_EMPTY + 8 * i, 1, 2);
              }
            }
          }
        }
        for (int g = 0; g < 2; g++) {
          mbar_wait(bar + B_Y + 8 * g, 1);
          tma_st4(&tm.yst, sb + g * 2 * XBLK, 0, 0, 2 * u, b * 8 + 4 + rank * 2 + g);
          bulk_commit();
        }
        bulk_wait<0>();
        PROF_T(1);
      }
      __syncwarp();
    }
    asm volatile("barrier.cluster.arrive.relaxed.aligned;\nbarrier.cluster.wait.aligned;" ::: "memory");
  } else {
    asm volatile("setmaxnreg.inc.sync.aligned.u32 232;");
    asm volatile("barrier.cluster.wait.aligned;" ::: "memory");
    const int wg = warp >> 2, w = warp & 3;
    float yr[84], yi[84], t[32];
    const int swx = (2 * cta + wg) & 7, sww = (cta >> 1) & 7;
    int seq = 0;
    mbar_wait(bar + B_F, 0);
#pragma unroll 1
    for (int m = 0; m < LEAD; m++) {
      const int r2 = x2_of(cta, m);
      t_issue<true>(t, sb, seq, wg);
      wg_wait<0>();
      t_finish<true>(t, sb, seq++, swx, wg, w, lane);
      t_issue<false>(t, sb, seq, wg);
      wg_wait<0>();
      t_finish<false>(t, sb, seq++, sww, wg, w, lane);
      if (r2 < 80 && (m & 1) == wg) {
        t_issue<true>(t, sb, seq, wg);
        wg_wait<0>();
        t_finish<true>(t, sb, seq++, r2 & 7, wg, w, lane);
      }
    }
    int s = 0, ph = 0;
#pragma unroll 1
    for (int pass = 0; pass < 2; pass++) {
      int sprev = -1;
#pragma unroll 1
      for (int i = 0; i < 16; i++) {
        const int m = pass * 16 + i + LEAD;
        const int r2 = x2_of(cta, m);
        const bool hx = m < 16, hw = m < 32, hx2 = hx && r2 < 80 && (m & 1) == wg;
        mbar_wait(bar + B_FULL + 8 * s, ph);
        if (threadIdx.x == 0) PROF_T(96 + pass * 16 + i);
        uint32_t st = sb + s * G_STAGE;
        if (hx) t_issue<true>(t, sb, seq, wg);
        main_issue(yr, yi, st, wg, 0, i != 0);
        wg_wait<1>();
        if (sprev >= 0 && w == 0 && lane < 2) mbar_arrive_cluster(bar + B_EMPTY + 8 * sprev, lane, 1);
        if (hx) t_finish<true>(t, sb, seq++, swx, wg, w, lane);
        if (hw) t_issue<false>(t, sb, seq, wg);
        main_issue(yr, yi, st, wg, 1, 1);
        wg_wait<1>();
        if (hw) t_finish<false>(t, sb, seq++, sww, wg, w, lane);
        sprev = s;
        if (++s == GST) { s = 0; ph ^= 1; }
        mbar_wait(bar + B_FULL + 8 * s, ph);
        st = sb + s * G_STAGE;
        if (hx2) t_issue<true>(t, sb, seq, wg);
        main_issue(yr, yi, st, wg, 0, 1);
        wg_wait<1>();
        if (w == 0 && lane < 2) mbar_arrive_cluster(bar + B_EMPTY + 8 * sprev, lane, 1);
        if (hx2) t_finish<true>(t, sb, seq++, r2 & 7, wg, w, lane);
        main_issue(yr, yi, st, wg, 1, 1);
        sprev = s;
        if (++s == GST) { s = 0; ph ^= 1; }
      }
      wg_wait<0>();
      fence_regs(yr);
      fence_regs(yi);
      if (w == 0 && lane < 2) mbar_arrive_cluster(bar + B_EMPTY + 8 * sprev, lane, 1);
      if (pass == 0) {
#pragma unroll 1
        for (int i = 0; i < 3; i++) mbar_wait(bar + B_FULL + 8 * (s++), ph);
      } else {
        asm volatile("bar.sync 3, 256;" ::: "memory");
      }
      const int m = lane >> 3, r = lane & 7;
      const uint32_t ad = sb + wg * 2 * XBLK + (m >> 1) * XBLK + r * 128 + (((2 * w + (m & 1)) ^ r) << 4);
#pragma unroll
      for (int j = 0; j < 21; j++)
        stsm4t(ad + j * 1024, pack2(yr[4 * j], yr[4 * j + 1]), pack2(yr[4 * j + 2], yr[4 * j + 3]), pack2(yi[4 * j], yi[4 * j + 1]),
               pack2(yi[4 * j + 2], yi[4 * j + 3]));
      fence_async_smem();
      __syncwarp();
      if (lane == 0) mbar_arrive(bar + B_Y + 8 * wg);
      if (threadIdx.x == 0) PROF_T(2 + pass);
    }
    asm volatile("barrier.cluster.arrive.relaxed.aligned;\nbarrier.cluster.wait.aligned;" ::: "memory");
  }
}

constexpr int K2_TILES = 21;
constexpr int K2_OFF_G = K2_TILES * 8192;
constexpr int K2_OFF_RED = K2_OFF_G + 6144;
constexpr int K2_OFF_PAR = K2_OFF_RED + 2048;
constexpr int K2_OFF_BAR = K2_OFF_PAR + 512;
constexpr int K2_SMEM = K2_OFF_BAR + 128;

struct K2Maps { CUtensorMap yld, out; };

__device__ __forceinline__ void inv_issue(float (&acc)[24], uint32_t sb, int tl) {
  const uint64_t da = mk_desc(sb + tl * 8192), db = mk_desc(sb + K2_OFF_G);
#pragma unroll
  for (int kk = 0; kk < 4; kk++) wgmma_inv<1>(acc, da + 128 * kk, db + 2 * kk, kk);
}

__global__ void __launch_bounds__(512, 1)
k2_tail(const __grid_constant__ K2Maps tm, const __nv_bfloat16* __restrict__ gamma, const __nv_bfloat16* __restrict__ beta) {
  extern __shared__ __align__(1024) uint8_t smem_raw[];
  const uint32_t sb = s2u(smem_raw);
  float* s_red = (float*)(smem_raw + K2_OFF_RED);
  float* s_par = (float*)(smem_raw + K2_OFF_PAR);
  const uint32_t full = sb + K2_OFF_BAR;
  const int warp = __shfl_sync(0xffffffffu, threadIdx.x >> 5, 0), lane = threadIdx.x & 31;
  const int grp = blockIdx.x >> 3, tr = blockIdx.x & 7;
  const int b = grp >> 3, d64 = grp & 7;
  const int t0 = tr * K2_TILES;
  if (threadIdx.x == 0) {
    for (int i = 0; i < 8; i++) mbar_init(full + 8 * i, 1);
    asm volatile("fence.mbarrier_init.release.cluster;" ::: "memory");
  }
  __syncthreads();
  if (warp == 7 && elect_one()) {
    mbar_expect(full + 56, 6144);
    bulk_ld(sb + K2_OFF_G, g_Gimg, 6144, full + 56);
  }
  float gam = 0.f, bet = 0.f;
  if (threadIdx.x < 64) {
    gam = __bfloat162float(gamma[d64 * 64 + threadIdx.x]);
    bet = __bfloat162float(beta[d64 * 64 + threadIdx.x]);
  }
  asm volatile("griddepcontrol.wait;" ::: "memory");
  if (threadIdx.x == 0) PROF_T(4);
  if (warp < 7 && elect_one()) {
    mbar_expect(full + 8 * warp, 3 * 8192);
    tma_ld2(sb + warp * 3 * 8192, &tm.yld, 0, (grp * NT + t0 + warp * 3) * 64, full + 8 * warp);
  }
  if (blockIdx.x == 0 && warp == 8) g_flag[lane * 32] = 0;
  const int wg = warp >> 2, w = warp & 3, a = lane & 3;
  float acc[24];
  float s1[2] = {0.f, 0.f}, s2[2] = {0.f, 0.f};
  mbar_wait(full + 56, 0);
#pragma unroll 1
  for (int tl = wg; tl < K2_TILES; tl += 4) {
    mbar_wait(full + 8 * (tl / 3), 0);
    wg_fence();
    inv_issue(acc, sb, tl);
    wg_commit();
    wg_wait<0>();
    fence_regs(acc);
    const int nv = LOUT - (t0 + tl) * MT - 2 * a;
    if (nv < 48) {
#pragma unroll
      for (int i = 0; i < 24; i++)
        if (8 * (i >> 2) + (i & 1) >= nv) acc[i] = 0.f;
    }
#pragma unroll
    for (int i = 0; i < 24; i++) {
      s1[(i >> 1) & 1] += acc[i];
      s2[(i >> 1) & 1] = fmaf(acc[i], acc[i], s2[(i >> 1) & 1]);
    }
  }
#pragma unroll
  for (int i = 0; i < 2; i++) {
#pragma unroll
    for (int o = 1; o < 4; o <<= 1) {
      s1[i] += __shfl_xor_sync(0xffffffffu, s1[i], o);
      s2[i] += __shfl_xor_sync(0xffffffffu, s2[i], o);
    }
  }
  const int d0 = 16 * w + (lane >> 2);
  if (a == 0) {
    s_red[wg * 128 + d0] = s1[0];
    s_red[wg * 128 + d0 + 8] = s1[1];
    s_red[wg * 128 + 64 + d0] = s2[0];
    s_red[wg * 128 + 64 + d0 + 8] = s2[1];
  }
  __syncthreads();
  if (threadIdx.x == 0) PROF_T(5);
  if (threadIdx.x < 128) {
    const float tsum = (s_red[threadIdx.x] + s_red[128 + threadIdx.x]) + (s_red[256 + threadIdx.x] + s_red[384 + threadIdx.x]);
    __stcg(&g_part[(grp * 8 + tr) * 128 + threadIdx.x], tsum);
    asm volatile("bar.sync 1, 128;" ::: "memory");
    if (threadIdx.x == 0) {
      flag_add(&g_cnt[grp * 32]);
      flag_wait(&g_cnt[grp * 32], 8);
    }
    asm volatile("bar.sync 1, 128;" ::: "memory");
    if (threadIdx.x < 64) {
      float a1 = 0.f, a2 = 0.f;
#pragma unroll
      for (int i = 0; i < 8; i++) {
        a1 += __ldcg(&g_part[(grp * 8 + i) * 128 + threadIdx.x]);
        a2 += __ldcg(&g_part[(grp * 8 + i) * 128 + 64 + threadIdx.x]);
      }
      const float mu = a1 * (1.f / LOUT);
      const float var = fmaxf(a2 * (1.f / LOUT) - mu * mu, 0.f);
      const float g = gam / sqrtf(var + 1e-5f);
      s_par[threadIdx.x] = g;
      s_par[64 + threadIdx.x] = bet - mu * g;
    }
  }
  __syncthreads();
  if (threadIdx.x == 0) PROF_T(6);
  s1[0] = s_par[d0]; s1[1] = s_par[d0 + 8];
  s2[0] = s_par[64 + d0]; s2[1] = s_par[64 + d0 + 8];
  const int m = lane >> 3, r = lane & 7;
  const uint32_t ad = sb + ((m >> 1) * 8 + r) * 128 + (((2 * w + (m & 1)) ^ r) << 4);
#pragma unroll 1
  for (int tl = wg; tl < K2_TILES; tl += 4) {
    if ((t0 + tl) * MT >= LOUT) break;
    wg_fence();
    inv_issue(acc, sb, tl);
    wg_commit();
    wg_wait<0>();
    fence_regs(acc);
#pragma unroll
    for (int i = 0; i < 24; i++) {
      const float z = fmaf(acc[i], s1[(i >> 1) & 1], s2[(i >> 1) & 1]);
      const float in = z * fmaf(z * z, 0.044715f * 0.7978845608028654f, 0.7978845608028654f);
      float th;
      asm("tanh.approx.f32 %0, %1;" : "=f"(th) : "f"(in));
      const float hz = 0.5f * z;
      acc[i] = fmaf(hz, th, hz);
    }
    asm volatile("bar.sync %0, 128;" ::"r"(2 + wg) : "memory");
#pragma unroll
    for (int jj = 0; jj < 3; jj++) {
      const float* c = acc + 8 * jj;
      stsm4t(ad + tl * 8192 + jj * 2048, pack2(c[0], c[1]), pack2(c[2], c[3]), pack2(c[4], c[5]), pack2(c[6], c[7]));
    }
    fence_async_smem();
    asm volatile("bar.sync %0, 128;" ::"r"(2 + wg) : "memory");
    if (w == 0 && elect_one()) {
      tma_st3(&tm.out, sb + tl * 8192, d64 * 64, (t0 + tl) * MT, b);
      bulk_commit();
    }
  }
  if (w == 0) bulk_wait_read<0>();
  if (threadIdx.x == 0) PROF_T(7);
}

typedef CUresult (*EncFn)(CUtensorMap*, CUtensorMapDataType, cuuint32_t, void*, const cuuint64_t*, const cuuint64_t*, const cuuint32_t*,
                          const cuuint32_t*, CUtensorMapInterleave, CUtensorMapSwizzle, CUtensorMapL2promotion, CUtensorMapFloatOOBfill);

void encode(EncFn fn, CUtensorMap* m, int rank, void* base, const cuuint64_t* dims, const cuuint64_t* strides, const cuuint32_t* box,
            CUtensorMapL2promotion promo) {
  cuuint32_t es[5] = {1, 1, 1, 1, 1};
  fn(m, CU_TENSOR_MAP_DATA_TYPE_BFLOAT16, rank, base, dims, strides, box, es, CU_TENSOR_MAP_INTERLEAVE_NONE, CU_TENSOR_MAP_SWIZZLE_128B, promo,
     CU_TENSOR_MAP_FLOAT_OOB_FILL_NONE);
}

}

extern "C" void kernel_launch(void* const* d_in, const int* in_sizes, int n_in, void* d_out, int out_size) {
  (void)in_sizes; (void)n_in; (void)out_size;
  const __nv_bfloat16* x = (const __nv_bfloat16*)d_in[0];
  const __nv_bfloat16* w = (const __nv_bfloat16*)d_in[1];
  const __nv_bfloat16* gamma = (const __nv_bfloat16*)d_in[2];
  const __nv_bfloat16* beta = (const __nv_bfloat16*)d_in[3];
  void* fnp = nullptr;
  cudaDriverEntryPointQueryResult qr;
  cudaGetDriverEntryPoint("cuTensorMapEncodeTiled", &fnp, cudaEnableDefault, &qr);
  EncFn fn = (EncFn)fnp;
  void *xptr = nullptr, *wptr = nullptr, *yptr = nullptr;
  cudaGetSymbolAddress(&xptr, g_X);
  cudaGetSymbolAddress(&wptr, g_W);
  cudaGetSymbolAddress(&yptr, g_Y);
  K1Maps m1;
  K2Maps m2;
  {
    cuuint64_t d[3] = {1024, 8000, 2}, s[2] = {2048, 8000ull * 2048};
    cuuint32_t bx[3] = {64, 64, 1};
    encode(fn, &m1.x, 3, (void*)x, d, s, bx, CU_TENSOR_MAP_L2_PROMOTION_L2_256B);
  }
  for (int ph = 0; ph < 2; ph++) {
    cuuint64_t d[3] = {64, (cuuint64_t)(16 - ph), 4096}, s[2] = {2ull * 262144 * 2, 128};
    cuuint32_t bx[3] = {64, 16, 1};
    encode(fn, ph ? &m1.wo : &m1.we, 3, (void*)(w + (size_t)ph * 262144), d, s, bx, CU_TENSOR_MAP_L2_PROMOTION_L2_256B);
  }
  {
    cuuint64_t d[4] = {64, 32, 2, 2048 * NT}, s[3] = {4ull * XBLK, XBLK, 128};
    cuuint32_t bx[4] = {64, 32, 2, 1};
    encode(fn, &m1.xst, 4, xptr, d, s, bx, CU_TENSOR_MAP_L2_PROMOTION_NONE);
  }
  {
    cuuint64_t d[4] = {64, 32, 2, (cuuint64_t)WR * WCHUNK / 128}, s[3] = {4ull * WBLK, 4096, 128};
    cuuint32_t bx[4] = {64, 32, 2, 1};
    encode(fn, &m1.wst, 4, wptr, d, s, bx, CU_TENSOR_MAP_L2_PROMOTION_NONE);
  }
  {
    cuuint64_t d[4] = {64, NT, 64, 16}, s[3] = {8192, 128, (cuuint64_t)NT * 8192};
    cuuint32_t bx[4] = {64, NT, 2, 1};
    encode(fn, &m1.yst, 4, yptr, d, s, bx, CU_TENSOR_MAP_L2_PROMOTION_NONE);
  }
  {
    cuuint64_t d[2] = {64, 16ull * NT * 64}, s[1] = {128};
    cuuint32_t bx[2] = {64, 192};
    encode(fn, &m2.yld, 2, yptr, d, s, bx, CU_TENSOR_MAP_L2_PROMOTION_L2_256B);
  }
  {
    cuuint64_t d[3] = {512, LOUT, 2}, s[2] = {1024, (cuuint64_t)LOUT * 1024};
    cuuint32_t bx[3] = {64, MT, 1};
    encode(fn, &m2.out, 3, d_out, d, s, bx, CU_TENSOR_MAP_L2_PROMOTION_NONE);
  }
  cudaFuncSetAttribute(k1_main, cudaFuncAttributeMaxDynamicSharedMemorySize, K1_SMEM);
  cudaFuncSetAttribute(k2_tail, cudaFuncAttributeMaxDynamicSharedMemorySize, K2_SMEM);
  k1_main<<<128, 384, K1_SMEM>>>(m1);
  cudaLaunchConfig_t cfg = {};
  cfg.gridDim = dim3(128);
  cfg.blockDim = dim3(512);
  cfg.dynamicSmemBytes = K2_SMEM;
  cfg.stream = cudaStreamPerThread;
  cudaLaunchAttribute at[1];
  at[0].id = cudaLaunchAttributeProgrammaticStreamSerialization;
  at[0].val.programmaticStreamSerializationAllowed = 1;
  cfg.attrs = at;
  cfg.numAttrs = 1;
  cudaLaunchKernelEx(&cfg, k2_tail, m2, gamma, beta);
}
```

```cpp
#include <cuda_runtime.h>
#include <cuda_bf16.h>
#include <cuda.h>
#include <stdint.h>

namespace {

#define LW_ 4
#define WR_ 6
#define OB_ 2
#define XEF0 8
#define XC(c) (c)
#define NOFENCE 0
#define XFIRST 0
constexpr int LOUT = 7985;
constexpr int MT = 48;
constexpr int NT = 168;
constexpr int XBLK = NT * 128;
constexpr int WBLK = 16384;
constexpr int LW = LW_;
constexpr int WR = WR_;
constexpr int OB = OB_;
constexpr int WCHUNK = 32 * 4 * WBLK;
constexpr int XPAGES = 24;
constexpr int YFLUSH = 16 + LW + 5;

__device__ __align__(1024) uint8_t g_X[(XPAGES + 1) << 21];
__device__ __align__(1024) uint8_t g_W[(size_t)WR * WCHUNK];
__device__ __align__(1024) uint8_t g_Y[16ull * NT * 8192];
__device__ unsigned long long g_part[128 * 128];
constexpr int C_FLAG = 0, C_LOADED = 36, C_REG = 68, C_EXIT = 69, C_NUM = 70;
__device__ __align__(128) unsigned g_ctr[C_NUM * 32];
#define PROF_T(i)
#define PROF_C(i)
#define PROF_V(i, v)
#define PROF_W(acc, stmt) stmt

__device__ __align__(128) const uint32_t g_Fimg[2048] = {
 0x3f803f80,0x3f7d3f7f,0x3f783f7b,0x3f713f75,0x3f673f6d,0x3f5c3f62,0x3f4e3f55,0x3f3e3f46,0x3f2c3f35,0x3f183f22,0x3f043f0e,0x3edb3ef1,0x3eac3ec4,0x3e793e95,0x3e163e48,0x3d493dc9,
 0xbd490000,0xbe16bdc9,0xbe79be48,0xbeacbe95,0xbedbbec4,0xbf04bef1,0xbf18bf0e,0xbf2cbf22,0xbf3ebf35,0xbf4ebf46,0xbf5cbf55,0xbf67bf62,0xbf71bf6d,0xbf78bf75,0xbf7dbf7b,0xbf80bf7f,
 0x3e793ec4,0xbd493dc9,0xbeacbe48,0xbf18bef1,0x3f7d3f80,0x3f673f75,0x3f3e3f55,0x3f043f22,0xbf5cbf6d,0xbf2cbf46,0xbedbbf0e,0xbe16be95,0xbf4ebf35,0xbf71bf62,0xbf80bf7b,0xbf78bf7f,
 0x3f783f6d,0x3f803f7f,0x3f713f7b,0x3f4e3f62,0x3e160000,0x3edb3e95,0x3f2c3f0e,0x3f5c3f46,0xbf04bec4,0xbf3ebf22,0xbf67bf55,0xbf7dbf75,0x3f183f35,0x3eac3ef1,0x3d493e48,0xbe79bdc9,
 0xbf04bf35,0xbd49be95,0x3edb3e48,0x3f4e3f22,0x3f7d3f6d,0x3f713f7f,0x3f2c3f55,0x3e793ef1,0x3f783f80,0x3f3e3f62,0x3eac3f0e,0xbe163dc9,0xbf18bec4,0xbf67bf46,0xbf80bf7b,0xbf5cbf75,
 0x3f5c3f35,0x3f803f75,0x3f673f7b,0x3f183f46,0x3e163ec4,0xbeacbdc9,0xbf3ebf0e,0xbf78bf62,0xbe790000,0xbf2cbef1,0xbf71bf55,0xbf7dbf7f,0xbf4ebf6d,0xbedbbf22,0x3d49be48,0x3f043e95,
 0xbf2cbec4,0xbf7dbf62,0xbf5cbf7b,0xbeacbf22,0x3f673f35,0x3f783f7f,0x3f183f55,0xbd493e95,0xbf80bf6d,0xbf4ebf75,0xbe79bf0e,0x3edb3dc9,0x3f713f80,0x3f043f46,0xbe163e48,0xbf3ebef1,
 0x3f3e3f6d,0x3e163ef1,0xbf04be48,0xbf71bf46,0xbedbbf35,0x3e79bdc9,0x3f4e3f0e,0x3f803f75,0x3d493ec4,0xbf18be95,0xbf78bf55,0xbf67bf7f,0x3eac0000,0x3f5c3f22,0x3f7d3f7b,0x3f2c3f62,
 0xbedb0000,0xbf78bf46,0xbf4ebf7b,0xbd49bef1,0x3f3e3ec4,0x3f7d3f75,0x3f043f55,0xbeac3dc9,0xbf71bf35,0xbf5cbf7f,0xbe16bf0e,0x3f2c3e95,0x3f803f6d,0x3f183f62,0xbe793e48,0xbf67bf22,
 0x3f673f80,0x3e793f22,0xbf18be48,0xbf80bf62,0xbf2cbf6d,0x3e16be95,0x3f5c3f0e,0x3f713f7f,0x3eac3f35,0xbf04bdc9,0xbf7dbf55,0xbf3ebf75,0x3d49bec4,0x3f4e3ef1,0x3f783f7b,0x3edb3f46,
 0xbf7dbf6d,0xbeacbf46,0x3f2c3e48,0x3f783f75,0x3f040000,0x3f803f62,0x3edb3f55,0xbf18bdc9,0x3f4e3ec4,0x3f673f7f,0x3d493f0e,0xbf5cbef1,0x3e793f35,0xbf3ebe95,0xbf71bf7b,0xbe16bf22,
 0x3e16bec4,0x3f713f22,0x3f3e3f7b,0xbe793e95,0x3f5c3f80,0xbd493ef1,0xbf67bf0e,0xbf4ebf7f,0x3f183f6d,0xbedb3dc9,0xbf80bf55,0xbf04bf62,0xbf78bf35,0xbf2cbf75,0x3eacbe48,0x3f7d3f46,
 0x3f7d3f35,0x3edb3f62,0xbf3ebe48,0xbf5cbf7f,0x3e79bec4,0x3f803f46,0x3eac3f55,0xbf4ebe95,0xbf180000,0xbf71bf75,0x3d49bf0e,0x3f783f22,0x3f043f6d,0xbf2cbdc9,0xbf67bf7b,0x3e16bef1,
 0xbe16bf35,0x3f673ef1,0x3f2c3f7b,0xbf043dc9,0xbf78bf6d,0xbd49bf22,0x3f713f0e,0x3f183f75,0x3f4e3f80,0xbeac3e95,0xbf80bf55,0xbe79bf46,0x3f5c3ec4,0x3f3e3f7f,0xbedb3e48,0xbf7dbf62,
 0xbedbbf6d,0x3f5c3e95,0x3f183f7b,0xbf3ebdc9,0xbd49bf35,0x3f7d3f22,0x3e793f55,0xbf71bef1,0x3eacbec4,0x3f783f62,0xbe163f0e,0xbf80bf46,0x3f2c0000,0x3f4e3f7f,0xbf043e48,0xbf67bf75,
 0x3f673ec4,0x3f043f75,0xbf4ebe48,0xbf2cbf7f,0x3f803f35,0x3e163f46,0xbf78bf0e,0xbeacbf62,0x3f713f6d,0xbe793ef1,0xbf7dbf55,0x3d49bf22,0x3f3e3f80,0xbf183dc9,0xbf5cbf7b,0x3edbbe95,
 0xbd490000,0xbe16bdc9,0xbe79be48,0xbeacbe95,0xbedbbec4,0xbf04bef1,0xbf18bf0e,0xbf2cbf22,0xbf3ebf35,0xbf4ebf46,0xbf5cbf55,0xbf67bf62,0xbf71bf6d,0xbf78bf75,0xbf7dbf7b,0xbf80bf7f,
 0xbf80bf80,0xbf7dbf7f,0xbf78bf7b,0xbf71bf75,0xbf67bf6d,0xbf5cbf62,0xbf4ebf55,0xbf3ebf46,0xbf2cbf35,0xbf18bf22,0xbf04bf0e,0xbedbbef1,0xbeacbec4,0xbe79be95,0xbe16be48,0xbd49bdc9,
 0xbf78bf6d,0xbf80bf7f,0xbf71bf7b,0xbf4ebf62,0xbe160000,0xbedbbe95,0xbf2cbf0e,0xbf5cbf46,0x3f043ec4,0x3f3e3f22,0x3f673f55,0x3f7d3f75,0xbf18bf35,0xbeacbef1,0xbd49be48,0x3e793dc9,
 0x3e793ec4,0xbd493dc9,0xbeacbe48,0xbf18bef1,0x3f7d3f80,0x3f673f75,0x3f3e3f55,0x3f043f22,0xbf5cbf6d,0xbf2cbf46,0xbedbbf0e,0xbe16be95,0xbf4ebf35,0xbf71bf62,0xbf80bf7b,0xbf78bf7f,
 0x3f5c3f35,0x3f803f75,0x3f673f7b,0x3f183f46,0x3e163ec4,0xbeacbdc9,0xbf3ebf0e,0xbf78bf62,0xbe790000,0xbf2cbef1,0xbf71bf55,0xbf7dbf7f,0xbf4ebf6d,0xbedbbf22,0x3d49be48,0x3f043e95,
 0x3f043f35,0x3d493e95,0xbedbbe48,0xbf4ebf22,0xbf7dbf6d,0xbf71bf7f,0xbf2cbf55,0xbe79bef1,0xbf78bf80,0xbf3ebf62,0xbeacbf0e,0x3e16bdc9,0x3f183ec4,0x3f673f46,0x3f803f7b,0x3f5c3f75,
 0xbf3ebf6d,0xbe16bef1,0x3f043e48,0x3f713f46,0x3edb3f35,0xbe793dc9,0xbf4ebf0e,0xbf80bf75,0xbd49bec4,0x3f183e95,0x3f783f55,0x3f673f7f,0xbeac0000,0xbf5cbf22,0xbf7dbf7b,0xbf2cbf62,
 0xbf2cbec4,0xbf7dbf62,0xbf5cbf7b,0xbeacbf22,0x3f673f35,0x3f783f7f,0x3f183f55,0xbd493e95,0xbf80bf6d,0xbf4ebf75,0xbe79bf0e,0x3edb3dc9,0x3f713f80,0x3f043f46,0xbe163e48,0xbf3ebef1,
 0xbf67bf80,0xbe79bf22,0x3f183e48,0x3f803f62,0x3f2c3f6d,0xbe163e95,0xbf5cbf0e,0xbf71bf7f,0xbeacbf35,0x3f043dc9,0x3f7d3f55,0x3f3e3f75,0xbd493ec4,0xbf4ebef1,0xbf78bf7b,0xbedbbf46,
 0xbedb0000,0xbf78bf46,0xbf4ebf7b,0xbd49bef1,0x3f3e3ec4,0x3f7d3f75,0x3f043f55,0xbeac3dc9,0xbf71bf35,0xbf5cbf7f,0xbe16bf0e,0x3f2c3e95,0x3f803f6d,0x3f183f62,0xbe793e48,0xbf67bf22,
 0x3e16bec4,0x3f713f22,0x3f3e3f7b,0xbe793e95,0x3f5c3f80,0xbd493ef1,0xbf67bf0e,0xbf4ebf7f,0x3f183f6d,0xbedb3dc9,0xbf80bf55,0xbf04bf62,0xbf78bf35,0xbf2cbf75,0x3eacbe48,0x3f7d3f46,
 0x3f7d3f6d,0x3eac3f46,0xbf2cbe48,0xbf78bf75,0xbf040000,0xbf80bf62,0xbedbbf55,0x3f183dc9,0xbf4ebec4,0xbf67bf7f,0xbd49bf0e,0x3f5c3ef1,0xbe79bf35,0x3f3e3e95,0x3f713f7b,0x3e163f22,
 0x3e163f35,0xbf67bef1,0xbf2cbf7b,0x3f04bdc9,0x3f783f6d,0x3d493f22,0xbf71bf0e,0xbf18bf75,0xbf4ebf80,0x3eacbe95,0x3f803f55,0x3e793f46,0xbf5cbec4,0xbf3ebf7f,0x3edbbe48,0x3f7d3f62,
 0x3f7d3f35,0x3edb3f62,0xbf3ebe48,0xbf5cbf7f,0x3e79bec4,0x3f803f46,0x3eac3f55,0xbf4ebe95,0xbf180000,0xbf71bf75,0x3d49bf0e,0x3f783f22,0x3f043f6d,0xbf2cbdc9,0xbf67bf7b,0x3e16bef1,
 0x3f673ec4,0x3f043f75,0xbf4ebe48,0xbf2cbf7f,0x3f803f35,0x3e163f46,0xbf78bf0e,0xbeacbf62,0x3f713f6d,0xbe793ef1,0xbf7dbf55,0x3d49bf22,0x3f3e3f80,0xbf183dc9,0xbf5cbf7b,0x3edbbe95,
 0x3edb3f6d,0xbf5cbe95,0xbf18bf7b,0x3f3e3dc9,0x3d493f35,0xbf7dbf22,0xbe79bf55,0x3f713ef1,0xbeac3ec4,0xbf78bf62,0x3e16bf0e,0x3f803f46,0xbf2c0000,0xbf4ebf7f,0x3f04be48,0x3f673f75,
 0x3f2c3f80,0xbf4ebdc9,0xbf04bf7b,0x3f673e95,0x3eac3f6d,0xbf78bef1,0xbe16bf55,0x3f803f22,0xbd493f35,0xbf7dbf46,0x3e79bf0e,0x3f713f62,0xbedb3ec4,0xbf5cbf75,0x3f18be48,0x3f3e3f7f,
 0xbf3e0000,0xbf18bf7f,0x3f5c3e48,0x3edb3f75,0xbf71bec4,0xbe79bf62,0x3f7d3f0e,0x3d493f46,0xbf80bf35,0x3e16bf22,0x3f783f55,0xbeac3ef1,0xbf67bf6d,0x3f04be95,0x3f4e3f7b,0xbf2c3dc9,
 0xbf043ec4,0xbf2cbf7f,0x3f673e48,0x3e163f62,0x3f183f80,0xbf71be95,0xbd49bf55,0x3f783f46,0xbe79bf6d,0x3f803f22,0xbeac3f0e,0xbf4ebf75,0xbf7dbf35,0x3edbbef1,0x3f3e3f7b,0xbf5cbdc9,
 0x3f5c3f6d,0xbf3e3dc9,0xbedbbf7b,0x3f7d3ef1,0x3f4e0000,0x3eac3f75,0xbf80bf0e,0x3e79bf22,0xbf78bec4,0x3d49bf46,0x3f713f55,0xbf183e95,0xbe163f35,0xbf67bf62,0x3f2cbe48,0x3f043f7f,
 0x3e79bf35,0x3f3e3f75,0xbf71be48,0x3e16bf46,0x3f4e3f6d,0xbf67bdc9,0x3d49bf55,0x3f5c3f62,0x3f043f80,0xbf80bef1,0x3edbbf0e,0x3f183f7f,0xbf7dbec4,0x3eacbf22,0x3f2c3f7b,0xbf78be95,
 0x3f783f35,0xbf2c3e95,0xbeacbf7b,0x3f7d3f22,0xbf183ec4,0xbedbbf7f,0x3f803f0e,0xbf043ef1,0xbf5c0000,0xbd49bf62,0x3f673f55,0xbf4e3dc9,0xbe16bf6d,0x3f713f46,0xbf3e3e48,0xbe79bf75,
 0xbf80bec4,0x3f18bef1,0x3e793f7b,0xbf67bf46,0x3f713f35,0xbf5c3dc9,0x3e16bf55,0x3f2c3f75,0xbf3ebf6d,0x3f7d3e95,0xbf043f0e,0xbeacbf7f,0x3edb3f80,0xbf78bf22,0x3f4ebe48,0xbd493f62,
 0x3d493f6d,0xbf4ebf62,0x3f783e48,0xbedb3f22,0x3eacbf35,0x3f043f7f,0xbf7dbf0e,0x3f3ebe95,0xbf2c3ec4,0xbe16bf75,0x3f5c3f55,0xbf71bdc9,0x3f670000,0xbe793f46,0xbf18bf7b,0x3f803ef1,
 0xbf710000,0x3f04bf22,0x3e163f7b,0xbf3ebf62,0x3f803ec4,0xbf4e3e95,0x3e79bf55,0x3edb3f7f,0xbf67bf35,0x3f783dc9,0xbf183f0e,0xbd49bf75,0x3f2c3f6d,0xbf7dbef1,0x3f5cbe48,0xbeac3f46,
 0x3eac3f80,0xbf5cbf46,0x3f7d3e48,0xbf2c3ef1,0x3d49bf6d,0x3f183f75,0xbf78bf0e,0x3f67bdc9,0xbedb3f35,0xbe79bf7f,0x3f4e3f55,0xbf80be95,0x3f3ebec4,0xbe163f62,0xbf04bf7b,0x3f713f22,
 0xbf18bf6d,0x3f673f22,0xbf80be48,0x3f5cbe95,0x3f780000,0xbf3e3ef1,0x3eacbf55,0x3e163f7f,0x3f7d3ec4,0xbf713dc9,0x3f2cbf0e,0xbe793f62,0xbf043f35,0x3d49bf75,0x3edb3f7b,0xbf4ebf46,
 0x3f4ebec4,0xbedb3f46,0xbd49bf7b,0x3f043f75,0x3e793f80,0xbf2cbf62,0x3f713f0e,0xbf7dbdc9,0xbe163f6d,0xbeacbf7f,0x3f3e3f55,0xbf78bef1,0xbf5cbf35,0x3f803e95,0xbf673e48,0x3f18bf22,
 0x3f4e3f35,0xbf71bef1,0x3f803e48,0xbf783dc9,0x3f5cbec4,0xbf2c3f22,0x3edbbf55,0xbe163f75,0xbf7d0000,0x3f67be95,0xbf3e3f0e,0x3f04bf46,0xbe793f6d,0xbd49bf7f,0x3eac3f7b,0xbf18bf62,
 0x3f18bf35,0xbeac3f62,0x3d49bf7b,0x3e793f7f,0xbf04bf6d,0x3f3e3f46,0xbf67bf0e,0x3f7d3e95,0x3e163f80,0xbedbbf75,0x3f2c3f55,0xbf5cbf22,0x3f783ec4,0xbf80bdc9,0x3f71be48,0xbf4e3ef1,
 0x3eacbf6d,0xbe793f75,0x3e16bf7b,0xbd493f7f,0x3f2cbf35,0xbf183f46,0x3f04bf55,0xbedb3f62,0x3f67bec4,0xbf5c3ef1,0x3f4ebf0e,0xbf3e3f22,0x3f800000,0xbf7d3dc9,0x3f78be48,0xbf713e95,
 0x3f713ec4,0xbf78be95,0x3f7d3e48,0xbf80bdc9,0x3f3e3f35,0xbf4ebf22,0x3f5c3f0e,0xbf67bef1,0x3edb3f6d,0xbf04bf62,0x3f183f55,0xbf2cbf46,0x3d493f80,0xbe16bf7f,0x3e793f7b,0xbeacbf75,
 0xbf3e0000,0xbf18bf7f,0x3f5c3e48,0x3edb3f75,0xbf71bec4,0xbe79bf62,0x3f7d3f0e,0x3d493f46,0xbf80bf35,0x3e16bf22,0x3f783f55,0xbeac3ef1,0xbf67bf6d,0x3f04be95,0x3f4e3f7b,0xbf2c3dc9,
 0xbf2cbf80,0x3f4e3dc9,0x3f043f7b,0xbf67be95,0xbeacbf6d,0x3f783ef1,0x3e163f55,0xbf80bf22,0x3d49bf35,0x3f7d3f46,0xbe793f0e,0xbf71bf62,0x3edbbec4,0x3f5c3f75,0xbf183e48,0xbf3ebf7f,
 0xbf5cbf6d,0x3f3ebdc9,0x3edb3f7b,0xbf7dbef1,0xbf4e0000,0xbeacbf75,0x3f803f0e,0xbe793f22,0x3f783ec4,0xbd493f46,0xbf71bf55,0x3f18be95,0x3e16bf35,0x3f673f62,0xbf2c3e48,0xbf04bf7f,
 0xbf043ec4,0xbf2cbf7f,0x3f673e48,0x3e163f62,0x3f183f80,0xbf71be95,0xbd49bf55,0x3f783f46,0xbe79bf6d,0x3f803f22,0xbeac3f0e,0xbf4ebf75,0xbf7dbf35,0x3edbbef1,0x3f3e3f7b,0xbf5cbdc9,
 0x3f783f35,0xbf2c3e95,0xbeacbf7b,0x3f7d3f22,0xbf183ec4,0xbedbbf7f,0x3f803f0e,0xbf043ef1,0xbf5c0000,0xbd49bf62,0x3f673f55,0xbf4e3dc9,0xbe16bf6d,0x3f713f46,0xbf3e3e48,0xbe79bf75,
 0xbe793f35,0xbf3ebf75,0x3f713e48,0xbe163f46,0xbf4ebf6d,0x3f673dc9,0xbd493f55,0xbf5cbf62,0xbf04bf80,0x3f803ef1,0xbedb3f0e,0xbf18bf7f,0x3f7d3ec4,0xbeac3f22,0xbf2cbf7b,0x3f783e95,
 0xbd49bf6d,0x3f4e3f62,0xbf78be48,0x3edbbf22,0xbeac3f35,0xbf04bf7f,0x3f7d3f0e,0xbf3e3e95,0x3f2cbec4,0x3e163f75,0xbf5cbf55,0x3f713dc9,0xbf670000,0x3e79bf46,0x3f183f7b,0xbf80bef1,
 0xbf80bec4,0x3f18bef1,0x3e793f7b,0xbf67bf46,0x3f713f35,0xbf5c3dc9,0x3e16bf55,0x3f2c3f75,0xbf3ebf6d,0x3f7d3e95,0xbf043f0e,0xbeacbf7f,0x3edb3f80,0xbf78bf22,0x3f4ebe48,0xbd493f62,
 0xbeacbf80,0x3f5c3f46,0xbf7dbe48,0x3f2cbef1,0xbd493f6d,0xbf18bf75,0x3f783f0e,0xbf673dc9,0x3edbbf35,0x3e793f7f,0xbf4ebf55,0x3f803e95,0xbf3e3ec4,0x3e16bf62,0x3f043f7b,0xbf71bf22,
 0xbf710000,0x3f04bf22,0x3e163f7b,0xbf3ebf62,0x3f803ec4,0xbf4e3e95,0x3e79bf55,0x3edb3f7f,0xbf67bf35,0x3f783dc9,0xbf183f0e,0xbd49bf75,0x3f2c3f6d,0xbf7dbef1,0x3f5cbe48,0xbeac3f46,
 0x3f4ebec4,0xbedb3f46,0xbd49bf7b,0x3f043f75,0x3e793f80,0xbf2cbf62,0x3f713f0e,0xbf7dbdc9,0xbe163f6d,0xbeacbf7f,0x3f3e3f55,0xbf78bef1,0xbf5cbf35,0x3f803e95,0xbf673e48,0x3f18bf22,
 0x3f183f6d,0xbf67bf22,0x3f803e48,0xbf5c3e95,0xbf780000,0x3f3ebef1,0xbeac3f55,0xbe16bf7f,0xbf7dbec4,0x3f71bdc9,0xbf2c3f0e,0x3e79bf62,0x3f04bf35,0xbd493f75,0xbedbbf7b,0x3f4e3f46,
 0xbf183f35,0x3eacbf62,0xbd493f7b,0xbe79bf7f,0x3f043f6d,0xbf3ebf46,0x3f673f0e,0xbf7dbe95,0xbe16bf80,0x3edb3f75,0xbf2cbf55,0x3f5c3f22,0xbf78bec4,0x3f803dc9,0xbf713e48,0x3f4ebef1,
 0x3f4e3f35,0xbf71bef1,0x3f803e48,0xbf783dc9,0x3f5cbec4,0xbf2c3f22,0x3edbbf55,0xbe163f75,0xbf7d0000,0x3f67be95,0xbf3e3f0e,0x3f04bf46,0xbe793f6d,0xbd49bf7f,0x3eac3f7b,0xbf18bf62,
 0x3f713ec4,0xbf78be95,0x3f7d3e48,0xbf80bdc9,0x3f3e3f35,0xbf4ebf22,0x3f5c3f0e,0xbf67bef1,0x3edb3f6d,0xbf04bf62,0x3f183f55,0xbf2cbf46,0x3d493f80,0xbe16bf7f,0x3e793f7b,0xbeacbf75,
 0xbeac3f6d,0x3e79bf75,0xbe163f7b,0x3d49bf7f,0xbf2c3f35,0x3f18bf46,0xbf043f55,0x3edbbf62,0xbf673ec4,0x3f5cbef1,0xbf4e3f0e,0x3f3ebf22,0xbf800000,0x3f7dbdc9,0xbf783e48,0x3f71be95,
 0xbd493f80,0x3e16bf7f,0xbe793f7b,0x3eacbf75,0xbedb3f6d,0x3f04bf62,0xbf183f55,0x3f2cbf46,0xbf3e3f35,0x3f4ebf22,0xbf5c3f0e,0x3f67bef1,0xbf713ec4,0x3f78be95,0xbf7d3e48,0x3f80bdc9,
 0xbf800000,0x3f7d3dc9,0xbf78be48,0x3f713e95,0xbf67bec4,0x3f5c3ef1,0xbf4ebf0e,0x3f3e3f22,0xbf2cbf35,0x3f183f46,0xbf04bf55,0x3edb3f62,0xbeacbf6d,0x3e793f75,0xbe16bf7b,0x3d493f7f,
 0xbf783ec4,0x3f80bdc9,0xbf71be48,0x3f4e3ef1,0xbe163f80,0x3edbbf75,0xbf2c3f55,0x3f5cbf22,0x3f04bf6d,0xbf3e3f46,0x3f67bf0e,0xbf7d3e95,0xbf18bf35,0x3eac3f62,0xbd49bf7b,0xbe793f7f,
 0x3e793f6d,0x3d49bf7f,0xbeac3f7b,0x3f18bf62,0x3f7d0000,0xbf67be95,0x3f3e3f0e,0xbf04bf46,0xbf5cbec4,0x3f2c3f22,0xbedbbf55,0x3e163f75,0xbf4e3f35,0x3f71bef1,0xbf803e48,0x3f783dc9,
 0x3f5cbf35,0xbf803e95,0x3f673e48,0xbf18bf22,0x3e163f6d,0x3eacbf7f,0xbf3e3f55,0x3f78bef1,0xbe793f80,0x3f2cbf62,0xbf713f0e,0x3f7dbdc9,0xbf4ebec4,0x3edb3f46,0x3d49bf7b,0xbf043f75,
 0x3f043f35,0xbd49bf75,0xbedb3f7b,0x3f4ebf46,0xbf7d3ec4,0x3f713dc9,0xbf2cbf0e,0x3e793f62,0xbf780000,0x3f3e3ef1,0xbeacbf55,0xbe163f7f,0x3f18bf6d,0xbf673f22,0x3f80be48,0xbf5cbe95,
 0xbf3ebec4,0x3e163f62,0x3f04bf7b,0xbf713f22,0x3edb3f35,0x3e79bf7f,0xbf4e3f55,0x3f80be95,0xbd49bf6d,0xbf183f75,0x3f78bf0e,0xbf67bdc9,0xbeac3f80,0x3f5cbf46,0xbf7d3e48,0x3f2c3ef1,
 0xbf2c3f6d,0x3f7dbef1,0xbf5cbe48,0x3eac3f46,0x3f67bf35,0xbf783dc9,0x3f183f0e,0x3d49bf75,0xbf803ec4,0x3f4e3e95,0xbe79bf55,0xbedb3f7f,0x3f710000,0xbf04bf22,0xbe163f7b,0x3f3ebf62,
 0xbf670000,0x3e793f46,0x3f18bf7b,0xbf803ef1,0x3f2c3ec4,0x3e16bf75,0xbf5c3f55,0x3f71bdc9,0xbeacbf35,0xbf043f7f,0x3f7dbf0e,0xbf3ebe95,0xbd493f6d,0x3f4ebf62,0xbf783e48,0x3edb3f22,
 0xbedb3f80,0x3f78bf22,0xbf4ebe48,0x3d493f62,0x3f3ebf6d,0xbf7d3e95,0x3f043f0e,0x3eacbf7f,0xbf713f35,0x3f5c3dc9,0xbe16bf55,0xbf2c3f75,0x3f80bec4,0xbf18bef1,0xbe793f7b,0x3f67bf46,
 0x3e16bf6d,0xbf713f46,0x3f3e3e48,0x3e79bf75,0x3f5c0000,0x3d49bf62,0xbf673f55,0x3f4e3dc9,0x3f183ec4,0x3edbbf7f,0xbf803f0e,0x3f043ef1,0xbf783f35,0x3f2c3e95,0x3eacbf7b,0xbf7d3f22,
 0x3f7dbec4,0xbeacbf22,0xbf2c3f7b,0x3f78be95,0xbf043f80,0x3f80bef1,0xbedbbf0e,0xbf183f7f,0xbf4e3f6d,0x3f67bdc9,0xbd49bf55,0xbf5c3f62,0xbe79bf35,0xbf3e3f75,0x3f71be48,0xbe16bf46,
 0x3e163f35,0x3f67bf62,0xbf2cbe48,0xbf043f7f,0x3f78bec4,0xbd49bf46,0xbf713f55,0x3f183e95,0xbf4e0000,0xbeac3f75,0x3f80bf0e,0xbe79bf22,0xbf5c3f6d,0x3f3e3dc9,0x3edbbf7b,0xbf7d3ef1,
 0x3f7dbf35,0xbedbbef1,0xbf3e3f7b,0x3f5cbdc9,0x3e79bf6d,0xbf803f22,0x3eac3f0e,0x3f4ebf75,0xbf183f80,0x3f71be95,0x3d49bf55,0xbf783f46,0x3f043ec4,0x3f2cbf7f,0xbf673e48,0xbe163f62,
 0x3f67bf6d,0xbf04be95,0xbf4e3f7b,0x3f2c3dc9,0x3f80bf35,0xbe16bf22,0xbf783f55,0x3eac3ef1,0x3f71bec4,0x3e79bf62,0xbf7d3f0e,0xbd493f46,0x3f3e0000,0x3f18bf7f,0xbf5c3e48,0xbedb3f75,
 0x3edb3ec4,0x3f5cbf75,0xbf18be48,0xbf3e3f7f,0x3d493f35,0x3f7dbf46,0xbe79bf0e,0xbf713f62,0xbeac3f6d,0x3f78bef1,0x3e16bf55,0xbf803f22,0xbf2c3f80,0x3f4ebdc9,0x3f04bf7b,0xbf673e95,
 0xbf800000,0x3f7d3dc9,0xbf78be48,0x3f713e95,0xbf67bec4,0x3f5c3ef1,0xbf4ebf0e,0x3f3e3f22,0xbf2cbf35,0x3f183f46,0xbf04bf55,0x3edb3f62,0xbeacbf6d,0x3e793f75,0xbe16bf7b,0x3d493f7f,
 0x3d49bf80,0xbe163f7f,0x3e79bf7b,0xbeac3f75,0x3edbbf6d,0xbf043f62,0x3f18bf55,0xbf2c3f46,0x3f3ebf35,0xbf4e3f22,0x3f5cbf0e,0xbf673ef1,0x3f71bec4,0xbf783e95,0x3f7dbe48,0xbf803dc9,
 0xbe79bf6d,0xbd493f7f,0x3eacbf7b,0xbf183f62,0xbf7d0000,0x3f673e95,0xbf3ebf0e,0x3f043f46,0x3f5c3ec4,0xbf2cbf22,0x3edb3f55,0xbe16bf75,0x3f4ebf35,0xbf713ef1,0x3f80be48,0xbf78bdc9,
 0xbf783ec4,0x3f80bdc9,0xbf71be48,0x3f4e3ef1,0xbe163f80,0x3edbbf75,0xbf2c3f55,0x3f5cbf22,0x3f04bf6d,0xbf3e3f46,0x3f67bf0e,0xbf7d3e95,0xbf18bf35,0x3eac3f62,0xbd49bf7b,0xbe793f7f,
 0x3f043f35,0xbd49bf75,0xbedb3f7b,0x3f4ebf46,0xbf7d3ec4,0x3f713dc9,0xbf2cbf0e,0x3e793f62,0xbf780000,0x3f3e3ef1,0xbeacbf55,0xbe163f7f,0x3f18bf6d,0xbf673f22,0x3f80be48,0xbf5cbe95,
 0xbf5c3f35,0x3f80be95,0xbf67be48,0x3f183f22,0xbe16bf6d,0xbeac3f7f,0x3f3ebf55,0xbf783ef1,0x3e79bf80,0xbf2c3f62,0x3f71bf0e,0xbf7d3dc9,0x3f4e3ec4,0xbedbbf46,0xbd493f7b,0x3f04bf75,
 0x3f2cbf6d,0xbf7d3ef1,0x3f5c3e48,0xbeacbf46,0xbf673f35,0x3f78bdc9,0xbf18bf0e,0xbd493f75,0x3f80bec4,0xbf4ebe95,0x3e793f55,0x3edbbf7f,0xbf710000,0x3f043f22,0x3e16bf7b,0xbf3e3f62,
 0xbf3ebec4,0x3e163f62,0x3f04bf7b,0xbf713f22,0x3edb3f35,0x3e79bf7f,0xbf4e3f55,0x3f80be95,0xbd49bf6d,0xbf183f75,0x3f78bf0e,0xbf67bdc9,0xbeac3f80,0x3f5cbf46,0xbf7d3e48,0x3f2c3ef1,
 0x3edbbf80,0xbf783f22,0x3f4e3e48,0xbd49bf62,0xbf3e3f6d,0x3f7dbe95,0xbf04bf0e,0xbeac3f7f,0x3f71bf35,0xbf5cbdc9,0x3e163f55,0x3f2cbf75,0xbf803ec4,0x3f183ef1,0x3e79bf7b,0xbf673f46,
 0xbf670000,0x3e793f46,0x3f18bf7b,0xbf803ef1,0x3f2c3ec4,0x3e16bf75,0xbf5c3f55,0x3f71bdc9,0xbeacbf35,0xbf043f7f,0x3f7dbf0e,0xbf3ebe95,0xbd493f6d,0x3f4ebf62,0xbf783e48,0x3edb3f22,
 0x3f7dbec4,0xbeacbf22,0xbf2c3f7b,0x3f78be95,0xbf043f80,0x3f80bef1,0xbedbbf0e,0xbf183f7f,0xbf4e3f6d,0x3f67bdc9,0xbd49bf55,0xbf5c3f62,0xbe79bf35,0xbf3e3f75,0x3f71be48,0xbe16bf46,
 0xbe163f6d,0x3f71bf46,0xbf3ebe48,0xbe793f75,0xbf5c0000,0xbd493f62,0x3f67bf55,0xbf4ebdc9,0xbf18bec4,0xbedb3f7f,0x3f80bf0e,0xbf04bef1,0x3f78bf35,0xbf2cbe95,0xbeac3f7b,0x3f7dbf22,
 0xbf7d3f35,0x3edb3ef1,0x3f3ebf7b,0xbf5c3dc9,0xbe793f6d,0x3f80bf22,0xbeacbf0e,0xbf4e3f75,0x3f18bf80,0xbf713e95,0xbd493f55,0x3f78bf46,0xbf04bec4,0xbf2c3f7f,0x3f67be48,0x3e16bf62,
 0x3e163f35,0x3f67bf62,0xbf2cbe48,0xbf043f7f,0x3f78bec4,0xbd49bf46,0xbf713f55,0x3f183e95,0xbf4e0000,0xbeac3f75,0x3f80bf0e,0xbe79bf22,0xbf5c3f6d,0x3f3e3dc9,0x3edbbf7b,0xbf7d3ef1,
 0x3edb3ec4,0x3f5cbf75,0xbf18be48,0xbf3e3f7f,0x3d493f35,0x3f7dbf46,0xbe79bf0e,0xbf713f62,0xbeac3f6d,0x3f78bef1,0x3e16bf55,0xbf803f22,0xbf2c3f80,0x3f4ebdc9,0x3f04bf7b,0xbf673e95,
 0xbf673f6d,0x3f043e95,0x3f4ebf7b,0xbf2cbdc9,0xbf803f35,0x3e163f22,0x3f78bf55,0xbeacbef1,0xbf713ec4,0xbe793f62,0x3f7dbf0e,0x3d49bf46,0xbf3e0000,0xbf183f7f,0x3f5cbe48,0x3edbbf75,
 0xbf3e3f80,0x3f183dc9,0x3f5cbf7b,0xbedbbe95,0xbf713f6d,0x3e793ef1,0x3f7dbf55,0xbd49bf22,0xbf803f35,0xbe163f46,0x3f78bf0e,0x3eacbf62,0xbf673ec4,0xbf043f75,0x3f4ebe48,0x3f2cbf7f,
 0xbf2c0000,0xbf4e3f7f,0x3f043e48,0x3f67bf75,0xbeacbec4,0xbf783f62,0x3e163f0e,0x3f80bf46,0x3d49bf35,0xbf7d3f22,0xbe793f55,0x3f71bef1,0x3edbbf6d,0xbf5c3e95,0xbf183f7b,0x3f3ebdc9,
 0xbf5c3ec4,0xbf3e3f7f,0x3edb3e48,0x3f7dbf62,0xbf4e3f80,0x3eac3e95,0x3f80bf55,0x3e79bf46,0x3f78bf6d,0x3d49bf22,0xbf713f0e,0xbf183f75,0x3e16bf35,0xbf673ef1,0xbf2c3f7b,0x3f043dc9,
 0xbf043f6d,0x3f2cbdc9,0x3f67bf7b,0xbe16bef1,0x3f180000,0x3f71bf75,0xbd49bf0e,0xbf783f22,0xbe79bec4,0xbf803f46,0xbeac3f55,0x3f4ebe95,0xbf7d3f35,0xbedb3f62,0x3f3ebe48,0x3f5cbf7f,
 0x3f78bf35,0x3f2cbf75,0xbeacbe48,0xbf7d3f46,0xbf183f6d,0x3edb3dc9,0x3f80bf55,0x3f04bf62,0xbf5c3f80,0x3d493ef1,0x3f67bf0e,0x3f4ebf7f,0xbe16bec4,0xbf713f22,0xbf3e3f7b,0x3e793e95,
 0xbe793f35,0x3f3ebe95,0x3f71bf7b,0x3e16bf22,0xbf4e3ec4,0xbf673f7f,0xbd493f0e,0x3f5cbef1,0xbf040000,0xbf803f62,0xbedb3f55,0x3f18bdc9,0x3f7dbf6d,0x3eacbf46,0xbf2c3e48,0xbf783f75,
 0xbd49bec4,0xbf4e3ef1,0xbf783f7b,0xbedb3f46,0xbeac3f35,0x3f04bdc9,0x3f7dbf55,0x3f3ebf75,0x3f2cbf6d,0xbe16be95,0xbf5c3f0e,0xbf713f7f,0xbf673f80,0xbe793f22,0x3f18be48,0x3f80bf62,
 0xbf803f6d,0xbf183f62,0x3e793e48,0x3f67bf22,0x3f71bf35,0x3f5cbf7f,0x3e16bf0e,0xbf2c3e95,0xbf3e3ec4,0xbf7d3f75,0xbf043f55,0x3eac3dc9,0x3edb0000,0x3f78bf46,0x3f4ebf7b,0x3d49bef1,
 0xbeac0000,0xbf5c3f22,0xbf7d3f7b,0xbf2c3f62,0xbd493ec4,0x3f18be95,0x3f78bf55,0x3f67bf7f,0x3edbbf35,0xbe79bdc9,0xbf4e3f0e,0xbf803f75,0xbf3e3f6d,0xbe163ef1,0x3f04be48,0x3f71bf46,
 0xbf713f80,0xbf043f46,0x3e163e48,0x3f3ebef1,0x3f80bf6d,0x3f4ebf75,0x3e79bf0e,0xbedb3dc9,0xbf673f35,0xbf783f7f,0xbf183f55,0x3d493e95,0x3f2cbec4,0x3f7dbf62,0x3f5cbf7b,0x3eacbf22,
 0x3f4ebf6d,0x3edbbf22,0xbd49be48,0xbf043e95,0x3e790000,0x3f2cbef1,0x3f71bf55,0x3f7dbf7f,0xbe163ec4,0x3eacbdc9,0x3f3ebf0e,0x3f78bf62,0xbf5c3f35,0xbf803f75,0xbf673f7b,0xbf183f46,
 0x3f18bec4,0x3f67bf46,0x3f80bf7b,0x3f5cbf75,0xbf783f80,0xbf3e3f62,0xbeac3f0e,0x3e163dc9,0xbf7d3f6d,0xbf713f7f,0xbf2c3f55,0xbe793ef1,0x3f04bf35,0x3d49be95,0xbedb3e48,0xbf4e3f22,
 0xbf183f35,0xbeac3ef1,0xbd493e48,0x3e79bdc9,0x3f04bec4,0x3f3ebf22,0x3f67bf55,0x3f7dbf75,0xbe160000,0xbedb3e95,0xbf2c3f0e,0xbf5c3f46,0xbf783f6d,0xbf803f7f,0xbf713f7b,0xbf4e3f62,
 0x3f4ebf35,0x3f71bf62,0x3f80bf7b,0x3f78bf7f,0x3f5cbf6d,0x3f2cbf46,0x3edbbf0e,0x3e16be95,0xbf7d3f80,0xbf673f75,0xbf3e3f55,0xbf043f22,0xbe793ec4,0x3d493dc9,0x3eacbe48,0x3f18bef1,
 0x3f71bf6d,0x3f78bf75,0x3f7dbf7b,0x3f80bf7f,0x3f3ebf35,0x3f4ebf46,0x3f5cbf55,0x3f67bf62,0x3edbbec4,0x3f04bef1,0x3f18bf0e,0x3f2cbf22,0x3d490000,0x3e16bdc9,0x3e79be48,0x3eacbe95,
 0xbeac3ec4,0xbe793e95,0xbe163e48,0xbd493dc9,0xbf2c3f35,0xbf183f22,0xbf043f0e,0xbedb3ef1,0xbf673f6d,0xbf5c3f62,0xbf4e3f55,0xbf3e3f46,0xbf803f80,0xbf7d3f7f,0xbf783f7b,0xbf713f75,
 0xbf2c0000,0xbf4e3f7f,0x3f043e48,0x3f67bf75,0xbeacbec4,0xbf783f62,0x3e163f0e,0x3f80bf46,0x3d49bf35,0xbf7d3f22,0xbe793f55,0x3f71bef1,0x3edbbf6d,0xbf5c3e95,0xbf183f7b,0x3f3ebdc9,
 0x3f3ebf80,0xbf18bdc9,0xbf5c3f7b,0x3edb3e95,0x3f71bf6d,0xbe79bef1,0xbf7d3f55,0x3d493f22,0x3f80bf35,0x3e16bf46,0xbf783f0e,0xbeac3f62,0x3f67bec4,0x3f04bf75,0xbf4e3e48,0xbf2c3f7f,
 0x3f04bf6d,0xbf2c3dc9,0xbf673f7b,0x3e163ef1,0xbf180000,0xbf713f75,0x3d493f0e,0x3f78bf22,0x3e793ec4,0x3f80bf46,0x3eacbf55,0xbf4e3e95,0x3f7dbf35,0x3edbbf62,0xbf3e3e48,0xbf5c3f7f,
 0xbf5c3ec4,0xbf3e3f7f,0x3edb3e48,0x3f7dbf62,0xbf4e3f80,0x3eac3e95,0x3f80bf55,0x3e79bf46,0x3f78bf6d,0x3d49bf22,0xbf713f0e,0xbf183f75,0x3e16bf35,0xbf673ef1,0xbf2c3f7b,0x3f043dc9,
 0xbe793f35,0x3f3ebe95,0x3f71bf7b,0x3e16bf22,0xbf4e3ec4,0xbf673f7f,0xbd493f0e,0x3f5cbef1,0xbf040000,0xbf803f62,0xbedb3f55,0x3f18bdc9,0x3f7dbf6d,0x3eacbf46,0xbf2c3e48,0xbf783f75,
 0xbf783f35,0xbf2c3f75,0x3eac3e48,0x3f7dbf46,0x3f18bf6d,0xbedbbdc9,0xbf803f55,0xbf043f62,0x3f5cbf80,0xbd49bef1,0xbf673f0e,0xbf4e3f7f,0x3e163ec4,0x3f71bf22,0x3f3ebf7b,0xbe79be95,
 0x3f80bf6d,0x3f18bf62,0xbe79be48,0xbf673f22,0xbf713f35,0xbf5c3f7f,0xbe163f0e,0x3f2cbe95,0x3f3ebec4,0x3f7dbf75,0x3f04bf55,0xbeacbdc9,0xbedb0000,0xbf783f46,0xbf4e3f7b,0xbd493ef1,
 0xbd49bec4,0xbf4e3ef1,0xbf783f7b,0xbedb3f46,0xbeac3f35,0x3f04bdc9,0x3f7dbf55,0x3f3ebf75,0x3f2cbf6d,0xbe16be95,0xbf5c3f0e,0xbf713f7f,0xbf673f80,0xbe793f22,0x3f18be48,0x3f80bf62,
 0x3f71bf80,0x3f04bf46,0xbe16be48,0xbf3e3ef1,0xbf803f6d,0xbf4e3f75,0xbe793f0e,0x3edbbdc9,0x3f67bf35,0x3f78bf7f,0x3f18bf55,0xbd49be95,0xbf2c3ec4,0xbf7d3f62,0xbf5c3f7b,0xbeac3f22,
 0xbeac0000,0xbf5c3f22,0xbf7d3f7b,0xbf2c3f62,0xbd493ec4,0x3f18be95,0x3f78bf55,0x3f67bf7f,0x3edbbf35,0xbe79bdc9,0xbf4e3f0e,0xbf803f75,0xbf3e3f6d,0xbe163ef1,0x3f04be48,0x3f71bf46,
 0x3f18bec4,0x3f67bf46,0x3f80bf7b,0x3f5cbf75,0xbf783f80,0xbf3e3f62,0xbeac3f0e,0x3e163dc9,0xbf7d3f6d,0xbf713f7f,0xbf2c3f55,0xbe793ef1,0x3f04bf35,0x3d49be95,0xbedb3e48,0xbf4e3f22,
 0xbf4e3f6d,0xbedb3f22,0x3d493e48,0x3f04be95,0xbe790000,0xbf2c3ef1,0xbf713f55,0xbf7d3f7f,0x3e16bec4,0xbeac3dc9,0xbf3e3f0e,0xbf783f62,0x3f5cbf35,0x3f80bf75,0x3f67bf7b,0x3f18bf46,
 0xbf4e3f35,0xbf713f62,0xbf803f7b,0xbf783f7f,0xbf5c3f6d,0xbf2c3f46,0xbedb3f0e,0xbe163e95,0x3f7dbf80,0x3f67bf75,0x3f3ebf55,0x3f04bf22,0x3e79bec4,0xbd49bdc9,0xbeac3e48,0xbf183ef1,
 0xbf183f35,0xbeac3ef1,0xbd493e48,0x3e79bdc9,0x3f04bec4,0x3f3ebf22,0x3f67bf55,0x3f7dbf75,0xbe160000,0xbedb3e95,0xbf2c3f0e,0xbf5c3f46,0xbf783f6d,0xbf803f7f,0xbf713f7b,0xbf4e3f62,
 0xbeac3ec4,0xbe793e95,0xbe163e48,0xbd493dc9,0xbf2c3f35,0xbf183f22,0xbf043f0e,0xbedb3ef1,0xbf673f6d,0xbf5c3f62,0xbf4e3f55,0xbf3e3f46,0xbf803f80,0xbf7d3f7f,0xbf783f7b,0xbf713f75,
 0xbf713f6d,0xbf783f75,0xbf7d3f7b,0xbf803f7f,0xbf3e3f35,0xbf4e3f46,0xbf5c3f55,0xbf673f62,0xbedb3ec4,0xbf043ef1,0xbf183f0e,0xbf2c3f22,0xbd490000,0xbe163dc9,0xbe793e48,0xbeac3e95,
};
__device__ __align__(128) const uint32_t g_Gimg[1536] = {
 0x00003d00,0x00003d00,0x00003d00,0x00003d00,0x00003d00,0x00003d00,0x00003d00,0x00003d00,0x00003d00,0x00003d00,0x00003d00,0x00003d00,0x00003d00,0x00003d00,0x00003d00,0x00003d00,
 0x00003d00,0x00003d00,0x00003d00,0x00003d00,0x00003d00,0x00003d00,0x00003d00,0x00003d00,0x00003d00,0x00003d00,0x00003d00,0x00003d00,0x00003d00,0x00003d00,0x00003d00,0x00003d00,
 0xbc5b3ce7,0xbc843cdc,0xbc983cce,0xbcac3cbe,0xbac93d00,0xbb963cfd,0xbbf93cf8,0xbc2c3cf1,0xbcf13c2c,0xbcf83bf9,0xbcfd3b96,0xbd003ac9,0xbcbe3cac,0xbcce3c98,0xbcdc3c84,0xbce73c5b,
 0xbce7bc5b,0xbcdcbc84,0xbccebc98,0xbcbebcac,0xbd00bac9,0xbcfdbb96,0xbcf8bbf9,0xbcf1bc2c,0xbc2cbcf1,0xbbf9bcf8,0xbb96bcfd,0xbac9bd00,0xbcacbcbe,0xbc98bcce,0xbc84bcdc,0xbc5bbce7,
 0xbcffbb49,0xbcf5bc15,0xbce2bc71,0xbcc6bca2,0xbca2bcc6,0xbc71bce2,0xbc15bcf5,0xbb49bcff,0xbb493cff,0xbc153cf5,0xbc713ce2,0xbca23cc6,0xbcc63ca2,0xbce23c71,0xbcf53c15,0xbcff3b49,
 0x3cff3b49,0x3cf53c15,0x3ce23c71,0x3cc63ca2,0x3ca23cc6,0x3c713ce2,0x3c153cf5,0x3b493cff,0x3b49bcff,0x3c15bcf5,0x3c71bce2,0x3ca2bcc6,0x3cc6bca2,0x3ce2bc71,0x3cf5bc15,0x3cffbb49,
 0x3c84bcdc,0x3cbebcac,0x3ce7bc5b,0x3cfdbb96,0xbc98bcce,0xbc2cbcf1,0xbac9bd00,0x3bf9bcf8,0xbcf83bf9,0xbd00bac9,0xbcf1bc2c,0xbccebc98,0xbb963cfd,0xbc5b3ce7,0xbcac3cbe,0xbcdc3c84,
 0xbcdcbc84,0xbcacbcbe,0xbc5bbce7,0xbb96bcfd,0xbcce3c98,0xbcf13c2c,0xbd003ac9,0xbcf8bbf9,0x3bf93cf8,0xbac93d00,0xbc2c3cf1,0xbc983cce,0x3cfd3b96,0x3ce73c5b,0x3cbe3cac,0x3c843cdc,
 0xbbc83cfb,0xbc8e3cd5,0xbcd53c8e,0xbcfb3bc8,0xbcfbbbc8,0xbcd5bc8e,0xbc8ebcd5,0xbbc8bcfb,0x3bc8bcfb,0x3c8ebcd5,0x3cd5bc8e,0x3cfbbbc8,0x3cfb3bc8,0x3cd53c8e,0x3c8e3cd5,0x3bc83cfb,
 0xbbc83cfb,0xbc8e3cd5,0xbcd53c8e,0xbcfb3bc8,0xbcfbbbc8,0xbcd5bc8e,0xbc8ebcd5,0xbbc8bcfb,0x3bc8bcfb,0x3c8ebcd5,0x3cd5bc8e,0x3cfbbbc8,0x3cfb3bc8,0x3cd53c8e,0x3c8e3cd5,0x3bc83cfb,
 0x3c98bcce,0x3ce7bc5b,0x3d003ac9,0x3cdc3c84,0xbcf8bbf9,0xbcbebcac,0xbc2cbcf1,0x3b96bcfd,0xbcfd3b96,0xbcf1bc2c,0xbcacbcbe,0xbbf9bcf8,0x3c843cdc,0x3ac93d00,0xbc5b3ce7,0xbcce3c98,
 0xbccebc98,0xbc5bbce7,0x3ac9bd00,0x3c84bcdc,0xbbf93cf8,0xbcac3cbe,0xbcf13c2c,0xbcfdbb96,0x3b963cfd,0xbc2c3cf1,0xbcbe3cac,0xbcf83bf9,0x3cdcbc84,0x3d00bac9,0x3ce73c5b,0x3c983cce,
 0xbcf5bc15,0xbca2bcc6,0xbb49bcff,0x3c71bce2,0x3ce2bc71,0x3cff3b49,0x3cc63ca2,0x3c153cf5,0x3c15bcf5,0x3cc6bca2,0x3cffbb49,0x3ce23c71,0x3c713ce2,0xbb493cff,0xbca23cc6,0xbcf53c15,
 0x3cf53c15,0x3ca23cc6,0x3b493cff,0xbc713ce2,0xbce23c71,0xbcffbb49,0xbcc6bca2,0xbc15bcf5,0xbc153cf5,0xbcc63ca2,0xbcff3b49,0xbce2bc71,0xbc71bce2,0x3b49bcff,0x3ca2bcc6,0x3cf5bc15,
 0xbcac3cbe,0xbcfd3b96,0xbcdcbc84,0xbc2cbcf1,0x3ce7bc5b,0x3cf83bf9,0x3c983cce,0xbac93d00,0xbd003ac9,0xbccebc98,0xbbf9bcf8,0x3c5bbce7,0x3cf13c2c,0x3c843cdc,0xbb963cfd,0xbcbe3cac,
 0xbcbebcac,0xbb96bcfd,0x3c84bcdc,0x3cf1bc2c,0x3c5b3ce7,0xbbf93cf8,0xbcce3c98,0xbd00bac9,0xbac9bd00,0x3c98bcce,0x3cf8bbf9,0x3ce73c5b,0xbc2c3cf1,0xbcdc3c84,0xbcfdbb96,0xbcacbcbe,
 0xbc443ced,0xbced3c44,0xbcedbc44,0xbc44bced,0x3c44bced,0x3cedbc44,0x3ced3c44,0x3c443ced,0xbc443ced,0xbced3c44,0xbcedbc44,0xbc44bced,0x3c44bced,0x3cedbc44,0x3ced3c44,0x3c443ced,
 0xbc443ced,0xbced3c44,0xbcedbc44,0xbc44bced,0x3c44bced,0x3cedbc44,0x3ced3c44,0x3c443ced,0xbc443ced,0xbced3c44,0xbcedbc44,0xbc44bced,0x3c44bced,0x3cedbc44,0x3ced3c44,0x3c443ced,
 0x3cbebcac,0x3cfd3b96,0x3c843cdc,0xbc2c3cf1,0xbc5b3ce7,0xbcf83bf9,0xbccebc98,0xbac9bd00,0x3d003ac9,0x3c983cce,0xbbf93cf8,0xbce73c5b,0xbcf13c2c,0xbcdcbc84,0xbb96bcfd,0x3cacbcbe,
 0x3cac3cbe,0xbb963cfd,0xbcdc3c84,0xbcf1bc2c,0xbce7bc5b,0xbbf9bcf8,0x3c98bcce,0x3d00bac9,0xbac93d00,0xbcce3c98,0xbcf8bbf9,0xbc5bbce7,0xbc2cbcf1,0x3c84bcdc,0x3cfdbb96,0x3cbe3cac,
 0xbce2bc71,0xbb49bcff,0x3cc6bca2,0x3cf53c15,0x3c153cf5,0xbca23cc6,0xbcffbb49,0xbc71bce2,0xbc713ce2,0xbcff3b49,0xbca2bcc6,0x3c15bcf5,0x3cf5bc15,0x3cc63ca2,0xbb493cff,0xbce23c71,
 0x3ce23c71,0x3b493cff,0xbcc63ca2,0xbcf5bc15,0xbc15bcf5,0x3ca2bcc6,0x3cff3b49,0x3c713ce2,0x3c71bce2,0x3cffbb49,0x3ca23cc6,0xbc153cf5,0xbcf53c15,0xbcc6bca2,0x3b49bcff,0x3ce2bc71,
 0xbcce3c98,0xbce7bc5b,0xbac9bd00,0x3cdcbc84,0xbbf9bcf8,0x3cbebcac,0x3cf13c2c,0x3b963cfd,0x3cfd3b96,0x3c2c3cf1,0xbcac3cbe,0xbcf8bbf9,0xbc843cdc,0xbd00bac9,0xbc5bbce7,0x3c98bcce,
 0x3c983cce,0xbc5b3ce7,0xbd003ac9,0xbc84bcdc,0xbcf83bf9,0xbcacbcbe,0x3c2cbcf1,0x3cfdbb96,0x3b96bcfd,0x3cf1bc2c,0x3cbe3cac,0xbbf93cf8,0x3cdc3c84,0xbac93d00,0xbce73c5b,0xbccebc98,
 0xbc8e3cd5,0xbcfbbbc8,0xbbc8bcfb,0x3cd5bc8e,0x3cd53c8e,0xbbc83cfb,0xbcfb3bc8,0xbc8ebcd5,0x3c8ebcd5,0x3cfb3bc8,0x3bc83cfb,0xbcd53c8e,0xbcd5bc8e,0x3bc8bcfb,0x3cfbbbc8,0x3c8e3cd5,
 0xbc8e3cd5,0xbcfbbbc8,0xbbc8bcfb,0x3cd5bc8e,0x3cd53c8e,0xbbc83cfb,0xbcfb3bc8,0xbc8ebcd5,0x3c8ebcd5,0x3cfb3bc8,0x3bc83cfb,0xbcd53c8e,0xbcd5bc8e,0x3bc8bcfb,0x3cfbbbc8,0x3c8e3cd5,
 0xbcdc3c84,0xbcbebcac,0x3c5bbce7,0x3cfd3b96,0xbccebc98,0x3c2cbcf1,0x3d003ac9,0x3bf93cf8,0x3cf83bf9,0x3ac93d00,0xbcf13c2c,0xbc98bcce,0x3b963cfd,0xbce73c5b,0xbcacbcbe,0x3c84bcdc,
 0x3c843cdc,0xbcac3cbe,0xbce7bc5b,0x3b96bcfd,0xbc983cce,0xbcf1bc2c,0x3ac9bd00,0x3cf8bbf9,0x3bf9bcf8,0x3d00bac9,0x3c2c3cf1,0xbcce3c98,0x3cfdbb96,0x3c5b3ce7,0xbcbe3cac,0xbcdcbc84,
 0xbcc6bca2,0x3c71bce2,0x3cf53c15,0xbb493cff,0xbcff3b49,0xbc15bcf5,0x3ce2bc71,0x3ca23cc6,0x3ca2bcc6,0x3ce23c71,0xbc153cf5,0xbcffbb49,0xbb49bcff,0x3cf5bc15,0x3c713ce2,0xbcc63ca2,
 0x3cc63ca2,0xbc713ce2,0xbcf5bc15,0x3b49bcff,0x3cffbb49,0x3c153cf5,0xbce23c71,0xbca2bcc6,0xbca23cc6,0xbce2bc71,0x3c15bcf5,0x3cff3b49,0x3b493cff,0xbcf53c15,0xbc71bce2,0x3cc6bca2,
 0x3ce7bc5b,0x3c843cdc,0xbcce3c98,0xbcacbcbe,0x3d00bac9,0x3b963cfd,0xbcf83bf9,0xbc2cbcf1,0x3cf13c2c,0xbbf93cf8,0xbcfdbb96,0x3ac9bd00,0x3cbe3cac,0xbc983cce,0xbcdcbc84,0x3c5bbce7,
 0x3c5b3ce7,0xbcdc3c84,0xbc98bcce,0x3cbebcac,0x3ac93d00,0xbcfd3b96,0xbbf9bcf8,0x3cf1bc2c,0xbc2c3cf1,0xbcf8bbf9,0x3b96bcfd,0x3d003ac9,0xbcac3cbe,0xbccebc98,0x3c84bcdc,0x3ce73c5b,
 0xbcb53cb5,0xbcb5bcb5,0x3cb5bcb5,0x3cb53cb5,0xbcb53cb5,0xbcb5bcb5,0x3cb5bcb5,0x3cb53cb5,0xbcb53cb5,0xbcb5bcb5,0x3cb5bcb5,0x3cb53cb5,0xbcb53cb5,0xbcb5bcb5,0x3cb5bcb5,0x3cb53cb5,
 0xbcb53cb5,0xbcb5bcb5,0x3cb5bcb5,0x3cb53cb5,0xbcb53cb5,0xbcb5bcb5,0x3cb5bcb5,0x3cb53cb5,0xbcb53cb5,0xbcb5bcb5,0x3cb5bcb5,0x3cb53cb5,0xbcb53cb5,0xbcb5bcb5,0x3cb5bcb5,0x3cb53cb5,
 0xbcf13c2c,0xbbf9bcf8,0x3cfdbb96,0x3ac93d00,0xbcbe3cac,0xbc98bcce,0x3cdcbc84,0x3c5b3ce7,0xbce7bc5b,0x3c84bcdc,0x3cce3c98,0xbcac3cbe,0xbd00bac9,0x3b96bcfd,0x3cf83bf9,0xbc2c3cf1,
 0xbc2cbcf1,0x3cf8bbf9,0x3b963cfd,0xbd003ac9,0xbcacbcbe,0x3ccebc98,0x3c843cdc,0xbce73c5b,0x3c5bbce7,0x3cdc3c84,0xbc983cce,0xbcbebcac,0x3ac9bd00,0x3cfd3b96,0xbbf93cf8,0xbcf1bc2c,
 0xbca2bcc6,0x3ce2bc71,0x3c153cf5,0xbcff3b49,0x3b49bcff,0x3cf53c15,0xbc713ce2,0xbcc6bca2,0xbcc63ca2,0xbc71bce2,0x3cf5bc15,0x3b493cff,0xbcffbb49,0x3c15bcf5,0x3ce23c71,0xbca23cc6,
 0x3ca23cc6,0xbce23c71,0xbc15bcf5,0x3cffbb49,0xbb493cff,0xbcf5bc15,0x3c71bce2,0x3cc63ca2,0x3cc6bca2,0x3c713ce2,0xbcf53c15,0xbb49bcff,0x3cff3b49,0xbc153cf5,0xbce2bc71,0x3ca2bcc6,
 0x3cf8bbf9,0xbac93d00,0xbcf1bc2c,0x3c98bcce,0x3b96bcfd,0x3ce73c5b,0xbcac3cbe,0xbc84bcdc,0xbcdcbc84,0x3cbebcac,0x3c5b3ce7,0xbcfd3b96,0xbcce3c98,0xbc2cbcf1,0x3d00bac9,0xbbf93cf8,
 0xbbf9bcf8,0x3d003ac9,0xbc2c3cf1,0xbccebc98,0xbcfdbb96,0x3c5bbce7,0x3cbe3cac,0xbcdc3c84,0xbc843cdc,0xbcacbcbe,0x3ce7bc5b,0x3b963cfd,0x3c983cce,0xbcf13c2c,0xbac9bd00,0x3cf83bf9,
 0xbcd53c8e,0xbbc8bcfb,0x3cfb3bc8,0xbc8e3cd5,0xbc8ebcd5,0x3cfbbbc8,0xbbc83cfb,0xbcd5bc8e,0x3cd5bc8e,0x3bc83cfb,0xbcfbbbc8,0x3c8ebcd5,0x3c8e3cd5,0xbcfb3bc8,0x3bc8bcfb,0x3cd53c8e,
 0xbcd53c8e,0xbbc8bcfb,0x3cfb3bc8,0xbc8e3cd5,0xbc8ebcd5,0x3cfbbbc8,0xbbc83cfb,0xbcd5bc8e,0x3cd5bc8e,0x3bc83cfb,0xbcfbbbc8,0x3c8ebcd5,0x3c8e3cd5,0xbcfb3bc8,0x3bc8bcfb,0x3cd53c8e,
 0x3cfdbb96,0xbc2c3cf1,0xbcacbcbe,0x3cf8bbf9,0xbc84bcdc,0x3d00bac9,0xbc5b3ce7,0xbc98bcce,0xbccebc98,0x3ce7bc5b,0xbac93d00,0xbcdcbc84,0xbbf93cf8,0xbcbebcac,0x3cf1bc2c,0xbb963cfd,
 0xbb96bcfd,0x3cf13c2c,0xbcbe3cac,0xbbf9bcf8,0xbcdc3c84,0xbac9bd00,0x3ce73c5b,0xbcce3c98,0xbc983cce,0xbc5bbce7,0x3d003ac9,0xbc843cdc,0x3cf83bf9,0xbcac3cbe,0xbc2cbcf1,0x3cfd3b96,
 0xbc71bce2,0x3cff3b49,0xbca23cc6,0xbc15bcf5,0x3cf53c15,0xbcc63ca2,0xbb49bcff,0x3ce23c71,0x3ce2bc71,0xbb493cff,0xbcc6bca2,0x3cf5bc15,0xbc153cf5,0xbca2bcc6,0x3cffbb49,0xbc713ce2,
 0x3c713ce2,0xbcffbb49,0x3ca2bcc6,0x3c153cf5,0xbcf5bc15,0x3cc6bca2,0x3b493cff,0xbce2bc71,0xbce23c71,0x3b49bcff,0x3cc63ca2,0xbcf53c15,0x3c15bcf5,0x3ca23cc6,0xbcff3b49,0x3c71bce2,
 0xbd003ac9,0x3c98bcce,0x3bf93cf8,0xbce7bc5b,0x3cf13c2c,0xbcdc3c84,0x3b96bcfd,0x3cac3cbe,0xbcbebcac,0x3cfdbb96,0xbc843cdc,0xbc2cbcf1,0x3c5b3ce7,0xbcf8bbf9,0x3ccebc98,0xbac93d00,
 0xbac9bd00,0x3cce3c98,0xbcf83bf9,0x3c5bbce7,0xbc2c3cf1,0xbc84bcdc,0x3cfd3b96,0xbcbe3cac,0x3cacbcbe,0x3b963cfd,0xbcdcbc84,0x3cf1bc2c,0xbce73c5b,0x3bf9bcf8,0x3c983cce,0xbd00bac9,
 0xbced3c44,0x3c44bced,0x3c443ced,0xbcedbc44,0x3cedbc44,0xbc443ced,0xbc44bced,0x3ced3c44,0xbced3c44,0x3c44bced,0x3c443ced,0xbcedbc44,0x3cedbc44,0xbc443ced,0xbc44bced,0x3ced3c44,
 0xbced3c44,0x3c44bced,0x3c443ced,0xbcedbc44,0x3cedbc44,0xbc443ced,0xbc44bced,0x3ced3c44,0xbced3c44,0x3c44bced,0x3c443ced,0xbcedbc44,0x3cedbc44,0xbc443ced,0xbc44bced,0x3ced3c44,
 0x3d003ac9,0xbcce3c98,0x3bf9bcf8,0x3c5b3ce7,0xbcf13c2c,0x3c84bcdc,0x3b963cfd,0xbcbebcac,0x3cac3cbe,0xbcfdbb96,0x3cdcbc84,0xbc2c3cf1,0xbce7bc5b,0x3cf8bbf9,0xbc983cce,0xbac9bd00,
 0xbac93d00,0xbc98bcce,0x3cf83bf9,0xbce73c5b,0xbc2cbcf1,0x3cdc3c84,0xbcfd3b96,0x3cacbcbe,0xbcbe3cac,0x3b96bcfd,0x3c843cdc,0xbcf1bc2c,0x3c5bbce7,0x3bf93cf8,0xbccebc98,0x3d00bac9,
 0xbc15bcf5,0x3cc63ca2,0xbcffbb49,0x3ce2bc71,0xbc713ce2,0xbb49bcff,0x3ca23cc6,0xbcf5bc15,0xbcf53c15,0x3ca2bcc6,0xbb493cff,0xbc71bce2,0x3ce23c71,0xbcff3b49,0x3cc6bca2,0xbc153cf5,
 0x3c153cf5,0xbcc6bca2,0x3cff3b49,0xbce23c71,0x3c71bce2,0x3b493cff,0xbca2bcc6,0x3cf53c15,0x3cf5bc15,0xbca23cc6,0x3b49bcff,0x3c713ce2,0xbce2bc71,0x3cffbb49,0xbcc63ca2,0x3c15bcf5,
 0xbcfdbb96,0x3cf1bc2c,0xbcac3cbe,0x3bf9bcf8,0x3c84bcdc,0xbac93d00,0xbc5bbce7,0x3cce3c98,0x3c983cce,0xbce7bc5b,0x3d00bac9,0xbcdc3c84,0xbcf83bf9,0x3cbebcac,0xbc2c3cf1,0xbb96bcfd,
 0xbb963cfd,0xbc2cbcf1,0x3cbe3cac,0xbcf8bbf9,0xbcdcbc84,0x3d003ac9,0xbce73c5b,0x3c98bcce,0x3ccebc98,0xbc5b3ce7,0xbac9bd00,0x3c843cdc,0x3bf93cf8,0xbcacbcbe,0x3cf13c2c,0xbcfd3b96,
 0xbcfb3bc8,0x3cd5bc8e,0xbc8e3cd5,0x3bc8bcfb,0x3bc83cfb,0xbc8ebcd5,0x3cd53c8e,0xbcfbbbc8,0x3cfbbbc8,0xbcd53c8e,0x3c8ebcd5,0xbbc83cfb,0xbbc8bcfb,0x3c8e3cd5,0xbcd5bc8e,0x3cfb3bc8,
 0xbcfb3bc8,0x3cd5bc8e,0xbc8e3cd5,0x3bc8bcfb,0x3bc83cfb,0xbc8ebcd5,0x3cd53c8e,0xbcfbbbc8,0x3cfbbbc8,0xbcd53c8e,0x3c8ebcd5,0xbbc83cfb,0xbbc8bcfb,0x3c8e3cd5,0xbcd5bc8e,0x3cfb3bc8,
 0xbcf8bbf9,0x3d00bac9,0xbcf13c2c,0x3ccebc98,0xbb96bcfd,0x3c5b3ce7,0xbcacbcbe,0x3cdc3c84,0x3c843cdc,0xbcbebcac,0x3ce73c5b,0xbcfdbb96,0xbc983cce,0x3c2cbcf1,0xbac93d00,0xbbf9bcf8,
 0xbbf93cf8,0xbac9bd00,0x3c2c3cf1,0xbc98bcce,0xbcfd3b96,0x3ce7bc5b,0xbcbe3cac,0x3c84bcdc,0x3cdcbc84,0xbcac3cbe,0x3c5bbce7,0xbb963cfd,0x3cce3c98,0xbcf1bc2c,0x3d003ac9,0xbcf83bf9,
 0xbb49bcff,0x3c153cf5,0xbc71bce2,0x3ca23cc6,0xbcc6bca2,0x3ce23c71,0xbcf5bc15,0x3cff3b49,0x3cffbb49,0xbcf53c15,0x3ce2bc71,0xbcc63ca2,0x3ca2bcc6,0xbc713ce2,0x3c15bcf5,0xbb493cff,
 0x3b493cff,0xbc15bcf5,0x3c713ce2,0xbca2bcc6,0x3cc63ca2,0xbce2bc71,0x3cf53c15,0xbcffbb49,0xbcff3b49,0x3cf5bc15,0xbce23c71,0x3cc6bca2,0xbca23cc6,0x3c71bce2,0xbc153cf5,0x3b49bcff,
 0x3cf13c2c,0xbcf8bbf9,0x3cfd3b96,0xbd00bac9,0x3cbe3cac,0xbccebc98,0x3cdc3c84,0xbce7bc5b,0x3c5b3ce7,0xbc84bcdc,0x3c983cce,0xbcacbcbe,0x3ac93d00,0xbb96bcfd,0x3bf93cf8,0xbc2cbcf1,
 0xbc2c3cf1,0x3bf9bcf8,0xbb963cfd,0x3ac9bd00,0xbcac3cbe,0x3c98bcce,0xbc843cdc,0x3c5bbce7,0xbce73c5b,0x3cdcbc84,0xbcce3c98,0x3cbebcac,0xbd003ac9,0x3cfdbb96,0xbcf83bf9,0x3cf1bc2c,
 0xbd000000,0x3d000000,0xbd000000,0x3d000000,0xbd000000,0x3d000000,0xbd000000,0x3d000000,0xbd000000,0x3d000000,0xbd000000,0x3d000000,0xbd000000,0x3d000000,0xbd000000,0x3d000000,
 0xbd000000,0x3d000000,0xbd000000,0x3d000000,0xbd000000,0x3d000000,0xbd000000,0x3d000000,0xbd000000,0x3d000000,0xbd000000,0x3d000000,0xbd000000,0x3d000000,0xbd000000,0x3d000000,
 0xbce7bc5b,0x3cdc3c84,0xbccebc98,0x3cbe3cac,0xbd00bac9,0x3cfd3b96,0xbcf8bbf9,0x3cf13c2c,0xbc2cbcf1,0x3bf93cf8,0xbb96bcfd,0x3ac93d00,0xbcacbcbe,0x3c983cce,0xbc84bcdc,0x3c5b3ce7,
 0x3c5bbce7,0xbc843cdc,0x3c98bcce,0xbcac3cbe,0x3ac9bd00,0xbb963cfd,0x3bf9bcf8,0xbc2c3cf1,0x3cf1bc2c,0xbcf83bf9,0x3cfdbb96,0xbd003ac9,0x3cbebcac,0xbcce3c98,0x3cdcbc84,0xbce73c5b,
 0x3b49bcff,0xbc153cf5,0x3c71bce2,0xbca23cc6,0x3cc6bca2,0xbce23c71,0x3cf5bc15,0xbcff3b49,0xbcffbb49,0x3cf53c15,0xbce2bc71,0x3cc63ca2,0xbca2bcc6,0x3c713ce2,0xbc15bcf5,0x3b493cff,
 0xbb493cff,0x3c15bcf5,0xbc713ce2,0x3ca2bcc6,0xbcc63ca2,0x3ce2bc71,0xbcf53c15,0x3cffbb49,0x3cff3b49,0xbcf5bc15,0x3ce23c71,0xbcc6bca2,0x3ca23cc6,0xbc71bce2,0x3c153cf5,0xbb49bcff,
 0x3cdc3c84,0xbcacbcbe,0x3c5b3ce7,0xbb96bcfd,0x3ccebc98,0xbcf13c2c,0x3d00bac9,0xbcf8bbf9,0xbbf9bcf8,0xbac93d00,0x3c2cbcf1,0xbc983cce,0xbcfdbb96,0x3ce73c5b,0xbcbebcac,0x3c843cdc,
 0x3c84bcdc,0xbcbe3cac,0x3ce7bc5b,0xbcfd3b96,0xbc98bcce,0x3c2c3cf1,0xbac9bd00,0xbbf93cf8,0xbcf83bf9,0x3d003ac9,0xbcf1bc2c,0x3cce3c98,0xbb963cfd,0x3c5bbce7,0xbcac3cbe,0x3cdcbc84,
 0xbcfbbbc8,0x3cd53c8e,0xbc8ebcd5,0x3bc83cfb,0x3bc8bcfb,0xbc8e3cd5,0x3cd5bc8e,0xbcfb3bc8,0x3cfb3bc8,0xbcd5bc8e,0x3c8e3cd5,0xbbc8bcfb,0xbbc83cfb,0x3c8ebcd5,0xbcd53c8e,0x3cfbbbc8,
 0xbcfbbbc8,0x3cd53c8e,0xbc8ebcd5,0x3bc83cfb,0x3bc8bcfb,0xbc8e3cd5,0x3cd5bc8e,0xbcfb3bc8,0x3cfb3bc8,0xbcd5bc8e,0x3c8e3cd5,0xbbc8bcfb,0xbbc83cfb,0x3c8ebcd5,0xbcd53c8e,0x3cfbbbc8,
 0x3cce3c98,0xbc5bbce7,0xbac93d00,0x3c84bcdc,0x3bf9bcf8,0xbcac3cbe,0x3cf1bc2c,0xbcfdbb96,0xbb96bcfd,0xbc2c3cf1,0x3cbebcac,0xbcf83bf9,0xbcdc3c84,0x3d00bac9,0xbce7bc5b,0x3c983cce,
 0x3c98bcce,0xbce73c5b,0x3d003ac9,0xbcdcbc84,0xbcf8bbf9,0x3cbe3cac,0xbc2cbcf1,0xbb963cfd,0xbcfd3b96,0x3cf13c2c,0xbcacbcbe,0x3bf93cf8,0x3c843cdc,0xbac9bd00,0xbc5b3ce7,0x3ccebc98,
 0x3c15bcf5,0xbcc63ca2,0x3cffbb49,0xbce2bc71,0x3c713ce2,0x3b49bcff,0xbca23cc6,0x3cf5bc15,0x3cf53c15,0xbca2bcc6,0x3b493cff,0x3c71bce2,0xbce23c71,0x3cff3b49,0xbcc6bca2,0x3c153cf5,
 0xbc153cf5,0x3cc6bca2,0xbcff3b49,0x3ce23c71,0xbc71bce2,0xbb493cff,0x3ca2bcc6,0xbcf53c15,0xbcf5bc15,0x3ca23cc6,0xbb49bcff,0xbc713ce2,0x3ce2bc71,0xbcffbb49,0x3cc63ca2,0xbc15bcf5,
 0xbcbebcac,0x3b963cfd,0x3c84bcdc,0xbcf13c2c,0x3c5b3ce7,0x3bf9bcf8,0xbcce3c98,0x3d003ac9,0xbac9bd00,0xbc983cce,0x3cf8bbf9,0xbce7bc5b,0xbc2c3cf1,0x3cdcbc84,0xbcfdbb96,0x3cac3cbe,
 0x3cacbcbe,0xbcfd3b96,0x3cdc3c84,0xbc2cbcf1,0xbce73c5b,0x3cf83bf9,0xbc98bcce,0xbac93d00,0x3d00bac9,0xbccebc98,0x3bf93cf8,0x3c5bbce7,0xbcf1bc2c,0x3c843cdc,0x3b96bcfd,0xbcbe3cac,
 0xbcedbc44,0x3c443ced,0x3c44bced,0xbced3c44,0x3ced3c44,0xbc44bced,0xbc443ced,0x3cedbc44,0xbcedbc44,0x3c443ced,0x3c44bced,0xbced3c44,0x3ced3c44,0xbc44bced,0xbc443ced,0x3cedbc44,
 0xbcedbc44,0x3c443ced,0x3c44bced,0xbced3c44,0x3ced3c44,0xbc44bced,0xbc443ced,0x3cedbc44,0xbcedbc44,0x3c443ced,0x3c44bced,0xbced3c44,0x3ced3c44,0xbc44bced,0xbc443ced,0x3cedbc44,
 0x3cac3cbe,0x3b96bcfd,0xbcdc3c84,0x3cf13c2c,0xbce7bc5b,0x3bf93cf8,0x3c98bcce,0xbd003ac9,0xbac93d00,0x3ccebc98,0xbcf8bbf9,0x3c5b3ce7,0xbc2cbcf1,0xbc843cdc,0x3cfdbb96,0xbcbebcac,
 0xbcbe3cac,0x3cfd3b96,0xbc84bcdc,0xbc2c3cf1,0x3c5bbce7,0xbcf83bf9,0x3cce3c98,0xbac9bd00,0xbd00bac9,0x3c983cce,0x3bf9bcf8,0xbce73c5b,0x3cf1bc2c,0xbcdcbc84,0x3b963cfd,0x3cacbcbe,
 0x3c71bce2,0xbcff3b49,0x3ca23cc6,0x3c15bcf5,0xbcf53c15,0x3cc63ca2,0x3b49bcff,0xbce23c71,0xbce2bc71,0x3b493cff,0x3cc6bca2,0xbcf5bc15,0x3c153cf5,0x3ca2bcc6,0xbcffbb49,0x3c713ce2,
 0xbc713ce2,0x3cffbb49,0xbca2bcc6,0xbc153cf5,0x3cf5bc15,0xbcc6bca2,0xbb493cff,0x3ce2bc71,0x3ce23c71,0xbb49bcff,0xbcc63ca2,0x3cf53c15,0xbc15bcf5,0xbca23cc6,0x3cff3b49,0xbc71bce2,
 0xbc98bcce,0xbc5b3ce7,0x3d00bac9,0xbc84bcdc,0x3cf8bbf9,0xbcacbcbe,0xbc2c3cf1,0x3cfdbb96,0xbb963cfd,0x3cf1bc2c,0xbcbebcac,0xbbf93cf8,0xbcdcbc84,0xbac93d00,0x3ce7bc5b,0xbccebc98,
 0xbcce3c98,0x3ce73c5b,0xbac9bd00,0xbcdc3c84,0xbbf9bcf8,0xbcbe3cac,0x3cf13c2c,0xbb96bcfd,0x3cfd3b96,0xbc2cbcf1,0xbcac3cbe,0x3cf83bf9,0xbc843cdc,0x3d003ac9,0xbc5bbce7,0xbc983cce,
 0xbcd5bc8e,0xbbc83cfb,0x3cfbbbc8,0xbc8ebcd5,0xbc8e3cd5,0x3cfb3bc8,0xbbc8bcfb,0xbcd53c8e,0x3cd53c8e,0x3bc8bcfb,0xbcfb3bc8,0x3c8e3cd5,0x3c8ebcd5,0xbcfbbbc8,0x3bc83cfb,0x3cd5bc8e,
 0xbcd5bc8e,0xbbc83cfb,0x3cfbbbc8,0xbc8ebcd5,0xbc8e3cd5,0x3cfb3bc8,0xbbc8bcfb,0xbcd53c8e,0x3cd53c8e,0x3bc8bcfb,0xbcfb3bc8,0x3c8e3cd5,0x3c8ebcd5,0xbcfbbbc8,0x3bc83cfb,0x3cd5bc8e,
 0xbc84bcdc,0xbcac3cbe,0x3ce73c5b,0x3b96bcfd,0x3c98bcce,0xbcf1bc2c,0xbac93d00,0x3cf8bbf9,0xbbf93cf8,0x3d00bac9,0xbc2cbcf1,0xbcce3c98,0xbcfd3b96,0x3c5b3ce7,0x3cbebcac,0xbcdcbc84,
 0xbcdc3c84,0x3cbe3cac,0x3c5bbce7,0xbcfdbb96,0xbccebc98,0xbc2c3cf1,0x3d003ac9,0xbbf9bcf8,0x3cf83bf9,0xbac9bd00,0xbcf13c2c,0x3c983cce,0x3b963cfd,0x3ce7bc5b,0xbcacbcbe,0xbc843cdc,
 0x3ca2bcc6,0xbce2bc71,0xbc153cf5,0x3cff3b49,0xbb49bcff,0xbcf53c15,0x3c713ce2,0x3cc6bca2,0x3cc63ca2,0x3c71bce2,0xbcf5bc15,0xbb493cff,0x3cffbb49,0xbc15bcf5,0xbce23c71,0x3ca23cc6,
 0xbca23cc6,0x3ce23c71,0x3c15bcf5,0xbcffbb49,0x3b493cff,0x3cf5bc15,0xbc71bce2,0xbcc63ca2,0xbcc6bca2,0xbc713ce2,0x3cf53c15,0x3b49bcff,0xbcff3b49,0x3c153cf5,0x3ce2bc71,0xbca2bcc6,
 0x3c5b3ce7,0x3cdcbc84,0xbc98bcce,0xbcbe3cac,0x3ac93d00,0x3cfdbb96,0xbbf9bcf8,0xbcf13c2c,0xbc2c3cf1,0x3cf83bf9,0x3b96bcfd,0xbd00bac9,0xbcac3cbe,0x3cce3c98,0x3c84bcdc,0xbce7bc5b,
 0xbce73c5b,0x3c843cdc,0x3ccebc98,0xbcacbcbe,0xbd003ac9,0x3b963cfd,0x3cf8bbf9,0xbc2cbcf1,0xbcf1bc2c,0xbbf93cf8,0x3cfd3b96,0x3ac9bd00,0xbcbebcac,0xbc983cce,0x3cdc3c84,0x3c5bbce7,
};

template<int SA>
__device__ __forceinline__ void wgmma_main(float (&d)[84], uint64_t da, uint64_t db, int sd) {
  asm volatile("{\n.reg .pred p;\nsetp.ne.b32 p, %86, 0;\n"
    "wgmma.mma_async.sync.aligned.m64n168k16.f32.bf16.bf16 "
    "{%0, %1, %2, %3, %4, %5, %6, %7, %8, %9, %10, %11, %12, %13, %14, %15, %16, %17, %18, %19, %20, %21, %22, %23, %24, %25, %26, %27, %28, %29, %30, %31, %32, %33, %34, %35, %36, %37, %38, %39, %40, %41, %42, %43, %44, %45, %46, %47, %48, %49, %50, %51, %52, %53, %54, %55, %56, %57, %58, %59, %60, %61, %62, %63, %64, %65, %66, %67, %68, %69, %70, %71, %72, %73, %74, %75, %76, %77, %78, %79, %80, %81, %82, %83}, %84, %85, p, %87, 1, 1, 0;\n}\n"
    : "+f"(d[0]), "+f"(d[1]), "+f"(d[2]), "+f"(d[3]), "+f"(d[4]), "+f"(d[5]), "+f"(d[6]), "+f"(d[7]), "+f"(d[8]), "+f"(d[9]), "+f"(d[10]), "+f"(d[11]), "+f"(d[12]), "+f"(d[13]), "+f"(d[14]), "+f"(d[15]), "+f"(d[16]), "+f"(d[17]), "+f"(d[18]), "+f"(d[19]), "+f"(d[20]), "+f"(d[21]), "+f"(d[22]), "+f"(d[23]), "+f"(d[24]), "+f"(d[25]), "+f"(d[26]), "+f"(d[27]), "+f"(d[28]), "+f"(d[29]), "+f"(d[30]), "+f"(d[31]), "+f"(d[32]), "+f"(d[33]), "+f"(d[34]), "+f"(d[35]), "+f"(d[36]), "+f"(d[37]), "+f"(d[38]), "+f"(d[39]), "+f"(d[40]), "+f"(d[41]), "+f"(d[42]), "+f"(d[43]), "+f"(d[44]), "+f"(d[45]), "+f"(d[46]), "+f"(d[47]), "+f"(d[48]), "+f"(d[49]), "+f"(d[50]), "+f"(d[51]), "+f"(d[52]), "+f"(d[53]), "+f"(d[54]), "+f"(d[55]), "+f"(d[56]), "+f"(d[57]), "+f"(d[58]), "+f"(d[59]), "+f"(d[60]), "+f"(d[61]), "+f"(d[62]), "+f"(d[63]), "+f"(d[64]), "+f"(d[65]), "+f"(d[66]), "+f"(d[67]), "+f"(d[68]), "+f"(d[69]), "+f"(d[70]), "+f"(d[71]), "+f"(d[72]), "+f"(d[73]), "+f"(d[74]), "+f"(d[75]), "+f"(d[76]), "+f"(d[77]), "+f"(d[78]), "+f"(d[79]), "+f"(d[80]), "+f"(d[81]), "+f"(d[82]), "+f"(d[83])
    : "l"(da), "l"(db), "r"(sd), "n"(SA));
}
template<int SA>
__device__ __forceinline__ void wgmma_fwd(float (&d)[32], uint64_t da, uint64_t db, int sd) {
  asm volatile("{\n.reg .pred p;\nsetp.ne.b32 p, %34, 0;\n"
    "wgmma.mma_async.sync.aligned.m64n64k16.f32.bf16.bf16 "
    "{%0, %1, %2, %3, %4, %5, %6, %7, %8, %9, %10, %11, %12, %13, %14, %15, %16, %17, %18, %19, %20, %21, %22, %23, %24, %25, %26, %27, %28, %29, %30, %31}, %32, %33, p, %35, 1, 0, 1;\n}\n"
    : "+f"(d[0]), "+f"(d[1]), "+f"(d[2]), "+f"(d[3]), "+f"(d[4]), "+f"(d[5]), "+f"(d[6]), "+f"(d[7]), "+f"(d[8]), "+f"(d[9]), "+f"(d[10]), "+f"(d[11]), "+f"(d[12]), "+f"(d[13]), "+f"(d[14]), "+f"(d[15]), "+f"(d[16]), "+f"(d[17]), "+f"(d[18]), "+f"(d[19]), "+f"(d[20]), "+f"(d[21]), "+f"(d[22]), "+f"(d[23]), "+f"(d[24]), "+f"(d[25]), "+f"(d[26]), "+f"(d[27]), "+f"(d[28]), "+f"(d[29]), "+f"(d[30]), "+f"(d[31])
    : "l"(da), "l"(db), "r"(sd), "n"(SA));
}
template<int SA>
__device__ __forceinline__ void wgmma_inv(float (&d)[24], uint64_t da, uint64_t db, int sd) {
  asm volatile("{\n.reg .pred p;\nsetp.ne.b32 p, %26, 0;\n"
    "wgmma.mma_async.sync.aligned.m64n48k16.f32.bf16.bf16 "
    "{%0, %1, %2, %3, %4, %5, %6, %7, %8, %9, %10, %11, %12, %13, %14, %15, %16, %17, %18, %19, %20, %21, %22, %23}, %24, %25, p, %27, 1, 1, 0;\n}\n"
    : "+f"(d[0]), "+f"(d[1]), "+f"(d[2]), "+f"(d[3]), "+f"(d[4]), "+f"(d[5]), "+f"(d[6]), "+f"(d[7]), "+f"(d[8]), "+f"(d[9]), "+f"(d[10]), "+f"(d[11]), "+f"(d[12]), "+f"(d[13]), "+f"(d[14]), "+f"(d[15]), "+f"(d[16]), "+f"(d[17]), "+f"(d[18]), "+f"(d[19]), "+f"(d[20]), "+f"(d[21]), "+f"(d[22]), "+f"(d[23])
    : "l"(da), "l"(db), "r"(sd), "n"(SA));
}

__device__ __forceinline__ uint32_t s2u(const void* p) { return (uint32_t)__cvta_generic_to_shared(p); }
__device__ __forceinline__ void mbar_init(uint32_t a, int c) { asm volatile("mbarrier.init.shared::cta.b64 [%0], %1;" ::"r"(a), "r"(c)); }
__device__ __forceinline__ void mbar_expect(uint32_t a, int b) { asm volatile("mbarrier.arrive.expect_tx.shared::cta.b64 _, [%0], %1;" ::"r"(a), "r"(b) : "memory"); }
__device__ __forceinline__ void mbar_arrive(uint32_t a) { asm volatile("mbarrier.arrive.shared::cta.b64 _, [%0];" ::"r"(a) : "memory"); }
__device__ __forceinline__ void mbar_arrive_cluster(uint32_t a, uint32_t cta, uint32_t cnt) {
  asm volatile("{\n.reg .b32 r;\nmapa.shared::cluster.u32 r, %0, %1;\nmbarrier.arrive.shared::cluster.b64 _, [r], %2;\n}" ::"r"(a), "r"(cta), "r"(cnt) : "memory");
}
__device__ __forceinline__ void mbar_wait(uint32_t a, int ph) {
  asm volatile("{\n.reg .pred p;\n.reg .u32 c;\nmov.u32 c, 0;\nWAIT:\n"
               "mbarrier.try_wait.parity.shared::cta.b64 p, [%0], %1;\n@p bra DONE;\n"
               "add.u32 c, c, 1;\nsetp.lt.u32 p, c, 0x400000;\n@p bra WAIT;\ntrap;\nDONE:\n}" ::"r"(a), "r"(ph) : "memory");
}
__device__ __forceinline__ void flag_wait(const unsigned* p, unsigned target) {
  asm volatile("{\n.reg .pred p;\n.reg .u32 c, v;\nmov.u32 c, 0;\nWAIT:\n"
               "ld.relaxed.gpu.global.u32 v, [%0];\nsetp.ge.u32 p, v, %1;\n@p bra DONE;\n"
               "add.u32 c, c, 1;\nsetp.lt.u32 p, c, 0x400000;\n@p bra WAIT;\ntrap;\nDONE:\n}" ::"l"(p), "r"(target) : "memory");
}
__device__ __forceinline__ void flag_add(unsigned* p) { asm volatile("red.release.gpu.global.add.u32 [%0], 1;" ::"l"(p) : "memory"); }
__device__ __forceinline__ bool elect_one() {
  uint32_t p;
  asm volatile("{\n.reg .pred P;\nelect.sync _|P, 0xffffffff;\nselp.u32 %0, 1, 0, P;\n}" : "=r"(p));
  return p != 0;
}
__device__ __forceinline__ void bulk_ld(uint32_t dst, const void* src, int bytes, uint32_t bar) {
  asm volatile("cp.async.bulk.shared::cluster.global.mbarrier::complete_tx::bytes [%0], [%1], %2, [%3];" ::"r"(dst), "l"(src), "r"(bytes), "r"(bar) : "memory");
}
__device__ __forceinline__ void bulk_ld_mc(uint32_t dst, const void* src, int bytes, uint32_t bar, uint16_t mask) {
  asm volatile("cp.async.bulk.shared::cluster.global.mbarrier::complete_tx::bytes.multicast::cluster [%0], [%1], %2, [%3], %4;" ::"r"(dst), "l"(src), "r"(bytes), "r"(bar), "h"(mask) : "memory");
}
__device__ __forceinline__ void bulk_ld_h(uint32_t dst, const void* src, int bytes, uint32_t bar, uint64_t pol) {
  asm volatile("cp.async.bulk.shared::cluster.global.mbarrier::complete_tx::bytes.L2::cache_hint [%0], [%1], %2, [%3], %4;" ::"r"(dst), "l"(src), "r"(bytes), "r"(bar), "l"(pol) : "memory");
}
__device__ __forceinline__ void bulk_ld_mc_h(uint32_t dst, const void* src, int bytes, uint32_t bar, uint16_t mask, uint64_t pol) {
  asm volatile("cp.async.bulk.shared::cluster.global.mbarrier::complete_tx::bytes.multicast::cluster.L2::cache_hint [%0], [%1], %2, [%3], %4, %5;" ::"r"(dst), "l"(src), "r"(bytes), "r"(bar), "h"(mask), "l"(pol) : "memory");
}
__device__ __forceinline__ uint64_t policy_evict_normal() {
  uint64_t p;
  asm("createpolicy.fractional.L2::evict_normal.b64 %0, 1.0;" : "=l"(p));
  return p;
}
__device__ __forceinline__ void tma_ld2(uint32_t dst, const CUtensorMap* tm, int c0, int c1, uint32_t bar) {
  asm volatile("cp.async.bulk.tensor.2d.shared::cluster.global.mbarrier::complete_tx::bytes [%0], [%1, {%3,%4}], [%2];" ::"r"(dst), "l"(tm), "r"(bar), "r"(c0), "r"(c1) : "memory");
}
__device__ __forceinline__ void tma_ld3(uint32_t dst, const CUtensorMap* tm, int c0, int c1, int c2, uint32_t bar) {
  asm volatile("cp.async.bulk.tensor.3d.shared::cluster.global.mbarrier::complete_tx::bytes [%0], [%1, {%3,%4,%5}], [%2];" ::"r"(dst), "l"(tm), "r"(bar), "r"(c0), "r"(c1), "r"(c2) : "memory");
}
__device__ __forceinline__ void tma_ld3h(uint32_t dst, const CUtensorMap* tm, int c0, int c1, int c2, uint32_t bar, uint64_t pol) {
  asm volatile("cp.async.bulk.tensor.3d.shared::cluster.global.mbarrier::complete_tx::bytes.L2::cache_hint [%0], [%1, {%3,%4,%5}], [%2], %6;" ::"r"(dst), "l"(tm), "r"(bar), "r"(c0), "r"(c1), "r"(c2), "l"(pol) : "memory");
}
__device__ __forceinline__ uint64_t policy_evict_first() {
  uint64_t p;
  asm("createpolicy.fractional.L2::evict_first.b64 %0, 1.0;" : "=l"(p));
  return p;
}
__device__ __forceinline__ void tma_pf3(const CUtensorMap* tm, int c0, int c1, int c2) {
  asm volatile("cp.async.bulk.prefetch.tensor.3d.L2.global [%0, {%1,%2,%3}];" ::"l"(tm), "r"(c0), "r"(c1), "r"(c2) : "memory");
}
__device__ __forceinline__ void tma_st3(const CUtensorMap* tm, uint32_t src, int c0, int c1, int c2) {
  asm volatile("cp.async.bulk.tensor.3d.global.shared::cta.bulk_group [%0, {%2,%3,%4}], [%1];" ::"l"(tm), "r"(src), "r"(c0), "r"(c1), "r"(c2) : "memory");
}
__device__ __forceinline__ void tma_st4(const CUtensorMap* tm, uint32_t src, int c0, int c1, int c2, int c3) {
  asm volatile("cp.async.bulk.tensor.4d.global.shared::cta.bulk_group [%0, {%2,%3,%4,%5}], [%1];" ::"l"(tm), "r"(src), "r"(c0), "r"(c1), "r"(c2), "r"(c3) : "memory");
}
__device__ __forceinline__ void tma_st5(const CUtensorMap* tm, uint32_t src, int c0) {
  asm volatile("cp.async.bulk.tensor.5d.global.shared::cta.bulk_group [%0, {%2,%3,%3,%3,%3}], [%1];" ::"l"(tm), "r"(src), "r"(c0), "r"(0) : "memory");
}
__device__ __forceinline__ void bulk_commit() { asm volatile("cp.async.bulk.commit_group;" ::: "memory"); }
template <int N> __device__ __forceinline__ void bulk_wait_read() { asm volatile("cp.async.bulk.wait_group.read %0;" ::"n"(N) : "memory"); }
template <int N> __device__ __forceinline__ void bulk_wait() { asm volatile("cp.async.bulk.wait_group %0;" ::"n"(N) : "memory"); }
__device__ __forceinline__ void fence_async_smem() { asm volatile("fence.proxy.async.shared::cta;" ::: "memory"); }
__device__ __forceinline__ void wg_fence() { asm volatile("wgmma.fence.sync.aligned;" ::: "memory"); }
__device__ __forceinline__ void wg_commit() { asm volatile("wgmma.commit_group.sync.aligned;" ::: "memory"); }
template <int N> __device__ __forceinline__ void wg_wait() { asm volatile("wgmma.wait_group.sync.aligned %0;" ::"n"(N) : "memory"); }
template <int R> __device__ __forceinline__ void fence_regs(float (&d)[R]) {
#pragma unroll
  for (int i = 0; i < R; i++) asm volatile("" : "+f"(d[i])::"memory");
}
__device__ __forceinline__ uint64_t mk_desc(uint32_t addr) {
  return (uint64_t)((addr & 0x3FFFF) >> 4) | (1ull << 16) | (64ull << 32) | (1ull << 62);
}
__device__ __forceinline__ uint32_t pack2(float lo, float hi) {
  uint32_t r;
  asm("cvt.rn.bf16x2.f32 %0, %1, %2;" : "=r"(r) : "f"(hi), "f"(lo));
  return r;
}
__device__ __forceinline__ void stsm4(uint32_t ad, uint32_t a, uint32_t b, uint32_t c, uint32_t d) {
  asm volatile("stmatrix.sync.aligned.m8n8.x4.shared.b16 [%0], {%1,%2,%3,%4};" ::"r"(ad), "r"(a), "r"(b), "r"(c), "r"(d) : "memory");
}
__device__ __forceinline__ void stsm4t(uint32_t ad, uint32_t a, uint32_t b, uint32_t c, uint32_t d) {
  asm volatile("stmatrix.sync.aligned.m8n8.x4.trans.shared.b16 [%0], {%1,%2,%3,%4};" ::"r"(ad), "r"(a), "r"(b), "r"(c), "r"(d) : "memory");
}

__device__ __forceinline__ bool mbar_test(uint32_t a, int ph) {
  uint32_t ok;
  asm volatile("{\n.reg .pred p;\nmbarrier.test_wait.parity.shared::cta.b64 p, [%1], %2;\nselp.u32 %0, 1, 0, p;\n}" : "=r"(ok) : "r"(a), "r"(ph) : "memory");
  return ok != 0;
}
__device__ __forceinline__ void poll64x4(const unsigned long long* p, unsigned long long (&v)[4]) {
  asm volatile("{\n.reg .pred p;\n.reg .u32 c;\n.reg .b64 t, u;\nmov.u32 c, 0;\nWAIT:\n"
               "ld.relaxed.gpu.global.u64 %0, [%4];\nld.relaxed.gpu.global.u64 %1, [%4+512];\n"
               "ld.relaxed.gpu.global.u64 %2, [%4+1024];\nld.relaxed.gpu.global.u64 %3, [%4+1536];\n"
               "or.b64 t, %0, %1;\nor.b64 u, %2, %3;\nor.b64 t, t, u;\nsetp.ge.s64 p, t, 0;\n@p bra DONE;\n"
               "add.u32 c, c, 1;\nsetp.lt.u32 p, c, 0x400000;\n@p bra WAIT;\ntrap;\nDONE:\n}"
               : "=l"(v[0]), "=l"(v[1]), "=l"(v[2]), "=l"(v[3]) : "l"(p) : "memory");
}

constexpr int G_STAGE = WBLK + XBLK;
constexpr int OFF_XR = 4 * G_STAGE;
constexpr int OFF_WS = OFF_XR + 6 * 8192;
constexpr int OFF_F = OFF_WS + 2 * 8192;
constexpr int OFF_WRAW = OFF_F + 8192;
constexpr int OFF_BAR = OFF_WRAW + 4096;
constexpr int SMEM_BYTES = OFF_BAR + 1024;
constexpr int OFF_Y0 = 3 * G_STAGE + 1024;
constexpr int OFF_H0 = OFF_F - 11 * 8192;
constexpr int B_FULL = 0, B_EMPTY = 32, B_RAWX = 64, B_STGX = 112, B_RAWW = 160, B_STGW = 176, B_Y = 192, B_F = 208, B_RET = 216,
              B_ROLE = 224, B_H0 = 240, B_H1 = 248, B_DONE = 272, S_ROLE = 544, S_PROBE = 560;

struct Maps { CUtensorMap x, we, wo, xst[2], wst, yst, yld, out; };

__device__ __forceinline__ int chunk_of(int n) { return n < 16 ? n : 31 - n; }
__device__ __forceinline__ int x2_of(int id, int n) { return (id + 40 * n) & 63; }
__device__ __forceinline__ bool has_x2(int id, int n, int g) { return x2_of(id, n) < 40 && (n & 1) == g; }
__device__ __forceinline__ uint32_t x_base(int s, int idx, uint32_t pgmask, int& par) {
  const int page = idx >> 3, o = idx & 7;
  par = (s ^ (pgmask >> page) ^ __popc(o)) & 1;
  return (page << 21) | ((o & 3) << 16) | ((o >> 2) << 19);
}
__device__ __forceinline__ int next_slot(int s, int v) {
  return s == 3 ? 0 : (s == 2 && ((v >= 32 && v < 38) || v >= 62)) ? 0 : s + 1;
}
__device__ __forceinline__ uint32_t read_info(uint32_t bar, int i) {
  uint32_t v;
  mbar_wait(bar + B_ROLE + 8 * i, 0);
  asm volatile("ld.shared.b32 %0, [%1];" : "=r"(v) : "r"(bar + S_ROLE + 4 * i) : "memory");
  return v;
}
__device__ __forceinline__ void send_info(uint32_t bar, int i, uint32_t v) {
#pragma unroll
  for (int r = 0; r < 2; r++)
    asm volatile("{\n.reg .b32 a, m;\nmapa.shared::cluster.u32 a, %0, %2;\nmapa.shared::cluster.u32 m, %1, %2;\n"
                 "st.async.weak.shared::cluster.mbarrier::complete_tx::bytes.b32 [a], %3, [m];\n}"
                 ::"r"(bar + S_ROLE + 4 * i), "r"(bar + B_ROLE + 8 * i), "r"(r), "r"(v) : "memory");
}
__device__ __forceinline__ unsigned probe(uint8_t* p, int lane, int pb) {
  if (lane < 2) *(uint4*)(p + lane * 16) = make_uint4(0, 0, 0, 0);
  __syncwarp();
  unsigned v = 0, best = ~0u;
  if (lane == 0) {
#pragma unroll 1
    for (int r = 0; r < 2; r++) {
      unsigned t0, t1;
      asm volatile("mov.u32 %0, %%clock;" : "=r"(t0) : "r"(v) : "memory");
      asm volatile("atom.relaxed.gpu.global.exch.b32 %0, [%1], 0;" : "=r"(v) : "l"(p) : "memory");
      asm volatile("{\n.reg .pred p;\nsetp.ne.u32 p, %1, 0xffffffff;\nmov.u32 %0, 0;\n@p mov.u32 %0, %%clock;\n}" : "=r"(t1) : "r"(v) : "memory");
      best = min(best, t1 - t0);
      if (r < 3) PROF_V(pb + r, t1 - t0);
    }
  }
  return best;
}

template <bool ISX>
__device__ __forceinline__ void t_issue(float (&t)[32], uint32_t sb, uint32_t raw) {
  const uint64_t da = mk_desc(sb + OFF_F), db = mk_desc(raw);
  wg_fence();
#pragma unroll
  for (int kk = 0; kk < (ISX ? 4 : 1); kk++) wgmma_fwd<1>(t, da + 2 * kk, db + 128 * kk, kk);
  wg_commit();
}
template <bool ISX>
__device__ __forceinline__ void t_finish(float (&t)[32], uint32_t dst, uint32_t sbar, int sw, int wg, int w, int lane) {
  fence_regs(t);
  if (ISX) asm volatile("bar.sync %0, 128;" ::"r"(1 + wg) : "memory");
  const int m = lane >> 3, r = lane & 7;
  uint32_t ad = dst + (8 * w + r) * 128;
  if (ISX) ad += ((((m & 1) * 4 + (m >> 1)) ^ sw ^ r) << 4);
  else ad += (m & 1) * 4096 + (((m >> 1) ^ sw ^ r) << 4);
#pragma unroll
  for (int i = 0; i < 4; i++) {
    const uint32_t a = ISX ? ((ad ^ ((i & 1) * 32)) + (i >> 1) * 4096) : (ad ^ (i * 32));
    stsm4(a, pack2(t[8 * i], t[8 * i + 1]), pack2(t[8 * i + 2], t[8 * i + 3]), pack2(t[8 * i + 4], t[8 * i + 5]), pack2(t[8 * i + 6], t[8 * i + 7]));
  }
  fence_async_smem();
  __syncwarp();
  if (lane == 0) mbar_arrive(sbar);
}
template <int NT, int K0, int K1>
__device__ __forceinline__ void batch(float (&yr)[84], float (&yi)[84], float (&t)[32], uint32_t st, int wg, int sd, uint32_t fa, uint32_t raw) {
  const uint64_t w0 = mk_desc(st + wg * 8192), x0 = mk_desc(st + WBLK);
  const uint64_t da = mk_desc(fa), db = mk_desc(raw);
  wg_fence();
  if (NT) {
#pragma unroll
    for (int kk = 0; kk < NT; kk++) wgmma_fwd<1>(t, da + 2 * kk, db + 128 * kk, kk);
    wg_commit();
  }
#pragma unroll
  for (int kk = K0; kk < K1; kk++) {
    const uint64_t wr = w0 + kk * 128, wi = wr + 256, xr = x0 + kk * 2, xi = xr + 4;
    wgmma_main<1>(yr, wr, xr, kk ? 1 : sd);
    wgmma_main<1>(yi, wr, xi, kk ? 1 : sd);
    wgmma_main<1>(yr, wi, xi, 1);
    wgmma_main<-1>(yi, wi, xr, 1);
  }
  wg_commit();
}

#define X_WAIT() PROF_W(wraw, mbar_wait(bar + B_RAWX + 8 * (wg * 3 + xs), xph))
#define X_ISSUE() t_issue<true>(t, sb, sb + OFF_XR + (wg * 3 + xs) * 8192)
#define X_FINISH(sw) do { t_finish<true>(t, sb + OFF_XR + (wg * 3 + xs) * 8192, bar + B_STGX + 8 * (wg * 3 + xs), sw, wg, w, lane); \
                          if (++xs == 3) { xs = 0; xph ^= 1; } } while (0)
#define W_WAIT(n) PROF_W(wraw, mbar_wait(bar + B_RAWW + 8 * wg, (n) & 1))
#define W_ISSUE() t_issue<false>(t, sb, sb + OFF_WRAW + wg * 2048)
#define W_FINISH() t_finish<false>(t, sb + OFF_WS + wg * 8192, bar + B_STGW + 8 * wg, sww, wg, w, lane)

__global__ void __cluster_dims__(2, 1, 1) __launch_bounds__(384, 1)
k1_main(const __grid_constant__ Maps tm, uint8_t* __restrict__ xbuf, const __nv_bfloat16* __restrict__ gamma,
        const __nv_bfloat16* __restrict__ beta) {
  extern __shared__ __align__(1024) uint8_t smem_raw[];
  const uint32_t sb = s2u(smem_raw);
  const uint32_t bar = sb + OFF_BAR;
  const int warp = __shfl_sync(0xffffffffu, threadIdx.x >> 5, 0), lane = threadIdx.x & 31;
  const int bid = blockIdx.x;
  const uint32_t rank = bid & 1;
  if (warp < 3 && elect_one()) {
    if (warp == 0) {
      PROF_T(0);
#pragma unroll
      for (int o = 0; o < B_DONE; o += 8)
        mbar_init(bar + o, (o >= B_RAWW && o < B_STGW) ? 2 : ((o >= B_EMPTY && o < B_RAWX) || (o >= B_STGX && o < B_F) || o == B_RET) ? 4 : 1);
      mbar_expect(bar + B_ROLE, 4);
      mbar_expect(bar + B_ROLE + 8, 4);
      asm volatile("fence.mbarrier_init.release.cluster;" ::: "memory");
    } else if (warp == 1) {
#pragma unroll
      for (int i = 0; i < 33; i++) mbar_init(bar + B_DONE + 8 * i, 2);
    } else {
#pragma unroll
      for (int i = 3; i < 6; i++) asm volatile("prefetch.tensormap [%0];" ::"l"(&tm.x + i) : "memory");
    }
  }
  __syncthreads();
  if (threadIdx.x == 64) PROF_T(20);
  asm volatile("barrier.cluster.arrive.relaxed.aligned;" ::: "memory");
  if (rank == 0 && (warp >> 2) == 1) {
    const int k = bid >> 1;
    const uint32_t off = (warp & 2) ? ((k % XPAGES) << 21) + (1 << 18) + (k / XPAGES) * 128 : ((k >> 4) << 14) + (k & 15) * 32;
    const unsigned lat = probe(xbuf + off + 28 * 128 + (warp & 1) * 4096, lane, 400 + (warp & 2) * 5 + (warp & 1) * 3);
    if (lane == 0) asm volatile("st.shared.b32 [%0], %1;" ::"r"(bar + S_PROBE + 4 * (warp & 3)), "r"(lat) : "memory");
    asm volatile("bar.arrive 4, 160;" ::: "memory");
  }
  if (warp >= 8) {
    asm volatile("setmaxnreg.dec.sync.aligned.u32 40;");
    if (warp == 9 || warp == 10) {
      if (elect_one()) {
        const int g = warp - 9;
        const uint64_t pol = policy_evict_first();
        int id = bid, role = -1;
        uint32_t pgmask = 0;
        int ln = 0, lj = 0;
        auto load_x = [&](int sl) {
          if (ln >= 16) return;
          if (ln >= OB && role < 0) role = read_info(bar, 0);
          const int lid = ln < OB ? bid : role * 2 + rank;
          const int t = lj ? 128 + x2_of(lid, ln) : 2 * (lid & 63) + g;
          mbar_expect(bar + B_RAWX + 8 * sl, 8192);
          tma_ld3h(sb + OFF_XR + sl * 8192, &tm.x, ln * 64, t * MT, lid >> 6, bar + B_RAWX + 8 * sl, pol);
          if (lj == 0 && has_x2(lid, ln, g)) lj = 1; else { lj = 0; ln++; }
        };
        auto load_w = [&](int n, bool pf) {
          if (n >= 32) return;
          const int cp = chunk_of(n) * 64 + (bid >> 1), col = (cp & 511) * 8 + (n >> 4) * 4 + rank * 2 + g;
          const CUtensorMap* mp = cp < 512 ? &tm.we : &tm.wo;
          if (pf) { tma_pf3(mp, 0, 0, col); return; }
          mbar_expect(bar + B_RAWW + 8 * g, 2048);
          tma_ld3h(sb + OFF_WRAW + g * 2048, mp, 0, 0, col, bar + B_RAWW + 8 * g, pol);
        };
        if (g == 0) PROF_T(22);
        load_x(g * 3);
        if (g == 0) {
          mbar_expect(bar + B_F, 8192);
          bulk_ld(sb + OFF_F, g_Fimg, 8192, bar + B_F);
        }
        load_w(0, false);
        mbar_arrive(bar + B_RAWW + 8 * g);
        load_x(g * 3 + 1);
        if (g == 0) PROF_T(23);
        load_w(1, true);
        load_w(2, true);
        bool late = ln >= OB;
        if (!late) load_x(g * 3 + 2);
        int xs = 0, xph = 0, yp = 7;
        for (int n = 0; n < 32; n++) {
          if (n == OB) {
            if (role < 0) role = read_info(bar, 0);
            pgmask = read_info(bar, 1);
            id = role * 2 + rank;
          }
          unsigned freed = 128;
          if (n >= WR) asm volatile("ld.relaxed.gpu.global.u32 %0, [%1];" : "=r"(freed) : "l"(&g_ctr[(C_LOADED + n - WR) * 32]) : "memory");
          if (n < 16) {
            const int nx = has_x2(id, n, g) ? 2 : 1;
            for (int j = 0; j < nx; j++) {
              const int t = j ? 128 + x2_of(id, n) : 2 * (id & 63) + g;
              const int tg = t / 28, row = t - tg * 28, sl = g * 3 + xs;
              int par0, par1;
              const uint32_t off0 = x_base(id >> 6, XC(n) * 12 + tg, pgmask, par0), off1 = x_base(id >> 6, XC(n) * 12 + 6 + tg, pgmask, par1);
              const uint32_t buf = sb + OFF_XR + sl * 8192;
              mbar_wait(bar + B_STGX + 8 * sl, xph);
              tma_st5(&tm.xst[par0], buf, (off0 + (par0 << 12) + row * 128) >> 1);
              tma_st5(&tm.xst[par1], buf + 4096, (off1 + (par1 << 12) + row * 128) >> 1);
              bulk_commit();
              if (late) { load_x(g * 3 + 2); late = false; }
              bulk_wait_read<0>();
              load_x(sl);
              if (++xs == 3) { xs = 0; xph ^= 1; }
            }
          }
          if (freed < 128) flag_wait(&g_ctr[(C_LOADED + n - WR) * 32], 128);
          if (n == 16 + LW) {
            mbar_wait(bar + B_Y + 8 * g, 0);
            yp = 0;
          }
          while (yp < 7 && (n == YFLUSH || !mbar_test(bar + B_STGW + 8 * g, n & 1))) {
            tma_st4(&tm.yst, sb + OFF_Y0 + (yp * 2 + g) * 6144, 0, yp * 24, 2 * (role & 31), (role >> 5) * 8 + rank * 2 + g);
            bulk_commit();
            bulk_wait_read<0>();
            if (++yp == 3) {
              mbar_arrive_cluster(bar + B_RET, 0, 1);
              mbar_arrive_cluster(bar + B_RET, 1, 1);
            }
          }
          const int wrow = (n % WR) * (WCHUNK / 128) + (rank * 2 + (bid >> 6)) * 128 + g * 64 + ((bid >> 1) & 31);
          mbar_wait(bar + B_STGW + 8 * g, n & 1);
          tma_st4(&tm.wst, sb + OFF_WS + g * 8192, 0, 0, 0, wrow);
          bulk_commit();
          load_w(n + 1, false);
          bulk_wait_read<0>();
          mbar_arrive(bar + B_DONE + 8 * n);
          mbar_arrive(bar + B_RAWW + 8 * g);
          load_w(n + 3, true);
        }
        mbar_wait(bar + B_Y + 8 * g, 1);
        for (int p = 0; p < 7; p++) tma_st4(&tm.yst, sb + (p * 2 + g) * 6144, 0, p * 24, 2 * (role & 31), (role >> 5) * 8 + 4 + rank * 2 + g);
        bulk_commit();
        bulk_wait_read<0>();
        mbar_arrive(bar + B_DONE + 8 * 32);
      }
      __syncwarp();
      asm volatile("barrier.cluster.wait.aligned;" ::: "memory");
    } else if (warp == 11) {
      asm volatile("barrier.cluster.wait.aligned;" ::: "memory");
      if (elect_one()) {
        for (int n = 0; n < 32;) {
          mbar_wait(bar + B_DONE + 8 * n, 0);
          int e = n + 1;
          while (e < 32 && mbar_test(bar + B_DONE + 8 * e, 0)) e++;
          if (!NOFENCE) asm volatile("fence.release.gpu;" ::: "memory");
          for (; n < e; n++) {
            asm volatile("red.relaxed.gpu.global.add.u32 [%0], 1;" ::"l"(&g_ctr[(C_FLAG + n) * 32]) : "memory");
            PROF_T(64 + n); PROF_V(192 + n, tm0);
          }
        }
        const int role = read_info(bar, 0);
        mbar_wait(bar + B_DONE + 8 * 32, 0);
        PROF_T(4);
        flag_add(&g_ctr[(C_FLAG + 32 + (role >> 5) * 2 + rank) * 32]);
      }
      __syncwarp();
    } else {
      if (rank == 0) asm volatile("bar.sync 4, 160;" ::: "memory");
      asm volatile("barrier.cluster.wait.aligned;" ::: "memory");
      if (lane == 0 && rank == 0) {
        const int k = bid >> 1;
        uint32_t l0, l1, l2, l3;
        asm volatile("ld.shared.v4.b32 {%0, %1, %2, %3}, [%4];" : "=r"(l0), "=r"(l1), "=r"(l2), "=r"(l3) : "r"(bar + S_PROBE) : "memory");
        const int side = l1 < l0, near = l3 < l2;
        unsigned long long add = 1ull << (8 * side), v;
        if (k < XPAGES && k >= OB * 3 / 2) add += (unsigned long long)(near ^ side) << (16 + k);
        unsigned long long* reg = (unsigned long long*)&g_ctr[C_REG * 32];
        PROF_T(14);
        const int ticket = (atomicAdd(reg, add) >> (8 * side)) & 255;
        if (ticket < 1000) PROF_T(15);
        const int role = ticket < 32 ? side * 32 + ticket : (side ^ 1) * 32 + 63 - ticket;
        send_info(bar, 0, role);
        asm volatile("{\n.reg .pred p;\n.reg .u32 c, a, b;\nmov.u32 c, 0;\nWAIT:\n"
                     "ld.relaxed.gpu.global.u64 %0, [%1];\ncvt.u32.u64 a, %0;\nbfe.u32 b, a, 8, 8;\nand.b32 a, a, 255;\nadd.u32 a, a, b;\n"
                     "setp.ge.u32 p, a, 64;\n@p bra DONE;\n"
                     "add.u32 c, c, 1;\nsetp.lt.u32 p, c, 0x400000;\n@p bra WAIT;\ntrap;\nDONE:\n}" : "=l"(v) : "l"(reg) : "memory");
        send_info(bar, 1, (uint32_t)(v >> 16));
        PROF_V(16, side); PROF_V(17, role); PROF_V(18, v);
      }
      __syncwarp();
      if (elect_one()) {
        const int role = read_info(bar, 0);
        const uint32_t pgmask = read_info(bar, 1);
        PROF_T(1);
        const int b = role >> 5, u = role & 31;
        const uint64_t pef = policy_evict_first(), pen = policy_evict_normal();
        const uint8_t* xs = xbuf + ((((u >> 1) & 3) << 14) | (((u >> 3) & 1) << 18) | ((u >> 4) << 20) | ((u & 1) << 13));
        const uint8_t* ws = g_W + (size_t)(u * 2 + rank) * 2 * WBLK;
        int s = 3, phm = 15;
        for (int v = 0; v < 64; v++) {
          const int n = v >> 1, h = v & 1, c = chunk_of(n);
          const uint64_t polx = (n < XEF0 || n >= 16) ? pef : pen;
          const uint32_t dst = sb + s * G_STAGE, fb = bar + B_FULL + 8 * s;
          const uint8_t* wsrc = ws + (size_t)(n % WR) * WCHUNK + h * WBLK;
          uint32_t xo[3];
#pragma unroll
          for (int g = 0; g < 3; g++) {
            int par;
            xo[g] = x_base(b, XC(c) * 12 + h * 6 + rank * 3 + g, pgmask, par);
            xo[g] += ((par ^ u) & 1) << 12;
          }
          if (h == 0 && n < 16) {
            flag_wait(&g_ctr[(C_FLAG + n) * 32], 128);
            asm volatile("fence.proxy.async.global;" ::: "memory");
            PROF_T(32 + n);
          }
          if (v == 38) mbar_wait(bar + B_RET, 0);
          mbar_wait(bar + B_EMPTY + 8 * s, (phm >> s) & 1);
          phm ^= 1 << s;
          mbar_expect(fb, G_STAGE);
#pragma unroll
          for (int g = 0; g < 3; g++) bulk_ld_mc_h(dst + WBLK + (rank * 3 + g) * 3584, xs + xo[g], 3584, fb, 3, polx);
          if (h == 0 && n >= 16) {
            flag_wait(&g_ctr[(C_FLAG + n) * 32], 128);
            asm volatile("fence.proxy.async.global;" ::: "memory");
            PROF_T(32 + n);
          }
          bulk_ld(dst, wsrc, WBLK, fb);
          s = next_slot(s, v + 1);
        }
        const int dq = rank * 2 + (u & 1), t0 = ((u >> 1) * 167) >> 4, nb = ((((u >> 1) + 1) * 167) >> 4) - t0;
        mbar_wait(bar + B_DONE + 8 * 31, 0);
        mbar_wait(bar + B_EMPTY + 8 * 3, (phm >> 3) & 1);
        mbar_expect(bar + B_H0, nb * 8192 + 6144);
        bulk_ld(sb + OFF_F, g_Gimg, 6144, bar + B_H0);
        for (int i = 0; i < nb; i++) tma_ld2(sb + OFF_H0 + i * 8192, &tm.yld, 0, ((b * 8 + dq) * NT + t0 + i) * 64, bar + B_H0);
        flag_wait(&g_ctr[(C_FLAG + 32 + b * 2 + rank) * 32], 32);
        asm volatile("fence.proxy.async.global;" ::: "memory");
        PROF_T(5);
        for (int i = 0; i < nb; i++) {
          const uint32_t fb = bar + B_H1 + 8 * (i >> 2);
          if ((i & 3) == 0) mbar_expect(fb, min(4, nb - i) * 8192);
          tma_ld2(sb + i * 8192, &tm.yld, 0, ((b * 8 + 4 + dq) * NT + t0 + i) * 64, fb);
        }
      }
      __syncwarp();
      unsigned old = 0;
      if (lane == 0) old = atomicAdd(&g_ctr[C_EXIT * 32], 1);
      if (__shfl_sync(0xffffffffu, old, 0) == 127) {
        for (int i = lane; i < C_NUM; i += 32) *(volatile unsigned long long*)&g_ctr[i * 32] = 0;
      }
    }
    asm volatile("barrier.cluster.arrive.relaxed.aligned;\nbarrier.cluster.wait.aligned;" ::: "memory");
  } else {
    asm volatile("setmaxnreg.inc.sync.aligned.u32 232;");
    const int wg = warp >> 2, w = warp & 3;
    if (wg == 0) g_part[bid * 128 + threadIdx.x] = ~0ull;
    asm volatile("barrier.cluster.wait.aligned;" ::: "memory");
    int id = bid;
    {
      float yr[84], yi[84], t[32];
      const int sww = (bid >> 1) & 7;
      int xs = 0, xph = 0;
      unsigned wraw = 0, wfull = 0;
      if (threadIdx.x == 0) PROF_T(24);
      mbar_wait(bar + B_F, 0);
      if (threadIdx.x == 0) PROF_T(25);
#pragma unroll 1
      for (int m = 0; m < LW + 1 - XFIRST; m++) {
        if (m == OB) id = __shfl_sync(0xffffffffu, read_info(bar, 0), 0) * 2 + rank;
        X_WAIT();
        X_ISSUE();
        wg_wait<0>();
        X_FINISH((2 * id + wg) & 7);
        if (threadIdx.x == 0 && m == 0) PROF_T(26);
        if (has_x2(id, m, wg)) {
          X_WAIT();
          X_ISSUE();
          wg_wait<0>();
          X_FINISH(x2_of(id, m) & 7);
        }
        if (m < LW) {
          W_WAIT(m);
          W_ISSUE();
          wg_wait<0>();
          W_FINISH();
        }
      }
      if (threadIdx.x == 0) PROF_T(27);
      static_assert(OB < LW + 1 - XFIRST, "role is read in the prologue");
      int s = 3, phm = 0;
#pragma unroll 1
      for (int pass = 0; pass < 2; pass++) {
        int sprev = -1;
#pragma unroll 1
        for (int i = 0; i < 32; i++) {
          const int v = pass * 32 + i, n = v >> 1;
          const int mw = n + LW, mx = mw + 1 - XFIRST;
          const bool xstage = (v & 1) != XFIRST;
          if (!(v & 1)) { wraw = 0; wfull = 0; }
          PROF_W(wfull, mbar_wait(bar + B_FULL + 8 * s, (phm >> s) & 1));
          phm ^= 1 << s;
          const uint32_t st = sb + s * G_STAGE;
#define RELEASE() do { if (w == 0 && lane < 2) { if (sprev >= 0) mbar_arrive_cluster(bar + B_EMPTY + 8 * sprev, lane, 1); } \
                       else if (threadIdx.x == 32 && (v & 1)) asm volatile("red.relaxed.gpu.global.add.u32 [%0], 1;" ::"l"(&g_ctr[(C_LOADED + n) * 32]) : "memory"); } while (0)
#define XRAW (sb + OFF_XR + (wg * 3 + xs) * 8192)
          if (xstage && mx < 16) {
            X_WAIT();
            batch<4, 0, 1>(yr, yi, t, st, wg, i != 0, sb + OFF_F, XRAW);
            wg_wait<1>();
            RELEASE();
            X_FINISH((2 * id + wg) & 7);
            if (has_x2(id, mx, wg)) {
              X_WAIT();
              batch<4, 1, 2>(yr, yi, t, st, wg, 1, sb + OFF_F, XRAW);
              wg_wait<1>();
              X_FINISH(x2_of(id, mx) & 7);
            } else {
              batch<0, 1, 2>(yr, yi, t, st, wg, 1, 0, 0);
            }
          } else if (!xstage && mw < 32) {
            W_WAIT(mw);
            batch<1, 0, 1>(yr, yi, t, st, wg, i != 0, sb + OFF_F, sb + OFF_WRAW + wg * 2048);
            wg_wait<1>();
            RELEASE();
            W_FINISH();
            batch<0, 1, 2>(yr, yi, t, st, wg, 1, 0, 0);
          } else {
            batch<0, 0, 1>(yr, yi, t, st, wg, i != 0, 0, 0);
            wg_wait<1>();
            RELEASE();
            batch<0, 1, 2>(yr, yi, t, st, wg, 1, 0, 0);
          }
          sprev = s;
          s = next_slot(s, v + 1);
        }
        wg_wait<0>();
        fence_regs(yr);
        fence_regs(yi);
        if (w == 0 && lane < 2) mbar_arrive_cluster(bar + B_EMPTY + 8 * sprev, lane, 1);
        if (pass == 0) mbar_wait(bar + B_EMPTY + 8 * 3, 1);
        else asm volatile("bar.sync 3, 256;" ::: "memory");
        const int m = lane >> 3, r = lane & 7;
        const uint32_t ad = sb + (pass ? 0 : OFF_Y0) + wg * 6144 + (m >> 1) * 3072 + r * 128 + (((2 * w + (m & 1)) ^ r) << 4);
#pragma unroll
        for (int j = 0; j < 21; j++)
          stsm4t(ad + (j / 3) * 12288 + (j % 3) * 1024, pack2(yr[4 * j], yr[4 * j + 1]), pack2(yr[4 * j + 2], yr[4 * j + 3]),
                 pack2(yi[4 * j], yi[4 * j + 1]), pack2(yi[4 * j + 2], yi[4 * j + 3]));
        fence_async_smem();
        __syncwarp();
        if (lane == 0) mbar_arrive(bar + B_Y + 8 * wg);
        if (threadIdx.x == 0) PROF_T(2 + pass);
      }
    }
    const int b = id >> 6, u = (id >> 1) & 31;
    const int dq = rank * 2 + (u & 1), tr = u >> 1, t0 = (tr * 167) >> 4, nb = (((tr + 1) * 167) >> 4) - t0;
    const int a = lane & 3, d0 = 16 * w + (lane >> 2);
    float2* s_red = (float2*)(smem_raw + OFF_WRAW);
#pragma unroll 1
    for (int hf = 0; hf < 2; hf++) {
      const uint32_t base = sb + (hf ? 0 : OFF_H0);
      const int d64 = hf * 4 + dq;
      const float gam0 = __bfloat162float(gamma[d64 * 64 + d0]), gam1 = __bfloat162float(gamma[d64 * 64 + d0 + 8]);
      const float bet0 = __bfloat162float(beta[d64 * 64 + d0]), bet1 = __bfloat162float(beta[d64 * 64 + d0 + 8]);
      float acc[6][24];
      float s1[2] = {0.f, 0.f}, s2[2] = {0.f, 0.f};
      if (hf == 0) mbar_wait(bar + B_H0, 0);
#pragma unroll
      for (int k2 = 0; k2 < 4; k2++) {
        if (k2 < 3) {
          if (hf) mbar_wait(bar + B_H1 + 8 * k2, 0);
          const uint64_t da0 = mk_desc(base + (4 * k2 + wg) * 8192), da1 = mk_desc(base + min(4 * k2 + 2 + wg, nb - 1) * 8192), db = mk_desc(sb + OFF_F);
          wg_fence();
#pragma unroll
          for (int kk = 0; kk < 4; kk++) {
            wgmma_inv<1>(acc[2 * k2], da0 + 128 * kk, db + 2 * kk, kk);
            wgmma_inv<1>(acc[2 * k2 + 1], da1 + 128 * kk, db + 2 * kk, kk);
          }
          wg_commit();
        }
        if (k2 > 0) {
          if (k2 < 3) wg_wait<1>(); else wg_wait<0>();
#pragma unroll
          for (int k = 2 * k2 - 2; k < 2 * k2; k++) {
            fence_regs(acc[k]);
            const int nv = 2 * k + wg < nb ? LOUT - (t0 + 2 * k + wg) * MT - 2 * a : 0;
            if (k >= 4 && nv < 48) {
#pragma unroll
              for (int i = 0; i < 24; i++)
                if (8 * (i >> 2) + (i & 1) >= nv) acc[k][i] = 0.f;
            }
#pragma unroll
            for (int i = 0; i < 24; i += 2) {
              s1[(i >> 1) & 1] += acc[k][i] + acc[k][i + 1];
              s2[(i >> 1) & 1] += fmaf(acc[k][i], acc[k][i], acc[k][i + 1] * acc[k][i + 1]);
            }
          }
        }
      }
#pragma unroll
      for (int i = 0; i < 2; i++) {
#pragma unroll
        for (int o = 1; o < 4; o <<= 1) {
          s1[i] += __shfl_xor_sync(0xffffffffu, s1[i], o);
          s2[i] += __shfl_xor_sync(0xffffffffu, s2[i], o);
        }
      }
      if (a == 0) {
        s_red[wg * 64 + d0] = make_float2(s1[0], s2[0]);
        s_red[wg * 64 + d0 + 8] = make_float2(s1[1], s2[1]);
      }
      asm volatile("bar.sync 3, 256;" ::: "memory");
      if (threadIdx.x == 0) PROF_T(6 + 3 * hf);
      unsigned long long* part = g_part + ((hf * 2 + b) * 4 + dq) * 1024;
      if (threadIdx.x < 64) {
        const float2 p0 = s_red[threadIdx.x], p1 = s_red[64 + threadIdx.x];
        const float x1 = p0.x + p1.x, x2 = p0.y + p1.y;
        const unsigned long long v = ((unsigned long long)(__float_as_uint(x2) & 0x7fffffffu) << 32) | __float_as_uint(x1);
        asm volatile("st.relaxed.gpu.global.u64 [%0], %1;" ::"l"(part + tr * 64 + threadIdx.x), "l"(v) : "memory");
      }
      {
        const unsigned long long* q = part + (threadIdx.x >> 6) * 256 + (threadIdx.x & 63);
        unsigned long long v[4];
        poll64x4(q, v);
        float x1 = 0.f, x2 = 0.f;
#pragma unroll
        for (int i = 0; i < 4; i++) {
          x1 += __uint_as_float((uint32_t)v[i]);
          x2 += __uint_as_float((uint32_t)(v[i] >> 32));
        }
        s_red[128 + threadIdx.x] = make_float2(x1, x2);
      }
      asm volatile("bar.sync 3, 256;" ::: "memory");
      if (threadIdx.x == 0) PROF_T(7 + 3 * hf);
#pragma unroll
      for (int i = 0; i < 2; i++) {
        const float2 q0 = s_red[128 + d0 + 8 * i], q1 = s_red[192 + d0 + 8 * i], q2 = s_red[256 + d0 + 8 * i], q3 = s_red[320 + d0 + 8 * i];
        const float mu = ((q0.x + q1.x) + (q2.x + q3.x)) * (1.f / LOUT);
        const float var = fmaxf(((q0.y + q1.y) + (q2.y + q3.y)) * (1.f / LOUT) - mu * mu, 0.f);
        s1[i] = 0.5f * (i ? gam1 : gam0) / sqrtf(var + 1e-5f);
        s2[i] = 0.5f * (i ? bet1 : bet0) - mu * s1[i];
      }
      const int m = lane >> 3, r = lane & 7;
      const uint32_t ad = base + wg * 8192 + ((m >> 1) * 8 + r) * 128 + (((2 * w + (m & 1)) ^ r) << 4);
#pragma unroll
      for (int k = 0; k < 6; k++) {
        if (k < 5 || 2 * k + wg < nb) {
          fence_regs(acc[k]);
#pragma unroll
          for (int i = 0; i < 24; i++) {
            const float hz = fmaf(acc[k][i], s1[(i >> 1) & 1], s2[(i >> 1) & 1]);
            const float in = hz * fmaf(hz * hz, 8.f * 0.044715f * 0.7978845608028654f, 2.f * 0.7978845608028654f);
            float th;
            asm("tanh.approx.f32 %0, %1;" : "=f"(th) : "f"(in));
            acc[k][i] = fmaf(hz, th, hz);
          }
#pragma unroll
          for (int jj = 0; jj < 3; jj++) {
            const float* c = acc[k] + 8 * jj;
            stsm4t(ad + k * 16384 + jj * 2048, pack2(c[0], c[1]), pack2(c[2], c[3]), pack2(c[4], c[5]), pack2(c[6], c[7]));
          }
          fence_async_smem();
          asm volatile("bar.sync %0, 128;" ::"r"(1 + wg) : "memory");
          if (w == 0 && elect_one()) {
            tma_st3(&tm.out, base + (2 * k + wg) * 8192, d64 * 64, (t0 + 2 * k + wg) * MT, b);
            bulk_commit();
          }
        }
      }
      if (threadIdx.x == 0) PROF_T(8 + 3 * hf);
    }
    if (w == 0) bulk_wait_read<0>();
    if (threadIdx.x == 0) PROF_T(12);
    asm volatile("barrier.cluster.arrive.relaxed.aligned;\nbarrier.cluster.wait.aligned;" ::: "memory");
  }
}

typedef CUresult (*EncFn)(CUtensorMap*, CUtensorMapDataType, cuuint32_t, void*, const cuuint64_t*, const cuuint64_t*, const cuuint32_t*,
                          const cuuint32_t*, CUtensorMapInterleave, CUtensorMapSwizzle, CUtensorMapL2promotion, CUtensorMapFloatOOBfill);

void encode(EncFn fn, CUtensorMap* m, int rank, void* base, const cuuint64_t* dims, const cuuint64_t* strides, const cuuint32_t* box,
            CUtensorMapL2promotion promo) {
  cuuint32_t es[5] = {1, 1, 1, 1, 1};
  fn(m, CU_TENSOR_MAP_DATA_TYPE_BFLOAT16, rank, base, dims, strides, box, es, CU_TENSOR_MAP_INTERLEAVE_NONE, CU_TENSOR_MAP_SWIZZLE_128B, promo,
     CU_TENSOR_MAP_FLOAT_OOB_FILL_NONE);
}

}

extern "C" void kernel_launch(void* const* d_in, const int* in_sizes, int n_in, void* d_out, int out_size) {
  (void)in_sizes; (void)n_in; (void)out_size;
  const __nv_bfloat16* x = (const __nv_bfloat16*)d_in[0];
  const __nv_bfloat16* w = (const __nv_bfloat16*)d_in[1];
  const __nv_bfloat16* gamma = (const __nv_bfloat16*)d_in[2];
  const __nv_bfloat16* beta = (const __nv_bfloat16*)d_in[3];
  void* fnp = nullptr;
  cudaDriverEntryPointQueryResult qr;
  cudaGetDriverEntryPoint("cuTensorMapEncodeTiled", &fnp, cudaEnableDefault, &qr);
  EncFn fn = (EncFn)fnp;
  void *xptr = nullptr, *wptr = nullptr, *yptr = nullptr;
  cudaGetSymbolAddress(&xptr, g_X);
  cudaGetSymbolAddress(&wptr, g_W);
  cudaGetSymbolAddress(&yptr, g_Y);
  xptr = (void*)(((uintptr_t)xptr + (1u << 21) - 1) & ~(uintptr_t)((1u << 21) - 1));
  const CUtensorMapL2promotion P0 = CU_TENSOR_MAP_L2_PROMOTION_NONE, P128 = CU_TENSOR_MAP_L2_PROMOTION_L2_128B;
  Maps m;
  {
    cuuint64_t d[3] = {1024, 8000, 2}, s[2] = {2048, 8000ull * 2048};
    cuuint32_t bx[3] = {64, 64, 1};
    encode(fn, &m.x, 3, (void*)x, d, s, bx, P128);
  }
  for (int ph = 0; ph < 2; ph++) {
    cuuint64_t d[3] = {64, (cuuint64_t)(16 - ph), 4096}, s[2] = {2ull * 262144 * 2, 128};
    cuuint32_t bx[3] = {64, 16, 1};
    encode(fn, ph ? &m.wo : &m.we, 3, (void*)(w + (size_t)ph * 262144), d, s, bx, P128);
  }
  for (int par = 0; par < 2; par++) {
    cuuint64_t d[5] = {(cuuint64_t)XPAGES << 20, 2, 4, 2, 2}, s[4] = {par ? 0x1000u : 0x3000u, 1u << 14, 1u << 18, 1u << 20};
    cuuint32_t bx[5] = {64, 2, 4, 2, 2};
    encode(fn, &m.xst[par], 5, xptr, d, s, bx, P0);
  }
  {
    cuuint64_t d[4] = {64, 32, 2, (cuuint64_t)WR * WCHUNK / 128}, s[3] = {4ull * WBLK, 4096, 128};
    cuuint32_t bx[4] = {64, 32, 2, 1};
    encode(fn, &m.wst, 4, wptr, d, s, bx, P0);
  }
  {
    cuuint64_t d[4] = {64, NT, 64, 16}, s[3] = {8192, 128, (cuuint64_t)NT * 8192};
    cuuint32_t bx[4] = {64, 24, 2, 1};
    encode(fn, &m.yst, 4, yptr, d, s, bx, P0);
  }
  {
    cuuint64_t d[2] = {64, 16ull * NT * 64}, s[1] = {128};
    cuuint32_t bx[2] = {64, 64};
    encode(fn, &m.yld, 2, yptr, d, s, bx, P128);
  }
  {
    cuuint64_t d[3] = {512, LOUT, 2}, s[2] = {1024, (cuuint64_t)LOUT * 1024};
    cuuint32_t bx[3] = {64, MT, 1};
    encode(fn, &m.out, 3, d_out, d, s, bx, P0);
  }
  cudaFuncSetAttribute(k1_main, cudaFuncAttributeMaxDynamicSharedMemorySize, SMEM_BYTES);
  k1_main<<<128, 384, SMEM_BYTES>>>(m, (uint8_t*)xptr, gamma, beta);
}
```

```cpp
#include <cuda_runtime.h>
#include <cuda_bf16.h>
#include <cuda.h>
#include <stdint.h>

namespace {

#define LW_ 4
#define WR_ 6
#define OB_ 2
#define XEF0 8
#define XC(c) (c)
#define NOFENCE 0
#define XFIRST 0
constexpr int LOUT = 7985;
constexpr int MT = 50;
constexpr int NT = 160;
constexpr int XBLK = NT * 128;
constexpr int WBLK = 16384;
constexpr int LW = LW_;
constexpr int WR = WR_;
constexpr int OB = OB_;
constexpr int WCHUNK = 32 * 4 * WBLK;
constexpr int XPAGES = 20;
#define NFL 2
constexpr int YFLUSH = 16 + LW + 5;

__device__ __align__(1024) uint8_t g_X[(XPAGES + 2) << 21];
__device__ __align__(1024) uint8_t g_W[(size_t)WR * WCHUNK];
__device__ __align__(1024) uint8_t g_Y[16ull * NT * 8192];
__device__ __align__(128) float g_E[16 * NT * 64];
__device__ unsigned long long g_part[128 * 128];
constexpr int C_FLAG = 0, C_LOADED = 36, C_REG = 68, C_EXIT = 69, C_E = 70, C_NUM = 71;
__device__ __align__(128) unsigned g_ctr[C_NUM * 32];
#define PROF_T(i)
#define PROF_C(i)
#define PROF_V(i, v)
#define PROF_W(acc, stmt) stmt

__device__ __align__(128) const uint32_t g_Fimg[2048] = {
 0x3f803f80,0x3f7d3f7f,0x3f783f7b,0x3f713f75,0x3f673f6d,0x3f5c3f62,0x3f4e3f55,0x3f3e3f46,0x3f2c3f35,0x3f183f22,0x3f043f0e,0x3edb3ef1,0x3eac3ec4,0x3e793e95,0x3e163e48,0x3d493dc9,
 0xbd490000,0xbe16bdc9,0xbe79be48,0xbeacbe95,0xbedbbec4,0xbf04bef1,0xbf18bf0e,0xbf2cbf22,0xbf3ebf35,0xbf4ebf46,0xbf5cbf55,0xbf67bf62,0xbf71bf6d,0xbf78bf75,0xbf7dbf7b,0xbf80bf7f,
 0x3e793ec4,0xbd493dc9,0xbeacbe48,0xbf18bef1,0x3f7d3f80,0x3f673f75,0x3f3e3f55,0x3f043f22,0xbf5cbf6d,0xbf2cbf46,0xbedbbf0e,0xbe16be95,0xbf4ebf35,0xbf71bf62,0xbf80bf7b,0xbf78bf7f,
 0x3f783f6d,0x3f803f7f,0x3f713f7b,0x3f4e3f62,0x3e160000,0x3edb3e95,0x3f2c3f0e,0x3f5c3f46,0xbf04bec4,0xbf3ebf22,0xbf67bf55,0xbf7dbf75,0x3f183f35,0x3eac3ef1,0x3d493e48,0xbe79bdc9,
 0xbf04bf35,0xbd49be95,0x3edb3e48,0x3f4e3f22,0x3f7d3f6d,0x3f713f7f,0x3f2c3f55,0x3e793ef1,0x3f783f80,0x3f3e3f62,0x3eac3f0e,0xbe163dc9,0xbf18bec4,0xbf67bf46,0xbf80bf7b,0xbf5cbf75,
 0x3f5c3f35,0x3f803f75,0x3f673f7b,0x3f183f46,0x3e163ec4,0xbeacbdc9,0xbf3ebf0e,0xbf78bf62,0xbe790000,0xbf2cbef1,0xbf71bf55,0xbf7dbf7f,0xbf4ebf6d,0xbedbbf22,0x3d49be48,0x3f043e95,
 0xbf2cbec4,0xbf7dbf62,0xbf5cbf7b,0xbeacbf22,0x3f673f35,0x3f783f7f,0x3f183f55,0xbd493e95,0xbf80bf6d,0xbf4ebf75,0xbe79bf0e,0x3edb3dc9,0x3f713f80,0x3f043f46,0xbe163e48,0xbf3ebef1,
 0x3f3e3f6d,0x3e163ef1,0xbf04be48,0xbf71bf46,0xbedbbf35,0x3e79bdc9,0x3f4e3f0e,0x3f803f75,0x3d493ec4,0xbf18be95,0xbf78bf55,0xbf67bf7f,0x3eac0000,0x3f5c3f22,0x3f7d3f7b,0x3f2c3f62,
 0xbedb0000,0xbf78bf46,0xbf4ebf7b,0xbd49bef1,0x3f3e3ec4,0x3f7d3f75,0x3f043f55,0xbeac3dc9,0xbf71bf35,0xbf5cbf7f,0xbe16bf0e,0x3f2c3e95,0x3f803f6d,0x3f183f62,0xbe793e48,0xbf67bf22,
 0x3f673f80,0x3e793f22,0xbf18be48,0xbf80bf62,0xbf2cbf6d,0x3e16be95,0x3f5c3f0e,0x3f713f7f,0x3eac3f35,0xbf04bdc9,0xbf7dbf55,0xbf3ebf75,0x3d49bec4,0x3f4e3ef1,0x3f783f7b,0x3edb3f46,
 0xbf7dbf6d,0xbeacbf46,0x3f2c3e48,0x3f783f75,0x3f040000,0x3f803f62,0x3edb3f55,0xbf18bdc9,0x3f4e3ec4,0x3f673f7f,0x3d493f0e,0xbf5cbef1,0x3e793f35,0xbf3ebe95,0xbf71bf7b,0xbe16bf22,
 0x3e16bec4,0x3f713f22,0x3f3e3f7b,0xbe793e95,0x3f5c3f80,0xbd493ef1,0xbf67bf0e,0xbf4ebf7f,0x3f183f6d,0xbedb3dc9,0xbf80bf55,0xbf04bf62,0xbf78bf35,0xbf2cbf75,0x3eacbe48,0x3f7d3f46,
 0x3f7d3f35,0x3edb3f62,0xbf3ebe48,0xbf5cbf7f,0x3e79bec4,0x3f803f46,0x3eac3f55,0xbf4ebe95,0xbf180000,0xbf71bf75,0x3d49bf0e,0x3f783f22,0x3f043f6d,0xbf2cbdc9,0xbf67bf7b,0x3e16bef1,
 0xbe16bf35,0x3f673ef1,0x3f2c3f7b,0xbf043dc9,0xbf78bf6d,0xbd49bf22,0x3f713f0e,0x3f183f75,0x3f4e3f80,0xbeac3e95,0xbf80bf55,0xbe79bf46,0x3f5c3ec4,0x3f3e3f7f,0xbedb3e48,0xbf7dbf62,
 0xbedbbf6d,0x3f5c3e95,0x3f183f7b,0xbf3ebdc9,0xbd49bf35,0x3f7d3f22,0x3e793f55,0xbf71bef1,0x3eacbec4,0x3f783f62,0xbe163f0e,0xbf80bf46,0x3f2c0000,0x3f4e3f7f,0xbf043e48,0xbf67bf75,
 0x3f673ec4,0x3f043f75,0xbf4ebe48,0xbf2cbf7f,0x3f803f35,0x3e163f46,0xbf78bf0e,0xbeacbf62,0x3f713f6d,0xbe793ef1,0xbf7dbf55,0x3d49bf22,0x3f3e3f80,0xbf183dc9,0xbf5cbf7b,0x3edbbe95,
 0xbd490000,0xbe16bdc9,0xbe79be48,0xbeacbe95,0xbedbbec4,0xbf04bef1,0xbf18bf0e,0xbf2cbf22,0xbf3ebf35,0xbf4ebf46,0xbf5cbf55,0xbf67bf62,0xbf71bf6d,0xbf78bf75,0xbf7dbf7b,0xbf80bf7f,
 0xbf80bf80,0xbf7dbf7f,0xbf78bf7b,0xbf71bf75,0xbf67bf6d,0xbf5cbf62,0xbf4ebf55,0xbf3ebf46,0xbf2cbf35,0xbf18bf22,0xbf04bf0e,0xbedbbef1,0xbeacbec4,0xbe79be95,0xbe16be48,0xbd49bdc9,
 0xbf78bf6d,0xbf80bf7f,0xbf71bf7b,0xbf4ebf62,0xbe160000,0xbedbbe95,0xbf2cbf0e,0xbf5cbf46,0x3f043ec4,0x3f3e3f22,0x3f673f55,0x3f7d3f75,0xbf18bf35,0xbeacbef1,0xbd49be48,0x3e793dc9,
 0x3e793ec4,0xbd493dc9,0xbeacbe48,0xbf18bef1,0x3f7d3f80,0x3f673f75,0x3f3e3f55,0x3f043f22,0xbf5cbf6d,0xbf2cbf46,0xbedbbf0e,0xbe16be95,0xbf4ebf35,0xbf71bf62,0xbf80bf7b,0xbf78bf7f,
 0x3f5c3f35,0x3f803f75,0x3f673f7b,0x3f183f46,0x3e163ec4,0xbeacbdc9,0xbf3ebf0e,0xbf78bf62,0xbe790000,0xbf2cbef1,0xbf71bf55,0xbf7dbf7f,0xbf4ebf6d,0xbedbbf22,0x3d49be48,0x3f043e95,
 0x3f043f35,0x3d493e95,0xbedbbe48,0xbf4ebf22,0xbf7dbf6d,0xbf71bf7f,0xbf2cbf55,0xbe79bef1,0xbf78bf80,0xbf3ebf62,0xbeacbf0e,0x3e16bdc9,0x3f183ec4,0x3f673f46,0x3f803f7b,0x3f5c3f75,
 0xbf3ebf6d,0xbe16bef1,0x3f043e48,0x3f713f46,0x3edb3f35,0xbe793dc9,0xbf4ebf0e,0xbf80bf75,0xbd49bec4,0x3f183e95,0x3f783f55,0x3f673f7f,0xbeac0000,0xbf5cbf22,0xbf7dbf7b,0xbf2cbf62,
 0xbf2cbec4,0xbf7dbf62,0xbf5cbf7b,0xbeacbf22,0x3f673f35,0x3f783f7f,0x3f183f55,0xbd493e95,0xbf80bf6d,0xbf4ebf75,0xbe79bf0e,0x3edb3dc9,0x3f713f80,0x3f043f46,0xbe163e48,0xbf3ebef1,
 0xbf67bf80,0xbe79bf22,0x3f183e48,0x3f803f62,0x3f2c3f6d,0xbe163e95,0xbf5cbf0e,0xbf71bf7f,0xbeacbf35,0x3f043dc9,0x3f7d3f55,0x3f3e3f75,0xbd493ec4,0xbf4ebef1,0xbf78bf7b,0xbedbbf46,
 0xbedb0000,0xbf78bf46,0xbf4ebf7b,0xbd49bef1,0x3f3e3ec4,0x3f7d3f75,0x3f043f55,0xbeac3dc9,0xbf71bf35,0xbf5cbf7f,0xbe16bf0e,0x3f2c3e95,0x3f803f6d,0x3f183f62,0xbe793e48,0xbf67bf22,
 0x3e16bec4,0x3f713f22,0x3f3e3f7b,0xbe793e95,0x3f5c3f80,0xbd493ef1,0xbf67bf0e,0xbf4ebf7f,0x3f183f6d,0xbedb3dc9,0xbf80bf55,0xbf04bf62,0xbf78bf35,0xbf2cbf75,0x3eacbe48,0x3f7d3f46,
 0x3f7d3f6d,0x3eac3f46,0xbf2cbe48,0xbf78bf75,0xbf040000,0xbf80bf62,0xbedbbf55,0x3f183dc9,0xbf4ebec4,0xbf67bf7f,0xbd49bf0e,0x3f5c3ef1,0xbe79bf35,0x3f3e3e95,0x3f713f7b,0x3e163f22,
 0x3e163f35,0xbf67bef1,0xbf2cbf7b,0x3f04bdc9,0x3f783f6d,0x3d493f22,0xbf71bf0e,0xbf18bf75,0xbf4ebf80,0x3eacbe95,0x3f803f55,0x3e793f46,0xbf5cbec4,0xbf3ebf7f,0x3edbbe48,0x3f7d3f62,
 0x3f7d3f35,0x3edb3f62,0xbf3ebe48,0xbf5cbf7f,0x3e79bec4,0x3f803f46,0x3eac3f55,0xbf4ebe95,0xbf180000,0xbf71bf75,0x3d49bf0e,0x3f783f22,0x3f043f6d,0xbf2cbdc9,0xbf67bf7b,0x3e16bef1,
 0x3f673ec4,0x3f043f75,0xbf4ebe48,0xbf2cbf7f,0x3f803f35,0x3e163f46,0xbf78bf0e,0xbeacbf62,0x3f713f6d,0xbe793ef1,0xbf7dbf55,0x3d49bf22,0x3f3e3f80,0xbf183dc9,0xbf5cbf7b,0x3edbbe95,
 0x3edb3f6d,0xbf5cbe95,0xbf18bf7b,0x3f3e3dc9,0x3d493f35,0xbf7dbf22,0xbe79bf55,0x3f713ef1,0xbeac3ec4,0xbf78bf62,0x3e16bf0e,0x3f803f46,0xbf2c0000,0xbf4ebf7f,0x3f04be48,0x3f673f75,
 0x3f2c3f80,0xbf4ebdc9,0xbf04bf7b,0x3f673e95,0x3eac3f6d,0xbf78bef1,0xbe16bf55,0x3f803f22,0xbd493f35,0xbf7dbf46,0x3e79bf0e,0x3f713f62,0xbedb3ec4,0xbf5cbf75,0x3f18be48,0x3f3e3f7f,
 0xbf3e0000,0xbf18bf7f,0x3f5c3e48,0x3edb3f75,0xbf71bec4,0xbe79bf62,0x3f7d3f0e,0x3d493f46,0xbf80bf35,0x3e16bf22,0x3f783f55,0xbeac3ef1,0xbf67bf6d,0x3f04be95,0x3f4e3f7b,0xbf2c3dc9,
 0xbf043ec4,0xbf2cbf7f,0x3f673e48,0x3e163f62,0x3f183f80,0xbf71be95,0xbd49bf55,0x3f783f46,0xbe79bf6d,0x3f803f22,0xbeac3f0e,0xbf4ebf75,0xbf7dbf35,0x3edbbef1,0x3f3e3f7b,0xbf5cbdc9,
 0x3f5c3f6d,0xbf3e3dc9,0xbedbbf7b,0x3f7d3ef1,0x3f4e0000,0x3eac3f75,0xbf80bf0e,0x3e79bf22,0xbf78bec4,0x3d49bf46,0x3f713f55,0xbf183e95,0xbe163f35,0xbf67bf62,0x3f2cbe48,0x3f043f7f,
 0x3e79bf35,0x3f3e3f75,0xbf71be48,0x3e16bf46,0x3f4e3f6d,0xbf67bdc9,0x3d49bf55,0x3f5c3f62,0x3f043f80,0xbf80bef1,0x3edbbf0e,0x3f183f7f,0xbf7dbec4,0x3eacbf22,0x3f2c3f7b,0xbf78be95,
 0x3f783f35,0xbf2c3e95,0xbeacbf7b,0x3f7d3f22,0xbf183ec4,0xbedbbf7f,0x3f803f0e,0xbf043ef1,0xbf5c0000,0xbd49bf62,0x3f673f55,0xbf4e3dc9,0xbe16bf6d,0x3f713f46,0xbf3e3e48,0xbe79bf75,
 0xbf80bec4,0x3f18bef1,0x3e793f7b,0xbf67bf46,0x3f713f35,0xbf5c3dc9,0x3e16bf55,0x3f2c3f75,0xbf3ebf6d,0x3f7d3e95,0xbf043f0e,0xbeacbf7f,0x3edb3f80,0xbf78bf22,0x3f4ebe48,0xbd493f62,
 0x3d493f6d,0xbf4ebf62,0x3f783e48,0xbedb3f22,0x3eacbf35,0x3f043f7f,0xbf7dbf0e,0x3f3ebe95,0xbf2c3ec4,0xbe16bf75,0x3f5c3f55,0xbf71bdc9,0x3f670000,0xbe793f46,0xbf18bf7b,0x3f803ef1,
 0xbf710000,0x3f04bf22,0x3e163f7b,0xbf3ebf62,0x3f803ec4,0xbf4e3e95,0x3e79bf55,0x3edb3f7f,0xbf67bf35,0x3f783dc9,0xbf183f0e,0xbd49bf75,0x3f2c3f6d,0xbf7dbef1,0x3f5cbe48,0xbeac3f46,
 0x3eac3f80,0xbf5cbf46,0x3f7d3e48,0xbf2c3ef1,0x3d49bf6d,0x3f183f75,0xbf78bf0e,0x3f67bdc9,0xbedb3f35,0xbe79bf7f,0x3f4e3f55,0xbf80be95,0x3f3ebec4,0xbe163f62,0xbf04bf7b,0x3f713f22,
 0xbf18bf6d,0x3f673f22,0xbf80be48,0x3f5cbe95,0x3f780000,0xbf3e3ef1,0x3eacbf55,0x3e163f7f,0x3f7d3ec4,0xbf713dc9,0x3f2cbf0e,0xbe793f62,0xbf043f35,0x3d49bf75,0x3edb3f7b,0xbf4ebf46,
 0x3f4ebec4,0xbedb3f46,0xbd49bf7b,0x3f043f75,0x3e793f80,0xbf2cbf62,0x3f713f0e,0xbf7dbdc9,0xbe163f6d,0xbeacbf7f,0x3f3e3f55,0xbf78bef1,0xbf5cbf35,0x3f803e95,0xbf673e48,0x3f18bf22,
 0x3f4e3f35,0xbf71bef1,0x3f803e48,0xbf783dc9,0x3f5cbec4,0xbf2c3f22,0x3edbbf55,0xbe163f75,0xbf7d0000,0x3f67be95,0xbf3e3f0e,0x3f04bf46,0xbe793f6d,0xbd49bf7f,0x3eac3f7b,0xbf18bf62,
 0x3f18bf35,0xbeac3f62,0x3d49bf7b,0x3e793f7f,0xbf04bf6d,0x3f3e3f46,0xbf67bf0e,0x3f7d3e95,0x3e163f80,0xbedbbf75,0x3f2c3f55,0xbf5cbf22,0x3f783ec4,0xbf80bdc9,0x3f71be48,0xbf4e3ef1,
 0x3eacbf6d,0xbe793f75,0x3e16bf7b,0xbd493f7f,0x3f2cbf35,0xbf183f46,0x3f04bf55,0xbedb3f62,0x3f67bec4,0xbf5c3ef1,0x3f4ebf0e,0xbf3e3f22,0x3f800000,0xbf7d3dc9,0x3f78be48,0xbf713e95,
 0x3f713ec4,0xbf78be95,0x3f7d3e48,0xbf80bdc9,0x3f3e3f35,0xbf4ebf22,0x3f5c3f0e,0xbf67bef1,0x3edb3f6d,0xbf04bf62,0x3f183f55,0xbf2cbf46,0x3d493f80,0xbe16bf7f,0x3e793f7b,0xbeacbf75,
 0xbf3e0000,0xbf18bf7f,0x3f5c3e48,0x3edb3f75,0xbf71bec4,0xbe79bf62,0x3f7d3f0e,0x3d493f46,0xbf80bf35,0x3e16bf22,0x3f783f55,0xbeac3ef1,0xbf67bf6d,0x3f04be95,0x3f4e3f7b,0xbf2c3dc9,
 0xbf2cbf80,0x3f4e3dc9,0x3f043f7b,0xbf67be95,0xbeacbf6d,0x3f783ef1,0x3e163f55,0xbf80bf22,0x3d49bf35,0x3f7d3f46,0xbe793f0e,0xbf71bf62,0x3edbbec4,0x3f5c3f75,0xbf183e48,0xbf3ebf7f,
 0xbf5cbf6d,0x3f3ebdc9,0x3edb3f7b,0xbf7dbef1,0xbf4e0000,0xbeacbf75,0x3f803f0e,0xbe793f22,0x3f783ec4,0xbd493f46,0xbf71bf55,0x3f18be95,0x3e16bf35,0x3f673f62,0xbf2c3e48,0xbf04bf7f,
 0xbf043ec4,0xbf2cbf7f,0x3f673e48,0x3e163f62,0x3f183f80,0xbf71be95,0xbd49bf55,0x3f783f46,0xbe79bf6d,0x3f803f22,0xbeac3f0e,0xbf4ebf75,0xbf7dbf35,0x3edbbef1,0x3f3e3f7b,0xbf5cbdc9,
 0x3f783f35,0xbf2c3e95,0xbeacbf7b,0x3f7d3f22,0xbf183ec4,0xbedbbf7f,0x3f803f0e,0xbf043ef1,0xbf5c0000,0xbd49bf62,0x3f673f55,0xbf4e3dc9,0xbe16bf6d,0x3f713f46,0xbf3e3e48,0xbe79bf75,
 0xbe793f35,0xbf3ebf75,0x3f713e48,0xbe163f46,0xbf4ebf6d,0x3f673dc9,0xbd493f55,0xbf5cbf62,0xbf04bf80,0x3f803ef1,0xbedb3f0e,0xbf18bf7f,0x3f7d3ec4,0xbeac3f22,0xbf2cbf7b,0x3f783e95,
 0xbd49bf6d,0x3f4e3f62,0xbf78be48,0x3edbbf22,0xbeac3f35,0xbf04bf7f,0x3f7d3f0e,0xbf3e3e95,0x3f2cbec4,0x3e163f75,0xbf5cbf55,0x3f713dc9,0xbf670000,0x3e79bf46,0x3f183f7b,0xbf80bef1,
 0xbf80bec4,0x3f18bef1,0x3e793f7b,0xbf67bf46,0x3f713f35,0xbf5c3dc9,0x3e16bf55,0x3f2c3f75,0xbf3ebf6d,0x3f7d3e95,0xbf043f0e,0xbeacbf7f,0x3edb3f80,0xbf78bf22,0x3f4ebe48,0xbd493f62,
 0xbeacbf80,0x3f5c3f46,0xbf7dbe48,0x3f2cbef1,0xbd493f6d,0xbf18bf75,0x3f783f0e,0xbf673dc9,0x3edbbf35,0x3e793f7f,0xbf4ebf55,0x3f803e95,0xbf3e3ec4,0x3e16bf62,0x3f043f7b,0xbf71bf22,
 0xbf710000,0x3f04bf22,0x3e163f7b,0xbf3ebf62,0x3f803ec4,0xbf4e3e95,0x3e79bf55,0x3edb3f7f,0xbf67bf35,0x3f783dc9,0xbf183f0e,0xbd49bf75,0x3f2c3f6d,0xbf7dbef1,0x3f5cbe48,0xbeac3f46,
 0x3f4ebec4,0xbedb3f46,0xbd49bf7b,0x3f043f75,0x3e793f80,0xbf2cbf62,0x3f713f0e,0xbf7dbdc9,0xbe163f6d,0xbeacbf7f,0x3f3e3f55,0xbf78bef1,0xbf5cbf35,0x3f803e95,0xbf673e48,0x3f18bf22,
 0x3f183f6d,0xbf67bf22,0x3f803e48,0xbf5c3e95,0xbf780000,0x3f3ebef1,0xbeac3f55,0xbe16bf7f,0xbf7dbec4,0x3f71bdc9,0xbf2c3f0e,0x3e79bf62,0x3f04bf35,0xbd493f75,0xbedbbf7b,0x3f4e3f46,
 0xbf183f35,0x3eacbf62,0xbd493f7b,0xbe79bf7f,0x3f043f6d,0xbf3ebf46,0x3f673f0e,0xbf7dbe95,0xbe16bf80,0x3edb3f75,0xbf2cbf55,0x3f5c3f22,0xbf78bec4,0x3f803dc9,0xbf713e48,0x3f4ebef1,
 0x3f4e3f35,0xbf71bef1,0x3f803e48,0xbf783dc9,0x3f5cbec4,0xbf2c3f22,0x3edbbf55,0xbe163f75,0xbf7d0000,0x3f67be95,0xbf3e3f0e,0x3f04bf46,0xbe793f6d,0xbd49bf7f,0x3eac3f7b,0xbf18bf62,
 0x3f713ec4,0xbf78be95,0x3f7d3e48,0xbf80bdc9,0x3f3e3f35,0xbf4ebf22,0x3f5c3f0e,0xbf67bef1,0x3edb3f6d,0xbf04bf62,0x3f183f55,0xbf2cbf46,0x3d493f80,0xbe16bf7f,0x3e793f7b,0xbeacbf75,
 0xbeac3f6d,0x3e79bf75,0xbe163f7b,0x3d49bf7f,0xbf2c3f35,0x3f18bf46,0xbf043f55,0x3edbbf62,0xbf673ec4,0x3f5cbef1,0xbf4e3f0e,0x3f3ebf22,0xbf800000,0x3f7dbdc9,0xbf783e48,0x3f71be95,
 0xbd493f80,0x3e16bf7f,0xbe793f7b,0x3eacbf75,0xbedb3f6d,0x3f04bf62,0xbf183f55,0x3f2cbf46,0xbf3e3f35,0x3f4ebf22,0xbf5c3f0e,0x3f67bef1,0xbf713ec4,0x3f78be95,0xbf7d3e48,0x3f80bdc9,
 0xbf800000,0x3f7d3dc9,0xbf78be48,0x3f713e95,0xbf67bec4,0x3f5c3ef1,0xbf4ebf0e,0x3f3e3f22,0xbf2cbf35,0x3f183f46,0xbf04bf55,0x3edb3f62,0xbeacbf6d,0x3e793f75,0xbe16bf7b,0x3d493f7f,
 0xbf783ec4,0x3f80bdc9,0xbf71be48,0x3f4e3ef1,0xbe163f80,0x3edbbf75,0xbf2c3f55,0x3f5cbf22,0x3f04bf6d,0xbf3e3f46,0x3f67bf0e,0xbf7d3e95,0xbf18bf35,0x3eac3f62,0xbd49bf7b,0xbe793f7f,
 0x3e793f6d,0x3d49bf7f,0xbeac3f7b,0x3f18bf62,0x3f7d0000,0xbf67be95,0x3f3e3f0e,0xbf04bf46,0xbf5cbec4,0x3f2c3f22,0xbedbbf55,0x3e163f75,0xbf4e3f35,0x3f71bef1,0xbf803e48,0x3f783dc9,
 0x3f5cbf35,0xbf803e95,0x3f673e48,0xbf18bf22,0x3e163f6d,0x3eacbf7f,0xbf3e3f55,0x3f78bef1,0xbe793f80,0x3f2cbf62,0xbf713f0e,0x3f7dbdc9,0xbf4ebec4,0x3edb3f46,0x3d49bf7b,0xbf043f75,
 0x3f043f35,0xbd49bf75,0xbedb3f7b,0x3f4ebf46,0xbf7d3ec4,0x3f713dc9,0xbf2cbf0e,0x3e793f62,0xbf780000,0x3f3e3ef1,0xbeacbf55,0xbe163f7f,0x3f18bf6d,0xbf673f22,0x3f80be48,0xbf5cbe95,
 0xbf3ebec4,0x3e163f62,0x3f04bf7b,0xbf713f22,0x3edb3f35,0x3e79bf7f,0xbf4e3f55,0x3f80be95,0xbd49bf6d,0xbf183f75,0x3f78bf0e,0xbf67bdc9,0xbeac3f80,0x3f5cbf46,0xbf7d3e48,0x3f2c3ef1,
 0xbf2c3f6d,0x3f7dbef1,0xbf5cbe48,0x3eac3f46,0x3f67bf35,0xbf783dc9,0x3f183f0e,0x3d49bf75,0xbf803ec4,0x3f4e3e95,0xbe79bf55,0xbedb3f7f,0x3f710000,0xbf04bf22,0xbe163f7b,0x3f3ebf62,
 0xbf670000,0x3e793f46,0x3f18bf7b,0xbf803ef1,0x3f2c3ec4,0x3e16bf75,0xbf5c3f55,0x3f71bdc9,0xbeacbf35,0xbf043f7f,0x3f7dbf0e,0xbf3ebe95,0xbd493f6d,0x3f4ebf62,0xbf783e48,0x3edb3f22,
 0xbedb3f80,0x3f78bf22,0xbf4ebe48,0x3d493f62,0x3f3ebf6d,0xbf7d3e95,0x3f043f0e,0x3eacbf7f,0xbf713f35,0x3f5c3dc9,0xbe16bf55,0xbf2c3f75,0x3f80bec4,0xbf18bef1,0xbe793f7b,0x3f67bf46,
 0x3e16bf6d,0xbf713f46,0x3f3e3e48,0x3e79bf75,0x3f5c0000,0x3d49bf62,0xbf673f55,0x3f4e3dc9,0x3f183ec4,0x3edbbf7f,0xbf803f0e,0x3f043ef1,0xbf783f35,0x3f2c3e95,0x3eacbf7b,0xbf7d3f22,
 0x3f7dbec4,0xbeacbf22,0xbf2c3f7b,0x3f78be95,0xbf043f80,0x3f80bef1,0xbedbbf0e,0xbf183f7f,0xbf4e3f6d,0x3f67bdc9,0xbd49bf55,0xbf5c3f62,0xbe79bf35,0xbf3e3f75,0x3f71be48,0xbe16bf46,
 0x3e163f35,0x3f67bf62,0xbf2cbe48,0xbf043f7f,0x3f78bec4,0xbd49bf46,0xbf713f55,0x3f183e95,0xbf4e0000,0xbeac3f75,0x3f80bf0e,0xbe79bf22,0xbf5c3f6d,0x3f3e3dc9,0x3edbbf7b,0xbf7d3ef1,
 0x3f7dbf35,0xbedbbef1,0xbf3e3f7b,0x3f5cbdc9,0x3e79bf6d,0xbf803f22,0x3eac3f0e,0x3f4ebf75,0xbf183f80,0x3f71be95,0x3d49bf55,0xbf783f46,0x3f043ec4,0x3f2cbf7f,0xbf673e48,0xbe163f62,
 0x3f67bf6d,0xbf04be95,0xbf4e3f7b,0x3f2c3dc9,0x3f80bf35,0xbe16bf22,0xbf783f55,0x3eac3ef1,0x3f71bec4,0x3e79bf62,0xbf7d3f0e,0xbd493f46,0x3f3e0000,0x3f18bf7f,0xbf5c3e48,0xbedb3f75,
 0x3edb3ec4,0x3f5cbf75,0xbf18be48,0xbf3e3f7f,0x3d493f35,0x3f7dbf46,0xbe79bf0e,0xbf713f62,0xbeac3f6d,0x3f78bef1,0x3e16bf55,0xbf803f22,0xbf2c3f80,0x3f4ebdc9,0x3f04bf7b,0xbf673e95,
 0xbf800000,0x3f7d3dc9,0xbf78be48,0x3f713e95,0xbf67bec4,0x3f5c3ef1,0xbf4ebf0e,0x3f3e3f22,0xbf2cbf35,0x3f183f46,0xbf04bf55,0x3edb3f62,0xbeacbf6d,0x3e793f75,0xbe16bf7b,0x3d493f7f,
 0x3d49bf80,0xbe163f7f,0x3e79bf7b,0xbeac3f75,0x3edbbf6d,0xbf043f62,0x3f18bf55,0xbf2c3f46,0x3f3ebf35,0xbf4e3f22,0x3f5cbf0e,0xbf673ef1,0x3f71bec4,0xbf783e95,0x3f7dbe48,0xbf803dc9,
 0xbe79bf6d,0xbd493f7f,0x3eacbf7b,0xbf183f62,0xbf7d0000,0x3f673e95,0xbf3ebf0e,0x3f043f46,0x3f5c3ec4,0xbf2cbf22,0x3edb3f55,0xbe16bf75,0x3f4ebf35,0xbf713ef1,0x3f80be48,0xbf78bdc9,
 0xbf783ec4,0x3f80bdc9,0xbf71be48,0x3f4e3ef1,0xbe163f80,0x3edbbf75,0xbf2c3f55,0x3f5cbf22,0x3f04bf6d,0xbf3e3f46,0x3f67bf0e,0xbf7d3e95,0xbf18bf35,0x3eac3f62,0xbd49bf7b,0xbe793f7f,
 0x3f043f35,0xbd49bf75,0xbedb3f7b,0x3f4ebf46,0xbf7d3ec4,0x3f713dc9,0xbf2cbf0e,0x3e793f62,0xbf780000,0x3f3e3ef1,0xbeacbf55,0xbe163f7f,0x3f18bf6d,0xbf673f22,0x3f80be48,0xbf5cbe95,
 0xbf5c3f35,0x3f80be95,0xbf67be48,0x3f183f22,0xbe16bf6d,0xbeac3f7f,0x3f3ebf55,0xbf783ef1,0x3e79bf80,0xbf2c3f62,0x3f71bf0e,0xbf7d3dc9,0x3f4e3ec4,0xbedbbf46,0xbd493f7b,0x3f04bf75,
 0x3f2cbf6d,0xbf7d3ef1,0x3f5c3e48,0xbeacbf46,0xbf673f35,0x3f78bdc9,0xbf18bf0e,0xbd493f75,0x3f80bec4,0xbf4ebe95,0x3e793f55,0x3edbbf7f,0xbf710000,0x3f043f22,0x3e16bf7b,0xbf3e3f62,
 0xbf3ebec4,0x3e163f62,0x3f04bf7b,0xbf713f22,0x3edb3f35,0x3e79bf7f,0xbf4e3f55,0x3f80be95,0xbd49bf6d,0xbf183f75,0x3f78bf0e,0xbf67bdc9,0xbeac3f80,0x3f5cbf46,0xbf7d3e48,0x3f2c3ef1,
 0x3edbbf80,0xbf783f22,0x3f4e3e48,0xbd49bf62,0xbf3e3f6d,0x3f7dbe95,0xbf04bf0e,0xbeac3f7f,0x3f71bf35,0xbf5cbdc9,0x3e163f55,0x3f2cbf75,0xbf803ec4,0x3f183ef1,0x3e79bf7b,0xbf673f46,
 0xbf670000,0x3e793f46,0x3f18bf7b,0xbf803ef1,0x3f2c3ec4,0x3e16bf75,0xbf5c3f55,0x3f71bdc9,0xbeacbf35,0xbf043f7f,0x3f7dbf0e,0xbf3ebe95,0xbd493f6d,0x3f4ebf62,0xbf783e48,0x3edb3f22,
 0x3f7dbec4,0xbeacbf22,0xbf2c3f7b,0x3f78be95,0xbf043f80,0x3f80bef1,0xbedbbf0e,0xbf183f7f,0xbf4e3f6d,0x3f67bdc9,0xbd49bf55,0xbf5c3f62,0xbe79bf35,0xbf3e3f75,0x3f71be48,0xbe16bf46,
 0xbe163f6d,0x3f71bf46,0xbf3ebe48,0xbe793f75,0xbf5c0000,0xbd493f62,0x3f67bf55,0xbf4ebdc9,0xbf18bec4,0xbedb3f7f,0x3f80bf0e,0xbf04bef1,0x3f78bf35,0xbf2cbe95,0xbeac3f7b,0x3f7dbf22,
 0xbf7d3f35,0x3edb3ef1,0x3f3ebf7b,0xbf5c3dc9,0xbe793f6d,0x3f80bf22,0xbeacbf0e,0xbf4e3f75,0x3f18bf80,0xbf713e95,0xbd493f55,0x3f78bf46,0xbf04bec4,0xbf2c3f7f,0x3f67be48,0x3e16bf62,
 0x3e163f35,0x3f67bf62,0xbf2cbe48,0xbf043f7f,0x3f78bec4,0xbd49bf46,0xbf713f55,0x3f183e95,0xbf4e0000,0xbeac3f75,0x3f80bf0e,0xbe79bf22,0xbf5c3f6d,0x3f3e3dc9,0x3edbbf7b,0xbf7d3ef1,
 0x3edb3ec4,0x3f5cbf75,0xbf18be48,0xbf3e3f7f,0x3d493f35,0x3f7dbf46,0xbe79bf0e,0xbf713f62,0xbeac3f6d,0x3f78bef1,0x3e16bf55,0xbf803f22,0xbf2c3f80,0x3f4ebdc9,0x3f04bf7b,0xbf673e95,
 0xbf673f6d,0x3f043e95,0x3f4ebf7b,0xbf2cbdc9,0xbf803f35,0x3e163f22,0x3f78bf55,0xbeacbef1,0xbf713ec4,0xbe793f62,0x3f7dbf0e,0x3d49bf46,0xbf3e0000,0xbf183f7f,0x3f5cbe48,0x3edbbf75,
 0xbf3e3f80,0x3f183dc9,0x3f5cbf7b,0xbedbbe95,0xbf713f6d,0x3e793ef1,0x3f7dbf55,0xbd49bf22,0xbf803f35,0xbe163f46,0x3f78bf0e,0x3eacbf62,0xbf673ec4,0xbf043f75,0x3f4ebe48,0x3f2cbf7f,
 0xbf2c0000,0xbf4e3f7f,0x3f043e48,0x3f67bf75,0xbeacbec4,0xbf783f62,0x3e163f0e,0x3f80bf46,0x3d49bf35,0xbf7d3f22,0xbe793f55,0x3f71bef1,0x3edbbf6d,0xbf5c3e95,0xbf183f7b,0x3f3ebdc9,
 0xbf5c3ec4,0xbf3e3f7f,0x3edb3e48,0x3f7dbf62,0xbf4e3f80,0x3eac3e95,0x3f80bf55,0x3e79bf46,0x3f78bf6d,0x3d49bf22,0xbf713f0e,0xbf183f75,0x3e16bf35,0xbf673ef1,0xbf2c3f7b,0x3f043dc9,
 0xbf043f6d,0x3f2cbdc9,0x3f67bf7b,0xbe16bef1,0x3f180000,0x3f71bf75,0xbd49bf0e,0xbf783f22,0xbe79bec4,0xbf803f46,0xbeac3f55,0x3f4ebe95,0xbf7d3f35,0xbedb3f62,0x3f3ebe48,0x3f5cbf7f,
 0x3f78bf35,0x3f2cbf75,0xbeacbe48,0xbf7d3f46,0xbf183f6d,0x3edb3dc9,0x3f80bf55,0x3f04bf62,0xbf5c3f80,0x3d493ef1,0x3f67bf0e,0x3f4ebf7f,0xbe16bec4,0xbf713f22,0xbf3e3f7b,0x3e793e95,
 0xbe793f35,0x3f3ebe95,0x3f71bf7b,0x3e16bf22,0xbf4e3ec4,0xbf673f7f,0xbd493f0e,0x3f5cbef1,0xbf040000,0xbf803f62,0xbedb3f55,0x3f18bdc9,0x3f7dbf6d,0x3eacbf46,0xbf2c3e48,0xbf783f75,
 0xbd49bec4,0xbf4e3ef1,0xbf783f7b,0xbedb3f46,0xbeac3f35,0x3f04bdc9,0x3f7dbf55,0x3f3ebf75,0x3f2cbf6d,0xbe16be95,0xbf5c3f0e,0xbf713f7f,0xbf673f80,0xbe793f22,0x3f18be48,0x3f80bf62,
 0xbf803f6d,0xbf183f62,0x3e793e48,0x3f67bf22,0x3f71bf35,0x3f5cbf7f,0x3e16bf0e,0xbf2c3e95,0xbf3e3ec4,0xbf7d3f75,0xbf043f55,0x3eac3dc9,0x3edb0000,0x3f78bf46,0x3f4ebf7b,0x3d49bef1,
 0xbeac0000,0xbf5c3f22,0xbf7d3f7b,0xbf2c3f62,0xbd493ec4,0x3f18be95,0x3f78bf55,0x3f67bf7f,0x3edbbf35,0xbe79bdc9,0xbf4e3f0e,0xbf803f75,0xbf3e3f6d,0xbe163ef1,0x3f04be48,0x3f71bf46,
 0xbf713f80,0xbf043f46,0x3e163e48,0x3f3ebef1,0x3f80bf6d,0x3f4ebf75,0x3e79bf0e,0xbedb3dc9,0xbf673f35,0xbf783f7f,0xbf183f55,0x3d493e95,0x3f2cbec4,0x3f7dbf62,0x3f5cbf7b,0x3eacbf22,
 0x3f4ebf6d,0x3edbbf22,0xbd49be48,0xbf043e95,0x3e790000,0x3f2cbef1,0x3f71bf55,0x3f7dbf7f,0xbe163ec4,0x3eacbdc9,0x3f3ebf0e,0x3f78bf62,0xbf5c3f35,0xbf803f75,0xbf673f7b,0xbf183f46,
 0x3f18bec4,0x3f67bf46,0x3f80bf7b,0x3f5cbf75,0xbf783f80,0xbf3e3f62,0xbeac3f0e,0x3e163dc9,0xbf7d3f6d,0xbf713f7f,0xbf2c3f55,0xbe793ef1,0x3f04bf35,0x3d49be95,0xbedb3e48,0xbf4e3f22,
 0xbf183f35,0xbeac3ef1,0xbd493e48,0x3e79bdc9,0x3f04bec4,0x3f3ebf22,0x3f67bf55,0x3f7dbf75,0xbe160000,0xbedb3e95,0xbf2c3f0e,0xbf5c3f46,0xbf783f6d,0xbf803f7f,0xbf713f7b,0xbf4e3f62,
 0x3f4ebf35,0x3f71bf62,0x3f80bf7b,0x3f78bf7f,0x3f5cbf6d,0x3f2cbf46,0x3edbbf0e,0x3e16be95,0xbf7d3f80,0xbf673f75,0xbf3e3f55,0xbf043f22,0xbe793ec4,0x3d493dc9,0x3eacbe48,0x3f18bef1,
 0x3f71bf6d,0x3f78bf75,0x3f7dbf7b,0x3f80bf7f,0x3f3ebf35,0x3f4ebf46,0x3f5cbf55,0x3f67bf62,0x3edbbec4,0x3f04bef1,0x3f18bf0e,0x3f2cbf22,0x3d490000,0x3e16bdc9,0x3e79be48,0x3eacbe95,
 0xbeac3ec4,0xbe793e95,0xbe163e48,0xbd493dc9,0xbf2c3f35,0xbf183f22,0xbf043f0e,0xbedb3ef1,0xbf673f6d,0xbf5c3f62,0xbf4e3f55,0xbf3e3f46,0xbf803f80,0xbf7d3f7f,0xbf783f7b,0xbf713f75,
 0xbf2c0000,0xbf4e3f7f,0x3f043e48,0x3f67bf75,0xbeacbec4,0xbf783f62,0x3e163f0e,0x3f80bf46,0x3d49bf35,0xbf7d3f22,0xbe793f55,0x3f71bef1,0x3edbbf6d,0xbf5c3e95,0xbf183f7b,0x3f3ebdc9,
 0x3f3ebf80,0xbf18bdc9,0xbf5c3f7b,0x3edb3e95,0x3f71bf6d,0xbe79bef1,0xbf7d3f55,0x3d493f22,0x3f80bf35,0x3e16bf46,0xbf783f0e,0xbeac3f62,0x3f67bec4,0x3f04bf75,0xbf4e3e48,0xbf2c3f7f,
 0x3f04bf6d,0xbf2c3dc9,0xbf673f7b,0x3e163ef1,0xbf180000,0xbf713f75,0x3d493f0e,0x3f78bf22,0x3e793ec4,0x3f80bf46,0x3eacbf55,0xbf4e3e95,0x3f7dbf35,0x3edbbf62,0xbf3e3e48,0xbf5c3f7f,
 0xbf5c3ec4,0xbf3e3f7f,0x3edb3e48,0x3f7dbf62,0xbf4e3f80,0x3eac3e95,0x3f80bf55,0x3e79bf46,0x3f78bf6d,0x3d49bf22,0xbf713f0e,0xbf183f75,0x3e16bf35,0xbf673ef1,0xbf2c3f7b,0x3f043dc9,
 0xbe793f35,0x3f3ebe95,0x3f71bf7b,0x3e16bf22,0xbf4e3ec4,0xbf673f7f,0xbd493f0e,0x3f5cbef1,0xbf040000,0xbf803f62,0xbedb3f55,0x3f18bdc9,0x3f7dbf6d,0x3eacbf46,0xbf2c3e48,0xbf783f75,
 0xbf783f35,0xbf2c3f75,0x3eac3e48,0x3f7dbf46,0x3f18bf6d,0xbedbbdc9,0xbf803f55,0xbf043f62,0x3f5cbf80,0xbd49bef1,0xbf673f0e,0xbf4e3f7f,0x3e163ec4,0x3f71bf22,0x3f3ebf7b,0xbe79be95,
 0x3f80bf6d,0x3f18bf62,0xbe79be48,0xbf673f22,0xbf713f35,0xbf5c3f7f,0xbe163f0e,0x3f2cbe95,0x3f3ebec4,0x3f7dbf75,0x3f04bf55,0xbeacbdc9,0xbedb0000,0xbf783f46,0xbf4e3f7b,0xbd493ef1,
 0xbd49bec4,0xbf4e3ef1,0xbf783f7b,0xbedb3f46,0xbeac3f35,0x3f04bdc9,0x3f7dbf55,0x3f3ebf75,0x3f2cbf6d,0xbe16be95,0xbf5c3f0e,0xbf713f7f,0xbf673f80,0xbe793f22,0x3f18be48,0x3f80bf62,
 0x3f71bf80,0x3f04bf46,0xbe16be48,0xbf3e3ef1,0xbf803f6d,0xbf4e3f75,0xbe793f0e,0x3edbbdc9,0x3f67bf35,0x3f78bf7f,0x3f18bf55,0xbd49be95,0xbf2c3ec4,0xbf7d3f62,0xbf5c3f7b,0xbeac3f22,
 0xbeac0000,0xbf5c3f22,0xbf7d3f7b,0xbf2c3f62,0xbd493ec4,0x3f18be95,0x3f78bf55,0x3f67bf7f,0x3edbbf35,0xbe79bdc9,0xbf4e3f0e,0xbf803f75,0xbf3e3f6d,0xbe163ef1,0x3f04be48,0x3f71bf46,
 0x3f18bec4,0x3f67bf46,0x3f80bf7b,0x3f5cbf75,0xbf783f80,0xbf3e3f62,0xbeac3f0e,0x3e163dc9,0xbf7d3f6d,0xbf713f7f,0xbf2c3f55,0xbe793ef1,0x3f04bf35,0x3d49be95,0xbedb3e48,0xbf4e3f22,
 0xbf4e3f6d,0xbedb3f22,0x3d493e48,0x3f04be95,0xbe790000,0xbf2c3ef1,0xbf713f55,0xbf7d3f7f,0x3e16bec4,0xbeac3dc9,0xbf3e3f0e,0xbf783f62,0x3f5cbf35,0x3f80bf75,0x3f67bf7b,0x3f18bf46,
 0xbf4e3f35,0xbf713f62,0xbf803f7b,0xbf783f7f,0xbf5c3f6d,0xbf2c3f46,0xbedb3f0e,0xbe163e95,0x3f7dbf80,0x3f67bf75,0x3f3ebf55,0x3f04bf22,0x3e79bec4,0xbd49bdc9,0xbeac3e48,0xbf183ef1,
 0xbf183f35,0xbeac3ef1,0xbd493e48,0x3e79bdc9,0x3f04bec4,0x3f3ebf22,0x3f67bf55,0x3f7dbf75,0xbe160000,0xbedb3e95,0xbf2c3f0e,0xbf5c3f46,0xbf783f6d,0xbf803f7f,0xbf713f7b,0xbf4e3f62,
 0xbeac3ec4,0xbe793e95,0xbe163e48,0xbd493dc9,0xbf2c3f35,0xbf183f22,0xbf043f0e,0xbedb3ef1,0xbf673f6d,0xbf5c3f62,0xbf4e3f55,0xbf3e3f46,0xbf803f80,0xbf7d3f7f,0xbf783f7b,0xbf713f75,
 0xbf713f6d,0xbf783f75,0xbf7d3f7b,0xbf803f7f,0xbf3e3f35,0xbf4e3f46,0xbf5c3f55,0xbf673f62,0xbedb3ec4,0xbf043ef1,0xbf183f0e,0xbf2c3f22,0xbd490000,0xbe163dc9,0xbe793e48,0xbeac3e95,
};
__device__ __align__(128) const uint32_t g_Gimg[1792] = {
 0x00003d00,0x00003d00,0x00003d00,0x00003d00,0x00003d00,0x00003d00,0x00003d00,0x00003d00,0x00003d00,0x00003d00,0x00003d00,0x00003d00,0x00003d00,0x00003d00,0x00003d00,0x00003d00,
 0x00003d00,0x00003d00,0x00003d00,0x00003d00,0x00003d00,0x00003d00,0x00003d00,0x00003d00,0x00003d00,0x00003d00,0x00003d00,0x00003d00,0x00003d00,0x00003d00,0x00003d00,0x00003d00,
 0xbc5b3ce7,0xbc843cdc,0xbc983cce,0xbcac3cbe,0xbac93d00,0xbb963cfd,0xbbf93cf8,0xbc2c3cf1,0xbcf13c2c,0xbcf83bf9,0xbcfd3b96,0xbd003ac9,0xbcbe3cac,0xbcce3c98,0xbcdc3c84,0xbce73c5b,
 0xbce7bc5b,0xbcdcbc84,0xbccebc98,0xbcbebcac,0xbd00bac9,0xbcfdbb96,0xbcf8bbf9,0xbcf1bc2c,0xbc2cbcf1,0xbbf9bcf8,0xbb96bcfd,0xbac9bd00,0xbcacbcbe,0xbc98bcce,0xbc84bcdc,0xbc5bbce7,
 0xbcffbb49,0xbcf5bc15,0xbce2bc71,0xbcc6bca2,0xbca2bcc6,0xbc71bce2,0xbc15bcf5,0xbb49bcff,0xbb493cff,0xbc153cf5,0xbc713ce2,0xbca23cc6,0xbcc63ca2,0xbce23c71,0xbcf53c15,0xbcff3b49,
 0x3cff3b49,0x3cf53c15,0x3ce23c71,0x3cc63ca2,0x3ca23cc6,0x3c713ce2,0x3c153cf5,0x3b493cff,0x3b49bcff,0x3c15bcf5,0x3c71bce2,0x3ca2bcc6,0x3cc6bca2,0x3ce2bc71,0x3cf5bc15,0x3cffbb49,
 0x3c84bcdc,0x3cbebcac,0x3ce7bc5b,0x3cfdbb96,0xbc98bcce,0xbc2cbcf1,0xbac9bd00,0x3bf9bcf8,0xbcf83bf9,0xbd00bac9,0xbcf1bc2c,0xbccebc98,0xbb963cfd,0xbc5b3ce7,0xbcac3cbe,0xbcdc3c84,
 0xbcdcbc84,0xbcacbcbe,0xbc5bbce7,0xbb96bcfd,0xbcce3c98,0xbcf13c2c,0xbd003ac9,0xbcf8bbf9,0x3bf93cf8,0xbac93d00,0xbc2c3cf1,0xbc983cce,0x3cfd3b96,0x3ce73c5b,0x3cbe3cac,0x3c843cdc,
 0xbbc83cfb,0xbc8e3cd5,0xbcd53c8e,0xbcfb3bc8,0xbcfbbbc8,0xbcd5bc8e,0xbc8ebcd5,0xbbc8bcfb,0x3bc8bcfb,0x3c8ebcd5,0x3cd5bc8e,0x3cfbbbc8,0x3cfb3bc8,0x3cd53c8e,0x3c8e3cd5,0x3bc83cfb,
 0xbbc83cfb,0xbc8e3cd5,0xbcd53c8e,0xbcfb3bc8,0xbcfbbbc8,0xbcd5bc8e,0xbc8ebcd5,0xbbc8bcfb,0x3bc8bcfb,0x3c8ebcd5,0x3cd5bc8e,0x3cfbbbc8,0x3cfb3bc8,0x3cd53c8e,0x3c8e3cd5,0x3bc83cfb,
 0x3c98bcce,0x3ce7bc5b,0x3d003ac9,0x3cdc3c84,0xbcf8bbf9,0xbcbebcac,0xbc2cbcf1,0x3b96bcfd,0xbcfd3b96,0xbcf1bc2c,0xbcacbcbe,0xbbf9bcf8,0x3c843cdc,0x3ac93d00,0xbc5b3ce7,0xbcce3c98,
 0xbccebc98,0xbc5bbce7,0x3ac9bd00,0x3c84bcdc,0xbbf93cf8,0xbcac3cbe,0xbcf13c2c,0xbcfdbb96,0x3b963cfd,0xbc2c3cf1,0xbcbe3cac,0xbcf83bf9,0x3cdcbc84,0x3d00bac9,0x3ce73c5b,0x3c983cce,
 0xbcf5bc15,0xbca2bcc6,0xbb49bcff,0x3c71bce2,0x3ce2bc71,0x3cff3b49,0x3cc63ca2,0x3c153cf5,0x3c15bcf5,0x3cc6bca2,0x3cffbb49,0x3ce23c71,0x3c713ce2,0xbb493cff,0xbca23cc6,0xbcf53c15,
 0x3cf53c15,0x3ca23cc6,0x3b493cff,0xbc713ce2,0xbce23c71,0xbcffbb49,0xbcc6bca2,0xbc15bcf5,0xbc153cf5,0xbcc63ca2,0xbcff3b49,0xbce2bc71,0xbc71bce2,0x3b49bcff,0x3ca2bcc6,0x3cf5bc15,
 0xbcac3cbe,0xbcfd3b96,0xbcdcbc84,0xbc2cbcf1,0x3ce7bc5b,0x3cf83bf9,0x3c983cce,0xbac93d00,0xbd003ac9,0xbccebc98,0xbbf9bcf8,0x3c5bbce7,0x3cf13c2c,0x3c843cdc,0xbb963cfd,0xbcbe3cac,
 0xbcbebcac,0xbb96bcfd,0x3c84bcdc,0x3cf1bc2c,0x3c5b3ce7,0xbbf93cf8,0xbcce3c98,0xbd00bac9,0xbac9bd00,0x3c98bcce,0x3cf8bbf9,0x3ce73c5b,0xbc2c3cf1,0xbcdc3c84,0xbcfdbb96,0xbcacbcbe,
 0xbc443ced,0xbced3c44,0xbcedbc44,0xbc44bced,0x3c44bced,0x3cedbc44,0x3ced3c44,0x3c443ced,0xbc443ced,0xbced3c44,0xbcedbc44,0xbc44bced,0x3c44bced,0x3cedbc44,0x3ced3c44,0x3c443ced,
 0xbc443ced,0xbced3c44,0xbcedbc44,0xbc44bced,0x3c44bced,0x3cedbc44,0x3ced3c44,0x3c443ced,0xbc443ced,0xbced3c44,0xbcedbc44,0xbc44bced,0x3c44bced,0x3cedbc44,0x3ced3c44,0x3c443ced,
 0x3cbebcac,0x3cfd3b96,0x3c843cdc,0xbc2c3cf1,0xbc5b3ce7,0xbcf83bf9,0xbccebc98,0xbac9bd00,0x3d003ac9,0x3c983cce,0xbbf93cf8,0xbce73c5b,0xbcf13c2c,0xbcdcbc84,0xbb96bcfd,0x3cacbcbe,
 0x3cac3cbe,0xbb963cfd,0xbcdc3c84,0xbcf1bc2c,0xbce7bc5b,0xbbf9bcf8,0x3c98bcce,0x3d00bac9,0xbac93d00,0xbcce3c98,0xbcf8bbf9,0xbc5bbce7,0xbc2cbcf1,0x3c84bcdc,0x3cfdbb96,0x3cbe3cac,
 0xbce2bc71,0xbb49bcff,0x3cc6bca2,0x3cf53c15,0x3c153cf5,0xbca23cc6,0xbcffbb49,0xbc71bce2,0xbc713ce2,0xbcff3b49,0xbca2bcc6,0x3c15bcf5,0x3cf5bc15,0x3cc63ca2,0xbb493cff,0xbce23c71,
 0x3ce23c71,0x3b493cff,0xbcc63ca2,0xbcf5bc15,0xbc15bcf5,0x3ca2bcc6,0x3cff3b49,0x3c713ce2,0x3c71bce2,0x3cffbb49,0x3ca23cc6,0xbc153cf5,0xbcf53c15,0xbcc6bca2,0x3b49bcff,0x3ce2bc71,
 0xbcce3c98,0xbce7bc5b,0xbac9bd00,0x3cdcbc84,0xbbf9bcf8,0x3cbebcac,0x3cf13c2c,0x3b963cfd,0x3cfd3b96,0x3c2c3cf1,0xbcac3cbe,0xbcf8bbf9,0xbc843cdc,0xbd00bac9,0xbc5bbce7,0x3c98bcce,
 0x3c983cce,0xbc5b3ce7,0xbd003ac9,0xbc84bcdc,0xbcf83bf9,0xbcacbcbe,0x3c2cbcf1,0x3cfdbb96,0x3b96bcfd,0x3cf1bc2c,0x3cbe3cac,0xbbf93cf8,0x3cdc3c84,0xbac93d00,0xbce73c5b,0xbccebc98,
 0xbc8e3cd5,0xbcfbbbc8,0xbbc8bcfb,0x3cd5bc8e,0x3cd53c8e,0xbbc83cfb,0xbcfb3bc8,0xbc8ebcd5,0x3c8ebcd5,0x3cfb3bc8,0x3bc83cfb,0xbcd53c8e,0xbcd5bc8e,0x3bc8bcfb,0x3cfbbbc8,0x3c8e3cd5,
 0xbc8e3cd5,0xbcfbbbc8,0xbbc8bcfb,0x3cd5bc8e,0x3cd53c8e,0xbbc83cfb,0xbcfb3bc8,0xbc8ebcd5,0x3c8ebcd5,0x3cfb3bc8,0x3bc83cfb,0xbcd53c8e,0xbcd5bc8e,0x3bc8bcfb,0x3cfbbbc8,0x3c8e3cd5,
 0xbcdc3c84,0xbcbebcac,0x3c5bbce7,0x3cfd3b96,0xbccebc98,0x3c2cbcf1,0x3d003ac9,0x3bf93cf8,0x3cf83bf9,0x3ac93d00,0xbcf13c2c,0xbc98bcce,0x3b963cfd,0xbce73c5b,0xbcacbcbe,0x3c84bcdc,
 0x3c843cdc,0xbcac3cbe,0xbce7bc5b,0x3b96bcfd,0xbc983cce,0xbcf1bc2c,0x3ac9bd00,0x3cf8bbf9,0x3bf9bcf8,0x3d00bac9,0x3c2c3cf1,0xbcce3c98,0x3cfdbb96,0x3c5b3ce7,0xbcbe3cac,0xbcdcbc84,
 0xbcc6bca2,0x3c71bce2,0x3cf53c15,0xbb493cff,0xbcff3b49,0xbc15bcf5,0x3ce2bc71,0x3ca23cc6,0x3ca2bcc6,0x3ce23c71,0xbc153cf5,0xbcffbb49,0xbb49bcff,0x3cf5bc15,0x3c713ce2,0xbcc63ca2,
 0x3cc63ca2,0xbc713ce2,0xbcf5bc15,0x3b49bcff,0x3cffbb49,0x3c153cf5,0xbce23c71,0xbca2bcc6,0xbca23cc6,0xbce2bc71,0x3c15bcf5,0x3cff3b49,0x3b493cff,0xbcf53c15,0xbc71bce2,0x3cc6bca2,
 0x3ce7bc5b,0x3c843cdc,0xbcce3c98,0xbcacbcbe,0x3d00bac9,0x3b963cfd,0xbcf83bf9,0xbc2cbcf1,0x3cf13c2c,0xbbf93cf8,0xbcfdbb96,0x3ac9bd00,0x3cbe3cac,0xbc983cce,0xbcdcbc84,0x3c5bbce7,
 0x3c5b3ce7,0xbcdc3c84,0xbc98bcce,0x3cbebcac,0x3ac93d00,0xbcfd3b96,0xbbf9bcf8,0x3cf1bc2c,0xbc2c3cf1,0xbcf8bbf9,0x3b96bcfd,0x3d003ac9,0xbcac3cbe,0xbccebc98,0x3c84bcdc,0x3ce73c5b,
 0xbcb53cb5,0xbcb5bcb5,0x3cb5bcb5,0x3cb53cb5,0xbcb53cb5,0xbcb5bcb5,0x3cb5bcb5,0x3cb53cb5,0xbcb53cb5,0xbcb5bcb5,0x3cb5bcb5,0x3cb53cb5,0xbcb53cb5,0xbcb5bcb5,0x3cb5bcb5,0x3cb53cb5,
 0xbcb53cb5,0xbcb5bcb5,0x3cb5bcb5,0x3cb53cb5,0xbcb53cb5,0xbcb5bcb5,0x3cb5bcb5,0x3cb53cb5,0xbcb53cb5,0xbcb5bcb5,0x3cb5bcb5,0x3cb53cb5,0xbcb53cb5,0xbcb5bcb5,0x3cb5bcb5,0x3cb53cb5,
 0xbcf13c2c,0xbbf9bcf8,0x3cfdbb96,0x3ac93d00,0xbcbe3cac,0xbc98bcce,0x3cdcbc84,0x3c5b3ce7,0xbce7bc5b,0x3c84bcdc,0x3cce3c98,0xbcac3cbe,0xbd00bac9,0x3b96bcfd,0x3cf83bf9,0xbc2c3cf1,
 0xbc2cbcf1,0x3cf8bbf9,0x3b963cfd,0xbd003ac9,0xbcacbcbe,0x3ccebc98,0x3c843cdc,0xbce73c5b,0x3c5bbce7,0x3cdc3c84,0xbc983cce,0xbcbebcac,0x3ac9bd00,0x3cfd3b96,0xbbf93cf8,0xbcf1bc2c,
 0xbca2bcc6,0x3ce2bc71,0x3c153cf5,0xbcff3b49,0x3b49bcff,0x3cf53c15,0xbc713ce2,0xbcc6bca2,0xbcc63ca2,0xbc71bce2,0x3cf5bc15,0x3b493cff,0xbcffbb49,0x3c15bcf5,0x3ce23c71,0xbca23cc6,
 0x3ca23cc6,0xbce23c71,0xbc15bcf5,0x3cffbb49,0xbb493cff,0xbcf5bc15,0x3c71bce2,0x3cc63ca2,0x3cc6bca2,0x3c713ce2,0xbcf53c15,0xbb49bcff,0x3cff3b49,0xbc153cf5,0xbce2bc71,0x3ca2bcc6,
 0x3cf8bbf9,0xbac93d00,0xbcf1bc2c,0x3c98bcce,0x3b96bcfd,0x3ce73c5b,0xbcac3cbe,0xbc84bcdc,0xbcdcbc84,0x3cbebcac,0x3c5b3ce7,0xbcfd3b96,0xbcce3c98,0xbc2cbcf1,0x3d00bac9,0xbbf93cf8,
 0xbbf9bcf8,0x3d003ac9,0xbc2c3cf1,0xbccebc98,0xbcfdbb96,0x3c5bbce7,0x3cbe3cac,0xbcdc3c84,0xbc843cdc,0xbcacbcbe,0x3ce7bc5b,0x3b963cfd,0x3c983cce,0xbcf13c2c,0xbac9bd00,0x3cf83bf9,
 0xbcd53c8e,0xbbc8bcfb,0x3cfb3bc8,0xbc8e3cd5,0xbc8ebcd5,0x3cfbbbc8,0xbbc83cfb,0xbcd5bc8e,0x3cd5bc8e,0x3bc83cfb,0xbcfbbbc8,0x3c8ebcd5,0x3c8e3cd5,0xbcfb3bc8,0x3bc8bcfb,0x3cd53c8e,
 0xbcd53c8e,0xbbc8bcfb,0x3cfb3bc8,0xbc8e3cd5,0xbc8ebcd5,0x3cfbbbc8,0xbbc83cfb,0xbcd5bc8e,0x3cd5bc8e,0x3bc83cfb,0xbcfbbbc8,0x3c8ebcd5,0x3c8e3cd5,0xbcfb3bc8,0x3bc8bcfb,0x3cd53c8e,
 0x3cfdbb96,0xbc2c3cf1,0xbcacbcbe,0x3cf8bbf9,0xbc84bcdc,0x3d00bac9,0xbc5b3ce7,0xbc98bcce,0xbccebc98,0x3ce7bc5b,0xbac93d00,0xbcdcbc84,0xbbf93cf8,0xbcbebcac,0x3cf1bc2c,0xbb963cfd,
 0xbb96bcfd,0x3cf13c2c,0xbcbe3cac,0xbbf9bcf8,0xbcdc3c84,0xbac9bd00,0x3ce73c5b,0xbcce3c98,0xbc983cce,0xbc5bbce7,0x3d003ac9,0xbc843cdc,0x3cf83bf9,0xbcac3cbe,0xbc2cbcf1,0x3cfd3b96,
 0xbc71bce2,0x3cff3b49,0xbca23cc6,0xbc15bcf5,0x3cf53c15,0xbcc63ca2,0xbb49bcff,0x3ce23c71,0x3ce2bc71,0xbb493cff,0xbcc6bca2,0x3cf5bc15,0xbc153cf5,0xbca2bcc6,0x3cffbb49,0xbc713ce2,
 0x3c713ce2,0xbcffbb49,0x3ca2bcc6,0x3c153cf5,0xbcf5bc15,0x3cc6bca2,0x3b493cff,0xbce2bc71,0xbce23c71,0x3b49bcff,0x3cc63ca2,0xbcf53c15,0x3c15bcf5,0x3ca23cc6,0xbcff3b49,0x3c71bce2,
 0xbd003ac9,0x3c98bcce,0x3bf93cf8,0xbce7bc5b,0x3cf13c2c,0xbcdc3c84,0x3b96bcfd,0x3cac3cbe,0xbcbebcac,0x3cfdbb96,0xbc843cdc,0xbc2cbcf1,0x3c5b3ce7,0xbcf8bbf9,0x3ccebc98,0xbac93d00,
 0xbac9bd00,0x3cce3c98,0xbcf83bf9,0x3c5bbce7,0xbc2c3cf1,0xbc84bcdc,0x3cfd3b96,0xbcbe3cac,0x3cacbcbe,0x3b963cfd,0xbcdcbc84,0x3cf1bc2c,0xbce73c5b,0x3bf9bcf8,0x3c983cce,0xbd00bac9,
 0xbced3c44,0x3c44bced,0x3c443ced,0xbcedbc44,0x3cedbc44,0xbc443ced,0xbc44bced,0x3ced3c44,0xbced3c44,0x3c44bced,0x3c443ced,0xbcedbc44,0x3cedbc44,0xbc443ced,0xbc44bced,0x3ced3c44,
 0xbced3c44,0x3c44bced,0x3c443ced,0xbcedbc44,0x3cedbc44,0xbc443ced,0xbc44bced,0x3ced3c44,0xbced3c44,0x3c44bced,0x3c443ced,0xbcedbc44,0x3cedbc44,0xbc443ced,0xbc44bced,0x3ced3c44,
 0x3d003ac9,0xbcce3c98,0x3bf9bcf8,0x3c5b3ce7,0xbcf13c2c,0x3c84bcdc,0x3b963cfd,0xbcbebcac,0x3cac3cbe,0xbcfdbb96,0x3cdcbc84,0xbc2c3cf1,0xbce7bc5b,0x3cf8bbf9,0xbc983cce,0xbac9bd00,
 0xbac93d00,0xbc98bcce,0x3cf83bf9,0xbce73c5b,0xbc2cbcf1,0x3cdc3c84,0xbcfd3b96,0x3cacbcbe,0xbcbe3cac,0x3b96bcfd,0x3c843cdc,0xbcf1bc2c,0x3c5bbce7,0x3bf93cf8,0xbccebc98,0x3d00bac9,
 0xbc15bcf5,0x3cc63ca2,0xbcffbb49,0x3ce2bc71,0xbc713ce2,0xbb49bcff,0x3ca23cc6,0xbcf5bc15,0xbcf53c15,0x3ca2bcc6,0xbb493cff,0xbc71bce2,0x3ce23c71,0xbcff3b49,0x3cc6bca2,0xbc153cf5,
 0x3c153cf5,0xbcc6bca2,0x3cff3b49,0xbce23c71,0x3c71bce2,0x3b493cff,0xbca2bcc6,0x3cf53c15,0x3cf5bc15,0xbca23cc6,0x3b49bcff,0x3c713ce2,0xbce2bc71,0x3cffbb49,0xbcc63ca2,0x3c15bcf5,
 0xbcfdbb96,0x3cf1bc2c,0xbcac3cbe,0x3bf9bcf8,0x3c84bcdc,0xbac93d00,0xbc5bbce7,0x3cce3c98,0x3c983cce,0xbce7bc5b,0x3d00bac9,0xbcdc3c84,0xbcf83bf9,0x3cbebcac,0xbc2c3cf1,0xbb96bcfd,
 0xbb963cfd,0xbc2cbcf1,0x3cbe3cac,0xbcf8bbf9,0xbcdcbc84,0x3d003ac9,0xbce73c5b,0x3c98bcce,0x3ccebc98,0xbc5b3ce7,0xbac9bd00,0x3c843cdc,0x3bf93cf8,0xbcacbcbe,0x3cf13c2c,0xbcfd3b96,
 0xbcfb3bc8,0x3cd5bc8e,0xbc8e3cd5,0x3bc8bcfb,0x3bc83cfb,0xbc8ebcd5,0x3cd53c8e,0xbcfbbbc8,0x3cfbbbc8,0xbcd53c8e,0x3c8ebcd5,0xbbc83cfb,0xbbc8bcfb,0x3c8e3cd5,0xbcd5bc8e,0x3cfb3bc8,
 0xbcfb3bc8,0x3cd5bc8e,0xbc8e3cd5,0x3bc8bcfb,0x3bc83cfb,0xbc8ebcd5,0x3cd53c8e,0xbcfbbbc8,0x3cfbbbc8,0xbcd53c8e,0x3c8ebcd5,0xbbc83cfb,0xbbc8bcfb,0x3c8e3cd5,0xbcd5bc8e,0x3cfb3bc8,
 0xbcf8bbf9,0x3d00bac9,0xbcf13c2c,0x3ccebc98,0xbb96bcfd,0x3c5b3ce7,0xbcacbcbe,0x3cdc3c84,0x3c843cdc,0xbcbebcac,0x3ce73c5b,0xbcfdbb96,0xbc983cce,0x3c2cbcf1,0xbac93d00,0xbbf9bcf8,
 0xbbf93cf8,0xbac9bd00,0x3c2c3cf1,0xbc98bcce,0xbcfd3b96,0x3ce7bc5b,0xbcbe3cac,0x3c84bcdc,0x3cdcbc84,0xbcac3cbe,0x3c5bbce7,0xbb963cfd,0x3cce3c98,0xbcf1bc2c,0x3d003ac9,0xbcf83bf9,
 0xbb49bcff,0x3c153cf5,0xbc71bce2,0x3ca23cc6,0xbcc6bca2,0x3ce23c71,0xbcf5bc15,0x3cff3b49,0x3cffbb49,0xbcf53c15,0x3ce2bc71,0xbcc63ca2,0x3ca2bcc6,0xbc713ce2,0x3c15bcf5,0xbb493cff,
 0x3b493cff,0xbc15bcf5,0x3c713ce2,0xbca2bcc6,0x3cc63ca2,0xbce2bc71,0x3cf53c15,0xbcffbb49,0xbcff3b49,0x3cf5bc15,0xbce23c71,0x3cc6bca2,0xbca23cc6,0x3c71bce2,0xbc153cf5,0x3b49bcff,
 0x3cf13c2c,0xbcf8bbf9,0x3cfd3b96,0xbd00bac9,0x3cbe3cac,0xbccebc98,0x3cdc3c84,0xbce7bc5b,0x3c5b3ce7,0xbc84bcdc,0x3c983cce,0xbcacbcbe,0x3ac93d00,0xbb96bcfd,0x3bf93cf8,0xbc2cbcf1,
 0xbc2c3cf1,0x3bf9bcf8,0xbb963cfd,0x3ac9bd00,0xbcac3cbe,0x3c98bcce,0xbc843cdc,0x3c5bbce7,0xbce73c5b,0x3cdcbc84,0xbcce3c98,0x3cbebcac,0xbd003ac9,0x3cfdbb96,0xbcf83bf9,0x3cf1bc2c,
 0xbd000000,0x3d000000,0xbd000000,0x3d000000,0xbd000000,0x3d000000,0xbd000000,0x3d000000,0xbd000000,0x3d000000,0xbd000000,0x3d000000,0xbd000000,0x3d000000,0xbd000000,0x3d000000,
 0xbd000000,0x3d000000,0xbd000000,0x3d000000,0xbd000000,0x3d000000,0xbd000000,0x3d000000,0xbd000000,0x3d000000,0xbd000000,0x3d000000,0xbd000000,0x3d000000,0xbd000000,0x3d000000,
 0xbce7bc5b,0x3cdc3c84,0xbccebc98,0x3cbe3cac,0xbd00bac9,0x3cfd3b96,0xbcf8bbf9,0x3cf13c2c,0xbc2cbcf1,0x3bf93cf8,0xbb96bcfd,0x3ac93d00,0xbcacbcbe,0x3c983cce,0xbc84bcdc,0x3c5b3ce7,
 0x3c5bbce7,0xbc843cdc,0x3c98bcce,0xbcac3cbe,0x3ac9bd00,0xbb963cfd,0x3bf9bcf8,0xbc2c3cf1,0x3cf1bc2c,0xbcf83bf9,0x3cfdbb96,0xbd003ac9,0x3cbebcac,0xbcce3c98,0x3cdcbc84,0xbce73c5b,
 0x3b49bcff,0xbc153cf5,0x3c71bce2,0xbca23cc6,0x3cc6bca2,0xbce23c71,0x3cf5bc15,0xbcff3b49,0xbcffbb49,0x3cf53c15,0xbce2bc71,0x3cc63ca2,0xbca2bcc6,0x3c713ce2,0xbc15bcf5,0x3b493cff,
 0xbb493cff,0x3c15bcf5,0xbc713ce2,0x3ca2bcc6,0xbcc63ca2,0x3ce2bc71,0xbcf53c15,0x3cffbb49,0x3cff3b49,0xbcf5bc15,0x3ce23c71,0xbcc6bca2,0x3ca23cc6,0xbc71bce2,0x3c153cf5,0xbb49bcff,
 0x3cdc3c84,0xbcacbcbe,0x3c5b3ce7,0xbb96bcfd,0x3ccebc98,0xbcf13c2c,0x3d00bac9,0xbcf8bbf9,0xbbf9bcf8,0xbac93d00,0x3c2cbcf1,0xbc983cce,0xbcfdbb96,0x3ce73c5b,0xbcbebcac,0x3c843cdc,
 0x3c84bcdc,0xbcbe3cac,0x3ce7bc5b,0xbcfd3b96,0xbc98bcce,0x3c2c3cf1,0xbac9bd00,0xbbf93cf8,0xbcf83bf9,0x3d003ac9,0xbcf1bc2c,0x3cce3c98,0xbb963cfd,0x3c5bbce7,0xbcac3cbe,0x3cdcbc84,
 0xbcfbbbc8,0x3cd53c8e,0xbc8ebcd5,0x3bc83cfb,0x3bc8bcfb,0xbc8e3cd5,0x3cd5bc8e,0xbcfb3bc8,0x3cfb3bc8,0xbcd5bc8e,0x3c8e3cd5,0xbbc8bcfb,0xbbc83cfb,0x3c8ebcd5,0xbcd53c8e,0x3cfbbbc8,
 0xbcfbbbc8,0x3cd53c8e,0xbc8ebcd5,0x3bc83cfb,0x3bc8bcfb,0xbc8e3cd5,0x3cd5bc8e,0xbcfb3bc8,0x3cfb3bc8,0xbcd5bc8e,0x3c8e3cd5,0xbbc8bcfb,0xbbc83cfb,0x3c8ebcd5,0xbcd53c8e,0x3cfbbbc8,
 0x3cce3c98,0xbc5bbce7,0xbac93d00,0x3c84bcdc,0x3bf9bcf8,0xbcac3cbe,0x3cf1bc2c,0xbcfdbb96,0xbb96bcfd,0xbc2c3cf1,0x3cbebcac,0xbcf83bf9,0xbcdc3c84,0x3d00bac9,0xbce7bc5b,0x3c983cce,
 0x3c98bcce,0xbce73c5b,0x3d003ac9,0xbcdcbc84,0xbcf8bbf9,0x3cbe3cac,0xbc2cbcf1,0xbb963cfd,0xbcfd3b96,0x3cf13c2c,0xbcacbcbe,0x3bf93cf8,0x3c843cdc,0xbac9bd00,0xbc5b3ce7,0x3ccebc98,
 0x3c15bcf5,0xbcc63ca2,0x3cffbb49,0xbce2bc71,0x3c713ce2,0x3b49bcff,0xbca23cc6,0x3cf5bc15,0x3cf53c15,0xbca2bcc6,0x3b493cff,0x3c71bce2,0xbce23c71,0x3cff3b49,0xbcc6bca2,0x3c153cf5,
 0xbc153cf5,0x3cc6bca2,0xbcff3b49,0x3ce23c71,0xbc71bce2,0xbb493cff,0x3ca2bcc6,0xbcf53c15,0xbcf5bc15,0x3ca23cc6,0xbb49bcff,0xbc713ce2,0x3ce2bc71,0xbcffbb49,0x3cc63ca2,0xbc15bcf5,
 0xbcbebcac,0x3b963cfd,0x3c84bcdc,0xbcf13c2c,0x3c5b3ce7,0x3bf9bcf8,0xbcce3c98,0x3d003ac9,0xbac9bd00,0xbc983cce,0x3cf8bbf9,0xbce7bc5b,0xbc2c3cf1,0x3cdcbc84,0xbcfdbb96,0x3cac3cbe,
 0x3cacbcbe,0xbcfd3b96,0x3cdc3c84,0xbc2cbcf1,0xbce73c5b,0x3cf83bf9,0xbc98bcce,0xbac93d00,0x3d00bac9,0xbccebc98,0x3bf93cf8,0x3c5bbce7,0xbcf1bc2c,0x3c843cdc,0x3b96bcfd,0xbcbe3cac,
 0xbcedbc44,0x3c443ced,0x3c44bced,0xbced3c44,0x3ced3c44,0xbc44bced,0xbc443ced,0x3cedbc44,0xbcedbc44,0x3c443ced,0x3c44bced,0xbced3c44,0x3ced3c44,0xbc44bced,0xbc443ced,0x3cedbc44,
 0xbcedbc44,0x3c443ced,0x3c44bced,0xbced3c44,0x3ced3c44,0xbc44bced,0xbc443ced,0x3cedbc44,0xbcedbc44,0x3c443ced,0x3c44bced,0xbced3c44,0x3ced3c44,0xbc44bced,0xbc443ced,0x3cedbc44,
 0x3cac3cbe,0x3b96bcfd,0xbcdc3c84,0x3cf13c2c,0xbce7bc5b,0x3bf93cf8,0x3c98bcce,0xbd003ac9,0xbac93d00,0x3ccebc98,0xbcf8bbf9,0x3c5b3ce7,0xbc2cbcf1,0xbc843cdc,0x3cfdbb96,0xbcbebcac,
 0xbcbe3cac,0x3cfd3b96,0xbc84bcdc,0xbc2c3cf1,0x3c5bbce7,0xbcf83bf9,0x3cce3c98,0xbac9bd00,0xbd00bac9,0x3c983cce,0x3bf9bcf8,0xbce73c5b,0x3cf1bc2c,0xbcdcbc84,0x3b963cfd,0x3cacbcbe,
 0x3c71bce2,0xbcff3b49,0x3ca23cc6,0x3c15bcf5,0xbcf53c15,0x3cc63ca2,0x3b49bcff,0xbce23c71,0xbce2bc71,0x3b493cff,0x3cc6bca2,0xbcf5bc15,0x3c153cf5,0x3ca2bcc6,0xbcffbb49,0x3c713ce2,
 0xbc713ce2,0x3cffbb49,0xbca2bcc6,0xbc153cf5,0x3cf5bc15,0xbcc6bca2,0xbb493cff,0x3ce2bc71,0x3ce23c71,0xbb49bcff,0xbcc63ca2,0x3cf53c15,0xbc15bcf5,0xbca23cc6,0x3cff3b49,0xbc71bce2,
 0xbc98bcce,0xbc5b3ce7,0x3d00bac9,0xbc84bcdc,0x3cf8bbf9,0xbcacbcbe,0xbc2c3cf1,0x3cfdbb96,0xbb963cfd,0x3cf1bc2c,0xbcbebcac,0xbbf93cf8,0xbcdcbc84,0xbac93d00,0x3ce7bc5b,0xbccebc98,
 0xbcce3c98,0x3ce73c5b,0xbac9bd00,0xbcdc3c84,0xbbf9bcf8,0xbcbe3cac,0x3cf13c2c,0xbb96bcfd,0x3cfd3b96,0xbc2cbcf1,0xbcac3cbe,0x3cf83bf9,0xbc843cdc,0x3d003ac9,0xbc5bbce7,0xbc983cce,
 0xbcd5bc8e,0xbbc83cfb,0x3cfbbbc8,0xbc8ebcd5,0xbc8e3cd5,0x3cfb3bc8,0xbbc8bcfb,0xbcd53c8e,0x3cd53c8e,0x3bc8bcfb,0xbcfb3bc8,0x3c8e3cd5,0x3c8ebcd5,0xbcfbbbc8,0x3bc83cfb,0x3cd5bc8e,
 0xbcd5bc8e,0xbbc83cfb,0x3cfbbbc8,0xbc8ebcd5,0xbc8e3cd5,0x3cfb3bc8,0xbbc8bcfb,0xbcd53c8e,0x3cd53c8e,0x3bc8bcfb,0xbcfb3bc8,0x3c8e3cd5,0x3c8ebcd5,0xbcfbbbc8,0x3bc83cfb,0x3cd5bc8e,
 0xbc84bcdc,0xbcac3cbe,0x3ce73c5b,0x3b96bcfd,0x3c98bcce,0xbcf1bc2c,0xbac93d00,0x3cf8bbf9,0xbbf93cf8,0x3d00bac9,0xbc2cbcf1,0xbcce3c98,0xbcfd3b96,0x3c5b3ce7,0x3cbebcac,0xbcdcbc84,
 0xbcdc3c84,0x3cbe3cac,0x3c5bbce7,0xbcfdbb96,0xbccebc98,0xbc2c3cf1,0x3d003ac9,0xbbf9bcf8,0x3cf83bf9,0xbac9bd00,0xbcf13c2c,0x3c983cce,0x3b963cfd,0x3ce7bc5b,0xbcacbcbe,0xbc843cdc,
 0x3ca2bcc6,0xbce2bc71,0xbc153cf5,0x3cff3b49,0xbb49bcff,0xbcf53c15,0x3c713ce2,0x3cc6bca2,0x3cc63ca2,0x3c71bce2,0xbcf5bc15,0xbb493cff,0x3cffbb49,0xbc15bcf5,0xbce23c71,0x3ca23cc6,
 0xbca23cc6,0x3ce23c71,0x3c15bcf5,0xbcffbb49,0x3b493cff,0x3cf5bc15,0xbc71bce2,0xbcc63ca2,0xbcc6bca2,0xbc713ce2,0x3cf53c15,0x3b49bcff,0xbcff3b49,0x3c153cf5,0x3ce2bc71,0xbca2bcc6,
 0x3c5b3ce7,0x3cdcbc84,0xbc98bcce,0xbcbe3cac,0x3ac93d00,0x3cfdbb96,0xbbf9bcf8,0xbcf13c2c,0xbc2c3cf1,0x3cf83bf9,0x3b96bcfd,0xbd00bac9,0xbcac3cbe,0x3cce3c98,0x3c84bcdc,0xbce7bc5b,
 0xbce73c5b,0x3c843cdc,0x3ccebc98,0xbcacbcbe,0xbd003ac9,0x3b963cfd,0x3cf8bbf9,0xbc2cbcf1,0xbcf1bc2c,0xbbf93cf8,0x3cfd3b96,0x3ac9bd00,0xbcbebcac,0xbc983cce,0x3cdc3c84,0x3c5bbce7,
 0xbcb5bcb5,0xbcb53cb5,0x3cb53cb5,0x3cb5bcb5,0xbcb5bcb5,0xbcb53cb5,0x3cb53cb5,0x3cb5bcb5,0xbcb5bcb5,0xbcb53cb5,0x3cb53cb5,0x3cb5bcb5,0xbcb5bcb5,0xbcb53cb5,0x3cb53cb5,0x3cb5bcb5,
 0xbcb5bcb5,0xbcb53cb5,0x3cb53cb5,0x3cb5bcb5,0xbcb5bcb5,0xbcb53cb5,0x3cb53cb5,0x3cb5bcb5,0xbcb5bcb5,0xbcb53cb5,0x3cb53cb5,0x3cb5bcb5,0xbcb5bcb5,0xbcb53cb5,0x3cb53cb5,0x3cb5bcb5,
 0xbc2cbcf1,0xbcf83bf9,0x3b963cfd,0x3d00bac9,0xbcacbcbe,0xbcce3c98,0x3c843cdc,0x3ce7bc5b,0x3c5bbce7,0xbcdcbc84,0xbc983cce,0x3cbe3cac,0x3ac9bd00,0xbcfdbb96,0xbbf93cf8,0x3cf13c2c,
 0x3cf1bc2c,0xbbf9bcf8,0xbcfd3b96,0x3ac93d00,0x3cbebcac,0xbc98bcce,0xbcdc3c84,0x3c5b3ce7,0x3ce73c5b,0x3c84bcdc,0xbccebc98,0xbcac3cbe,0x3d003ac9,0x3b96bcfd,0xbcf8bbf9,0xbc2c3cf1,
 0x00000000,0x00000000,0x00000000,0x00000000,0x00000000,0x00000000,0x00000000,0x00000000,0x00000000,0x00000000,0x00000000,0x00000000,0x00000000,0x00000000,0x00000000,0x00000000,
 0x00000000,0x00000000,0x00000000,0x00000000,0x00000000,0x00000000,0x00000000,0x00000000,0x00000000,0x00000000,0x00000000,0x00000000,0x00000000,0x00000000,0x00000000,0x00000000,
 0x00000000,0x00000000,0x00000000,0x00000000,0x00000000,0x00000000,0x00000000,0x00000000,0x00000000,0x00000000,0x00000000,0x00000000,0x00000000,0x00000000,0x00000000,0x00000000,
 0x00000000,0x00000000,0x00000000,0x00000000,0x00000000,0x00000000,0x00000000,0x00000000,0x00000000,0x00000000,0x00000000,0x00000000,0x00000000,0x00000000,0x00000000,0x00000000,
 0x00000000,0x00000000,0x00000000,0x00000000,0x00000000,0x00000000,0x00000000,0x00000000,0x00000000,0x00000000,0x00000000,0x00000000,0x00000000,0x00000000,0x00000000,0x00000000,
 0x00000000,0x00000000,0x00000000,0x00000000,0x00000000,0x00000000,0x00000000,0x00000000,0x00000000,0x00000000,0x00000000,0x00000000,0x00000000,0x00000000,0x00000000,0x00000000,
 0x00000000,0x00000000,0x00000000,0x00000000,0x00000000,0x00000000,0x00000000,0x00000000,0x00000000,0x00000000,0x00000000,0x00000000,0x00000000,0x00000000,0x00000000,0x00000000,
 0x00000000,0x00000000,0x00000000,0x00000000,0x00000000,0x00000000,0x00000000,0x00000000,0x00000000,0x00000000,0x00000000,0x00000000,0x00000000,0x00000000,0x00000000,0x00000000,
 0x00000000,0x00000000,0x00000000,0x00000000,0x00000000,0x00000000,0x00000000,0x00000000,0x00000000,0x00000000,0x00000000,0x00000000,0x00000000,0x00000000,0x00000000,0x00000000,
 0x00000000,0x00000000,0x00000000,0x00000000,0x00000000,0x00000000,0x00000000,0x00000000,0x00000000,0x00000000,0x00000000,0x00000000,0x00000000,0x00000000,0x00000000,0x00000000,
 0x00000000,0x00000000,0x00000000,0x00000000,0x00000000,0x00000000,0x00000000,0x00000000,0x00000000,0x00000000,0x00000000,0x00000000,0x00000000,0x00000000,0x00000000,0x00000000,
 0x00000000,0x00000000,0x00000000,0x00000000,0x00000000,0x00000000,0x00000000,0x00000000,0x00000000,0x00000000,0x00000000,0x00000000,0x00000000,0x00000000,0x00000000,0x00000000,
};

template<int SA>
__device__ __forceinline__ void wgmma_main(float (&d)[80], uint64_t da, uint64_t db, int sd) {
  asm volatile("{\n.reg .pred p;\nsetp.ne.b32 p, %82, 0;\n"
    "wgmma.mma_async.sync.aligned.m64n160k16.f32.bf16.bf16 "
    "{%0, %1, %2, %3, %4, %5, %6, %7, %8, %9, %10, %11, %12, %13, %14, %15, %16, %17, %18, %19, %20, %21, %22, %23, %24, %25, %26, %27, %28, %29, %30, %31, %32, %33, %34, %35, %36, %37, %38, %39, %40, %41, %42, %43, %44, %45, %46, %47, %48, %49, %50, %51, %52, %53, %54, %55, %56, %57, %58, %59, %60, %61, %62, %63, %64, %65, %66, %67, %68, %69, %70, %71, %72, %73, %74, %75, %76, %77, %78, %79}, %80, %81, p, %83, 1, 1, 0;\n}\n"
    : "+f"(d[0]), "+f"(d[1]), "+f"(d[2]), "+f"(d[3]), "+f"(d[4]), "+f"(d[5]), "+f"(d[6]), "+f"(d[7]), "+f"(d[8]), "+f"(d[9]), "+f"(d[10]), "+f"(d[11]), "+f"(d[12]), "+f"(d[13]), "+f"(d[14]), "+f"(d[15]), "+f"(d[16]), "+f"(d[17]), "+f"(d[18]), "+f"(d[19]), "+f"(d[20]), "+f"(d[21]), "+f"(d[22]), "+f"(d[23]), "+f"(d[24]), "+f"(d[25]), "+f"(d[26]), "+f"(d[27]), "+f"(d[28]), "+f"(d[29]), "+f"(d[30]), "+f"(d[31]), "+f"(d[32]), "+f"(d[33]), "+f"(d[34]), "+f"(d[35]), "+f"(d[36]), "+f"(d[37]), "+f"(d[38]), "+f"(d[39]), "+f"(d[40]), "+f"(d[41]), "+f"(d[42]), "+f"(d[43]), "+f"(d[44]), "+f"(d[45]), "+f"(d[46]), "+f"(d[47]), "+f"(d[48]), "+f"(d[49]), "+f"(d[50]), "+f"(d[51]), "+f"(d[52]), "+f"(d[53]), "+f"(d[54]), "+f"(d[55]), "+f"(d[56]), "+f"(d[57]), "+f"(d[58]), "+f"(d[59]), "+f"(d[60]), "+f"(d[61]), "+f"(d[62]), "+f"(d[63]), "+f"(d[64]), "+f"(d[65]), "+f"(d[66]), "+f"(d[67]), "+f"(d[68]), "+f"(d[69]), "+f"(d[70]), "+f"(d[71]), "+f"(d[72]), "+f"(d[73]), "+f"(d[74]), "+f"(d[75]), "+f"(d[76]), "+f"(d[77]), "+f"(d[78]), "+f"(d[79])
    : "l"(da), "l"(db), "r"(sd), "n"(SA));
}
template<int SA>
__device__ __forceinline__ void wgmma_fwd(float (&d)[32], uint64_t da, uint64_t db, int sd) {
  asm volatile("{\n.reg .pred p;\nsetp.ne.b32 p, %34, 0;\n"
    "wgmma.mma_async.sync.aligned.m64n64k16.f32.bf16.bf16 "
    "{%0, %1, %2, %3, %4, %5, %6, %7, %8, %9, %10, %11, %12, %13, %14, %15, %16, %17, %18, %19, %20, %21, %22, %23, %24, %25, %26, %27, %28, %29, %30, %31}, %32, %33, p, %35, 1, 0, 1;\n}\n"
    : "+f"(d[0]), "+f"(d[1]), "+f"(d[2]), "+f"(d[3]), "+f"(d[4]), "+f"(d[5]), "+f"(d[6]), "+f"(d[7]), "+f"(d[8]), "+f"(d[9]), "+f"(d[10]), "+f"(d[11]), "+f"(d[12]), "+f"(d[13]), "+f"(d[14]), "+f"(d[15]), "+f"(d[16]), "+f"(d[17]), "+f"(d[18]), "+f"(d[19]), "+f"(d[20]), "+f"(d[21]), "+f"(d[22]), "+f"(d[23]), "+f"(d[24]), "+f"(d[25]), "+f"(d[26]), "+f"(d[27]), "+f"(d[28]), "+f"(d[29]), "+f"(d[30]), "+f"(d[31])
    : "l"(da), "l"(db), "r"(sd), "n"(SA));
}
template<int SA>
__device__ __forceinline__ void wgmma_inv(float (&d)[28], uint64_t da, uint64_t db, int sd) {
  asm volatile("{\n.reg .pred p;\nsetp.ne.b32 p, %30, 0;\n"
    "wgmma.mma_async.sync.aligned.m64n56k16.f32.bf16.bf16 "
    "{%0, %1, %2, %3, %4, %5, %6, %7, %8, %9, %10, %11, %12, %13, %14, %15, %16, %17, %18, %19, %20, %21, %22, %23, %24, %25, %26, %27}, %28, %29, p, %31, 1, 1, 0;\n}\n"
    : "+f"(d[0]), "+f"(d[1]), "+f"(d[2]), "+f"(d[3]), "+f"(d[4]), "+f"(d[5]), "+f"(d[6]), "+f"(d[7]), "+f"(d[8]), "+f"(d[9]), "+f"(d[10]), "+f"(d[11]), "+f"(d[12]), "+f"(d[13]), "+f"(d[14]), "+f"(d[15]), "+f"(d[16]), "+f"(d[17]), "+f"(d[18]), "+f"(d[19]), "+f"(d[20]), "+f"(d[21]), "+f"(d[22]), "+f"(d[23]), "+f"(d[24]), "+f"(d[25]), "+f"(d[26]), "+f"(d[27])
    : "l"(da), "l"(db), "r"(sd), "n"(SA));
}

__device__ __forceinline__ uint32_t s2u(const void* p) { return (uint32_t)__cvta_generic_to_shared(p); }
__device__ __forceinline__ void mbar_init(uint32_t a, int c) { asm volatile("mbarrier.init.shared::cta.b64 [%0], %1;" ::"r"(a), "r"(c)); }
__device__ __forceinline__ void mbar_expect(uint32_t a, int b) { asm volatile("mbarrier.arrive.expect_tx.shared::cta.b64 _, [%0], %1;" ::"r"(a), "r"(b) : "memory"); }
__device__ __forceinline__ void mbar_arrive(uint32_t a) { asm volatile("mbarrier.arrive.shared::cta.b64 _, [%0];" ::"r"(a) : "memory"); }
__device__ __forceinline__ void mbar_arrive_cluster(uint32_t a, uint32_t cta, uint32_t cnt) {
  asm volatile("{\n.reg .b32 r;\nmapa.shared::cluster.u32 r, %0, %1;\nmbarrier.arrive.shared::cluster.b64 _, [r], %2;\n}" ::"r"(a), "r"(cta), "r"(cnt) : "memory");
}
__device__ __forceinline__ void mbar_wait(uint32_t a, int ph) {
  asm volatile("{\n.reg .pred p;\n.reg .u32 c;\nmov.u32 c, 0;\nWAIT:\n"
               "mbarrier.try_wait.parity.shared::cta.b64 p, [%0], %1;\n@p bra DONE;\n"
               "add.u32 c, c, 1;\nsetp.lt.u32 p, c, 0x400000;\n@p bra WAIT;\ntrap;\nDONE:\n}" ::"r"(a), "r"(ph) : "memory");
}
__device__ __forceinline__ void flag_wait(const unsigned* p, unsigned target) {
  asm volatile("{\n.reg .pred p;\n.reg .u32 c, v;\nmov.u32 c, 0;\nWAIT:\n"
               "ld.acquire.gpu.global.u32 v, [%0];\nsetp.ge.u32 p, v, %1;\n@p bra DONE;\n"
               "add.u32 c, c, 1;\nsetp.lt.u32 p, c, 0x400000;\n@p bra WAIT;\ntrap;\nDONE:\n}" ::"l"(p), "r"(target) : "memory");
}
__device__ __forceinline__ bool elect_one() {
  uint32_t p;
  asm volatile("{\n.reg .pred P;\nelect.sync _|P, 0xffffffff;\nselp.u32 %0, 1, 0, P;\n}" : "=r"(p));
  return p != 0;
}
__device__ __forceinline__ void bulk_ld(uint32_t dst, const void* src, int bytes, uint32_t bar) {
  asm volatile("cp.async.bulk.shared::cluster.global.mbarrier::complete_tx::bytes [%0], [%1], %2, [%3];" ::"r"(dst), "l"(src), "r"(bytes), "r"(bar) : "memory");
}
__device__ __forceinline__ void bulk_ld_mc_h(uint32_t dst, const void* src, int bytes, uint32_t bar, uint16_t mask, uint64_t pol) {
  asm volatile("cp.async.bulk.shared::cluster.global.mbarrier::complete_tx::bytes.multicast::cluster.L2::cache_hint [%0], [%1], %2, [%3], %4, %5;" ::"r"(dst), "l"(src), "r"(bytes), "r"(bar), "h"(mask), "l"(pol) : "memory");
}
__device__ __forceinline__ uint64_t policy_evict_normal() {
  uint64_t p;
  asm("createpolicy.fractional.L2::evict_normal.b64 %0, 1.0;" : "=l"(p));
  return p;
}
__device__ __forceinline__ void tma_ld2(uint32_t dst, const CUtensorMap* tm, int c0, int c1, uint32_t bar) {
  asm volatile("cp.async.bulk.tensor.2d.shared::cluster.global.mbarrier::complete_tx::bytes [%0], [%1, {%3,%4}], [%2];" ::"r"(dst), "l"(tm), "r"(bar), "r"(c0), "r"(c1) : "memory");
}
__device__ __forceinline__ void tma_ld3(uint32_t dst, const CUtensorMap* tm, int c0, int c1, int c2, uint32_t bar) {
  asm volatile("cp.async.bulk.tensor.3d.shared::cluster.global.mbarrier::complete_tx::bytes [%0], [%1, {%3,%4,%5}], [%2];" ::"r"(dst), "l"(tm), "r"(bar), "r"(c0), "r"(c1), "r"(c2) : "memory");
}
__device__ __forceinline__ void tma_ld3h(uint32_t dst, const CUtensorMap* tm, int c0, int c1, int c2, uint32_t bar, uint64_t pol) {
  asm volatile("cp.async.bulk.tensor.3d.shared::cluster.global.mbarrier::complete_tx::bytes.L2::cache_hint [%0], [%1, {%3,%4,%5}], [%2], %6;" ::"r"(dst), "l"(tm), "r"(bar), "r"(c0), "r"(c1), "r"(c2), "l"(pol) : "memory");
}
__device__ __forceinline__ uint64_t policy_evict_first() {
  uint64_t p;
  asm("createpolicy.fractional.L2::evict_first.b64 %0, 1.0;" : "=l"(p));
  return p;
}
__device__ __forceinline__ void tma_st3(const CUtensorMap* tm, uint32_t src, int c0, int c1, int c2) {
  asm volatile("cp.async.bulk.tensor.3d.global.shared::cta.bulk_group [%0, {%2,%3,%4}], [%1];" ::"l"(tm), "r"(src), "r"(c0), "r"(c1), "r"(c2) : "memory");
}
__device__ __forceinline__ void tma_st4(const CUtensorMap* tm, uint32_t src, int c0, int c1, int c2, int c3) {
  asm volatile("cp.async.bulk.tensor.4d.global.shared::cta.bulk_group [%0, {%2,%3,%4,%5}], [%1];" ::"l"(tm), "r"(src), "r"(c0), "r"(c1), "r"(c2), "r"(c3) : "memory");
}
__device__ __forceinline__ void tma_st5(const CUtensorMap* tm, uint32_t src, int c0) {
  asm volatile("cp.async.bulk.tensor.5d.global.shared::cta.bulk_group [%0, {%2,%3,%3,%3,%3}], [%1];" ::"l"(tm), "r"(src), "r"(c0), "r"(0) : "memory");
}
__device__ __forceinline__ void bulk_commit() { asm volatile("cp.async.bulk.commit_group;" ::: "memory"); }
template <int N> __device__ __forceinline__ void bulk_wait_read() { asm volatile("cp.async.bulk.wait_group.read %0;" ::"n"(N) : "memory"); }
__device__ __forceinline__ void bulk_wait_all() { asm volatile("cp.async.bulk.wait_group 0;" ::: "memory"); }
__device__ __forceinline__ void fence_async_smem() { asm volatile("fence.proxy.async.shared::cta;" ::: "memory"); }
__device__ __forceinline__ void wg_fence() { asm volatile("wgmma.fence.sync.aligned;" ::: "memory"); }
__device__ __forceinline__ void wg_commit() { asm volatile("wgmma.commit_group.sync.aligned;" ::: "memory"); }
template <int N> __device__ __forceinline__ void wg_wait() { asm volatile("wgmma.wait_group.sync.aligned %0;" ::"n"(N) : "memory"); }
template <int R> __device__ __forceinline__ void fence_regs(float (&d)[R]) {
#pragma unroll
  for (int i = 0; i < R; i++) asm volatile("" : "+f"(d[i])::"memory");
}
__device__ __forceinline__ uint64_t mk_desc(uint32_t addr) {
  return (uint64_t)((addr & 0x3FFFF) >> 4) | (1ull << 16) | (64ull << 32) | (1ull << 62);
}
__device__ __forceinline__ uint32_t pack2(float lo, float hi) {
  uint32_t r;
  asm("cvt.rn.bf16x2.f32 %0, %1, %2;" : "=r"(r) : "f"(hi), "f"(lo));
  return r;
}
__device__ __forceinline__ void stsm4(uint32_t ad, uint32_t a, uint32_t b, uint32_t c, uint32_t d) {
  asm volatile("stmatrix.sync.aligned.m8n8.x4.shared.b16 [%0], {%1,%2,%3,%4};" ::"r"(ad), "r"(a), "r"(b), "r"(c), "r"(d) : "memory");
}
__device__ __forceinline__ void stsm4t(uint32_t ad, uint32_t a, uint32_t b, uint32_t c, uint32_t d) {
  asm volatile("stmatrix.sync.aligned.m8n8.x4.trans.shared.b16 [%0], {%1,%2,%3,%4};" ::"r"(ad), "r"(a), "r"(b), "r"(c), "r"(d) : "memory");
}

__device__ __forceinline__ void stsm2t(uint32_t ad, uint32_t a, uint32_t b) {
  asm volatile("stmatrix.sync.aligned.m8n8.x2.trans.shared.b16 [%0], {%1,%2};" ::"r"(ad), "r"(a), "r"(b) : "memory");
}
__device__ __forceinline__ void red_add(unsigned* p) { asm volatile("red.relaxed.gpu.global.add.u32 [%0], 1;" ::"l"(p) : "memory"); }
__device__ __forceinline__ void fence_release() { asm volatile("fence.release.gpu;" ::: "memory"); }
__device__ __forceinline__ void fence_async_global() { asm volatile("fence.proxy.async.global;" ::: "memory"); }

__device__ __forceinline__ bool mbar_test(uint32_t a, int ph) {
  uint32_t ok;
  asm volatile("{\n.reg .pred p;\nmbarrier.test_wait.parity.shared::cta.b64 p, [%1], %2;\nselp.u32 %0, 1, 0, p;\n}" : "=r"(ok) : "r"(a), "r"(ph) : "memory");
  return ok != 0;
}
__device__ __forceinline__ void poll64x4(const unsigned long long* p, unsigned long long (&v)[4]) {
  asm volatile("{\n.reg .pred p;\n.reg .u32 c;\n.reg .b64 t, u;\nmov.u32 c, 0;\nWAIT:\n"
               "ld.relaxed.gpu.global.u64 %0, [%4];\nld.relaxed.gpu.global.u64 %1, [%4+512];\n"
               "ld.relaxed.gpu.global.u64 %2, [%4+1024];\nld.relaxed.gpu.global.u64 %3, [%4+1536];\n"
               "or.b64 t, %0, %1;\nor.b64 u, %2, %3;\nor.b64 t, t, u;\nsetp.ge.s64 p, t, 0;\n@p bra DONE;\n"
               "add.u32 c, c, 1;\nsetp.lt.u32 p, c, 0x400000;\n@p bra WAIT;\ntrap;\nDONE:\n}"
               : "=l"(v[0]), "=l"(v[1]), "=l"(v[2]), "=l"(v[3]) : "l"(p) : "memory");
}

constexpr int G_STAGE = WBLK + XBLK;
constexpr int OFF_XR = 4 * G_STAGE;
constexpr int OFF_WS = OFF_XR + 6 * 8192;
constexpr int OFF_F = OFF_WS + 2 * 8192;
constexpr int OFF_WRAW = OFF_F + 8192;
constexpr int OFF_BAR = OFF_WRAW + 8192;
constexpr int OFF_GB = OFF_BAR + 1024;
constexpr int SMEM_BYTES = OFF_GB + 512;
constexpr int OFF_Y0 = 3 * G_STAGE + 4096;
constexpr int OFF_H0 = OFF_F - 10 * 8192;
constexpr int OFF_E = OFF_WRAW + 3072;
constexpr int B_FULL = 0, B_RAWX = 32, B_F = 80, B_ROLE = 88, B_H0 = 104, B_H1 = 112,
              B_EMPTY = 136, B_STGX = 168, B_STGW = 216, B_Y = 232, B_RET = 248, B_OUT = 256,
              B_RAWW = 336, B_DONE = 368, B_END = 632, S_ROLE = 640, S_PROBE = 656;

struct Maps { CUtensorMap x, we, wo, xst[2], wst, yst, yld, out, xe[2], w30; };

__device__ __forceinline__ int chunk_of(int n) { return n < 16 ? n : 31 - n; }
__device__ __forceinline__ bool has_x2(int id, int n, int g) { return (((id >> 5) ^ n) & 1) == 0 && ((n >> 1) & 1) == g; }
__device__ __forceinline__ uint32_t x_base(int s, int idx, uint32_t pgmask, int& par) {
  const int page = idx >> 3, o = idx & 7;
  par = (s ^ (pgmask >> page) ^ __popc(o)) & 1;
  return (page << 21) | ((o & 3) << 16) | ((o >> 2) << 19);
}
__device__ __forceinline__ int next_slot(int s, int v) {
  return s == 3 ? 0 : (s == 2 && ((v >= 32 && v < 38) || v >= 62)) ? 0 : s + 1;
}
__device__ __forceinline__ uint32_t read_info(uint32_t bar, int i) {
  uint32_t v;
  mbar_wait(bar + B_ROLE + 8 * i, 0);
  asm volatile("ld.shared.b32 %0, [%1];" : "=r"(v) : "r"(bar + S_ROLE + 4 * i) : "memory");
  return v;
}
__device__ __forceinline__ void send_info(uint32_t bar, int i, uint32_t v) {
#pragma unroll
  for (int r = 0; r < 2; r++)
    asm volatile("{\n.reg .b32 a, m;\nmapa.shared::cluster.u32 a, %0, %2;\nmapa.shared::cluster.u32 m, %1, %2;\n"
                 "st.async.weak.shared::cluster.mbarrier::complete_tx::bytes.b32 [a], %3, [m];\n}"
                 ::"r"(bar + S_ROLE + 4 * i), "r"(bar + B_ROLE + 8 * i), "r"(r), "r"(v) : "memory");
}
__device__ __forceinline__ unsigned probe(uint8_t* p, int lane, int pb) {
  if (lane < 2) *(uint4*)(p + lane * 16) = make_uint4(0, 0, 0, 0);
  __syncwarp();
  unsigned v = 0, best = ~0u;
  if (lane == 0) {
#pragma unroll 1
    for (int r = 0; r < 2; r++) {
      unsigned t0, t1;
      asm volatile("mov.u32 %0, %%clock;" : "=r"(t0) : "r"(v) : "memory");
      asm volatile("atom.relaxed.gpu.global.exch.b32 %0, [%1], 0;" : "=r"(v) : "l"(p) : "memory");
      asm volatile("{\n.reg .pred p;\nsetp.ne.u32 p, %1, 0xffffffff;\nmov.u32 %0, 0;\n@p mov.u32 %0, %%clock;\n}" : "=r"(t1) : "r"(v) : "memory");
      best = min(best, t1 - t0);
      if (r < 3) PROF_V(pb + r, t1 - t0);
    }
  }
  return best;
}

template <bool ISX>
__device__ __forceinline__ void t_issue(float (&t)[32], uint32_t sb, uint32_t raw) {
  const uint64_t da = mk_desc(sb + OFF_F), db = mk_desc(raw);
  wg_fence();
#pragma unroll
  for (int kk = 0; kk < (ISX ? 4 : 1); kk++) wgmma_fwd<1>(t, da + 2 * kk, db + 128 * kk, kk);
  wg_commit();
}
template <bool ISX>
__device__ __forceinline__ void t_finish(float (&t)[32], uint32_t dst, uint32_t sbar, int sw, int wg, int w, int lane) {
  fence_regs(t);
  if (ISX) asm volatile("bar.sync %0, 128;" ::"r"(1 + wg) : "memory");
  const int m = lane >> 3, r = lane & 7;
  uint32_t ad = dst + (8 * w + r) * 128;
  if (ISX) ad += ((((m & 1) * 4 + (m >> 1)) ^ sw ^ r) << 4);
  else ad += (m & 1) * 4096 + (((m >> 1) ^ sw ^ r) << 4);
#pragma unroll
  for (int i = 0; i < 4; i++) {
    const uint32_t a = ISX ? ((ad ^ ((i & 1) * 32)) + (i >> 1) * 4096) : (ad ^ (i * 32));
    stsm4(a, pack2(t[8 * i], t[8 * i + 1]), pack2(t[8 * i + 2], t[8 * i + 3]), pack2(t[8 * i + 4], t[8 * i + 5]), pack2(t[8 * i + 6], t[8 * i + 7]));
  }
  fence_async_smem();
  __syncwarp();
  if (lane == 0) mbar_arrive(sbar);
}
template <int NT, int K0, int K1>
__device__ __forceinline__ void batch(float (&yr)[80], float (&yi)[80], float (&t)[32], uint32_t st, int wg, int sd, uint32_t fa, uint32_t raw) {
  const uint64_t w0 = mk_desc(st + wg * 8192), x0 = mk_desc(st + WBLK);
  const uint64_t da = mk_desc(fa), db = mk_desc(raw);
  wg_fence();
  if (NT) {
#pragma unroll
    for (int kk = 0; kk < NT; kk++) wgmma_fwd<1>(t, da + 2 * kk, db + 128 * kk, kk);
    wg_commit();
  }
#pragma unroll
  for (int kk = K0; kk < K1; kk++) {
    const uint64_t wr = w0 + kk * 128, wi = wr + 256, xr = x0 + kk * 2, xi = xr + 4;
    wgmma_main<1>(yr, wr, xr, kk ? 1 : sd);
    wgmma_main<1>(yi, wr, xi, kk ? 1 : sd);
    wgmma_main<1>(yr, wi, xi, 1);
    wgmma_main<-1>(yi, wi, xr, 1);
  }
  wg_commit();
}

#define X_WAIT() PROF_W(wraw, mbar_wait(bar + B_RAWX + 8 * (wg * 3 + xs), xph))
#define X_ISSUE() t_issue<true>(t, sb, sb + OFF_XR + (wg * 3 + xs) * 8192)
#define X_FINISH(sw) do { t_finish<true>(t, sb + OFF_XR + (wg * 3 + xs) * 8192, bar + B_STGX + 8 * (wg * 3 + xs), sw, wg, w, lane); \
                          if (++xs == 3) { xs = 0; xph ^= 1; } } while (0)
#define W_WAIT(n) PROF_W(wraw, mbar_wait(bar + B_RAWW + 8 * (wg * 2 + ((n) & 1)), ((n) >> 1) & 1))
#define WRAW(n) (sb + OFF_WRAW + (wg * 2 + ((n) & 1)) * 2048)
#define W_FINISH() t_finish<false>(t, sb + OFF_WS + wg * 8192, bar + B_STGW + 8 * wg, sww, wg, w, lane)

__global__ void __cluster_dims__(2, 1, 1) __launch_bounds__(512, 1)
k1_main(const __grid_constant__ Maps tm, uint8_t* __restrict__ xbuf, const __nv_bfloat16* __restrict__ gamma,
        const __nv_bfloat16* __restrict__ beta) {
  extern __shared__ __align__(1024) uint8_t smem_raw[];
  const uint32_t sb = s2u(smem_raw);
  const uint32_t bar = sb + OFF_BAR;
  const int warp = __shfl_sync(0xffffffffu, threadIdx.x >> 5, 0), lane = threadIdx.x & 31;
  const int bid = (int)blockIdx.x - 4;
  const uint32_t rank = bid & 1;
  if (warp < 3 && elect_one()) {
    if (warp == 0) {
      PROF_T(0);
#pragma unroll
      for (int o = 0; o < B_RAWW; o += 8) mbar_init(bar + o, o < B_EMPTY ? 1 : 4);
      mbar_expect(bar + B_ROLE, 4);
      mbar_expect(bar + B_ROLE + 8, 4);
      asm volatile("fence.mbarrier_init.release.cluster;" ::: "memory");
    } else if (warp == 1) {
#pragma unroll
      for (int o = B_RAWW; o < B_END; o += 8) mbar_init(bar + o, 2);
    } else {
#pragma unroll
      for (int i = 3; i < 6; i++) asm volatile("prefetch.tensormap [%0];" ::"l"(&tm.x + i) : "memory");
    }
  }
  __syncthreads();
  if (threadIdx.x == 64) PROF_T(20);
  asm volatile("barrier.cluster.arrive.relaxed.aligned;" ::: "memory");
  if (warp >= 12) {
    asm volatile("setmaxnreg.dec.sync.aligned.u32 24;");
    if (bid >= 0) {
      if (rank == 0) {
        const int k = bid >> 1, page = 2 + k % (XPAGES - 2);
        const uint32_t off = (warp & 2) ? (page << 21) + 0xb0000 + (k / (XPAGES - 2)) * 128 : (XPAGES << 21) + k * 64;
        const unsigned lat = probe(xbuf + off + (warp & 1) * 4096, lane, 400 + (warp & 2) * 5 + (warp & 1) * 3);
        if (lane == 0) asm volatile("st.shared.b32 [%0], %1;" ::"r"(bar + S_PROBE + 4 * (warp & 3)), "r"(lat) : "memory");
        asm volatile("bar.arrive 4, 160;" ::: "memory");
      }
      if (warp - 12 < NFL && elect_one()) {
        for (int n = warp - 12; n < 33; n += NFL) {
          int f = n;
          if (n == 32) f += (read_info(bar, 0) >> 5) * 2 + rank;
          mbar_wait(bar + B_DONE + 8 * n, 0);
          if (!NOFENCE) fence_release();
          red_add(&g_ctr[(C_FLAG + f) * 32]);
          if (n < 32) { PROF_T(64 + n); PROF_V(192 + n, tm0); } else { PROF_V(4, tm0); }
        }
      }
      __syncwarp();
    }
    asm volatile("barrier.cluster.wait.aligned;" ::: "memory");
    asm volatile("barrier.cluster.arrive.relaxed.aligned;\nbarrier.cluster.wait.aligned;" ::: "memory");
  } else if (warp >= 8) {
    asm volatile("setmaxnreg.dec.sync.aligned.u32 40;");
    if (bid < 0) {
      asm volatile("barrier.cluster.wait.aligned;" ::: "memory");
    } else if (warp == 9 || warp == 10) {
      if (elect_one()) {
        const int g = warp - 9;
        const uint64_t pol = policy_evict_first();
        int id = bid, role = -1;
        uint32_t pgmask = 0;
        int ln = 0, lj = 0;
        auto load_x = [&](int sl) {
          if (ln >= 16) return;
          if (ln >= OB && role < 0) role = read_info(bar, 0);
          const int lid = ln < OB ? bid : role * 2 + rank;
          const int t = lj ? 128 + (lid & 31) : 2 * (lid & 63) + g;
          mbar_expect(bar + B_RAWX + 8 * sl, 8192);
          tma_ld3h(sb + OFF_XR + sl * 8192, &tm.x, ln * 64, t * MT, lid >> 6, bar + B_RAWX + 8 * sl, pol);
          if (lj == 0 && has_x2(lid, ln, g)) lj = 1; else { lj = 0; ln++; }
        };
        auto load_w = [&](int n) {
          if (n >= 32) return;
          const int cp = chunk_of(n) * 64 + (bid >> 1), col = (cp & 511) * 8 + (n >> 4) * 4 + rank * 2 + g, sl = g * 2 + (n & 1);
          mbar_expect(bar + B_RAWW + 8 * sl, 2048);
          tma_ld3h(sb + OFF_WRAW + sl * 2048, cp < 512 ? &tm.we : &tm.wo, 0, 0, col, bar + B_RAWW + 8 * sl, pol);
        };
        if (g == 0) PROF_T(22);
        load_x(g * 3);
        if (g == 0) {
          mbar_expect(bar + B_F, 8192);
          bulk_ld(sb + OFF_F, g_Fimg, 8192, bar + B_F);
        }
        load_w(0);
        mbar_arrive(bar + B_RAWW + 16 * g);
        load_x(g * 3 + 1);
        load_w(1);
        if (g == 0) PROF_T(23);
        bool late = ln >= OB;
        if (!late) load_x(g * 3 + 2);
        int xs = 0, xph = 0, yp = 5;
        for (int n = 0; n < 32; n++) {
          if (n == OB) {
            if (role < 0) role = read_info(bar, 0);
            pgmask = read_info(bar, 1);
            id = role * 2 + rank;
          }
          unsigned freed = 128;
          if (n >= WR) asm volatile("ld.relaxed.gpu.global.u32 %0, [%1];" : "=r"(freed) : "l"(&g_ctr[(C_LOADED + n - WR) * 32]) : "memory");
          if (n < 16) {
            const int nx = has_x2(id, n, g) ? 2 : 1;
            for (int j = 0; j < nx; j++) {
              const int t = j ? 128 + (id & 31) : 2 * (id & 63) + g;
              const int tg = t >> 5, row = t & 31, sl = g * 3 + xs;
              int par0, par1;
              const uint32_t off0 = x_base(id >> 6, XC(n) * 10 + tg, pgmask, par0), off1 = x_base(id >> 6, XC(n) * 10 + 5 + tg, pgmask, par1);
              const uint32_t buf = sb + OFF_XR + sl * 8192;
              mbar_wait(bar + B_STGX + 8 * sl, xph);
              tma_st5(&tm.xst[par0], buf, (off0 + (par0 << 12) + row * 128) >> 1);
              tma_st5(&tm.xst[par1], buf + 4096, (off1 + (par1 << 12) + row * 128) >> 1);
              bulk_commit();
              if (late) { load_x(g * 3 + 2); late = false; }
              bulk_wait_read<0>();
              load_x(sl);
              if (++xs == 3) { xs = 0; xph ^= 1; }
            }
          }
          if (freed < 128) flag_wait(&g_ctr[(C_LOADED + n - WR) * 32], 128);
          if (n == 16 + LW) {
            mbar_wait(bar + B_Y + 8 * g, 0);
            yp = 0;
          }
          while (yp < 5 && (n == YFLUSH || !mbar_test(bar + B_STGW + 8 * g, n & 1))) {
            tma_st4(&tm.yst, sb + OFF_Y0 + (yp * 2 + g) * 8192, 0, yp * 32, 2 * (role & 31), (role >> 5) * 8 + rank * 2 + g);
            bulk_commit();
            bulk_wait_read<0>();
            if (++yp == 2) {
              mbar_arrive_cluster(bar + B_RET, 0, 1);
              mbar_arrive_cluster(bar + B_RET, 1, 1);
            }
          }
          const int wrow = (n % WR) * (WCHUNK / 128) + (rank * 2 + (bid >> 6)) * 128 + g * 64 + ((bid >> 1) & 31);
          mbar_wait(bar + B_STGW + 8 * g, n & 1);
          tma_st4(&tm.wst, sb + OFF_WS + g * 8192, 0, 0, 0, wrow);
          bulk_commit();
          load_w(n + 2);
          bulk_wait_all();
          mbar_arrive(bar + B_DONE + 8 * n);
          mbar_arrive(bar + B_RAWW + 8 * (g * 2 + ((n + 1) & 1)));
        }
        const int b = role >> 5, u = role & 31;
        mbar_wait(bar + B_Y + 8 * g, 1);
        for (int p = 0; p < 5; p++) tma_st4(&tm.yst, sb + (p * 2 + g) * 8192, 0, p * 32, 2 * u, b * 8 + 4 + rank * 2 + g);
        bulk_commit();
        bulk_wait_all();
        mbar_arrive(bar + B_DONE + 8 * 32);
        for (int i = 0; i < 10; i++) {
          const int hf = i >= 5, k = i - 5 * hf;
          mbar_wait(bar + B_OUT + 8 * (g * 5 + k), hf);
          tma_st3(&tm.out, sb + (hf ? 0 : OFF_H0) + (2 * k + g) * 8192, (hf * 4 + rank * 2 + (u & 1)) * 64, ((u >> 1) * 10 + 2 * k + g) * MT, b);
          bulk_commit();
        }
        bulk_wait_read<0>();
        if (g == 0) PROF_T(12);
      }
      __syncwarp();
      asm volatile("barrier.cluster.wait.aligned;" ::: "memory");
    } else if (warp == 11) {
      if (rank == 0) asm volatile("bar.sync 4, 160;" ::: "memory");
      asm volatile("barrier.cluster.wait.aligned;" ::: "memory");
      if (lane == 0 && rank == 0) {
        const int k = bid >> 1;
        uint32_t l0, l1, l2, l3;
        asm volatile("ld.shared.v4.b32 {%0, %1, %2, %3}, [%4];" : "=r"(l0), "=r"(l1), "=r"(l2), "=r"(l3) : "r"(bar + S_PROBE) : "memory");
        const int side = l1 < l0, near = l3 >= l2;
        unsigned long long add = 1ull << (8 * side), v;
        if (k < XPAGES - 2) add += (unsigned long long)(near ^ side) << (18 + k);
        unsigned long long* reg = (unsigned long long*)&g_ctr[C_REG * 32];
        PROF_T(14);
        const int ticket = (atomicAdd(reg, add) >> (8 * side)) & 255;
        if (ticket < 1000) PROF_T(15);
        const int role = ticket < 32 ? side * 32 + ticket : (side ^ 1) * 32 + 63 - ticket;
        send_info(bar, 0, role);
        asm volatile("{\n.reg .pred p;\n.reg .u32 c, a, b;\nmov.u32 c, 0;\nWAIT:\n"
                     "ld.relaxed.gpu.global.u64 %0, [%1];\ncvt.u32.u64 a, %0;\nbfe.u32 b, a, 8, 8;\nand.b32 a, a, 255;\nadd.u32 a, a, b;\n"
                     "setp.ge.u32 p, a, 64;\n@p bra DONE;\n"
                     "add.u32 c, c, 1;\nsetp.lt.u32 p, c, 0x400000;\n@p bra WAIT;\ntrap;\nDONE:\n}" : "=l"(v) : "l"(reg) : "memory");
        send_info(bar, 1, (uint32_t)(v >> 16));
        PROF_V(16, side); PROF_V(17, role); PROF_V(18, v);
      }
      __syncwarp();
    } else {
      asm volatile("barrier.cluster.wait.aligned;" ::: "memory");
      if (elect_one()) {
        const int role = read_info(bar, 0);
        uint32_t pgmask = 0;
        PROF_T(1);
        const int b = role >> 5, u = role & 31;
        const uint64_t pef = policy_evict_first(), pen = policy_evict_normal();
        const uint8_t* xs = xbuf + ((((u >> 1) & 3) << 14) | (((u >> 3) & 1) << 18) | ((u >> 4) << 20) | ((u & 1) << 13));
        const uint8_t* ws = g_W + (size_t)(u * 2 + rank) * 2 * WBLK;
        int s = 3, phm = 15;
        for (int v = 0; v < 64; v++) {
          const int n = v >> 1, h = v & 1, c = chunk_of(n);
          const uint64_t polx = (n < XEF0 || n >= 16) ? pef : pen;
          const uint32_t dst = sb + s * G_STAGE, fb = bar + B_FULL + 8 * s;
          const uint8_t* wsrc = ws + (size_t)(n % WR) * WCHUNK + h * WBLK;
          if (v == 2 * OB) pgmask = read_info(bar, 1);
          uint32_t xo[3];
#pragma unroll
          for (int g = 0; g < 3; g++) {
            int par;
            xo[g] = x_base(b, XC(c) * 10 + h * 5 + rank * 2 + g, c < OB ? 0 : pgmask, par);
            xo[g] += ((par ^ u) & 1) << 12;
          }
          if (h == 0 && n < 16) {
            flag_wait(&g_ctr[(C_FLAG + n) * 32], 128);
            fence_async_global();
            PROF_T(32 + n);
          }
          if (v == 38) mbar_wait(bar + B_RET, 0);
          mbar_wait(bar + B_EMPTY + 8 * s, (phm >> s) & 1);
          phm ^= 1 << s;
          mbar_expect(fb, G_STAGE);
#pragma unroll
          for (int g = 0; g < 3; g++) {
            const int skip = (g == 0 && rank) ? 2048 : 0, len = (g == (rank ? 0 : 2)) ? 2048 : 4096;
            bulk_ld_mc_h(dst + WBLK + (rank * 2 + g) * 4096 + skip, xs + xo[g] + skip, len, fb, 3, polx);
          }
          if (h == 0 && n >= 16) {
            flag_wait(&g_ctr[(C_FLAG + n) * 32], 128);
            fence_async_global();
            PROF_T(32 + n);
          }
          bulk_ld(dst, wsrc, WBLK, fb);
          s = next_slot(s, v + 1);
        }
        const int dq = rank * 2 + (u & 1), t0 = (u >> 1) * 10;
        flag_wait(&g_ctr[C_E * 32], 4);
        fence_async_global();
        mbar_wait(bar + B_DONE + 8 * 31, 0);
        mbar_wait(bar + B_EMPTY + 8 * 3, (phm >> 3) & 1);
        mbar_expect(bar + B_H0, 10 * 8192 + 7168 + 5120 + 512);
        bulk_ld(sb + OFF_F, g_Gimg, 7168, bar + B_H0);
        for (int i = 0; i < 5; i++) tma_ld2(sb + OFF_H0 + i * 16384, &tm.yld, 0, ((b * 8 + dq) * NT + t0 + 2 * i) * 64, bar + B_H0);
        for (int hf = 0; hf < 2; hf++) {
          bulk_ld(sb + OFF_E + hf * 2560, g_E + ((b * 8 + hf * 4 + dq) * NT + t0) * 64, 2560, bar + B_H0);
          bulk_ld(sb + OFF_GB + hf * 256, gamma + (hf * 4 + dq) * 64, 128, bar + B_H0);
          bulk_ld(sb + OFF_GB + hf * 256 + 128, beta + (hf * 4 + dq) * 64, 128, bar + B_H0);
        }
        flag_wait(&g_ctr[(C_FLAG + 32 + b * 2 + rank) * 32], 32);
        fence_async_global();
        PROF_T(5);
        for (int i = 0; i < 5; i++) {
          const uint32_t fb = bar + B_H1 + 8 * (i >> 1);
          if ((i & 1) == 0) mbar_expect(fb, i < 4 ? 32768 : 16384);
          tma_ld2(sb + i * 16384, &tm.yld, 0, ((b * 8 + 4 + dq) * NT + t0 + 2 * i) * 64, fb);
        }
      }
      __syncwarp();
      unsigned old = 0;
      if (lane == 0) old = atomicAdd(&g_ctr[C_EXIT * 32], 1);
      if (__shfl_sync(0xffffffffu, old, 0) == 127) {
        for (int i = lane; i < C_NUM; i += 32) *(volatile unsigned long long*)&g_ctr[i * 32] = 0;
      }
    }
    asm volatile("barrier.cluster.arrive.relaxed.aligned;\nbarrier.cluster.wait.aligned;" ::: "memory");
  } else {
    asm volatile("setmaxnreg.inc.sync.aligned.u32 224;");
    const int wg = warp >> 2, w = warp & 3;
    asm volatile("barrier.cluster.wait.aligned;" ::: "memory");
    if (bid < 0) {
      float ea[80], eb[80];
      const int b = blockIdx.x >> 1;
      constexpr int ES = 32768 + 2 * XBLK;
#pragma unroll 1
      for (int k = -3; k < 8; k++) {
        const int sl = (k + 3) % 3;
        if (k >= 0) {
          mbar_wait(bar + B_FULL + 8 * sl, (k / 3) & 1);
          const uint64_t da = mk_desc(sb + sl * ES + wg * 16384), db = mk_desc(sb + sl * ES + 32768);
          wg_fence();
#pragma unroll
          for (int kk = 0; kk < 8; kk++) {
            const uint64_t a0 = da + (kk & 3) * 128, b0 = db + (kk & 3) * 2 + (kk >> 2) * (XBLK >> 4);
            wgmma_main<1>(ea, a0, b0, (k | kk) != 0);
            wgmma_main<1>(eb, a0 + 512, b0, (k | kk) != 0);
          }
          wg_commit();
          wg_wait<0>();
          asm volatile("bar.sync 3, 256;" ::: "memory");
        }
        if (k + 3 < 8 && warp == 0 && elect_one()) {
          const uint32_t dst = sb + sl * ES, fb = bar + B_FULL + 8 * sl;
          mbar_expect(fb, ES);
          for (int q = 0; q < 4; q++) tma_ld2(dst + q * 8192, &tm.w30, rank * 256 + q * 64, (k + 3) * 64, fb);
          for (int q = 0; q < 2; q++) tma_ld3(dst + 32768 + q * XBLK, &tm.xe[q], (k + 3) * 64, 0, b, fb);
        }
        __syncwarp();
      }
      fence_regs(ea);
      fence_regs(eb);
      float* e0 = g_E + ((b * 8 + rank * 4 + wg * 2) * NT + 2 * (lane & 3)) * 64 + 16 * w + (lane >> 2);
#pragma unroll
      for (int i = 0; i < 80; i++) {
        const int o = (8 * (i >> 2) + (i & 1)) * 64 + ((i >> 1) & 1) * 8;
        e0[o] = ea[i];
        e0[o + NT * 64] = eb[i];
      }
      asm volatile("bar.sync 3, 256;" ::: "memory");
      if (threadIdx.x == 0) {
        fence_release();
        red_add(&g_ctr[C_E * 32]);
        PROF_T(28);
      }
      asm volatile("barrier.cluster.arrive.relaxed.aligned;\nbarrier.cluster.wait.aligned;" ::: "memory");
      return;
    }
    if (wg == 0) g_part[bid * 128 + threadIdx.x] = ~0ull;
    int id = bid;
    {
      float yr[80], yi[80], t[32];
      const int sww = (bid >> 1) & 7;
      int xs = 0, xph = 0;
      unsigned wraw = 0, wfull = 0;
      if (threadIdx.x == 0) PROF_T(24);
      mbar_wait(bar + B_F, 0);
      if (threadIdx.x == 0) PROF_T(25);
#pragma unroll 1
      for (int m = 0; m < LW + 1 - XFIRST; m++) {
        if (m == OB) id = __shfl_sync(0xffffffffu, read_info(bar, 0), 0) * 2 + rank;
        X_WAIT();
        X_ISSUE();
        wg_wait<0>();
        X_FINISH((2 * id + wg) & 7);
        if (threadIdx.x == 0 && m == 0) PROF_T(26);
        if (has_x2(id, m, wg)) {
          X_WAIT();
          X_ISSUE();
          wg_wait<0>();
          X_FINISH(id & 7);
        }
        if (m < LW) {
          W_WAIT(m);
          t_issue<false>(t, sb, WRAW(m));
          wg_wait<0>();
          W_FINISH();
        }
      }
      if (threadIdx.x == 0) PROF_T(27);
      static_assert(OB < LW + 1 - XFIRST, "role is read in the prologue");
      int s = 3, phm = 0;
#pragma unroll 1
      for (int pass = 0; pass < 2; pass++) {
        int sprev = -1;
#pragma unroll 1
        for (int i = 0; i < 32; i++) {
          const int v = pass * 32 + i, n = v >> 1;
          const int mw = n + LW, mx = mw + 1 - XFIRST;
          const bool xstage = (v & 1) != XFIRST;
          if (!(v & 1)) { wraw = 0; wfull = 0; }
          PROF_W(wfull, mbar_wait(bar + B_FULL + 8 * s, (phm >> s) & 1));
          phm ^= 1 << s;
          const uint32_t st = sb + s * G_STAGE;
#define RELEASE() do { if (w == 0 && lane < 2) { if (sprev >= 0) mbar_arrive_cluster(bar + B_EMPTY + 8 * sprev, lane, 1); } \
                       else if (threadIdx.x == 32 && (v & 1)) red_add(&g_ctr[(C_LOADED + n) * 32]); } while (0)
#define XRAW (sb + OFF_XR + (wg * 3 + xs) * 8192)
          if (xstage && mx < 16) {
            X_WAIT();
            batch<4, 0, 1>(yr, yi, t, st, wg, i != 0, sb + OFF_F, XRAW);
            wg_wait<1>();
            RELEASE();
            X_FINISH((2 * id + wg) & 7);
            if (has_x2(id, mx, wg)) {
              X_WAIT();
              batch<4, 1, 2>(yr, yi, t, st, wg, 1, sb + OFF_F, XRAW);
              wg_wait<1>();
              X_FINISH(id & 7);
            } else {
              batch<0, 1, 2>(yr, yi, t, st, wg, 1, 0, 0);
            }
          } else if (!xstage && mw < 32) {
            W_WAIT(mw);
            batch<1, 0, 1>(yr, yi, t, st, wg, i != 0, sb + OFF_F, WRAW(mw));
            wg_wait<1>();
            RELEASE();
            W_FINISH();
            batch<0, 1, 2>(yr, yi, t, st, wg, 1, 0, 0);
          } else {
            batch<0, 0, 1>(yr, yi, t, st, wg, i != 0, 0, 0);
            wg_wait<1>();
            RELEASE();
            batch<0, 1, 2>(yr, yi, t, st, wg, 1, 0, 0);
          }
          sprev = s;
          s = next_slot(s, v + 1);
        }
        wg_wait<0>();
        fence_regs(yr);
        fence_regs(yi);
        if (w == 0 && lane < 2) mbar_arrive_cluster(bar + B_EMPTY + 8 * sprev, lane, 1);
        if (pass == 0) mbar_wait(bar + B_EMPTY + 8 * 3, 1);
        else asm volatile("bar.sync 3, 256;" ::: "memory");
        const int m = lane >> 3, r = lane & 7;
        const uint32_t ad = sb + (pass ? 0 : OFF_Y0) + wg * 8192 + (m >> 1) * 4096 + r * 128 + (((2 * w + (m & 1)) ^ r) << 4);
#pragma unroll
        for (int j = 0; j < 20; j++)
          stsm4t(ad + (j >> 2) * 16384 + (j & 3) * 1024, pack2(yr[4 * j], yr[4 * j + 1]), pack2(yr[4 * j + 2], yr[4 * j + 3]),
                 pack2(yi[4 * j], yi[4 * j + 1]), pack2(yi[4 * j + 2], yi[4 * j + 3]));
        fence_async_smem();
        __syncwarp();
        if (lane == 0) mbar_arrive(bar + B_Y + 8 * wg);
        if (threadIdx.x == 0) PROF_T(2 + pass);
      }
    }
    const int b = id >> 6, u = (id >> 1) & 31;
    const int dq = rank * 2 + (u & 1), tr = u >> 1;
    const int a = lane & 3, d0 = 16 * w + (lane >> 2);
    float2* s_red = (float2*)(smem_raw + OFF_WRAW);
#pragma unroll 1
    for (int hf = 0; hf < 2; hf++) {
      const uint32_t base = sb + (hf ? 0 : OFF_H0);
      float acc[5][28];
      float s1[2] = {0.f, 0.f}, s2[2] = {0.f, 0.f};
      if (hf == 0) mbar_wait(bar + B_H0, 0);
      const float* se = (const float*)(smem_raw + OFF_E + hf * 2560) + wg * 64 + d0;
#pragma unroll
      for (int k2 = 0; k2 < 4; k2++) {
        if (k2 < 3) {
          if (hf) mbar_wait(bar + B_H1 + 8 * k2, 0);
          const uint64_t da = mk_desc(base + (4 * k2 + wg) * 8192), db = mk_desc(sb + OFF_F);
          wg_fence();
#pragma unroll
          for (int kk = 0; kk < 4; kk++) {
            wgmma_inv<1>(acc[2 * k2], da + 128 * kk, db + 2 * kk, kk);
            if (k2 < 2) wgmma_inv<1>(acc[2 * k2 + 1], da + 1024 + 128 * kk, db + 2 * kk, kk);
          }
          wg_commit();
        }
        if (k2 > 0) {
          if (k2 < 3) wg_wait<1>(); else wg_wait<0>();
#pragma unroll
          for (int k = 2 * k2 - 2; k < 2 * k2 && k < 5; k++) {
            fence_regs(acc[k]);
            if (a == 0) {
              acc[k][25] += se[k * 128];
              acc[k][27] += se[k * 128 + 8];
            }
            if (k == 4 && tr == 15 && wg == 1) {
#pragma unroll
              for (int i = 16; i < 28; i++)
                if (8 * (i >> 2) + (i & 1) + 2 * a >= LOUT - (NT - 1) * MT) acc[k][i] = 0.f;
            }
#pragma unroll
            for (int i = 0; i < 28; i += 2) {
              s1[(i >> 1) & 1] += acc[k][i] + acc[k][i + 1];
              s2[(i >> 1) & 1] += fmaf(acc[k][i], acc[k][i], acc[k][i + 1] * acc[k][i + 1]);
            }
          }
        }
      }
#pragma unroll
      for (int i = 0; i < 2; i++) {
#pragma unroll
        for (int o = 1; o < 4; o <<= 1) {
          s1[i] += __shfl_xor_sync(0xffffffffu, s1[i], o);
          s2[i] += __shfl_xor_sync(0xffffffffu, s2[i], o);
        }
      }
      if (a == 0) {
        s_red[wg * 64 + d0] = make_float2(s1[0], s2[0]);
        s_red[wg * 64 + d0 + 8] = make_float2(s1[1], s2[1]);
      }
      asm volatile("bar.sync 3, 256;" ::: "memory");
      if (threadIdx.x == 0) PROF_T(6 + 3 * hf);
      unsigned long long* part = g_part + ((hf * 2 + b) * 4 + dq) * 1024;
      if (threadIdx.x < 64) {
        const float2 p0 = s_red[threadIdx.x], p1 = s_red[64 + threadIdx.x];
        const float x1 = p0.x + p1.x, x2 = p0.y + p1.y;
        const unsigned long long v = ((unsigned long long)(__float_as_uint(x2) & 0x7fffffffu) << 32) | __float_as_uint(x1);
        asm volatile("st.relaxed.gpu.global.u64 [%0], %1;" ::"l"(part + tr * 64 + threadIdx.x), "l"(v) : "memory");
      }
      {
        const unsigned long long* q = part + (threadIdx.x >> 6) * 256 + (threadIdx.x & 63);
        unsigned long long v[4];
        poll64x4(q, v);
        float x1 = 0.f, x2 = 0.f;
#pragma unroll
        for (int i = 0; i < 4; i++) {
          x1 += __uint_as_float((uint32_t)v[i]);
          x2 += __uint_as_float((uint32_t)(v[i] >> 32));
        }
        s_red[128 + threadIdx.x] = make_float2(x1, x2);
      }
      asm volatile("bar.sync 3, 256;" ::: "memory");
      if (threadIdx.x == 0) PROF_T(7 + 3 * hf);
#pragma unroll
      for (int i = 0; i < 2; i++) {
        const float2 q0 = s_red[128 + d0 + 8 * i], q1 = s_red[192 + d0 + 8 * i], q2 = s_red[256 + d0 + 8 * i], q3 = s_red[320 + d0 + 8 * i];
        const float mu = ((q0.x + q1.x) + (q2.x + q3.x)) * (1.f / LOUT);
        const float var = fmaxf(((q0.y + q1.y) + (q2.y + q3.y)) * (1.f / LOUT) - mu * mu, 0.f);
        const __nv_bfloat16* gb = (const __nv_bfloat16*)(smem_raw + OFF_GB + hf * 256) + d0 + 8 * i;
        s1[i] = 0.5f * __bfloat162float(gb[0]) / sqrtf(var + 1e-5f);
        s2[i] = 0.5f * __bfloat162float(gb[64]) - mu * s1[i];
      }
      const int m = lane >> 3, r = lane & 7;
      const uint32_t ad = base + wg * 8192 + ((m >> 1) * 8 + r) * 128 + (((2 * w + (m & 1)) ^ r) << 4);
#pragma unroll
      for (int k = 0; k < 5; k++) {
        fence_regs(acc[k]);
#pragma unroll
        for (int i = 0; i < 28; i++) {
          const float hz = fmaf(acc[k][i], s1[(i >> 1) & 1], s2[(i >> 1) & 1]);
          const float in = hz * fmaf(hz * hz, 8.f * 0.044715f * 0.7978845608028654f, 2.f * 0.7978845608028654f);
          float th;
          asm("tanh.approx.f32 %0, %1;" : "=f"(th) : "f"(in));
          acc[k][i] = fmaf(hz, th, hz);
        }
#pragma unroll
        for (int jj = 0; jj < 3; jj++) {
          const float* c = acc[k] + 8 * jj;
          stsm4t(ad + k * 16384 + jj * 2048, pack2(c[0], c[1]), pack2(c[2], c[3]), pack2(c[4], c[5]), pack2(c[6], c[7]));
        }
        stsm2t(ad + k * 16384 + 3 * 2048, pack2(acc[k][24], acc[k][25]), pack2(acc[k][26], acc[k][27]));
        fence_async_smem();
        __syncwarp();
        if (lane == 0) mbar_arrive(bar + B_OUT + 8 * (wg * 5 + k));
      }
      if (threadIdx.x == 0) PROF_T(8 + 3 * hf);
    }
    asm volatile("barrier.cluster.arrive.relaxed.aligned;\nbarrier.cluster.wait.aligned;" ::: "memory");
  }
}

typedef CUresult (*EncFn)(CUtensorMap*, CUtensorMapDataType, cuuint32_t, void*, const cuuint64_t*, const cuuint64_t*, const cuuint32_t*,
                          const cuuint32_t*, CUtensorMapInterleave, CUtensorMapSwizzle, CUtensorMapL2promotion, CUtensorMapFloatOOBfill);

void encode(EncFn fn, CUtensorMap* m, int rank, void* base, const cuuint64_t* dims, const cuuint64_t* strides, const cuuint32_t* box,
            CUtensorMapL2promotion promo) {
  cuuint32_t es[5] = {1, 1, 1, 1, 1};
  fn(m, CU_TENSOR_MAP_DATA_TYPE_BFLOAT16, rank, base, dims, strides, box, es, CU_TENSOR_MAP_INTERLEAVE_NONE, CU_TENSOR_MAP_SWIZZLE_128B, promo,
     CU_TENSOR_MAP_FLOAT_OOB_FILL_NONE);
}

}

extern "C" void kernel_launch(void* const* d_in, const int* in_sizes, int n_in, void* d_out, int out_size) {
  (void)in_sizes; (void)n_in; (void)out_size;
  const __nv_bfloat16* x = (const __nv_bfloat16*)d_in[0];
  const __nv_bfloat16* w = (const __nv_bfloat16*)d_in[1];
  const __nv_bfloat16* gamma = (const __nv_bfloat16*)d_in[2];
  const __nv_bfloat16* beta = (const __nv_bfloat16*)d_in[3];
  void* fnp = nullptr;
  cudaDriverEntryPointQueryResult qr;
  cudaGetDriverEntryPoint("cuTensorMapEncodeTiled", &fnp, cudaEnableDefault, &qr);
  EncFn fn = (EncFn)fnp;
  void *xptr = nullptr, *wptr = nullptr, *yptr = nullptr;
  cudaGetSymbolAddress(&xptr, g_X);
  cudaGetSymbolAddress(&wptr, g_W);
  cudaGetSymbolAddress(&yptr, g_Y);
  xptr = (void*)(((uintptr_t)xptr + (1u << 21) - 1) & ~(uintptr_t)((1u << 21) - 1));
  const CUtensorMapL2promotion P0 = CU_TENSOR_MAP_L2_PROMOTION_NONE, P128 = CU_TENSOR_MAP_L2_PROMOTION_L2_128B;
  Maps m;
  {
    cuuint64_t d[3] = {1024, 8000, 2}, s[2] = {2048, 8000ull * 2048};
    cuuint32_t bx[3] = {64, 64, 1};
    encode(fn, &m.x, 3, (void*)x, d, s, bx, P128);
  }
  for (int ph = 0; ph < 2; ph++) {
    cuuint64_t d[3] = {64, (cuuint64_t)(16 - ph), 4096}, s[2] = {2ull * 262144 * 2, 128};
    cuuint32_t bx[3] = {64, 16, 1};
    encode(fn, ph ? &m.wo : &m.we, 3, (void*)(w + (size_t)ph * 262144), d, s, bx, P128);
  }
  for (int par = 0; par < 2; par++) {
    cuuint64_t d[5] = {(cuuint64_t)XPAGES << 20, 2, 4, 2, 2}, s[4] = {par ? 0x1000u : 0x3000u, 1u << 14, 1u << 18, 1u << 20};
    cuuint32_t bx[5] = {64, 2, 4, 2, 2};
    encode(fn, &m.xst[par], 5, xptr, d, s, bx, P0);
  }
  {
    cuuint64_t d[4] = {64, 32, 2, (cuuint64_t)WR * WCHUNK / 128}, s[3] = {4ull * WBLK, 4096, 128};
    cuuint32_t bx[4] = {64, 32, 2, 1};
    encode(fn, &m.wst, 4, wptr, d, s, bx, P0);
  }
  {
    cuuint64_t d[4] = {64, NT, 64, 16}, s[3] = {8192, 128, (cuuint64_t)NT * 8192};
    cuuint32_t bx[4] = {64, 32, 2, 1};
    encode(fn, &m.yst, 4, yptr, d, s, bx, P0);
  }
  {
    cuuint64_t d[2] = {64, 16ull * NT * 64}, s[1] = {128};
    cuuint32_t bx[2] = {64, 128};
    encode(fn, &m.yld, 2, yptr, d, s, bx, P128);
  }
  {
    cuuint64_t d[3] = {512, LOUT, 2}, s[2] = {1024, (cuuint64_t)LOUT * 1024};
    cuuint32_t bx[3] = {64, MT, 1};
    encode(fn, &m.out, 3, d_out, d, s, bx, P0);
  }
  for (int q = 0; q < 2; q++) {
    cuuint64_t d[3] = {512, (cuuint64_t)(NT - q), 2}, s[2] = {MT * 2048, 8000ull * 2048};
    cuuint32_t bx[3] = {64, NT, 1};
    encode(fn, &m.xe[q], 3, (void*)(x + q * 64 * 1024), d, s, bx, P128);
  }
  {
    cuuint64_t d[2] = {512, 512}, s[1] = {1024};
    cuuint32_t bx[2] = {64, 64};
    encode(fn, &m.w30, 2, (void*)(w + 30 * 262144), d, s, bx, P128);
  }
  cudaFuncSetAttribute(k1_main, cudaFuncAttributeMaxDynamicSharedMemorySize, SMEM_BYTES);
  k1_main<<<132, 512, SMEM_BYTES>>>(m, (uint8_t*)xptr, gamma, beta);
}
```

```cpp
#include <cuda_runtime.h>
#include <cuda_bf16.h>
#include <cuda.h>
#include <stdint.h>

namespace {

#define LW_ 4
#define WR_ 5
#define OB_ 2
#define XEF0 11
#define XC(c) (c)
#define NOFENCE 0
constexpr int LOUT = 7985;
constexpr int MT = 50;
constexpr int NT = 160;
constexpr int XBLK = NT * 128;
constexpr int WBLK = 16384;
constexpr int LW = LW_;
constexpr int WR = WR_;
constexpr int OB = OB_;
constexpr int WCHUNK = 32 * 4 * WBLK;
constexpr int XPAGES = 20;
#define NFL 2
constexpr int YFLUSH = 16 + LW + 4;

__device__ __align__(1024) uint8_t g_X[(XPAGES + 2) << 21];
__device__ __align__(1024) uint8_t g_W[(size_t)WR * WCHUNK];
__device__ __align__(1024) uint8_t g_Y[16ull * NT * 8192];
__device__ __align__(128) float g_E[16 * NT * 64];
__device__ unsigned long long g_part[128 * 128];
constexpr int C_FLAG = 0, C_LOADED = 36, C_REG = 68, C_EXIT = 69, C_E = 70, C_NUM = 71;
__device__ __align__(128) unsigned g_ctr[C_NUM * 32];
#define PROF_T(i)
#define PROF_C(i)
#define PROF_V(i, v)
#define PROF_W(acc, stmt) stmt

__device__ __align__(128) const uint32_t g_Fimg[2048] = {
 0x3f803f80,0x3f7d3f7f,0x3f783f7b,0x3f713f75,0x3f673f6d,0x3f5c3f62,0x3f4e3f55,0x3f3e3f46,0x3f2c3f35,0x3f183f22,0x3f043f0e,0x3edb3ef1,0x3eac3ec4,0x3e793e95,0x3e163e48,0x3d493dc9,
 0xbd490000,0xbe16bdc9,0xbe79be48,0xbeacbe95,0xbedbbec4,0xbf04bef1,0xbf18bf0e,0xbf2cbf22,0xbf3ebf35,0xbf4ebf46,0xbf5cbf55,0xbf67bf62,0xbf71bf6d,0xbf78bf75,0xbf7dbf7b,0xbf80bf7f,
 0x3e793ec4,0xbd493dc9,0xbeacbe48,0xbf18bef1,0x3f7d3f80,0x3f673f75,0x3f3e3f55,0x3f043f22,0xbf5cbf6d,0xbf2cbf46,0xbedbbf0e,0xbe16be95,0xbf4ebf35,0xbf71bf62,0xbf80bf7b,0xbf78bf7f,
 0x3f783f6d,0x3f803f7f,0x3f713f7b,0x3f4e3f62,0x3e160000,0x3edb3e95,0x3f2c3f0e,0x3f5c3f46,0xbf04bec4,0xbf3ebf22,0xbf67bf55,0xbf7dbf75,0x3f183f35,0x3eac3ef1,0x3d493e48,0xbe79bdc9,
 0xbf04bf35,0xbd49be95,0x3edb3e48,0x3f4e3f22,0x3f7d3f6d,0x3f713f7f,0x3f2c3f55,0x3e793ef1,0x3f783f80,0x3f3e3f62,0x3eac3f0e,0xbe163dc9,0xbf18bec4,0xbf67bf46,0xbf80bf7b,0xbf5cbf75,
 0x3f5c3f35,0x3f803f75,0x3f673f7b,0x3f183f46,0x3e163ec4,0xbeacbdc9,0xbf3ebf0e,0xbf78bf62,0xbe790000,0xbf2cbef1,0xbf71bf55,0xbf7dbf7f,0xbf4ebf6d,0xbedbbf22,0x3d49be48,0x3f043e95,
 0xbf2cbec4,0xbf7dbf62,0xbf5cbf7b,0xbeacbf22,0x3f673f35,0x3f783f7f,0x3f183f55,0xbd493e95,0xbf80bf6d,0xbf4ebf75,0xbe79bf0e,0x3edb3dc9,0x3f713f80,0x3f043f46,0xbe163e48,0xbf3ebef1,
 0x3f3e3f6d,0x3e163ef1,0xbf04be48,0xbf71bf46,0xbedbbf35,0x3e79bdc9,0x3f4e3f0e,0x3f803f75,0x3d493ec4,0xbf18be95,0xbf78bf55,0xbf67bf7f,0x3eac0000,0x3f5c3f22,0x3f7d3f7b,0x3f2c3f62,
 0xbedb0000,0xbf78bf46,0xbf4ebf7b,0xbd49bef1,0x3f3e3ec4,0x3f7d3f75,0x3f043f55,0xbeac3dc9,0xbf71bf35,0xbf5cbf7f,0xbe16bf0e,0x3f2c3e95,0x3f803f6d,0x3f183f62,0xbe793e48,0xbf67bf22,
 0x3f673f80,0x3e793f22,0xbf18be48,0xbf80bf62,0xbf2cbf6d,0x3e16be95,0x3f5c3f0e,0x3f713f7f,0x3eac3f35,0xbf04bdc9,0xbf7dbf55,0xbf3ebf75,0x3d49bec4,0x3f4e3ef1,0x3f783f7b,0x3edb3f46,
 0xbf7dbf6d,0xbeacbf46,0x3f2c3e48,0x3f783f75,0x3f040000,0x3f803f62,0x3edb3f55,0xbf18bdc9,0x3f4e3ec4,0x3f673f7f,0x3d493f0e,0xbf5cbef1,0x3e793f35,0xbf3ebe95,0xbf71bf7b,0xbe16bf22,
 0x3e16bec4,0x3f713f22,0x3f3e3f7b,0xbe793e95,0x3f5c3f80,0xbd493ef1,0xbf67bf0e,0xbf4ebf7f,0x3f183f6d,0xbedb3dc9,0xbf80bf55,0xbf04bf62,0xbf78bf35,0xbf2cbf75,0x3eacbe48,0x3f7d3f46,
 0x3f7d3f35,0x3edb3f62,0xbf3ebe48,0xbf5cbf7f,0x3e79bec4,0x3f803f46,0x3eac3f55,0xbf4ebe95,0xbf180000,0xbf71bf75,0x3d49bf0e,0x3f783f22,0x3f043f6d,0xbf2cbdc9,0xbf67bf7b,0x3e16bef1,
 0xbe16bf35,0x3f673ef1,0x3f2c3f7b,0xbf043dc9,0xbf78bf6d,0xbd49bf22,0x3f713f0e,0x3f183f75,0x3f4e3f80,0xbeac3e95,0xbf80bf55,0xbe79bf46,0x3f5c3ec4,0x3f3e3f7f,0xbedb3e48,0xbf7dbf62,
 0xbedbbf6d,0x3f5c3e95,0x3f183f7b,0xbf3ebdc9,0xbd49bf35,0x3f7d3f22,0x3e793f55,0xbf71bef1,0x3eacbec4,0x3f783f62,0xbe163f0e,0xbf80bf46,0x3f2c0000,0x3f4e3f7f,0xbf043e48,0xbf67bf75,
 0x3f673ec4,0x3f043f75,0xbf4ebe48,0xbf2cbf7f,0x3f803f35,0x3e163f46,0xbf78bf0e,0xbeacbf62,0x3f713f6d,0xbe793ef1,0xbf7dbf55,0x3d49bf22,0x3f3e3f80,0xbf183dc9,0xbf5cbf7b,0x3edbbe95,
 0xbd490000,0xbe16bdc9,0xbe79be48,0xbeacbe95,0xbedbbec4,0xbf04bef1,0xbf18bf0e,0xbf2cbf22,0xbf3ebf35,0xbf4ebf46,0xbf5cbf55,0xbf67bf62,0xbf71bf6d,0xbf78bf75,0xbf7dbf7b,0xbf80bf7f,
 0xbf80bf80,0xbf7dbf7f,0xbf78bf7b,0xbf71bf75,0xbf67bf6d,0xbf5cbf62,0xbf4ebf55,0xbf3ebf46,0xbf2cbf35,0xbf18bf22,0xbf04bf0e,0xbedbbef1,0xbeacbec4,0xbe79be95,0xbe16be48,0xbd49bdc9,
 0xbf78bf6d,0xbf80bf7f,0xbf71bf7b,0xbf4ebf62,0xbe160000,0xbedbbe95,0xbf2cbf0e,0xbf5cbf46,0x3f043ec4,0x3f3e3f22,0x3f673f55,0x3f7d3f75,0xbf18bf35,0xbeacbef1,0xbd49be48,0x3e793dc9,
 0x3e793ec4,0xbd493dc9,0xbeacbe48,0xbf18bef1,0x3f7d3f80,0x3f673f75,0x3f3e3f55,0x3f043f22,0xbf5cbf6d,0xbf2cbf46,0xbedbbf0e,0xbe16be95,0xbf4ebf35,0xbf71bf62,0xbf80bf7b,0xbf78bf7f,
 0x3f5c3f35,0x3f803f75,0x3f673f7b,0x3f183f46,0x3e163ec4,0xbeacbdc9,0xbf3ebf0e,0xbf78bf62,0xbe790000,0xbf2cbef1,0xbf71bf55,0xbf7dbf7f,0xbf4ebf6d,0xbedbbf22,0x3d49be48,0x3f043e95,
 0x3f043f35,0x3d493e95,0xbedbbe48,0xbf4ebf22,0xbf7dbf6d,0xbf71bf7f,0xbf2cbf55,0xbe79bef1,0xbf78bf80,0xbf3ebf62,0xbeacbf0e,0x3e16bdc9,0x3f183ec4,0x3f673f46,0x3f803f7b,0x3f5c3f75,
 0xbf3ebf6d,0xbe16bef1,0x3f043e48,0x3f713f46,0x3edb3f35,0xbe793dc9,0xbf4ebf0e,0xbf80bf75,0xbd49bec4,0x3f183e95,0x3f783f55,0x3f673f7f,0xbeac0000,0xbf5cbf22,0xbf7dbf7b,0xbf2cbf62,
 0xbf2cbec4,0xbf7dbf62,0xbf5cbf7b,0xbeacbf22,0x3f673f35,0x3f783f7f,0x3f183f55,0xbd493e95,0xbf80bf6d,0xbf4ebf75,0xbe79bf0e,0x3edb3dc9,0x3f713f80,0x3f043f46,0xbe163e48,0xbf3ebef1,
 0xbf67bf80,0xbe79bf22,0x3f183e48,0x3f803f62,0x3f2c3f6d,0xbe163e95,0xbf5cbf0e,0xbf71bf7f,0xbeacbf35,0x3f043dc9,0x3f7d3f55,0x3f3e3f75,0xbd493ec4,0xbf4ebef1,0xbf78bf7b,0xbedbbf46,
 0xbedb0000,0xbf78bf46,0xbf4ebf7b,0xbd49bef1,0x3f3e3ec4,0x3f7d3f75,0x3f043f55,0xbeac3dc9,0xbf71bf35,0xbf5cbf7f,0xbe16bf0e,0x3f2c3e95,0x3f803f6d,0x3f183f62,0xbe793e48,0xbf67bf22,
 0x3e16bec4,0x3f713f22,0x3f3e3f7b,0xbe793e95,0x3f5c3f80,0xbd493ef1,0xbf67bf0e,0xbf4ebf7f,0x3f183f6d,0xbedb3dc9,0xbf80bf55,0xbf04bf62,0xbf78bf35,0xbf2cbf75,0x3eacbe48,0x3f7d3f46,
 0x3f7d3f6d,0x3eac3f46,0xbf2cbe48,0xbf78bf75,0xbf040000,0xbf80bf62,0xbedbbf55,0x3f183dc9,0xbf4ebec4,0xbf67bf7f,0xbd49bf0e,0x3f5c3ef1,0xbe79bf35,0x3f3e3e95,0x3f713f7b,0x3e163f22,
 0x3e163f35,0xbf67bef1,0xbf2cbf7b,0x3f04bdc9,0x3f783f6d,0x3d493f22,0xbf71bf0e,0xbf18bf75,0xbf4ebf80,0x3eacbe95,0x3f803f55,0x3e793f46,0xbf5cbec4,0xbf3ebf7f,0x3edbbe48,0x3f7d3f62,
 0x3f7d3f35,0x3edb3f62,0xbf3ebe48,0xbf5cbf7f,0x3e79bec4,0x3f803f46,0x3eac3f55,0xbf4ebe95,0xbf180000,0xbf71bf75,0x3d49bf0e,0x3f783f22,0x3f043f6d,0xbf2cbdc9,0xbf67bf7b,0x3e16bef1,
 0x3f673ec4,0x3f043f75,0xbf4ebe48,0xbf2cbf7f,0x3f803f35,0x3e163f46,0xbf78bf0e,0xbeacbf62,0x3f713f6d,0xbe793ef1,0xbf7dbf55,0x3d49bf22,0x3f3e3f80,0xbf183dc9,0xbf5cbf7b,0x3edbbe95,
 0x3edb3f6d,0xbf5cbe95,0xbf18bf7b,0x3f3e3dc9,0x3d493f35,0xbf7dbf22,0xbe79bf55,0x3f713ef1,0xbeac3ec4,0xbf78bf62,0x3e16bf0e,0x3f803f46,0xbf2c0000,0xbf4ebf7f,0x3f04be48,0x3f673f75,
 0x3f2c3f80,0xbf4ebdc9,0xbf04bf7b,0x3f673e95,0x3eac3f6d,0xbf78bef1,0xbe16bf55,0x3f803f22,0xbd493f35,0xbf7dbf46,0x3e79bf0e,0x3f713f62,0xbedb3ec4,0xbf5cbf75,0x3f18be48,0x3f3e3f7f,
 0xbf3e0000,0xbf18bf7f,0x3f5c3e48,0x3edb3f75,0xbf71bec4,0xbe79bf62,0x3f7d3f0e,0x3d493f46,0xbf80bf35,0x3e16bf22,0x3f783f55,0xbeac3ef1,0xbf67bf6d,0x3f04be95,0x3f4e3f7b,0xbf2c3dc9,
 0xbf043ec4,0xbf2cbf7f,0x3f673e48,0x3e163f62,0x3f183f80,0xbf71be95,0xbd49bf55,0x3f783f46,0xbe79bf6d,0x3f803f22,0xbeac3f0e,0xbf4ebf75,0xbf7dbf35,0x3edbbef1,0x3f3e3f7b,0xbf5cbdc9,
 0x3f5c3f6d,0xbf3e3dc9,0xbedbbf7b,0x3f7d3ef1,0x3f4e0000,0x3eac3f75,0xbf80bf0e,0x3e79bf22,0xbf78bec4,0x3d49bf46,0x3f713f55,0xbf183e95,0xbe163f35,0xbf67bf62,0x3f2cbe48,0x3f043f7f,
 0x3e79bf35,0x3f3e3f75,0xbf71be48,0x3e16bf46,0x3f4e3f6d,0xbf67bdc9,0x3d49bf55,0x3f5c3f62,0x3f043f80,0xbf80bef1,0x3edbbf0e,0x3f183f7f,0xbf7dbec4,0x3eacbf22,0x3f2c3f7b,0xbf78be95,
 0x3f783f35,0xbf2c3e95,0xbeacbf7b,0x3f7d3f22,0xbf183ec4,0xbedbbf7f,0x3f803f0e,0xbf043ef1,0xbf5c0000,0xbd49bf62,0x3f673f55,0xbf4e3dc9,0xbe16bf6d,0x3f713f46,0xbf3e3e48,0xbe79bf75,
 0xbf80bec4,0x3f18bef1,0x3e793f7b,0xbf67bf46,0x3f713f35,0xbf5c3dc9,0x3e16bf55,0x3f2c3f75,0xbf3ebf6d,0x3f7d3e95,0xbf043f0e,0xbeacbf7f,0x3edb3f80,0xbf78bf22,0x3f4ebe48,0xbd493f62,
 0x3d493f6d,0xbf4ebf62,0x3f783e48,0xbedb3f22,0x3eacbf35,0x3f043f7f,0xbf7dbf0e,0x3f3ebe95,0xbf2c3ec4,0xbe16bf75,0x3f5c3f55,0xbf71bdc9,0x3f670000,0xbe793f46,0xbf18bf7b,0x3f803ef1,
 0xbf710000,0x3f04bf22,0x3e163f7b,0xbf3ebf62,0x3f803ec4,0xbf4e3e95,0x3e79bf55,0x3edb3f7f,0xbf67bf35,0x3f783dc9,0xbf183f0e,0xbd49bf75,0x3f2c3f6d,0xbf7dbef1,0x3f5cbe48,0xbeac3f46,
 0x3eac3f80,0xbf5cbf46,0x3f7d3e48,0xbf2c3ef1,0x3d49bf6d,0x3f183f75,0xbf78bf0e,0x3f67bdc9,0xbedb3f35,0xbe79bf7f,0x3f4e3f55,0xbf80be95,0x3f3ebec4,0xbe163f62,0xbf04bf7b,0x3f713f22,
 0xbf18bf6d,0x3f673f22,0xbf80be48,0x3f5cbe95,0x3f780000,0xbf3e3ef1,0x3eacbf55,0x3e163f7f,0x3f7d3ec4,0xbf713dc9,0x3f2cbf0e,0xbe793f62,0xbf043f35,0x3d49bf75,0x3edb3f7b,0xbf4ebf46,
 0x3f4ebec4,0xbedb3f46,0xbd49bf7b,0x3f043f75,0x3e793f80,0xbf2cbf62,0x3f713f0e,0xbf7dbdc9,0xbe163f6d,0xbeacbf7f,0x3f3e3f55,0xbf78bef1,0xbf5cbf35,0x3f803e95,0xbf673e48,0x3f18bf22,
 0x3f4e3f35,0xbf71bef1,0x3f803e48,0xbf783dc9,0x3f5cbec4,0xbf2c3f22,0x3edbbf55,0xbe163f75,0xbf7d0000,0x3f67be95,0xbf3e3f0e,0x3f04bf46,0xbe793f6d,0xbd49bf7f,0x3eac3f7b,0xbf18bf62,
 0x3f18bf35,0xbeac3f62,0x3d49bf7b,0x3e793f7f,0xbf04bf6d,0x3f3e3f46,0xbf67bf0e,0x3f7d3e95,0x3e163f80,0xbedbbf75,0x3f2c3f55,0xbf5cbf22,0x3f783ec4,0xbf80bdc9,0x3f71be48,0xbf4e3ef1,
 0x3eacbf6d,0xbe793f75,0x3e16bf7b,0xbd493f7f,0x3f2cbf35,0xbf183f46,0x3f04bf55,0xbedb3f62,0x3f67bec4,0xbf5c3ef1,0x3f4ebf0e,0xbf3e3f22,0x3f800000,0xbf7d3dc9,0x3f78be48,0xbf713e95,
 0x3f713ec4,0xbf78be95,0x3f7d3e48,0xbf80bdc9,0x3f3e3f35,0xbf4ebf22,0x3f5c3f0e,0xbf67bef1,0x3edb3f6d,0xbf04bf62,0x3f183f55,0xbf2cbf46,0x3d493f80,0xbe16bf7f,0x3e793f7b,0xbeacbf75,
 0xbf3e0000,0xbf18bf7f,0x3f5c3e48,0x3edb3f75,0xbf71bec4,0xbe79bf62,0x3f7d3f0e,0x3d493f46,0xbf80bf35,0x3e16bf22,0x3f783f55,0xbeac3ef1,0xbf67bf6d,0x3f04be95,0x3f4e3f7b,0xbf2c3dc9,
 0xbf2cbf80,0x3f4e3dc9,0x3f043f7b,0xbf67be95,0xbeacbf6d,0x3f783ef1,0x3e163f55,0xbf80bf22,0x3d49bf35,0x3f7d3f46,0xbe793f0e,0xbf71bf62,0x3edbbec4,0x3f5c3f75,0xbf183e48,0xbf3ebf7f,
 0xbf5cbf6d,0x3f3ebdc9,0x3edb3f7b,0xbf7dbef1,0xbf4e0000,0xbeacbf75,0x3f803f0e,0xbe793f22,0x3f783ec4,0xbd493f46,0xbf71bf55,0x3f18be95,0x3e16bf35,0x3f673f62,0xbf2c3e48,0xbf04bf7f,
 0xbf043ec4,0xbf2cbf7f,0x3f673e48,0x3e163f62,0x3f183f80,0xbf71be95,0xbd49bf55,0x3f783f46,0xbe79bf6d,0x3f803f22,0xbeac3f0e,0xbf4ebf75,0xbf7dbf35,0x3edbbef1,0x3f3e3f7b,0xbf5cbdc9,
 0x3f783f35,0xbf2c3e95,0xbeacbf7b,0x3f7d3f22,0xbf183ec4,0xbedbbf7f,0x3f803f0e,0xbf043ef1,0xbf5c0000,0xbd49bf62,0x3f673f55,0xbf4e3dc9,0xbe16bf6d,0x3f713f46,0xbf3e3e48,0xbe79bf75,
 0xbe793f35,0xbf3ebf75,0x3f713e48,0xbe163f46,0xbf4ebf6d,0x3f673dc9,0xbd493f55,0xbf5cbf62,0xbf04bf80,0x3f803ef1,0xbedb3f0e,0xbf18bf7f,0x3f7d3ec4,0xbeac3f22,0xbf2cbf7b,0x3f783e95,
 0xbd49bf6d,0x3f4e3f62,0xbf78be48,0x3edbbf22,0xbeac3f35,0xbf04bf7f,0x3f7d3f0e,0xbf3e3e95,0x3f2cbec4,0x3e163f75,0xbf5cbf55,0x3f713dc9,0xbf670000,0x3e79bf46,0x3f183f7b,0xbf80bef1,
 0xbf80bec4,0x3f18bef1,0x3e793f7b,0xbf67bf46,0x3f713f35,0xbf5c3dc9,0x3e16bf55,0x3f2c3f75,0xbf3ebf6d,0x3f7d3e95,0xbf043f0e,0xbeacbf7f,0x3edb3f80,0xbf78bf22,0x3f4ebe48,0xbd493f62,
 0xbeacbf80,0x3f5c3f46,0xbf7dbe48,0x3f2cbef1,0xbd493f6d,0xbf18bf75,0x3f783f0e,0xbf673dc9,0x3edbbf35,0x3e793f7f,0xbf4ebf55,0x3f803e95,0xbf3e3ec4,0x3e16bf62,0x3f043f7b,0xbf71bf22,
 0xbf710000,0x3f04bf22,0x3e163f7b,0xbf3ebf62,0x3f803ec4,0xbf4e3e95,0x3e79bf55,0x3edb3f7f,0xbf67bf35,0x3f783dc9,0xbf183f0e,0xbd49bf75,0x3f2c3f6d,0xbf7dbef1,0x3f5cbe48,0xbeac3f46,
 0x3f4ebec4,0xbedb3f46,0xbd49bf7b,0x3f043f75,0x3e793f80,0xbf2cbf62,0x3f713f0e,0xbf7dbdc9,0xbe163f6d,0xbeacbf7f,0x3f3e3f55,0xbf78bef1,0xbf5cbf35,0x3f803e95,0xbf673e48,0x3f18bf22,
 0x3f183f6d,0xbf67bf22,0x3f803e48,0xbf5c3e95,0xbf780000,0x3f3ebef1,0xbeac3f55,0xbe16bf7f,0xbf7dbec4,0x3f71bdc9,0xbf2c3f0e,0x3e79bf62,0x3f04bf35,0xbd493f75,0xbedbbf7b,0x3f4e3f46,
 0xbf183f35,0x3eacbf62,0xbd493f7b,0xbe79bf7f,0x3f043f6d,0xbf3ebf46,0x3f673f0e,0xbf7dbe95,0xbe16bf80,0x3edb3f75,0xbf2cbf55,0x3f5c3f22,0xbf78bec4,0x3f803dc9,0xbf713e48,0x3f4ebef1,
 0x3f4e3f35,0xbf71bef1,0x3f803e48,0xbf783dc9,0x3f5cbec4,0xbf2c3f22,0x3edbbf55,0xbe163f75,0xbf7d0000,0x3f67be95,0xbf3e3f0e,0x3f04bf46,0xbe793f6d,0xbd49bf7f,0x3eac3f7b,0xbf18bf62,
 0x3f713ec4,0xbf78be95,0x3f7d3e48,0xbf80bdc9,0x3f3e3f35,0xbf4ebf22,0x3f5c3f0e,0xbf67bef1,0x3edb3f6d,0xbf04bf62,0x3f183f55,0xbf2cbf46,0x3d493f80,0xbe16bf7f,0x3e793f7b,0xbeacbf75,
 0xbeac3f6d,0x3e79bf75,0xbe163f7b,0x3d49bf7f,0xbf2c3f35,0x3f18bf46,0xbf043f55,0x3edbbf62,0xbf673ec4,0x3f5cbef1,0xbf4e3f0e,0x3f3ebf22,0xbf800000,0x3f7dbdc9,0xbf783e48,0x3f71be95,
 0xbd493f80,0x3e16bf7f,0xbe793f7b,0x3eacbf75,0xbedb3f6d,0x3f04bf62,0xbf183f55,0x3f2cbf46,0xbf3e3f35,0x3f4ebf22,0xbf5c3f0e,0x3f67bef1,0xbf713ec4,0x3f78be95,0xbf7d3e48,0x3f80bdc9,
 0xbf800000,0x3f7d3dc9,0xbf78be48,0x3f713e95,0xbf67bec4,0x3f5c3ef1,0xbf4ebf0e,0x3f3e3f22,0xbf2cbf35,0x3f183f46,0xbf04bf55,0x3edb3f62,0xbeacbf6d,0x3e793f75,0xbe16bf7b,0x3d493f7f,
 0xbf783ec4,0x3f80bdc9,0xbf71be48,0x3f4e3ef1,0xbe163f80,0x3edbbf75,0xbf2c3f55,0x3f5cbf22,0x3f04bf6d,0xbf3e3f46,0x3f67bf0e,0xbf7d3e95,0xbf18bf35,0x3eac3f62,0xbd49bf7b,0xbe793f7f,
 0x3e793f6d,0x3d49bf7f,0xbeac3f7b,0x3f18bf62,0x3f7d0000,0xbf67be95,0x3f3e3f0e,0xbf04bf46,0xbf5cbec4,0x3f2c3f22,0xbedbbf55,0x3e163f75,0xbf4e3f35,0x3f71bef1,0xbf803e48,0x3f783dc9,
 0x3f5cbf35,0xbf803e95,0x3f673e48,0xbf18bf22,0x3e163f6d,0x3eacbf7f,0xbf3e3f55,0x3f78bef1,0xbe793f80,0x3f2cbf62,0xbf713f0e,0x3f7dbdc9,0xbf4ebec4,0x3edb3f46,0x3d49bf7b,0xbf043f75,
 0x3f043f35,0xbd49bf75,0xbedb3f7b,0x3f4ebf46,0xbf7d3ec4,0x3f713dc9,0xbf2cbf0e,0x3e793f62,0xbf780000,0x3f3e3ef1,0xbeacbf55,0xbe163f7f,0x3f18bf6d,0xbf673f22,0x3f80be48,0xbf5cbe95,
 0xbf3ebec4,0x3e163f62,0x3f04bf7b,0xbf713f22,0x3edb3f35,0x3e79bf7f,0xbf4e3f55,0x3f80be95,0xbd49bf6d,0xbf183f75,0x3f78bf0e,0xbf67bdc9,0xbeac3f80,0x3f5cbf46,0xbf7d3e48,0x3f2c3ef1,
 0xbf2c3f6d,0x3f7dbef1,0xbf5cbe48,0x3eac3f46,0x3f67bf35,0xbf783dc9,0x3f183f0e,0x3d49bf75,0xbf803ec4,0x3f4e3e95,0xbe79bf55,0xbedb3f7f,0x3f710000,0xbf04bf22,0xbe163f7b,0x3f3ebf62,
 0xbf670000,0x3e793f46,0x3f18bf7b,0xbf803ef1,0x3f2c3ec4,0x3e16bf75,0xbf5c3f55,0x3f71bdc9,0xbeacbf35,0xbf043f7f,0x3f7dbf0e,0xbf3ebe95,0xbd493f6d,0x3f4ebf62,0xbf783e48,0x3edb3f22,
 0xbedb3f80,0x3f78bf22,0xbf4ebe48,0x3d493f62,0x3f3ebf6d,0xbf7d3e95,0x3f043f0e,0x3eacbf7f,0xbf713f35,0x3f5c3dc9,0xbe16bf55,0xbf2c3f75,0x3f80bec4,0xbf18bef1,0xbe793f7b,0x3f67bf46,
 0x3e16bf6d,0xbf713f46,0x3f3e3e48,0x3e79bf75,0x3f5c0000,0x3d49bf62,0xbf673f55,0x3f4e3dc9,0x3f183ec4,0x3edbbf7f,0xbf803f0e,0x3f043ef1,0xbf783f35,0x3f2c3e95,0x3eacbf7b,0xbf7d3f22,
 0x3f7dbec4,0xbeacbf22,0xbf2c3f7b,0x3f78be95,0xbf043f80,0x3f80bef1,0xbedbbf0e,0xbf183f7f,0xbf4e3f6d,0x3f67bdc9,0xbd49bf55,0xbf5c3f62,0xbe79bf35,0xbf3e3f75,0x3f71be48,0xbe16bf46,
 0x3e163f35,0x3f67bf62,0xbf2cbe48,0xbf043f7f,0x3f78bec4,0xbd49bf46,0xbf713f55,0x3f183e95,0xbf4e0000,0xbeac3f75,0x3f80bf0e,0xbe79bf22,0xbf5c3f6d,0x3f3e3dc9,0x3edbbf7b,0xbf7d3ef1,
 0x3f7dbf35,0xbedbbef1,0xbf3e3f7b,0x3f5cbdc9,0x3e79bf6d,0xbf803f22,0x3eac3f0e,0x3f4ebf75,0xbf183f80,0x3f71be95,0x3d49bf55,0xbf783f46,0x3f043ec4,0x3f2cbf7f,0xbf673e48,0xbe163f62,
 0x3f67bf6d,0xbf04be95,0xbf4e3f7b,0x3f2c3dc9,0x3f80bf35,0xbe16bf22,0xbf783f55,0x3eac3ef1,0x3f71bec4,0x3e79bf62,0xbf7d3f0e,0xbd493f46,0x3f3e0000,0x3f18bf7f,0xbf5c3e48,0xbedb3f75,
 0x3edb3ec4,0x3f5cbf75,0xbf18be48,0xbf3e3f7f,0x3d493f35,0x3f7dbf46,0xbe79bf0e,0xbf713f62,0xbeac3f6d,0x3f78bef1,0x3e16bf55,0xbf803f22,0xbf2c3f80,0x3f4ebdc9,0x3f04bf7b,0xbf673e95,
 0xbf800000,0x3f7d3dc9,0xbf78be48,0x3f713e95,0xbf67bec4,0x3f5c3ef1,0xbf4ebf0e,0x3f3e3f22,0xbf2cbf35,0x3f183f46,0xbf04bf55,0x3edb3f62,0xbeacbf6d,0x3e793f75,0xbe16bf7b,0x3d493f7f,
 0x3d49bf80,0xbe163f7f,0x3e79bf7b,0xbeac3f75,0x3edbbf6d,0xbf043f62,0x3f18bf55,0xbf2c3f46,0x3f3ebf35,0xbf4e3f22,0x3f5cbf0e,0xbf673ef1,0x3f71bec4,0xbf783e95,0x3f7dbe48,0xbf803dc9,
 0xbe79bf6d,0xbd493f7f,0x3eacbf7b,0xbf183f62,0xbf7d0000,0x3f673e95,0xbf3ebf0e,0x3f043f46,0x3f5c3ec4,0xbf2cbf22,0x3edb3f55,0xbe16bf75,0x3f4ebf35,0xbf713ef1,0x3f80be48,0xbf78bdc9,
 0xbf783ec4,0x3f80bdc9,0xbf71be48,0x3f4e3ef1,0xbe163f80,0x3edbbf75,0xbf2c3f55,0x3f5cbf22,0x3f04bf6d,0xbf3e3f46,0x3f67bf0e,0xbf7d3e95,0xbf18bf35,0x3eac3f62,0xbd49bf7b,0xbe793f7f,
 0x3f043f35,0xbd49bf75,0xbedb3f7b,0x3f4ebf46,0xbf7d3ec4,0x3f713dc9,0xbf2cbf0e,0x3e793f62,0xbf780000,0x3f3e3ef1,0xbeacbf55,0xbe163f7f,0x3f18bf6d,0xbf673f22,0x3f80be48,0xbf5cbe95,
 0xbf5c3f35,0x3f80be95,0xbf67be48,0x3f183f22,0xbe16bf6d,0xbeac3f7f,0x3f3ebf55,0xbf783ef1,0x3e79bf80,0xbf2c3f62,0x3f71bf0e,0xbf7d3dc9,0x3f4e3ec4,0xbedbbf46,0xbd493f7b,0x3f04bf75,
 0x3f2cbf6d,0xbf7d3ef1,0x3f5c3e48,0xbeacbf46,0xbf673f35,0x3f78bdc9,0xbf18bf0e,0xbd493f75,0x3f80bec4,0xbf4ebe95,0x3e793f55,0x3edbbf7f,0xbf710000,0x3f043f22,0x3e16bf7b,0xbf3e3f62,
 0xbf3ebec4,0x3e163f62,0x3f04bf7b,0xbf713f22,0x3edb3f35,0x3e79bf7f,0xbf4e3f55,0x3f80be95,0xbd49bf6d,0xbf183f75,0x3f78bf0e,0xbf67bdc9,0xbeac3f80,0x3f5cbf46,0xbf7d3e48,0x3f2c3ef1,
 0x3edbbf80,0xbf783f22,0x3f4e3e48,0xbd49bf62,0xbf3e3f6d,0x3f7dbe95,0xbf04bf0e,0xbeac3f7f,0x3f71bf35,0xbf5cbdc9,0x3e163f55,0x3f2cbf75,0xbf803ec4,0x3f183ef1,0x3e79bf7b,0xbf673f46,
 0xbf670000,0x3e793f46,0x3f18bf7b,0xbf803ef1,0x3f2c3ec4,0x3e16bf75,0xbf5c3f55,0x3f71bdc9,0xbeacbf35,0xbf043f7f,0x3f7dbf0e,0xbf3ebe95,0xbd493f6d,0x3f4ebf62,0xbf783e48,0x3edb3f22,
 0x3f7dbec4,0xbeacbf22,0xbf2c3f7b,0x3f78be95,0xbf043f80,0x3f80bef1,0xbedbbf0e,0xbf183f7f,0xbf4e3f6d,0x3f67bdc9,0xbd49bf55,0xbf5c3f62,0xbe79bf35,0xbf3e3f75,0x3f71be48,0xbe16bf46,
 0xbe163f6d,0x3f71bf46,0xbf3ebe48,0xbe793f75,0xbf5c0000,0xbd493f62,0x3f67bf55,0xbf4ebdc9,0xbf18bec4,0xbedb3f7f,0x3f80bf0e,0xbf04bef1,0x3f78bf35,0xbf2cbe95,0xbeac3f7b,0x3f7dbf22,
 0xbf7d3f35,0x3edb3ef1,0x3f3ebf7b,0xbf5c3dc9,0xbe793f6d,0x3f80bf22,0xbeacbf0e,0xbf4e3f75,0x3f18bf80,0xbf713e95,0xbd493f55,0x3f78bf46,0xbf04bec4,0xbf2c3f7f,0x3f67be48,0x3e16bf62,
 0x3e163f35,0x3f67bf62,0xbf2cbe48,0xbf043f7f,0x3f78bec4,0xbd49bf46,0xbf713f55,0x3f183e95,0xbf4e0000,0xbeac3f75,0x3f80bf0e,0xbe79bf22,0xbf5c3f6d,0x3f3e3dc9,0x3edbbf7b,0xbf7d3ef1,
 0x3edb3ec4,0x3f5cbf75,0xbf18be48,0xbf3e3f7f,0x3d493f35,0x3f7dbf46,0xbe79bf0e,0xbf713f62,0xbeac3f6d,0x3f78bef1,0x3e16bf55,0xbf803f22,0xbf2c3f80,0x3f4ebdc9,0x3f04bf7b,0xbf673e95,
 0xbf673f6d,0x3f043e95,0x3f4ebf7b,0xbf2cbdc9,0xbf803f35,0x3e163f22,0x3f78bf55,0xbeacbef1,0xbf713ec4,0xbe793f62,0x3f7dbf0e,0x3d49bf46,0xbf3e0000,0xbf183f7f,0x3f5cbe48,0x3edbbf75,
 0xbf3e3f80,0x3f183dc9,0x3f5cbf7b,0xbedbbe95,0xbf713f6d,0x3e793ef1,0x3f7dbf55,0xbd49bf22,0xbf803f35,0xbe163f46,0x3f78bf0e,0x3eacbf62,0xbf673ec4,0xbf043f75,0x3f4ebe48,0x3f2cbf7f,
 0xbf2c0000,0xbf4e3f7f,0x3f043e48,0x3f67bf75,0xbeacbec4,0xbf783f62,0x3e163f0e,0x3f80bf46,0x3d49bf35,0xbf7d3f22,0xbe793f55,0x3f71bef1,0x3edbbf6d,0xbf5c3e95,0xbf183f7b,0x3f3ebdc9,
 0xbf5c3ec4,0xbf3e3f7f,0x3edb3e48,0x3f7dbf62,0xbf4e3f80,0x3eac3e95,0x3f80bf55,0x3e79bf46,0x3f78bf6d,0x3d49bf22,0xbf713f0e,0xbf183f75,0x3e16bf35,0xbf673ef1,0xbf2c3f7b,0x3f043dc9,
 0xbf043f6d,0x3f2cbdc9,0x3f67bf7b,0xbe16bef1,0x3f180000,0x3f71bf75,0xbd49bf0e,0xbf783f22,0xbe79bec4,0xbf803f46,0xbeac3f55,0x3f4ebe95,0xbf7d3f35,0xbedb3f62,0x3f3ebe48,0x3f5cbf7f,
 0x3f78bf35,0x3f2cbf75,0xbeacbe48,0xbf7d3f46,0xbf183f6d,0x3edb3dc9,0x3f80bf55,0x3f04bf62,0xbf5c3f80,0x3d493ef1,0x3f67bf0e,0x3f4ebf7f,0xbe16bec4,0xbf713f22,0xbf3e3f7b,0x3e793e95,
 0xbe793f35,0x3f3ebe95,0x3f71bf7b,0x3e16bf22,0xbf4e3ec4,0xbf673f7f,0xbd493f0e,0x3f5cbef1,0xbf040000,0xbf803f62,0xbedb3f55,0x3f18bdc9,0x3f7dbf6d,0x3eacbf46,0xbf2c3e48,0xbf783f75,
 0xbd49bec4,0xbf4e3ef1,0xbf783f7b,0xbedb3f46,0xbeac3f35,0x3f04bdc9,0x3f7dbf55,0x3f3ebf75,0x3f2cbf6d,0xbe16be95,0xbf5c3f0e,0xbf713f7f,0xbf673f80,0xbe793f22,0x3f18be48,0x3f80bf62,
 0xbf803f6d,0xbf183f62,0x3e793e48,0x3f67bf22,0x3f71bf35,0x3f5cbf7f,0x3e16bf0e,0xbf2c3e95,0xbf3e3ec4,0xbf7d3f75,0xbf043f55,0x3eac3dc9,0x3edb0000,0x3f78bf46,0x3f4ebf7b,0x3d49bef1,
 0xbeac0000,0xbf5c3f22,0xbf7d3f7b,0xbf2c3f62,0xbd493ec4,0x3f18be95,0x3f78bf55,0x3f67bf7f,0x3edbbf35,0xbe79bdc9,0xbf4e3f0e,0xbf803f75,0xbf3e3f6d,0xbe163ef1,0x3f04be48,0x3f71bf46,
 0xbf713f80,0xbf043f46,0x3e163e48,0x3f3ebef1,0x3f80bf6d,0x3f4ebf75,0x3e79bf0e,0xbedb3dc9,0xbf673f35,0xbf783f7f,0xbf183f55,0x3d493e95,0x3f2cbec4,0x3f7dbf62,0x3f5cbf7b,0x3eacbf22,
 0x3f4ebf6d,0x3edbbf22,0xbd49be48,0xbf043e95,0x3e790000,0x3f2cbef1,0x3f71bf55,0x3f7dbf7f,0xbe163ec4,0x3eacbdc9,0x3f3ebf0e,0x3f78bf62,0xbf5c3f35,0xbf803f75,0xbf673f7b,0xbf183f46,
 0x3f18bec4,0x3f67bf46,0x3f80bf7b,0x3f5cbf75,0xbf783f80,0xbf3e3f62,0xbeac3f0e,0x3e163dc9,0xbf7d3f6d,0xbf713f7f,0xbf2c3f55,0xbe793ef1,0x3f04bf35,0x3d49be95,0xbedb3e48,0xbf4e3f22,
 0xbf183f35,0xbeac3ef1,0xbd493e48,0x3e79bdc9,0x3f04bec4,0x3f3ebf22,0x3f67bf55,0x3f7dbf75,0xbe160000,0xbedb3e95,0xbf2c3f0e,0xbf5c3f46,0xbf783f6d,0xbf803f7f,0xbf713f7b,0xbf4e3f62,
 0x3f4ebf35,0x3f71bf62,0x3f80bf7b,0x3f78bf7f,0x3f5cbf6d,0x3f2cbf46,0x3edbbf0e,0x3e16be95,0xbf7d3f80,0xbf673f75,0xbf3e3f55,0xbf043f22,0xbe793ec4,0x3d493dc9,0x3eacbe48,0x3f18bef1,
 0x3f71bf6d,0x3f78bf75,0x3f7dbf7b,0x3f80bf7f,0x3f3ebf35,0x3f4ebf46,0x3f5cbf55,0x3f67bf62,0x3edbbec4,0x3f04bef1,0x3f18bf0e,0x3f2cbf22,0x3d490000,0x3e16bdc9,0x3e79be48,0x3eacbe95,
 0xbeac3ec4,0xbe793e95,0xbe163e48,0xbd493dc9,0xbf2c3f35,0xbf183f22,0xbf043f0e,0xbedb3ef1,0xbf673f6d,0xbf5c3f62,0xbf4e3f55,0xbf3e3f46,0xbf803f80,0xbf7d3f7f,0xbf783f7b,0xbf713f75,
 0xbf2c0000,0xbf4e3f7f,0x3f043e48,0x3f67bf75,0xbeacbec4,0xbf783f62,0x3e163f0e,0x3f80bf46,0x3d49bf35,0xbf7d3f22,0xbe793f55,0x3f71bef1,0x3edbbf6d,0xbf5c3e95,0xbf183f7b,0x3f3ebdc9,
 0x3f3ebf80,0xbf18bdc9,0xbf5c3f7b,0x3edb3e95,0x3f71bf6d,0xbe79bef1,0xbf7d3f55,0x3d493f22,0x3f80bf35,0x3e16bf46,0xbf783f0e,0xbeac3f62,0x3f67bec4,0x3f04bf75,0xbf4e3e48,0xbf2c3f7f,
 0x3f04bf6d,0xbf2c3dc9,0xbf673f7b,0x3e163ef1,0xbf180000,0xbf713f75,0x3d493f0e,0x3f78bf22,0x3e793ec4,0x3f80bf46,0x3eacbf55,0xbf4e3e95,0x3f7dbf35,0x3edbbf62,0xbf3e3e48,0xbf5c3f7f,
 0xbf5c3ec4,0xbf3e3f7f,0x3edb3e48,0x3f7dbf62,0xbf4e3f80,0x3eac3e95,0x3f80bf55,0x3e79bf46,0x3f78bf6d,0x3d49bf22,0xbf713f0e,0xbf183f75,0x3e16bf35,0xbf673ef1,0xbf2c3f7b,0x3f043dc9,
 0xbe793f35,0x3f3ebe95,0x3f71bf7b,0x3e16bf22,0xbf4e3ec4,0xbf673f7f,0xbd493f0e,0x3f5cbef1,0xbf040000,0xbf803f62,0xbedb3f55,0x3f18bdc9,0x3f7dbf6d,0x3eacbf46,0xbf2c3e48,0xbf783f75,
 0xbf783f35,0xbf2c3f75,0x3eac3e48,0x3f7dbf46,0x3f18bf6d,0xbedbbdc9,0xbf803f55,0xbf043f62,0x3f5cbf80,0xbd49bef1,0xbf673f0e,0xbf4e3f7f,0x3e163ec4,0x3f71bf22,0x3f3ebf7b,0xbe79be95,
 0x3f80bf6d,0x3f18bf62,0xbe79be48,0xbf673f22,0xbf713f35,0xbf5c3f7f,0xbe163f0e,0x3f2cbe95,0x3f3ebec4,0x3f7dbf75,0x3f04bf55,0xbeacbdc9,0xbedb0000,0xbf783f46,0xbf4e3f7b,0xbd493ef1,
 0xbd49bec4,0xbf4e3ef1,0xbf783f7b,0xbedb3f46,0xbeac3f35,0x3f04bdc9,0x3f7dbf55,0x3f3ebf75,0x3f2cbf6d,0xbe16be95,0xbf5c3f0e,0xbf713f7f,0xbf673f80,0xbe793f22,0x3f18be48,0x3f80bf62,
 0x3f71bf80,0x3f04bf46,0xbe16be48,0xbf3e3ef1,0xbf803f6d,0xbf4e3f75,0xbe793f0e,0x3edbbdc9,0x3f67bf35,0x3f78bf7f,0x3f18bf55,0xbd49be95,0xbf2c3ec4,0xbf7d3f62,0xbf5c3f7b,0xbeac3f22,
 0xbeac0000,0xbf5c3f22,0xbf7d3f7b,0xbf2c3f62,0xbd493ec4,0x3f18be95,0x3f78bf55,0x3f67bf7f,0x3edbbf35,0xbe79bdc9,0xbf4e3f0e,0xbf803f75,0xbf3e3f6d,0xbe163ef1,0x3f04be48,0x3f71bf46,
 0x3f18bec4,0x3f67bf46,0x3f80bf7b,0x3f5cbf75,0xbf783f80,0xbf3e3f62,0xbeac3f0e,0x3e163dc9,0xbf7d3f6d,0xbf713f7f,0xbf2c3f55,0xbe793ef1,0x3f04bf35,0x3d49be95,0xbedb3e48,0xbf4e3f22,
 0xbf4e3f6d,0xbedb3f22,0x3d493e48,0x3f04be95,0xbe790000,0xbf2c3ef1,0xbf713f55,0xbf7d3f7f,0x3e16bec4,0xbeac3dc9,0xbf3e3f0e,0xbf783f62,0x3f5cbf35,0x3f80bf75,0x3f67bf7b,0x3f18bf46,
 0xbf4e3f35,0xbf713f62,0xbf803f7b,0xbf783f7f,0xbf5c3f6d,0xbf2c3f46,0xbedb3f0e,0xbe163e95,0x3f7dbf80,0x3f67bf75,0x3f3ebf55,0x3f04bf22,0x3e79bec4,0xbd49bdc9,0xbeac3e48,0xbf183ef1,
 0xbf183f35,0xbeac3ef1,0xbd493e48,0x3e79bdc9,0x3f04bec4,0x3f3ebf22,0x3f67bf55,0x3f7dbf75,0xbe160000,0xbedb3e95,0xbf2c3f0e,0xbf5c3f46,0xbf783f6d,0xbf803f7f,0xbf713f7b,0xbf4e3f62,
 0xbeac3ec4,0xbe793e95,0xbe163e48,0xbd493dc9,0xbf2c3f35,0xbf183f22,0xbf043f0e,0xbedb3ef1,0xbf673f6d,0xbf5c3f62,0xbf4e3f55,0xbf3e3f46,0xbf803f80,0xbf7d3f7f,0xbf783f7b,0xbf713f75,
 0xbf713f6d,0xbf783f75,0xbf7d3f7b,0xbf803f7f,0xbf3e3f35,0xbf4e3f46,0xbf5c3f55,0xbf673f62,0xbedb3ec4,0xbf043ef1,0xbf183f0e,0xbf2c3f22,0xbd490000,0xbe163dc9,0xbe793e48,0xbeac3e95,
};
__device__ __align__(128) const uint32_t g_Gimg[1792] = {
 0x00003d00,0x00003d00,0x00003d00,0x00003d00,0x00003d00,0x00003d00,0x00003d00,0x00003d00,0x00003d00,0x00003d00,0x00003d00,0x00003d00,0x00003d00,0x00003d00,0x00003d00,0x00003d00,
 0x00003d00,0x00003d00,0x00003d00,0x00003d00,0x00003d00,0x00003d00,0x00003d00,0x00003d00,0x00003d00,0x00003d00,0x00003d00,0x00003d00,0x00003d00,0x00003d00,0x00003d00,0x00003d00,
 0xbc5b3ce7,0xbc843cdc,0xbc983cce,0xbcac3cbe,0xbac93d00,0xbb963cfd,0xbbf93cf8,0xbc2c3cf1,0xbcf13c2c,0xbcf83bf9,0xbcfd3b96,0xbd003ac9,0xbcbe3cac,0xbcce3c98,0xbcdc3c84,0xbce73c5b,
 0xbce7bc5b,0xbcdcbc84,0xbccebc98,0xbcbebcac,0xbd00bac9,0xbcfdbb96,0xbcf8bbf9,0xbcf1bc2c,0xbc2cbcf1,0xbbf9bcf8,0xbb96bcfd,0xbac9bd00,0xbcacbcbe,0xbc98bcce,0xbc84bcdc,0xbc5bbce7,
 0xbcffbb49,0xbcf5bc15,0xbce2bc71,0xbcc6bca2,0xbca2bcc6,0xbc71bce2,0xbc15bcf5,0xbb49bcff,0xbb493cff,0xbc153cf5,0xbc713ce2,0xbca23cc6,0xbcc63ca2,0xbce23c71,0xbcf53c15,0xbcff3b49,
 0x3cff3b49,0x3cf53c15,0x3ce23c71,0x3cc63ca2,0x3ca23cc6,0x3c713ce2,0x3c153cf5,0x3b493cff,0x3b49bcff,0x3c15bcf5,0x3c71bce2,0x3ca2bcc6,0x3cc6bca2,0x3ce2bc71,0x3cf5bc15,0x3cffbb49,
 0x3c84bcdc,0x3cbebcac,0x3ce7bc5b,0x3cfdbb96,0xbc98bcce,0xbc2cbcf1,0xbac9bd00,0x3bf9bcf8,0xbcf83bf9,0xbd00bac9,0xbcf1bc2c,0xbccebc98,0xbb963cfd,0xbc5b3ce7,0xbcac3cbe,0xbcdc3c84,
 0xbcdcbc84,0xbcacbcbe,0xbc5bbce7,0xbb96bcfd,0xbcce3c98,0xbcf13c2c,0xbd003ac9,0xbcf8bbf9,0x3bf93cf8,0xbac93d00,0xbc2c3cf1,0xbc983cce,0x3cfd3b96,0x3ce73c5b,0x3cbe3cac,0x3c843cdc,
 0xbbc83cfb,0xbc8e3cd5,0xbcd53c8e,0xbcfb3bc8,0xbcfbbbc8,0xbcd5bc8e,0xbc8ebcd5,0xbbc8bcfb,0x3bc8bcfb,0x3c8ebcd5,0x3cd5bc8e,0x3cfbbbc8,0x3cfb3bc8,0x3cd53c8e,0x3c8e3cd5,0x3bc83cfb,
 0xbbc83cfb,0xbc8e3cd5,0xbcd53c8e,0xbcfb3bc8,0xbcfbbbc8,0xbcd5bc8e,0xbc8ebcd5,0xbbc8bcfb,0x3bc8bcfb,0x3c8ebcd5,0x3cd5bc8e,0x3cfbbbc8,0x3cfb3bc8,0x3cd53c8e,0x3c8e3cd5,0x3bc83cfb,
 0x3c98bcce,0x3ce7bc5b,0x3d003ac9,0x3cdc3c84,0xbcf8bbf9,0xbcbebcac,0xbc2cbcf1,0x3b96bcfd,0xbcfd3b96,0xbcf1bc2c,0xbcacbcbe,0xbbf9bcf8,0x3c843cdc,0x3ac93d00,0xbc5b3ce7,0xbcce3c98,
 0xbccebc98,0xbc5bbce7,0x3ac9bd00,0x3c84bcdc,0xbbf93cf8,0xbcac3cbe,0xbcf13c2c,0xbcfdbb96,0x3b963cfd,0xbc2c3cf1,0xbcbe3cac,0xbcf83bf9,0x3cdcbc84,0x3d00bac9,0x3ce73c5b,0x3c983cce,
 0xbcf5bc15,0xbca2bcc6,0xbb49bcff,0x3c71bce2,0x3ce2bc71,0x3cff3b49,0x3cc63ca2,0x3c153cf5,0x3c15bcf5,0x3cc6bca2,0x3cffbb49,0x3ce23c71,0x3c713ce2,0xbb493cff,0xbca23cc6,0xbcf53c15,
 0x3cf53c15,0x3ca23cc6,0x3b493cff,0xbc713ce2,0xbce23c71,0xbcffbb49,0xbcc6bca2,0xbc15bcf5,0xbc153cf5,0xbcc63ca2,0xbcff3b49,0xbce2bc71,0xbc71bce2,0x3b49bcff,0x3ca2bcc6,0x3cf5bc15,
 0xbcac3cbe,0xbcfd3b96,0xbcdcbc84,0xbc2cbcf1,0x3ce7bc5b,0x3cf83bf9,0x3c983cce,0xbac93d00,0xbd003ac9,0xbccebc98,0xbbf9bcf8,0x3c5bbce7,0x3cf13c2c,0x3c843cdc,0xbb963cfd,0xbcbe3cac,
 0xbcbebcac,0xbb96bcfd,0x3c84bcdc,0x3cf1bc2c,0x3c5b3ce7,0xbbf93cf8,0xbcce3c98,0xbd00bac9,0xbac9bd00,0x3c98bcce,0x3cf8bbf9,0x3ce73c5b,0xbc2c3cf1,0xbcdc3c84,0xbcfdbb96,0xbcacbcbe,
 0xbc443ced,0xbced3c44,0xbcedbc44,0xbc44bced,0x3c44bced,0x3cedbc44,0x3ced3c44,0x3c443ced,0xbc443ced,0xbced3c44,0xbcedbc44,0xbc44bced,0x3c44bced,0x3cedbc44,0x3ced3c44,0x3c443ced,
 0xbc443ced,0xbced3c44,0xbcedbc44,0xbc44bced,0x3c44bced,0x3cedbc44,0x3ced3c44,0x3c443ced,0xbc443ced,0xbced3c44,0xbcedbc44,0xbc44bced,0x3c44bced,0x3cedbc44,0x3ced3c44,0x3c443ced,
 0x3cbebcac,0x3cfd3b96,0x3c843cdc,0xbc2c3cf1,0xbc5b3ce7,0xbcf83bf9,0xbccebc98,0xbac9bd00,0x3d003ac9,0x3c983cce,0xbbf93cf8,0xbce73c5b,0xbcf13c2c,0xbcdcbc84,0xbb96bcfd,0x3cacbcbe,
 0x3cac3cbe,0xbb963cfd,0xbcdc3c84,0xbcf1bc2c,0xbce7bc5b,0xbbf9bcf8,0x3c98bcce,0x3d00bac9,0xbac93d00,0xbcce3c98,0xbcf8bbf9,0xbc5bbce7,0xbc2cbcf1,0x3c84bcdc,0x3cfdbb96,0x3cbe3cac,
 0xbce2bc71,0xbb49bcff,0x3cc6bca2,0x3cf53c15,0x3c153cf5,0xbca23cc6,0xbcffbb49,0xbc71bce2,0xbc713ce2,0xbcff3b49,0xbca2bcc6,0x3c15bcf5,0x3cf5bc15,0x3cc63ca2,0xbb493cff,0xbce23c71,
 0x3ce23c71,0x3b493cff,0xbcc63ca2,0xbcf5bc15,0xbc15bcf5,0x3ca2bcc6,0x3cff3b49,0x3c713ce2,0x3c71bce2,0x3cffbb49,0x3ca23cc6,0xbc153cf5,0xbcf53c15,0xbcc6bca2,0x3b49bcff,0x3ce2bc71,
 0xbcce3c98,0xbce7bc5b,0xbac9bd00,0x3cdcbc84,0xbbf9bcf8,0x3cbebcac,0x3cf13c2c,0x3b963cfd,0x3cfd3b96,0x3c2c3cf1,0xbcac3cbe,0xbcf8bbf9,0xbc843cdc,0xbd00bac9,0xbc5bbce7,0x3c98bcce,
 0x3c983cce,0xbc5b3ce7,0xbd003ac9,0xbc84bcdc,0xbcf83bf9,0xbcacbcbe,0x3c2cbcf1,0x3cfdbb96,0x3b96bcfd,0x3cf1bc2c,0x3cbe3cac,0xbbf93cf8,0x3cdc3c84,0xbac93d00,0xbce73c5b,0xbccebc98,
 0xbc8e3cd5,0xbcfbbbc8,0xbbc8bcfb,0x3cd5bc8e,0x3cd53c8e,0xbbc83cfb,0xbcfb3bc8,0xbc8ebcd5,0x3c8ebcd5,0x3cfb3bc8,0x3bc83cfb,0xbcd53c8e,0xbcd5bc8e,0x3bc8bcfb,0x3cfbbbc8,0x3c8e3cd5,
 0xbc8e3cd5,0xbcfbbbc8,0xbbc8bcfb,0x3cd5bc8e,0x3cd53c8e,0xbbc83cfb,0xbcfb3bc8,0xbc8ebcd5,0x3c8ebcd5,0x3cfb3bc8,0x3bc83cfb,0xbcd53c8e,0xbcd5bc8e,0x3bc8bcfb,0x3cfbbbc8,0x3c8e3cd5,
 0xbcdc3c84,0xbcbebcac,0x3c5bbce7,0x3cfd3b96,0xbccebc98,0x3c2cbcf1,0x3d003ac9,0x3bf93cf8,0x3cf83bf9,0x3ac93d00,0xbcf13c2c,0xbc98bcce,0x3b963cfd,0xbce73c5b,0xbcacbcbe,0x3c84bcdc,
 0x3c843cdc,0xbcac3cbe,0xbce7bc5b,0x3b96bcfd,0xbc983cce,0xbcf1bc2c,0x3ac9bd00,0x3cf8bbf9,0x3bf9bcf8,0x3d00bac9,0x3c2c3cf1,0xbcce3c98,0x3cfdbb96,0x3c5b3ce7,0xbcbe3cac,0xbcdcbc84,
 0xbcc6bca2,0x3c71bce2,0x3cf53c15,0xbb493cff,0xbcff3b49,0xbc15bcf5,0x3ce2bc71,0x3ca23cc6,0x3ca2bcc6,0x3ce23c71,0xbc153cf5,0xbcffbb49,0xbb49bcff,0x3cf5bc15,0x3c713ce2,0xbcc63ca2,
 0x3cc63ca2,0xbc713ce2,0xbcf5bc15,0x3b49bcff,0x3cffbb49,0x3c153cf5,0xbce23c71,0xbca2bcc6,0xbca23cc6,0xbce2bc71,0x3c15bcf5,0x3cff3b49,0x3b493cff,0xbcf53c15,0xbc71bce2,0x3cc6bca2,
 0x3ce7bc5b,0x3c843cdc,0xbcce3c98,0xbcacbcbe,0x3d00bac9,0x3b963cfd,0xbcf83bf9,0xbc2cbcf1,0x3cf13c2c,0xbbf93cf8,0xbcfdbb96,0x3ac9bd00,0x3cbe3cac,0xbc983cce,0xbcdcbc84,0x3c5bbce7,
 0x3c5b3ce7,0xbcdc3c84,0xbc98bcce,0x3cbebcac,0x3ac93d00,0xbcfd3b96,0xbbf9bcf8,0x3cf1bc2c,0xbc2c3cf1,0xbcf8bbf9,0x3b96bcfd,0x3d003ac9,0xbcac3cbe,0xbccebc98,0x3c84bcdc,0x3ce73c5b,
 0xbcb53cb5,0xbcb5bcb5,0x3cb5bcb5,0x3cb53cb5,0xbcb53cb5,0xbcb5bcb5,0x3cb5bcb5,0x3cb53cb5,0xbcb53cb5,0xbcb5bcb5,0x3cb5bcb5,0x3cb53cb5,0xbcb53cb5,0xbcb5bcb5,0x3cb5bcb5,0x3cb53cb5,
 0xbcb53cb5,0xbcb5bcb5,0x3cb5bcb5,0x3cb53cb5,0xbcb53cb5,0xbcb5bcb5,0x3cb5bcb5,0x3cb53cb5,0xbcb53cb5,0xbcb5bcb5,0x3cb5bcb5,0x3cb53cb5,0xbcb53cb5,0xbcb5bcb5,0x3cb5bcb5,0x3cb53cb5,
 0xbcf13c2c,0xbbf9bcf8,0x3cfdbb96,0x3ac93d00,0xbcbe3cac,0xbc98bcce,0x3cdcbc84,0x3c5b3ce7,0xbce7bc5b,0x3c84bcdc,0x3cce3c98,0xbcac3cbe,0xbd00bac9,0x3b96bcfd,0x3cf83bf9,0xbc2c3cf1,
 0xbc2cbcf1,0x3cf8bbf9,0x3b963cfd,0xbd003ac9,0xbcacbcbe,0x3ccebc98,0x3c843cdc,0xbce73c5b,0x3c5bbce7,0x3cdc3c84,0xbc983cce,0xbcbebcac,0x3ac9bd00,0x3cfd3b96,0xbbf93cf8,0xbcf1bc2c,
 0xbca2bcc6,0x3ce2bc71,0x3c153cf5,0xbcff3b49,0x3b49bcff,0x3cf53c15,0xbc713ce2,0xbcc6bca2,0xbcc63ca2,0xbc71bce2,0x3cf5bc15,0x3b493cff,0xbcffbb49,0x3c15bcf5,0x3ce23c71,0xbca23cc6,
 0x3ca23cc6,0xbce23c71,0xbc15bcf5,0x3cffbb49,0xbb493cff,0xbcf5bc15,0x3c71bce2,0x3cc63ca2,0x3cc6bca2,0x3c713ce2,0xbcf53c15,0xbb49bcff,0x3cff3b49,0xbc153cf5,0xbce2bc71,0x3ca2bcc6,
 0x3cf8bbf9,0xbac93d00,0xbcf1bc2c,0x3c98bcce,0x3b96bcfd,0x3ce73c5b,0xbcac3cbe,0xbc84bcdc,0xbcdcbc84,0x3cbebcac,0x3c5b3ce7,0xbcfd3b96,0xbcce3c98,0xbc2cbcf1,0x3d00bac9,0xbbf93cf8,
 0xbbf9bcf8,0x3d003ac9,0xbc2c3cf1,0xbccebc98,0xbcfdbb96,0x3c5bbce7,0x3cbe3cac,0xbcdc3c84,0xbc843cdc,0xbcacbcbe,0x3ce7bc5b,0x3b963cfd,0x3c983cce,0xbcf13c2c,0xbac9bd00,0x3cf83bf9,
 0xbcd53c8e,0xbbc8bcfb,0x3cfb3bc8,0xbc8e3cd5,0xbc8ebcd5,0x3cfbbbc8,0xbbc83cfb,0xbcd5bc8e,0x3cd5bc8e,0x3bc83cfb,0xbcfbbbc8,0x3c8ebcd5,0x3c8e3cd5,0xbcfb3bc8,0x3bc8bcfb,0x3cd53c8e,
 0xbcd53c8e,0xbbc8bcfb,0x3cfb3bc8,0xbc8e3cd5,0xbc8ebcd5,0x3cfbbbc8,0xbbc83cfb,0xbcd5bc8e,0x3cd5bc8e,0x3bc83cfb,0xbcfbbbc8,0x3c8ebcd5,0x3c8e3cd5,0xbcfb3bc8,0x3bc8bcfb,0x3cd53c8e,
 0x3cfdbb96,0xbc2c3cf1,0xbcacbcbe,0x3cf8bbf9,0xbc84bcdc,0x3d00bac9,0xbc5b3ce7,0xbc98bcce,0xbccebc98,0x3ce7bc5b,0xbac93d00,0xbcdcbc84,0xbbf93cf8,0xbcbebcac,0x3cf1bc2c,0xbb963cfd,
 0xbb96bcfd,0x3cf13c2c,0xbcbe3cac,0xbbf9bcf8,0xbcdc3c84,0xbac9bd00,0x3ce73c5b,0xbcce3c98,0xbc983cce,0xbc5bbce7,0x3d003ac9,0xbc843cdc,0x3cf83bf9,0xbcac3cbe,0xbc2cbcf1,0x3cfd3b96,
 0xbc71bce2,0x3cff3b49,0xbca23cc6,0xbc15bcf5,0x3cf53c15,0xbcc63ca2,0xbb49bcff,0x3ce23c71,0x3ce2bc71,0xbb493cff,0xbcc6bca2,0x3cf5bc15,0xbc153cf5,0xbca2bcc6,0x3cffbb49,0xbc713ce2,
 0x3c713ce2,0xbcffbb49,0x3ca2bcc6,0x3c153cf5,0xbcf5bc15,0x3cc6bca2,0x3b493cff,0xbce2bc71,0xbce23c71,0x3b49bcff,0x3cc63ca2,0xbcf53c15,0x3c15bcf5,0x3ca23cc6,0xbcff3b49,0x3c71bce2,
 0xbd003ac9,0x3c98bcce,0x3bf93cf8,0xbce7bc5b,0x3cf13c2c,0xbcdc3c84,0x3b96bcfd,0x3cac3cbe,0xbcbebcac,0x3cfdbb96,0xbc843cdc,0xbc2cbcf1,0x3c5b3ce7,0xbcf8bbf9,0x3ccebc98,0xbac93d00,
 0xbac9bd00,0x3cce3c98,0xbcf83bf9,0x3c5bbce7,0xbc2c3cf1,0xbc84bcdc,0x3cfd3b96,0xbcbe3cac,0x3cacbcbe,0x3b963cfd,0xbcdcbc84,0x3cf1bc2c,0xbce73c5b,0x3bf9bcf8,0x3c983cce,0xbd00bac9,
 0xbced3c44,0x3c44bced,0x3c443ced,0xbcedbc44,0x3cedbc44,0xbc443ced,0xbc44bced,0x3ced3c44,0xbced3c44,0x3c44bced,0x3c443ced,0xbcedbc44,0x3cedbc44,0xbc443ced,0xbc44bced,0x3ced3c44,
 0xbced3c44,0x3c44bced,0x3c443ced,0xbcedbc44,0x3cedbc44,0xbc443ced,0xbc44bced,0x3ced3c44,0xbced3c44,0x3c44bced,0x3c443ced,0xbcedbc44,0x3cedbc44,0xbc443ced,0xbc44bced,0x3ced3c44,
 0x3d003ac9,0xbcce3c98,0x3bf9bcf8,0x3c5b3ce7,0xbcf13c2c,0x3c84bcdc,0x3b963cfd,0xbcbebcac,0x3cac3cbe,0xbcfdbb96,0x3cdcbc84,0xbc2c3cf1,0xbce7bc5b,0x3cf8bbf9,0xbc983cce,0xbac9bd00,
 0xbac93d00,0xbc98bcce,0x3cf83bf9,0xbce73c5b,0xbc2cbcf1,0x3cdc3c84,0xbcfd3b96,0x3cacbcbe,0xbcbe3cac,0x3b96bcfd,0x3c843cdc,0xbcf1bc2c,0x3c5bbce7,0x3bf93cf8,0xbccebc98,0x3d00bac9,
 0xbc15bcf5,0x3cc63ca2,0xbcffbb49,0x3ce2bc71,0xbc713ce2,0xbb49bcff,0x3ca23cc6,0xbcf5bc15,0xbcf53c15,0x3ca2bcc6,0xbb493cff,0xbc71bce2,0x3ce23c71,0xbcff3b49,0x3cc6bca2,0xbc153cf5,
 0x3c153cf5,0xbcc6bca2,0x3cff3b49,0xbce23c71,0x3c71bce2,0x3b493cff,0xbca2bcc6,0x3cf53c15,0x3cf5bc15,0xbca23cc6,0x3b49bcff,0x3c713ce2,0xbce2bc71,0x3cffbb49,0xbcc63ca2,0x3c15bcf5,
 0xbcfdbb96,0x3cf1bc2c,0xbcac3cbe,0x3bf9bcf8,0x3c84bcdc,0xbac93d00,0xbc5bbce7,0x3cce3c98,0x3c983cce,0xbce7bc5b,0x3d00bac9,0xbcdc3c84,0xbcf83bf9,0x3cbebcac,0xbc2c3cf1,0xbb96bcfd,
 0xbb963cfd,0xbc2cbcf1,0x3cbe3cac,0xbcf8bbf9,0xbcdcbc84,0x3d003ac9,0xbce73c5b,0x3c98bcce,0x3ccebc98,0xbc5b3ce7,0xbac9bd00,0x3c843cdc,0x3bf93cf8,0xbcacbcbe,0x3cf13c2c,0xbcfd3b96,
 0xbcfb3bc8,0x3cd5bc8e,0xbc8e3cd5,0x3bc8bcfb,0x3bc83cfb,0xbc8ebcd5,0x3cd53c8e,0xbcfbbbc8,0x3cfbbbc8,0xbcd53c8e,0x3c8ebcd5,0xbbc83cfb,0xbbc8bcfb,0x3c8e3cd5,0xbcd5bc8e,0x3cfb3bc8,
 0xbcfb3bc8,0x3cd5bc8e,0xbc8e3cd5,0x3bc8bcfb,0x3bc83cfb,0xbc8ebcd5,0x3cd53c8e,0xbcfbbbc8,0x3cfbbbc8,0xbcd53c8e,0x3c8ebcd5,0xbbc83cfb,0xbbc8bcfb,0x3c8e3cd5,0xbcd5bc8e,0x3cfb3bc8,
 0xbcf8bbf9,0x3d00bac9,0xbcf13c2c,0x3ccebc98,0xbb96bcfd,0x3c5b3ce7,0xbcacbcbe,0x3cdc3c84,0x3c843cdc,0xbcbebcac,0x3ce73c5b,0xbcfdbb96,0xbc983cce,0x3c2cbcf1,0xbac93d00,0xbbf9bcf8,
 0xbbf93cf8,0xbac9bd00,0x3c2c3cf1,0xbc98bcce,0xbcfd3b96,0x3ce7bc5b,0xbcbe3cac,0x3c84bcdc,0x3cdcbc84,0xbcac3cbe,0x3c5bbce7,0xbb963cfd,0x3cce3c98,0xbcf1bc2c,0x3d003ac9,0xbcf83bf9,
 0xbb49bcff,0x3c153cf5,0xbc71bce2,0x3ca23cc6,0xbcc6bca2,0x3ce23c71,0xbcf5bc15,0x3cff3b49,0x3cffbb49,0xbcf53c15,0x3ce2bc71,0xbcc63ca2,0x3ca2bcc6,0xbc713ce2,0x3c15bcf5,0xbb493cff,
 0x3b493cff,0xbc15bcf5,0x3c713ce2,0xbca2bcc6,0x3cc63ca2,0xbce2bc71,0x3cf53c15,0xbcffbb49,0xbcff3b49,0x3cf5bc15,0xbce23c71,0x3cc6bca2,0xbca23cc6,0x3c71bce2,0xbc153cf5,0x3b49bcff,
 0x3cf13c2c,0xbcf8bbf9,0x3cfd3b96,0xbd00bac9,0x3cbe3cac,0xbccebc98,0x3cdc3c84,0xbce7bc5b,0x3c5b3ce7,0xbc84bcdc,0x3c983cce,0xbcacbcbe,0x3ac93d00,0xbb96bcfd,0x3bf93cf8,0xbc2cbcf1,
 0xbc2c3cf1,0x3bf9bcf8,0xbb963cfd,0x3ac9bd00,0xbcac3cbe,0x3c98bcce,0xbc843cdc,0x3c5bbce7,0xbce73c5b,0x3cdcbc84,0xbcce3c98,0x3cbebcac,0xbd003ac9,0x3cfdbb96,0xbcf83bf9,0x3cf1bc2c,
 0xbd000000,0x3d000000,0xbd000000,0x3d000000,0xbd000000,0x3d000000,0xbd000000,0x3d000000,0xbd000000,0x3d000000,0xbd000000,0x3d000000,0xbd000000,0x3d000000,0xbd000000,0x3d000000,
 0xbd000000,0x3d000000,0xbd000000,0x3d000000,0xbd000000,0x3d000000,0xbd000000,0x3d000000,0xbd000000,0x3d000000,0xbd000000,0x3d000000,0xbd000000,0x3d000000,0xbd000000,0x3d000000,
 0xbce7bc5b,0x3cdc3c84,0xbccebc98,0x3cbe3cac,0xbd00bac9,0x3cfd3b96,0xbcf8bbf9,0x3cf13c2c,0xbc2cbcf1,0x3bf93cf8,0xbb96bcfd,0x3ac93d00,0xbcacbcbe,0x3c983cce,0xbc84bcdc,0x3c5b3ce7,
 0x3c5bbce7,0xbc843cdc,0x3c98bcce,0xbcac3cbe,0x3ac9bd00,0xbb963cfd,0x3bf9bcf8,0xbc2c3cf1,0x3cf1bc2c,0xbcf83bf9,0x3cfdbb96,0xbd003ac9,0x3cbebcac,0xbcce3c98,0x3cdcbc84,0xbce73c5b,
 0x3b49bcff,0xbc153cf5,0x3c71bce2,0xbca23cc6,0x3cc6bca2,0xbce23c71,0x3cf5bc15,0xbcff3b49,0xbcffbb49,0x3cf53c15,0xbce2bc71,0x3cc63ca2,0xbca2bcc6,0x3c713ce2,0xbc15bcf5,0x3b493cff,
 0xbb493cff,0x3c15bcf5,0xbc713ce2,0x3ca2bcc6,0xbcc63ca2,0x3ce2bc71,0xbcf53c15,0x3cffbb49,0x3cff3b49,0xbcf5bc15,0x3ce23c71,0xbcc6bca2,0x3ca23cc6,0xbc71bce2,0x3c153cf5,0xbb49bcff,
 0x3cdc3c84,0xbcacbcbe,0x3c5b3ce7,0xbb96bcfd,0x3ccebc98,0xbcf13c2c,0x3d00bac9,0xbcf8bbf9,0xbbf9bcf8,0xbac93d00,0x3c2cbcf1,0xbc983cce,0xbcfdbb96,0x3ce73c5b,0xbcbebcac,0x3c843cdc,
 0x3c84bcdc,0xbcbe3cac,0x3ce7bc5b,0xbcfd3b96,0xbc98bcce,0x3c2c3cf1,0xbac9bd00,0xbbf93cf8,0xbcf83bf9,0x3d003ac9,0xbcf1bc2c,0x3cce3c98,0xbb963cfd,0x3c5bbce7,0xbcac3cbe,0x3cdcbc84,
 0xbcfbbbc8,0x3cd53c8e,0xbc8ebcd5,0x3bc83cfb,0x3bc8bcfb,0xbc8e3cd5,0x3cd5bc8e,0xbcfb3bc8,0x3cfb3bc8,0xbcd5bc8e,0x3c8e3cd5,0xbbc8bcfb,0xbbc83cfb,0x3c8ebcd5,0xbcd53c8e,0x3cfbbbc8,
 0xbcfbbbc8,0x3cd53c8e,0xbc8ebcd5,0x3bc83cfb,0x3bc8bcfb,0xbc8e3cd5,0x3cd5bc8e,0xbcfb3bc8,0x3cfb3bc8,0xbcd5bc8e,0x3c8e3cd5,0xbbc8bcfb,0xbbc83cfb,0x3c8ebcd5,0xbcd53c8e,0x3cfbbbc8,
 0x3cce3c98,0xbc5bbce7,0xbac93d00,0x3c84bcdc,0x3bf9bcf8,0xbcac3cbe,0x3cf1bc2c,0xbcfdbb96,0xbb96bcfd,0xbc2c3cf1,0x3cbebcac,0xbcf83bf9,0xbcdc3c84,0x3d00bac9,0xbce7bc5b,0x3c983cce,
 0x3c98bcce,0xbce73c5b,0x3d003ac9,0xbcdcbc84,0xbcf8bbf9,0x3cbe3cac,0xbc2cbcf1,0xbb963cfd,0xbcfd3b96,0x3cf13c2c,0xbcacbcbe,0x3bf93cf8,0x3c843cdc,0xbac9bd00,0xbc5b3ce7,0x3ccebc98,
 0x3c15bcf5,0xbcc63ca2,0x3cffbb49,0xbce2bc71,0x3c713ce2,0x3b49bcff,0xbca23cc6,0x3cf5bc15,0x3cf53c15,0xbca2bcc6,0x3b493cff,0x3c71bce2,0xbce23c71,0x3cff3b49,0xbcc6bca2,0x3c153cf5,
 0xbc153cf5,0x3cc6bca2,0xbcff3b49,0x3ce23c71,0xbc71bce2,0xbb493cff,0x3ca2bcc6,0xbcf53c15,0xbcf5bc15,0x3ca23cc6,0xbb49bcff,0xbc713ce2,0x3ce2bc71,0xbcffbb49,0x3cc63ca2,0xbc15bcf5,
 0xbcbebcac,0x3b963cfd,0x3c84bcdc,0xbcf13c2c,0x3c5b3ce7,0x3bf9bcf8,0xbcce3c98,0x3d003ac9,0xbac9bd00,0xbc983cce,0x3cf8bbf9,0xbce7bc5b,0xbc2c3cf1,0x3cdcbc84,0xbcfdbb96,0x3cac3cbe,
 0x3cacbcbe,0xbcfd3b96,0x3cdc3c84,0xbc2cbcf1,0xbce73c5b,0x3cf83bf9,0xbc98bcce,0xbac93d00,0x3d00bac9,0xbccebc98,0x3bf93cf8,0x3c5bbce7,0xbcf1bc2c,0x3c843cdc,0x3b96bcfd,0xbcbe3cac,
 0xbcedbc44,0x3c443ced,0x3c44bced,0xbced3c44,0x3ced3c44,0xbc44bced,0xbc443ced,0x3cedbc44,0xbcedbc44,0x3c443ced,0x3c44bced,0xbced3c44,0x3ced3c44,0xbc44bced,0xbc443ced,0x3cedbc44,
 0xbcedbc44,0x3c443ced,0x3c44bced,0xbced3c44,0x3ced3c44,0xbc44bced,0xbc443ced,0x3cedbc44,0xbcedbc44,0x3c443ced,0x3c44bced,0xbced3c44,0x3ced3c44,0xbc44bced,0xbc443ced,0x3cedbc44,
 0x3cac3cbe,0x3b96bcfd,0xbcdc3c84,0x3cf13c2c,0xbce7bc5b,0x3bf93cf8,0x3c98bcce,0xbd003ac9,0xbac93d00,0x3ccebc98,0xbcf8bbf9,0x3c5b3ce7,0xbc2cbcf1,0xbc843cdc,0x3cfdbb96,0xbcbebcac,
 0xbcbe3cac,0x3cfd3b96,0xbc84bcdc,0xbc2c3cf1,0x3c5bbce7,0xbcf83bf9,0x3cce3c98,0xbac9bd00,0xbd00bac9,0x3c983cce,0x3bf9bcf8,0xbce73c5b,0x3cf1bc2c,0xbcdcbc84,0x3b963cfd,0x3cacbcbe,
 0x3c71bce2,0xbcff3b49,0x3ca23cc6,0x3c15bcf5,0xbcf53c15,0x3cc63ca2,0x3b49bcff,0xbce23c71,0xbce2bc71,0x3b493cff,0x3cc6bca2,0xbcf5bc15,0x3c153cf5,0x3ca2bcc6,0xbcffbb49,0x3c713ce2,
 0xbc713ce2,0x3cffbb49,0xbca2bcc6,0xbc153cf5,0x3cf5bc15,0xbcc6bca2,0xbb493cff,0x3ce2bc71,0x3ce23c71,0xbb49bcff,0xbcc63ca2,0x3cf53c15,0xbc15bcf5,0xbca23cc6,0x3cff3b49,0xbc71bce2,
 0xbc98bcce,0xbc5b3ce7,0x3d00bac9,0xbc84bcdc,0x3cf8bbf9,0xbcacbcbe,0xbc2c3cf1,0x3cfdbb96,0xbb963cfd,0x3cf1bc2c,0xbcbebcac,0xbbf93cf8,0xbcdcbc84,0xbac93d00,0x3ce7bc5b,0xbccebc98,
 0xbcce3c98,0x3ce73c5b,0xbac9bd00,0xbcdc3c84,0xbbf9bcf8,0xbcbe3cac,0x3cf13c2c,0xbb96bcfd,0x3cfd3b96,0xbc2cbcf1,0xbcac3cbe,0x3cf83bf9,0xbc843cdc,0x3d003ac9,0xbc5bbce7,0xbc983cce,
 0xbcd5bc8e,0xbbc83cfb,0x3cfbbbc8,0xbc8ebcd5,0xbc8e3cd5,0x3cfb3bc8,0xbbc8bcfb,0xbcd53c8e,0x3cd53c8e,0x3bc8bcfb,0xbcfb3bc8,0x3c8e3cd5,0x3c8ebcd5,0xbcfbbbc8,0x3bc83cfb,0x3cd5bc8e,
 0xbcd5bc8e,0xbbc83cfb,0x3cfbbbc8,0xbc8ebcd5,0xbc8e3cd5,0x3cfb3bc8,0xbbc8bcfb,0xbcd53c8e,0x3cd53c8e,0x3bc8bcfb,0xbcfb3bc8,0x3c8e3cd5,0x3c8ebcd5,0xbcfbbbc8,0x3bc83cfb,0x3cd5bc8e,
 0xbc84bcdc,0xbcac3cbe,0x3ce73c5b,0x3b96bcfd,0x3c98bcce,0xbcf1bc2c,0xbac93d00,0x3cf8bbf9,0xbbf93cf8,0x3d00bac9,0xbc2cbcf1,0xbcce3c98,0xbcfd3b96,0x3c5b3ce7,0x3cbebcac,0xbcdcbc84,
 0xbcdc3c84,0x3cbe3cac,0x3c5bbce7,0xbcfdbb96,0xbccebc98,0xbc2c3cf1,0x3d003ac9,0xbbf9bcf8,0x3cf83bf9,0xbac9bd00,0xbcf13c2c,0x3c983cce,0x3b963cfd,0x3ce7bc5b,0xbcacbcbe,0xbc843cdc,
 0x3ca2bcc6,0xbce2bc71,0xbc153cf5,0x3cff3b49,0xbb49bcff,0xbcf53c15,0x3c713ce2,0x3cc6bca2,0x3cc63ca2,0x3c71bce2,0xbcf5bc15,0xbb493cff,0x3cffbb49,0xbc15bcf5,0xbce23c71,0x3ca23cc6,
 0xbca23cc6,0x3ce23c71,0x3c15bcf5,0xbcffbb49,0x3b493cff,0x3cf5bc15,0xbc71bce2,0xbcc63ca2,0xbcc6bca2,0xbc713ce2,0x3cf53c15,0x3b49bcff,0xbcff3b49,0x3c153cf5,0x3ce2bc71,0xbca2bcc6,
 0x3c5b3ce7,0x3cdcbc84,0xbc98bcce,0xbcbe3cac,0x3ac93d00,0x3cfdbb96,0xbbf9bcf8,0xbcf13c2c,0xbc2c3cf1,0x3cf83bf9,0x3b96bcfd,0xbd00bac9,0xbcac3cbe,0x3cce3c98,0x3c84bcdc,0xbce7bc5b,
 0xbce73c5b,0x3c843cdc,0x3ccebc98,0xbcacbcbe,0xbd003ac9,0x3b963cfd,0x3cf8bbf9,0xbc2cbcf1,0xbcf1bc2c,0xbbf93cf8,0x3cfd3b96,0x3ac9bd00,0xbcbebcac,0xbc983cce,0x3cdc3c84,0x3c5bbce7,
 0xbcb5bcb5,0xbcb53cb5,0x3cb53cb5,0x3cb5bcb5,0xbcb5bcb5,0xbcb53cb5,0x3cb53cb5,0x3cb5bcb5,0xbcb5bcb5,0xbcb53cb5,0x3cb53cb5,0x3cb5bcb5,0xbcb5bcb5,0xbcb53cb5,0x3cb53cb5,0x3cb5bcb5,
 0xbcb5bcb5,0xbcb53cb5,0x3cb53cb5,0x3cb5bcb5,0xbcb5bcb5,0xbcb53cb5,0x3cb53cb5,0x3cb5bcb5,0xbcb5bcb5,0xbcb53cb5,0x3cb53cb5,0x3cb5bcb5,0xbcb5bcb5,0xbcb53cb5,0x3cb53cb5,0x3cb5bcb5,
 0xbc2cbcf1,0xbcf83bf9,0x3b963cfd,0x3d00bac9,0xbcacbcbe,0xbcce3c98,0x3c843cdc,0x3ce7bc5b,0x3c5bbce7,0xbcdcbc84,0xbc983cce,0x3cbe3cac,0x3ac9bd00,0xbcfdbb96,0xbbf93cf8,0x3cf13c2c,
 0x3cf1bc2c,0xbbf9bcf8,0xbcfd3b96,0x3ac93d00,0x3cbebcac,0xbc98bcce,0xbcdc3c84,0x3c5b3ce7,0x3ce73c5b,0x3c84bcdc,0xbccebc98,0xbcac3cbe,0x3d003ac9,0x3b96bcfd,0xbcf8bbf9,0xbc2c3cf1,
 0x00000000,0x00000000,0x00000000,0x00000000,0x00000000,0x00000000,0x00000000,0x00000000,0x00000000,0x00000000,0x00000000,0x00000000,0x00000000,0x00000000,0x00000000,0x00000000,
 0x00000000,0x00000000,0x00000000,0x00000000,0x00000000,0x00000000,0x00000000,0x00000000,0x00000000,0x00000000,0x00000000,0x00000000,0x00000000,0x00000000,0x00000000,0x00000000,
 0x00000000,0x00000000,0x00000000,0x00000000,0x00000000,0x00000000,0x00000000,0x00000000,0x00000000,0x00000000,0x00000000,0x00000000,0x00000000,0x00000000,0x00000000,0x00000000,
 0x00000000,0x00000000,0x00000000,0x00000000,0x00000000,0x00000000,0x00000000,0x00000000,0x00000000,0x00000000,0x00000000,0x00000000,0x00000000,0x00000000,0x00000000,0x00000000,
 0x00000000,0x00000000,0x00000000,0x00000000,0x00000000,0x00000000,0x00000000,0x00000000,0x00000000,0x00000000,0x00000000,0x00000000,0x00000000,0x00000000,0x00000000,0x00000000,
 0x00000000,0x00000000,0x00000000,0x00000000,0x00000000,0x00000000,0x00000000,0x00000000,0x00000000,0x00000000,0x00000000,0x00000000,0x00000000,0x00000000,0x00000000,0x00000000,
 0x00000000,0x00000000,0x00000000,0x00000000,0x00000000,0x00000000,0x00000000,0x00000000,0x00000000,0x00000000,0x00000000,0x00000000,0x00000000,0x00000000,0x00000000,0x00000000,
 0x00000000,0x00000000,0x00000000,0x00000000,0x00000000,0x00000000,0x00000000,0x00000000,0x00000000,0x00000000,0x00000000,0x00000000,0x00000000,0x00000000,0x00000000,0x00000000,
 0x00000000,0x00000000,0x00000000,0x00000000,0x00000000,0x00000000,0x00000000,0x00000000,0x00000000,0x00000000,0x00000000,0x00000000,0x00000000,0x00000000,0x00000000,0x00000000,
 0x00000000,0x00000000,0x00000000,0x00000000,0x00000000,0x00000000,0x00000000,0x00000000,0x00000000,0x00000000,0x00000000,0x00000000,0x00000000,0x00000000,0x00000000,0x00000000,
 0x00000000,0x00000000,0x00000000,0x00000000,0x00000000,0x00000000,0x00000000,0x00000000,0x00000000,0x00000000,0x00000000,0x00000000,0x00000000,0x00000000,0x00000000,0x00000000,
 0x00000000,0x00000000,0x00000000,0x00000000,0x00000000,0x00000000,0x00000000,0x00000000,0x00000000,0x00000000,0x00000000,0x00000000,0x00000000,0x00000000,0x00000000,0x00000000,
};

template<int SA>
__device__ __forceinline__ void wgmma_main(float (&d)[80], uint64_t da, uint64_t db, int sd) {
  asm volatile("{\n.reg .pred p;\nsetp.ne.b32 p, %82, 0;\n"
    "wgmma.mma_async.sync.aligned.m64n160k16.f32.bf16.bf16 "
    "{%0, %1, %2, %3, %4, %5, %6, %7, %8, %9, %10, %11, %12, %13, %14, %15, %16, %17, %18, %19, %20, %21, %22, %23, %24, %25, %26, %27, %28, %29, %30, %31, %32, %33, %34, %35, %36, %37, %38, %39, %40, %41, %42, %43, %44, %45, %46, %47, %48, %49, %50, %51, %52, %53, %54, %55, %56, %57, %58, %59, %60, %61, %62, %63, %64, %65, %66, %67, %68, %69, %70, %71, %72, %73, %74, %75, %76, %77, %78, %79}, %80, %81, p, %83, 1, 1, 0;\n}\n"
    : "+f"(d[0]), "+f"(d[1]), "+f"(d[2]), "+f"(d[3]), "+f"(d[4]), "+f"(d[5]), "+f"(d[6]), "+f"(d[7]), "+f"(d[8]), "+f"(d[9]), "+f"(d[10]), "+f"(d[11]), "+f"(d[12]), "+f"(d[13]), "+f"(d[14]), "+f"(d[15]), "+f"(d[16]), "+f"(d[17]), "+f"(d[18]), "+f"(d[19]), "+f"(d[20]), "+f"(d[21]), "+f"(d[22]), "+f"(d[23]), "+f"(d[24]), "+f"(d[25]), "+f"(d[26]), "+f"(d[27]), "+f"(d[28]), "+f"(d[29]), "+f"(d[30]), "+f"(d[31]), "+f"(d[32]), "+f"(d[33]), "+f"(d[34]), "+f"(d[35]), "+f"(d[36]), "+f"(d[37]), "+f"(d[38]), "+f"(d[39]), "+f"(d[40]), "+f"(d[41]), "+f"(d[42]), "+f"(d[43]), "+f"(d[44]), "+f"(d[45]), "+f"(d[46]), "+f"(d[47]), "+f"(d[48]), "+f"(d[49]), "+f"(d[50]), "+f"(d[51]), "+f"(d[52]), "+f"(d[53]), "+f"(d[54]), "+f"(d[55]), "+f"(d[56]), "+f"(d[57]), "+f"(d[58]), "+f"(d[59]), "+f"(d[60]), "+f"(d[61]), "+f"(d[62]), "+f"(d[63]), "+f"(d[64]), "+f"(d[65]), "+f"(d[66]), "+f"(d[67]), "+f"(d[68]), "+f"(d[69]), "+f"(d[70]), "+f"(d[71]), "+f"(d[72]), "+f"(d[73]), "+f"(d[74]), "+f"(d[75]), "+f"(d[76]), "+f"(d[77]), "+f"(d[78]), "+f"(d[79])
    : "l"(da), "l"(db), "r"(sd), "n"(SA));
}
template<int SA>
__device__ __forceinline__ void wgmma_fwd(float (&d)[32], uint64_t da, uint64_t db, int sd) {
  asm volatile("{\n.reg .pred p;\nsetp.ne.b32 p, %34, 0;\n"
    "wgmma.mma_async.sync.aligned.m64n64k16.f32.bf16.bf16 "
    "{%0, %1, %2, %3, %4, %5, %6, %7, %8, %9, %10, %11, %12, %13, %14, %15, %16, %17, %18, %19, %20, %21, %22, %23, %24, %25, %26, %27, %28, %29, %30, %31}, %32, %33, p, %35, 1, 0, 1;\n}\n"
    : "+f"(d[0]), "+f"(d[1]), "+f"(d[2]), "+f"(d[3]), "+f"(d[4]), "+f"(d[5]), "+f"(d[6]), "+f"(d[7]), "+f"(d[8]), "+f"(d[9]), "+f"(d[10]), "+f"(d[11]), "+f"(d[12]), "+f"(d[13]), "+f"(d[14]), "+f"(d[15]), "+f"(d[16]), "+f"(d[17]), "+f"(d[18]), "+f"(d[19]), "+f"(d[20]), "+f"(d[21]), "+f"(d[22]), "+f"(d[23]), "+f"(d[24]), "+f"(d[25]), "+f"(d[26]), "+f"(d[27]), "+f"(d[28]), "+f"(d[29]), "+f"(d[30]), "+f"(d[31])
    : "l"(da), "l"(db), "r"(sd), "n"(SA));
}
template<int SA>
__device__ __forceinline__ void wgmma_inv(float (&d)[28], uint64_t da, uint64_t db, int sd) {
  asm volatile("{\n.reg .pred p;\nsetp.ne.b32 p, %30, 0;\n"
    "wgmma.mma_async.sync.aligned.m64n56k16.f32.bf16.bf16 "
    "{%0, %1, %2, %3, %4, %5, %6, %7, %8, %9, %10, %11, %12, %13, %14, %15, %16, %17, %18, %19, %20, %21, %22, %23, %24, %25, %26, %27}, %28, %29, p, %31, 1, 1, 0;\n}\n"
    : "+f"(d[0]), "+f"(d[1]), "+f"(d[2]), "+f"(d[3]), "+f"(d[4]), "+f"(d[5]), "+f"(d[6]), "+f"(d[7]), "+f"(d[8]), "+f"(d[9]), "+f"(d[10]), "+f"(d[11]), "+f"(d[12]), "+f"(d[13]), "+f"(d[14]), "+f"(d[15]), "+f"(d[16]), "+f"(d[17]), "+f"(d[18]), "+f"(d[19]), "+f"(d[20]), "+f"(d[21]), "+f"(d[22]), "+f"(d[23]), "+f"(d[24]), "+f"(d[25]), "+f"(d[26]), "+f"(d[27])
    : "l"(da), "l"(db), "r"(sd), "n"(SA));
}

__device__ __forceinline__ uint32_t s2u(const void* p) { return (uint32_t)__cvta_generic_to_shared(p); }
__device__ __forceinline__ void mbar_init(uint32_t a, int c) { asm volatile("mbarrier.init.shared::cta.b64 [%0], %1;" ::"r"(a), "r"(c)); }
__device__ __forceinline__ void mbar_expect(uint32_t a, int b) { asm volatile("mbarrier.arrive.expect_tx.shared::cta.b64 _, [%0], %1;" ::"r"(a), "r"(b) : "memory"); }
__device__ __forceinline__ void mbar_arrive(uint32_t a) { asm volatile("mbarrier.arrive.shared::cta.b64 _, [%0];" ::"r"(a) : "memory"); }
__device__ __forceinline__ void mbar_arrive_cluster(uint32_t a, uint32_t cta, uint32_t cnt) {
  asm volatile("{\n.reg .b32 r;\nmapa.shared::cluster.u32 r, %0, %1;\nmbarrier.arrive.shared::cluster.b64 _, [r], %2;\n}" ::"r"(a), "r"(cta), "r"(cnt) : "memory");
}
__device__ __forceinline__ void mbar_wait(uint32_t a, int ph) {
  asm volatile("{\n.reg .pred p;\n.reg .u32 c;\nmov.u32 c, 0;\nWAIT:\n"
               "mbarrier.try_wait.parity.shared::cta.b64 p, [%0], %1;\n@p bra DONE;\n"
               "add.u32 c, c, 1;\nsetp.lt.u32 p, c, 0x400000;\n@p bra WAIT;\ntrap;\nDONE:\n}" ::"r"(a), "r"(ph) : "memory");
}
__device__ __forceinline__ void flag_wait(const unsigned* p, unsigned target) {
  asm volatile("{\n.reg .pred p;\n.reg .u32 c, v;\nmov.u32 c, 0;\nWAIT:\n"
               "ld.acquire.gpu.global.u32 v, [%0];\nsetp.ge.u32 p, v, %1;\n@p bra DONE;\n"
               "add.u32 c, c, 1;\nsetp.lt.u32 p, c, 0x400000;\n@p bra WAIT;\ntrap;\nDONE:\n}" ::"l"(p), "r"(target) : "memory");
}
__device__ __forceinline__ bool elect_one() {
  uint32_t p;
  asm volatile("{\n.reg .pred P;\nelect.sync _|P, 0xffffffff;\nselp.u32 %0, 1, 0, P;\n}" : "=r"(p));
  return p != 0;
}
__device__ __forceinline__ void bulk_ld(uint32_t dst, const void* src, int bytes, uint32_t bar) {
  asm volatile("cp.async.bulk.shared::cluster.global.mbarrier::complete_tx::bytes [%0], [%1], %2, [%3];" ::"r"(dst), "l"(src), "r"(bytes), "r"(bar) : "memory");
}
__device__ __forceinline__ void bulk_ld_mc_h(uint32_t dst, const void* src, int bytes, uint32_t bar, uint16_t mask, uint64_t pol) {
  asm volatile("cp.async.bulk.shared::cluster.global.mbarrier::complete_tx::bytes.multicast::cluster.L2::cache_hint [%0], [%1], %2, [%3], %4, %5;" ::"r"(dst), "l"(src), "r"(bytes), "r"(bar), "h"(mask), "l"(pol) : "memory");
}
__device__ __forceinline__ uint64_t policy_evict_normal() {
  uint64_t p;
  asm("createpolicy.fractional.L2::evict_normal.b64 %0, 1.0;" : "=l"(p));
  return p;
}
__device__ __forceinline__ void tma_ld2(uint32_t dst, const CUtensorMap* tm, int c0, int c1, uint32_t bar) {
  asm volatile("cp.async.bulk.tensor.2d.shared::cluster.global.mbarrier::complete_tx::bytes [%0], [%1, {%3,%4}], [%2];" ::"r"(dst), "l"(tm), "r"(bar), "r"(c0), "r"(c1) : "memory");
}
__device__ __forceinline__ void tma_ld3(uint32_t dst, const CUtensorMap* tm, int c0, int c1, int c2, uint32_t bar) {
  asm volatile("cp.async.bulk.tensor.3d.shared::cluster.global.mbarrier::complete_tx::bytes [%0], [%1, {%3,%4,%5}], [%2];" ::"r"(dst), "l"(tm), "r"(bar), "r"(c0), "r"(c1), "r"(c2) : "memory");
}
__device__ __forceinline__ void tma_ld3h(uint32_t dst, const CUtensorMap* tm, int c0, int c1, int c2, uint32_t bar, uint64_t pol) {
  asm volatile("cp.async.bulk.tensor.3d.shared::cluster.global.mbarrier::complete_tx::bytes.L2::cache_hint [%0], [%1, {%3,%4,%5}], [%2], %6;" ::"r"(dst), "l"(tm), "r"(bar), "r"(c0), "r"(c1), "r"(c2), "l"(pol) : "memory");
}
__device__ __forceinline__ uint64_t policy_evict_first() {
  uint64_t p;
  asm("createpolicy.fractional.L2::evict_first.b64 %0, 1.0;" : "=l"(p));
  return p;
}
__device__ __forceinline__ void tma_st3(const CUtensorMap* tm, uint32_t src, int c0, int c1, int c2) {
  asm volatile("cp.async.bulk.tensor.3d.global.shared::cta.bulk_group [%0, {%2,%3,%4}], [%1];" ::"l"(tm), "r"(src), "r"(c0), "r"(c1), "r"(c2) : "memory");
}
__device__ __forceinline__ void tma_st4(const CUtensorMap* tm, uint32_t src, int c0, int c1, int c2, int c3) {
  asm volatile("cp.async.bulk.tensor.4d.global.shared::cta.bulk_group [%0, {%2,%3,%4,%5}], [%1];" ::"l"(tm), "r"(src), "r"(c0), "r"(c1), "r"(c2), "r"(c3) : "memory");
}
__device__ __forceinline__ void tma_st5(const CUtensorMap* tm, uint32_t src, int c0) {
  asm volatile("cp.async.bulk.tensor.5d.global.shared::cta.bulk_group [%0, {%2,%3,%3,%3,%3}], [%1];" ::"l"(tm), "r"(src), "r"(c0), "r"(0) : "memory");
}
__device__ __forceinline__ void bulk_commit() { asm volatile("cp.async.bulk.commit_group;" ::: "memory"); }
template <int N> __device__ __forceinline__ void bulk_wait_read() { asm volatile("cp.async.bulk.wait_group.read %0;" ::"n"(N) : "memory"); }
__device__ __forceinline__ void bulk_wait_all() { asm volatile("cp.async.bulk.wait_group 0;" ::: "memory"); }
__device__ __forceinline__ void fence_async_smem() { asm volatile("fence.proxy.async.shared::cta;" ::: "memory"); }
__device__ __forceinline__ void wg_fence() { asm volatile("wgmma.fence.sync.aligned;" ::: "memory"); }
__device__ __forceinline__ void wg_commit() { asm volatile("wgmma.commit_group.sync.aligned;" ::: "memory"); }
template <int N> __device__ __forceinline__ void wg_wait() { asm volatile("wgmma.wait_group.sync.aligned %0;" ::"n"(N) : "memory"); }
template <int R> __device__ __forceinline__ void fence_regs(float (&d)[R]) {
#pragma unroll
  for (int i = 0; i < R; i++) asm volatile("" : "+f"(d[i])::"memory");
}
__device__ __forceinline__ uint64_t mk_desc(uint32_t addr) {
  return (uint64_t)((addr & 0x3FFFF) >> 4) | (1ull << 16) | (64ull << 32) | (1ull << 62);
}
__device__ __forceinline__ uint32_t pack2(float lo, float hi) {
  uint32_t r;
  asm("cvt.rn.bf16x2.f32 %0, %1, %2;" : "=r"(r) : "f"(hi), "f"(lo));
  return r;
}
__device__ __forceinline__ void stsm4(uint32_t ad, uint32_t a, uint32_t b, uint32_t c, uint32_t d) {
  asm volatile("stmatrix.sync.aligned.m8n8.x4.shared.b16 [%0], {%1,%2,%3,%4};" ::"r"(ad), "r"(a), "r"(b), "r"(c), "r"(d) : "memory");
}
__device__ __forceinline__ void stsm4t(uint32_t ad, uint32_t a, uint32_t b, uint32_t c, uint32_t d) {
  asm volatile("stmatrix.sync.aligned.m8n8.x4.trans.shared.b16 [%0], {%1,%2,%3,%4};" ::"r"(ad), "r"(a), "r"(b), "r"(c), "r"(d) : "memory");
}

__device__ __forceinline__ void stsm2t(uint32_t ad, uint32_t a, uint32_t b) {
  asm volatile("stmatrix.sync.aligned.m8n8.x2.trans.shared.b16 [%0], {%1,%2};" ::"r"(ad), "r"(a), "r"(b) : "memory");
}
__device__ __forceinline__ void red_add(unsigned* p) { asm volatile("red.relaxed.gpu.global.add.u32 [%0], 1;" ::"l"(p) : "memory"); }
__device__ __forceinline__ void fence_release() { asm volatile("fence.release.gpu;" ::: "memory"); }
__device__ __forceinline__ void fence_async_global() { asm volatile("fence.proxy.async.global;" ::: "memory"); }
__device__ __forceinline__ void bulk_ld_h(uint32_t dst, const void* src, int bytes, uint32_t bar, uint64_t pol) {
  asm volatile("cp.async.bulk.shared::cluster.global.mbarrier::complete_tx::bytes.L2::cache_hint [%0], [%1], %2, [%3], %4;" ::"r"(dst), "l"(src), "r"(bytes), "r"(bar), "l"(pol) : "memory");
}

__device__ __forceinline__ bool mbar_test(uint32_t a, int ph) {
  uint32_t ok;
  asm volatile("{\n.reg .pred p;\nmbarrier.test_wait.parity.shared::cta.b64 p, [%1], %2;\nselp.u32 %0, 1, 0, p;\n}" : "=r"(ok) : "r"(a), "r"(ph) : "memory");
  return ok != 0;
}
__device__ __forceinline__ void poll64x4(const unsigned long long* p, unsigned long long (&v)[4]) {
  asm volatile("{\n.reg .pred p;\n.reg .u32 c;\n.reg .b64 t, u;\nmov.u32 c, 0;\nWAIT:\n"
               "ld.relaxed.gpu.global.u64 %0, [%4];\nld.relaxed.gpu.global.u64 %1, [%4+512];\n"
               "ld.relaxed.gpu.global.u64 %2, [%4+1024];\nld.relaxed.gpu.global.u64 %3, [%4+1536];\n"
               "or.b64 t, %0, %1;\nor.b64 u, %2, %3;\nor.b64 t, t, u;\nsetp.ge.s64 p, t, 0;\n@p bra DONE;\n"
               "add.u32 c, c, 1;\nsetp.lt.u32 p, c, 0x400000;\n@p bra WAIT;\ntrap;\nDONE:\n}"
               : "=l"(v[0]), "=l"(v[1]), "=l"(v[2]), "=l"(v[3]) : "l"(p) : "memory");
}

constexpr int G_STAGE = WBLK + XBLK;
constexpr int OFF_XR = 4 * G_STAGE;
constexpr int OFF_WS = OFF_XR + 6 * 8192;
constexpr int OFF_F = OFF_WS + 2 * 8192;
constexpr int OFF_WRAW = OFF_F + 8192;
constexpr int OFF_BAR = OFF_WRAW + 8192;
constexpr int OFF_GB = OFF_BAR + 1024;
constexpr int SMEM_BYTES = OFF_GB + 512;
constexpr int OFF_H0B = 10 * 8192;
constexpr int OFF_E = OFF_WRAW + 3072;
constexpr int B_RAWX = 0, B_F = 48, B_ROLE = 56, B_H0 = 72, B_H1 = 88, B_YFREE = 112,
              B_EMPTY = 128, B_STGX = 160, B_STGW = 208, B_Y = 224, B_OUT = 240,
              B_FULL = 320, B_RAWW = 352, B_DONE = 384, B_END = 648, S_ROLE = 656, S_PROBE = 672;

struct Maps { CUtensorMap x, we, wo, xst[2], wst, yst, yld, out, xe[2], w30; };

__device__ __forceinline__ int chunk_of(int n) { return n < 16 ? n : 31 - n; }
__device__ __forceinline__ bool has_x2(int id, int n, int g) { return (((id >> 5) ^ n) & 1) == 0 && ((n >> 1) & 1) == g; }
__device__ __forceinline__ uint32_t x_base(int s, int idx, uint32_t pgmask, int& par) {
  const int page = idx >> 3, o = idx & 7;
  par = (s ^ (pgmask >> page) ^ __popc(o)) & 1;
  return (page << 21) | ((o & 3) << 16) | ((o >> 2) << 19);
}
__device__ __forceinline__ uint32_t read_info(uint32_t bar, int i) {
  uint32_t v;
  mbar_wait(bar + B_ROLE + 8 * i, 0);
  asm volatile("ld.shared.b32 %0, [%1];" : "=r"(v) : "r"(bar + S_ROLE + 4 * i) : "memory");
  return v;
}
__device__ __forceinline__ void send_info(uint32_t bar, int i, uint32_t v) {
#pragma unroll
  for (int r = 0; r < 2; r++)
    asm volatile("{\n.reg .b32 a, m;\nmapa.shared::cluster.u32 a, %0, %2;\nmapa.shared::cluster.u32 m, %1, %2;\n"
                 "st.async.weak.shared::cluster.mbarrier::complete_tx::bytes.b32 [a], %3, [m];\n}"
                 ::"r"(bar + S_ROLE + 4 * i), "r"(bar + B_ROLE + 8 * i), "r"(r), "r"(v) : "memory");
}
__device__ __forceinline__ unsigned probe(uint8_t* p, int lane, int pb) {
  if (lane < 2) *(uint4*)(p + lane * 16) = make_uint4(0, 0, 0, 0);
  __syncwarp();
  unsigned v = 0, best = ~0u;
  if (lane == 0) {
#pragma unroll 1
    for (int r = 0; r < 2; r++) {
      unsigned t0, t1;
      asm volatile("mov.u32 %0, %%clock;" : "=r"(t0) : "r"(v) : "memory");
      asm volatile("atom.relaxed.gpu.global.exch.b32 %0, [%1], 0;" : "=r"(v) : "l"(p) : "memory");
      asm volatile("{\n.reg .pred p;\nsetp.ne.u32 p, %1, 0xffffffff;\nmov.u32 %0, 0;\n@p mov.u32 %0, %%clock;\n}" : "=r"(t1) : "r"(v) : "memory");
      best = min(best, t1 - t0);
      if (r < 3) PROF_V(pb + r, t1 - t0);
    }
  }
  return best;
}

template <bool ISX>
__device__ __forceinline__ void t_issue(float (&t)[32], uint32_t sb, uint32_t raw) {
  const uint64_t da = mk_desc(sb + OFF_F), db = mk_desc(raw);
  wg_fence();
#pragma unroll
  for (int kk = 0; kk < (ISX ? 4 : 1); kk++) wgmma_fwd<1>(t, da + 2 * kk, db + 128 * kk, kk);
  wg_commit();
}
template <bool ISX>
__device__ __forceinline__ void t_finish(float (&t)[32], uint32_t dst, uint32_t sbar, int sw, int wg, int w, int lane) {
  fence_regs(t);
  if (ISX) asm volatile("bar.sync %0, 128;" ::"r"(1 + wg) : "memory");
  const int m = lane >> 3, r = lane & 7;
  uint32_t ad = dst + (8 * w + r) * 128;
  if (ISX) ad += ((((m & 1) * 4 + (m >> 1)) ^ sw ^ r) << 4);
  else ad += (m & 1) * 4096 + (((m >> 1) ^ sw ^ r) << 4);
#pragma unroll
  for (int i = 0; i < 4; i++) {
    const uint32_t a = ISX ? ((ad ^ ((i & 1) * 32)) + (i >> 1) * 4096) : (ad ^ (i * 32));
    stsm4(a, pack2(t[8 * i], t[8 * i + 1]), pack2(t[8 * i + 2], t[8 * i + 3]), pack2(t[8 * i + 4], t[8 * i + 5]), pack2(t[8 * i + 6], t[8 * i + 7]));
  }
  fence_async_smem();
  __syncwarp();
  if (lane == 0) mbar_arrive(sbar);
}
template <int NT, int K0, int K1>
__device__ __forceinline__ void batch(float (&yr)[80], float (&yi)[80], float (&t)[32], uint32_t st, int wg, int sd, uint32_t fa, uint32_t raw) {
  const uint64_t w0 = mk_desc(st + wg * 8192), x0 = mk_desc(st + WBLK);
  const uint64_t da = mk_desc(fa), db = mk_desc(raw);
  wg_fence();
  if (NT) {
#pragma unroll
    for (int kk = 0; kk < NT; kk++) wgmma_fwd<1>(t, da + 2 * kk, db + 128 * kk, kk);
    wg_commit();
  }
#pragma unroll
  for (int kk = K0; kk < K1; kk++) {
    const uint64_t wr = w0 + kk * 128, wi = wr + 256, xr = x0 + kk * 2, xi = xr + 4;
    wgmma_main<1>(yr, wr, xr, kk ? 1 : sd);
    wgmma_main<1>(yi, wr, xi, kk ? 1 : sd);
    wgmma_main<1>(yr, wi, xi, 1);
    wgmma_main<-1>(yi, wi, xr, 1);
  }
  wg_commit();
}

#define X_WAIT() PROF_W(wraw, mbar_wait(bar + B_RAWX + 8 * (wg * 3 + xs), xph))
#define X_ISSUE() t_issue<true>(t, sb, sb + OFF_XR + (wg * 3 + xs) * 8192)
#define X_FINISH(sw) do { t_finish<true>(t, sb + OFF_XR + (wg * 3 + xs) * 8192, bar + B_STGX + 8 * (wg * 3 + xs), sw, wg, w, lane); \
                          if (++xs == 3) { xs = 0; xph ^= 1; } } while (0)
#define W_WAIT(n) PROF_W(wraw, mbar_wait(bar + B_RAWW + 8 * (wg * 2 + ((n) & 1)), ((n) >> 1) & 1))
#define WRAW(n) (sb + OFF_WRAW + (wg * 2 + ((n) & 1)) * 2048)
#define W_FINISH() t_finish<false>(t, sb + OFF_WS + wg * 8192, bar + B_STGW + 8 * wg, (bid >> 1) & 7, wg, w, lane)

__global__ void __cluster_dims__(2, 1, 1) __launch_bounds__(512, 1)
k1_main(const __grid_constant__ Maps tm, uint8_t* __restrict__ xbuf, const __nv_bfloat16* __restrict__ gamma,
        const __nv_bfloat16* __restrict__ beta) {
  extern __shared__ __align__(1024) uint8_t smem_raw[];
  const uint32_t sb = s2u(smem_raw);
  const uint32_t bar = sb + OFF_BAR;
  const int warp = __shfl_sync(0xffffffffu, threadIdx.x >> 5, 0), lane = threadIdx.x & 31;
  const int bid = (int)blockIdx.x - 4;
  const uint32_t rank = bid & 1;
  if (warp < 5 && elect_one()) {
    if (warp == 0) {
      PROF_T(0);
#pragma unroll
      for (int o = 0; o < B_EMPTY; o += 8) mbar_init(bar + o, 1);
      mbar_expect(bar + B_ROLE, 4);
      mbar_expect(bar + B_ROLE + 8, 4);
    } else if (warp == 1) {
#pragma unroll
      for (int o = B_EMPTY; o < B_FULL; o += 8) mbar_init(bar + o, 4);
    } else if (warp < 4) {
#pragma unroll
      for (int o = B_FULL; o < B_END; o += 16) mbar_init(bar + o + (warp & 1) * 8, 2);
    } else {
#pragma unroll
      for (int i = 3; i < 6; i++) asm volatile("prefetch.tensormap [%0];" ::"l"(&tm.x + i) : "memory");
    }
    asm volatile("fence.mbarrier_init.release.cluster;" ::: "memory");
  }
  __syncthreads();
  if (threadIdx.x == 64) PROF_T(20);
  asm volatile("barrier.cluster.arrive.relaxed.aligned;" ::: "memory");
  if (warp >= 12) {
    asm volatile("setmaxnreg.dec.sync.aligned.u32 24;");
    if (bid >= 0) {
      if (rank == 0) {
        const int k = bid >> 1, page = 2 + k % (XPAGES - 2);
        const uint32_t off = (warp & 2) ? (page << 21) + 0xb0000 + (k / (XPAGES - 2)) * 128 : (XPAGES << 21) + k * 64;
        const unsigned lat = probe(xbuf + off + (warp & 1) * 4096, lane, 400 + (warp & 2) * 5 + (warp & 1) * 3);
        if (lane == 0) asm volatile("st.shared.b32 [%0], %1;" ::"r"(bar + S_PROBE + 4 * (warp & 3)), "r"(lat) : "memory");
        asm volatile("bar.arrive 4, 160;" ::: "memory");
      }
      if (warp - 12 < NFL && elect_one()) {
        for (int n = warp - 12; n < 33; n += NFL) {
          int f = n;
          if (n == 32) f += (read_info(bar, 0) >> 5) * 2 + rank;
          mbar_wait(bar + B_DONE + 8 * n, 0);
          if (!NOFENCE) fence_release();
          red_add(&g_ctr[(C_FLAG + f) * 32]);
          if (n < 32) { PROF_T(64 + n); PROF_V(192 + n, tm0); } else { PROF_V(4, tm0); }
        }
      }
      if (warp == 15 && elect_one()) {
        for (int v = 0; v < 2 * (32 - WR); v++) {
          mbar_wait(bar + B_FULL + 8 * (v & 3), (v >> 2) & 1);
          if (v & 1) red_add(&g_ctr[(C_LOADED + (v >> 1)) * 32]);
        }
      }
      __syncwarp();
    }
    asm volatile("barrier.cluster.wait.aligned;" ::: "memory");
    asm volatile("barrier.cluster.arrive.relaxed.aligned;\nbarrier.cluster.wait.aligned;" ::: "memory");
  } else if (warp >= 8) {
    asm volatile("setmaxnreg.dec.sync.aligned.u32 40;");
    if (bid < 0) {
      asm volatile("barrier.cluster.wait.aligned;" ::: "memory");
    } else if (warp == 9 || warp == 10) {
      if (elect_one()) {
        const int g = warp - 9;
        const uint64_t pol = policy_evict_first();
        int id = bid, role = -1;
        uint32_t pgmask = 0;
        int ln = 0, lj = 0;
        auto load_x = [&](int sl) {
          if (ln >= 16) return;
          if (ln >= OB && role < 0) role = read_info(bar, 0);
          const int lid = ln < OB ? bid : role * 2 + rank;
          const int t = lj ? 128 + (lid & 31) : 2 * (lid & 63) + g;
          mbar_expect(bar + B_RAWX + 8 * sl, 8192);
          tma_ld3h(sb + OFF_XR + sl * 8192, &tm.x, ln * 64, t * MT, lid >> 6, bar + B_RAWX + 8 * sl, pol);
          if (lj == 0 && has_x2(lid, ln, g)) lj = 1; else { lj = 0; ln++; }
        };
        auto load_w = [&](int n) {
          if (n >= 32) return;
          const int cp = chunk_of(n) * 64 + (bid >> 1), col = (cp & 511) * 8 + (n >> 4) * 4 + rank * 2 + g, sl = g * 2 + (n & 1);
          mbar_expect(bar + B_RAWW + 8 * sl, 2048);
          tma_ld3h(sb + OFF_WRAW + sl * 2048, cp < 512 ? &tm.we : &tm.wo, 0, 0, col, bar + B_RAWW + 8 * sl, pol);
        };
        if (g == 0) PROF_T(22);
        load_x(g * 3);
        if (g == 0) {
          mbar_expect(bar + B_F, 8192);
          bulk_ld(sb + OFF_F, g_Fimg, 8192, bar + B_F);
        }
        load_w(0);
        mbar_arrive(bar + B_RAWW + 16 * g);
        load_x(g * 3 + 1);
        load_w(1);
        if (g == 0) PROF_T(23);
        bool late = ln >= OB;
        if (!late) load_x(g * 3 + 2);
        int xs = 0, xph = 0, yp = 0;
        for (int n = 0; n < 32; n++) {
          if (n == OB) {
            if (role < 0) role = read_info(bar, 0);
            pgmask = read_info(bar, 1);
            id = role * 2 + rank;
          }
          unsigned freed = 128;
          if (n >= WR) asm volatile("ld.relaxed.gpu.global.u32 %0, [%1];" : "=r"(freed) : "l"(&g_ctr[(C_LOADED + n - WR) * 32]) : "memory");
          if (n < 16) {
            const int nx = has_x2(id, n, g) ? 2 : 1;
            for (int j = 0; j < nx; j++) {
              const int t = j ? 128 + (id & 31) : 2 * (id & 63) + g;
              const int tg = t >> 5, row = t & 31, sl = g * 3 + xs;
              int par0, par1;
              const uint32_t off0 = x_base(id >> 6, XC(n) * 10 + tg, pgmask, par0), off1 = x_base(id >> 6, XC(n) * 10 + 5 + tg, pgmask, par1);
              const uint32_t buf = sb + OFF_XR + sl * 8192;
              mbar_wait(bar + B_STGX + 8 * sl, xph);
              tma_st5(&tm.xst[par0], buf, (off0 + (par0 << 12) + row * 128) >> 1);
              tma_st5(&tm.xst[par1], buf + 4096, (off1 + (par1 << 12) + row * 128) >> 1);
              bulk_commit();
              if (late) { load_x(g * 3 + 2); late = false; }
              bulk_wait_read<0>();
              load_x(sl);
              if (++xs == 3) { xs = 0; xph ^= 1; }
            }
          }
          if (n > 16 + LW && n <= YFLUSH) {
            if (yp == 0 || yp == 3) mbar_wait(bar + B_Y + 8 * g, yp & 1);
            do {
              tma_st4(&tm.yst, sb + OFF_XR + (g * 3 + yp % 3) * 8192, 0, yp * 32, 2 * (role & 31), (role >> 5) * 8 + rank * 2 + g);
            } while (++yp < 2);
            bulk_commit();
            bulk_wait_read<0>();
            if (yp == 2) mbar_arrive(bar + B_YFREE + 8 * g);
          }
          const int wrow = (n % WR) * (WCHUNK / 128) + (rank * 2 + (bid >> 6)) * 128 + g * 64 + ((bid >> 1) & 31);
          if (freed < 128) flag_wait(&g_ctr[(C_LOADED + n - WR) * 32], 128);
          mbar_wait(bar + B_STGW + 8 * g, n & 1);
          tma_st4(&tm.wst, sb + OFF_WS + g * 8192, 0, 0, 0, wrow);
          bulk_commit();
          load_w(n + 2);
          bulk_wait_all();
          mbar_arrive(bar + B_DONE + 8 * n);
          mbar_arrive(bar + B_RAWW + 8 * (g * 2 + ((n + 1) & 1)));
        }
        const int b = role >> 5, u = role & 31;
        mbar_wait(bar + B_Y + 8 * g, 0);
        for (int p = 0; p < 5; p++) tma_st4(&tm.yst, sb + (p * 2 + g) * 8192, 0, p * 32, 2 * u, b * 8 + 4 + rank * 2 + g);
        bulk_commit();
        bulk_wait_all();
        mbar_arrive(bar + B_DONE + 8 * 32);
        for (int i = 0; i < 10; i++) {
          const int hf = i >= 5, k = i - 5 * hf;
          mbar_wait(bar + B_OUT + 8 * (g * 5 + k), hf);
          tma_st3(&tm.out, sb + (hf ? 0 : k < 4 ? OFF_XR : OFF_H0B - 65536) + (2 * k + g) * 8192, (hf * 4 + rank * 2 + (u & 1)) * 64, ((u >> 1) * 10 + 2 * k + g) * MT, b);
          bulk_commit();
        }
        bulk_wait_read<0>();
        if (g == 0) PROF_T(12);
      }
      __syncwarp();
      asm volatile("barrier.cluster.wait.aligned;" ::: "memory");
    } else if (warp == 11) {
      if (rank == 0) asm volatile("bar.sync 4, 160;" ::: "memory");
      asm volatile("barrier.cluster.wait.aligned;" ::: "memory");
      if (lane == 0 && rank == 0) {
        const int k = bid >> 1;
        uint32_t l0, l1, l2, l3;
        asm volatile("ld.shared.v4.b32 {%0, %1, %2, %3}, [%4];" : "=r"(l0), "=r"(l1), "=r"(l2), "=r"(l3) : "r"(bar + S_PROBE) : "memory");
        const int side = l1 < l0, near = l3 >= l2;
        unsigned long long add = 1ull << (8 * side), v;
        if (k < XPAGES - 2) add += (unsigned long long)(near ^ side) << (18 + k);
        unsigned long long* reg = (unsigned long long*)&g_ctr[C_REG * 32];
        PROF_T(14);
        const int ticket = (atomicAdd(reg, add) >> (8 * side)) & 255;
        if (ticket < 1000) PROF_T(15);
        const int role = ticket < 32 ? side * 32 + ticket : (side ^ 1) * 32 + 63 - ticket;
        send_info(bar, 0, role);
        asm volatile("{\n.reg .pred p;\n.reg .u32 c, a, b;\nmov.u32 c, 0;\nWAIT:\n"
                     "ld.relaxed.gpu.global.u64 %0, [%1];\ncvt.u32.u64 a, %0;\nbfe.u32 b, a, 8, 8;\nand.b32 a, a, 255;\nadd.u32 a, a, b;\n"
                     "setp.ge.u32 p, a, 64;\n@p bra DONE;\n"
                     "add.u32 c, c, 1;\nsetp.lt.u32 p, c, 0x400000;\n@p bra WAIT;\ntrap;\nDONE:\n}" : "=l"(v) : "l"(reg) : "memory");
        send_info(bar, 1, (uint32_t)(v >> 16));
        PROF_V(16, side); PROF_V(17, role); PROF_V(18, v);
      }
      __syncwarp();
      if (elect_one()) {
        const uint8_t* ws = g_W + (size_t)((read_info(bar, 0) & 31) * 2 + rank) * 2 * WBLK;
        for (int v = 0; v < 64; v++) {
          const int n = v >> 1, s = v & 3;
          const uint8_t* src = ws + (size_t)(n % WR) * WCHUNK + (v & 1) * WBLK;
          if (!(v & 1)) {
            flag_wait(&g_ctr[(C_FLAG + n) * 32], 128);
            fence_async_global();
            PROF_T(32 + n);
          }
          mbar_wait(bar + B_EMPTY + 8 * s, ((v >> 2) & 1) ^ 1);
          mbar_expect(bar + B_FULL + 8 * s, WBLK);
          bulk_ld(sb + s * G_STAGE, src, WBLK, bar + B_FULL + 8 * s);
        }
      }
      __syncwarp();
    } else {
      asm volatile("barrier.cluster.wait.aligned;" ::: "memory");
      if (elect_one()) {
        const int role = read_info(bar, 0);
        uint32_t pgmask = 0;
        PROF_T(1);
        const int b = role >> 5, u = role & 31;
        const uint64_t pef = policy_evict_first(), pen = policy_evict_normal();
        const uint8_t* xs = xbuf + ((((u >> 1) & 3) << 14) | (((u >> 3) & 1) << 18) | ((u >> 4) << 20) | ((u & 1) << 13));
        for (int v = 0; v < 64; v++) {
          const int n = v >> 1, h = v & 1, c = chunk_of(n), s = v & 3;
          const uint64_t polx = (n < XEF0 || n >= 16) ? pef : pen;
          const uint32_t dst = sb + s * G_STAGE, fb = bar + B_FULL + 8 * s;
          if (v == 2 * OB) pgmask = read_info(bar, 1);
          uint32_t xo[3];
#pragma unroll
          for (int g = 0; g < 3; g++) {
            int par;
            xo[g] = x_base(b, XC(c) * 10 + h * 5 + rank * 2 + g, c < OB ? 0 : pgmask, par);
            xo[g] += ((par ^ u) & 1) << 12;
          }
          if (h == 0 && n < 16) {
            flag_wait(&g_ctr[(C_FLAG + n) * 32], 128);
            fence_async_global();
          }
          mbar_wait(bar + B_EMPTY + 8 * s, ((v >> 2) & 1) ^ 1);
          mbar_expect(fb, XBLK);
#pragma unroll
          for (int g = 0; g < 3; g++) {
            const int skip = (g == 0 && rank) ? 2048 : 0, len = (g == (rank ? 0 : 2)) ? 2048 : 4096;
            bulk_ld_mc_h(dst + WBLK + (rank * 2 + g) * 4096 + skip, xs + xo[g] + skip, len, fb, 3, polx);
          }
        }
        const int dq = rank * 2 + (u & 1), t0 = (u >> 1) * 10;
        flag_wait(&g_ctr[C_E * 32], 4);
        flag_wait(&g_ctr[(C_FLAG + YFLUSH) * 32], 128);
        fence_async_global();
        mbar_wait(bar + B_DONE + 8 * 31, 0);
        mbar_expect(bar + B_H0, 8 * 8192 + 7168 + 5120 + 512);
        bulk_ld(sb + OFF_F, g_Gimg, 7168, bar + B_H0);
        for (int i = 0; i < 4; i++) tma_ld2(sb + OFF_XR + i * 16384, &tm.yld, 0, ((b * 8 + dq) * NT + t0 + 2 * i) * 64, bar + B_H0);
        for (int hf = 0; hf < 2; hf++) {
          bulk_ld(sb + OFF_E + hf * 2560, g_E + ((b * 8 + hf * 4 + dq) * NT + t0) * 64, 2560, bar + B_H0);
          bulk_ld(sb + OFF_GB + hf * 256, gamma + (hf * 4 + dq) * 64, 128, bar + B_H0);
          bulk_ld(sb + OFF_GB + hf * 256 + 128, beta + (hf * 4 + dq) * 64, 128, bar + B_H0);
        }
        mbar_wait(bar + B_EMPTY + 8 * 2, 1);
        mbar_expect(bar + B_H0 + 8, 16384);
        tma_ld2(sb + OFF_H0B, &tm.yld, 0, ((b * 8 + dq) * NT + t0 + 8) * 64, bar + B_H0 + 8);
        flag_wait(&g_ctr[(C_FLAG + 32 + b * 2 + rank) * 32], 32);
        fence_async_global();
        PROF_T(5);
        for (int i = 0; i < 5; i++) {
          const uint32_t fb = bar + B_H1 + 8 * (i >> 1);
          if ((i & 1) == 0) mbar_expect(fb, i < 4 ? 32768 : 16384);
          tma_ld2(sb + i * 16384, &tm.yld, 0, ((b * 8 + 4 + dq) * NT + t0 + 2 * i) * 64, fb);
        }
      }
      __syncwarp();
      unsigned old = 0;
      if (lane == 0) old = atomicAdd(&g_ctr[C_EXIT * 32], 1);
      if (__shfl_sync(0xffffffffu, old, 0) == 127) {
        for (int i = lane; i < C_NUM; i += 32) *(volatile unsigned long long*)&g_ctr[i * 32] = 0;
      }
    }
    asm volatile("barrier.cluster.arrive.relaxed.aligned;\nbarrier.cluster.wait.aligned;" ::: "memory");
  } else {
    asm volatile("setmaxnreg.inc.sync.aligned.u32 224;");
    const int wg = warp >> 2, w = warp & 3;
    asm volatile("barrier.cluster.wait.aligned;" ::: "memory");
    if (bid < 0) {
      float ea[80], eb[80];
      const int b = blockIdx.x >> 1;
      constexpr int ES = 32768 + 2 * XBLK;
#pragma unroll 1
      for (int k = -3; k < 8; k++) {
        const int sl = (k + 3) % 3;
        if (k >= 0) {
          mbar_wait(bar + B_RAWX + 8 * sl, (k / 3) & 1);
          const uint64_t da = mk_desc(sb + sl * ES + wg * 16384), db = mk_desc(sb + sl * ES + 32768);
          wg_fence();
#pragma unroll
          for (int kk = 0; kk < 8; kk++) {
            const uint64_t a0 = da + (kk & 3) * 128, b0 = db + (kk & 3) * 2 + (kk >> 2) * (XBLK >> 4);
            wgmma_main<1>(ea, a0, b0, (k | kk) != 0);
            wgmma_main<1>(eb, a0 + 512, b0, (k | kk) != 0);
          }
          wg_commit();
          wg_wait<0>();
          asm volatile("bar.sync 3, 256;" ::: "memory");
        }
        if (k + 3 < 8 && warp == 0 && elect_one()) {
          const uint32_t dst = sb + sl * ES, fb = bar + B_RAWX + 8 * sl;
          mbar_expect(fb, ES);
          for (int q = 0; q < 4; q++) tma_ld2(dst + q * 8192, &tm.w30, rank * 256 + q * 64, (k + 3) * 64, fb);
          for (int q = 0; q < 2; q++) tma_ld3(dst + 32768 + q * XBLK, &tm.xe[q], (k + 3) * 64, 0, b, fb);
        }
        __syncwarp();
      }
      fence_regs(ea);
      fence_regs(eb);
      float* e0 = g_E + ((b * 8 + rank * 4 + wg * 2) * NT + 2 * (lane & 3)) * 64 + 16 * w + (lane >> 2);
#pragma unroll
      for (int i = 0; i < 80; i++) {
        const int o = (8 * (i >> 2) + (i & 1)) * 64 + ((i >> 1) & 1) * 8;
        e0[o] = ea[i];
        e0[o + NT * 64] = eb[i];
      }
      asm volatile("bar.sync 3, 256;" ::: "memory");
      if (threadIdx.x == 0) {
        fence_release();
        red_add(&g_ctr[C_E * 32]);
        PROF_T(28);
      }
      asm volatile("barrier.cluster.arrive.relaxed.aligned;\nbarrier.cluster.wait.aligned;" ::: "memory");
      return;
    }
    int id = bid;
    {
      float yr[80], yi[80], t[32];

      int xs = 0, xph = 0;
      unsigned wraw = 0, wfull = 0;
      if (threadIdx.x == 0) PROF_T(24);
      mbar_wait(bar + B_F, 0);
      if (threadIdx.x == 0) PROF_T(25);
#pragma unroll 1
      for (int m = 0; m <= LW; m++) {
        if (m == OB) id = __shfl_sync(0xffffffffu, read_info(bar, 0), 0) * 2 + rank;
        X_WAIT();
        X_ISSUE();
        wg_wait<0>();
        X_FINISH((2 * id + wg) & 7);
        if (threadIdx.x == 0 && m == 0) PROF_T(26);
        if (has_x2(id, m, wg)) {
          X_WAIT();
          X_ISSUE();
          wg_wait<0>();
          X_FINISH(id & 7);
        }
        if (m < LW) {
          W_WAIT(m);
          t_issue<false>(t, sb, WRAW(m));
          wg_wait<0>();
          W_FINISH();
        }
      }
      if (threadIdx.x == 0) PROF_T(27);
      static_assert(OB <= LW, "role is read in the prologue");
      const int ym = lane >> 3, yr8 = lane & 7;
      const uint32_t yad = (ym >> 1) * 4096 + yr8 * 128 + (((2 * w + (ym & 1)) ^ yr8) << 4);
#define STAGE_PROF0()
#define STAGE_PROF1()
#define STAGE_BEGIN() PROF_W(wfull, mbar_wait(bar + B_FULL + 8 * (v & 3), (v >> 2) & 1)); STAGE_PROF0(); const uint32_t st = sb + (v & 3) * G_STAGE
#define RELEASE(vv) do { if (w == 0 && lane < 2) mbar_arrive_cluster(bar + B_EMPTY + 8 * ((vv) & 3), lane, 1); } while (0)
#define XRAW (sb + OFF_XR + (wg * 3 + xs) * 8192)
#define STAGE_W(mw, sd) do { W_WAIT(mw); batch<1, 0, 1>(yr, yi, t, st, wg, sd, sb + OFF_F, WRAW(mw)); wg_wait<1>(); if (sd) RELEASE(v - 1); \
                             W_FINISH(); batch<0, 1, 2>(yr, yi, t, st, wg, 1, 0, 0); } while (0)
#define STAGE_PLAIN(sd) do { batch<0, 0, 1>(yr, yi, t, st, wg, sd, 0, 0); wg_wait<1>(); if (sd) RELEASE(v - 1); \
                             batch<0, 1, 2>(yr, yi, t, st, wg, 1, 0, 0); } while (0)
#pragma unroll 1
      for (int v = 0; v < 32; v++) {
        const int m = ((v + 1) >> 1) + LW;
        STAGE_BEGIN();
        if (!(v & 1) || v == 31) {
          STAGE_W(m, v != 0);
        } else if (m < 16) {
          X_WAIT();
          batch<4, 0, 1>(yr, yi, t, st, wg, 1, sb + OFF_F, XRAW);
          wg_wait<1>();
          RELEASE(v - 1);
          X_FINISH((2 * id + wg) & 7);
          if (has_x2(id, m, wg)) {
            X_WAIT();
            batch<4, 1, 2>(yr, yi, t, st, wg, 1, sb + OFF_F, XRAW);
            wg_wait<1>();
            X_FINISH(id & 7);
          } else {
            batch<0, 1, 2>(yr, yi, t, st, wg, 1, 0, 0);
          }
        } else {
          STAGE_PLAIN(1);
        }
        STAGE_PROF1();
      }
      wg_wait<0>();
      fence_regs(yr);
      fence_regs(yi);
      RELEASE(31);
      {
        uint32_t hold[32];
#pragma unroll
        for (int j = 0; j < 20; j++) {
          const uint32_t p0 = pack2(yr[4 * j], yr[4 * j + 1]), p1 = pack2(yr[4 * j + 2], yr[4 * j + 3]);
          const uint32_t p2 = pack2(yi[4 * j], yi[4 * j + 1]), p3 = pack2(yi[4 * j + 2], yi[4 * j + 3]);
          if (j < 12) {
            stsm4t(sb + OFF_XR + wg * 3 * 8192 + yad + (j >> 2) * 8192 + (j & 3) * 1024, p0, p1, p2, p3);
          } else {
            hold[4 * j - 48] = p0; hold[4 * j - 47] = p1; hold[4 * j - 46] = p2; hold[4 * j - 45] = p3;
          }
        }
#pragma unroll
        for (int j = 0; j < 32; j++) asm volatile("" : "+r"(hold[j])::"memory");
        fence_async_smem();
        __syncwarp();
        if (lane == 0) mbar_arrive(bar + B_Y + 8 * wg);
        if (threadIdx.x == 0) PROF_T(2);
#pragma unroll
        for (int v = 32; v < 34; v++) {
          STAGE_BEGIN();
          STAGE_PLAIN(v != 32);
          STAGE_PROF1();
        }
        mbar_wait(bar + B_YFREE + 8 * wg, 0);
#pragma unroll
        for (int j = 0; j < 8; j++)
          stsm4t(sb + OFF_XR + wg * 3 * 8192 + yad + (j >> 2) * 8192 + (j & 3) * 1024, hold[4 * j], hold[4 * j + 1], hold[4 * j + 2], hold[4 * j + 3]);
        fence_async_smem();
        __syncwarp();
        if (lane == 0) mbar_arrive(bar + B_Y + 8 * wg);
#pragma unroll
        for (int j = 0; j < 32; j++) t[j] = __uint_as_float(hold[j]);
      }
#pragma unroll 1
      for (int v = 34; v < 64; v++) {
        const int m = (v >> 1) + LW;
        STAGE_BEGIN();
        if (!(v & 1) && m < 32) {
          STAGE_W(m, 1);
        } else {
          STAGE_PLAIN(1);
          if (v == 49 && wg == 0) g_part[bid * 128 + threadIdx.x] = ~0ull;
        }
        STAGE_PROF1();
      }
      wg_wait<0>();
      fence_regs(yr);
      fence_regs(yi);
      asm volatile("bar.sync 3, 256;" ::: "memory");
#pragma unroll
      for (int j = 0; j < 20; j++)
        stsm4t(sb + wg * 8192 + yad + (j >> 2) * 16384 + (j & 3) * 1024, pack2(yr[4 * j], yr[4 * j + 1]), pack2(yr[4 * j + 2], yr[4 * j + 3]),
               pack2(yi[4 * j], yi[4 * j + 1]), pack2(yi[4 * j + 2], yi[4 * j + 3]));
      fence_async_smem();
      __syncwarp();
      if (lane == 0) mbar_arrive(bar + B_Y + 8 * wg);
      if (threadIdx.x == 0) PROF_T(3);
    }
    const int b = id >> 6, u = (id >> 1) & 31;
    const int dq = rank * 2 + (u & 1), tr = u >> 1;
    const int a = lane & 3, d0 = 16 * w + (lane >> 2);
    float2* s_red = (float2*)(smem_raw + OFF_WRAW);
#pragma unroll 1
    for (int hf = 0; hf < 2; hf++) {
      const uint32_t base = sb + (hf ? 0 : OFF_XR), last = hf ? 0 : OFF_H0B - 65536 - OFF_XR;
      float acc[5][28];
      float s1[2] = {0.f, 0.f}, s2[2] = {0.f, 0.f};
      if (hf == 0) mbar_wait(bar + B_H0, 0);
      const float* se = (const float*)(smem_raw + OFF_E + hf * 2560) + wg * 64 + d0;
#pragma unroll
      for (int k2 = 0; k2 < 4; k2++) {
        if (k2 < 3) {
          if (hf) mbar_wait(bar + B_H1 + 8 * k2, 0);
          else if (k2 == 2) mbar_wait(bar + B_H0 + 8, 0);
          const uint64_t da = mk_desc(base + (4 * k2 + wg) * 8192 + (k2 == 2 ? last : 0)), db = mk_desc(sb + OFF_F);
          wg_fence();
#pragma unroll
          for (int kk = 0; kk < 4; kk++) {
            wgmma_inv<1>(acc[2 * k2], da + 128 * kk, db + 2 * kk, kk);
            if (k2 < 2) wgmma_inv<1>(acc[2 * k2 + 1], da + 1024 + 128 * kk, db + 2 * kk, kk);
          }
          wg_commit();
        }
        if (k2 > 0) {
          if (k2 < 3) wg_wait<1>(); else wg_wait<0>();
#pragma unroll
          for (int k = 2 * k2 - 2; k < 2 * k2 && k < 5; k++) {
            fence_regs(acc[k]);
            if (a == 0) {
              acc[k][25] += se[k * 128];
              acc[k][27] += se[k * 128 + 8];
            }
            if (k == 4 && tr == 15 && wg == 1) {
#pragma unroll
              for (int i = 16; i < 28; i++)
                if (8 * (i >> 2) + (i & 1) + 2 * a >= LOUT - (NT - 1) * MT) acc[k][i] = 0.f;
            }
#pragma unroll
            for (int i = 0; i < 28; i += 2) {
              s1[(i >> 1) & 1] += acc[k][i] + acc[k][i + 1];
              s2[(i >> 1) & 1] += fmaf(acc[k][i], acc[k][i], acc[k][i + 1] * acc[k][i + 1]);
            }
          }
        }
      }
#pragma unroll
      for (int i = 0; i < 2; i++) {
#pragma unroll
        for (int o = 1; o < 4; o <<= 1) {
          s1[i] += __shfl_xor_sync(0xffffffffu, s1[i], o);
          s2[i] += __shfl_xor_sync(0xffffffffu, s2[i], o);
        }
      }
      if (a == 0) {
        s_red[wg * 64 + d0] = make_float2(s1[0], s2[0]);
        s_red[wg * 64 + d0 + 8] = make_float2(s1[1], s2[1]);
      }
      asm volatile("bar.sync 3, 256;" ::: "memory");
      if (threadIdx.x == 0) PROF_T(6 + 3 * hf);
      unsigned long long* part = g_part + ((hf * 2 + b) * 4 + dq) * 1024;
      if (threadIdx.x < 64) {
        const float2 p0 = s_red[threadIdx.x], p1 = s_red[64 + threadIdx.x];
        const float x1 = p0.x + p1.x, x2 = p0.y + p1.y;
        const unsigned long long v = ((unsigned long long)(__float_as_uint(x2) & 0x7fffffffu) << 32) | __float_as_uint(x1);
        asm volatile("st.relaxed.gpu.global.u64 [%0], %1;" ::"l"(part + tr * 64 + threadIdx.x), "l"(v) : "memory");
      }
      {
        const unsigned long long* q = part + (threadIdx.x >> 6) * 256 + (threadIdx.x & 63);
        unsigned long long v[4];
        poll64x4(q, v);
        float x1 = 0.f, x2 = 0.f;
#pragma unroll
        for (int i = 0; i < 4; i++) {
          x1 += __uint_as_float((uint32_t)v[i]);
          x2 += __uint_as_float((uint32_t)(v[i] >> 32));
        }
        s_red[128 + threadIdx.x] = make_float2(x1, x2);
      }
      asm volatile("bar.sync 3, 256;" ::: "memory");
      if (threadIdx.x == 0) PROF_T(7 + 3 * hf);
#pragma unroll
      for (int i = 0; i < 2; i++) {
        const float2 q0 = s_red[128 + d0 + 8 * i], q1 = s_red[192 + d0 + 8 * i], q2 = s_red[256 + d0 + 8 * i], q3 = s_red[320 + d0 + 8 * i];
        const float mu = ((q0.x + q1.x) + (q2.x + q3.x)) * (1.f / LOUT);
        const float var = fmaxf(((q0.y + q1.y) + (q2.y + q3.y)) * (1.f / LOUT) - mu * mu, 0.f);
        const __nv_bfloat16* gb = (const __nv_bfloat16*)(smem_raw + OFF_GB + hf * 256) + d0 + 8 * i;
        s1[i] = 0.5f * __bfloat162float(gb[0]) / sqrtf(var + 1e-5f);
        s2[i] = 0.5f * __bfloat162float(gb[64]) - mu * s1[i];
      }
      const int m = lane >> 3, r = lane & 7;
      const uint32_t ad = base + wg * 8192 + ((m >> 1) * 8 + r) * 128 + (((2 * w + (m & 1)) ^ r) << 4);
#pragma unroll
      for (int k = 0; k < 5; k++) {
        fence_regs(acc[k]);
#pragma unroll
        for (int i = 0; i < 28; i++) {
          const float hz = fmaf(acc[k][i], s1[(i >> 1) & 1], s2[(i >> 1) & 1]);
          const float in = hz * fmaf(hz * hz, 8.f * 0.044715f * 0.7978845608028654f, 2.f * 0.7978845608028654f);
          float th;
          asm("tanh.approx.f32 %0, %1;" : "=f"(th) : "f"(in));
          acc[k][i] = fmaf(hz, th, hz);
        }
#pragma unroll
        for (int jj = 0; jj < 3; jj++) {
          const float* c = acc[k] + 8 * jj;
          stsm4t(ad + (k == 4 ? last : 0) + k * 16384 + jj * 2048, pack2(c[0], c[1]), pack2(c[2], c[3]), pack2(c[4], c[5]), pack2(c[6], c[7]));
        }
        stsm2t(ad + (k == 4 ? last : 0) + k * 16384 + 3 * 2048, pack2(acc[k][24], acc[k][25]), pack2(acc[k][26], acc[k][27]));
        fence_async_smem();
        __syncwarp();
        if (lane == 0) mbar_arrive(bar + B_OUT + 8 * (wg * 5 + k));
      }
      if (threadIdx.x == 0) PROF_T(8 + 3 * hf);
    }
    asm volatile("barrier.cluster.arrive.relaxed.aligned;\nbarrier.cluster.wait.aligned;" ::: "memory");
  }
}

typedef CUresult (*EncFn)(CUtensorMap*, CUtensorMapDataType, cuuint32_t, void*, const cuuint64_t*, const cuuint64_t*, const cuuint32_t*,
                          const cuuint32_t*, CUtensorMapInterleave, CUtensorMapSwizzle, CUtensorMapL2promotion, CUtensorMapFloatOOBfill);

void encode(EncFn fn, CUtensorMap* m, int rank, void* base, const cuuint64_t* dims, const cuuint64_t* strides, const cuuint32_t* box,
            CUtensorMapL2promotion promo) {
  cuuint32_t es[5] = {1, 1, 1, 1, 1};
  fn(m, CU_TENSOR_MAP_DATA_TYPE_BFLOAT16, rank, base, dims, strides, box, es, CU_TENSOR_MAP_INTERLEAVE_NONE, CU_TENSOR_MAP_SWIZZLE_128B, promo,
     CU_TENSOR_MAP_FLOAT_OOB_FILL_NONE);
}

}

extern "C" void kernel_launch(void* const* d_in, const int* in_sizes, int n_in, void* d_out, int out_size) {
  (void)in_sizes; (void)n_in; (void)out_size;
  const __nv_bfloat16* x = (const __nv_bfloat16*)d_in[0];
  const __nv_bfloat16* w = (const __nv_bfloat16*)d_in[1];
  const __nv_bfloat16* gamma = (const __nv_bfloat16*)d_in[2];
  const __nv_bfloat16* beta = (const __nv_bfloat16*)d_in[3];
  void* fnp = nullptr;
  cudaDriverEntryPointQueryResult qr;
  cudaGetDriverEntryPoint("cuTensorMapEncodeTiled", &fnp, cudaEnableDefault, &qr);
  EncFn fn = (EncFn)fnp;
  void *xptr = nullptr, *wptr = nullptr, *yptr = nullptr;
  cudaGetSymbolAddress(&xptr, g_X);
  cudaGetSymbolAddress(&wptr, g_W);
  cudaGetSymbolAddress(&yptr, g_Y);
  xptr = (void*)(((uintptr_t)xptr + (1u << 21) - 1) & ~(uintptr_t)((1u << 21) - 1));
  const CUtensorMapL2promotion P0 = CU_TENSOR_MAP_L2_PROMOTION_NONE, P128 = CU_TENSOR_MAP_L2_PROMOTION_L2_128B;
  Maps m;
  {
    cuuint64_t d[3] = {1024, 8000, 2}, s[2] = {2048, 8000ull * 2048};
    cuuint32_t bx[3] = {64, 64, 1};
    encode(fn, &m.x, 3, (void*)x, d, s, bx, P128);
  }
  for (int ph = 0; ph < 2; ph++) {
    cuuint64_t d[3] = {64, (cuuint64_t)(16 - ph), 4096}, s[2] = {2ull * 262144 * 2, 128};
    cuuint32_t bx[3] = {64, 16, 1};
    encode(fn, ph ? &m.wo : &m.we, 3, (void*)(w + (size_t)ph * 262144), d, s, bx, P128);
  }
  for (int par = 0; par < 2; par++) {
    cuuint64_t d[5] = {(cuuint64_t)XPAGES << 20, 2, 4, 2, 2}, s[4] = {par ? 0x1000u : 0x3000u, 1u << 14, 1u << 18, 1u << 20};
    cuuint32_t bx[5] = {64, 2, 4, 2, 2};
    encode(fn, &m.xst[par], 5, xptr, d, s, bx, P0);
  }
  {
    cuuint64_t d[4] = {64, 32, 2, (cuuint64_t)WR * WCHUNK / 128}, s[3] = {4ull * WBLK, 4096, 128};
    cuuint32_t bx[4] = {64, 32, 2, 1};
    encode(fn, &m.wst, 4, wptr, d, s, bx, P0);
  }
  {
    cuuint64_t d[4] = {64, NT, 64, 16}, s[3] = {8192, 128, (cuuint64_t)NT * 8192};
    cuuint32_t bx[4] = {64, 32, 2, 1};
    encode(fn, &m.yst, 4, yptr, d, s, bx, P0);
  }
  {
    cuuint64_t d[2] = {64, 16ull * NT * 64}, s[1] = {128};
    cuuint32_t bx[2] = {64, 128};
    encode(fn, &m.yld, 2, yptr, d, s, bx, P128);
  }
  {
    cuuint64_t d[3] = {512, LOUT, 2}, s[2] = {1024, (cuuint64_t)LOUT * 1024};
    cuuint32_t bx[3] = {64, MT, 1};
    encode(fn, &m.out, 3, d_out, d, s, bx, P0);
  }
  for (int q = 0; q < 2; q++) {
    cuuint64_t d[3] = {512, (cuuint64_t)(NT - q), 2}, s[2] = {MT * 2048, 8000ull * 2048};
    cuuint32_t bx[3] = {64, NT, 1};
    encode(fn, &m.xe[q], 3, (void*)(x + q * 64 * 1024), d, s, bx, P128);
  }
  {
    cuuint64_t d[2] = {512, 512}, s[1] = {1024};
    cuuint32_t bx[2] = {64, 64};
    encode(fn, &m.w30, 2, (void*)(w + 30 * 262144), d, s, bx, P128);
  }
  cudaFuncSetAttribute(k1_main, cudaFuncAttributeMaxDynamicSharedMemorySize, SMEM_BYTES);
  k1_main<<<132, 512, SMEM_BYTES>>>(m, (uint8_t*)xptr, gamma, beta);
}
```

```cpp
#include <cuda_runtime.h>
#include <cuda_bf16.h>
#include <cuda.h>
#include <stdint.h>

namespace {

#define NPR 1
#define P0M 1
#define P1M 0
constexpr int LOUT = 7985;
constexpr int MT = 50;
constexpr int NT = 160;
constexpr int XBLK = NT * 128;
constexpr int WBLK = 16384;
constexpr int LW = 4;
constexpr int WR = 5;
#define OB_ 1
constexpr int OB = OB_;
constexpr int WCHUNK = 32 * 4 * WBLK;
constexpr int XPAGES = 20;
constexpr int NFL = 2;
constexpr int XKEEP = 9;
constexpr int YSTEP = 2;
constexpr int YFLUSH = 17 + LW + 3 * YSTEP;

__device__ __align__(1024) uint8_t g_X[(XPAGES + 2) << 21];
__device__ __align__(1024) uint8_t g_W[(size_t)WR * WCHUNK];
__device__ __align__(1024) uint8_t g_Y[8ull * NT * 8192];
__device__ __align__(128) float g_E[16 * NT * 64];
__device__ unsigned long long g_part[128 * 128];
constexpr int C_FLAG = 0, C_LOADED = 36, C_REG = 68, C_EXIT = 69, C_E = 70, C_NUM = 71;
__device__ __align__(128) unsigned g_ctr[C_NUM * 32];
#define PROF_T(i)
#define PROF_C(i)
#define PROF_V(i, v)
#define PROF_W(acc, stmt) stmt

__device__ __align__(128) const uint32_t g_Fimg[2048] = {
 0x3f803f80,0x3f7d3f7f,0x3f783f7b,0x3f713f75,0x3f673f6d,0x3f5c3f62,0x3f4e3f55,0x3f3e3f46,0x3f2c3f35,0x3f183f22,0x3f043f0e,0x3edb3ef1,0x3eac3ec4,0x3e793e95,0x3e163e48,0x3d493dc9,
 0xbd490000,0xbe16bdc9,0xbe79be48,0xbeacbe95,0xbedbbec4,0xbf04bef1,0xbf18bf0e,0xbf2cbf22,0xbf3ebf35,0xbf4ebf46,0xbf5cbf55,0xbf67bf62,0xbf71bf6d,0xbf78bf75,0xbf7dbf7b,0xbf80bf7f,
 0x3e793ec4,0xbd493dc9,0xbeacbe48,0xbf18bef1,0x3f7d3f80,0x3f673f75,0x3f3e3f55,0x3f043f22,0xbf5cbf6d,0xbf2cbf46,0xbedbbf0e,0xbe16be95,0xbf4ebf35,0xbf71bf62,0xbf80bf7b,0xbf78bf7f,
 0x3f783f6d,0x3f803f7f,0x3f713f7b,0x3f4e3f62,0x3e160000,0x3edb3e95,0x3f2c3f0e,0x3f5c3f46,0xbf04bec4,0xbf3ebf22,0xbf67bf55,0xbf7dbf75,0x3f183f35,0x3eac3ef1,0x3d493e48,0xbe79bdc9,
 0xbf04bf35,0xbd49be95,0x3edb3e48,0x3f4e3f22,0x3f7d3f6d,0x3f713f7f,0x3f2c3f55,0x3e793ef1,0x3f783f80,0x3f3e3f62,0x3eac3f0e,0xbe163dc9,0xbf18bec4,0xbf67bf46,0xbf80bf7b,0xbf5cbf75,
 0x3f5c3f35,0x3f803f75,0x3f673f7b,0x3f183f46,0x3e163ec4,0xbeacbdc9,0xbf3ebf0e,0xbf78bf62,0xbe790000,0xbf2cbef1,0xbf71bf55,0xbf7dbf7f,0xbf4ebf6d,0xbedbbf22,0x3d49be48,0x3f043e95,
 0xbf2cbec4,0xbf7dbf62,0xbf5cbf7b,0xbeacbf22,0x3f673f35,0x3f783f7f,0x3f183f55,0xbd493e95,0xbf80bf6d,0xbf4ebf75,0xbe79bf0e,0x3edb3dc9,0x3f713f80,0x3f043f46,0xbe163e48,0xbf3ebef1,
 0x3f3e3f6d,0x3e163ef1,0xbf04be48,0xbf71bf46,0xbedbbf35,0x3e79bdc9,0x3f4e3f0e,0x3f803f75,0x3d493ec4,0xbf18be95,0xbf78bf55,0xbf67bf7f,0x3eac0000,0x3f5c3f22,0x3f7d3f7b,0x3f2c3f62,
 0xbedb0000,0xbf78bf46,0xbf4ebf7b,0xbd49bef1,0x3f3e3ec4,0x3f7d3f75,0x3f043f55,0xbeac3dc9,0xbf71bf35,0xbf5cbf7f,0xbe16bf0e,0x3f2c3e95,0x3f803f6d,0x3f183f62,0xbe793e48,0xbf67bf22,
 0x3f673f80,0x3e793f22,0xbf18be48,0xbf80bf62,0xbf2cbf6d,0x3e16be95,0x3f5c3f0e,0x3f713f7f,0x3eac3f35,0xbf04bdc9,0xbf7dbf55,0xbf3ebf75,0x3d49bec4,0x3f4e3ef1,0x3f783f7b,0x3edb3f46,
 0xbf7dbf6d,0xbeacbf46,0x3f2c3e48,0x3f783f75,0x3f040000,0x3f803f62,0x3edb3f55,0xbf18bdc9,0x3f4e3ec4,0x3f673f7f,0x3d493f0e,0xbf5cbef1,0x3e793f35,0xbf3ebe95,0xbf71bf7b,0xbe16bf22,
 0x3e16bec4,0x3f713f22,0x3f3e3f7b,0xbe793e95,0x3f5c3f80,0xbd493ef1,0xbf67bf0e,0xbf4ebf7f,0x3f183f6d,0xbedb3dc9,0xbf80bf55,0xbf04bf62,0xbf78bf35,0xbf2cbf75,0x3eacbe48,0x3f7d3f46,
 0x3f7d3f35,0x3edb3f62,0xbf3ebe48,0xbf5cbf7f,0x3e79bec4,0x3f803f46,0x3eac3f55,0xbf4ebe95,0xbf180000,0xbf71bf75,0x3d49bf0e,0x3f783f22,0x3f043f6d,0xbf2cbdc9,0xbf67bf7b,0x3e16bef1,
 0xbe16bf35,0x3f673ef1,0x3f2c3f7b,0xbf043dc9,0xbf78bf6d,0xbd49bf22,0x3f713f0e,0x3f183f75,0x3f4e3f80,0xbeac3e95,0xbf80bf55,0xbe79bf46,0x3f5c3ec4,0x3f3e3f7f,0xbedb3e48,0xbf7dbf62,
 0xbedbbf6d,0x3f5c3e95,0x3f183f7b,0xbf3ebdc9,0xbd49bf35,0x3f7d3f22,0x3e793f55,0xbf71bef1,0x3eacbec4,0x3f783f62,0xbe163f0e,0xbf80bf46,0x3f2c0000,0x3f4e3f7f,0xbf043e48,0xbf67bf75,
 0x3f673ec4,0x3f043f75,0xbf4ebe48,0xbf2cbf7f,0x3f803f35,0x3e163f46,0xbf78bf0e,0xbeacbf62,0x3f713f6d,0xbe793ef1,0xbf7dbf55,0x3d49bf22,0x3f3e3f80,0xbf183dc9,0xbf5cbf7b,0x3edbbe95,
 0xbd490000,0xbe16bdc9,0xbe79be48,0xbeacbe95,0xbedbbec4,0xbf04bef1,0xbf18bf0e,0xbf2cbf22,0xbf3ebf35,0xbf4ebf46,0xbf5cbf55,0xbf67bf62,0xbf71bf6d,0xbf78bf75,0xbf7dbf7b,0xbf80bf7f,
 0xbf80bf80,0xbf7dbf7f,0xbf78bf7b,0xbf71bf75,0xbf67bf6d,0xbf5cbf62,0xbf4ebf55,0xbf3ebf46,0xbf2cbf35,0xbf18bf22,0xbf04bf0e,0xbedbbef1,0xbeacbec4,0xbe79be95,0xbe16be48,0xbd49bdc9,
 0xbf78bf6d,0xbf80bf7f,0xbf71bf7b,0xbf4ebf62,0xbe160000,0xbedbbe95,0xbf2cbf0e,0xbf5cbf46,0x3f043ec4,0x3f3e3f22,0x3f673f55,0x3f7d3f75,0xbf18bf35,0xbeacbef1,0xbd49be48,0x3e793dc9,
 0x3e793ec4,0xbd493dc9,0xbeacbe48,0xbf18bef1,0x3f7d3f80,0x3f673f75,0x3f3e3f55,0x3f043f22,0xbf5cbf6d,0xbf2cbf46,0xbedbbf0e,0xbe16be95,0xbf4ebf35,0xbf71bf62,0xbf80bf7b,0xbf78bf7f,
 0x3f5c3f35,0x3f803f75,0x3f673f7b,0x3f183f46,0x3e163ec4,0xbeacbdc9,0xbf3ebf0e,0xbf78bf62,0xbe790000,0xbf2cbef1,0xbf71bf55,0xbf7dbf7f,0xbf4ebf6d,0xbedbbf22,0x3d49be48,0x3f043e95,
 0x3f043f35,0x3d493e95,0xbedbbe48,0xbf4ebf22,0xbf7dbf6d,0xbf71bf7f,0xbf2cbf55,0xbe79bef1,0xbf78bf80,0xbf3ebf62,0xbeacbf0e,0x3e16bdc9,0x3f183ec4,0x3f673f46,0x3f803f7b,0x3f5c3f75,
 0xbf3ebf6d,0xbe16bef1,0x3f043e48,0x3f713f46,0x3edb3f35,0xbe793dc9,0xbf4ebf0e,0xbf80bf75,0xbd49bec4,0x3f183e95,0x3f783f55,0x3f673f7f,0xbeac0000,0xbf5cbf22,0xbf7dbf7b,0xbf2cbf62,
 0xbf2cbec4,0xbf7dbf62,0xbf5cbf7b,0xbeacbf22,0x3f673f35,0x3f783f7f,0x3f183f55,0xbd493e95,0xbf80bf6d,0xbf4ebf75,0xbe79bf0e,0x3edb3dc9,0x3f713f80,0x3f043f46,0xbe163e48,0xbf3ebef1,
 0xbf67bf80,0xbe79bf22,0x3f183e48,0x3f803f62,0x3f2c3f6d,0xbe163e95,0xbf5cbf0e,0xbf71bf7f,0xbeacbf35,0x3f043dc9,0x3f7d3f55,0x3f3e3f75,0xbd493ec4,0xbf4ebef1,0xbf78bf7b,0xbedbbf46,
 0xbedb0000,0xbf78bf46,0xbf4ebf7b,0xbd49bef1,0x3f3e3ec4,0x3f7d3f75,0x3f043f55,0xbeac3dc9,0xbf71bf35,0xbf5cbf7f,0xbe16bf0e,0x3f2c3e95,0x3f803f6d,0x3f183f62,0xbe793e48,0xbf67bf22,
 0x3e16bec4,0x3f713f22,0x3f3e3f7b,0xbe793e95,0x3f5c3f80,0xbd493ef1,0xbf67bf0e,0xbf4ebf7f,0x3f183f6d,0xbedb3dc9,0xbf80bf55,0xbf04bf62,0xbf78bf35,0xbf2cbf75,0x3eacbe48,0x3f7d3f46,
 0x3f7d3f6d,0x3eac3f46,0xbf2cbe48,0xbf78bf75,0xbf040000,0xbf80bf62,0xbedbbf55,0x3f183dc9,0xbf4ebec4,0xbf67bf7f,0xbd49bf0e,0x3f5c3ef1,0xbe79bf35,0x3f3e3e95,0x3f713f7b,0x3e163f22,
 0x3e163f35,0xbf67bef1,0xbf2cbf7b,0x3f04bdc9,0x3f783f6d,0x3d493f22,0xbf71bf0e,0xbf18bf75,0xbf4ebf80,0x3eacbe95,0x3f803f55,0x3e793f46,0xbf5cbec4,0xbf3ebf7f,0x3edbbe48,0x3f7d3f62,
 0x3f7d3f35,0x3edb3f62,0xbf3ebe48,0xbf5cbf7f,0x3e79bec4,0x3f803f46,0x3eac3f55,0xbf4ebe95,0xbf180000,0xbf71bf75,0x3d49bf0e,0x3f783f22,0x3f043f6d,0xbf2cbdc9,0xbf67bf7b,0x3e16bef1,
 0x3f673ec4,0x3f043f75,0xbf4ebe48,0xbf2cbf7f,0x3f803f35,0x3e163f46,0xbf78bf0e,0xbeacbf62,0x3f713f6d,0xbe793ef1,0xbf7dbf55,0x3d49bf22,0x3f3e3f80,0xbf183dc9,0xbf5cbf7b,0x3edbbe95,
 0x3edb3f6d,0xbf5cbe95,0xbf18bf7b,0x3f3e3dc9,0x3d493f35,0xbf7dbf22,0xbe79bf55,0x3f713ef1,0xbeac3ec4,0xbf78bf62,0x3e16bf0e,0x3f803f46,0xbf2c0000,0xbf4ebf7f,0x3f04be48,0x3f673f75,
 0x3f2c3f80,0xbf4ebdc9,0xbf04bf7b,0x3f673e95,0x3eac3f6d,0xbf78bef1,0xbe16bf55,0x3f803f22,0xbd493f35,0xbf7dbf46,0x3e79bf0e,0x3f713f62,0xbedb3ec4,0xbf5cbf75,0x3f18be48,0x3f3e3f7f,
 0xbf3e0000,0xbf18bf7f,0x3f5c3e48,0x3edb3f75,0xbf71bec4,0xbe79bf62,0x3f7d3f0e,0x3d493f46,0xbf80bf35,0x3e16bf22,0x3f783f55,0xbeac3ef1,0xbf67bf6d,0x3f04be95,0x3f4e3f7b,0xbf2c3dc9,
 0xbf043ec4,0xbf2cbf7f,0x3f673e48,0x3e163f62,0x3f183f80,0xbf71be95,0xbd49bf55,0x3f783f46,0xbe79bf6d,0x3f803f22,0xbeac3f0e,0xbf4ebf75,0xbf7dbf35,0x3edbbef1,0x3f3e3f7b,0xbf5cbdc9,
 0x3f5c3f6d,0xbf3e3dc9,0xbedbbf7b,0x3f7d3ef1,0x3f4e0000,0x3eac3f75,0xbf80bf0e,0x3e79bf22,0xbf78bec4,0x3d49bf46,0x3f713f55,0xbf183e95,0xbe163f35,0xbf67bf62,0x3f2cbe48,0x3f043f7f,
 0x3e79bf35,0x3f3e3f75,0xbf71be48,0x3e16bf46,0x3f4e3f6d,0xbf67bdc9,0x3d49bf55,0x3f5c3f62,0x3f043f80,0xbf80bef1,0x3edbbf0e,0x3f183f7f,0xbf7dbec4,0x3eacbf22,0x3f2c3f7b,0xbf78be95,
 0x3f783f35,0xbf2c3e95,0xbeacbf7b,0x3f7d3f22,0xbf183ec4,0xbedbbf7f,0x3f803f0e,0xbf043ef1,0xbf5c0000,0xbd49bf62,0x3f673f55,0xbf4e3dc9,0xbe16bf6d,0x3f713f46,0xbf3e3e48,0xbe79bf75,
 0xbf80bec4,0x3f18bef1,0x3e793f7b,0xbf67bf46,0x3f713f35,0xbf5c3dc9,0x3e16bf55,0x3f2c3f75,0xbf3ebf6d,0x3f7d3e95,0xbf043f0e,0xbeacbf7f,0x3edb3f80,0xbf78bf22,0x3f4ebe48,0xbd493f62,
 0x3d493f6d,0xbf4ebf62,0x3f783e48,0xbedb3f22,0x3eacbf35,0x3f043f7f,0xbf7dbf0e,0x3f3ebe95,0xbf2c3ec4,0xbe16bf75,0x3f5c3f55,0xbf71bdc9,0x3f670000,0xbe793f46,0xbf18bf7b,0x3f803ef1,
 0xbf710000,0x3f04bf22,0x3e163f7b,0xbf3ebf62,0x3f803ec4,0xbf4e3e95,0x3e79bf55,0x3edb3f7f,0xbf67bf35,0x3f783dc9,0xbf183f0e,0xbd49bf75,0x3f2c3f6d,0xbf7dbef1,0x3f5cbe48,0xbeac3f46,
 0x3eac3f80,0xbf5cbf46,0x3f7d3e48,0xbf2c3ef1,0x3d49bf6d,0x3f183f75,0xbf78bf0e,0x3f67bdc9,0xbedb3f35,0xbe79bf7f,0x3f4e3f55,0xbf80be95,0x3f3ebec4,0xbe163f62,0xbf04bf7b,0x3f713f22,
 0xbf18bf6d,0x3f673f22,0xbf80be48,0x3f5cbe95,0x3f780000,0xbf3e3ef1,0x3eacbf55,0x3e163f7f,0x3f7d3ec4,0xbf713dc9,0x3f2cbf0e,0xbe793f62,0xbf043f35,0x3d49bf75,0x3edb3f7b,0xbf4ebf46,
 0x3f4ebec4,0xbedb3f46,0xbd49bf7b,0x3f043f75,0x3e793f80,0xbf2cbf62,0x3f713f0e,0xbf7dbdc9,0xbe163f6d,0xbeacbf7f,0x3f3e3f55,0xbf78bef1,0xbf5cbf35,0x3f803e95,0xbf673e48,0x3f18bf22,
 0x3f4e3f35,0xbf71bef1,0x3f803e48,0xbf783dc9,0x3f5cbec4,0xbf2c3f22,0x3edbbf55,0xbe163f75,0xbf7d0000,0x3f67be95,0xbf3e3f0e,0x3f04bf46,0xbe793f6d,0xbd49bf7f,0x3eac3f7b,0xbf18bf62,
 0x3f18bf35,0xbeac3f62,0x3d49bf7b,0x3e793f7f,0xbf04bf6d,0x3f3e3f46,0xbf67bf0e,0x3f7d3e95,0x3e163f80,0xbedbbf75,0x3f2c3f55,0xbf5cbf22,0x3f783ec4,0xbf80bdc9,0x3f71be48,0xbf4e3ef1,
 0x3eacbf6d,0xbe793f75,0x3e16bf7b,0xbd493f7f,0x3f2cbf35,0xbf183f46,0x3f04bf55,0xbedb3f62,0x3f67bec4,0xbf5c3ef1,0x3f4ebf0e,0xbf3e3f22,0x3f800000,0xbf7d3dc9,0x3f78be48,0xbf713e95,
 0x3f713ec4,0xbf78be95,0x3f7d3e48,0xbf80bdc9,0x3f3e3f35,0xbf4ebf22,0x3f5c3f0e,0xbf67bef1,0x3edb3f6d,0xbf04bf62,0x3f183f55,0xbf2cbf46,0x3d493f80,0xbe16bf7f,0x3e793f7b,0xbeacbf75,
 0xbf3e0000,0xbf18bf7f,0x3f5c3e48,0x3edb3f75,0xbf71bec4,0xbe79bf62,0x3f7d3f0e,0x3d493f46,0xbf80bf35,0x3e16bf22,0x3f783f55,0xbeac3ef1,0xbf67bf6d,0x3f04be95,0x3f4e3f7b,0xbf2c3dc9,
 0xbf2cbf80,0x3f4e3dc9,0x3f043f7b,0xbf67be95,0xbeacbf6d,0x3f783ef1,0x3e163f55,0xbf80bf22,0x3d49bf35,0x3f7d3f46,0xbe793f0e,0xbf71bf62,0x3edbbec4,0x3f5c3f75,0xbf183e48,0xbf3ebf7f,
 0xbf5cbf6d,0x3f3ebdc9,0x3edb3f7b,0xbf7dbef1,0xbf4e0000,0xbeacbf75,0x3f803f0e,0xbe793f22,0x3f783ec4,0xbd493f46,0xbf71bf55,0x3f18be95,0x3e16bf35,0x3f673f62,0xbf2c3e48,0xbf04bf7f,
 0xbf043ec4,0xbf2cbf7f,0x3f673e48,0x3e163f62,0x3f183f80,0xbf71be95,0xbd49bf55,0x3f783f46,0xbe79bf6d,0x3f803f22,0xbeac3f0e,0xbf4ebf75,0xbf7dbf35,0x3edbbef1,0x3f3e3f7b,0xbf5cbdc9,
 0x3f783f35,0xbf2c3e95,0xbeacbf7b,0x3f7d3f22,0xbf183ec4,0xbedbbf7f,0x3f803f0e,0xbf043ef1,0xbf5c0000,0xbd49bf62,0x3f673f55,0xbf4e3dc9,0xbe16bf6d,0x3f713f46,0xbf3e3e48,0xbe79bf75,
 0xbe793f35,0xbf3ebf75,0x3f713e48,0xbe163f46,0xbf4ebf6d,0x3f673dc9,0xbd493f55,0xbf5cbf62,0xbf04bf80,0x3f803ef1,0xbedb3f0e,0xbf18bf7f,0x3f7d3ec4,0xbeac3f22,0xbf2cbf7b,0x3f783e95,
 0xbd49bf6d,0x3f4e3f62,0xbf78be48,0x3edbbf22,0xbeac3f35,0xbf04bf7f,0x3f7d3f0e,0xbf3e3e95,0x3f2cbec4,0x3e163f75,0xbf5cbf55,0x3f713dc9,0xbf670000,0x3e79bf46,0x3f183f7b,0xbf80bef1,
 0xbf80bec4,0x3f18bef1,0x3e793f7b,0xbf67bf46,0x3f713f35,0xbf5c3dc9,0x3e16bf55,0x3f2c3f75,0xbf3ebf6d,0x3f7d3e95,0xbf043f0e,0xbeacbf7f,0x3edb3f80,0xbf78bf22,0x3f4ebe48,0xbd493f62,
 0xbeacbf80,0x3f5c3f46,0xbf7dbe48,0x3f2cbef1,0xbd493f6d,0xbf18bf75,0x3f783f0e,0xbf673dc9,0x3edbbf35,0x3e793f7f,0xbf4ebf55,0x3f803e95,0xbf3e3ec4,0x3e16bf62,0x3f043f7b,0xbf71bf22,
 0xbf710000,0x3f04bf22,0x3e163f7b,0xbf3ebf62,0x3f803ec4,0xbf4e3e95,0x3e79bf55,0x3edb3f7f,0xbf67bf35,0x3f783dc9,0xbf183f0e,0xbd49bf75,0x3f2c3f6d,0xbf7dbef1,0x3f5cbe48,0xbeac3f46,
 0x3f4ebec4,0xbedb3f46,0xbd49bf7b,0x3f043f75,0x3e793f80,0xbf2cbf62,0x3f713f0e,0xbf7dbdc9,0xbe163f6d,0xbeacbf7f,0x3f3e3f55,0xbf78bef1,0xbf5cbf35,0x3f803e95,0xbf673e48,0x3f18bf22,
 0x3f183f6d,0xbf67bf22,0x3f803e48,0xbf5c3e95,0xbf780000,0x3f3ebef1,0xbeac3f55,0xbe16bf7f,0xbf7dbec4,0x3f71bdc9,0xbf2c3f0e,0x3e79bf62,0x3f04bf35,0xbd493f75,0xbedbbf7b,0x3f4e3f46,
 0xbf183f35,0x3eacbf62,0xbd493f7b,0xbe79bf7f,0x3f043f6d,0xbf3ebf46,0x3f673f0e,0xbf7dbe95,0xbe16bf80,0x3edb3f75,0xbf2cbf55,0x3f5c3f22,0xbf78bec4,0x3f803dc9,0xbf713e48,0x3f4ebef1,
 0x3f4e3f35,0xbf71bef1,0x3f803e48,0xbf783dc9,0x3f5cbec4,0xbf2c3f22,0x3edbbf55,0xbe163f75,0xbf7d0000,0x3f67be95,0xbf3e3f0e,0x3f04bf46,0xbe793f6d,0xbd49bf7f,0x3eac3f7b,0xbf18bf62,
 0x3f713ec4,0xbf78be95,0x3f7d3e48,0xbf80bdc9,0x3f3e3f35,0xbf4ebf22,0x3f5c3f0e,0xbf67bef1,0x3edb3f6d,0xbf04bf62,0x3f183f55,0xbf2cbf46,0x3d493f80,0xbe16bf7f,0x3e793f7b,0xbeacbf75,
 0xbeac3f6d,0x3e79bf75,0xbe163f7b,0x3d49bf7f,0xbf2c3f35,0x3f18bf46,0xbf043f55,0x3edbbf62,0xbf673ec4,0x3f5cbef1,0xbf4e3f0e,0x3f3ebf22,0xbf800000,0x3f7dbdc9,0xbf783e48,0x3f71be95,
 0xbd493f80,0x3e16bf7f,0xbe793f7b,0x3eacbf75,0xbedb3f6d,0x3f04bf62,0xbf183f55,0x3f2cbf46,0xbf3e3f35,0x3f4ebf22,0xbf5c3f0e,0x3f67bef1,0xbf713ec4,0x3f78be95,0xbf7d3e48,0x3f80bdc9,
 0xbf800000,0x3f7d3dc9,0xbf78be48,0x3f713e95,0xbf67bec4,0x3f5c3ef1,0xbf4ebf0e,0x3f3e3f22,0xbf2cbf35,0x3f183f46,0xbf04bf55,0x3edb3f62,0xbeacbf6d,0x3e793f75,0xbe16bf7b,0x3d493f7f,
 0xbf783ec4,0x3f80bdc9,0xbf71be48,0x3f4e3ef1,0xbe163f80,0x3edbbf75,0xbf2c3f55,0x3f5cbf22,0x3f04bf6d,0xbf3e3f46,0x3f67bf0e,0xbf7d3e95,0xbf18bf35,0x3eac3f62,0xbd49bf7b,0xbe793f7f,
 0x3e793f6d,0x3d49bf7f,0xbeac3f7b,0x3f18bf62,0x3f7d0000,0xbf67be95,0x3f3e3f0e,0xbf04bf46,0xbf5cbec4,0x3f2c3f22,0xbedbbf55,0x3e163f75,0xbf4e3f35,0x3f71bef1,0xbf803e48,0x3f783dc9,
 0x3f5cbf35,0xbf803e95,0x3f673e48,0xbf18bf22,0x3e163f6d,0x3eacbf7f,0xbf3e3f55,0x3f78bef1,0xbe793f80,0x3f2cbf62,0xbf713f0e,0x3f7dbdc9,0xbf4ebec4,0x3edb3f46,0x3d49bf7b,0xbf043f75,
 0x3f043f35,0xbd49bf75,0xbedb3f7b,0x3f4ebf46,0xbf7d3ec4,0x3f713dc9,0xbf2cbf0e,0x3e793f62,0xbf780000,0x3f3e3ef1,0xbeacbf55,0xbe163f7f,0x3f18bf6d,0xbf673f22,0x3f80be48,0xbf5cbe95,
 0xbf3ebec4,0x3e163f62,0x3f04bf7b,0xbf713f22,0x3edb3f35,0x3e79bf7f,0xbf4e3f55,0x3f80be95,0xbd49bf6d,0xbf183f75,0x3f78bf0e,0xbf67bdc9,0xbeac3f80,0x3f5cbf46,0xbf7d3e48,0x3f2c3ef1,
 0xbf2c3f6d,0x3f7dbef1,0xbf5cbe48,0x3eac3f46,0x3f67bf35,0xbf783dc9,0x3f183f0e,0x3d49bf75,0xbf803ec4,0x3f4e3e95,0xbe79bf55,0xbedb3f7f,0x3f710000,0xbf04bf22,0xbe163f7b,0x3f3ebf62,
 0xbf670000,0x3e793f46,0x3f18bf7b,0xbf803ef1,0x3f2c3ec4,0x3e16bf75,0xbf5c3f55,0x3f71bdc9,0xbeacbf35,0xbf043f7f,0x3f7dbf0e,0xbf3ebe95,0xbd493f6d,0x3f4ebf62,0xbf783e48,0x3edb3f22,
 0xbedb3f80,0x3f78bf22,0xbf4ebe48,0x3d493f62,0x3f3ebf6d,0xbf7d3e95,0x3f043f0e,0x3eacbf7f,0xbf713f35,0x3f5c3dc9,0xbe16bf55,0xbf2c3f75,0x3f80bec4,0xbf18bef1,0xbe793f7b,0x3f67bf46,
 0x3e16bf6d,0xbf713f46,0x3f3e3e48,0x3e79bf75,0x3f5c0000,0x3d49bf62,0xbf673f55,0x3f4e3dc9,0x3f183ec4,0x3edbbf7f,0xbf803f0e,0x3f043ef1,0xbf783f35,0x3f2c3e95,0x3eacbf7b,0xbf7d3f22,
 0x3f7dbec4,0xbeacbf22,0xbf2c3f7b,0x3f78be95,0xbf043f80,0x3f80bef1,0xbedbbf0e,0xbf183f7f,0xbf4e3f6d,0x3f67bdc9,0xbd49bf55,0xbf5c3f62,0xbe79bf35,0xbf3e3f75,0x3f71be48,0xbe16bf46,
 0x3e163f35,0x3f67bf62,0xbf2cbe48,0xbf043f7f,0x3f78bec4,0xbd49bf46,0xbf713f55,0x3f183e95,0xbf4e0000,0xbeac3f75,0x3f80bf0e,0xbe79bf22,0xbf5c3f6d,0x3f3e3dc9,0x3edbbf7b,0xbf7d3ef1,
 0x3f7dbf35,0xbedbbef1,0xbf3e3f7b,0x3f5cbdc9,0x3e79bf6d,0xbf803f22,0x3eac3f0e,0x3f4ebf75,0xbf183f80,0x3f71be95,0x3d49bf55,0xbf783f46,0x3f043ec4,0x3f2cbf7f,0xbf673e48,0xbe163f62,
 0x3f67bf6d,0xbf04be95,0xbf4e3f7b,0x3f2c3dc9,0x3f80bf35,0xbe16bf22,0xbf783f55,0x3eac3ef1,0x3f71bec4,0x3e79bf62,0xbf7d3f0e,0xbd493f46,0x3f3e0000,0x3f18bf7f,0xbf5c3e48,0xbedb3f75,
 0x3edb3ec4,0x3f5cbf75,0xbf18be48,0xbf3e3f7f,0x3d493f35,0x3f7dbf46,0xbe79bf0e,0xbf713f62,0xbeac3f6d,0x3f78bef1,0x3e16bf55,0xbf803f22,0xbf2c3f80,0x3f4ebdc9,0x3f04bf7b,0xbf673e95,
 0xbf800000,0x3f7d3dc9,0xbf78be48,0x3f713e95,0xbf67bec4,0x3f5c3ef1,0xbf4ebf0e,0x3f3e3f22,0xbf2cbf35,0x3f183f46,0xbf04bf55,0x3edb3f62,0xbeacbf6d,0x3e793f75,0xbe16bf7b,0x3d493f7f,
 0x3d49bf80,0xbe163f7f,0x3e79bf7b,0xbeac3f75,0x3edbbf6d,0xbf043f62,0x3f18bf55,0xbf2c3f46,0x3f3ebf35,0xbf4e3f22,0x3f5cbf0e,0xbf673ef1,0x3f71bec4,0xbf783e95,0x3f7dbe48,0xbf803dc9,
 0xbe79bf6d,0xbd493f7f,0x3eacbf7b,0xbf183f62,0xbf7d0000,0x3f673e95,0xbf3ebf0e,0x3f043f46,0x3f5c3ec4,0xbf2cbf22,0x3edb3f55,0xbe16bf75,0x3f4ebf35,0xbf713ef1,0x3f80be48,0xbf78bdc9,
 0xbf783ec4,0x3f80bdc9,0xbf71be48,0x3f4e3ef1,0xbe163f80,0x3edbbf75,0xbf2c3f55,0x3f5cbf22,0x3f04bf6d,0xbf3e3f46,0x3f67bf0e,0xbf7d3e95,0xbf18bf35,0x3eac3f62,0xbd49bf7b,0xbe793f7f,
 0x3f043f35,0xbd49bf75,0xbedb3f7b,0x3f4ebf46,0xbf7d3ec4,0x3f713dc9,0xbf2cbf0e,0x3e793f62,0xbf780000,0x3f3e3ef1,0xbeacbf55,0xbe163f7f,0x3f18bf6d,0xbf673f22,0x3f80be48,0xbf5cbe95,
 0xbf5c3f35,0x3f80be95,0xbf67be48,0x3f183f22,0xbe16bf6d,0xbeac3f7f,0x3f3ebf55,0xbf783ef1,0x3e79bf80,0xbf2c3f62,0x3f71bf0e,0xbf7d3dc9,0x3f4e3ec4,0xbedbbf46,0xbd493f7b,0x3f04bf75,
 0x3f2cbf6d,0xbf7d3ef1,0x3f5c3e48,0xbeacbf46,0xbf673f35,0x3f78bdc9,0xbf18bf0e,0xbd493f75,0x3f80bec4,0xbf4ebe95,0x3e793f55,0x3edbbf7f,0xbf710000,0x3f043f22,0x3e16bf7b,0xbf3e3f62,
 0xbf3ebec4,0x3e163f62,0x3f04bf7b,0xbf713f22,0x3edb3f35,0x3e79bf7f,0xbf4e3f55,0x3f80be95,0xbd49bf6d,0xbf183f75,0x3f78bf0e,0xbf67bdc9,0xbeac3f80,0x3f5cbf46,0xbf7d3e48,0x3f2c3ef1,
 0x3edbbf80,0xbf783f22,0x3f4e3e48,0xbd49bf62,0xbf3e3f6d,0x3f7dbe95,0xbf04bf0e,0xbeac3f7f,0x3f71bf35,0xbf5cbdc9,0x3e163f55,0x3f2cbf75,0xbf803ec4,0x3f183ef1,0x3e79bf7b,0xbf673f46,
 0xbf670000,0x3e793f46,0x3f18bf7b,0xbf803ef1,0x3f2c3ec4,0x3e16bf75,0xbf5c3f55,0x3f71bdc9,0xbeacbf35,0xbf043f7f,0x3f7dbf0e,0xbf3ebe95,0xbd493f6d,0x3f4ebf62,0xbf783e48,0x3edb3f22,
 0x3f7dbec4,0xbeacbf22,0xbf2c3f7b,0x3f78be95,0xbf043f80,0x3f80bef1,0xbedbbf0e,0xbf183f7f,0xbf4e3f6d,0x3f67bdc9,0xbd49bf55,0xbf5c3f62,0xbe79bf35,0xbf3e3f75,0x3f71be48,0xbe16bf46,
 0xbe163f6d,0x3f71bf46,0xbf3ebe48,0xbe793f75,0xbf5c0000,0xbd493f62,0x3f67bf55,0xbf4ebdc9,0xbf18bec4,0xbedb3f7f,0x3f80bf0e,0xbf04bef1,0x3f78bf35,0xbf2cbe95,0xbeac3f7b,0x3f7dbf22,
 0xbf7d3f35,0x3edb3ef1,0x3f3ebf7b,0xbf5c3dc9,0xbe793f6d,0x3f80bf22,0xbeacbf0e,0xbf4e3f75,0x3f18bf80,0xbf713e95,0xbd493f55,0x3f78bf46,0xbf04bec4,0xbf2c3f7f,0x3f67be48,0x3e16bf62,
 0x3e163f35,0x3f67bf62,0xbf2cbe48,0xbf043f7f,0x3f78bec4,0xbd49bf46,0xbf713f55,0x3f183e95,0xbf4e0000,0xbeac3f75,0x3f80bf0e,0xbe79bf22,0xbf5c3f6d,0x3f3e3dc9,0x3edbbf7b,0xbf7d3ef1,
 0x3edb3ec4,0x3f5cbf75,0xbf18be48,0xbf3e3f7f,0x3d493f35,0x3f7dbf46,0xbe79bf0e,0xbf713f62,0xbeac3f6d,0x3f78bef1,0x3e16bf55,0xbf803f22,0xbf2c3f80,0x3f4ebdc9,0x3f04bf7b,0xbf673e95,
 0xbf673f6d,0x3f043e95,0x3f4ebf7b,0xbf2cbdc9,0xbf803f35,0x3e163f22,0x3f78bf55,0xbeacbef1,0xbf713ec4,0xbe793f62,0x3f7dbf0e,0x3d49bf46,0xbf3e0000,0xbf183f7f,0x3f5cbe48,0x3edbbf75,
 0xbf3e3f80,0x3f183dc9,0x3f5cbf7b,0xbedbbe95,0xbf713f6d,0x3e793ef1,0x3f7dbf55,0xbd49bf22,0xbf803f35,0xbe163f46,0x3f78bf0e,0x3eacbf62,0xbf673ec4,0xbf043f75,0x3f4ebe48,0x3f2cbf7f,
 0xbf2c0000,0xbf4e3f7f,0x3f043e48,0x3f67bf75,0xbeacbec4,0xbf783f62,0x3e163f0e,0x3f80bf46,0x3d49bf35,0xbf7d3f22,0xbe793f55,0x3f71bef1,0x3edbbf6d,0xbf5c3e95,0xbf183f7b,0x3f3ebdc9,
 0xbf5c3ec4,0xbf3e3f7f,0x3edb3e48,0x3f7dbf62,0xbf4e3f80,0x3eac3e95,0x3f80bf55,0x3e79bf46,0x3f78bf6d,0x3d49bf22,0xbf713f0e,0xbf183f75,0x3e16bf35,0xbf673ef1,0xbf2c3f7b,0x3f043dc9,
 0xbf043f6d,0x3f2cbdc9,0x3f67bf7b,0xbe16bef1,0x3f180000,0x3f71bf75,0xbd49bf0e,0xbf783f22,0xbe79bec4,0xbf803f46,0xbeac3f55,0x3f4ebe95,0xbf7d3f35,0xbedb3f62,0x3f3ebe48,0x3f5cbf7f,
 0x3f78bf35,0x3f2cbf75,0xbeacbe48,0xbf7d3f46,0xbf183f6d,0x3edb3dc9,0x3f80bf55,0x3f04bf62,0xbf5c3f80,0x3d493ef1,0x3f67bf0e,0x3f4ebf7f,0xbe16bec4,0xbf713f22,0xbf3e3f7b,0x3e793e95,
 0xbe793f35,0x3f3ebe95,0x3f71bf7b,0x3e16bf22,0xbf4e3ec4,0xbf673f7f,0xbd493f0e,0x3f5cbef1,0xbf040000,0xbf803f62,0xbedb3f55,0x3f18bdc9,0x3f7dbf6d,0x3eacbf46,0xbf2c3e48,0xbf783f75,
 0xbd49bec4,0xbf4e3ef1,0xbf783f7b,0xbedb3f46,0xbeac3f35,0x3f04bdc9,0x3f7dbf55,0x3f3ebf75,0x3f2cbf6d,0xbe16be95,0xbf5c3f0e,0xbf713f7f,0xbf673f80,0xbe793f22,0x3f18be48,0x3f80bf62,
 0xbf803f6d,0xbf183f62,0x3e793e48,0x3f67bf22,0x3f71bf35,0x3f5cbf7f,0x3e16bf0e,0xbf2c3e95,0xbf3e3ec4,0xbf7d3f75,0xbf043f55,0x3eac3dc9,0x3edb0000,0x3f78bf46,0x3f4ebf7b,0x3d49bef1,
 0xbeac0000,0xbf5c3f22,0xbf7d3f7b,0xbf2c3f62,0xbd493ec4,0x3f18be95,0x3f78bf55,0x3f67bf7f,0x3edbbf35,0xbe79bdc9,0xbf4e3f0e,0xbf803f75,0xbf3e3f6d,0xbe163ef1,0x3f04be48,0x3f71bf46,
 0xbf713f80,0xbf043f46,0x3e163e48,0x3f3ebef1,0x3f80bf6d,0x3f4ebf75,0x3e79bf0e,0xbedb3dc9,0xbf673f35,0xbf783f7f,0xbf183f55,0x3d493e95,0x3f2cbec4,0x3f7dbf62,0x3f5cbf7b,0x3eacbf22,
 0x3f4ebf6d,0x3edbbf22,0xbd49be48,0xbf043e95,0x3e790000,0x3f2cbef1,0x3f71bf55,0x3f7dbf7f,0xbe163ec4,0x3eacbdc9,0x3f3ebf0e,0x3f78bf62,0xbf5c3f35,0xbf803f75,0xbf673f7b,0xbf183f46,
 0x3f18bec4,0x3f67bf46,0x3f80bf7b,0x3f5cbf75,0xbf783f80,0xbf3e3f62,0xbeac3f0e,0x3e163dc9,0xbf7d3f6d,0xbf713f7f,0xbf2c3f55,0xbe793ef1,0x3f04bf35,0x3d49be95,0xbedb3e48,0xbf4e3f22,
 0xbf183f35,0xbeac3ef1,0xbd493e48,0x3e79bdc9,0x3f04bec4,0x3f3ebf22,0x3f67bf55,0x3f7dbf75,0xbe160000,0xbedb3e95,0xbf2c3f0e,0xbf5c3f46,0xbf783f6d,0xbf803f7f,0xbf713f7b,0xbf4e3f62,
 0x3f4ebf35,0x3f71bf62,0x3f80bf7b,0x3f78bf7f,0x3f5cbf6d,0x3f2cbf46,0x3edbbf0e,0x3e16be95,0xbf7d3f80,0xbf673f75,0xbf3e3f55,0xbf043f22,0xbe793ec4,0x3d493dc9,0x3eacbe48,0x3f18bef1,
 0x3f71bf6d,0x3f78bf75,0x3f7dbf7b,0x3f80bf7f,0x3f3ebf35,0x3f4ebf46,0x3f5cbf55,0x3f67bf62,0x3edbbec4,0x3f04bef1,0x3f18bf0e,0x3f2cbf22,0x3d490000,0x3e16bdc9,0x3e79be48,0x3eacbe95,
 0xbeac3ec4,0xbe793e95,0xbe163e48,0xbd493dc9,0xbf2c3f35,0xbf183f22,0xbf043f0e,0xbedb3ef1,0xbf673f6d,0xbf5c3f62,0xbf4e3f55,0xbf3e3f46,0xbf803f80,0xbf7d3f7f,0xbf783f7b,0xbf713f75,
 0xbf2c0000,0xbf4e3f7f,0x3f043e48,0x3f67bf75,0xbeacbec4,0xbf783f62,0x3e163f0e,0x3f80bf46,0x3d49bf35,0xbf7d3f22,0xbe793f55,0x3f71bef1,0x3edbbf6d,0xbf5c3e95,0xbf183f7b,0x3f3ebdc9,
 0x3f3ebf80,0xbf18bdc9,0xbf5c3f7b,0x3edb3e95,0x3f71bf6d,0xbe79bef1,0xbf7d3f55,0x3d493f22,0x3f80bf35,0x3e16bf46,0xbf783f0e,0xbeac3f62,0x3f67bec4,0x3f04bf75,0xbf4e3e48,0xbf2c3f7f,
 0x3f04bf6d,0xbf2c3dc9,0xbf673f7b,0x3e163ef1,0xbf180000,0xbf713f75,0x3d493f0e,0x3f78bf22,0x3e793ec4,0x3f80bf46,0x3eacbf55,0xbf4e3e95,0x3f7dbf35,0x3edbbf62,0xbf3e3e48,0xbf5c3f7f,
 0xbf5c3ec4,0xbf3e3f7f,0x3edb3e48,0x3f7dbf62,0xbf4e3f80,0x3eac3e95,0x3f80bf55,0x3e79bf46,0x3f78bf6d,0x3d49bf22,0xbf713f0e,0xbf183f75,0x3e16bf35,0xbf673ef1,0xbf2c3f7b,0x3f043dc9,
 0xbe793f35,0x3f3ebe95,0x3f71bf7b,0x3e16bf22,0xbf4e3ec4,0xbf673f7f,0xbd493f0e,0x3f5cbef1,0xbf040000,0xbf803f62,0xbedb3f55,0x3f18bdc9,0x3f7dbf6d,0x3eacbf46,0xbf2c3e48,0xbf783f75,
 0xbf783f35,0xbf2c3f75,0x3eac3e48,0x3f7dbf46,0x3f18bf6d,0xbedbbdc9,0xbf803f55,0xbf043f62,0x3f5cbf80,0xbd49bef1,0xbf673f0e,0xbf4e3f7f,0x3e163ec4,0x3f71bf22,0x3f3ebf7b,0xbe79be95,
 0x3f80bf6d,0x3f18bf62,0xbe79be48,0xbf673f22,0xbf713f35,0xbf5c3f7f,0xbe163f0e,0x3f2cbe95,0x3f3ebec4,0x3f7dbf75,0x3f04bf55,0xbeacbdc9,0xbedb0000,0xbf783f46,0xbf4e3f7b,0xbd493ef1,
 0xbd49bec4,0xbf4e3ef1,0xbf783f7b,0xbedb3f46,0xbeac3f35,0x3f04bdc9,0x3f7dbf55,0x3f3ebf75,0x3f2cbf6d,0xbe16be95,0xbf5c3f0e,0xbf713f7f,0xbf673f80,0xbe793f22,0x3f18be48,0x3f80bf62,
 0x3f71bf80,0x3f04bf46,0xbe16be48,0xbf3e3ef1,0xbf803f6d,0xbf4e3f75,0xbe793f0e,0x3edbbdc9,0x3f67bf35,0x3f78bf7f,0x3f18bf55,0xbd49be95,0xbf2c3ec4,0xbf7d3f62,0xbf5c3f7b,0xbeac3f22,
 0xbeac0000,0xbf5c3f22,0xbf7d3f7b,0xbf2c3f62,0xbd493ec4,0x3f18be95,0x3f78bf55,0x3f67bf7f,0x3edbbf35,0xbe79bdc9,0xbf4e3f0e,0xbf803f75,0xbf3e3f6d,0xbe163ef1,0x3f04be48,0x3f71bf46,
 0x3f18bec4,0x3f67bf46,0x3f80bf7b,0x3f5cbf75,0xbf783f80,0xbf3e3f62,0xbeac3f0e,0x3e163dc9,0xbf7d3f6d,0xbf713f7f,0xbf2c3f55,0xbe793ef1,0x3f04bf35,0x3d49be95,0xbedb3e48,0xbf4e3f22,
 0xbf4e3f6d,0xbedb3f22,0x3d493e48,0x3f04be95,0xbe790000,0xbf2c3ef1,0xbf713f55,0xbf7d3f7f,0x3e16bec4,0xbeac3dc9,0xbf3e3f0e,0xbf783f62,0x3f5cbf35,0x3f80bf75,0x3f67bf7b,0x3f18bf46,
 0xbf4e3f35,0xbf713f62,0xbf803f7b,0xbf783f7f,0xbf5c3f6d,0xbf2c3f46,0xbedb3f0e,0xbe163e95,0x3f7dbf80,0x3f67bf75,0x3f3ebf55,0x3f04bf22,0x3e79bec4,0xbd49bdc9,0xbeac3e48,0xbf183ef1,
 0xbf183f35,0xbeac3ef1,0xbd493e48,0x3e79bdc9,0x3f04bec4,0x3f3ebf22,0x3f67bf55,0x3f7dbf75,0xbe160000,0xbedb3e95,0xbf2c3f0e,0xbf5c3f46,0xbf783f6d,0xbf803f7f,0xbf713f7b,0xbf4e3f62,
 0xbeac3ec4,0xbe793e95,0xbe163e48,0xbd493dc9,0xbf2c3f35,0xbf183f22,0xbf043f0e,0xbedb3ef1,0xbf673f6d,0xbf5c3f62,0xbf4e3f55,0xbf3e3f46,0xbf803f80,0xbf7d3f7f,0xbf783f7b,0xbf713f75,
 0xbf713f6d,0xbf783f75,0xbf7d3f7b,0xbf803f7f,0xbf3e3f35,0xbf4e3f46,0xbf5c3f55,0xbf673f62,0xbedb3ec4,0xbf043ef1,0xbf183f0e,0xbf2c3f22,0xbd490000,0xbe163dc9,0xbe793e48,0xbeac3e95,
};
__device__ __align__(128) const uint32_t g_Gimg[1792] = {
 0x00003d00,0x00003d00,0x00003d00,0x00003d00,0x00003d00,0x00003d00,0x00003d00,0x00003d00,0x00003d00,0x00003d00,0x00003d00,0x00003d00,0x00003d00,0x00003d00,0x00003d00,0x00003d00,
 0x00003d00,0x00003d00,0x00003d00,0x00003d00,0x00003d00,0x00003d00,0x00003d00,0x00003d00,0x00003d00,0x00003d00,0x00003d00,0x00003d00,0x00003d00,0x00003d00,0x00003d00,0x00003d00,
 0xbc5b3ce7,0xbc843cdc,0xbc983cce,0xbcac3cbe,0xbac93d00,0xbb963cfd,0xbbf93cf8,0xbc2c3cf1,0xbcf13c2c,0xbcf83bf9,0xbcfd3b96,0xbd003ac9,0xbcbe3cac,0xbcce3c98,0xbcdc3c84,0xbce73c5b,
 0xbce7bc5b,0xbcdcbc84,0xbccebc98,0xbcbebcac,0xbd00bac9,0xbcfdbb96,0xbcf8bbf9,0xbcf1bc2c,0xbc2cbcf1,0xbbf9bcf8,0xbb96bcfd,0xbac9bd00,0xbcacbcbe,0xbc98bcce,0xbc84bcdc,0xbc5bbce7,
 0xbcffbb49,0xbcf5bc15,0xbce2bc71,0xbcc6bca2,0xbca2bcc6,0xbc71bce2,0xbc15bcf5,0xbb49bcff,0xbb493cff,0xbc153cf5,0xbc713ce2,0xbca23cc6,0xbcc63ca2,0xbce23c71,0xbcf53c15,0xbcff3b49,
 0x3cff3b49,0x3cf53c15,0x3ce23c71,0x3cc63ca2,0x3ca23cc6,0x3c713ce2,0x3c153cf5,0x3b493cff,0x3b49bcff,0x3c15bcf5,0x3c71bce2,0x3ca2bcc6,0x3cc6bca2,0x3ce2bc71,0x3cf5bc15,0x3cffbb49,
 0x3c84bcdc,0x3cbebcac,0x3ce7bc5b,0x3cfdbb96,0xbc98bcce,0xbc2cbcf1,0xbac9bd00,0x3bf9bcf8,0xbcf83bf9,0xbd00bac9,0xbcf1bc2c,0xbccebc98,0xbb963cfd,0xbc5b3ce7,0xbcac3cbe,0xbcdc3c84,
 0xbcdcbc84,0xbcacbcbe,0xbc5bbce7,0xbb96bcfd,0xbcce3c98,0xbcf13c2c,0xbd003ac9,0xbcf8bbf9,0x3bf93cf8,0xbac93d00,0xbc2c3cf1,0xbc983cce,0x3cfd3b96,0x3ce73c5b,0x3cbe3cac,0x3c843cdc,
 0xbbc83cfb,0xbc8e3cd5,0xbcd53c8e,0xbcfb3bc8,0xbcfbbbc8,0xbcd5bc8e,0xbc8ebcd5,0xbbc8bcfb,0x3bc8bcfb,0x3c8ebcd5,0x3cd5bc8e,0x3cfbbbc8,0x3cfb3bc8,0x3cd53c8e,0x3c8e3cd5,0x3bc83cfb,
 0xbbc83cfb,0xbc8e3cd5,0xbcd53c8e,0xbcfb3bc8,0xbcfbbbc8,0xbcd5bc8e,0xbc8ebcd5,0xbbc8bcfb,0x3bc8bcfb,0x3c8ebcd5,0x3cd5bc8e,0x3cfbbbc8,0x3cfb3bc8,0x3cd53c8e,0x3c8e3cd5,0x3bc83cfb,
 0x3c98bcce,0x3ce7bc5b,0x3d003ac9,0x3cdc3c84,0xbcf8bbf9,0xbcbebcac,0xbc2cbcf1,0x3b96bcfd,0xbcfd3b96,0xbcf1bc2c,0xbcacbcbe,0xbbf9bcf8,0x3c843cdc,0x3ac93d00,0xbc5b3ce7,0xbcce3c98,
 0xbccebc98,0xbc5bbce7,0x3ac9bd00,0x3c84bcdc,0xbbf93cf8,0xbcac3cbe,0xbcf13c2c,0xbcfdbb96,0x3b963cfd,0xbc2c3cf1,0xbcbe3cac,0xbcf83bf9,0x3cdcbc84,0x3d00bac9,0x3ce73c5b,0x3c983cce,
 0xbcf5bc15,0xbca2bcc6,0xbb49bcff,0x3c71bce2,0x3ce2bc71,0x3cff3b49,0x3cc63ca2,0x3c153cf5,0x3c15bcf5,0x3cc6bca2,0x3cffbb49,0x3ce23c71,0x3c713ce2,0xbb493cff,0xbca23cc6,0xbcf53c15,
 0x3cf53c15,0x3ca23cc6,0x3b493cff,0xbc713ce2,0xbce23c71,0xbcffbb49,0xbcc6bca2,0xbc15bcf5,0xbc153cf5,0xbcc63ca2,0xbcff3b49,0xbce2bc71,0xbc71bce2,0x3b49bcff,0x3ca2bcc6,0x3cf5bc15,
 0xbcac3cbe,0xbcfd3b96,0xbcdcbc84,0xbc2cbcf1,0x3ce7bc5b,0x3cf83bf9,0x3c983cce,0xbac93d00,0xbd003ac9,0xbccebc98,0xbbf9bcf8,0x3c5bbce7,0x3cf13c2c,0x3c843cdc,0xbb963cfd,0xbcbe3cac,
 0xbcbebcac,0xbb96bcfd,0x3c84bcdc,0x3cf1bc2c,0x3c5b3ce7,0xbbf93cf8,0xbcce3c98,0xbd00bac9,0xbac9bd00,0x3c98bcce,0x3cf8bbf9,0x3ce73c5b,0xbc2c3cf1,0xbcdc3c84,0xbcfdbb96,0xbcacbcbe,
 0xbc443ced,0xbced3c44,0xbcedbc44,0xbc44bced,0x3c44bced,0x3cedbc44,0x3ced3c44,0x3c443ced,0xbc443ced,0xbced3c44,0xbcedbc44,0xbc44bced,0x3c44bced,0x3cedbc44,0x3ced3c44,0x3c443ced,
 0xbc443ced,0xbced3c44,0xbcedbc44,0xbc44bced,0x3c44bced,0x3cedbc44,0x3ced3c44,0x3c443ced,0xbc443ced,0xbced3c44,0xbcedbc44,0xbc44bced,0x3c44bced,0x3cedbc44,0x3ced3c44,0x3c443ced,
 0x3cbebcac,0x3cfd3b96,0x3c843cdc,0xbc2c3cf1,0xbc5b3ce7,0xbcf83bf9,0xbccebc98,0xbac9bd00,0x3d003ac9,0x3c983cce,0xbbf93cf8,0xbce73c5b,0xbcf13c2c,0xbcdcbc84,0xbb96bcfd,0x3cacbcbe,
 0x3cac3cbe,0xbb963cfd,0xbcdc3c84,0xbcf1bc2c,0xbce7bc5b,0xbbf9bcf8,0x3c98bcce,0x3d00bac9,0xbac93d00,0xbcce3c98,0xbcf8bbf9,0xbc5bbce7,0xbc2cbcf1,0x3c84bcdc,0x3cfdbb96,0x3cbe3cac,
 0xbce2bc71,0xbb49bcff,0x3cc6bca2,0x3cf53c15,0x3c153cf5,0xbca23cc6,0xbcffbb49,0xbc71bce2,0xbc713ce2,0xbcff3b49,0xbca2bcc6,0x3c15bcf5,0x3cf5bc15,0x3cc63ca2,0xbb493cff,0xbce23c71,
 0x3ce23c71,0x3b493cff,0xbcc63ca2,0xbcf5bc15,0xbc15bcf5,0x3ca2bcc6,0x3cff3b49,0x3c713ce2,0x3c71bce2,0x3cffbb49,0x3ca23cc6,0xbc153cf5,0xbcf53c15,0xbcc6bca2,0x3b49bcff,0x3ce2bc71,
 0xbcce3c98,0xbce7bc5b,0xbac9bd00,0x3cdcbc84,0xbbf9bcf8,0x3cbebcac,0x3cf13c2c,0x3b963cfd,0x3cfd3b96,0x3c2c3cf1,0xbcac3cbe,0xbcf8bbf9,0xbc843cdc,0xbd00bac9,0xbc5bbce7,0x3c98bcce,
 0x3c983cce,0xbc5b3ce7,0xbd003ac9,0xbc84bcdc,0xbcf83bf9,0xbcacbcbe,0x3c2cbcf1,0x3cfdbb96,0x3b96bcfd,0x3cf1bc2c,0x3cbe3cac,0xbbf93cf8,0x3cdc3c84,0xbac93d00,0xbce73c5b,0xbccebc98,
 0xbc8e3cd5,0xbcfbbbc8,0xbbc8bcfb,0x3cd5bc8e,0x3cd53c8e,0xbbc83cfb,0xbcfb3bc8,0xbc8ebcd5,0x3c8ebcd5,0x3cfb3bc8,0x3bc83cfb,0xbcd53c8e,0xbcd5bc8e,0x3bc8bcfb,0x3cfbbbc8,0x3c8e3cd5,
 0xbc8e3cd5,0xbcfbbbc8,0xbbc8bcfb,0x3cd5bc8e,0x3cd53c8e,0xbbc83cfb,0xbcfb3bc8,0xbc8ebcd5,0x3c8ebcd5,0x3cfb3bc8,0x3bc83cfb,0xbcd53c8e,0xbcd5bc8e,0x3bc8bcfb,0x3cfbbbc8,0x3c8e3cd5,
 0xbcdc3c84,0xbcbebcac,0x3c5bbce7,0x3cfd3b96,0xbccebc98,0x3c2cbcf1,0x3d003ac9,0x3bf93cf8,0x3cf83bf9,0x3ac93d00,0xbcf13c2c,0xbc98bcce,0x3b963cfd,0xbce73c5b,0xbcacbcbe,0x3c84bcdc,
 0x3c843cdc,0xbcac3cbe,0xbce7bc5b,0x3b96bcfd,0xbc983cce,0xbcf1bc2c,0x3ac9bd00,0x3cf8bbf9,0x3bf9bcf8,0x3d00bac9,0x3c2c3cf1,0xbcce3c98,0x3cfdbb96,0x3c5b3ce7,0xbcbe3cac,0xbcdcbc84,
 0xbcc6bca2,0x3c71bce2,0x3cf53c15,0xbb493cff,0xbcff3b49,0xbc15bcf5,0x3ce2bc71,0x3ca23cc6,0x3ca2bcc6,0x3ce23c71,0xbc153cf5,0xbcffbb49,0xbb49bcff,0x3cf5bc15,0x3c713ce2,0xbcc63ca2,
 0x3cc63ca2,0xbc713ce2,0xbcf5bc15,0x3b49bcff,0x3cffbb49,0x3c153cf5,0xbce23c71,0xbca2bcc6,0xbca23cc6,0xbce2bc71,0x3c15bcf5,0x3cff3b49,0x3b493cff,0xbcf53c15,0xbc71bce2,0x3cc6bca2,
 0x3ce7bc5b,0x3c843cdc,0xbcce3c98,0xbcacbcbe,0x3d00bac9,0x3b963cfd,0xbcf83bf9,0xbc2cbcf1,0x3cf13c2c,0xbbf93cf8,0xbcfdbb96,0x3ac9bd00,0x3cbe3cac,0xbc983cce,0xbcdcbc84,0x3c5bbce7,
 0x3c5b3ce7,0xbcdc3c84,0xbc98bcce,0x3cbebcac,0x3ac93d00,0xbcfd3b96,0xbbf9bcf8,0x3cf1bc2c,0xbc2c3cf1,0xbcf8bbf9,0x3b96bcfd,0x3d003ac9,0xbcac3cbe,0xbccebc98,0x3c84bcdc,0x3ce73c5b,
 0xbcb53cb5,0xbcb5bcb5,0x3cb5bcb5,0x3cb53cb5,0xbcb53cb5,0xbcb5bcb5,0x3cb5bcb5,0x3cb53cb5,0xbcb53cb5,0xbcb5bcb5,0x3cb5bcb5,0x3cb53cb5,0xbcb53cb5,0xbcb5bcb5,0x3cb5bcb5,0x3cb53cb5,
 0xbcb53cb5,0xbcb5bcb5,0x3cb5bcb5,0x3cb53cb5,0xbcb53cb5,0xbcb5bcb5,0x3cb5bcb5,0x3cb53cb5,0xbcb53cb5,0xbcb5bcb5,0x3cb5bcb5,0x3cb53cb5,0xbcb53cb5,0xbcb5bcb5,0x3cb5bcb5,0x3cb53cb5,
 0xbcf13c2c,0xbbf9bcf8,0x3cfdbb96,0x3ac93d00,0xbcbe3cac,0xbc98bcce,0x3cdcbc84,0x3c5b3ce7,0xbce7bc5b,0x3c84bcdc,0x3cce3c98,0xbcac3cbe,0xbd00bac9,0x3b96bcfd,0x3cf83bf9,0xbc2c3cf1,
 0xbc2cbcf1,0x3cf8bbf9,0x3b963cfd,0xbd003ac9,0xbcacbcbe,0x3ccebc98,0x3c843cdc,0xbce73c5b,0x3c5bbce7,0x3cdc3c84,0xbc983cce,0xbcbebcac,0x3ac9bd00,0x3cfd3b96,0xbbf93cf8,0xbcf1bc2c,
 0xbca2bcc6,0x3ce2bc71,0x3c153cf5,0xbcff3b49,0x3b49bcff,0x3cf53c15,0xbc713ce2,0xbcc6bca2,0xbcc63ca2,0xbc71bce2,0x3cf5bc15,0x3b493cff,0xbcffbb49,0x3c15bcf5,0x3ce23c71,0xbca23cc6,
 0x3ca23cc6,0xbce23c71,0xbc15bcf5,0x3cffbb49,0xbb493cff,0xbcf5bc15,0x3c71bce2,0x3cc63ca2,0x3cc6bca2,0x3c713ce2,0xbcf53c15,0xbb49bcff,0x3cff3b49,0xbc153cf5,0xbce2bc71,0x3ca2bcc6,
 0x3cf8bbf9,0xbac93d00,0xbcf1bc2c,0x3c98bcce,0x3b96bcfd,0x3ce73c5b,0xbcac3cbe,0xbc84bcdc,0xbcdcbc84,0x3cbebcac,0x3c5b3ce7,0xbcfd3b96,0xbcce3c98,0xbc2cbcf1,0x3d00bac9,0xbbf93cf8,
 0xbbf9bcf8,0x3d003ac9,0xbc2c3cf1,0xbccebc98,0xbcfdbb96,0x3c5bbce7,0x3cbe3cac,0xbcdc3c84,0xbc843cdc,0xbcacbcbe,0x3ce7bc5b,0x3b963cfd,0x3c983cce,0xbcf13c2c,0xbac9bd00,0x3cf83bf9,
 0xbcd53c8e,0xbbc8bcfb,0x3cfb3bc8,0xbc8e3cd5,0xbc8ebcd5,0x3cfbbbc8,0xbbc83cfb,0xbcd5bc8e,0x3cd5bc8e,0x3bc83cfb,0xbcfbbbc8,0x3c8ebcd5,0x3c8e3cd5,0xbcfb3bc8,0x3bc8bcfb,0x3cd53c8e,
 0xbcd53c8e,0xbbc8bcfb,0x3cfb3bc8,0xbc8e3cd5,0xbc8ebcd5,0x3cfbbbc8,0xbbc83cfb,0xbcd5bc8e,0x3cd5bc8e,0x3bc83cfb,0xbcfbbbc8,0x3c8ebcd5,0x3c8e3cd5,0xbcfb3bc8,0x3bc8bcfb,0x3cd53c8e,
 0x3cfdbb96,0xbc2c3cf1,0xbcacbcbe,0x3cf8bbf9,0xbc84bcdc,0x3d00bac9,0xbc5b3ce7,0xbc98bcce,0xbccebc98,0x3ce7bc5b,0xbac93d00,0xbcdcbc84,0xbbf93cf8,0xbcbebcac,0x3cf1bc2c,0xbb963cfd,
 0xbb96bcfd,0x3cf13c2c,0xbcbe3cac,0xbbf9bcf8,0xbcdc3c84,0xbac9bd00,0x3ce73c5b,0xbcce3c98,0xbc983cce,0xbc5bbce7,0x3d003ac9,0xbc843cdc,0x3cf83bf9,0xbcac3cbe,0xbc2cbcf1,0x3cfd3b96,
 0xbc71bce2,0x3cff3b49,0xbca23cc6,0xbc15bcf5,0x3cf53c15,0xbcc63ca2,0xbb49bcff,0x3ce23c71,0x3ce2bc71,0xbb493cff,0xbcc6bca2,0x3cf5bc15,0xbc153cf5,0xbca2bcc6,0x3cffbb49,0xbc713ce2,
 0x3c713ce2,0xbcffbb49,0x3ca2bcc6,0x3c153cf5,0xbcf5bc15,0x3cc6bca2,0x3b493cff,0xbce2bc71,0xbce23c71,0x3b49bcff,0x3cc63ca2,0xbcf53c15,0x3c15bcf5,0x3ca23cc6,0xbcff3b49,0x3c71bce2,
 0xbd003ac9,0x3c98bcce,0x3bf93cf8,0xbce7bc5b,0x3cf13c2c,0xbcdc3c84,0x3b96bcfd,0x3cac3cbe,0xbcbebcac,0x3cfdbb96,0xbc843cdc,0xbc2cbcf1,0x3c5b3ce7,0xbcf8bbf9,0x3ccebc98,0xbac93d00,
 0xbac9bd00,0x3cce3c98,0xbcf83bf9,0x3c5bbce7,0xbc2c3cf1,0xbc84bcdc,0x3cfd3b96,0xbcbe3cac,0x3cacbcbe,0x3b963cfd,0xbcdcbc84,0x3cf1bc2c,0xbce73c5b,0x3bf9bcf8,0x3c983cce,0xbd00bac9,
 0xbced3c44,0x3c44bced,0x3c443ced,0xbcedbc44,0x3cedbc44,0xbc443ced,0xbc44bced,0x3ced3c44,0xbced3c44,0x3c44bced,0x3c443ced,0xbcedbc44,0x3cedbc44,0xbc443ced,0xbc44bced,0x3ced3c44,
 0xbced3c44,0x3c44bced,0x3c443ced,0xbcedbc44,0x3cedbc44,0xbc443ced,0xbc44bced,0x3ced3c44,0xbced3c44,0x3c44bced,0x3c443ced,0xbcedbc44,0x3cedbc44,0xbc443ced,0xbc44bced,0x3ced3c44,
 0x3d003ac9,0xbcce3c98,0x3bf9bcf8,0x3c5b3ce7,0xbcf13c2c,0x3c84bcdc,0x3b963cfd,0xbcbebcac,0x3cac3cbe,0xbcfdbb96,0x3cdcbc84,0xbc2c3cf1,0xbce7bc5b,0x3cf8bbf9,0xbc983cce,0xbac9bd00,
 0xbac93d00,0xbc98bcce,0x3cf83bf9,0xbce73c5b,0xbc2cbcf1,0x3cdc3c84,0xbcfd3b96,0x3cacbcbe,0xbcbe3cac,0x3b96bcfd,0x3c843cdc,0xbcf1bc2c,0x3c5bbce7,0x3bf93cf8,0xbccebc98,0x3d00bac9,
 0xbc15bcf5,0x3cc63ca2,0xbcffbb49,0x3ce2bc71,0xbc713ce2,0xbb49bcff,0x3ca23cc6,0xbcf5bc15,0xbcf53c15,0x3ca2bcc6,0xbb493cff,0xbc71bce2,0x3ce23c71,0xbcff3b49,0x3cc6bca2,0xbc153cf5,
 0x3c153cf5,0xbcc6bca2,0x3cff3b49,0xbce23c71,0x3c71bce2,0x3b493cff,0xbca2bcc6,0x3cf53c15,0x3cf5bc15,0xbca23cc6,0x3b49bcff,0x3c713ce2,0xbce2bc71,0x3cffbb49,0xbcc63ca2,0x3c15bcf5,
 0xbcfdbb96,0x3cf1bc2c,0xbcac3cbe,0x3bf9bcf8,0x3c84bcdc,0xbac93d00,0xbc5bbce7,0x3cce3c98,0x3c983cce,0xbce7bc5b,0x3d00bac9,0xbcdc3c84,0xbcf83bf9,0x3cbebcac,0xbc2c3cf1,0xbb96bcfd,
 0xbb963cfd,0xbc2cbcf1,0x3cbe3cac,0xbcf8bbf9,0xbcdcbc84,0x3d003ac9,0xbce73c5b,0x3c98bcce,0x3ccebc98,0xbc5b3ce7,0xbac9bd00,0x3c843cdc,0x3bf93cf8,0xbcacbcbe,0x3cf13c2c,0xbcfd3b96,
 0xbcfb3bc8,0x3cd5bc8e,0xbc8e3cd5,0x3bc8bcfb,0x3bc83cfb,0xbc8ebcd5,0x3cd53c8e,0xbcfbbbc8,0x3cfbbbc8,0xbcd53c8e,0x3c8ebcd5,0xbbc83cfb,0xbbc8bcfb,0x3c8e3cd5,0xbcd5bc8e,0x3cfb3bc8,
 0xbcfb3bc8,0x3cd5bc8e,0xbc8e3cd5,0x3bc8bcfb,0x3bc83cfb,0xbc8ebcd5,0x3cd53c8e,0xbcfbbbc8,0x3cfbbbc8,0xbcd53c8e,0x3c8ebcd5,0xbbc83cfb,0xbbc8bcfb,0x3c8e3cd5,0xbcd5bc8e,0x3cfb3bc8,
 0xbcf8bbf9,0x3d00bac9,0xbcf13c2c,0x3ccebc98,0xbb96bcfd,0x3c5b3ce7,0xbcacbcbe,0x3cdc3c84,0x3c843cdc,0xbcbebcac,0x3ce73c5b,0xbcfdbb96,0xbc983cce,0x3c2cbcf1,0xbac93d00,0xbbf9bcf8,
 0xbbf93cf8,0xbac9bd00,0x3c2c3cf1,0xbc98bcce,0xbcfd3b96,0x3ce7bc5b,0xbcbe3cac,0x3c84bcdc,0x3cdcbc84,0xbcac3cbe,0x3c5bbce7,0xbb963cfd,0x3cce3c98,0xbcf1bc2c,0x3d003ac9,0xbcf83bf9,
 0xbb49bcff,0x3c153cf5,0xbc71bce2,0x3ca23cc6,0xbcc6bca2,0x3ce23c71,0xbcf5bc15,0x3cff3b49,0x3cffbb49,0xbcf53c15,0x3ce2bc71,0xbcc63ca2,0x3ca2bcc6,0xbc713ce2,0x3c15bcf5,0xbb493cff,
 0x3b493cff,0xbc15bcf5,0x3c713ce2,0xbca2bcc6,0x3cc63ca2,0xbce2bc71,0x3cf53c15,0xbcffbb49,0xbcff3b49,0x3cf5bc15,0xbce23c71,0x3cc6bca2,0xbca23cc6,0x3c71bce2,0xbc153cf5,0x3b49bcff,
 0x3cf13c2c,0xbcf8bbf9,0x3cfd3b96,0xbd00bac9,0x3cbe3cac,0xbccebc98,0x3cdc3c84,0xbce7bc5b,0x3c5b3ce7,0xbc84bcdc,0x3c983cce,0xbcacbcbe,0x3ac93d00,0xbb96bcfd,0x3bf93cf8,0xbc2cbcf1,
 0xbc2c3cf1,0x3bf9bcf8,0xbb963cfd,0x3ac9bd00,0xbcac3cbe,0x3c98bcce,0xbc843cdc,0x3c5bbce7,0xbce73c5b,0x3cdcbc84,0xbcce3c98,0x3cbebcac,0xbd003ac9,0x3cfdbb96,0xbcf83bf9,0x3cf1bc2c,
 0xbd000000,0x3d000000,0xbd000000,0x3d000000,0xbd000000,0x3d000000,0xbd000000,0x3d000000,0xbd000000,0x3d000000,0xbd000000,0x3d000000,0xbd000000,0x3d000000,0xbd000000,0x3d000000,
 0xbd000000,0x3d000000,0xbd000000,0x3d000000,0xbd000000,0x3d000000,0xbd000000,0x3d000000,0xbd000000,0x3d000000,0xbd000000,0x3d000000,0xbd000000,0x3d000000,0xbd000000,0x3d000000,
 0xbce7bc5b,0x3cdc3c84,0xbccebc98,0x3cbe3cac,0xbd00bac9,0x3cfd3b96,0xbcf8bbf9,0x3cf13c2c,0xbc2cbcf1,0x3bf93cf8,0xbb96bcfd,0x3ac93d00,0xbcacbcbe,0x3c983cce,0xbc84bcdc,0x3c5b3ce7,
 0x3c5bbce7,0xbc843cdc,0x3c98bcce,0xbcac3cbe,0x3ac9bd00,0xbb963cfd,0x3bf9bcf8,0xbc2c3cf1,0x3cf1bc2c,0xbcf83bf9,0x3cfdbb96,0xbd003ac9,0x3cbebcac,0xbcce3c98,0x3cdcbc84,0xbce73c5b,
 0x3b49bcff,0xbc153cf5,0x3c71bce2,0xbca23cc6,0x3cc6bca2,0xbce23c71,0x3cf5bc15,0xbcff3b49,0xbcffbb49,0x3cf53c15,0xbce2bc71,0x3cc63ca2,0xbca2bcc6,0x3c713ce2,0xbc15bcf5,0x3b493cff,
 0xbb493cff,0x3c15bcf5,0xbc713ce2,0x3ca2bcc6,0xbcc63ca2,0x3ce2bc71,0xbcf53c15,0x3cffbb49,0x3cff3b49,0xbcf5bc15,0x3ce23c71,0xbcc6bca2,0x3ca23cc6,0xbc71bce2,0x3c153cf5,0xbb49bcff,
 0x3cdc3c84,0xbcacbcbe,0x3c5b3ce7,0xbb96bcfd,0x3ccebc98,0xbcf13c2c,0x3d00bac9,0xbcf8bbf9,0xbbf9bcf8,0xbac93d00,0x3c2cbcf1,0xbc983cce,0xbcfdbb96,0x3ce73c5b,0xbcbebcac,0x3c843cdc,
 0x3c84bcdc,0xbcbe3cac,0x3ce7bc5b,0xbcfd3b96,0xbc98bcce,0x3c2c3cf1,0xbac9bd00,0xbbf93cf8,0xbcf83bf9,0x3d003ac9,0xbcf1bc2c,0x3cce3c98,0xbb963cfd,0x3c5bbce7,0xbcac3cbe,0x3cdcbc84,
 0xbcfbbbc8,0x3cd53c8e,0xbc8ebcd5,0x3bc83cfb,0x3bc8bcfb,0xbc8e3cd5,0x3cd5bc8e,0xbcfb3bc8,0x3cfb3bc8,0xbcd5bc8e,0x3c8e3cd5,0xbbc8bcfb,0xbbc83cfb,0x3c8ebcd5,0xbcd53c8e,0x3cfbbbc8,
 0xbcfbbbc8,0x3cd53c8e,0xbc8ebcd5,0x3bc83cfb,0x3bc8bcfb,0xbc8e3cd5,0x3cd5bc8e,0xbcfb3bc8,0x3cfb3bc8,0xbcd5bc8e,0x3c8e3cd5,0xbbc8bcfb,0xbbc83cfb,0x3c8ebcd5,0xbcd53c8e,0x3cfbbbc8,
 0x3cce3c98,0xbc5bbce7,0xbac93d00,0x3c84bcdc,0x3bf9bcf8,0xbcac3cbe,0x3cf1bc2c,0xbcfdbb96,0xbb96bcfd,0xbc2c3cf1,0x3cbebcac,0xbcf83bf9,0xbcdc3c84,0x3d00bac9,0xbce7bc5b,0x3c983cce,
 0x3c98bcce,0xbce73c5b,0x3d003ac9,0xbcdcbc84,0xbcf8bbf9,0x3cbe3cac,0xbc2cbcf1,0xbb963cfd,0xbcfd3b96,0x3cf13c2c,0xbcacbcbe,0x3bf93cf8,0x3c843cdc,0xbac9bd00,0xbc5b3ce7,0x3ccebc98,
 0x3c15bcf5,0xbcc63ca2,0x3cffbb49,0xbce2bc71,0x3c713ce2,0x3b49bcff,0xbca23cc6,0x3cf5bc15,0x3cf53c15,0xbca2bcc6,0x3b493cff,0x3c71bce2,0xbce23c71,0x3cff3b49,0xbcc6bca2,0x3c153cf5,
 0xbc153cf5,0x3cc6bca2,0xbcff3b49,0x3ce23c71,0xbc71bce2,0xbb493cff,0x3ca2bcc6,0xbcf53c15,0xbcf5bc15,0x3ca23cc6,0xbb49bcff,0xbc713ce2,0x3ce2bc71,0xbcffbb49,0x3cc63ca2,0xbc15bcf5,
 0xbcbebcac,0x3b963cfd,0x3c84bcdc,0xbcf13c2c,0x3c5b3ce7,0x3bf9bcf8,0xbcce3c98,0x3d003ac9,0xbac9bd00,0xbc983cce,0x3cf8bbf9,0xbce7bc5b,0xbc2c3cf1,0x3cdcbc84,0xbcfdbb96,0x3cac3cbe,
 0x3cacbcbe,0xbcfd3b96,0x3cdc3c84,0xbc2cbcf1,0xbce73c5b,0x3cf83bf9,0xbc98bcce,0xbac93d00,0x3d00bac9,0xbccebc98,0x3bf93cf8,0x3c5bbce7,0xbcf1bc2c,0x3c843cdc,0x3b96bcfd,0xbcbe3cac,
 0xbcedbc44,0x3c443ced,0x3c44bced,0xbced3c44,0x3ced3c44,0xbc44bced,0xbc443ced,0x3cedbc44,0xbcedbc44,0x3c443ced,0x3c44bced,0xbced3c44,0x3ced3c44,0xbc44bced,0xbc443ced,0x3cedbc44,
 0xbcedbc44,0x3c443ced,0x3c44bced,0xbced3c44,0x3ced3c44,0xbc44bced,0xbc443ced,0x3cedbc44,0xbcedbc44,0x3c443ced,0x3c44bced,0xbced3c44,0x3ced3c44,0xbc44bced,0xbc443ced,0x3cedbc44,
 0x3cac3cbe,0x3b96bcfd,0xbcdc3c84,0x3cf13c2c,0xbce7bc5b,0x3bf93cf8,0x3c98bcce,0xbd003ac9,0xbac93d00,0x3ccebc98,0xbcf8bbf9,0x3c5b3ce7,0xbc2cbcf1,0xbc843cdc,0x3cfdbb96,0xbcbebcac,
 0xbcbe3cac,0x3cfd3b96,0xbc84bcdc,0xbc2c3cf1,0x3c5bbce7,0xbcf83bf9,0x3cce3c98,0xbac9bd00,0xbd00bac9,0x3c983cce,0x3bf9bcf8,0xbce73c5b,0x3cf1bc2c,0xbcdcbc84,0x3b963cfd,0x3cacbcbe,
 0x3c71bce2,0xbcff3b49,0x3ca23cc6,0x3c15bcf5,0xbcf53c15,0x3cc63ca2,0x3b49bcff,0xbce23c71,0xbce2bc71,0x3b493cff,0x3cc6bca2,0xbcf5bc15,0x3c153cf5,0x3ca2bcc6,0xbcffbb49,0x3c713ce2,
 0xbc713ce2,0x3cffbb49,0xbca2bcc6,0xbc153cf5,0x3cf5bc15,0xbcc6bca2,0xbb493cff,0x3ce2bc71,0x3ce23c71,0xbb49bcff,0xbcc63ca2,0x3cf53c15,0xbc15bcf5,0xbca23cc6,0x3cff3b49,0xbc71bce2,
 0xbc98bcce,0xbc5b3ce7,0x3d00bac9,0xbc84bcdc,0x3cf8bbf9,0xbcacbcbe,0xbc2c3cf1,0x3cfdbb96,0xbb963cfd,0x3cf1bc2c,0xbcbebcac,0xbbf93cf8,0xbcdcbc84,0xbac93d00,0x3ce7bc5b,0xbccebc98,
 0xbcce3c98,0x3ce73c5b,0xbac9bd00,0xbcdc3c84,0xbbf9bcf8,0xbcbe3cac,0x3cf13c2c,0xbb96bcfd,0x3cfd3b96,0xbc2cbcf1,0xbcac3cbe,0x3cf83bf9,0xbc843cdc,0x3d003ac9,0xbc5bbce7,0xbc983cce,
 0xbcd5bc8e,0xbbc83cfb,0x3cfbbbc8,0xbc8ebcd5,0xbc8e3cd5,0x3cfb3bc8,0xbbc8bcfb,0xbcd53c8e,0x3cd53c8e,0x3bc8bcfb,0xbcfb3bc8,0x3c8e3cd5,0x3c8ebcd5,0xbcfbbbc8,0x3bc83cfb,0x3cd5bc8e,
 0xbcd5bc8e,0xbbc83cfb,0x3cfbbbc8,0xbc8ebcd5,0xbc8e3cd5,0x3cfb3bc8,0xbbc8bcfb,0xbcd53c8e,0x3cd53c8e,0x3bc8bcfb,0xbcfb3bc8,0x3c8e3cd5,0x3c8ebcd5,0xbcfbbbc8,0x3bc83cfb,0x3cd5bc8e,
 0xbc84bcdc,0xbcac3cbe,0x3ce73c5b,0x3b96bcfd,0x3c98bcce,0xbcf1bc2c,0xbac93d00,0x3cf8bbf9,0xbbf93cf8,0x3d00bac9,0xbc2cbcf1,0xbcce3c98,0xbcfd3b96,0x3c5b3ce7,0x3cbebcac,0xbcdcbc84,
 0xbcdc3c84,0x3cbe3cac,0x3c5bbce7,0xbcfdbb96,0xbccebc98,0xbc2c3cf1,0x3d003ac9,0xbbf9bcf8,0x3cf83bf9,0xbac9bd00,0xbcf13c2c,0x3c983cce,0x3b963cfd,0x3ce7bc5b,0xbcacbcbe,0xbc843cdc,
 0x3ca2bcc6,0xbce2bc71,0xbc153cf5,0x3cff3b49,0xbb49bcff,0xbcf53c15,0x3c713ce2,0x3cc6bca2,0x3cc63ca2,0x3c71bce2,0xbcf5bc15,0xbb493cff,0x3cffbb49,0xbc15bcf5,0xbce23c71,0x3ca23cc6,
 0xbca23cc6,0x3ce23c71,0x3c15bcf5,0xbcffbb49,0x3b493cff,0x3cf5bc15,0xbc71bce2,0xbcc63ca2,0xbcc6bca2,0xbc713ce2,0x3cf53c15,0x3b49bcff,0xbcff3b49,0x3c153cf5,0x3ce2bc71,0xbca2bcc6,
 0x3c5b3ce7,0x3cdcbc84,0xbc98bcce,0xbcbe3cac,0x3ac93d00,0x3cfdbb96,0xbbf9bcf8,0xbcf13c2c,0xbc2c3cf1,0x3cf83bf9,0x3b96bcfd,0xbd00bac9,0xbcac3cbe,0x3cce3c98,0x3c84bcdc,0xbce7bc5b,
 0xbce73c5b,0x3c843cdc,0x3ccebc98,0xbcacbcbe,0xbd003ac9,0x3b963cfd,0x3cf8bbf9,0xbc2cbcf1,0xbcf1bc2c,0xbbf93cf8,0x3cfd3b96,0x3ac9bd00,0xbcbebcac,0xbc983cce,0x3cdc3c84,0x3c5bbce7,
 0xbcb5bcb5,0xbcb53cb5,0x3cb53cb5,0x3cb5bcb5,0xbcb5bcb5,0xbcb53cb5,0x3cb53cb5,0x3cb5bcb5,0xbcb5bcb5,0xbcb53cb5,0x3cb53cb5,0x3cb5bcb5,0xbcb5bcb5,0xbcb53cb5,0x3cb53cb5,0x3cb5bcb5,
 0xbcb5bcb5,0xbcb53cb5,0x3cb53cb5,0x3cb5bcb5,0xbcb5bcb5,0xbcb53cb5,0x3cb53cb5,0x3cb5bcb5,0xbcb5bcb5,0xbcb53cb5,0x3cb53cb5,0x3cb5bcb5,0xbcb5bcb5,0xbcb53cb5,0x3cb53cb5,0x3cb5bcb5,
 0xbc2cbcf1,0xbcf83bf9,0x3b963cfd,0x3d00bac9,0xbcacbcbe,0xbcce3c98,0x3c843cdc,0x3ce7bc5b,0x3c5bbce7,0xbcdcbc84,0xbc983cce,0x3cbe3cac,0x3ac9bd00,0xbcfdbb96,0xbbf93cf8,0x3cf13c2c,
 0x3cf1bc2c,0xbbf9bcf8,0xbcfd3b96,0x3ac93d00,0x3cbebcac,0xbc98bcce,0xbcdc3c84,0x3c5b3ce7,0x3ce73c5b,0x3c84bcdc,0xbccebc98,0xbcac3cbe,0x3d003ac9,0x3b96bcfd,0xbcf8bbf9,0xbc2c3cf1,
 0x00000000,0x00000000,0x00000000,0x00000000,0x00000000,0x00000000,0x00000000,0x00000000,0x00000000,0x00000000,0x00000000,0x00000000,0x00000000,0x00000000,0x00000000,0x00000000,
 0x00000000,0x00000000,0x00000000,0x00000000,0x00000000,0x00000000,0x00000000,0x00000000,0x00000000,0x00000000,0x00000000,0x00000000,0x00000000,0x00000000,0x00000000,0x00000000,
 0x00000000,0x00000000,0x00000000,0x00000000,0x00000000,0x00000000,0x00000000,0x00000000,0x00000000,0x00000000,0x00000000,0x00000000,0x00000000,0x00000000,0x00000000,0x00000000,
 0x00000000,0x00000000,0x00000000,0x00000000,0x00000000,0x00000000,0x00000000,0x00000000,0x00000000,0x00000000,0x00000000,0x00000000,0x00000000,0x00000000,0x00000000,0x00000000,
 0x00000000,0x00000000,0x00000000,0x00000000,0x00000000,0x00000000,0x00000000,0x00000000,0x00000000,0x00000000,0x00000000,0x00000000,0x00000000,0x00000000,0x00000000,0x00000000,
 0x00000000,0x00000000,0x00000000,0x00000000,0x00000000,0x00000000,0x00000000,0x00000000,0x00000000,0x00000000,0x00000000,0x00000000,0x00000000,0x00000000,0x00000000,0x00000000,
 0x00000000,0x00000000,0x00000000,0x00000000,0x00000000,0x00000000,0x00000000,0x00000000,0x00000000,0x00000000,0x00000000,0x00000000,0x00000000,0x00000000,0x00000000,0x00000000,
 0x00000000,0x00000000,0x00000000,0x00000000,0x00000000,0x00000000,0x00000000,0x00000000,0x00000000,0x00000000,0x00000000,0x00000000,0x00000000,0x00000000,0x00000000,0x00000000,
 0x00000000,0x00000000,0x00000000,0x00000000,0x00000000,0x00000000,0x00000000,0x00000000,0x00000000,0x00000000,0x00000000,0x00000000,0x00000000,0x00000000,0x00000000,0x00000000,
 0x00000000,0x00000000,0x00000000,0x00000000,0x00000000,0x00000000,0x00000000,0x00000000,0x00000000,0x00000000,0x00000000,0x00000000,0x00000000,0x00000000,0x00000000,0x00000000,
 0x00000000,0x00000000,0x00000000,0x00000000,0x00000000,0x00000000,0x00000000,0x00000000,0x00000000,0x00000000,0x00000000,0x00000000,0x00000000,0x00000000,0x00000000,0x00000000,
 0x00000000,0x00000000,0x00000000,0x00000000,0x00000000,0x00000000,0x00000000,0x00000000,0x00000000,0x00000000,0x00000000,0x00000000,0x00000000,0x00000000,0x00000000,0x00000000,
};

template<int SA>
__device__ __forceinline__ void wgmma_main(float (&d)[80], uint64_t da, uint64_t db, int sd) {
  asm volatile("{\n.reg .pred p;\nsetp.ne.b32 p, %82, 0;\n"
    "wgmma.mma_async.sync.aligned.m64n160k16.f32.bf16.bf16 "
    "{%0, %1, %2, %3, %4, %5, %6, %7, %8, %9, %10, %11, %12, %13, %14, %15, %16, %17, %18, %19, %20, %21, %22, %23, %24, %25, %26, %27, %28, %29, %30, %31, %32, %33, %34, %35, %36, %37, %38, %39, %40, %41, %42, %43, %44, %45, %46, %47, %48, %49, %50, %51, %52, %53, %54, %55, %56, %57, %58, %59, %60, %61, %62, %63, %64, %65, %66, %67, %68, %69, %70, %71, %72, %73, %74, %75, %76, %77, %78, %79}, %80, %81, p, %83, 1, 1, 0;\n}\n"
    : "+f"(d[0]), "+f"(d[1]), "+f"(d[2]), "+f"(d[3]), "+f"(d[4]), "+f"(d[5]), "+f"(d[6]), "+f"(d[7]), "+f"(d[8]), "+f"(d[9]), "+f"(d[10]), "+f"(d[11]), "+f"(d[12]), "+f"(d[13]), "+f"(d[14]), "+f"(d[15]), "+f"(d[16]), "+f"(d[17]), "+f"(d[18]), "+f"(d[19]), "+f"(d[20]), "+f"(d[21]), "+f"(d[22]), "+f"(d[23]), "+f"(d[24]), "+f"(d[25]), "+f"(d[26]), "+f"(d[27]), "+f"(d[28]), "+f"(d[29]), "+f"(d[30]), "+f"(d[31]), "+f"(d[32]), "+f"(d[33]), "+f"(d[34]), "+f"(d[35]), "+f"(d[36]), "+f"(d[37]), "+f"(d[38]), "+f"(d[39]), "+f"(d[40]), "+f"(d[41]), "+f"(d[42]), "+f"(d[43]), "+f"(d[44]), "+f"(d[45]), "+f"(d[46]), "+f"(d[47]), "+f"(d[48]), "+f"(d[49]), "+f"(d[50]), "+f"(d[51]), "+f"(d[52]), "+f"(d[53]), "+f"(d[54]), "+f"(d[55]), "+f"(d[56]), "+f"(d[57]), "+f"(d[58]), "+f"(d[59]), "+f"(d[60]), "+f"(d[61]), "+f"(d[62]), "+f"(d[63]), "+f"(d[64]), "+f"(d[65]), "+f"(d[66]), "+f"(d[67]), "+f"(d[68]), "+f"(d[69]), "+f"(d[70]), "+f"(d[71]), "+f"(d[72]), "+f"(d[73]), "+f"(d[74]), "+f"(d[75]), "+f"(d[76]), "+f"(d[77]), "+f"(d[78]), "+f"(d[79])
    : "l"(da), "l"(db), "r"(sd), "n"(SA));
}
template<int SA>
__device__ __forceinline__ void wgmma_fwd(float (&d)[32], uint64_t da, uint64_t db, int sd) {
  asm volatile("{\n.reg .pred p;\nsetp.ne.b32 p, %34, 0;\n"
    "wgmma.mma_async.sync.aligned.m64n64k16.f32.bf16.bf16 "
    "{%0, %1, %2, %3, %4, %5, %6, %7, %8, %9, %10, %11, %12, %13, %14, %15, %16, %17, %18, %19, %20, %21, %22, %23, %24, %25, %26, %27, %28, %29, %30, %31}, %32, %33, p, %35, 1, 0, 1;\n}\n"
    : "+f"(d[0]), "+f"(d[1]), "+f"(d[2]), "+f"(d[3]), "+f"(d[4]), "+f"(d[5]), "+f"(d[6]), "+f"(d[7]), "+f"(d[8]), "+f"(d[9]), "+f"(d[10]), "+f"(d[11]), "+f"(d[12]), "+f"(d[13]), "+f"(d[14]), "+f"(d[15]), "+f"(d[16]), "+f"(d[17]), "+f"(d[18]), "+f"(d[19]), "+f"(d[20]), "+f"(d[21]), "+f"(d[22]), "+f"(d[23]), "+f"(d[24]), "+f"(d[25]), "+f"(d[26]), "+f"(d[27]), "+f"(d[28]), "+f"(d[29]), "+f"(d[30]), "+f"(d[31])
    : "l"(da), "l"(db), "r"(sd), "n"(SA));
}
template<int SA>
__device__ __forceinline__ void wgmma_inv(float (&d)[28], uint64_t da, uint64_t db, int sd) {
  asm volatile("{\n.reg .pred p;\nsetp.ne.b32 p, %30, 0;\n"
    "wgmma.mma_async.sync.aligned.m64n56k16.f32.bf16.bf16 "
    "{%0, %1, %2, %3, %4, %5, %6, %7, %8, %9, %10, %11, %12, %13, %14, %15, %16, %17, %18, %19, %20, %21, %22, %23, %24, %25, %26, %27}, %28, %29, p, %31, 1, 1, 0;\n}\n"
    : "+f"(d[0]), "+f"(d[1]), "+f"(d[2]), "+f"(d[3]), "+f"(d[4]), "+f"(d[5]), "+f"(d[6]), "+f"(d[7]), "+f"(d[8]), "+f"(d[9]), "+f"(d[10]), "+f"(d[11]), "+f"(d[12]), "+f"(d[13]), "+f"(d[14]), "+f"(d[15]), "+f"(d[16]), "+f"(d[17]), "+f"(d[18]), "+f"(d[19]), "+f"(d[20]), "+f"(d[21]), "+f"(d[22]), "+f"(d[23]), "+f"(d[24]), "+f"(d[25]), "+f"(d[26]), "+f"(d[27])
    : "l"(da), "l"(db), "r"(sd), "n"(SA));
}

__device__ __forceinline__ uint32_t s2u(const void* p) { return (uint32_t)__cvta_generic_to_shared(p); }
__device__ __forceinline__ void mbar_init(uint32_t a, int c) { asm volatile("mbarrier.init.shared::cta.b64 [%0], %1;" ::"r"(a), "r"(c)); }
__device__ __forceinline__ void mbar_expect(uint32_t a, int b) { asm volatile("mbarrier.arrive.expect_tx.shared::cta.b64 _, [%0], %1;" ::"r"(a), "r"(b) : "memory"); }
__device__ __forceinline__ void mbar_arrive(uint32_t a) { asm volatile("mbarrier.arrive.shared::cta.b64 _, [%0];" ::"r"(a) : "memory"); }
__device__ __forceinline__ void mbar_arrive_cluster(uint32_t a, uint32_t cta, uint32_t cnt) {
  asm volatile("{\n.reg .b32 r;\nmapa.shared::cluster.u32 r, %0, %1;\nmbarrier.arrive.shared::cluster.b64 _, [r], %2;\n}" ::"r"(a), "r"(cta), "r"(cnt) : "memory");
}
__device__ __forceinline__ void mbar_wait(uint32_t a, int ph) {
  asm volatile("{\n.reg .pred p;\n.reg .u32 c;\nmov.u32 c, 0;\nWAIT:\n"
               "mbarrier.try_wait.parity.shared::cta.b64 p, [%0], %1;\n@p bra DONE;\n"
               "add.u32 c, c, 1;\nsetp.lt.u32 p, c, 0x400000;\n@p bra WAIT;\ntrap;\nDONE:\n}" ::"r"(a), "r"(ph) : "memory");
}
__device__ __forceinline__ void flag_wait(const unsigned* p, unsigned target) {
  asm volatile("{\n.reg .pred p;\n.reg .u32 c, v;\nmov.u32 c, 0;\nWAIT:\n"
               "ld.acquire.gpu.global.u32 v, [%0];\nsetp.ge.u32 p, v, %1;\n@p bra DONE;\n"
               "add.u32 c, c, 1;\nsetp.lt.u32 p, c, 0x400000;\n@p bra WAIT;\ntrap;\nDONE:\n}" ::"l"(p), "r"(target) : "memory");
}
__device__ __forceinline__ bool elect_one() {
  uint32_t p;
  asm volatile("{\n.reg .pred P;\nelect.sync _|P, 0xffffffff;\nselp.u32 %0, 1, 0, P;\n}" : "=r"(p));
  return p != 0;
}
__device__ __forceinline__ void bulk_ld(uint32_t dst, const void* src, int bytes, uint32_t bar) {
  asm volatile("cp.async.bulk.shared::cluster.global.mbarrier::complete_tx::bytes [%0], [%1], %2, [%3];" ::"r"(dst), "l"(src), "r"(bytes), "r"(bar) : "memory");
}
__device__ __forceinline__ void bulk_ld_mc_h(uint32_t dst, const void* src, int bytes, uint32_t bar, uint16_t mask, uint64_t pol) {
  asm volatile("cp.async.bulk.shared::cluster.global.mbarrier::complete_tx::bytes.multicast::cluster.L2::cache_hint [%0], [%1], %2, [%3], %4, %5;" ::"r"(dst), "l"(src), "r"(bytes), "r"(bar), "h"(mask), "l"(pol) : "memory");
}
__device__ __forceinline__ uint64_t policy_evict_normal() {
  uint64_t p;
  asm("createpolicy.fractional.L2::evict_normal.b64 %0, 1.0;" : "=l"(p));
  return p;
}
__device__ __forceinline__ void tma_ld2(uint32_t dst, const CUtensorMap* tm, int c0, int c1, uint32_t bar) {
  asm volatile("cp.async.bulk.tensor.2d.shared::cluster.global.mbarrier::complete_tx::bytes [%0], [%1, {%3,%4}], [%2];" ::"r"(dst), "l"(tm), "r"(bar), "r"(c0), "r"(c1) : "memory");
}
__device__ __forceinline__ void tma_ld3(uint32_t dst, const CUtensorMap* tm, int c0, int c1, int c2, uint32_t bar) {
  asm volatile("cp.async.bulk.tensor.3d.shared::cluster.global.mbarrier::complete_tx::bytes [%0], [%1, {%3,%4,%5}], [%2];" ::"r"(dst), "l"(tm), "r"(bar), "r"(c0), "r"(c1), "r"(c2) : "memory");
}
__device__ __forceinline__ void tma_ld3h(uint32_t dst, const CUtensorMap* tm, int c0, int c1, int c2, uint32_t bar, uint64_t pol) {
  asm volatile("cp.async.bulk.tensor.3d.shared::cluster.global.mbarrier::complete_tx::bytes.L2::cache_hint [%0], [%1, {%3,%4,%5}], [%2], %6;" ::"r"(dst), "l"(tm), "r"(bar), "r"(c0), "r"(c1), "r"(c2), "l"(pol) : "memory");
}
__device__ __forceinline__ uint64_t policy_evict_first() {
  uint64_t p;
  asm("createpolicy.fractional.L2::evict_first.b64 %0, 1.0;" : "=l"(p));
  return p;
}
__device__ __forceinline__ void tma_st3(const CUtensorMap* tm, uint32_t src, int c0, int c1, int c2) {
  asm volatile("cp.async.bulk.tensor.3d.global.shared::cta.bulk_group [%0, {%2,%3,%4}], [%1];" ::"l"(tm), "r"(src), "r"(c0), "r"(c1), "r"(c2) : "memory");
}
__device__ __forceinline__ void tma_st4(const CUtensorMap* tm, uint32_t src, int c0, int c1, int c2, int c3) {
  asm volatile("cp.async.bulk.tensor.4d.global.shared::cta.bulk_group [%0, {%2,%3,%4,%5}], [%1];" ::"l"(tm), "r"(src), "r"(c0), "r"(c1), "r"(c2), "r"(c3) : "memory");
}
__device__ __forceinline__ void tma_st5(const CUtensorMap* tm, uint32_t src, int c0) {
  asm volatile("cp.async.bulk.tensor.5d.global.shared::cta.bulk_group [%0, {%2,%3,%3,%3,%3}], [%1];" ::"l"(tm), "r"(src), "r"(c0), "r"(0) : "memory");
}
__device__ __forceinline__ void bulk_commit() { asm volatile("cp.async.bulk.commit_group;" ::: "memory"); }
template <int N> __device__ __forceinline__ void bulk_wait_read() { asm volatile("cp.async.bulk.wait_group.read %0;" ::"n"(N) : "memory"); }
template <int N> __device__ __forceinline__ void bulk_wait() { asm volatile("cp.async.bulk.wait_group %0;" ::"n"(N) : "memory"); }
__device__ __forceinline__ void fence_async_smem() { asm volatile("fence.proxy.async.shared::cta;" ::: "memory"); }
__device__ __forceinline__ void wg_fence() { asm volatile("wgmma.fence.sync.aligned;" ::: "memory"); }
__device__ __forceinline__ void wg_commit() { asm volatile("wgmma.commit_group.sync.aligned;" ::: "memory"); }
template <int N> __device__ __forceinline__ void wg_wait() { asm volatile("wgmma.wait_group.sync.aligned %0;" ::"n"(N) : "memory"); }
template <int R> __device__ __forceinline__ void fence_regs(float (&d)[R]) {
#pragma unroll
  for (int i = 0; i < R; i++) asm volatile("" : "+f"(d[i])::"memory");
}
__device__ __forceinline__ uint64_t mk_desc(uint32_t addr) {
  return (uint64_t)((addr & 0x3FFFF) >> 4) | (1ull << 16) | (64ull << 32) | (1ull << 62);
}
__device__ __forceinline__ uint32_t pack2(float lo, float hi) {
  uint32_t r;
  asm("cvt.rn.bf16x2.f32 %0, %1, %2;" : "=r"(r) : "f"(hi), "f"(lo));
  return r;
}
__device__ __forceinline__ void stsm4(uint32_t ad, uint32_t a, uint32_t b, uint32_t c, uint32_t d) {
  asm volatile("stmatrix.sync.aligned.m8n8.x4.shared.b16 [%0], {%1,%2,%3,%4};" ::"r"(ad), "r"(a), "r"(b), "r"(c), "r"(d) : "memory");
}
__device__ __forceinline__ void stsm4t(uint32_t ad, uint32_t a, uint32_t b, uint32_t c, uint32_t d) {
  asm volatile("stmatrix.sync.aligned.m8n8.x4.trans.shared.b16 [%0], {%1,%2,%3,%4};" ::"r"(ad), "r"(a), "r"(b), "r"(c), "r"(d) : "memory");
}

__device__ __forceinline__ void stsm2t(uint32_t ad, uint32_t a, uint32_t b) {
  asm volatile("stmatrix.sync.aligned.m8n8.x2.trans.shared.b16 [%0], {%1,%2};" ::"r"(ad), "r"(a), "r"(b) : "memory");
}
__device__ __forceinline__ void red_add(unsigned* p) { asm volatile("red.relaxed.gpu.global.add.u32 [%0], 1;" ::"l"(p) : "memory"); }
__device__ __forceinline__ void fence_release() { asm volatile("fence.release.gpu;" ::: "memory"); }
__device__ __forceinline__ void fence_async_global() { asm volatile("fence.proxy.async.global;" ::: "memory"); }
__device__ __forceinline__ void tma_pf2(const CUtensorMap* tm, int c0, int c1) {
  asm volatile("cp.async.bulk.prefetch.tensor.2d.L2.global [%0, {%1,%2}];" ::"l"(tm), "r"(c0), "r"(c1) : "memory");
}
__device__ __forceinline__ void tma_pf3(const CUtensorMap* tm, int c0, int c1, int c2) {
  asm volatile("cp.async.bulk.prefetch.tensor.3d.L2.global [%0, {%1,%2,%3}];" ::"l"(tm), "r"(c0), "r"(c1), "r"(c2) : "memory");
}

__device__ __forceinline__ int lane_id() {
  int l;
  asm volatile("mov.u32 %0, %%laneid;" : "=r"(l));
  return l;
}
__device__ __forceinline__ void poll64x4(const unsigned long long* p, unsigned long long (&v)[4]) {
  asm volatile("{\n.reg .pred p;\n.reg .u32 c;\n.reg .b64 t, u;\nmov.u32 c, 0;\nWAIT:\n"
               "ld.relaxed.gpu.global.u64 %0, [%4];\nld.relaxed.gpu.global.u64 %1, [%4+512];\n"
               "ld.relaxed.gpu.global.u64 %2, [%4+1024];\nld.relaxed.gpu.global.u64 %3, [%4+1536];\n"
               "or.b64 t, %0, %1;\nor.b64 u, %2, %3;\nor.b64 t, t, u;\nsetp.ge.s64 p, t, 0;\n@p bra DONE;\n"
               "add.u32 c, c, 1;\nsetp.lt.u32 p, c, 0x400000;\n@p bra WAIT;\ntrap;\nDONE:\n}"
               : "=l"(v[0]), "=l"(v[1]), "=l"(v[2]), "=l"(v[3]) : "l"(p) : "memory");
}

constexpr int G_STAGE = WBLK + XBLK;
constexpr int OFF_XR = 4 * G_STAGE;
constexpr int OFF_WS = OFF_XR + 6 * 8192;
constexpr int OFF_F = OFF_WS + 2 * 8192;
constexpr int OFF_WRAW = OFF_F + 8192;
constexpr int OFF_BAR = OFF_WRAW + 8192;
constexpr int OFF_GB = OFF_BAR + 1024;
constexpr int SMEM_BYTES = OFF_GB + 512;
constexpr int OFF_H0B = 10 * 8192;
constexpr int OFF_E = OFF_WRAW + 3072;
constexpr int B_RAWX = 0, B_F = 48, B_ROLE = 56, B_H0 = 72, B_H1 = 88, B_YFREE = 112, B_H0C = 128,
              B_EMPTY = 160, B_STGX = 192, B_STGW = 240, B_Y = 256, B_OUT = 272,
              B_FULL = 360, B_RAWW = 392, B_DONE = 424, S_ROLE = 480, S_PROBE = 496;

struct Maps { CUtensorMap x, we, wo, xst[2], wst, yst[2], yld[2], out, xe[2], w30; };

__device__ __forceinline__ int chunk_of(int n) { return n < 16 ? n : 31 - n; }
__device__ __forceinline__ bool has_x2(int id, int n, int g) { return (((id >> 5) ^ n) & 1) == 0 && ((n >> 1) & 1) == g; }
__device__ __forceinline__ uint32_t x_base(int s, int idx, uint32_t pgmask, int& par) {
  const int page = idx >> 3, o = idx & 7;
  par = (s ^ (pgmask >> page) ^ __popc(o)) & 1;
  return (page << 21) | ((o & 3) << 16) | ((o >> 2) << 19);
}
template <bool MASK = true>
__device__ __forceinline__ uint32_t read_info(uint32_t bar, int i) {
  uint32_t v;
  mbar_wait(bar + B_ROLE + 8 * i, 0);
  asm volatile("ld.shared.b32 %0, [%1];" : "=r"(v) : "r"(bar + S_ROLE + 4 * i) : "memory");
  return (MASK && i == 0) ? v & 63 : v;
}
__device__ __forceinline__ void send_info(uint32_t bar, int i, uint32_t v) {
#pragma unroll
  for (int r = 0; r < 2; r++)
    asm volatile("{\n.reg .b32 a, m;\nmapa.shared::cluster.u32 a, %0, %2;\nmapa.shared::cluster.u32 m, %1, %2;\n"
                 "st.async.weak.shared::cluster.mbarrier::complete_tx::bytes.b32 [a], %3, [m];\n}"
                 ::"r"(bar + S_ROLE + 4 * i), "r"(bar + B_ROLE + 8 * i), "r"(r), "r"(v) : "memory");
}
__device__ __forceinline__ unsigned probe(uint8_t* p, int lane, int pb) {
  if (lane < 2) *(uint4*)(p + lane * 16) = make_uint4(0, 0, 0, 0);
  __syncwarp();
  unsigned v = 0, best = ~0u;
  if (lane == 0) {
#pragma unroll 1
    for (int r = 0; r < NPR; r++) {
      unsigned t0, t1;
      asm volatile("mov.u32 %0, %%clock;" : "=r"(t0) : "r"(v) : "memory");
      asm volatile("atom.relaxed.gpu.global.exch.b32 %0, [%1], 0;" : "=r"(v) : "l"(p) : "memory");
      asm volatile("{\n.reg .pred p;\nsetp.ne.u32 p, %1, 0xffffffff;\nmov.u32 %0, 0;\n@p mov.u32 %0, %%clock;\n}" : "=r"(t1) : "r"(v) : "memory");
      best = min(best, t1 - t0);
      if (r < 3) PROF_V(pb + r, t1 - t0);
    }
  }
  return best;
}

template <bool ISX>
__device__ __forceinline__ void t_issue(float (&t)[32], uint32_t sb, uint32_t raw) {
  const uint64_t da = mk_desc(sb + OFF_F), db = mk_desc(raw);
  wg_fence();
#pragma unroll
  for (int kk = 0; kk < (ISX ? 4 : 1); kk++) wgmma_fwd<1>(t, da + 2 * kk, db + 128 * kk, kk);
  wg_commit();
}
template <bool ISX>
__device__ __forceinline__ void t_finish(float (&t)[32], uint32_t dst, uint32_t sbar, int sw, int wg, int w, int lane) {
  fence_regs(t);
  if (ISX) asm volatile("bar.sync %0, 128;" ::"r"(1 + wg) : "memory");
  const int m = lane >> 3, r = lane & 7;
  uint32_t ad = dst + (8 * w + r) * 128;
  if (ISX) ad += ((((m & 1) * 4 + (m >> 1)) ^ sw ^ r) << 4);
  else ad += (m & 1) * 4096 + (((m >> 1) ^ sw ^ r) << 4);
#pragma unroll
  for (int i = 0; i < 4; i++) {
    const uint32_t a = ISX ? ((ad ^ ((i & 1) * 32)) + (i >> 1) * 4096) : (ad ^ (i * 32));
    stsm4(a, pack2(t[8 * i], t[8 * i + 1]), pack2(t[8 * i + 2], t[8 * i + 3]), pack2(t[8 * i + 4], t[8 * i + 5]), pack2(t[8 * i + 6], t[8 * i + 7]));
  }
  __syncwarp();
  if (lane == 0) mbar_arrive(sbar);
}
template <int NT, int K0, int K1>
__device__ __forceinline__ void batch(float (&yr)[80], float (&yi)[80], float (&t)[32], uint32_t st, int wg, int sd, uint32_t fa, uint32_t raw) {
  const uint64_t w0 = mk_desc(st + wg * 8192), x0 = mk_desc(st + WBLK);
  const uint64_t da = mk_desc(fa), db = mk_desc(raw);
  wg_fence();
  if (NT) {
#pragma unroll
    for (int kk = 0; kk < NT; kk++) wgmma_fwd<1>(t, da + 2 * kk, db + 128 * kk, kk);
    wg_commit();
  }
#pragma unroll
  for (int kk = K0; kk < K1; kk++) {
    const uint64_t wr = w0 + kk * 128, wi = wr + 256, xr = x0 + kk * 2, xi = xr + 4;
    wgmma_main<1>(yr, wr, xr, kk ? 1 : sd);
    wgmma_main<1>(yi, wr, xi, kk ? 1 : sd);
    wgmma_main<1>(yr, wi, xi, 1);
    wgmma_main<-1>(yi, wi, xr, 1);
  }
  wg_commit();
}

#define X_WAIT() PROF_W(wraw, mbar_wait(bar + B_RAWX + 8 * (wg * 3 + xs), xph))
#define X_ISSUE() t_issue<true>(t, sb, sb + OFF_XR + (wg * 3 + xs) * 8192)
#define X_FINISH(sw) do { t_finish<true>(t, sb + OFF_XR + (wg * 3 + xs) * 8192, bar + B_STGX + 8 * (wg * 3 + xs), sw, wg, w, lane); \
                          if (++xs == 3) { xs = 0; xph ^= 1; } } while (0)
#define W_WAIT(n) PROF_W(wraw, mbar_wait(bar + B_RAWW + 8 * (wg * 2 + ((n) & 1)), ((n) >> 1) & 1))
#define WRAW(n) (sb + OFF_WRAW + (wg * 2 + ((n) & 1)) * 2048)
#define W_FINISH() t_finish<false>(t, sb + OFF_WS + wg * 8192, bar + B_STGW + 8 * wg, (bid >> 1) & 7, wg, w, lane)

template <int g>
__device__ __forceinline__ void manager(const Maps& tm, unsigned* ctr, const uint32_t sb, const int bid) {
  const uint32_t bar = sb + OFF_BAR, rank = bid & 1;
  const uint64_t pol = policy_evict_first();
  int id = bid, lid = bid;
  uint32_t pgmask = 0;
  int li = has_x2(bid, 0, g) ? 1 : 2;
  auto refill = [&](int sl) {
    if (li >= 32) return;
    if (li == 2 * OB) lid = read_info(bar, 0) * 2 + rank;
    const uint32_t fb = bar + B_RAWX + 8 * (g * 3 + sl);
    mbar_expect(fb, 8192);
    tma_ld3h(sb + OFF_XR + (g * 3 + sl) * 8192, &tm.x, (li >> 1) * 64, ((li & 1) ? 128 + (lid & 31) : 2 * (lid & 63) + g) * MT, lid >> 6, fb, pol);
    li += (li & 1) || has_x2(lid, li >> 1, g) ? 1 : 2;
  };
#pragma unroll 1
  for (int sl = 1; sl < 3; sl++) refill(sl);
  int xs = 0, xph = 0, yp = 0;
  int wrow = (rank * 2 + (bid >> 6)) * 128 + g * 64 + ((bid >> 1) & 31);
#pragma unroll 1
  for (int n = 0; n < 32; n++) {
    if (n == OB) {
      id = lid;
      pgmask = read_info(bar, 1);
    }
    unsigned freed = 128;
    if (n >= WR) asm volatile("ld.relaxed.gpu.global.u32 %0, [%1];" : "=r"(freed) : "l"(&ctr[(C_LOADED + n - WR) * 32]) : "memory");
    if (n < 16) {
#pragma unroll 1
      for (int j = 0; j < (has_x2(id, n, g) ? 2 : 1); j++) {
        const int t = j ? 128 + (id & 31) : 2 * (id & 63) + g;
        int par0, par1;
        const uint32_t off0 = x_base(id >> 6, n * 10 + (t >> 5), pgmask, par0), off1 = x_base(id >> 6, n * 10 + 5 + (t >> 5), pgmask, par1);
        const uint32_t buf = sb + OFF_XR + (g * 3 + xs) * 8192;
        mbar_wait(bar + B_STGX + 8 * (g * 3 + xs), xph);
        fence_async_smem();
        tma_st5(&tm.xst[par0], buf, (off0 + (par0 << 12) + (t & 31) * 128) >> 1);
        tma_st5(&tm.xst[par1], buf + 4096, (off1 + (par1 << 12) + (t & 31) * 128) >> 1);
        bulk_commit();
        bulk_wait_read<0>();
        refill(xs);
        if (++xs == 3) { xs = 0; xph ^= 1; }
      }
    }
    if (n > 16 + LW && n <= YFLUSH && (n - 17 - LW) % YSTEP == 0) {
      if (yp == 0 || yp == 3) mbar_wait(bar + B_Y + 8 * g, yp & 1);
#pragma unroll 1
      do {
        tma_st4(&tm.yst[0], sb + OFF_XR + (g * 3 + (yp < 3 ? yp : yp - 3)) * 8192, 0, yp * 32, id & 62, (id >> 6) * 4 + rank * 2 + g);
      } while (++yp < 2);
      bulk_commit();
      bulk_wait_read<0>();
      if (yp == 2) mbar_arrive(bar + B_YFREE + 8 * g);
    }
    if (freed < 128) flag_wait(&ctr[(C_LOADED + n - WR) * 32], 128);
    mbar_wait(bar + B_STGW + 8 * g, n & 1);
    fence_async_smem();
    tma_st4(&tm.wst, sb + OFF_WS + g * 8192, 0, 0, 0, wrow);
    bulk_commit();
    wrow += WCHUNK / 128;
    if (wrow >= WR * WCHUNK / 128) wrow -= WR * WCHUNK / 128;
    if (n < 30) {
      const int cp = chunk_of(n + 2) * 64 + (bid >> 1), sl = g * 2 + (n & 1);
      mbar_expect(bar + B_RAWW + 8 * sl, 2048);
      tma_ld3h(sb + OFF_WRAW + sl * 2048, &tm.we + (cp >> 9), 0, 0, (cp & 511) * 8 + ((n + 2) >> 4) * 4 + rank * 2 + g, bar + B_RAWW + 8 * sl, pol);
    }
    if (n < 4) {
#pragma unroll 1
      for (int q = 4 + n; q < 16; q += 4) {
        const int cp = q * 64 + (bid >> 1);
        tma_pf3(&tm.we + (cp >> 9), 0, 0, (cp & 511) * 8 + rank * 2 + g);
      }
    }
    bulk_wait<0>();
    mbar_arrive(bar + B_DONE + 8 * (n & 3));
    mbar_arrive(bar + B_RAWW + 8 * (g * 2 + ((n + 1) & 1)));
  }
  const int b = id >> 6, u = (id >> 1) & 31;
  flag_wait(&ctr[(C_LOADED + 31) * 32], 128);
  mbar_wait(bar + B_Y + 8 * g, 0);
  for (int p = 0; p < 5; p++) tma_st4(&tm.yst[1], sb + (p * 2 + g) * 8192, 0, p * 32, 2 * u, b * 4 + rank * 2 + g);
  bulk_commit();
  bulk_wait<0>();
  mbar_arrive(bar + B_DONE);
#pragma unroll 1
  for (int i = 0; i < 10; i++) {
    const int hf = i >= 5, k = i - 5 * hf;
    mbar_wait(bar + B_OUT + 8 * (g * 5 + k), hf);
    fence_async_smem();
    tma_st3(&tm.out, sb + (hf ? 0 : k < 4 ? OFF_XR : OFF_H0B - 65536) + (2 * k + g) * 8192, (hf * 4 + rank * 2 + (u & 1)) * 64, ((u >> 1) * 10 + 2 * k + g) * MT, b);
    bulk_commit();
  }
  bulk_wait_read<0>();
  if (g == 0) PROF_T(12);
}

__global__ void __cluster_dims__(2, 1, 1) __launch_bounds__(512, 1)
k1_main(uint8_t* __restrict__ xbuf, const void* __restrict__ fimg, unsigned* ctr, const __nv_bfloat16* __restrict__ gamma,
        const __nv_bfloat16* __restrict__ beta, const __grid_constant__ Maps tm) {
  extern __shared__ __align__(1024) uint8_t smem_raw[];
  const uint32_t sb = s2u(smem_raw);
  const uint32_t bar = sb + OFF_BAR;
  const int warp = __shfl_sync(0xffffffffu, threadIdx.x >> 5, 0);
  const int bid = (int)blockIdx.x - 4;
  const uint32_t rank = bid & 1;
  if (warp >= 12) {
    asm volatile("setmaxnreg.dec.sync.aligned.u32 24;");
    asm volatile("barrier.cluster.arrive.relaxed.aligned;" ::: "memory");
    if (bid >= 0) {
      const int lane = lane_id(), k = bid >> 1;
      if (rank == 0 || k < XPAGES - OB) {
        const uint32_t off = rank ? ((k + OB) << 21) + 0xb0000 : (XPAGES << 21) + ((k >> 4) << 14) + (k & 15) * 128;
        const unsigned lat = probe(xbuf + off + (warp & 1) * 4096 + (warp & 2) * 1024, lane, 400 + (warp & 2) * 5 + (warp & 1) * 3);
        if (lane == 0) asm volatile("st.shared.b32 [%0], %1;" ::"r"(bar + S_PROBE + 4 * (warp & 3)), "r"(lat) : "memory");
      }
      asm volatile("bar.sync 4, 128;" ::: "memory");
      int near = 0, ticket = 0;
      if (warp == 14 && lane == 0) {
        uint32_t l0, l1, l2, l3;
        asm volatile("ld.shared.v4.b32 {%0, %1, %2, %3}, [%4];" : "=r"(l0), "=r"(l1), "=r"(l2), "=r"(l3) : "r"(bar + S_PROBE) : "memory");
        near = min(l1, l3) < min(l0, l2);
        PROF_T(14);
        if (rank == 0) ticket = atomicAdd(&ctr[C_REG * 32 + near], 1);
      }
      asm volatile("barrier.cluster.wait.aligned;" ::: "memory");
      if (warp == 14 && lane == 0) {
        if (rank == 0) {
          send_info(bar, 0, (ticket < 32 ? near * 32 + ticket : (near ^ 1) * 32 + 63 - ticket) + 64 * near);
          PROF_T(15); PROF_V(16, near); PROF_V(17, ticket < 32 ? near * 32 : (near ^ 1) * 32);
        } else {
          unsigned* reg = &ctr[C_REG * 32 + 2];
          const int side = read_info<false>(bar, 0) >> 6;
          if (k < XPAGES - OB) atomicAdd(reg, 1 + ((near ^ side ^ 1) << (5 + OB + k)));
          uint32_t v;
          asm volatile("{\n.reg .pred p;\n.reg .u32 c, a;\nmov.u32 c, 0;\nWAIT:\n"
                       "ld.relaxed.gpu.global.u32 %0, [%1];\nand.b32 a, %0, 31;\nsetp.ge.u32 p, a, %2;\n@p bra DONE;\n"
                       "add.u32 c, c, 1;\nsetp.lt.u32 p, c, 0x400000;\n@p bra WAIT;\ntrap;\nDONE:\n}" : "=r"(v) : "l"(reg), "n"(XPAGES - OB) : "memory");
          send_info(bar, 1, v >> 5);
          PROF_T(13);
        }
      }
      __syncwarp();
      if (warp - 12 < NFL && elect_one()) {
#pragma unroll 1
        for (int n = warp - 12; n < 33; n += NFL) {
          int f = n;
          if (n == 32) f += (read_info(bar, 0) >> 5) * 2 + rank;
          mbar_wait(bar + B_DONE + 8 * (n & 3), (n >> 2) & 1);
          fence_release();
          red_add(&ctr[(C_FLAG + f) * 32]);
          if (n < 32) { PROF_T(64 + n); PROF_V(192 + n, tm0); } else { PROF_V(4, tm0); }
        }
      }
      if (warp == 15 && elect_one()) {
#pragma unroll 1
        for (int v = 0; v < 64; v++) {
          mbar_wait(bar + B_FULL + 8 * (v & 3), (v >> 2) & 1);
          if ((v & 1) && (v < 2 * (32 - WR) || v == 63)) red_add(&ctr[(C_LOADED + (v >> 1)) * 32]);
        }
      }
      __syncwarp();
    } else {
      asm volatile("barrier.cluster.wait.aligned;" ::: "memory");
    }
    asm volatile("barrier.cluster.arrive.relaxed.aligned;\nbarrier.cluster.wait.aligned;" ::: "memory");
    return;
  } else {
    if (elect_one()) {
      if (warp == 0) PROF_T(0);
      if (warp >= 6) asm volatile("prefetch.tensormap [%0];" ::"l"(&tm.x + (warp - 6)) : "memory");
      const int cnt = warp < 4 ? 1 : warp < 9 ? 4 : 2;
#pragma unroll
      for (int i = 0; i < 5; i++) mbar_init(bar + warp * 40 + 8 * i, cnt);
      if (warp == 1) {
        mbar_expect(bar + B_ROLE, 4);
        mbar_expect(bar + B_ROLE + 8, 4);
      }
      asm volatile("fence.mbarrier_init.release.cluster;" ::: "memory");
    }
    asm volatile("bar.sync 0, 384;" ::: "memory");
    asm volatile("barrier.cluster.arrive.relaxed.aligned;" ::: "memory");
    if (threadIdx.x == 64) PROF_T(20);
    if (bid >= 0 && warp < 7 && elect_one()) {
      const int g = warp & 1, q = warp >> 2;
      const uint64_t pol = policy_evict_first();
      if (warp < 2) {
        mbar_expect(bar + B_RAWX + 24 * g, 8192);
        tma_ld3h(sb + OFF_XR + g * 3 * 8192, &tm.x, 0, (2 * (bid & 63) + g) * MT, bid >> 6, bar + B_RAWX + 24 * g, pol);
      } else if (warp < 6) {
        const uint32_t fb = bar + B_RAWW + 8 * (g * 2 + q);
        mbar_expect(fb, 2048);
        tma_ld3h(sb + OFF_WRAW + (g * 2 + q) * 2048, &tm.we, 0, 0, (q * 64 + (bid >> 1)) * 8 + rank * 2 + g, fb, pol);
        if (!q) mbar_arrive(fb);
      } else {
        mbar_expect(bar + B_F, 8192);
        bulk_ld(sb + OFF_F, fimg, 8192, bar + B_F);
      }
    }
    __syncwarp();
  }
  if (warp >= 8) {
    asm volatile("setmaxnreg.dec.sync.aligned.u32 40;");
    if (bid < 0) {
      asm volatile("barrier.cluster.wait.aligned;" ::: "memory");
    } else if (warp == 9 || warp == 10) {
      if (elect_one()) {
        if (warp == 9) manager<0>(tm, ctr, sb, bid); else manager<1>(tm, ctr, sb, bid);
      }
      __syncwarp();
      asm volatile("barrier.cluster.wait.aligned;" ::: "memory");
    } else if (warp == 11) {
      asm volatile("barrier.cluster.wait.aligned;" ::: "memory");
      if (elect_one()) {
        const uint8_t* ws = g_W + (size_t)((read_info(bar, 0) & 31) * 2 + rank) * 2 * WBLK;
        int slot = 0;
#pragma unroll 1
        for (int n = 0; n < 32; n++) {
          const uint8_t* src = ws + (size_t)slot * WCHUNK;
          const uint32_t s8 = (n & 1) * 16, dst = sb + (n & 1) * 2 * G_STAGE;
          const int ph = ((n >> 1) & 1) ^ 1;
          if (++slot == WR) slot = 0;
          flag_wait(&ctr[(C_FLAG + n) * 32], 128);
          fence_async_global();
          PROF_T(32 + n);
#pragma unroll
          for (int h = 0; h < 2; h++) {
            mbar_wait(bar + B_EMPTY + s8 + 8 * h, ph);
            mbar_expect(bar + B_FULL + s8 + 8 * h, WBLK);
            bulk_ld(dst + h * G_STAGE, src + h * WBLK, WBLK, bar + B_FULL + s8 + 8 * h);
          }
        }
      }
      __syncwarp();
    } else {
      asm volatile("barrier.cluster.wait.aligned;" ::: "memory");
      if (elect_one()) {
        const int role = read_info(bar, 0);
        uint32_t pgmask = 0;
        PROF_T(1);
        const int b = role >> 5, u = role & 31;
        const int dq = rank * 2 + (u & 1), t0 = (u >> 1) * 10;
        const uint64_t pef = policy_evict_first(), pen = policy_evict_normal();
        const uint8_t* xs = xbuf + ((((u >> 1) & 3) << 14) | (((u >> 3) & 1) << 18) | ((u >> 4) << 20) | ((u & 1) << 13));
#pragma unroll 1
        for (int n = 0; n < 32; n++) {
          const int c = chunk_of(n);
          const uint64_t polx = (n < XKEEP || n >= 16) ? pef : pen;
          const uint32_t s8 = (n & 1) * 16, dst = sb + (n & 1) * 2 * G_STAGE + WBLK + rank * 8192;
          const int ph = ((n >> 1) & 1) ^ 1;
          if (n == OB) pgmask = read_info(bar, 1);
          uint32_t xo[6];
#pragma unroll
          for (int g = 0; g < 6; g++) {
            int par;
            xo[g] = x_base(b, c * 10 + (g / 3) * 5 + rank * 2 + g % 3, c < OB ? 0 : pgmask, par);
            xo[g] += ((par ^ u) & 1) << 12;
            asm volatile("" : "+r"(xo[g]));
          }
          if (n < 16) {
            flag_wait(&ctr[(C_FLAG + n) * 32], 128);
            fence_async_global();
          }
#pragma unroll
          for (int h = 0; h < 2; h++) {
            const uint32_t fb = bar + B_FULL + s8 + 8 * h;
            mbar_wait(bar + B_EMPTY + s8 + 8 * h, ph);
            mbar_expect(fb, XBLK);
#pragma unroll
            for (int g = 0; g < 3; g++) {
              const int skip = (g == 0 && rank) ? 2048 : 0, len = (g == (rank ? 0 : 2)) ? 2048 : 4096;
              bulk_ld_mc_h(dst + h * G_STAGE + g * 4096 + skip, xs + xo[3 * h + g] + skip, len, fb, 3, polx);
            }
          }
        }
        flag_wait(&ctr[C_E * 32], 4);
        flag_wait(&ctr[(C_FLAG + YFLUSH) * 32], 128);
        fence_async_global();
        mbar_expect(bar + B_H0C, 6 * 8192);
        for (int i = 0; i < 3; i++) tma_ld2(sb + OFF_XR + i * 16384, &tm.yld[0], 0, ((b * 4 + dq) * NT + t0 + 2 * i) * 64, bar + B_H0C);
        static_assert(YFLUSH >= 27 && LW <= 4, "phases of the B_DONE ring");
        mbar_wait(bar + B_DONE + 8 * 3, 1);
        mbar_expect(bar + B_H0, 2 * 8192 + 7168 + 5120 + 512);
        bulk_ld(sb + OFF_F, g_Gimg, 7168, bar + B_H0);
        tma_ld2(sb + OFF_WS, &tm.yld[0], 0, ((b * 4 + dq) * NT + t0 + 6) * 64, bar + B_H0);
        tma_pf2(&tm.yld[0], 0, ((b * 4 + dq) * NT + t0 + 8) * 64);
        for (int hf = 0; hf < 2; hf++) {
          bulk_ld(sb + OFF_E + hf * 2560, g_E + ((b * 8 + hf * 4 + dq) * NT + t0) * 64, 2560, bar + B_H0);
          bulk_ld(sb + OFF_GB + hf * 256, gamma + (hf * 4 + dq) * 64, 128, bar + B_H0);
          bulk_ld(sb + OFF_GB + hf * 256 + 128, beta + (hf * 4 + dq) * 64, 128, bar + B_H0);
        }
        mbar_wait(bar + B_EMPTY + 8 * 2, 1);
        mbar_expect(bar + B_H0 + 8, 16384);
        tma_ld2(sb + OFF_H0B, &tm.yld[0], 0, ((b * 4 + dq) * NT + t0 + 8) * 64, bar + B_H0 + 8);
        flag_wait(&ctr[(C_FLAG + 32 + b * 2 + rank) * 32], 32);
        fence_async_global();
        PROF_T(5);
        for (int i = 0; i < 5; i++) {
          const uint32_t fb = bar + B_H1 + 8 * (i >> 1);
          if ((i & 1) == 0) mbar_expect(fb, i < 4 ? 32768 : 16384);
          tma_ld2(sb + i * 16384, &tm.yld[1], 0, ((b * 4 + dq) * NT + t0 + 2 * i) * 64, fb);
        }
      }
      __syncwarp();
      const int lane = lane_id();
      unsigned old = 0;
      if (lane == 0) old = atomicAdd(&ctr[C_EXIT * 32], 1);
      if (__shfl_sync(0xffffffffu, old, 0) == 127) {
        for (int i = lane; i < C_NUM; i += 32) *(uint4*)&ctr[i * 32] = make_uint4(0, 0, 0, 0);
      }
    }
    asm volatile("barrier.cluster.arrive.relaxed.aligned;\nbarrier.cluster.wait.aligned;" ::: "memory");
  } else {
    asm volatile("setmaxnreg.inc.sync.aligned.u32 224;");
    const int wg = warp >> 2, w = warp & 3;
    int lane = lane_id();
    asm volatile("barrier.cluster.wait.aligned;" ::: "memory");
    if (bid < 0) {
      float ea[80], eb[80];
      const int b = blockIdx.x >> 1;
      constexpr int ES = 32768 + 2 * XBLK;
#pragma unroll 1
      for (int k = -3; k < 8; k++) {
        const int sl = (k + 3) % 3;
        if (k >= 0) {
          mbar_wait(bar + B_RAWX + 8 * sl, (k / 3) & 1);
          const uint64_t da = mk_desc(sb + sl * ES + wg * 16384), db = mk_desc(sb + sl * ES + 32768);
          wg_fence();
#pragma unroll
          for (int kk = 0; kk < 8; kk++) {
            const uint64_t a0 = da + (kk & 3) * 128, b0 = db + (kk & 3) * 2 + (kk >> 2) * (XBLK >> 4);
            wgmma_main<1>(ea, a0, b0, (k | kk) != 0);
            wgmma_main<1>(eb, a0 + 512, b0, (k | kk) != 0);
          }
          wg_commit();
          wg_wait<0>();
          asm volatile("bar.sync 3, 256;" ::: "memory");
        }
        if (k + 3 < 8 && warp == 0 && elect_one()) {
          const uint32_t dst = sb + sl * ES, fb = bar + B_RAWX + 8 * sl;
          mbar_expect(fb, ES);
          for (int q = 0; q < 4; q++) tma_ld2(dst + q * 8192, &tm.w30, rank * 256 + q * 64, (k + 3) * 64, fb);
          for (int q = 0; q < 2; q++) tma_ld3(dst + 32768 + q * XBLK, &tm.xe[q], (k + 3) * 64, 0, b, fb);
        }
        __syncwarp();
      }
      fence_regs(ea);
      fence_regs(eb);
      float* e0 = g_E + ((b * 8 + rank * 4 + wg * 2) * NT + 2 * (lane & 3)) * 64 + 16 * w + (lane >> 2);
#pragma unroll
      for (int i = 0; i < 80; i++) {
        const int o = (8 * (i >> 2) + (i & 1)) * 64 + ((i >> 1) & 1) * 8;
        e0[o] = ea[i];
        e0[o + NT * 64] = eb[i];
      }
      asm volatile("bar.sync 3, 256;" ::: "memory");
      if (threadIdx.x == 0) {
        fence_release();
        red_add(&ctr[C_E * 32]);
        PROF_T(28);
      }
      asm volatile("barrier.cluster.arrive.relaxed.aligned;\nbarrier.cluster.wait.aligned;" ::: "memory");
      return;
    }
    int id = bid;
    {
      float yr[80], yi[80], t[32];

      int xs = 0, xph = 0;
      if (threadIdx.x == 0) PROF_T(24);
      mbar_wait(bar + B_F, 0);
      if (threadIdx.x == 0) PROF_T(25);
#pragma unroll 1
      for (int m = 0; m <= LW; m++) {
        if (m == OB) id = __shfl_sync(0xffffffffu, read_info(bar, 0), 0) * 2 + rank;
        X_WAIT();
        X_ISSUE();
        wg_wait<0>();
        X_FINISH((2 * id + wg) & 7);
        if (threadIdx.x == 0 && m == 0) PROF_T(26);
        if (has_x2(id, m, wg)) {
          X_WAIT();
          X_ISSUE();
          wg_wait<0>();
          X_FINISH(id & 7);
        }
        if (m < LW) {
          W_WAIT(m);
          t_issue<false>(t, sb, WRAW(m));
          wg_wait<0>();
          W_FINISH();
        }
      }
      if (threadIdx.x == 0) PROF_T(27);
      static_assert(OB >= 1 && OB <= 2 && OB <= LW, "role is read in the prologue");
      const int ym = lane >> 3, yr8 = lane & 7;
      const uint32_t yad = (ym >> 1) * 4096 + yr8 * 128 + (((2 * w + (ym & 1)) ^ yr8) << 4);
#define STAGE_PROF0()
#define STAGE_PROF1()
#define STAGE_BEGIN() PROF_W(wfull, mbar_wait(bar + B_FULL + 8 * (v & 3), (v >> 2) & 1)); STAGE_PROF0(); const uint32_t st = sb + (v & 3) * G_STAGE
#define RELEASE(vv) do { if (w == 0 && lane < 2) mbar_arrive_cluster(bar + B_EMPTY + 8 * ((vv) & 3), lane, 1); } while (0)
#define XRAW (sb + OFF_XR + (wg * 3 + xs) * 8192)
#define STAGE_W0(mw, sd) do { W_WAIT(mw); batch<1, 0, 2>(yr, yi, t, st, wg, sd, sb + OFF_F, WRAW(mw)); wg_wait<1>(); W_FINISH(); wg_wait<0>(); RELEASE(v); } while (0)
#define STAGE_PLAIN0(sd) do { batch<0, 0, 2>(yr, yi, t, st, wg, sd, 0, 0); wg_wait<0>(); RELEASE(v); } while (0)
#define STAGE_W1(mw, sd) do { W_WAIT(mw); batch<1, 0, 1>(yr, yi, t, st, wg, sd, sb + OFF_F, WRAW(mw)); wg_wait<1>(); if (sd) RELEASE(v - 1); \
                              W_FINISH(); batch<0, 1, 2>(yr, yi, t, st, wg, 1, 0, 0); } while (0)
#define STAGE_PLAIN1(sd) do { batch<0, 0, 1>(yr, yi, t, st, wg, sd, 0, 0); wg_wait<1>(); if (sd) RELEASE(v - 1); \
                              batch<0, 1, 2>(yr, yi, t, st, wg, 1, 0, 0); } while (0)
#pragma unroll 1
      for (int v = 0; v < 32; v++) {
        const int m = ((v + 1) >> 1) + LW;
        STAGE_BEGIN();
        if (!(v & 1) || v == 31) {
          if (P0M) STAGE_W1(m, v != 0); else STAGE_W0(m, v != 0);
        } else if (m >= 16) {
          if (P0M) STAGE_PLAIN1(1); else STAGE_PLAIN0(1);
        } else {
          X_WAIT();
          batch<4, 0, 1>(yr, yi, t, st, wg, 1, sb + OFF_F, XRAW);
          wg_wait<1>();
          if (P0M) RELEASE(v - 1);
          X_FINISH((2 * id + wg) & 7);
          if (has_x2(id, m, wg)) {
            X_WAIT();
            batch<4, 1, 2>(yr, yi, t, st, wg, 1, sb + OFF_F, XRAW);
            wg_wait<1>();
            X_FINISH(id & 7);
          } else {
            batch<0, 1, 2>(yr, yi, t, st, wg, 1, 0, 0);
          }
          if (!P0M) { wg_wait<0>(); RELEASE(v); }
        }
        STAGE_PROF1();
      }
      wg_wait<0>();
      fence_regs(yr);
      fence_regs(yi);
      if (P0M) RELEASE(31);
      {
        uint32_t hold[32];
#pragma unroll
        for (int j = 0; j < 20; j++) {
          const uint32_t p0 = pack2(yr[4 * j], yr[4 * j + 1]), p1 = pack2(yr[4 * j + 2], yr[4 * j + 3]);
          const uint32_t p2 = pack2(yi[4 * j], yi[4 * j + 1]), p3 = pack2(yi[4 * j + 2], yi[4 * j + 3]);
          if (j < 12) {
            stsm4t(sb + OFF_XR + wg * 3 * 8192 + yad + (j >> 2) * 8192 + (j & 3) * 1024, p0, p1, p2, p3);
          } else {
            hold[4 * j - 48] = p0; hold[4 * j - 47] = p1; hold[4 * j - 46] = p2; hold[4 * j - 45] = p3;
          }
        }
#pragma unroll
        for (int j = 0; j < 32; j++) asm volatile("" : "+r"(hold[j])::"memory");
        fence_async_smem();
        __syncwarp();
        if (lane == 0) mbar_arrive(bar + B_Y + 8 * wg);
        if (threadIdx.x == 0) PROF_T(2);
#pragma unroll
        for (int v = 32; v < 34; v++) {
          STAGE_BEGIN();
          if (P1M) STAGE_PLAIN1(v != 32); else STAGE_PLAIN0(v != 32);
          STAGE_PROF1();
        }
        mbar_wait(bar + B_YFREE + 8 * wg, 0);
#pragma unroll
        for (int j = 0; j < 8; j++)
          stsm4t(sb + OFF_XR + wg * 3 * 8192 + yad + (j >> 2) * 8192 + (j & 3) * 1024, hold[4 * j], hold[4 * j + 1], hold[4 * j + 2], hold[4 * j + 3]);
        fence_async_smem();
        __syncwarp();
        if (lane == 0) mbar_arrive(bar + B_Y + 8 * wg);
#pragma unroll
        for (int j = 0; j < 32; j++) t[j] = __uint_as_float(hold[j]);
      }
#pragma unroll 1
      for (int v = 34; v < 64; v++) {
        const int m = (v >> 1) + LW;
        STAGE_BEGIN();
        if (!(v & 1) && m < 32) {
          if (P1M) STAGE_W1(m, 1); else STAGE_W0(m, 1);
        } else {
          if (P1M) STAGE_PLAIN1(1); else STAGE_PLAIN0(1);
          if (v == 49 && wg == 0) g_part[bid * 128 + w * 32 + lane] = ~0ull;
        }
        STAGE_PROF1();
      }
      wg_wait<0>();
      fence_regs(yr);
      fence_regs(yi);
      asm volatile("bar.sync 3, 256;" ::: "memory");
#pragma unroll
      for (int j = 0; j < 20; j++)
        stsm4t(sb + wg * 8192 + yad + (j >> 2) * 16384 + (j & 3) * 1024, pack2(yr[4 * j], yr[4 * j + 1]), pack2(yr[4 * j + 2], yr[4 * j + 3]),
               pack2(yi[4 * j], yi[4 * j + 1]), pack2(yi[4 * j + 2], yi[4 * j + 3]));
      fence_async_smem();
      __syncwarp();
      if (lane == 0) mbar_arrive(bar + B_Y + 8 * wg);
      if (threadIdx.x == 0) PROF_T(3);
    }
    lane = lane_id();
    const int tid = warp * 32 + lane, b = id >> 6, u = (id >> 1) & 31;
    const int dq = rank * 2 + (u & 1), tr = u >> 1;
    const int a = lane & 3, d0 = 16 * w + (lane >> 2);
    float2* s_red = (float2*)(smem_raw + OFF_WRAW);
#pragma unroll 1
    for (int hf = 0; hf < 2; hf++) {
      const uint32_t base = sb + (hf ? 0 : OFF_XR), last = hf ? 0 : OFF_H0B - 65536 - OFF_XR;
      float acc[5][28];
      float s1[2] = {0.f, 0.f}, s2[2] = {0.f, 0.f};
      if (hf == 0) { mbar_wait(bar + B_H0, 0); mbar_wait(bar + B_H0C, 0); }
      const float* se = (const float*)(smem_raw + OFF_E + hf * 2560) + wg * 64 + d0;
#pragma unroll
      for (int k2 = 0; k2 < 4; k2++) {
        if (k2 < 3) {
          if (hf) mbar_wait(bar + B_H1 + 8 * k2, 0);
          else if (k2 == 2) mbar_wait(bar + B_H0 + 8, 0);
          const uint64_t da = mk_desc(base + (4 * k2 + wg) * 8192 + (k2 == 2 ? last : 0)), db = mk_desc(sb + OFF_F);
          wg_fence();
#pragma unroll
          for (int kk = 0; kk < 4; kk++) {
            wgmma_inv<1>(acc[2 * k2], da + 128 * kk, db + 2 * kk, kk);
            if (k2 < 2) wgmma_inv<1>(acc[2 * k2 + 1], da + 1024 + 128 * kk, db + 2 * kk, kk);
          }
          wg_commit();
        }
        if (k2 > 0) {
          if (k2 < 3) wg_wait<1>(); else wg_wait<0>();
#pragma unroll
          for (int k = 2 * k2 - 2; k < 2 * k2 && k < 5; k++) {
            fence_regs(acc[k]);
            if (a == 0) {
              acc[k][25] += se[k * 128];
              acc[k][27] += se[k * 128 + 8];
            }
            if (k == 4 && tr == 15 && wg == 1) {
#pragma unroll
              for (int i = 16; i < 28; i++)
                if (8 * (i >> 2) + (i & 1) + 2 * a >= LOUT - (NT - 1) * MT) acc[k][i] = 0.f;
            }
#pragma unroll
            for (int i = 0; i < 28; i += 2) {
              s1[(i >> 1) & 1] += acc[k][i] + acc[k][i + 1];
              s2[(i >> 1) & 1] += fmaf(acc[k][i], acc[k][i], acc[k][i + 1] * acc[k][i + 1]);
            }
          }
        }
      }
#pragma unroll
      for (int i = 0; i < 2; i++) {
#pragma unroll
        for (int o = 1; o < 4; o <<= 1) {
          s1[i] += __shfl_xor_sync(0xffffffffu, s1[i], o);
          s2[i] += __shfl_xor_sync(0xffffffffu, s2[i], o);
        }
      }
      if (a == 0) {
        s_red[wg * 64 + d0] = make_float2(s1[0], s2[0]);
        s_red[wg * 64 + d0 + 8] = make_float2(s1[1], s2[1]);
      }
      asm volatile("bar.sync 3, 256;" ::: "memory");
      if (tid == 0) PROF_T(6 + 3 * hf);
      unsigned long long* part = g_part + ((hf * 2 + b) * 4 + dq) * 1024;
      if (tid < 64) {
        const float2 p0 = s_red[tid], p1 = s_red[64 + tid];
        const float x1 = p0.x + p1.x, x2 = p0.y + p1.y;
        const unsigned long long v = ((unsigned long long)(__float_as_uint(x2) & 0x7fffffffu) << 32) | __float_as_uint(x1);
        asm volatile("st.relaxed.gpu.global.u64 [%0], %1;" ::"l"(part + tr * 64 + tid), "l"(v) : "memory");
      }
      {
        const unsigned long long* q = part + (tid >> 6) * 256 + (tid & 63);
        unsigned long long v[4];
        poll64x4(q, v);
        float x1 = 0.f, x2 = 0.f;
#pragma unroll
        for (int i = 0; i < 4; i++) {
          x1 += __uint_as_float((uint32_t)v[i]);
          x2 += __uint_as_float((uint32_t)(v[i] >> 32));
        }
        s_red[128 + tid] = make_float2(x1, x2);
      }
      asm volatile("bar.sync 3, 256;" ::: "memory");
      if (tid == 0) PROF_T(7 + 3 * hf);
#pragma unroll
      for (int i = 0; i < 2; i++) {
        const float2 q0 = s_red[128 + d0 + 8 * i], q1 = s_red[192 + d0 + 8 * i], q2 = s_red[256 + d0 + 8 * i], q3 = s_red[320 + d0 + 8 * i];
        const float mu = ((q0.x + q1.x) + (q2.x + q3.x)) * (1.f / LOUT);
        const float var = fmaxf(((q0.y + q1.y) + (q2.y + q3.y)) * (1.f / LOUT) - mu * mu, 0.f);
        const __nv_bfloat16* gb = (const __nv_bfloat16*)(smem_raw + OFF_GB + hf * 256) + d0 + 8 * i;
        s1[i] = 0.5f * __bfloat162float(gb[0]) / sqrtf(var + 1e-5f);
        s2[i] = 0.5f * __bfloat162float(gb[64]) - mu * s1[i];
      }
      const int m = lane >> 3, r = lane & 7;
      const uint32_t ad = base + wg * 8192 + ((m >> 1) * 8 + r) * 128 + (((2 * w + (m & 1)) ^ r) << 4);
#pragma unroll
      for (int k = 0; k < 5; k++) {
#pragma unroll
        for (int i = 0; i < 28; i++) {
          const float hz = fmaf(acc[k][i], s1[(i >> 1) & 1], s2[(i >> 1) & 1]);
          const float in = hz * fmaf(hz * hz, 8.f * 0.044715f * 0.7978845608028654f, 2.f * 0.7978845608028654f);
          float th;
          asm("tanh.approx.f32 %0, %1;" : "=f"(th) : "f"(in));
          acc[k][i] = fmaf(hz, th, hz);
        }
#pragma unroll
        for (int jj = 0; jj < 3; jj++) {
          const float* c = acc[k] + 8 * jj;
          stsm4t(ad + (k == 4 ? last : 0) + k * 16384 + jj * 2048, pack2(c[0], c[1]), pack2(c[2], c[3]), pack2(c[4], c[5]), pack2(c[6], c[7]));
        }
        stsm2t(ad + (k == 4 ? last : 0) + k * 16384 + 3 * 2048, pack2(acc[k][24], acc[k][25]), pack2(acc[k][26], acc[k][27]));
        if (k < 4) {
          float z;
          asm volatile("ld.volatile.shared.f32 %0, [%1];" : "=f"(z) : "r"(sb + OFF_F + 55 * 128) : "memory");
          s2[0] += z;
          s2[1] += z;
        }
        __syncwarp();
        if (lane == 0) mbar_arrive(bar + B_OUT + 8 * (wg * 5 + k));
      }
      if (tid == 0) PROF_T(8 + 3 * hf);
    }
    asm volatile("barrier.cluster.arrive.relaxed.aligned;\nbarrier.cluster.wait.aligned;" ::: "memory");
  }
}

typedef CUresult (*EncFn)(CUtensorMap*, CUtensorMapDataType, cuuint32_t, void*, const cuuint64_t*, const cuuint64_t*, const cuuint32_t*,
                          const cuuint32_t*, CUtensorMapInterleave, CUtensorMapSwizzle, CUtensorMapL2promotion, CUtensorMapFloatOOBfill);

void encode(EncFn fn, CUtensorMap* m, int rank, void* base, const cuuint64_t* dims, const cuuint64_t* strides, const cuuint32_t* box,
            CUtensorMapL2promotion promo) {
  cuuint32_t es[5] = {1, 1, 1, 1, 1};
  fn(m, CU_TENSOR_MAP_DATA_TYPE_BFLOAT16, rank, base, dims, strides, box, es, CU_TENSOR_MAP_INTERLEAVE_NONE, CU_TENSOR_MAP_SWIZZLE_128B, promo,
     CU_TENSOR_MAP_FLOAT_OOB_FILL_NONE);
}

}

extern "C" void kernel_launch(void* const* d_in, const int* in_sizes, int n_in, void* d_out, int out_size) {
  (void)in_sizes; (void)n_in; (void)out_size;
  const __nv_bfloat16* x = (const __nv_bfloat16*)d_in[0];
  const __nv_bfloat16* w = (const __nv_bfloat16*)d_in[1];
  const __nv_bfloat16* gamma = (const __nv_bfloat16*)d_in[2];
  const __nv_bfloat16* beta = (const __nv_bfloat16*)d_in[3];
  void* fnp = nullptr;
  cudaDriverEntryPointQueryResult qr;
  cudaGetDriverEntryPoint("cuTensorMapEncodeTiled", &fnp, cudaEnableDefault, &qr);
  EncFn fn = (EncFn)fnp;
  void *cptr = nullptr, *fptr = nullptr, *xptr = nullptr, *wptr = nullptr, *yptr = nullptr;
  cudaGetSymbolAddress(&cptr, g_ctr);
  cudaGetSymbolAddress(&fptr, g_Fimg);
  cudaGetSymbolAddress(&xptr, g_X);
  cudaGetSymbolAddress(&wptr, g_W);
  cudaGetSymbolAddress(&yptr, g_Y);
  xptr = (void*)(((uintptr_t)xptr + (1u << 21) - 1) & ~(uintptr_t)((1u << 21) - 1));
  const CUtensorMapL2promotion P0 = CU_TENSOR_MAP_L2_PROMOTION_NONE, P128 = CU_TENSOR_MAP_L2_PROMOTION_L2_128B;
  Maps m;
  {
    cuuint64_t d[3] = {1024, 8000, 2}, s[2] = {2048, 8000ull * 2048};
    cuuint32_t bx[3] = {64, 64, 1};
    encode(fn, &m.x, 3, (void*)x, d, s, bx, P128);
  }
  for (int ph = 0; ph < 2; ph++) {
    cuuint64_t d[3] = {64, (cuuint64_t)(16 - ph), 4096}, s[2] = {2ull * 262144 * 2, 128};
    cuuint32_t bx[3] = {64, 16, 1};
    encode(fn, ph ? &m.wo : &m.we, 3, (void*)(w + (size_t)ph * 262144), d, s, bx, P128);
  }
  for (int par = 0; par < 2; par++) {
    cuuint64_t d[5] = {(cuuint64_t)XPAGES << 20, 2, 4, 2, 2}, s[4] = {par ? 0x1000u : 0x3000u, 1u << 14, 1u << 18, 1u << 20};
    cuuint32_t bx[5] = {64, 2, 4, 2, 2};
    encode(fn, &m.xst[par], 5, xptr, d, s, bx, P0);
  }
  {
    cuuint64_t d[4] = {64, 32, 2, (cuuint64_t)WR * WCHUNK / 128}, s[3] = {4ull * WBLK, 4096, 128};
    cuuint32_t bx[4] = {64, 32, 2, 1};
    encode(fn, &m.wst, 4, wptr, d, s, bx, P0);
  }
  for (int p = 0; p < 2; p++) {
    void* base = p ? wptr : yptr;
    cuuint64_t d[4] = {64, NT, 64, 8}, s[3] = {8192, 128, (cuuint64_t)NT * 8192};
    cuuint32_t bx[4] = {64, 32, 2, 1};
    encode(fn, &m.yst[p], 4, base, d, s, bx, P0);
    cuuint64_t d2[2] = {64, 8ull * NT * 64}, s2[1] = {128};
    cuuint32_t bx2[2] = {64, 128};
    encode(fn, &m.yld[p], 2, base, d2, s2, bx2, P128);
  }
  {
    cuuint64_t d[3] = {512, LOUT, 2}, s[2] = {1024, (cuuint64_t)LOUT * 1024};
    cuuint32_t bx[3] = {64, MT, 1};
    encode(fn, &m.out, 3, d_out, d, s, bx, P0);
  }
  for (int q = 0; q < 2; q++) {
    cuuint64_t d[3] = {512, (cuuint64_t)(NT - q), 2}, s[2] = {MT * 2048, 8000ull * 2048};
    cuuint32_t bx[3] = {64, NT, 1};
    encode(fn, &m.xe[q], 3, (void*)(x + q * 64 * 1024), d, s, bx, P128);
  }
  {
    cuuint64_t d[2] = {512, 512}, s[1] = {1024};
    cuuint32_t bx[2] = {64, 64};
    encode(fn, &m.w30, 2, (void*)(w + 30 * 262144), d, s, bx, P128);
  }
  cudaFuncSetAttribute(k1_main, cudaFuncAttributeMaxDynamicSharedMemorySize, SMEM_BYTES);
  k1_main<<<132, 512, SMEM_BYTES>>>((uint8_t*)xptr, fptr, (unsigned*)cptr, gamma, beta, m);
}
```

```cpp
#include <cuda_runtime.h>
#include <cuda_bf16.h>
#include <cuda.h>
#include <stdint.h>

namespace {

#define WFIRST 1
#define NPR 1
#define P0M 1
#define P1M 0
constexpr int LOUT = 7985;
constexpr int MT = 50;
constexpr int NT = 160;
constexpr int XBLK = NT * 128;
constexpr int WBLK = 16384;
constexpr int LW = 4;
constexpr int WR = 5;
constexpr int WCHUNK = 32 * 4 * WBLK;
constexpr int XPAGES = 20;
constexpr int NFL = 2;
constexpr int XKEEP = 9;
constexpr int YSTEP = 2;
constexpr int YFLUSH = 17 + LW + 3 * YSTEP;

__device__ __align__(1024) uint8_t g_X[(XPAGES + 2) << 21];
__device__ __align__(1024) uint8_t g_W[(size_t)WR * WCHUNK];
__device__ __align__(1024) uint8_t g_Y[8ull * NT * 8192];
__device__ __align__(128) float g_E[16 * NT * 64];
__device__ unsigned long long g_part[128 * 128];
constexpr int C_FLAG = 0, C_LOADED = 36, C_REG = 68, C_EXIT = 69, C_E = 70, C_NUM = 71;
__device__ __align__(128) unsigned g_ctr[C_NUM * 32];
#define PROF_T(i)
#define PROF_C(i)
#define PROF_V(i, v)
#define PROF_W(acc, stmt) stmt

__device__ __align__(128) const uint32_t g_Fimg[2048] = {
 0x3f803f80,0x3f7d3f7f,0x3f783f7b,0x3f713f75,0x3f673f6d,0x3f5c3f62,0x3f4e3f55,0x3f3e3f46,0x3f2c3f35,0x3f183f22,0x3f043f0e,0x3edb3ef1,0x3eac3ec4,0x3e793e95,0x3e163e48,0x3d493dc9,
 0xbd490000,0xbe16bdc9,0xbe79be48,0xbeacbe95,0xbedbbec4,0xbf04bef1,0xbf18bf0e,0xbf2cbf22,0xbf3ebf35,0xbf4ebf46,0xbf5cbf55,0xbf67bf62,0xbf71bf6d,0xbf78bf75,0xbf7dbf7b,0xbf80bf7f,
 0x3e793ec4,0xbd493dc9,0xbeacbe48,0xbf18bef1,0x3f7d3f80,0x3f673f75,0x3f3e3f55,0x3f043f22,0xbf5cbf6d,0xbf2cbf46,0xbedbbf0e,0xbe16be95,0xbf4ebf35,0xbf71bf62,0xbf80bf7b,0xbf78bf7f,
 0x3f783f6d,0x3f803f7f,0x3f713f7b,0x3f4e3f62,0x3e160000,0x3edb3e95,0x3f2c3f0e,0x3f5c3f46,0xbf04bec4,0xbf3ebf22,0xbf67bf55,0xbf7dbf75,0x3f183f35,0x3eac3ef1,0x3d493e48,0xbe79bdc9,
 0xbf04bf35,0xbd49be95,0x3edb3e48,0x3f4e3f22,0x3f7d3f6d,0x3f713f7f,0x3f2c3f55,0x3e793ef1,0x3f783f80,0x3f3e3f62,0x3eac3f0e,0xbe163dc9,0xbf18bec4,0xbf67bf46,0xbf80bf7b,0xbf5cbf75,
 0x3f5c3f35,0x3f803f75,0x3f673f7b,0x3f183f46,0x3e163ec4,0xbeacbdc9,0xbf3ebf0e,0xbf78bf62,0xbe790000,0xbf2cbef1,0xbf71bf55,0xbf7dbf7f,0xbf4ebf6d,0xbedbbf22,0x3d49be48,0x3f043e95,
 0xbf2cbec4,0xbf7dbf62,0xbf5cbf7b,0xbeacbf22,0x3f673f35,0x3f783f7f,0x3f183f55,0xbd493e95,0xbf80bf6d,0xbf4ebf75,0xbe79bf0e,0x3edb3dc9,0x3f713f80,0x3f043f46,0xbe163e48,0xbf3ebef1,
 0x3f3e3f6d,0x3e163ef1,0xbf04be48,0xbf71bf46,0xbedbbf35,0x3e79bdc9,0x3f4e3f0e,0x3f803f75,0x3d493ec4,0xbf18be95,0xbf78bf55,0xbf67bf7f,0x3eac0000,0x3f5c3f22,0x3f7d3f7b,0x3f2c3f62,
 0xbedb0000,0xbf78bf46,0xbf4ebf7b,0xbd49bef1,0x3f3e3ec4,0x3f7d3f75,0x3f043f55,0xbeac3dc9,0xbf71bf35,0xbf5cbf7f,0xbe16bf0e,0x3f2c3e95,0x3f803f6d,0x3f183f62,0xbe793e48,0xbf67bf22,
 0x3f673f80,0x3e793f22,0xbf18be48,0xbf80bf62,0xbf2cbf6d,0x3e16be95,0x3f5c3f0e,0x3f713f7f,0x3eac3f35,0xbf04bdc9,0xbf7dbf55,0xbf3ebf75,0x3d49bec4,0x3f4e3ef1,0x3f783f7b,0x3edb3f46,
 0xbf7dbf6d,0xbeacbf46,0x3f2c3e48,0x3f783f75,0x3f040000,0x3f803f62,0x3edb3f55,0xbf18bdc9,0x3f4e3ec4,0x3f673f7f,0x3d493f0e,0xbf5cbef1,0x3e793f35,0xbf3ebe95,0xbf71bf7b,0xbe16bf22,
 0x3e16bec4,0x3f713f22,0x3f3e3f7b,0xbe793e95,0x3f5c3f80,0xbd493ef1,0xbf67bf0e,0xbf4ebf7f,0x3f183f6d,0xbedb3dc9,0xbf80bf55,0xbf04bf62,0xbf78bf35,0xbf2cbf75,0x3eacbe48,0x3f7d3f46,
 0x3f7d3f35,0x3edb3f62,0xbf3ebe48,0xbf5cbf7f,0x3e79bec4,0x3f803f46,0x3eac3f55,0xbf4ebe95,0xbf180000,0xbf71bf75,0x3d49bf0e,0x3f783f22,0x3f043f6d,0xbf2cbdc9,0xbf67bf7b,0x3e16bef1,
 0xbe16bf35,0x3f673ef1,0x3f2c3f7b,0xbf043dc9,0xbf78bf6d,0xbd49bf22,0x3f713f0e,0x3f183f75,0x3f4e3f80,0xbeac3e95,0xbf80bf55,0xbe79bf46,0x3f5c3ec4,0x3f3e3f7f,0xbedb3e48,0xbf7dbf62,
 0xbedbbf6d,0x3f5c3e95,0x3f183f7b,0xbf3ebdc9,0xbd49bf35,0x3f7d3f22,0x3e793f55,0xbf71bef1,0x3eacbec4,0x3f783f62,0xbe163f0e,0xbf80bf46,0x3f2c0000,0x3f4e3f7f,0xbf043e48,0xbf67bf75,
 0x3f673ec4,0x3f043f75,0xbf4ebe48,0xbf2cbf7f,0x3f803f35,0x3e163f46,0xbf78bf0e,0xbeacbf62,0x3f713f6d,0xbe793ef1,0xbf7dbf55,0x3d49bf22,0x3f3e3f80,0xbf183dc9,0xbf5cbf7b,0x3edbbe95,
 0xbd490000,0xbe16bdc9,0xbe79be48,0xbeacbe95,0xbedbbec4,0xbf04bef1,0xbf18bf0e,0xbf2cbf22,0xbf3ebf35,0xbf4ebf46,0xbf5cbf55,0xbf67bf62,0xbf71bf6d,0xbf78bf75,0xbf7dbf7b,0xbf80bf7f,
 0xbf80bf80,0xbf7dbf7f,0xbf78bf7b,0xbf71bf75,0xbf67bf6d,0xbf5cbf62,0xbf4ebf55,0xbf3ebf46,0xbf2cbf35,0xbf18bf22,0xbf04bf0e,0xbedbbef1,0xbeacbec4,0xbe79be95,0xbe16be48,0xbd49bdc9,
 0xbf78bf6d,0xbf80bf7f,0xbf71bf7b,0xbf4ebf62,0xbe160000,0xbedbbe95,0xbf2cbf0e,0xbf5cbf46,0x3f043ec4,0x3f3e3f22,0x3f673f55,0x3f7d3f75,0xbf18bf35,0xbeacbef1,0xbd49be48,0x3e793dc9,
 0x3e793ec4,0xbd493dc9,0xbeacbe48,0xbf18bef1,0x3f7d3f80,0x3f673f75,0x3f3e3f55,0x3f043f22,0xbf5cbf6d,0xbf2cbf46,0xbedbbf0e,0xbe16be95,0xbf4ebf35,0xbf71bf62,0xbf80bf7b,0xbf78bf7f,
 0x3f5c3f35,0x3f803f75,0x3f673f7b,0x3f183f46,0x3e163ec4,0xbeacbdc9,0xbf3ebf0e,0xbf78bf62,0xbe790000,0xbf2cbef1,0xbf71bf55,0xbf7dbf7f,0xbf4ebf6d,0xbedbbf22,0x3d49be48,0x3f043e95,
 0x3f043f35,0x3d493e95,0xbedbbe48,0xbf4ebf22,0xbf7dbf6d,0xbf71bf7f,0xbf2cbf55,0xbe79bef1,0xbf78bf80,0xbf3ebf62,0xbeacbf0e,0x3e16bdc9,0x3f183ec4,0x3f673f46,0x3f803f7b,0x3f5c3f75,
 0xbf3ebf6d,0xbe16bef1,0x3f043e48,0x3f713f46,0x3edb3f35,0xbe793dc9,0xbf4ebf0e,0xbf80bf75,0xbd49bec4,0x3f183e95,0x3f783f55,0x3f673f7f,0xbeac0000,0xbf5cbf22,0xbf7dbf7b,0xbf2cbf62,
 0xbf2cbec4,0xbf7dbf62,0xbf5cbf7b,0xbeacbf22,0x3f673f35,0x3f783f7f,0x3f183f55,0xbd493e95,0xbf80bf6d,0xbf4ebf75,0xbe79bf0e,0x3edb3dc9,0x3f713f80,0x3f043f46,0xbe163e48,0xbf3ebef1,
 0xbf67bf80,0xbe79bf22,0x3f183e48,0x3f803f62,0x3f2c3f6d,0xbe163e95,0xbf5cbf0e,0xbf71bf7f,0xbeacbf35,0x3f043dc9,0x3f7d3f55,0x3f3e3f75,0xbd493ec4,0xbf4ebef1,0xbf78bf7b,0xbedbbf46,
 0xbedb0000,0xbf78bf46,0xbf4ebf7b,0xbd49bef1,0x3f3e3ec4,0x3f7d3f75,0x3f043f55,0xbeac3dc9,0xbf71bf35,0xbf5cbf7f,0xbe16bf0e,0x3f2c3e95,0x3f803f6d,0x3f183f62,0xbe793e48,0xbf67bf22,
 0x3e16bec4,0x3f713f22,0x3f3e3f7b,0xbe793e95,0x3f5c3f80,0xbd493ef1,0xbf67bf0e,0xbf4ebf7f,0x3f183f6d,0xbedb3dc9,0xbf80bf55,0xbf04bf62,0xbf78bf35,0xbf2cbf75,0x3eacbe48,0x3f7d3f46,
 0x3f7d3f6d,0x3eac3f46,0xbf2cbe48,0xbf78bf75,0xbf040000,0xbf80bf62,0xbedbbf55,0x3f183dc9,0xbf4ebec4,0xbf67bf7f,0xbd49bf0e,0x3f5c3ef1,0xbe79bf35,0x3f3e3e95,0x3f713f7b,0x3e163f22,
 0x3e163f35,0xbf67bef1,0xbf2cbf7b,0x3f04bdc9,0x3f783f6d,0x3d493f22,0xbf71bf0e,0xbf18bf75,0xbf4ebf80,0x3eacbe95,0x3f803f55,0x3e793f46,0xbf5cbec4,0xbf3ebf7f,0x3edbbe48,0x3f7d3f62,
 0x3f7d3f35,0x3edb3f62,0xbf3ebe48,0xbf5cbf7f,0x3e79bec4,0x3f803f46,0x3eac3f55,0xbf4ebe95,0xbf180000,0xbf71bf75,0x3d49bf0e,0x3f783f22,0x3f043f6d,0xbf2cbdc9,0xbf67bf7b,0x3e16bef1,
 0x3f673ec4,0x3f043f75,0xbf4ebe48,0xbf2cbf7f,0x3f803f35,0x3e163f46,0xbf78bf0e,0xbeacbf62,0x3f713f6d,0xbe793ef1,0xbf7dbf55,0x3d49bf22,0x3f3e3f80,0xbf183dc9,0xbf5cbf7b,0x3edbbe95,
 0x3edb3f6d,0xbf5cbe95,0xbf18bf7b,0x3f3e3dc9,0x3d493f35,0xbf7dbf22,0xbe79bf55,0x3f713ef1,0xbeac3ec4,0xbf78bf62,0x3e16bf0e,0x3f803f46,0xbf2c0000,0xbf4ebf7f,0x3f04be48,0x3f673f75,
 0x3f2c3f80,0xbf4ebdc9,0xbf04bf7b,0x3f673e95,0x3eac3f6d,0xbf78bef1,0xbe16bf55,0x3f803f22,0xbd493f35,0xbf7dbf46,0x3e79bf0e,0x3f713f62,0xbedb3ec4,0xbf5cbf75,0x3f18be48,0x3f3e3f7f,
 0xbf3e0000,0xbf18bf7f,0x3f5c3e48,0x3edb3f75,0xbf71bec4,0xbe79bf62,0x3f7d3f0e,0x3d493f46,0xbf80bf35,0x3e16bf22,0x3f783f55,0xbeac3ef1,0xbf67bf6d,0x3f04be95,0x3f4e3f7b,0xbf2c3dc9,
 0xbf043ec4,0xbf2cbf7f,0x3f673e48,0x3e163f62,0x3f183f80,0xbf71be95,0xbd49bf55,0x3f783f46,0xbe79bf6d,0x3f803f22,0xbeac3f0e,0xbf4ebf75,0xbf7dbf35,0x3edbbef1,0x3f3e3f7b,0xbf5cbdc9,
 0x3f5c3f6d,0xbf3e3dc9,0xbedbbf7b,0x3f7d3ef1,0x3f4e0000,0x3eac3f75,0xbf80bf0e,0x3e79bf22,0xbf78bec4,0x3d49bf46,0x3f713f55,0xbf183e95,0xbe163f35,0xbf67bf62,0x3f2cbe48,0x3f043f7f,
 0x3e79bf35,0x3f3e3f75,0xbf71be48,0x3e16bf46,0x3f4e3f6d,0xbf67bdc9,0x3d49bf55,0x3f5c3f62,0x3f043f80,0xbf80bef1,0x3edbbf0e,0x3f183f7f,0xbf7dbec4,0x3eacbf22,0x3f2c3f7b,0xbf78be95,
 0x3f783f35,0xbf2c3e95,0xbeacbf7b,0x3f7d3f22,0xbf183ec4,0xbedbbf7f,0x3f803f0e,0xbf043ef1,0xbf5c0000,0xbd49bf62,0x3f673f55,0xbf4e3dc9,0xbe16bf6d,0x3f713f46,0xbf3e3e48,0xbe79bf75,
 0xbf80bec4,0x3f18bef1,0x3e793f7b,0xbf67bf46,0x3f713f35,0xbf5c3dc9,0x3e16bf55,0x3f2c3f75,0xbf3ebf6d,0x3f7d3e95,0xbf043f0e,0xbeacbf7f,0x3edb3f80,0xbf78bf22,0x3f4ebe48,0xbd493f62,
 0x3d493f6d,0xbf4ebf62,0x3f783e48,0xbedb3f22,0x3eacbf35,0x3f043f7f,0xbf7dbf0e,0x3f3ebe95,0xbf2c3ec4,0xbe16bf75,0x3f5c3f55,0xbf71bdc9,0x3f670000,0xbe793f46,0xbf18bf7b,0x3f803ef1,
 0xbf710000,0x3f04bf22,0x3e163f7b,0xbf3ebf62,0x3f803ec4,0xbf4e3e95,0x3e79bf55,0x3edb3f7f,0xbf67bf35,0x3f783dc9,0xbf183f0e,0xbd49bf75,0x3f2c3f6d,0xbf7dbef1,0x3f5cbe48,0xbeac3f46,
 0x3eac3f80,0xbf5cbf46,0x3f7d3e48,0xbf2c3ef1,0x3d49bf6d,0x3f183f75,0xbf78bf0e,0x3f67bdc9,0xbedb3f35,0xbe79bf7f,0x3f4e3f55,0xbf80be95,0x3f3ebec4,0xbe163f62,0xbf04bf7b,0x3f713f22,
 0xbf18bf6d,0x3f673f22,0xbf80be48,0x3f5cbe95,0x3f780000,0xbf3e3ef1,0x3eacbf55,0x3e163f7f,0x3f7d3ec4,0xbf713dc9,0x3f2cbf0e,0xbe793f62,0xbf043f35,0x3d49bf75,0x3edb3f7b,0xbf4ebf46,
 0x3f4ebec4,0xbedb3f46,0xbd49bf7b,0x3f043f75,0x3e793f80,0xbf2cbf62,0x3f713f0e,0xbf7dbdc9,0xbe163f6d,0xbeacbf7f,0x3f3e3f55,0xbf78bef1,0xbf5cbf35,0x3f803e95,0xbf673e48,0x3f18bf22,
 0x3f4e3f35,0xbf71bef1,0x3f803e48,0xbf783dc9,0x3f5cbec4,0xbf2c3f22,0x3edbbf55,0xbe163f75,0xbf7d0000,0x3f67be95,0xbf3e3f0e,0x3f04bf46,0xbe793f6d,0xbd49bf7f,0x3eac3f7b,0xbf18bf62,
 0x3f18bf35,0xbeac3f62,0x3d49bf7b,0x3e793f7f,0xbf04bf6d,0x3f3e3f46,0xbf67bf0e,0x3f7d3e95,0x3e163f80,0xbedbbf75,0x3f2c3f55,0xbf5cbf22,0x3f783ec4,0xbf80bdc9,0x3f71be48,0xbf4e3ef1,
 0x3eacbf6d,0xbe793f75,0x3e16bf7b,0xbd493f7f,0x3f2cbf35,0xbf183f46,0x3f04bf55,0xbedb3f62,0x3f67bec4,0xbf5c3ef1,0x3f4ebf0e,0xbf3e3f22,0x3f800000,0xbf7d3dc9,0x3f78be48,0xbf713e95,
 0x3f713ec4,0xbf78be95,0x3f7d3e48,0xbf80bdc9,0x3f3e3f35,0xbf4ebf22,0x3f5c3f0e,0xbf67bef1,0x3edb3f6d,0xbf04bf62,0x3f183f55,0xbf2cbf46,0x3d493f80,0xbe16bf7f,0x3e793f7b,0xbeacbf75,
 0xbf3e0000,0xbf18bf7f,0x3f5c3e48,0x3edb3f75,0xbf71bec4,0xbe79bf62,0x3f7d3f0e,0x3d493f46,0xbf80bf35,0x3e16bf22,0x3f783f55,0xbeac3ef1,0xbf67bf6d,0x3f04be95,0x3f4e3f7b,0xbf2c3dc9,
 0xbf2cbf80,0x3f4e3dc9,0x3f043f7b,0xbf67be95,0xbeacbf6d,0x3f783ef1,0x3e163f55,0xbf80bf22,0x3d49bf35,0x3f7d3f46,0xbe793f0e,0xbf71bf62,0x3edbbec4,0x3f5c3f75,0xbf183e48,0xbf3ebf7f,
 0xbf5cbf6d,0x3f3ebdc9,0x3edb3f7b,0xbf7dbef1,0xbf4e0000,0xbeacbf75,0x3f803f0e,0xbe793f22,0x3f783ec4,0xbd493f46,0xbf71bf55,0x3f18be95,0x3e16bf35,0x3f673f62,0xbf2c3e48,0xbf04bf7f,
 0xbf043ec4,0xbf2cbf7f,0x3f673e48,0x3e163f62,0x3f183f80,0xbf71be95,0xbd49bf55,0x3f783f46,0xbe79bf6d,0x3f803f22,0xbeac3f0e,0xbf4ebf75,0xbf7dbf35,0x3edbbef1,0x3f3e3f7b,0xbf5cbdc9,
 0x3f783f35,0xbf2c3e95,0xbeacbf7b,0x3f7d3f22,0xbf183ec4,0xbedbbf7f,0x3f803f0e,0xbf043ef1,0xbf5c0000,0xbd49bf62,0x3f673f55,0xbf4e3dc9,0xbe16bf6d,0x3f713f46,0xbf3e3e48,0xbe79bf75,
 0xbe793f35,0xbf3ebf75,0x3f713e48,0xbe163f46,0xbf4ebf6d,0x3f673dc9,0xbd493f55,0xbf5cbf62,0xbf04bf80,0x3f803ef1,0xbedb3f0e,0xbf18bf7f,0x3f7d3ec4,0xbeac3f22,0xbf2cbf7b,0x3f783e95,
 0xbd49bf6d,0x3f4e3f62,0xbf78be48,0x3edbbf22,0xbeac3f35,0xbf04bf7f,0x3f7d3f0e,0xbf3e3e95,0x3f2cbec4,0x3e163f75,0xbf5cbf55,0x3f713dc9,0xbf670000,0x3e79bf46,0x3f183f7b,0xbf80bef1,
 0xbf80bec4,0x3f18bef1,0x3e793f7b,0xbf67bf46,0x3f713f35,0xbf5c3dc9,0x3e16bf55,0x3f2c3f75,0xbf3ebf6d,0x3f7d3e95,0xbf043f0e,0xbeacbf7f,0x3edb3f80,0xbf78bf22,0x3f4ebe48,0xbd493f62,
 0xbeacbf80,0x3f5c3f46,0xbf7dbe48,0x3f2cbef1,0xbd493f6d,0xbf18bf75,0x3f783f0e,0xbf673dc9,0x3edbbf35,0x3e793f7f,0xbf4ebf55,0x3f803e95,0xbf3e3ec4,0x3e16bf62,0x3f043f7b,0xbf71bf22,
 0xbf710000,0x3f04bf22,0x3e163f7b,0xbf3ebf62,0x3f803ec4,0xbf4e3e95,0x3e79bf55,0x3edb3f7f,0xbf67bf35,0x3f783dc9,0xbf183f0e,0xbd49bf75,0x3f2c3f6d,0xbf7dbef1,0x3f5cbe48,0xbeac3f46,
 0x3f4ebec4,0xbedb3f46,0xbd49bf7b,0x3f043f75,0x3e793f80,0xbf2cbf62,0x3f713f0e,0xbf7dbdc9,0xbe163f6d,0xbeacbf7f,0x3f3e3f55,0xbf78bef1,0xbf5cbf35,0x3f803e95,0xbf673e48,0x3f18bf22,
 0x3f183f6d,0xbf67bf22,0x3f803e48,0xbf5c3e95,0xbf780000,0x3f3ebef1,0xbeac3f55,0xbe16bf7f,0xbf7dbec4,0x3f71bdc9,0xbf2c3f0e,0x3e79bf62,0x3f04bf35,0xbd493f75,0xbedbbf7b,0x3f4e3f46,
 0xbf183f35,0x3eacbf62,0xbd493f7b,0xbe79bf7f,0x3f043f6d,0xbf3ebf46,0x3f673f0e,0xbf7dbe95,0xbe16bf80,0x3edb3f75,0xbf2cbf55,0x3f5c3f22,0xbf78bec4,0x3f803dc9,0xbf713e48,0x3f4ebef1,
 0x3f4e3f35,0xbf71bef1,0x3f803e48,0xbf783dc9,0x3f5cbec4,0xbf2c3f22,0x3edbbf55,0xbe163f75,0xbf7d0000,0x3f67be95,0xbf3e3f0e,0x3f04bf46,0xbe793f6d,0xbd49bf7f,0x3eac3f7b,0xbf18bf62,
 0x3f713ec4,0xbf78be95,0x3f7d3e48,0xbf80bdc9,0x3f3e3f35,0xbf4ebf22,0x3f5c3f0e,0xbf67bef1,0x3edb3f6d,0xbf04bf62,0x3f183f55,0xbf2cbf46,0x3d493f80,0xbe16bf7f,0x3e793f7b,0xbeacbf75,
 0xbeac3f6d,0x3e79bf75,0xbe163f7b,0x3d49bf7f,0xbf2c3f35,0x3f18bf46,0xbf043f55,0x3edbbf62,0xbf673ec4,0x3f5cbef1,0xbf4e3f0e,0x3f3ebf22,0xbf800000,0x3f7dbdc9,0xbf783e48,0x3f71be95,
 0xbd493f80,0x3e16bf7f,0xbe793f7b,0x3eacbf75,0xbedb3f6d,0x3f04bf62,0xbf183f55,0x3f2cbf46,0xbf3e3f35,0x3f4ebf22,0xbf5c3f0e,0x3f67bef1,0xbf713ec4,0x3f78be95,0xbf7d3e48,0x3f80bdc9,
 0xbf800000,0x3f7d3dc9,0xbf78be48,0x3f713e95,0xbf67bec4,0x3f5c3ef1,0xbf4ebf0e,0x3f3e3f22,0xbf2cbf35,0x3f183f46,0xbf04bf55,0x3edb3f62,0xbeacbf6d,0x3e793f75,0xbe16bf7b,0x3d493f7f,
 0xbf783ec4,0x3f80bdc9,0xbf71be48,0x3f4e3ef1,0xbe163f80,0x3edbbf75,0xbf2c3f55,0x3f5cbf22,0x3f04bf6d,0xbf3e3f46,0x3f67bf0e,0xbf7d3e95,0xbf18bf35,0x3eac3f62,0xbd49bf7b,0xbe793f7f,
 0x3e793f6d,0x3d49bf7f,0xbeac3f7b,0x3f18bf62,0x3f7d0000,0xbf67be95,0x3f3e3f0e,0xbf04bf46,0xbf5cbec4,0x3f2c3f22,0xbedbbf55,0x3e163f75,0xbf4e3f35,0x3f71bef1,0xbf803e48,0x3f783dc9,
 0x3f5cbf35,0xbf803e95,0x3f673e48,0xbf18bf22,0x3e163f6d,0x3eacbf7f,0xbf3e3f55,0x3f78bef1,0xbe793f80,0x3f2cbf62,0xbf713f0e,0x3f7dbdc9,0xbf4ebec4,0x3edb3f46,0x3d49bf7b,0xbf043f75,
 0x3f043f35,0xbd49bf75,0xbedb3f7b,0x3f4ebf46,0xbf7d3ec4,0x3f713dc9,0xbf2cbf0e,0x3e793f62,0xbf780000,0x3f3e3ef1,0xbeacbf55,0xbe163f7f,0x3f18bf6d,0xbf673f22,0x3f80be48,0xbf5cbe95,
 0xbf3ebec4,0x3e163f62,0x3f04bf7b,0xbf713f22,0x3edb3f35,0x3e79bf7f,0xbf4e3f55,0x3f80be95,0xbd49bf6d,0xbf183f75,0x3f78bf0e,0xbf67bdc9,0xbeac3f80,0x3f5cbf46,0xbf7d3e48,0x3f2c3ef1,
 0xbf2c3f6d,0x3f7dbef1,0xbf5cbe48,0x3eac3f46,0x3f67bf35,0xbf783dc9,0x3f183f0e,0x3d49bf75,0xbf803ec4,0x3f4e3e95,0xbe79bf55,0xbedb3f7f,0x3f710000,0xbf04bf22,0xbe163f7b,0x3f3ebf62,
 0xbf670000,0x3e793f46,0x3f18bf7b,0xbf803ef1,0x3f2c3ec4,0x3e16bf75,0xbf5c3f55,0x3f71bdc9,0xbeacbf35,0xbf043f7f,0x3f7dbf0e,0xbf3ebe95,0xbd493f6d,0x3f4ebf62,0xbf783e48,0x3edb3f22,
 0xbedb3f80,0x3f78bf22,0xbf4ebe48,0x3d493f62,0x3f3ebf6d,0xbf7d3e95,0x3f043f0e,0x3eacbf7f,0xbf713f35,0x3f5c3dc9,0xbe16bf55,0xbf2c3f75,0x3f80bec4,0xbf18bef1,0xbe793f7b,0x3f67bf46,
 0x3e16bf6d,0xbf713f46,0x3f3e3e48,0x3e79bf75,0x3f5c0000,0x3d49bf62,0xbf673f55,0x3f4e3dc9,0x3f183ec4,0x3edbbf7f,0xbf803f0e,0x3f043ef1,0xbf783f35,0x3f2c3e95,0x3eacbf7b,0xbf7d3f22,
 0x3f7dbec4,0xbeacbf22,0xbf2c3f7b,0x3f78be95,0xbf043f80,0x3f80bef1,0xbedbbf0e,0xbf183f7f,0xbf4e3f6d,0x3f67bdc9,0xbd49bf55,0xbf5c3f62,0xbe79bf35,0xbf3e3f75,0x3f71be48,0xbe16bf46,
 0x3e163f35,0x3f67bf62,0xbf2cbe48,0xbf043f7f,0x3f78bec4,0xbd49bf46,0xbf713f55,0x3f183e95,0xbf4e0000,0xbeac3f75,0x3f80bf0e,0xbe79bf22,0xbf5c3f6d,0x3f3e3dc9,0x3edbbf7b,0xbf7d3ef1,
 0x3f7dbf35,0xbedbbef1,0xbf3e3f7b,0x3f5cbdc9,0x3e79bf6d,0xbf803f22,0x3eac3f0e,0x3f4ebf75,0xbf183f80,0x3f71be95,0x3d49bf55,0xbf783f46,0x3f043ec4,0x3f2cbf7f,0xbf673e48,0xbe163f62,
 0x3f67bf6d,0xbf04be95,0xbf4e3f7b,0x3f2c3dc9,0x3f80bf35,0xbe16bf22,0xbf783f55,0x3eac3ef1,0x3f71bec4,0x3e79bf62,0xbf7d3f0e,0xbd493f46,0x3f3e0000,0x3f18bf7f,0xbf5c3e48,0xbedb3f75,
 0x3edb3ec4,0x3f5cbf75,0xbf18be48,0xbf3e3f7f,0x3d493f35,0x3f7dbf46,0xbe79bf0e,0xbf713f62,0xbeac3f6d,0x3f78bef1,0x3e16bf55,0xbf803f22,0xbf2c3f80,0x3f4ebdc9,0x3f04bf7b,0xbf673e95,
 0xbf800000,0x3f7d3dc9,0xbf78be48,0x3f713e95,0xbf67bec4,0x3f5c3ef1,0xbf4ebf0e,0x3f3e3f22,0xbf2cbf35,0x3f183f46,0xbf04bf55,0x3edb3f62,0xbeacbf6d,0x3e793f75,0xbe16bf7b,0x3d493f7f,
 0x3d49bf80,0xbe163f7f,0x3e79bf7b,0xbeac3f75,0x3edbbf6d,0xbf043f62,0x3f18bf55,0xbf2c3f46,0x3f3ebf35,0xbf4e3f22,0x3f5cbf0e,0xbf673ef1,0x3f71bec4,0xbf783e95,0x3f7dbe48,0xbf803dc9,
 0xbe79bf6d,0xbd493f7f,0x3eacbf7b,0xbf183f62,0xbf7d0000,0x3f673e95,0xbf3ebf0e,0x3f043f46,0x3f5c3ec4,0xbf2cbf22,0x3edb3f55,0xbe16bf75,0x3f4ebf35,0xbf713ef1,0x3f80be48,0xbf78bdc9,
 0xbf783ec4,0x3f80bdc9,0xbf71be48,0x3f4e3ef1,0xbe163f80,0x3edbbf75,0xbf2c3f55,0x3f5cbf22,0x3f04bf6d,0xbf3e3f46,0x3f67bf0e,0xbf7d3e95,0xbf18bf35,0x3eac3f62,0xbd49bf7b,0xbe793f7f,
 0x3f043f35,0xbd49bf75,0xbedb3f7b,0x3f4ebf46,0xbf7d3ec4,0x3f713dc9,0xbf2cbf0e,0x3e793f62,0xbf780000,0x3f3e3ef1,0xbeacbf55,0xbe163f7f,0x3f18bf6d,0xbf673f22,0x3f80be48,0xbf5cbe95,
 0xbf5c3f35,0x3f80be95,0xbf67be48,0x3f183f22,0xbe16bf6d,0xbeac3f7f,0x3f3ebf55,0xbf783ef1,0x3e79bf80,0xbf2c3f62,0x3f71bf0e,0xbf7d3dc9,0x3f4e3ec4,0xbedbbf46,0xbd493f7b,0x3f04bf75,
 0x3f2cbf6d,0xbf7d3ef1,0x3f5c3e48,0xbeacbf46,0xbf673f35,0x3f78bdc9,0xbf18bf0e,0xbd493f75,0x3f80bec4,0xbf4ebe95,0x3e793f55,0x3edbbf7f,0xbf710000,0x3f043f22,0x3e16bf7b,0xbf3e3f62,
 0xbf3ebec4,0x3e163f62,0x3f04bf7b,0xbf713f22,0x3edb3f35,0x3e79bf7f,0xbf4e3f55,0x3f80be95,0xbd49bf6d,0xbf183f75,0x3f78bf0e,0xbf67bdc9,0xbeac3f80,0x3f5cbf46,0xbf7d3e48,0x3f2c3ef1,
 0x3edbbf80,0xbf783f22,0x3f4e3e48,0xbd49bf62,0xbf3e3f6d,0x3f7dbe95,0xbf04bf0e,0xbeac3f7f,0x3f71bf35,0xbf5cbdc9,0x3e163f55,0x3f2cbf75,0xbf803ec4,0x3f183ef1,0x3e79bf7b,0xbf673f46,
 0xbf670000,0x3e793f46,0x3f18bf7b,0xbf803ef1,0x3f2c3ec4,0x3e16bf75,0xbf5c3f55,0x3f71bdc9,0xbeacbf35,0xbf043f7f,0x3f7dbf0e,0xbf3ebe95,0xbd493f6d,0x3f4ebf62,0xbf783e48,0x3edb3f22,
 0x3f7dbec4,0xbeacbf22,0xbf2c3f7b,0x3f78be95,0xbf043f80,0x3f80bef1,0xbedbbf0e,0xbf183f7f,0xbf4e3f6d,0x3f67bdc9,0xbd49bf55,0xbf5c3f62,0xbe79bf35,0xbf3e3f75,0x3f71be48,0xbe16bf46,
 0xbe163f6d,0x3f71bf46,0xbf3ebe48,0xbe793f75,0xbf5c0000,0xbd493f62,0x3f67bf55,0xbf4ebdc9,0xbf18bec4,0xbedb3f7f,0x3f80bf0e,0xbf04bef1,0x3f78bf35,0xbf2cbe95,0xbeac3f7b,0x3f7dbf22,
 0xbf7d3f35,0x3edb3ef1,0x3f3ebf7b,0xbf5c3dc9,0xbe793f6d,0x3f80bf22,0xbeacbf0e,0xbf4e3f75,0x3f18bf80,0xbf713e95,0xbd493f55,0x3f78bf46,0xbf04bec4,0xbf2c3f7f,0x3f67be48,0x3e16bf62,
 0x3e163f35,0x3f67bf62,0xbf2cbe48,0xbf043f7f,0x3f78bec4,0xbd49bf46,0xbf713f55,0x3f183e95,0xbf4e0000,0xbeac3f75,0x3f80bf0e,0xbe79bf22,0xbf5c3f6d,0x3f3e3dc9,0x3edbbf7b,0xbf7d3ef1,
 0x3edb3ec4,0x3f5cbf75,0xbf18be48,0xbf3e3f7f,0x3d493f35,0x3f7dbf46,0xbe79bf0e,0xbf713f62,0xbeac3f6d,0x3f78bef1,0x3e16bf55,0xbf803f22,0xbf2c3f80,0x3f4ebdc9,0x3f04bf7b,0xbf673e95,
 0xbf673f6d,0x3f043e95,0x3f4ebf7b,0xbf2cbdc9,0xbf803f35,0x3e163f22,0x3f78bf55,0xbeacbef1,0xbf713ec4,0xbe793f62,0x3f7dbf0e,0x3d49bf46,0xbf3e0000,0xbf183f7f,0x3f5cbe48,0x3edbbf75,
 0xbf3e3f80,0x3f183dc9,0x3f5cbf7b,0xbedbbe95,0xbf713f6d,0x3e793ef1,0x3f7dbf55,0xbd49bf22,0xbf803f35,0xbe163f46,0x3f78bf0e,0x3eacbf62,0xbf673ec4,0xbf043f75,0x3f4ebe48,0x3f2cbf7f,
 0xbf2c0000,0xbf4e3f7f,0x3f043e48,0x3f67bf75,0xbeacbec4,0xbf783f62,0x3e163f0e,0x3f80bf46,0x3d49bf35,0xbf7d3f22,0xbe793f55,0x3f71bef1,0x3edbbf6d,0xbf5c3e95,0xbf183f7b,0x3f3ebdc9,
 0xbf5c3ec4,0xbf3e3f7f,0x3edb3e48,0x3f7dbf62,0xbf4e3f80,0x3eac3e95,0x3f80bf55,0x3e79bf46,0x3f78bf6d,0x3d49bf22,0xbf713f0e,0xbf183f75,0x3e16bf35,0xbf673ef1,0xbf2c3f7b,0x3f043dc9,
 0xbf043f6d,0x3f2cbdc9,0x3f67bf7b,0xbe16bef1,0x3f180000,0x3f71bf75,0xbd49bf0e,0xbf783f22,0xbe79bec4,0xbf803f46,0xbeac3f55,0x3f4ebe95,0xbf7d3f35,0xbedb3f62,0x3f3ebe48,0x3f5cbf7f,
 0x3f78bf35,0x3f2cbf75,0xbeacbe48,0xbf7d3f46,0xbf183f6d,0x3edb3dc9,0x3f80bf55,0x3f04bf62,0xbf5c3f80,0x3d493ef1,0x3f67bf0e,0x3f4ebf7f,0xbe16bec4,0xbf713f22,0xbf3e3f7b,0x3e793e95,
 0xbe793f35,0x3f3ebe95,0x3f71bf7b,0x3e16bf22,0xbf4e3ec4,0xbf673f7f,0xbd493f0e,0x3f5cbef1,0xbf040000,0xbf803f62,0xbedb3f55,0x3f18bdc9,0x3f7dbf6d,0x3eacbf46,0xbf2c3e48,0xbf783f75,
 0xbd49bec4,0xbf4e3ef1,0xbf783f7b,0xbedb3f46,0xbeac3f35,0x3f04bdc9,0x3f7dbf55,0x3f3ebf75,0x3f2cbf6d,0xbe16be95,0xbf5c3f0e,0xbf713f7f,0xbf673f80,0xbe793f22,0x3f18be48,0x3f80bf62,
 0xbf803f6d,0xbf183f62,0x3e793e48,0x3f67bf22,0x3f71bf35,0x3f5cbf7f,0x3e16bf0e,0xbf2c3e95,0xbf3e3ec4,0xbf7d3f75,0xbf043f55,0x3eac3dc9,0x3edb0000,0x3f78bf46,0x3f4ebf7b,0x3d49bef1,
 0xbeac0000,0xbf5c3f22,0xbf7d3f7b,0xbf2c3f62,0xbd493ec4,0x3f18be95,0x3f78bf55,0x3f67bf7f,0x3edbbf35,0xbe79bdc9,0xbf4e3f0e,0xbf803f75,0xbf3e3f6d,0xbe163ef1,0x3f04be48,0x3f71bf46,
 0xbf713f80,0xbf043f46,0x3e163e48,0x3f3ebef1,0x3f80bf6d,0x3f4ebf75,0x3e79bf0e,0xbedb3dc9,0xbf673f35,0xbf783f7f,0xbf183f55,0x3d493e95,0x3f2cbec4,0x3f7dbf62,0x3f5cbf7b,0x3eacbf22,
 0x3f4ebf6d,0x3edbbf22,0xbd49be48,0xbf043e95,0x3e790000,0x3f2cbef1,0x3f71bf55,0x3f7dbf7f,0xbe163ec4,0x3eacbdc9,0x3f3ebf0e,0x3f78bf62,0xbf5c3f35,0xbf803f75,0xbf673f7b,0xbf183f46,
 0x3f18bec4,0x3f67bf46,0x3f80bf7b,0x3f5cbf75,0xbf783f80,0xbf3e3f62,0xbeac3f0e,0x3e163dc9,0xbf7d3f6d,0xbf713f7f,0xbf2c3f55,0xbe793ef1,0x3f04bf35,0x3d49be95,0xbedb3e48,0xbf4e3f22,
 0xbf183f35,0xbeac3ef1,0xbd493e48,0x3e79bdc9,0x3f04bec4,0x3f3ebf22,0x3f67bf55,0x3f7dbf75,0xbe160000,0xbedb3e95,0xbf2c3f0e,0xbf5c3f46,0xbf783f6d,0xbf803f7f,0xbf713f7b,0xbf4e3f62,
 0x3f4ebf35,0x3f71bf62,0x3f80bf7b,0x3f78bf7f,0x3f5cbf6d,0x3f2cbf46,0x3edbbf0e,0x3e16be95,0xbf7d3f80,0xbf673f75,0xbf3e3f55,0xbf043f22,0xbe793ec4,0x3d493dc9,0x3eacbe48,0x3f18bef1,
 0x3f71bf6d,0x3f78bf75,0x3f7dbf7b,0x3f80bf7f,0x3f3ebf35,0x3f4ebf46,0x3f5cbf55,0x3f67bf62,0x3edbbec4,0x3f04bef1,0x3f18bf0e,0x3f2cbf22,0x3d490000,0x3e16bdc9,0x3e79be48,0x3eacbe95,
 0xbeac3ec4,0xbe793e95,0xbe163e48,0xbd493dc9,0xbf2c3f35,0xbf183f22,0xbf043f0e,0xbedb3ef1,0xbf673f6d,0xbf5c3f62,0xbf4e3f55,0xbf3e3f46,0xbf803f80,0xbf7d3f7f,0xbf783f7b,0xbf713f75,
 0xbf2c0000,0xbf4e3f7f,0x3f043e48,0x3f67bf75,0xbeacbec4,0xbf783f62,0x3e163f0e,0x3f80bf46,0x3d49bf35,0xbf7d3f22,0xbe793f55,0x3f71bef1,0x3edbbf6d,0xbf5c3e95,0xbf183f7b,0x3f3ebdc9,
 0x3f3ebf80,0xbf18bdc9,0xbf5c3f7b,0x3edb3e95,0x3f71bf6d,0xbe79bef1,0xbf7d3f55,0x3d493f22,0x3f80bf35,0x3e16bf46,0xbf783f0e,0xbeac3f62,0x3f67bec4,0x3f04bf75,0xbf4e3e48,0xbf2c3f7f,
 0x3f04bf6d,0xbf2c3dc9,0xbf673f7b,0x3e163ef1,0xbf180000,0xbf713f75,0x3d493f0e,0x3f78bf22,0x3e793ec4,0x3f80bf46,0x3eacbf55,0xbf4e3e95,0x3f7dbf35,0x3edbbf62,0xbf3e3e48,0xbf5c3f7f,
 0xbf5c3ec4,0xbf3e3f7f,0x3edb3e48,0x3f7dbf62,0xbf4e3f80,0x3eac3e95,0x3f80bf55,0x3e79bf46,0x3f78bf6d,0x3d49bf22,0xbf713f0e,0xbf183f75,0x3e16bf35,0xbf673ef1,0xbf2c3f7b,0x3f043dc9,
 0xbe793f35,0x3f3ebe95,0x3f71bf7b,0x3e16bf22,0xbf4e3ec4,0xbf673f7f,0xbd493f0e,0x3f5cbef1,0xbf040000,0xbf803f62,0xbedb3f55,0x3f18bdc9,0x3f7dbf6d,0x3eacbf46,0xbf2c3e48,0xbf783f75,
 0xbf783f35,0xbf2c3f75,0x3eac3e48,0x3f7dbf46,0x3f18bf6d,0xbedbbdc9,0xbf803f55,0xbf043f62,0x3f5cbf80,0xbd49bef1,0xbf673f0e,0xbf4e3f7f,0x3e163ec4,0x3f71bf22,0x3f3ebf7b,0xbe79be95,
 0x3f80bf6d,0x3f18bf62,0xbe79be48,0xbf673f22,0xbf713f35,0xbf5c3f7f,0xbe163f0e,0x3f2cbe95,0x3f3ebec4,0x3f7dbf75,0x3f04bf55,0xbeacbdc9,0xbedb0000,0xbf783f46,0xbf4e3f7b,0xbd493ef1,
 0xbd49bec4,0xbf4e3ef1,0xbf783f7b,0xbedb3f46,0xbeac3f35,0x3f04bdc9,0x3f7dbf55,0x3f3ebf75,0x3f2cbf6d,0xbe16be95,0xbf5c3f0e,0xbf713f7f,0xbf673f80,0xbe793f22,0x3f18be48,0x3f80bf62,
 0x3f71bf80,0x3f04bf46,0xbe16be48,0xbf3e3ef1,0xbf803f6d,0xbf4e3f75,0xbe793f0e,0x3edbbdc9,0x3f67bf35,0x3f78bf7f,0x3f18bf55,0xbd49be95,0xbf2c3ec4,0xbf7d3f62,0xbf5c3f7b,0xbeac3f22,
 0xbeac0000,0xbf5c3f22,0xbf7d3f7b,0xbf2c3f62,0xbd493ec4,0x3f18be95,0x3f78bf55,0x3f67bf7f,0x3edbbf35,0xbe79bdc9,0xbf4e3f0e,0xbf803f75,0xbf3e3f6d,0xbe163ef1,0x3f04be48,0x3f71bf46,
 0x3f18bec4,0x3f67bf46,0x3f80bf7b,0x3f5cbf75,0xbf783f80,0xbf3e3f62,0xbeac3f0e,0x3e163dc9,0xbf7d3f6d,0xbf713f7f,0xbf2c3f55,0xbe793ef1,0x3f04bf35,0x3d49be95,0xbedb3e48,0xbf4e3f22,
 0xbf4e3f6d,0xbedb3f22,0x3d493e48,0x3f04be95,0xbe790000,0xbf2c3ef1,0xbf713f55,0xbf7d3f7f,0x3e16bec4,0xbeac3dc9,0xbf3e3f0e,0xbf783f62,0x3f5cbf35,0x3f80bf75,0x3f67bf7b,0x3f18bf46,
 0xbf4e3f35,0xbf713f62,0xbf803f7b,0xbf783f7f,0xbf5c3f6d,0xbf2c3f46,0xbedb3f0e,0xbe163e95,0x3f7dbf80,0x3f67bf75,0x3f3ebf55,0x3f04bf22,0x3e79bec4,0xbd49bdc9,0xbeac3e48,0xbf183ef1,
 0xbf183f35,0xbeac3ef1,0xbd493e48,0x3e79bdc9,0x3f04bec4,0x3f3ebf22,0x3f67bf55,0x3f7dbf75,0xbe160000,0xbedb3e95,0xbf2c3f0e,0xbf5c3f46,0xbf783f6d,0xbf803f7f,0xbf713f7b,0xbf4e3f62,
 0xbeac3ec4,0xbe793e95,0xbe163e48,0xbd493dc9,0xbf2c3f35,0xbf183f22,0xbf043f0e,0xbedb3ef1,0xbf673f6d,0xbf5c3f62,0xbf4e3f55,0xbf3e3f46,0xbf803f80,0xbf7d3f7f,0xbf783f7b,0xbf713f75,
 0xbf713f6d,0xbf783f75,0xbf7d3f7b,0xbf803f7f,0xbf3e3f35,0xbf4e3f46,0xbf5c3f55,0xbf673f62,0xbedb3ec4,0xbf043ef1,0xbf183f0e,0xbf2c3f22,0xbd490000,0xbe163dc9,0xbe793e48,0xbeac3e95,
};
__device__ __align__(128) const uint32_t g_Gimg[1792] = {
 0x00003d00,0x00003d00,0x00003d00,0x00003d00,0x00003d00,0x00003d00,0x00003d00,0x00003d00,0x00003d00,0x00003d00,0x00003d00,0x00003d00,0x00003d00,0x00003d00,0x00003d00,0x00003d00,
 0x00003d00,0x00003d00,0x00003d00,0x00003d00,0x00003d00,0x00003d00,0x00003d00,0x00003d00,0x00003d00,0x00003d00,0x00003d00,0x00003d00,0x00003d00,0x00003d00,0x00003d00,0x00003d00,
 0xbc5b3ce7,0xbc843cdc,0xbc983cce,0xbcac3cbe,0xbac93d00,0xbb963cfd,0xbbf93cf8,0xbc2c3cf1,0xbcf13c2c,0xbcf83bf9,0xbcfd3b96,0xbd003ac9,0xbcbe3cac,0xbcce3c98,0xbcdc3c84,0xbce73c5b,
 0xbce7bc5b,0xbcdcbc84,0xbccebc98,0xbcbebcac,0xbd00bac9,0xbcfdbb96,0xbcf8bbf9,0xbcf1bc2c,0xbc2cbcf1,0xbbf9bcf8,0xbb96bcfd,0xbac9bd00,0xbcacbcbe,0xbc98bcce,0xbc84bcdc,0xbc5bbce7,
 0xbcffbb49,0xbcf5bc15,0xbce2bc71,0xbcc6bca2,0xbca2bcc6,0xbc71bce2,0xbc15bcf5,0xbb49bcff,0xbb493cff,0xbc153cf5,0xbc713ce2,0xbca23cc6,0xbcc63ca2,0xbce23c71,0xbcf53c15,0xbcff3b49,
 0x3cff3b49,0x3cf53c15,0x3ce23c71,0x3cc63ca2,0x3ca23cc6,0x3c713ce2,0x3c153cf5,0x3b493cff,0x3b49bcff,0x3c15bcf5,0x3c71bce2,0x3ca2bcc6,0x3cc6bca2,0x3ce2bc71,0x3cf5bc15,0x3cffbb49,
 0x3c84bcdc,0x3cbebcac,0x3ce7bc5b,0x3cfdbb96,0xbc98bcce,0xbc2cbcf1,0xbac9bd00,0x3bf9bcf8,0xbcf83bf9,0xbd00bac9,0xbcf1bc2c,0xbccebc98,0xbb963cfd,0xbc5b3ce7,0xbcac3cbe,0xbcdc3c84,
 0xbcdcbc84,0xbcacbcbe,0xbc5bbce7,0xbb96bcfd,0xbcce3c98,0xbcf13c2c,0xbd003ac9,0xbcf8bbf9,0x3bf93cf8,0xbac93d00,0xbc2c3cf1,0xbc983cce,0x3cfd3b96,0x3ce73c5b,0x3cbe3cac,0x3c843cdc,
 0xbbc83cfb,0xbc8e3cd5,0xbcd53c8e,0xbcfb3bc8,0xbcfbbbc8,0xbcd5bc8e,0xbc8ebcd5,0xbbc8bcfb,0x3bc8bcfb,0x3c8ebcd5,0x3cd5bc8e,0x3cfbbbc8,0x3cfb3bc8,0x3cd53c8e,0x3c8e3cd5,0x3bc83cfb,
 0xbbc83cfb,0xbc8e3cd5,0xbcd53c8e,0xbcfb3bc8,0xbcfbbbc8,0xbcd5bc8e,0xbc8ebcd5,0xbbc8bcfb,0x3bc8bcfb,0x3c8ebcd5,0x3cd5bc8e,0x3cfbbbc8,0x3cfb3bc8,0x3cd53c8e,0x3c8e3cd5,0x3bc83cfb,
 0x3c98bcce,0x3ce7bc5b,0x3d003ac9,0x3cdc3c84,0xbcf8bbf9,0xbcbebcac,0xbc2cbcf1,0x3b96bcfd,0xbcfd3b96,0xbcf1bc2c,0xbcacbcbe,0xbbf9bcf8,0x3c843cdc,0x3ac93d00,0xbc5b3ce7,0xbcce3c98,
 0xbccebc98,0xbc5bbce7,0x3ac9bd00,0x3c84bcdc,0xbbf93cf8,0xbcac3cbe,0xbcf13c2c,0xbcfdbb96,0x3b963cfd,0xbc2c3cf1,0xbcbe3cac,0xbcf83bf9,0x3cdcbc84,0x3d00bac9,0x3ce73c5b,0x3c983cce,
 0xbcf5bc15,0xbca2bcc6,0xbb49bcff,0x3c71bce2,0x3ce2bc71,0x3cff3b49,0x3cc63ca2,0x3c153cf5,0x3c15bcf5,0x3cc6bca2,0x3cffbb49,0x3ce23c71,0x3c713ce2,0xbb493cff,0xbca23cc6,0xbcf53c15,
 0x3cf53c15,0x3ca23cc6,0x3b493cff,0xbc713ce2,0xbce23c71,0xbcffbb49,0xbcc6bca2,0xbc15bcf5,0xbc153cf5,0xbcc63ca2,0xbcff3b49,0xbce2bc71,0xbc71bce2,0x3b49bcff,0x3ca2bcc6,0x3cf5bc15,
 0xbcac3cbe,0xbcfd3b96,0xbcdcbc84,0xbc2cbcf1,0x3ce7bc5b,0x3cf83bf9,0x3c983cce,0xbac93d00,0xbd003ac9,0xbccebc98,0xbbf9bcf8,0x3c5bbce7,0x3cf13c2c,0x3c843cdc,0xbb963cfd,0xbcbe3cac,
 0xbcbebcac,0xbb96bcfd,0x3c84bcdc,0x3cf1bc2c,0x3c5b3ce7,0xbbf93cf8,0xbcce3c98,0xbd00bac9,0xbac9bd00,0x3c98bcce,0x3cf8bbf9,0x3ce73c5b,0xbc2c3cf1,0xbcdc3c84,0xbcfdbb96,0xbcacbcbe,
 0xbc443ced,0xbced3c44,0xbcedbc44,0xbc44bced,0x3c44bced,0x3cedbc44,0x3ced3c44,0x3c443ced,0xbc443ced,0xbced3c44,0xbcedbc44,0xbc44bced,0x3c44bced,0x3cedbc44,0x3ced3c44,0x3c443ced,
 0xbc443ced,0xbced3c44,0xbcedbc44,0xbc44bced,0x3c44bced,0x3cedbc44,0x3ced3c44,0x3c443ced,0xbc443ced,0xbced3c44,0xbcedbc44,0xbc44bced,0x3c44bced,0x3cedbc44,0x3ced3c44,0x3c443ced,
 0x3cbebcac,0x3cfd3b96,0x3c843cdc,0xbc2c3cf1,0xbc5b3ce7,0xbcf83bf9,0xbccebc98,0xbac9bd00,0x3d003ac9,0x3c983cce,0xbbf93cf8,0xbce73c5b,0xbcf13c2c,0xbcdcbc84,0xbb96bcfd,0x3cacbcbe,
 0x3cac3cbe,0xbb963cfd,0xbcdc3c84,0xbcf1bc2c,0xbce7bc5b,0xbbf9bcf8,0x3c98bcce,0x3d00bac9,0xbac93d00,0xbcce3c98,0xbcf8bbf9,0xbc5bbce7,0xbc2cbcf1,0x3c84bcdc,0x3cfdbb96,0x3cbe3cac,
 0xbce2bc71,0xbb49bcff,0x3cc6bca2,0x3cf53c15,0x3c153cf5,0xbca23cc6,0xbcffbb49,0xbc71bce2,0xbc713ce2,0xbcff3b49,0xbca2bcc6,0x3c15bcf5,0x3cf5bc15,0x3cc63ca2,0xbb493cff,0xbce23c71,
 0x3ce23c71,0x3b493cff,0xbcc63ca2,0xbcf5bc15,0xbc15bcf5,0x3ca2bcc6,0x3cff3b49,0x3c713ce2,0x3c71bce2,0x3cffbb49,0x3ca23cc6,0xbc153cf5,0xbcf53c15,0xbcc6bca2,0x3b49bcff,0x3ce2bc71,
 0xbcce3c98,0xbce7bc5b,0xbac9bd00,0x3cdcbc84,0xbbf9bcf8,0x3cbebcac,0x3cf13c2c,0x3b963cfd,0x3cfd3b96,0x3c2c3cf1,0xbcac3cbe,0xbcf8bbf9,0xbc843cdc,0xbd00bac9,0xbc5bbce7,0x3c98bcce,
 0x3c983cce,0xbc5b3ce7,0xbd003ac9,0xbc84bcdc,0xbcf83bf9,0xbcacbcbe,0x3c2cbcf1,0x3cfdbb96,0x3b96bcfd,0x3cf1bc2c,0x3cbe3cac,0xbbf93cf8,0x3cdc3c84,0xbac93d00,0xbce73c5b,0xbccebc98,
 0xbc8e3cd5,0xbcfbbbc8,0xbbc8bcfb,0x3cd5bc8e,0x3cd53c8e,0xbbc83cfb,0xbcfb3bc8,0xbc8ebcd5,0x3c8ebcd5,0x3cfb3bc8,0x3bc83cfb,0xbcd53c8e,0xbcd5bc8e,0x3bc8bcfb,0x3cfbbbc8,0x3c8e3cd5,
 0xbc8e3cd5,0xbcfbbbc8,0xbbc8bcfb,0x3cd5bc8e,0x3cd53c8e,0xbbc83cfb,0xbcfb3bc8,0xbc8ebcd5,0x3c8ebcd5,0x3cfb3bc8,0x3bc83cfb,0xbcd53c8e,0xbcd5bc8e,0x3bc8bcfb,0x3cfbbbc8,0x3c8e3cd5,
 0xbcdc3c84,0xbcbebcac,0x3c5bbce7,0x3cfd3b96,0xbccebc98,0x3c2cbcf1,0x3d003ac9,0x3bf93cf8,0x3cf83bf9,0x3ac93d00,0xbcf13c2c,0xbc98bcce,0x3b963cfd,0xbce73c5b,0xbcacbcbe,0x3c84bcdc,
 0x3c843cdc,0xbcac3cbe,0xbce7bc5b,0x3b96bcfd,0xbc983cce,0xbcf1bc2c,0x3ac9bd00,0x3cf8bbf9,0x3bf9bcf8,0x3d00bac9,0x3c2c3cf1,0xbcce3c98,0x3cfdbb96,0x3c5b3ce7,0xbcbe3cac,0xbcdcbc84,
 0xbcc6bca2,0x3c71bce2,0x3cf53c15,0xbb493cff,0xbcff3b49,0xbc15bcf5,0x3ce2bc71,0x3ca23cc6,0x3ca2bcc6,0x3ce23c71,0xbc153cf5,0xbcffbb49,0xbb49bcff,0x3cf5bc15,0x3c713ce2,0xbcc63ca2,
 0x3cc63ca2,0xbc713ce2,0xbcf5bc15,0x3b49bcff,0x3cffbb49,0x3c153cf5,0xbce23c71,0xbca2bcc6,0xbca23cc6,0xbce2bc71,0x3c15bcf5,0x3cff3b49,0x3b493cff,0xbcf53c15,0xbc71bce2,0x3cc6bca2,
 0x3ce7bc5b,0x3c843cdc,0xbcce3c98,0xbcacbcbe,0x3d00bac9,0x3b963cfd,0xbcf83bf9,0xbc2cbcf1,0x3cf13c2c,0xbbf93cf8,0xbcfdbb96,0x3ac9bd00,0x3cbe3cac,0xbc983cce,0xbcdcbc84,0x3c5bbce7,
 0x3c5b3ce7,0xbcdc3c84,0xbc98bcce,0x3cbebcac,0x3ac93d00,0xbcfd3b96,0xbbf9bcf8,0x3cf1bc2c,0xbc2c3cf1,0xbcf8bbf9,0x3b96bcfd,0x3d003ac9,0xbcac3cbe,0xbccebc98,0x3c84bcdc,0x3ce73c5b,
 0xbcb53cb5,0xbcb5bcb5,0x3cb5bcb5,0x3cb53cb5,0xbcb53cb5,0xbcb5bcb5,0x3cb5bcb5,0x3cb53cb5,0xbcb53cb5,0xbcb5bcb5,0x3cb5bcb5,0x3cb53cb5,0xbcb53cb5,0xbcb5bcb5,0x3cb5bcb5,0x3cb53cb5,
 0xbcb53cb5,0xbcb5bcb5,0x3cb5bcb5,0x3cb53cb5,0xbcb53cb5,0xbcb5bcb5,0x3cb5bcb5,0x3cb53cb5,0xbcb53cb5,0xbcb5bcb5,0x3cb5bcb5,0x3cb53cb5,0xbcb53cb5,0xbcb5bcb5,0x3cb5bcb5,0x3cb53cb5,
 0xbcf13c2c,0xbbf9bcf8,0x3cfdbb96,0x3ac93d00,0xbcbe3cac,0xbc98bcce,0x3cdcbc84,0x3c5b3ce7,0xbce7bc5b,0x3c84bcdc,0x3cce3c98,0xbcac3cbe,0xbd00bac9,0x3b96bcfd,0x3cf83bf9,0xbc2c3cf1,
 0xbc2cbcf1,0x3cf8bbf9,0x3b963cfd,0xbd003ac9,0xbcacbcbe,0x3ccebc98,0x3c843cdc,0xbce73c5b,0x3c5bbce7,0x3cdc3c84,0xbc983cce,0xbcbebcac,0x3ac9bd00,0x3cfd3b96,0xbbf93cf8,0xbcf1bc2c,
 0xbca2bcc6,0x3ce2bc71,0x3c153cf5,0xbcff3b49,0x3b49bcff,0x3cf53c15,0xbc713ce2,0xbcc6bca2,0xbcc63ca2,0xbc71bce2,0x3cf5bc15,0x3b493cff,0xbcffbb49,0x3c15bcf5,0x3ce23c71,0xbca23cc6,
 0x3ca23cc6,0xbce23c71,0xbc15bcf5,0x3cffbb49,0xbb493cff,0xbcf5bc15,0x3c71bce2,0x3cc63ca2,0x3cc6bca2,0x3c713ce2,0xbcf53c15,0xbb49bcff,0x3cff3b49,0xbc153cf5,0xbce2bc71,0x3ca2bcc6,
 0x3cf8bbf9,0xbac93d00,0xbcf1bc2c,0x3c98bcce,0x3b96bcfd,0x3ce73c5b,0xbcac3cbe,0xbc84bcdc,0xbcdcbc84,0x3cbebcac,0x3c5b3ce7,0xbcfd3b96,0xbcce3c98,0xbc2cbcf1,0x3d00bac9,0xbbf93cf8,
 0xbbf9bcf8,0x3d003ac9,0xbc2c3cf1,0xbccebc98,0xbcfdbb96,0x3c5bbce7,0x3cbe3cac,0xbcdc3c84,0xbc843cdc,0xbcacbcbe,0x3ce7bc5b,0x3b963cfd,0x3c983cce,0xbcf13c2c,0xbac9bd00,0x3cf83bf9,
 0xbcd53c8e,0xbbc8bcfb,0x3cfb3bc8,0xbc8e3cd5,0xbc8ebcd5,0x3cfbbbc8,0xbbc83cfb,0xbcd5bc8e,0x3cd5bc8e,0x3bc83cfb,0xbcfbbbc8,0x3c8ebcd5,0x3c8e3cd5,0xbcfb3bc8,0x3bc8bcfb,0x3cd53c8e,
 0xbcd53c8e,0xbbc8bcfb,0x3cfb3bc8,0xbc8e3cd5,0xbc8ebcd5,0x3cfbbbc8,0xbbc83cfb,0xbcd5bc8e,0x3cd5bc8e,0x3bc83cfb,0xbcfbbbc8,0x3c8ebcd5,0x3c8e3cd5,0xbcfb3bc8,0x3bc8bcfb,0x3cd53c8e,
 0x3cfdbb96,0xbc2c3cf1,0xbcacbcbe,0x3cf8bbf9,0xbc84bcdc,0x3d00bac9,0xbc5b3ce7,0xbc98bcce,0xbccebc98,0x3ce7bc5b,0xbac93d00,0xbcdcbc84,0xbbf93cf8,0xbcbebcac,0x3cf1bc2c,0xbb963cfd,
 0xbb96bcfd,0x3cf13c2c,0xbcbe3cac,0xbbf9bcf8,0xbcdc3c84,0xbac9bd00,0x3ce73c5b,0xbcce3c98,0xbc983cce,0xbc5bbce7,0x3d003ac9,0xbc843cdc,0x3cf83bf9,0xbcac3cbe,0xbc2cbcf1,0x3cfd3b96,
 0xbc71bce2,0x3cff3b49,0xbca23cc6,0xbc15bcf5,0x3cf53c15,0xbcc63ca2,0xbb49bcff,0x3ce23c71,0x3ce2bc71,0xbb493cff,0xbcc6bca2,0x3cf5bc15,0xbc153cf5,0xbca2bcc6,0x3cffbb49,0xbc713ce2,
 0x3c713ce2,0xbcffbb49,0x3ca2bcc6,0x3c153cf5,0xbcf5bc15,0x3cc6bca2,0x3b493cff,0xbce2bc71,0xbce23c71,0x3b49bcff,0x3cc63ca2,0xbcf53c15,0x3c15bcf5,0x3ca23cc6,0xbcff3b49,0x3c71bce2,
 0xbd003ac9,0x3c98bcce,0x3bf93cf8,0xbce7bc5b,0x3cf13c2c,0xbcdc3c84,0x3b96bcfd,0x3cac3cbe,0xbcbebcac,0x3cfdbb96,0xbc843cdc,0xbc2cbcf1,0x3c5b3ce7,0xbcf8bbf9,0x3ccebc98,0xbac93d00,
 0xbac9bd00,0x3cce3c98,0xbcf83bf9,0x3c5bbce7,0xbc2c3cf1,0xbc84bcdc,0x3cfd3b96,0xbcbe3cac,0x3cacbcbe,0x3b963cfd,0xbcdcbc84,0x3cf1bc2c,0xbce73c5b,0x3bf9bcf8,0x3c983cce,0xbd00bac9,
 0xbced3c44,0x3c44bced,0x3c443ced,0xbcedbc44,0x3cedbc44,0xbc443ced,0xbc44bced,0x3ced3c44,0xbced3c44,0x3c44bced,0x3c443ced,0xbcedbc44,0x3cedbc44,0xbc443ced,0xbc44bced,0x3ced3c44,
 0xbced3c44,0x3c44bced,0x3c443ced,0xbcedbc44,0x3cedbc44,0xbc443ced,0xbc44bced,0x3ced3c44,0xbced3c44,0x3c44bced,0x3c443ced,0xbcedbc44,0x3cedbc44,0xbc443ced,0xbc44bced,0x3ced3c44,
 0x3d003ac9,0xbcce3c98,0x3bf9bcf8,0x3c5b3ce7,0xbcf13c2c,0x3c84bcdc,0x3b963cfd,0xbcbebcac,0x3cac3cbe,0xbcfdbb96,0x3cdcbc84,0xbc2c3cf1,0xbce7bc5b,0x3cf8bbf9,0xbc983cce,0xbac9bd00,
 0xbac93d00,0xbc98bcce,0x3cf83bf9,0xbce73c5b,0xbc2cbcf1,0x3cdc3c84,0xbcfd3b96,0x3cacbcbe,0xbcbe3cac,0x3b96bcfd,0x3c843cdc,0xbcf1bc2c,0x3c5bbce7,0x3bf93cf8,0xbccebc98,0x3d00bac9,
 0xbc15bcf5,0x3cc63ca2,0xbcffbb49,0x3ce2bc71,0xbc713ce2,0xbb49bcff,0x3ca23cc6,0xbcf5bc15,0xbcf53c15,0x3ca2bcc6,0xbb493cff,0xbc71bce2,0x3ce23c71,0xbcff3b49,0x3cc6bca2,0xbc153cf5,
 0x3c153cf5,0xbcc6bca2,0x3cff3b49,0xbce23c71,0x3c71bce2,0x3b493cff,0xbca2bcc6,0x3cf53c15,0x3cf5bc15,0xbca23cc6,0x3b49bcff,0x3c713ce2,0xbce2bc71,0x3cffbb49,0xbcc63ca2,0x3c15bcf5,
 0xbcfdbb96,0x3cf1bc2c,0xbcac3cbe,0x3bf9bcf8,0x3c84bcdc,0xbac93d00,0xbc5bbce7,0x3cce3c98,0x3c983cce,0xbce7bc5b,0x3d00bac9,0xbcdc3c84,0xbcf83bf9,0x3cbebcac,0xbc2c3cf1,0xbb96bcfd,
 0xbb963cfd,0xbc2cbcf1,0x3cbe3cac,0xbcf8bbf9,0xbcdcbc84,0x3d003ac9,0xbce73c5b,0x3c98bcce,0x3ccebc98,0xbc5b3ce7,0xbac9bd00,0x3c843cdc,0x3bf93cf8,0xbcacbcbe,0x3cf13c2c,0xbcfd3b96,
 0xbcfb3bc8,0x3cd5bc8e,0xbc8e3cd5,0x3bc8bcfb,0x3bc83cfb,0xbc8ebcd5,0x3cd53c8e,0xbcfbbbc8,0x3cfbbbc8,0xbcd53c8e,0x3c8ebcd5,0xbbc83cfb,0xbbc8bcfb,0x3c8e3cd5,0xbcd5bc8e,0x3cfb3bc8,
 0xbcfb3bc8,0x3cd5bc8e,0xbc8e3cd5,0x3bc8bcfb,0x3bc83cfb,0xbc8ebcd5,0x3cd53c8e,0xbcfbbbc8,0x3cfbbbc8,0xbcd53c8e,0x3c8ebcd5,0xbbc83cfb,0xbbc8bcfb,0x3c8e3cd5,0xbcd5bc8e,0x3cfb3bc8,
 0xbcf8bbf9,0x3d00bac9,0xbcf13c2c,0x3ccebc98,0xbb96bcfd,0x3c5b3ce7,0xbcacbcbe,0x3cdc3c84,0x3c843cdc,0xbcbebcac,0x3ce73c5b,0xbcfdbb96,0xbc983cce,0x3c2cbcf1,0xbac93d00,0xbbf9bcf8,
 0xbbf93cf8,0xbac9bd00,0x3c2c3cf1,0xbc98bcce,0xbcfd3b96,0x3ce7bc5b,0xbcbe3cac,0x3c84bcdc,0x3cdcbc84,0xbcac3cbe,0x3c5bbce7,0xbb963cfd,0x3cce3c98,0xbcf1bc2c,0x3d003ac9,0xbcf83bf9,
 0xbb49bcff,0x3c153cf5,0xbc71bce2,0x3ca23cc6,0xbcc6bca2,0x3ce23c71,0xbcf5bc15,0x3cff3b49,0x3cffbb49,0xbcf53c15,0x3ce2bc71,0xbcc63ca2,0x3ca2bcc6,0xbc713ce2,0x3c15bcf5,0xbb493cff,
 0x3b493cff,0xbc15bcf5,0x3c713ce2,0xbca2bcc6,0x3cc63ca2,0xbce2bc71,0x3cf53c15,0xbcffbb49,0xbcff3b49,0x3cf5bc15,0xbce23c71,0x3cc6bca2,0xbca23cc6,0x3c71bce2,0xbc153cf5,0x3b49bcff,
 0x3cf13c2c,0xbcf8bbf9,0x3cfd3b96,0xbd00bac9,0x3cbe3cac,0xbccebc98,0x3cdc3c84,0xbce7bc5b,0x3c5b3ce7,0xbc84bcdc,0x3c983cce,0xbcacbcbe,0x3ac93d00,0xbb96bcfd,0x3bf93cf8,0xbc2cbcf1,
 0xbc2c3cf1,0x3bf9bcf8,0xbb963cfd,0x3ac9bd00,0xbcac3cbe,0x3c98bcce,0xbc843cdc,0x3c5bbce7,0xbce73c5b,0x3cdcbc84,0xbcce3c98,0x3cbebcac,0xbd003ac9,0x3cfdbb96,0xbcf83bf9,0x3cf1bc2c,
 0xbd000000,0x3d000000,0xbd000000,0x3d000000,0xbd000000,0x3d000000,0xbd000000,0x3d000000,0xbd000000,0x3d000000,0xbd000000,0x3d000000,0xbd000000,0x3d000000,0xbd000000,0x3d000000,
 0xbd000000,0x3d000000,0xbd000000,0x3d000000,0xbd000000,0x3d000000,0xbd000000,0x3d000000,0xbd000000,0x3d000000,0xbd000000,0x3d000000,0xbd000000,0x3d000000,0xbd000000,0x3d000000,
 0xbce7bc5b,0x3cdc3c84,0xbccebc98,0x3cbe3cac,0xbd00bac9,0x3cfd3b96,0xbcf8bbf9,0x3cf13c2c,0xbc2cbcf1,0x3bf93cf8,0xbb96bcfd,0x3ac93d00,0xbcacbcbe,0x3c983cce,0xbc84bcdc,0x3c5b3ce7,
 0x3c5bbce7,0xbc843cdc,0x3c98bcce,0xbcac3cbe,0x3ac9bd00,0xbb963cfd,0x3bf9bcf8,0xbc2c3cf1,0x3cf1bc2c,0xbcf83bf9,0x3cfdbb96,0xbd003ac9,0x3cbebcac,0xbcce3c98,0x3cdcbc84,0xbce73c5b,
 0x3b49bcff,0xbc153cf5,0x3c71bce2,0xbca23cc6,0x3cc6bca2,0xbce23c71,0x3cf5bc15,0xbcff3b49,0xbcffbb49,0x3cf53c15,0xbce2bc71,0x3cc63ca2,0xbca2bcc6,0x3c713ce2,0xbc15bcf5,0x3b493cff,
 0xbb493cff,0x3c15bcf5,0xbc713ce2,0x3ca2bcc6,0xbcc63ca2,0x3ce2bc71,0xbcf53c15,0x3cffbb49,0x3cff3b49,0xbcf5bc15,0x3ce23c71,0xbcc6bca2,0x3ca23cc6,0xbc71bce2,0x3c153cf5,0xbb49bcff,
 0x3cdc3c84,0xbcacbcbe,0x3c5b3ce7,0xbb96bcfd,0x3ccebc98,0xbcf13c2c,0x3d00bac9,0xbcf8bbf9,0xbbf9bcf8,0xbac93d00,0x3c2cbcf1,0xbc983cce,0xbcfdbb96,0x3ce73c5b,0xbcbebcac,0x3c843cdc,
 0x3c84bcdc,0xbcbe3cac,0x3ce7bc5b,0xbcfd3b96,0xbc98bcce,0x3c2c3cf1,0xbac9bd00,0xbbf93cf8,0xbcf83bf9,0x3d003ac9,0xbcf1bc2c,0x3cce3c98,0xbb963cfd,0x3c5bbce7,0xbcac3cbe,0x3cdcbc84,
 0xbcfbbbc8,0x3cd53c8e,0xbc8ebcd5,0x3bc83cfb,0x3bc8bcfb,0xbc8e3cd5,0x3cd5bc8e,0xbcfb3bc8,0x3cfb3bc8,0xbcd5bc8e,0x3c8e3cd5,0xbbc8bcfb,0xbbc83cfb,0x3c8ebcd5,0xbcd53c8e,0x3cfbbbc8,
 0xbcfbbbc8,0x3cd53c8e,0xbc8ebcd5,0x3bc83cfb,0x3bc8bcfb,0xbc8e3cd5,0x3cd5bc8e,0xbcfb3bc8,0x3cfb3bc8,0xbcd5bc8e,0x3c8e3cd5,0xbbc8bcfb,0xbbc83cfb,0x3c8ebcd5,0xbcd53c8e,0x3cfbbbc8,
 0x3cce3c98,0xbc5bbce7,0xbac93d00,0x3c84bcdc,0x3bf9bcf8,0xbcac3cbe,0x3cf1bc2c,0xbcfdbb96,0xbb96bcfd,0xbc2c3cf1,0x3cbebcac,0xbcf83bf9,0xbcdc3c84,0x3d00bac9,0xbce7bc5b,0x3c983cce,
 0x3c98bcce,0xbce73c5b,0x3d003ac9,0xbcdcbc84,0xbcf8bbf9,0x3cbe3cac,0xbc2cbcf1,0xbb963cfd,0xbcfd3b96,0x3cf13c2c,0xbcacbcbe,0x3bf93cf8,0x3c843cdc,0xbac9bd00,0xbc5b3ce7,0x3ccebc98,
 0x3c15bcf5,0xbcc63ca2,0x3cffbb49,0xbce2bc71,0x3c713ce2,0x3b49bcff,0xbca23cc6,0x3cf5bc15,0x3cf53c15,0xbca2bcc6,0x3b493cff,0x3c71bce2,0xbce23c71,0x3cff3b49,0xbcc6bca2,0x3c153cf5,
 0xbc153cf5,0x3cc6bca2,0xbcff3b49,0x3ce23c71,0xbc71bce2,0xbb493cff,0x3ca2bcc6,0xbcf53c15,0xbcf5bc15,0x3ca23cc6,0xbb49bcff,0xbc713ce2,0x3ce2bc71,0xbcffbb49,0x3cc63ca2,0xbc15bcf5,
 0xbcbebcac,0x3b963cfd,0x3c84bcdc,0xbcf13c2c,0x3c5b3ce7,0x3bf9bcf8,0xbcce3c98,0x3d003ac9,0xbac9bd00,0xbc983cce,0x3cf8bbf9,0xbce7bc5b,0xbc2c3cf1,0x3cdcbc84,0xbcfdbb96,0x3cac3cbe,
 0x3cacbcbe,0xbcfd3b96,0x3cdc3c84,0xbc2cbcf1,0xbce73c5b,0x3cf83bf9,0xbc98bcce,0xbac93d00,0x3d00bac9,0xbccebc98,0x3bf93cf8,0x3c5bbce7,0xbcf1bc2c,0x3c843cdc,0x3b96bcfd,0xbcbe3cac,
 0xbcedbc44,0x3c443ced,0x3c44bced,0xbced3c44,0x3ced3c44,0xbc44bced,0xbc443ced,0x3cedbc44,0xbcedbc44,0x3c443ced,0x3c44bced,0xbced3c44,0x3ced3c44,0xbc44bced,0xbc443ced,0x3cedbc44,
 0xbcedbc44,0x3c443ced,0x3c44bced,0xbced3c44,0x3ced3c44,0xbc44bced,0xbc443ced,0x3cedbc44,0xbcedbc44,0x3c443ced,0x3c44bced,0xbced3c44,0x3ced3c44,0xbc44bced,0xbc443ced,0x3cedbc44,
 0x3cac3cbe,0x3b96bcfd,0xbcdc3c84,0x3cf13c2c,0xbce7bc5b,0x3bf93cf8,0x3c98bcce,0xbd003ac9,0xbac93d00,0x3ccebc98,0xbcf8bbf9,0x3c5b3ce7,0xbc2cbcf1,0xbc843cdc,0x3cfdbb96,0xbcbebcac,
 0xbcbe3cac,0x3cfd3b96,0xbc84bcdc,0xbc2c3cf1,0x3c5bbce7,0xbcf83bf9,0x3cce3c98,0xbac9bd00,0xbd00bac9,0x3c983cce,0x3bf9bcf8,0xbce73c5b,0x3cf1bc2c,0xbcdcbc84,0x3b963cfd,0x3cacbcbe,
 0x3c71bce2,0xbcff3b49,0x3ca23cc6,0x3c15bcf5,0xbcf53c15,0x3cc63ca2,0x3b49bcff,0xbce23c71,0xbce2bc71,0x3b493cff,0x3cc6bca2,0xbcf5bc15,0x3c153cf5,0x3ca2bcc6,0xbcffbb49,0x3c713ce2,
 0xbc713ce2,0x3cffbb49,0xbca2bcc6,0xbc153cf5,0x3cf5bc15,0xbcc6bca2,0xbb493cff,0x3ce2bc71,0x3ce23c71,0xbb49bcff,0xbcc63ca2,0x3cf53c15,0xbc15bcf5,0xbca23cc6,0x3cff3b49,0xbc71bce2,
 0xbc98bcce,0xbc5b3ce7,0x3d00bac9,0xbc84bcdc,0x3cf8bbf9,0xbcacbcbe,0xbc2c3cf1,0x3cfdbb96,0xbb963cfd,0x3cf1bc2c,0xbcbebcac,0xbbf93cf8,0xbcdcbc84,0xbac93d00,0x3ce7bc5b,0xbccebc98,
 0xbcce3c98,0x3ce73c5b,0xbac9bd00,0xbcdc3c84,0xbbf9bcf8,0xbcbe3cac,0x3cf13c2c,0xbb96bcfd,0x3cfd3b96,0xbc2cbcf1,0xbcac3cbe,0x3cf83bf9,0xbc843cdc,0x3d003ac9,0xbc5bbce7,0xbc983cce,
 0xbcd5bc8e,0xbbc83cfb,0x3cfbbbc8,0xbc8ebcd5,0xbc8e3cd5,0x3cfb3bc8,0xbbc8bcfb,0xbcd53c8e,0x3cd53c8e,0x3bc8bcfb,0xbcfb3bc8,0x3c8e3cd5,0x3c8ebcd5,0xbcfbbbc8,0x3bc83cfb,0x3cd5bc8e,
 0xbcd5bc8e,0xbbc83cfb,0x3cfbbbc8,0xbc8ebcd5,0xbc8e3cd5,0x3cfb3bc8,0xbbc8bcfb,0xbcd53c8e,0x3cd53c8e,0x3bc8bcfb,0xbcfb3bc8,0x3c8e3cd5,0x3c8ebcd5,0xbcfbbbc8,0x3bc83cfb,0x3cd5bc8e,
 0xbc84bcdc,0xbcac3cbe,0x3ce73c5b,0x3b96bcfd,0x3c98bcce,0xbcf1bc2c,0xbac93d00,0x3cf8bbf9,0xbbf93cf8,0x3d00bac9,0xbc2cbcf1,0xbcce3c98,0xbcfd3b96,0x3c5b3ce7,0x3cbebcac,0xbcdcbc84,
 0xbcdc3c84,0x3cbe3cac,0x3c5bbce7,0xbcfdbb96,0xbccebc98,0xbc2c3cf1,0x3d003ac9,0xbbf9bcf8,0x3cf83bf9,0xbac9bd00,0xbcf13c2c,0x3c983cce,0x3b963cfd,0x3ce7bc5b,0xbcacbcbe,0xbc843cdc,
 0x3ca2bcc6,0xbce2bc71,0xbc153cf5,0x3cff3b49,0xbb49bcff,0xbcf53c15,0x3c713ce2,0x3cc6bca2,0x3cc63ca2,0x3c71bce2,0xbcf5bc15,0xbb493cff,0x3cffbb49,0xbc15bcf5,0xbce23c71,0x3ca23cc6,
 0xbca23cc6,0x3ce23c71,0x3c15bcf5,0xbcffbb49,0x3b493cff,0x3cf5bc15,0xbc71bce2,0xbcc63ca2,0xbcc6bca2,0xbc713ce2,0x3cf53c15,0x3b49bcff,0xbcff3b49,0x3c153cf5,0x3ce2bc71,0xbca2bcc6,
 0x3c5b3ce7,0x3cdcbc84,0xbc98bcce,0xbcbe3cac,0x3ac93d00,0x3cfdbb96,0xbbf9bcf8,0xbcf13c2c,0xbc2c3cf1,0x3cf83bf9,0x3b96bcfd,0xbd00bac9,0xbcac3cbe,0x3cce3c98,0x3c84bcdc,0xbce7bc5b,
 0xbce73c5b,0x3c843cdc,0x3ccebc98,0xbcacbcbe,0xbd003ac9,0x3b963cfd,0x3cf8bbf9,0xbc2cbcf1,0xbcf1bc2c,0xbbf93cf8,0x3cfd3b96,0x3ac9bd00,0xbcbebcac,0xbc983cce,0x3cdc3c84,0x3c5bbce7,
 0xbcb5bcb5,0xbcb53cb5,0x3cb53cb5,0x3cb5bcb5,0xbcb5bcb5,0xbcb53cb5,0x3cb53cb5,0x3cb5bcb5,0xbcb5bcb5,0xbcb53cb5,0x3cb53cb5,0x3cb5bcb5,0xbcb5bcb5,0xbcb53cb5,0x3cb53cb5,0x3cb5bcb5,
 0xbcb5bcb5,0xbcb53cb5,0x3cb53cb5,0x3cb5bcb5,0xbcb5bcb5,0xbcb53cb5,0x3cb53cb5,0x3cb5bcb5,0xbcb5bcb5,0xbcb53cb5,0x3cb53cb5,0x3cb5bcb5,0xbcb5bcb5,0xbcb53cb5,0x3cb53cb5,0x3cb5bcb5,
 0xbc2cbcf1,0xbcf83bf9,0x3b963cfd,0x3d00bac9,0xbcacbcbe,0xbcce3c98,0x3c843cdc,0x3ce7bc5b,0x3c5bbce7,0xbcdcbc84,0xbc983cce,0x3cbe3cac,0x3ac9bd00,0xbcfdbb96,0xbbf93cf8,0x3cf13c2c,
 0x3cf1bc2c,0xbbf9bcf8,0xbcfd3b96,0x3ac93d00,0x3cbebcac,0xbc98bcce,0xbcdc3c84,0x3c5b3ce7,0x3ce73c5b,0x3c84bcdc,0xbccebc98,0xbcac3cbe,0x3d003ac9,0x3b96bcfd,0xbcf8bbf9,0xbc2c3cf1,
 0x00000000,0x00000000,0x00000000,0x00000000,0x00000000,0x00000000,0x00000000,0x00000000,0x00000000,0x00000000,0x00000000,0x00000000,0x00000000,0x00000000,0x00000000,0x00000000,
 0x00000000,0x00000000,0x00000000,0x00000000,0x00000000,0x00000000,0x00000000,0x00000000,0x00000000,0x00000000,0x00000000,0x00000000,0x00000000,0x00000000,0x00000000,0x00000000,
 0x00000000,0x00000000,0x00000000,0x00000000,0x00000000,0x00000000,0x00000000,0x00000000,0x00000000,0x00000000,0x00000000,0x00000000,0x00000000,0x00000000,0x00000000,0x00000000,
 0x00000000,0x00000000,0x00000000,0x00000000,0x00000000,0x00000000,0x00000000,0x00000000,0x00000000,0x00000000,0x00000000,0x00000000,0x00000000,0x00000000,0x00000000,0x00000000,
 0x00000000,0x00000000,0x00000000,0x00000000,0x00000000,0x00000000,0x00000000,0x00000000,0x00000000,0x00000000,0x00000000,0x00000000,0x00000000,0x00000000,0x00000000,0x00000000,
 0x00000000,0x00000000,0x00000000,0x00000000,0x00000000,0x00000000,0x00000000,0x00000000,0x00000000,0x00000000,0x00000000,0x00000000,0x00000000,0x00000000,0x00000000,0x00000000,
 0x00000000,0x00000000,0x00000000,0x00000000,0x00000000,0x00000000,0x00000000,0x00000000,0x00000000,0x00000000,0x00000000,0x00000000,0x00000000,0x00000000,0x00000000,0x00000000,
 0x00000000,0x00000000,0x00000000,0x00000000,0x00000000,0x00000000,0x00000000,0x00000000,0x00000000,0x00000000,0x00000000,0x00000000,0x00000000,0x00000000,0x00000000,0x00000000,
 0x00000000,0x00000000,0x00000000,0x00000000,0x00000000,0x00000000,0x00000000,0x00000000,0x00000000,0x00000000,0x00000000,0x00000000,0x00000000,0x00000000,0x00000000,0x00000000,
 0x00000000,0x00000000,0x00000000,0x00000000,0x00000000,0x00000000,0x00000000,0x00000000,0x00000000,0x00000000,0x00000000,0x00000000,0x00000000,0x00000000,0x00000000,0x00000000,
 0x00000000,0x00000000,0x00000000,0x00000000,0x00000000,0x00000000,0x00000000,0x00000000,0x00000000,0x00000000,0x00000000,0x00000000,0x00000000,0x00000000,0x00000000,0x00000000,
 0x00000000,0x00000000,0x00000000,0x00000000,0x00000000,0x00000000,0x00000000,0x00000000,0x00000000,0x00000000,0x00000000,0x00000000,0x00000000,0x00000000,0x00000000,0x00000000,
};

template<int SA>
__device__ __forceinline__ void wgmma_main(float (&d)[80], uint64_t da, uint64_t db, int sd) {
  asm volatile("{\n.reg .pred p;\nsetp.ne.b32 p, %82, 0;\n"
    "wgmma.mma_async.sync.aligned.m64n160k16.f32.bf16.bf16 "
    "{%0, %1, %2, %3, %4, %5, %6, %7, %8, %9, %10, %11, %12, %13, %14, %15, %16, %17, %18, %19, %20, %21, %22, %23, %24, %25, %26, %27, %28, %29, %30, %31, %32, %33, %34, %35, %36, %37, %38, %39, %40, %41, %42, %43, %44, %45, %46, %47, %48, %49, %50, %51, %52, %53, %54, %55, %56, %57, %58, %59, %60, %61, %62, %63, %64, %65, %66, %67, %68, %69, %70, %71, %72, %73, %74, %75, %76, %77, %78, %79}, %80, %81, p, %83, 1, 1, 0;\n}\n"
    : "+f"(d[0]), "+f"(d[1]), "+f"(d[2]), "+f"(d[3]), "+f"(d[4]), "+f"(d[5]), "+f"(d[6]), "+f"(d[7]), "+f"(d[8]), "+f"(d[9]), "+f"(d[10]), "+f"(d[11]), "+f"(d[12]), "+f"(d[13]), "+f"(d[14]), "+f"(d[15]), "+f"(d[16]), "+f"(d[17]), "+f"(d[18]), "+f"(d[19]), "+f"(d[20]), "+f"(d[21]), "+f"(d[22]), "+f"(d[23]), "+f"(d[24]), "+f"(d[25]), "+f"(d[26]), "+f"(d[27]), "+f"(d[28]), "+f"(d[29]), "+f"(d[30]), "+f"(d[31]), "+f"(d[32]), "+f"(d[33]), "+f"(d[34]), "+f"(d[35]), "+f"(d[36]), "+f"(d[37]), "+f"(d[38]), "+f"(d[39]), "+f"(d[40]), "+f"(d[41]), "+f"(d[42]), "+f"(d[43]), "+f"(d[44]), "+f"(d[45]), "+f"(d[46]), "+f"(d[47]), "+f"(d[48]), "+f"(d[49]), "+f"(d[50]), "+f"(d[51]), "+f"(d[52]), "+f"(d[53]), "+f"(d[54]), "+f"(d[55]), "+f"(d[56]), "+f"(d[57]), "+f"(d[58]), "+f"(d[59]), "+f"(d[60]), "+f"(d[61]), "+f"(d[62]), "+f"(d[63]), "+f"(d[64]), "+f"(d[65]), "+f"(d[66]), "+f"(d[67]), "+f"(d[68]), "+f"(d[69]), "+f"(d[70]), "+f"(d[71]), "+f"(d[72]), "+f"(d[73]), "+f"(d[74]), "+f"(d[75]), "+f"(d[76]), "+f"(d[77]), "+f"(d[78]), "+f"(d[79])
    : "l"(da), "l"(db), "r"(sd), "n"(SA));
}
template<int SA>
__device__ __forceinline__ void wgmma_fwd(float (&d)[32], uint64_t da, uint64_t db, int sd) {
  asm volatile("{\n.reg .pred p;\nsetp.ne.b32 p, %34, 0;\n"
    "wgmma.mma_async.sync.aligned.m64n64k16.f32.bf16.bf16 "
    "{%0, %1, %2, %3, %4, %5, %6, %7, %8, %9, %10, %11, %12, %13, %14, %15, %16, %17, %18, %19, %20, %21, %22, %23, %24, %25, %26, %27, %28, %29, %30, %31}, %32, %33, p, %35, 1, 0, 1;\n}\n"
    : "+f"(d[0]), "+f"(d[1]), "+f"(d[2]), "+f"(d[3]), "+f"(d[4]), "+f"(d[5]), "+f"(d[6]), "+f"(d[7]), "+f"(d[8]), "+f"(d[9]), "+f"(d[10]), "+f"(d[11]), "+f"(d[12]), "+f"(d[13]), "+f"(d[14]), "+f"(d[15]), "+f"(d[16]), "+f"(d[17]), "+f"(d[18]), "+f"(d[19]), "+f"(d[20]), "+f"(d[21]), "+f"(d[22]), "+f"(d[23]), "+f"(d[24]), "+f"(d[25]), "+f"(d[26]), "+f"(d[27]), "+f"(d[28]), "+f"(d[29]), "+f"(d[30]), "+f"(d[31])
    : "l"(da), "l"(db), "r"(sd), "n"(SA));
}
template<int SA>
__device__ __forceinline__ void wgmma_inv(float (&d)[28], uint64_t da, uint64_t db, int sd) {
  asm volatile("{\n.reg .pred p;\nsetp.ne.b32 p, %30, 0;\n"
    "wgmma.mma_async.sync.aligned.m64n56k16.f32.bf16.bf16 "
    "{%0, %1, %2, %3, %4, %5, %6, %7, %8, %9, %10, %11, %12, %13, %14, %15, %16, %17, %18, %19, %20, %21, %22, %23, %24, %25, %26, %27}, %28, %29, p, %31, 1, 1, 0;\n}\n"
    : "+f"(d[0]), "+f"(d[1]), "+f"(d[2]), "+f"(d[3]), "+f"(d[4]), "+f"(d[5]), "+f"(d[6]), "+f"(d[7]), "+f"(d[8]), "+f"(d[9]), "+f"(d[10]), "+f"(d[11]), "+f"(d[12]), "+f"(d[13]), "+f"(d[14]), "+f"(d[15]), "+f"(d[16]), "+f"(d[17]), "+f"(d[18]), "+f"(d[19]), "+f"(d[20]), "+f"(d[21]), "+f"(d[22]), "+f"(d[23]), "+f"(d[24]), "+f"(d[25]), "+f"(d[26]), "+f"(d[27])
    : "l"(da), "l"(db), "r"(sd), "n"(SA));
}

__device__ __forceinline__ uint32_t s2u(const void* p) { return (uint32_t)__cvta_generic_to_shared(p); }
__device__ __forceinline__ void mbar_init(uint32_t a, int c) { asm volatile("mbarrier.init.shared::cta.b64 [%0], %1;" ::"r"(a), "r"(c)); }
__device__ __forceinline__ void mbar_expect(uint32_t a, int b) { asm volatile("mbarrier.arrive.expect_tx.shared::cta.b64 _, [%0], %1;" ::"r"(a), "r"(b) : "memory"); }
__device__ __forceinline__ void mbar_arrive(uint32_t a) { asm volatile("mbarrier.arrive.shared::cta.b64 _, [%0];" ::"r"(a) : "memory"); }
__device__ __forceinline__ void mbar_arrive_cluster(uint32_t a, uint32_t cta, uint32_t cnt) {
  asm volatile("{\n.reg .b32 r;\nmapa.shared::cluster.u32 r, %0, %1;\nmbarrier.arrive.shared::cluster.b64 _, [r], %2;\n}" ::"r"(a), "r"(cta), "r"(cnt) : "memory");
}
__device__ __forceinline__ void mbar_wait(uint32_t a, int ph) {
  asm volatile("{\n.reg .pred p;\n.reg .u32 c;\nmov.u32 c, 0;\nWAIT:\n"
               "mbarrier.try_wait.parity.shared::cta.b64 p, [%0], %1;\n@p bra DONE;\n"
               "add.u32 c, c, 1;\nsetp.lt.u32 p, c, 0x400000;\n@p bra WAIT;\ntrap;\nDONE:\n}" ::"r"(a), "r"(ph) : "memory");
}
__device__ __forceinline__ void flag_wait(const unsigned* p, unsigned target) {
  asm volatile("{\n.reg .pred p;\n.reg .u32 c, v;\nmov.u32 c, 0;\nWAIT:\n"
               "ld.acquire.gpu.global.u32 v, [%0];\nsetp.ge.u32 p, v, %1;\n@p bra DONE;\n"
               "add.u32 c, c, 1;\nsetp.lt.u32 p, c, 0x400000;\n@p bra WAIT;\ntrap;\nDONE:\n}" ::"l"(p), "r"(target) : "memory");
}
__device__ __forceinline__ bool elect_one() {
  uint32_t p;
  asm volatile("{\n.reg .pred P;\nelect.sync _|P, 0xffffffff;\nselp.u32 %0, 1, 0, P;\n}" : "=r"(p));
  return p != 0;
}
__device__ __forceinline__ void bulk_ld(uint32_t dst, const void* src, int bytes, uint32_t bar) {
  asm volatile("cp.async.bulk.shared::cluster.global.mbarrier::complete_tx::bytes [%0], [%1], %2, [%3];" ::"r"(dst), "l"(src), "r"(bytes), "r"(bar) : "memory");
}
__device__ __forceinline__ void bulk_ld_mc_h(uint32_t dst, const void* src, int bytes, uint32_t bar, uint16_t mask, uint64_t pol) {
  asm volatile("cp.async.bulk.shared::cluster.global.mbarrier::complete_tx::bytes.multicast::cluster.L2::cache_hint [%0], [%1], %2, [%3], %4, %5;" ::"r"(dst), "l"(src), "r"(bytes), "r"(bar), "h"(mask), "l"(pol) : "memory");
}
__device__ __forceinline__ uint64_t policy_evict_normal() {
  uint64_t p;
  asm("createpolicy.fractional.L2::evict_normal.b64 %0, 1.0;" : "=l"(p));
  return p;
}
__device__ __forceinline__ void tma_ld2(uint32_t dst, const CUtensorMap* tm, int c0, int c1, uint32_t bar) {
  asm volatile("cp.async.bulk.tensor.2d.shared::cluster.global.mbarrier::complete_tx::bytes [%0], [%1, {%3,%4}], [%2];" ::"r"(dst), "l"(tm), "r"(bar), "r"(c0), "r"(c1) : "memory");
}
__device__ __forceinline__ void tma_ld3(uint32_t dst, const CUtensorMap* tm, int c0, int c1, int c2, uint32_t bar) {
  asm volatile("cp.async.bulk.tensor.3d.shared::cluster.global.mbarrier::complete_tx::bytes [%0], [%1, {%3,%4,%5}], [%2];" ::"r"(dst), "l"(tm), "r"(bar), "r"(c0), "r"(c1), "r"(c2) : "memory");
}
__device__ __forceinline__ void tma_ld3h(uint32_t dst, const CUtensorMap* tm, int c0, int c1, int c2, uint32_t bar, uint64_t pol) {
  asm volatile("cp.async.bulk.tensor.3d.shared::cluster.global.mbarrier::complete_tx::bytes.L2::cache_hint [%0], [%1, {%3,%4,%5}], [%2], %6;" ::"r"(dst), "l"(tm), "r"(bar), "r"(c0), "r"(c1), "r"(c2), "l"(pol) : "memory");
}
__device__ __forceinline__ uint64_t policy_evict_first() {
  uint64_t p;
  asm("createpolicy.fractional.L2::evict_first.b64 %0, 1.0;" : "=l"(p));
  return p;
}
__device__ __forceinline__ void tma_st3(const CUtensorMap* tm, uint32_t src, int c0, int c1, int c2) {
  asm volatile("cp.async.bulk.tensor.3d.global.shared::cta.bulk_group [%0, {%2,%3,%4}], [%1];" ::"l"(tm), "r"(src), "r"(c0), "r"(c1), "r"(c2) : "memory");
}
__device__ __forceinline__ void tma_st4(const CUtensorMap* tm, uint32_t src, int c0, int c1, int c2, int c3) {
  asm volatile("cp.async.bulk.tensor.4d.global.shared::cta.bulk_group [%0, {%2,%3,%4,%5}], [%1];" ::"l"(tm), "r"(src), "r"(c0), "r"(c1), "r"(c2), "r"(c3) : "memory");
}
__device__ __forceinline__ void tma_st5(const CUtensorMap* tm, uint32_t src, int c0) {
  asm volatile("cp.async.bulk.tensor.5d.global.shared::cta.bulk_group [%0, {%2,%3,%3,%3,%3}], [%1];" ::"l"(tm), "r"(src), "r"(c0), "r"(0) : "memory");
}
__device__ __forceinline__ void bulk_commit() { asm volatile("cp.async.bulk.commit_group;" ::: "memory"); }
template <int N> __device__ __forceinline__ void bulk_wait_read() { asm volatile("cp.async.bulk.wait_group.read %0;" ::"n"(N) : "memory"); }
template <int N> __device__ __forceinline__ void bulk_wait() { asm volatile("cp.async.bulk.wait_group %0;" ::"n"(N) : "memory"); }
__device__ __forceinline__ void fence_async_smem() { asm volatile("fence.proxy.async.shared::cta;" ::: "memory"); }
__device__ __forceinline__ void wg_fence() { asm volatile("wgmma.fence.sync.aligned;" ::: "memory"); }
__device__ __forceinline__ void wg_commit() { asm volatile("wgmma.commit_group.sync.aligned;" ::: "memory"); }
template <int N> __device__ __forceinline__ void wg_wait() { asm volatile("wgmma.wait_group.sync.aligned %0;" ::"n"(N) : "memory"); }
template <int R> __device__ __forceinline__ void fence_regs(float (&d)[R]) {
#pragma unroll
  for (int i = 0; i < R; i++) asm volatile("" : "+f"(d[i])::"memory");
}
__device__ __forceinline__ uint64_t mk_desc(uint32_t addr) {
  return (uint64_t)((addr & 0x3FFFF) >> 4) | (1ull << 16) | (64ull << 32) | (1ull << 62);
}
__device__ __forceinline__ uint32_t pack2(float lo, float hi) {
  uint32_t r;
  asm("cvt.rn.bf16x2.f32 %0, %1, %2;" : "=r"(r) : "f"(hi), "f"(lo));
  return r;
}
__device__ __forceinline__ void stsm4(uint32_t ad, uint32_t a, uint32_t b, uint32_t c, uint32_t d) {
  asm volatile("stmatrix.sync.aligned.m8n8.x4.shared.b16 [%0], {%1,%2,%3,%4};" ::"r"(ad), "r"(a), "r"(b), "r"(c), "r"(d) : "memory");
}
__device__ __forceinline__ void stsm4t(uint32_t ad, uint32_t a, uint32_t b, uint32_t c, uint32_t d) {
  asm volatile("stmatrix.sync.aligned.m8n8.x4.trans.shared.b16 [%0], {%1,%2,%3,%4};" ::"r"(ad), "r"(a), "r"(b), "r"(c), "r"(d) : "memory");
}

__device__ __forceinline__ void stsm2t(uint32_t ad, uint32_t a, uint32_t b) {
  asm volatile("stmatrix.sync.aligned.m8n8.x2.trans.shared.b16 [%0], {%1,%2};" ::"r"(ad), "r"(a), "r"(b) : "memory");
}
__device__ __forceinline__ void red_add(unsigned* p) { asm volatile("red.relaxed.gpu.global.add.u32 [%0], 1;" ::"l"(p) : "memory"); }
__device__ __forceinline__ void fence_release() { asm volatile("fence.release.gpu;" ::: "memory"); }
__device__ __forceinline__ void fence_async_global() { asm volatile("fence.proxy.async.global;" ::: "memory"); }
__device__ __forceinline__ void tma_pf2(const CUtensorMap* tm, int c0, int c1) {
  asm volatile("cp.async.bulk.prefetch.tensor.2d.L2.global [%0, {%1,%2}];" ::"l"(tm), "r"(c0), "r"(c1) : "memory");
}
__device__ __forceinline__ void tma_pf3(const CUtensorMap* tm, int c0, int c1, int c2) {
  asm volatile("cp.async.bulk.prefetch.tensor.3d.L2.global [%0, {%1,%2,%3}];" ::"l"(tm), "r"(c0), "r"(c1), "r"(c2) : "memory");
}

__device__ __forceinline__ int lane_id() {
  int l;
  asm volatile("mov.u32 %0, %%laneid;" : "=r"(l));
  return l;
}
__device__ __forceinline__ void poll64x4(const unsigned long long* p, unsigned long long (&v)[4]) {
  asm volatile("{\n.reg .pred p;\n.reg .u32 c;\n.reg .b64 t, u;\nmov.u32 c, 0;\nWAIT:\n"
               "ld.relaxed.gpu.global.u64 %0, [%4];\nld.relaxed.gpu.global.u64 %1, [%4+512];\n"
               "ld.relaxed.gpu.global.u64 %2, [%4+1024];\nld.relaxed.gpu.global.u64 %3, [%4+1536];\n"
               "or.b64 t, %0, %1;\nor.b64 u, %2, %3;\nor.b64 t, t, u;\nsetp.ge.s64 p, t, 0;\n@p bra DONE;\n"
               "add.u32 c, c, 1;\nsetp.lt.u32 p, c, 0x400000;\n@p bra WAIT;\ntrap;\nDONE:\n}"
               : "=l"(v[0]), "=l"(v[1]), "=l"(v[2]), "=l"(v[3]) : "l"(p) : "memory");
}

constexpr int G_STAGE = WBLK + XBLK;
constexpr int OFF_XR = 4 * G_STAGE;
constexpr int OFF_WS = OFF_XR + 6 * 8192;
constexpr int OFF_F = OFF_WS + 2 * 8192;
constexpr int OFF_WRAW = OFF_F + 8192;
constexpr int OFF_BAR = OFF_WRAW + 8192;
constexpr int OFF_GB = OFF_BAR + 1024;
constexpr int SMEM_BYTES = OFF_GB + 512;
constexpr int OFF_H0B = 10 * 8192;
constexpr int OFF_E = OFF_WRAW + 3072;
constexpr int B_RAWX = 0, B_F = 48, B_ROLE = 56, B_H0 = 80, B_H1 = 96, B_YFREE = 120, B_H0C = 136,
              B_EMPTY = 160, B_STGX = 192, B_STGW = 240, B_Y = 256, B_OUT = 272,
              B_FULL = 360, B_RAWW = 392, B_DONE = 424, S_ROLE = 480, S_PROBE = 496;

struct Maps { CUtensorMap x, we, wo, xst[2], wst, yst[2], yld[2], out, xe[2], w30; };

__device__ __forceinline__ int chunk_of(int n) { return n < 16 ? n : 31 - n; }
__device__ __forceinline__ bool has_x2(int id, int n, int g) { return (((id >> 5) ^ n) & 1) == 0 && ((n >> 1) & 1) == g; }
__device__ __forceinline__ uint32_t x_base(int s, int idx, uint32_t pgmask, int& par) {
  const int page = idx >> 3, o = idx & 7;
  par = (s ^ (pgmask >> page) ^ __popc(o)) & 1;
  return (page << 21) | ((o & 3) << 16) | ((o >> 2) << 19);
}
__device__ __forceinline__ uint32_t read_info(uint32_t bar, int i) {
  uint32_t v;
  mbar_wait(bar + B_ROLE + 8 * i, 0);
  asm volatile("ld.shared.b32 %0, [%1];" : "=r"(v) : "r"(bar + S_ROLE + 4 * i) : "memory");
  return v;
}
__device__ __forceinline__ void send_info(uint32_t bar, int i, uint32_t v) {
#pragma unroll
  for (int r = 0; r < 2; r++)
    asm volatile("{\n.reg .b32 a, m;\nmapa.shared::cluster.u32 a, %0, %2;\nmapa.shared::cluster.u32 m, %1, %2;\n"
                 "st.async.weak.shared::cluster.mbarrier::complete_tx::bytes.b32 [a], %3, [m];\n}"
                 ::"r"(bar + S_ROLE + 4 * i), "r"(bar + B_ROLE + 8 * i), "r"(r), "r"(v) : "memory");
}
__device__ __forceinline__ unsigned probe(uint8_t* p, int lane, int pb) {
  if (lane < 2) *(uint4*)(p + lane * 16) = make_uint4(0, 0, 0, 0);
  __syncwarp();
  unsigned v = 0, best = ~0u;
  if (lane == 0) {
#pragma unroll 1
    for (int r = 0; r < NPR; r++) {
      unsigned t0, t1;
      asm volatile("mov.u32 %0, %%clock;" : "=r"(t0) : "r"(v) : "memory");
      asm volatile("atom.relaxed.gpu.global.exch.b32 %0, [%1], 0;" : "=r"(v) : "l"(p) : "memory");
      asm volatile("{\n.reg .pred p;\nsetp.ne.u32 p, %1, 0xffffffff;\nmov.u32 %0, 0;\n@p mov.u32 %0, %%clock;\n}" : "=r"(t1) : "r"(v) : "memory");
      best = min(best, t1 - t0);
      if (r < 3) PROF_V(pb + r, t1 - t0);
    }
  }
  return best;
}

template <bool ISX>
__device__ __forceinline__ void t_issue(float (&t)[32], uint32_t sb, uint32_t raw) {
  const uint64_t da = mk_desc(sb + OFF_F), db = mk_desc(raw);
  wg_fence();
#pragma unroll
  for (int kk = 0; kk < (ISX ? 4 : 1); kk++) wgmma_fwd<1>(t, da + 2 * kk, db + 128 * kk, kk);
  wg_commit();
}
template <bool ISX>
__device__ __forceinline__ void t_finish(float (&t)[32], uint32_t dst, uint32_t sbar, int sw, int wg, int w, int lane) {
  fence_regs(t);
  if (ISX) asm volatile("bar.sync %0, 128;" ::"r"(1 + wg) : "memory");
  const int m = lane >> 3, r = lane & 7;
  uint32_t ad = dst + (8 * w + r) * 128;
  if (ISX) ad += ((((m & 1) * 4 + (m >> 1)) ^ sw ^ r) << 4);
  else ad += (m & 1) * 4096 + (((m >> 1) ^ sw ^ r) << 4);
#pragma unroll
  for (int i = 0; i < 4; i++) {
    const uint32_t a = ISX ? ((ad ^ ((i & 1) * 32)) + (i >> 1) * 4096) : (ad ^ (i * 32));
    stsm4(a, pack2(t[8 * i], t[8 * i + 1]), pack2(t[8 * i + 2], t[8 * i + 3]), pack2(t[8 * i + 4], t[8 * i + 5]), pack2(t[8 * i + 6], t[8 * i + 7]));
  }
  __syncwarp();
  if (lane == 0) mbar_arrive(sbar);
}
template <int NT, int K0, int K1>
__device__ __forceinline__ void batch(float (&yr)[80], float (&yi)[80], float (&t)[32], uint32_t st, int wg, int sd, uint32_t fa, uint32_t raw) {
  const uint64_t w0 = mk_desc(st + wg * 8192), x0 = mk_desc(st + WBLK);
  const uint64_t da = mk_desc(fa), db = mk_desc(raw);
  wg_fence();
  if (NT) {
#pragma unroll
    for (int kk = 0; kk < NT; kk++) wgmma_fwd<1>(t, da + 2 * kk, db + 128 * kk, kk);
    wg_commit();
  }
#pragma unroll
  for (int kk = K0; kk < K1; kk++) {
    const uint64_t wr = w0 + kk * 128, wi = wr + 256, xr = x0 + kk * 2, xi = xr + 4;
    wgmma_main<1>(yr, wr, xr, kk ? 1 : sd);
    wgmma_main<1>(yi, wr, xi, kk ? 1 : sd);
    wgmma_main<1>(yr, wi, xi, 1);
    wgmma_main<-1>(yi, wi, xr, 1);
  }
  wg_commit();
}

#define X_WAIT() PROF_W(wraw, mbar_wait(bar + B_RAWX + 8 * (wg * 3 + xs), xph))
#define X_ISSUE() t_issue<true>(t, sb, sb + OFF_XR + (wg * 3 + xs) * 8192)
#define X_FINISH(sw) do { t_finish<true>(t, sb + OFF_XR + (wg * 3 + xs) * 8192, bar + B_STGX + 8 * (wg * 3 + xs), sw, wg, w, lane); \
                          if (++xs == 3) { xs = 0; xph ^= 1; } } while (0)
#define W_WAIT(n) PROF_W(wraw, mbar_wait(bar + B_RAWW + 8 * (wg * 2 + ((n) & 1)), ((n) >> 1) & 1))
#define WRAW(n) (sb + OFF_WRAW + (wg * 2 + ((n) & 1)) * 2048)
#define W_FINISH() t_finish<false>(t, sb + OFF_WS + wg * 8192, bar + B_STGW + 8 * wg, (bid >> 1) & 7, wg, w, lane)

template <int g>
__device__ __forceinline__ void manager(const Maps& tm, unsigned* ctr, const uint32_t sb, const int bid) {
  const uint32_t bar = sb + OFF_BAR, rank = bid & 1;
  const uint64_t pol = policy_evict_first();
  const int id = read_info(bar, 0) * 2 + rank;
  int li = 0;
  auto refill = [&](int sl) {
    if (li >= 32) return;
    const uint32_t fb = bar + B_RAWX + 8 * (g * 3 + sl);
    mbar_expect(fb, 8192);
    tma_ld3h(sb + OFF_XR + (g * 3 + sl) * 8192, &tm.x, (li >> 1) * 64, ((li & 1) ? 128 + (id & 31) : 2 * (id & 63) + g) * MT, id >> 6, fb, pol);
    li += (li & 1) || has_x2(id, li >> 1, g) ? 1 : 2;
  };
#pragma unroll 1
  for (int sl = 0; sl < 3; sl++) refill(sl);
  int xs = 0, xph = 0, yp = 0;
  int wrow = (rank * 2 + (bid >> 6)) * 128 + g * 64 + ((bid >> 1) & 31);
  if (WFIRST) {
    mbar_wait(bar + B_STGW + 8 * g, 0);
    fence_async_smem();
    tma_st4(&tm.wst, sb + OFF_WS + g * 8192, 0, 0, 0, wrow);
    bulk_commit();
  }
  const uint32_t pgmask = read_info(bar, 1);
#pragma unroll 1
  for (int n = 0; n < 32; n++) {
    unsigned freed = 128;
    if (n >= WR) asm volatile("ld.relaxed.gpu.global.u32 %0, [%1];" : "=r"(freed) : "l"(&ctr[(C_LOADED + n - WR) * 32]) : "memory");
    if (n < 16) {
#pragma unroll 1
      for (int j = 0; j < (has_x2(id, n, g) ? 2 : 1); j++) {
        const int t = j ? 128 + (id & 31) : 2 * (id & 63) + g;
        int par0, par1;
        const uint32_t off0 = x_base(id >> 6, n * 10 + (t >> 5), pgmask, par0), off1 = x_base(id >> 6, n * 10 + 5 + (t >> 5), pgmask, par1);
        const uint32_t buf = sb + OFF_XR + (g * 3 + xs) * 8192;
        mbar_wait(bar + B_STGX + 8 * (g * 3 + xs), xph);
        fence_async_smem();
        tma_st5(&tm.xst[par0], buf, (off0 + (par0 << 12) + (t & 31) * 128) >> 1);
        tma_st5(&tm.xst[par1], buf + 4096, (off1 + (par1 << 12) + (t & 31) * 128) >> 1);
        bulk_commit();
        bulk_wait_read<0>();
        refill(xs);
        if (++xs == 3) { xs = 0; xph ^= 1; }
      }
    }
    if (n > 16 + LW && n <= YFLUSH && (n - 17 - LW) % YSTEP == 0) {
      if (yp == 0 || yp == 3) mbar_wait(bar + B_Y + 8 * g, yp & 1);
#pragma unroll 1
      do {
        tma_st4(&tm.yst[0], sb + OFF_XR + (g * 3 + (yp < 3 ? yp : yp - 3)) * 8192, 0, yp * 32, id & 62, (id >> 6) * 4 + rank * 2 + g);
      } while (++yp < 2);
      bulk_commit();
      bulk_wait_read<0>();
      if (yp == 2) mbar_arrive(bar + B_YFREE + 8 * g);
    }
    if (freed < 128) flag_wait(&ctr[(C_LOADED + n - WR) * 32], 128);
    if (n || !WFIRST) {
      mbar_wait(bar + B_STGW + 8 * g, n & 1);
      fence_async_smem();
      tma_st4(&tm.wst, sb + OFF_WS + g * 8192, 0, 0, 0, wrow);
      bulk_commit();
    }
    wrow += WCHUNK / 128;
    if (wrow >= WR * WCHUNK / 128) wrow -= WR * WCHUNK / 128;
    if (n < 30) {
      const int cp = chunk_of(n + 2) * 64 + (bid >> 1), sl = g * 2 + (n & 1);
      mbar_expect(bar + B_RAWW + 8 * sl, 2048);
      tma_ld3h(sb + OFF_WRAW + sl * 2048, &tm.we + (cp >> 9), 0, 0, (cp & 511) * 8 + ((n + 2) >> 4) * 4 + rank * 2 + g, bar + B_RAWW + 8 * sl, pol);
    }
    if (n < 4) {
#pragma unroll 1
      for (int q = 4 + n; q < 16; q += 4) {
        const int cp = q * 64 + (bid >> 1);
        tma_pf3(&tm.we + (cp >> 9), 0, 0, (cp & 511) * 8 + rank * 2 + g);
      }
    }
    bulk_wait<0>();
    mbar_arrive(bar + B_DONE + 8 * (n & 3));
    mbar_arrive(bar + B_RAWW + 8 * (g * 2 + ((n + 1) & 1)));
  }
  const int b = id >> 6, u = (id >> 1) & 31;
  flag_wait(&ctr[(C_LOADED + 31) * 32], 128);
  mbar_wait(bar + B_Y + 8 * g, 0);
  for (int p = 0; p < 5; p++) tma_st4(&tm.yst[1], sb + (p * 2 + g) * 8192, 0, p * 32, 2 * u, b * 4 + rank * 2 + g);
  bulk_commit();
  bulk_wait<0>();
  mbar_arrive(bar + B_DONE);
#pragma unroll 1
  for (int i = 0; i < 10; i++) {
    const int hf = i >= 5, k = i - 5 * hf;
    mbar_wait(bar + B_OUT + 8 * (g * 5 + k), hf);
    fence_async_smem();
    tma_st3(&tm.out, sb + (hf ? 0 : k < 4 ? OFF_XR : OFF_H0B - 65536) + (2 * k + g) * 8192, (hf * 4 + rank * 2 + (u & 1)) * 64, ((u >> 1) * 10 + 2 * k + g) * MT, b);
    bulk_commit();
  }
  bulk_wait_read<0>();
  if (g == 0) PROF_T(12);
}

__global__ void __cluster_dims__(2, 1, 1) __launch_bounds__(512, 1)
k1_main(uint8_t* __restrict__ xbuf, const void* __restrict__ fimg, unsigned* ctr, const __nv_bfloat16* __restrict__ gamma,
        const __nv_bfloat16* __restrict__ beta, const __grid_constant__ Maps tm) {
  extern __shared__ __align__(1024) uint8_t smem_raw[];
  const uint32_t sb = s2u(smem_raw);
  const uint32_t bar = sb + OFF_BAR;
  const int warp = __shfl_sync(0xffffffffu, threadIdx.x >> 5, 0);
  const int bid = (int)blockIdx.x - 4;
  const uint32_t rank = bid & 1;
  if (warp >= 12) {
    asm volatile("setmaxnreg.dec.sync.aligned.u32 24;");
    asm volatile("barrier.cluster.arrive.relaxed.aligned;" ::: "memory");
    if (bid >= 0) {
      const int lane = lane_id(), k = bid >> 1;
      if (rank == 0 || k < XPAGES) {
        const uint32_t off = rank ? (k << 21) + 0xb0000 : (XPAGES << 21) + ((k >> 4) << 14) + (k & 15) * 128;
        const unsigned lat = probe(xbuf + off + (warp & 1) * 4096 + (warp & 2) * 1024, lane, 400 + (warp & 2) * 5 + (warp & 1) * 3);
        if (lane == 0) asm volatile("st.shared.b32 [%0], %1;" ::"r"(bar + S_PROBE + 4 * (warp & 3)), "r"(lat) : "memory");
      }
      asm volatile("bar.sync 4, 128;" ::: "memory");
      asm volatile("barrier.cluster.wait.aligned;" ::: "memory");
      if (warp == 14 && lane == 0) {
        uint32_t l0, l1, l2, l3;
        asm volatile("ld.shared.v4.b32 {%0, %1, %2, %3}, [%4];" : "=r"(l0), "=r"(l1), "=r"(l2), "=r"(l3) : "r"(bar + S_PROBE) : "memory");
        const int near = min(l1, l3) < min(l0, l2);
        if (rank) {
          send_info(bar, 2, near);
        } else {
          unsigned long long add = 1ull << (8 * near), v, *reg = (unsigned long long*)&ctr[C_REG * 32];
          if (k < XPAGES) add += (unsigned long long)(read_info(bar, 2) ^ near ^ 1) << (16 + k);
          PROF_T(14);
          asm volatile("{\n.reg .pred p;\n.reg .u32 c;\nmov.u32 c, 0;\nAGAIN:\n"
                       "atom.relaxed.gpu.global.add.u64 %0, [%1], %2;\nsetp.lt.s64 p, %0, 0;\n@p bra DONE;\n"
                       "add.u32 c, c, 1;\nsetp.lt.u32 p, c, 0x100000;\n@p bra AGAIN;\ntrap;\nDONE:\n}" : "=l"(v) : "l"(reg), "l"(add) : "memory");
          const int ticket = (v >> (8 * near)) & 255;
          send_info(bar, 0, ticket < 32 ? near * 32 + ticket : (near ^ 1) * 32 + 63 - ticket);
          PROF_T(15); PROF_V(16, near); PROF_V(17, ticket < 32 ? near * 32 : (near ^ 1) * 32);
          asm volatile("{\n.reg .pred p;\n.reg .u32 c, a, b;\nmov.u32 c, 0;\nWAIT:\n"
                       "ld.relaxed.gpu.global.u64 %0, [%1];\ncvt.u32.u64 a, %0;\nbfe.u32 b, a, 8, 8;\nand.b32 a, a, 255;\nadd.u32 a, a, b;\n"
                       "setp.ge.u32 p, a, 64;\n@p bra DONE;\n"
                       "add.u32 c, c, 1;\nsetp.lt.u32 p, c, 0x400000;\n@p bra WAIT;\ntrap;\nDONE:\n}" : "=l"(v) : "l"(reg) : "memory");
          send_info(bar, 1, (uint32_t)(v >> 16));
          PROF_T(13);
        }
      }
      __syncwarp();
      if (warp - 12 < NFL && elect_one()) {
#pragma unroll 1
        for (int n = warp - 12; n < 33; n += NFL) {
          int f = n;
          if (n == 32) f += (read_info(bar, 0) >> 5) * 2 + rank;
          mbar_wait(bar + B_DONE + 8 * (n & 3), (n >> 2) & 1);
          fence_release();
          red_add(&ctr[(C_FLAG + f) * 32]);
          if (n < 32) { PROF_T(64 + n); PROF_V(192 + n, tm0); } else { PROF_V(4, tm0); }
        }
      }
      if (warp == 15 && elect_one()) {
#pragma unroll 1
        for (int v = 0; v < 64; v++) {
          mbar_wait(bar + B_FULL + 8 * (v & 3), (v >> 2) & 1);
          if ((v & 1) && (v < 2 * (32 - WR) || v == 63)) red_add(&ctr[(C_LOADED + (v >> 1)) * 32]);
        }
      }
      __syncwarp();
    } else {
      if (blockIdx.x == 0 && warp == 12 && lane_id() < 4)
        asm volatile("st.relaxed.gpu.global.u64 [%0], %1;" ::"l"(&ctr[C_REG * 32 + 2 * lane_id()]), "l"(1ull << 63) : "memory");
      __syncwarp();
      asm volatile("barrier.cluster.wait.aligned;" ::: "memory");
    }
    asm volatile("barrier.cluster.arrive.relaxed.aligned;\nbarrier.cluster.wait.aligned;" ::: "memory");
    return;
  } else {
    if (elect_one()) {
      if (warp == 0) PROF_T(0);
      if (warp >= 6) asm volatile("prefetch.tensormap [%0];" ::"l"(&tm.x + (warp - 6)) : "memory");
      const int cnt = warp < 4 ? 1 : warp < 9 ? 4 : 2;
#pragma unroll
      for (int i = 0; i < 5; i++) mbar_init(bar + warp * 40 + 8 * i, cnt);
      if (warp == 1) {
        mbar_expect(bar + B_ROLE, 4);
        mbar_expect(bar + B_ROLE + 8, 4);
        mbar_expect(bar + B_ROLE + 16, 4);
      }
      asm volatile("fence.mbarrier_init.release.cluster;" ::: "memory");
    }
    asm volatile("bar.sync 0, 384;" ::: "memory");
    asm volatile("barrier.cluster.arrive.relaxed.aligned;" ::: "memory");
    if (threadIdx.x == 64) PROF_T(20);
    if (bid >= 0 && warp < 7 && elect_one()) {
      const int g = warp & 1, q = warp >> 2;
      const uint64_t pol = policy_evict_first();
      if (warp < 2) {
        tma_pf3(&tm.x, 0, (2 * (bid & 63) + g) * MT, bid >> 6);
        if (has_x2(bid, 0, g)) tma_pf3(&tm.x, 0, (128 + (bid & 31)) * MT, bid >> 6);
      } else if (warp < 6) {
        const uint32_t fb = bar + B_RAWW + 8 * (g * 2 + q);
        mbar_expect(fb, 2048);
        tma_ld3h(sb + OFF_WRAW + (g * 2 + q) * 2048, &tm.we, 0, 0, (q * 64 + (bid >> 1)) * 8 + rank * 2 + g, fb, pol);
        if (!q) mbar_arrive(fb);
      } else {
        mbar_expect(bar + B_F, 8192);
        bulk_ld(sb + OFF_F, fimg, 8192, bar + B_F);
      }
    }
    __syncwarp();
  }
  if (warp >= 8) {
    asm volatile("setmaxnreg.dec.sync.aligned.u32 40;");
    if (bid < 0) {
      asm volatile("barrier.cluster.wait.aligned;" ::: "memory");
    } else if (warp == 9 || warp == 10) {
      if (elect_one()) {
        if (warp == 9) manager<0>(tm, ctr, sb, bid); else manager<1>(tm, ctr, sb, bid);
      }
      __syncwarp();
      asm volatile("barrier.cluster.wait.aligned;" ::: "memory");
    } else if (warp == 11) {
      asm volatile("barrier.cluster.wait.aligned;" ::: "memory");
      if (elect_one()) {
        const uint8_t* ws = g_W + (size_t)((read_info(bar, 0) & 31) * 2 + rank) * 2 * WBLK;
        int slot = 0;
#pragma unroll 1
        for (int n = 0; n < 32; n++) {
          const uint8_t* src = ws + (size_t)slot * WCHUNK;
          const uint32_t s8 = (n & 1) * 16, dst = sb + (n & 1) * 2 * G_STAGE;
          const int ph = ((n >> 1) & 1) ^ 1;
          if (++slot == WR) slot = 0;
          flag_wait(&ctr[(C_FLAG + n) * 32], 128);
          fence_async_global();
          PROF_T(32 + n);
#pragma unroll
          for (int h = 0; h < 2; h++) {
            mbar_wait(bar + B_EMPTY + s8 + 8 * h, ph);
            mbar_expect(bar + B_FULL + s8 + 8 * h, WBLK);
            bulk_ld(dst + h * G_STAGE, src + h * WBLK, WBLK, bar + B_FULL + s8 + 8 * h);
          }
        }
      }
      __syncwarp();
    } else {
      asm volatile("barrier.cluster.wait.aligned;" ::: "memory");
      if (elect_one()) {
        const int role = read_info(bar, 0);
        const uint32_t pgmask = read_info(bar, 1);
        PROF_T(1);
        const int b = role >> 5, u = role & 31;
        const int dq = rank * 2 + (u & 1), t0 = (u >> 1) * 10;
        const uint64_t pef = policy_evict_first(), pen = policy_evict_normal();
        const uint8_t* xs = xbuf + ((((u >> 1) & 3) << 14) | (((u >> 3) & 1) << 18) | ((u >> 4) << 20) | ((u & 1) << 13));
#pragma unroll 1
        for (int n = 0; n < 32; n++) {
          const int c = chunk_of(n);
          const uint64_t polx = (n < XKEEP || n >= 16) ? pef : pen;
          const uint32_t s8 = (n & 1) * 16, dst = sb + (n & 1) * 2 * G_STAGE + WBLK + rank * 8192;
          const int ph = ((n >> 1) & 1) ^ 1;
          uint32_t xo[6];
#pragma unroll
          for (int g = 0; g < 6; g++) {
            int par;
            xo[g] = x_base(b, c * 10 + (g / 3) * 5 + rank * 2 + g % 3, pgmask, par);
            xo[g] += ((par ^ u) & 1) << 12;
            asm volatile("" : "+r"(xo[g]));
          }
          if (n < 16) {
            flag_wait(&ctr[(C_FLAG + n) * 32], 128);
            fence_async_global();
          }
#pragma unroll
          for (int h = 0; h < 2; h++) {
            const uint32_t fb = bar + B_FULL + s8 + 8 * h;
            mbar_wait(bar + B_EMPTY + s8 + 8 * h, ph);
            mbar_expect(fb, XBLK);
#pragma unroll
            for (int g = 0; g < 3; g++) {
              const int skip = (g == 0 && rank) ? 2048 : 0, len = (g == (rank ? 0 : 2)) ? 2048 : 4096;
              bulk_ld_mc_h(dst + h * G_STAGE + g * 4096 + skip, xs + xo[3 * h + g] + skip, len, fb, 3, polx);
            }
          }
        }
        flag_wait(&ctr[C_E * 32], 4);
        flag_wait(&ctr[(C_FLAG + YFLUSH) * 32], 128);
        fence_async_global();
        mbar_expect(bar + B_H0C, 6 * 8192);
        for (int i = 0; i < 3; i++) tma_ld2(sb + OFF_XR + i * 16384, &tm.yld[0], 0, ((b * 4 + dq) * NT + t0 + 2 * i) * 64, bar + B_H0C);
        static_assert(YFLUSH >= 27 && LW <= 4, "phases of the B_DONE ring");
        mbar_wait(bar + B_DONE + 8 * 3, 1);
        mbar_expect(bar + B_H0, 2 * 8192 + 7168 + 5120 + 512);
        bulk_ld(sb + OFF_F, g_Gimg, 7168, bar + B_H0);
        tma_ld2(sb + OFF_WS, &tm.yld[0], 0, ((b * 4 + dq) * NT + t0 + 6) * 64, bar + B_H0);
        tma_pf2(&tm.yld[0], 0, ((b * 4 + dq) * NT + t0 + 8) * 64);
        for (int hf = 0; hf < 2; hf++) {
          bulk_ld(sb + OFF_E + hf * 2560, g_E + ((b * 8 + hf * 4 + dq) * NT + t0) * 64, 2560, bar + B_H0);
          bulk_ld(sb + OFF_GB + hf * 256, gamma + (hf * 4 + dq) * 64, 128, bar + B_H0);
          bulk_ld(sb + OFF_GB + hf * 256 + 128, beta + (hf * 4 + dq) * 64, 128, bar + B_H0);
        }
        mbar_wait(bar + B_EMPTY + 8 * 2, 1);
        mbar_expect(bar + B_H0 + 8, 16384);
        tma_ld2(sb + OFF_H0B, &tm.yld[0], 0, ((b * 4 + dq) * NT + t0 + 8) * 64, bar + B_H0 + 8);
        flag_wait(&ctr[(C_FLAG + 32 + b * 2 + rank) * 32], 32);
        fence_async_global();
        PROF_T(5);
        for (int i = 0; i < 5; i++) {
          const uint32_t fb = bar + B_H1 + 8 * (i >> 1);
          if ((i & 1) == 0) mbar_expect(fb, i < 4 ? 32768 : 16384);
          tma_ld2(sb + i * 16384, &tm.yld[1], 0, ((b * 4 + dq) * NT + t0 + 2 * i) * 64, fb);
        }
      }
      __syncwarp();
      const int lane = lane_id();
      unsigned old = 0;
      if (lane == 0) old = atomicAdd(&ctr[C_EXIT * 32], 1);
      if (__shfl_sync(0xffffffffu, old, 0) == 127) {
        for (int i = lane; i < C_NUM; i += 32) *(uint4*)&ctr[i * 32] = make_uint4(0, 0, 0, 0);
      }
    }
    asm volatile("barrier.cluster.arrive.relaxed.aligned;\nbarrier.cluster.wait.aligned;" ::: "memory");
  } else {
    asm volatile("setmaxnreg.inc.sync.aligned.u32 224;");
    const int wg = warp >> 2, w = warp & 3;
    int lane = lane_id();
    asm volatile("barrier.cluster.wait.aligned;" ::: "memory");
    if (bid < 0) {
      float ea[80], eb[80];
      const int b = blockIdx.x >> 1;
      constexpr int ES = 32768 + 2 * XBLK;
#pragma unroll 1
      for (int k = -3; k < 8; k++) {
        const int sl = (k + 3) % 3;
        if (k >= 0) {
          mbar_wait(bar + B_RAWX + 8 * sl, (k / 3) & 1);
          const uint64_t da = mk_desc(sb + sl * ES + wg * 16384), db = mk_desc(sb + sl * ES + 32768);
          wg_fence();
#pragma unroll
          for (int kk = 0; kk < 8; kk++) {
            const uint64_t a0 = da + (kk & 3) * 128, b0 = db + (kk & 3) * 2 + (kk >> 2) * (XBLK >> 4);
            wgmma_main<1>(ea, a0, b0, (k | kk) != 0);
            wgmma_main<1>(eb, a0 + 512, b0, (k | kk) != 0);
          }
          wg_commit();
          wg_wait<0>();
          asm volatile("bar.sync 3, 256;" ::: "memory");
        }
        if (k + 3 < 8 && warp == 0 && elect_one()) {
          const uint32_t dst = sb + sl * ES, fb = bar + B_RAWX + 8 * sl;
          mbar_expect(fb, ES);
          for (int q = 0; q < 4; q++) tma_ld2(dst + q * 8192, &tm.w30, rank * 256 + q * 64, (k + 3) * 64, fb);
          for (int q = 0; q < 2; q++) tma_ld3(dst + 32768 + q * XBLK, &tm.xe[q], (k + 3) * 64, 0, b, fb);
        }
        __syncwarp();
      }
      fence_regs(ea);
      fence_regs(eb);
      float* e0 = g_E + ((b * 8 + rank * 4 + wg * 2) * NT + 2 * (lane & 3)) * 64 + 16 * w + (lane >> 2);
#pragma unroll
      for (int i = 0; i < 80; i++) {
        const int o = (8 * (i >> 2) + (i & 1)) * 64 + ((i >> 1) & 1) * 8;
        e0[o] = ea[i];
        e0[o + NT * 64] = eb[i];
      }
      asm volatile("bar.sync 3, 256;" ::: "memory");
      if (threadIdx.x == 0) {
        fence_release();
        red_add(&ctr[C_E * 32]);
        PROF_T(28);
      }
      asm volatile("barrier.cluster.arrive.relaxed.aligned;\nbarrier.cluster.wait.aligned;" ::: "memory");
      return;
    }
    int id;
    {
      float yr[80], yi[80], t[32];

      int xs = 0, xph = 0;
      if (threadIdx.x == 0) PROF_T(24);
      mbar_wait(bar + B_F, 0);
      W_WAIT(0);
      t_issue<false>(t, sb, WRAW(0));
      wg_wait<0>();
      W_FINISH();
      id = __shfl_sync(0xffffffffu, read_info(bar, 0), 0) * 2 + rank;
      if (threadIdx.x == 0) PROF_T(25);
#pragma unroll 1
      for (int m = 0; m <= LW; m++) {
        X_WAIT();
        X_ISSUE();
        wg_wait<0>();
        X_FINISH((2 * id + wg) & 7);
        if (threadIdx.x == 0 && m == 0) PROF_T(26);
        if (has_x2(id, m, wg)) {
          X_WAIT();
          X_ISSUE();
          wg_wait<0>();
          X_FINISH(id & 7);
        }
        if (m < LW && (m || !WFIRST)) {
          W_WAIT(m);
          t_issue<false>(t, sb, WRAW(m));
          wg_wait<0>();
          W_FINISH();
        }
      }
      if (threadIdx.x == 0) PROF_T(27);
      const int ym = lane >> 3, yr8 = lane & 7;
      const uint32_t yad = (ym >> 1) * 4096 + yr8 * 128 + (((2 * w + (ym & 1)) ^ yr8) << 4);
#define STAGE_PROF0()
#define STAGE_PROF1()
#define STAGE_BEGIN() PROF_W(wfull, mbar_wait(bar + B_FULL + 8 * (v & 3), (v >> 2) & 1)); STAGE_PROF0(); const uint32_t st = sb + (v & 3) * G_STAGE
#define RELEASE(vv) do { if (w == 0 && lane < 2) mbar_arrive_cluster(bar + B_EMPTY + 8 * ((vv) & 3), lane, 1); } while (0)
#define XRAW (sb + OFF_XR + (wg * 3 + xs) * 8192)
#define STAGE_W0(mw, sd) do { W_WAIT(mw); batch<1, 0, 2>(yr, yi, t, st, wg, sd, sb + OFF_F, WRAW(mw)); wg_wait<1>(); W_FINISH(); wg_wait<0>(); RELEASE(v); } while (0)
#define STAGE_PLAIN0(sd) do { batch<0, 0, 2>(yr, yi, t, st, wg, sd, 0, 0); wg_wait<0>(); RELEASE(v); } while (0)
#define STAGE_W1(mw, sd) do { W_WAIT(mw); batch<1, 0, 1>(yr, yi, t, st, wg, sd, sb + OFF_F, WRAW(mw)); wg_wait<1>(); if (sd) RELEASE(v - 1); \
                              W_FINISH(); batch<0, 1, 2>(yr, yi, t, st, wg, 1, 0, 0); } while (0)
#define STAGE_PLAIN1(sd) do { batch<0, 0, 1>(yr, yi, t, st, wg, sd, 0, 0); wg_wait<1>(); if (sd) RELEASE(v - 1); \
                              batch<0, 1, 2>(yr, yi, t, st, wg, 1, 0, 0); } while (0)
#pragma unroll 1
      for (int v = 0; v < 32; v++) {
        const int m = ((v + 1) >> 1) + LW;
        STAGE_BEGIN();
        if (!(v & 1) || v == 31) {
          if (P0M) STAGE_W1(m, v != 0); else STAGE_W0(m, v != 0);
        } else if (m >= 16) {
          if (P0M) STAGE_PLAIN1(1); else STAGE_PLAIN0(1);
        } else {
          X_WAIT();
          batch<4, 0, 1>(yr, yi, t, st, wg, 1, sb + OFF_F, XRAW);
          wg_wait<1>();
          if (P0M) RELEASE(v - 1);
          X_FINISH((2 * id + wg) & 7);
          if (has_x2(id, m, wg)) {
            X_WAIT();
            batch<4, 1, 2>(yr, yi, t, st, wg, 1, sb + OFF_F, XRAW);
            wg_wait<1>();
            X_FINISH(id & 7);
          } else {
            batch<0, 1, 2>(yr, yi, t, st, wg, 1, 0, 0);
          }
          if (!P0M) { wg_wait<0>(); RELEASE(v); }
        }
        STAGE_PROF1();
      }
      wg_wait<0>();
      fence_regs(yr);
      fence_regs(yi);
      if (P0M) RELEASE(31);
      {
        uint32_t hold[32];
#pragma unroll
        for (int j = 0; j < 20; j++) {
          const uint32_t p0 = pack2(yr[4 * j], yr[4 * j + 1]), p1 = pack2(yr[4 * j + 2], yr[4 * j + 3]);
          const uint32_t p2 = pack2(yi[4 * j], yi[4 * j + 1]), p3 = pack2(yi[4 * j + 2], yi[4 * j + 3]);
          if (j < 12) {
            stsm4t(sb + OFF_XR + wg * 3 * 8192 + yad + (j >> 2) * 8192 + (j & 3) * 1024, p0, p1, p2, p3);
          } else {
            hold[4 * j - 48] = p0; hold[4 * j - 47] = p1; hold[4 * j - 46] = p2; hold[4 * j - 45] = p3;
          }
        }
#pragma unroll
        for (int j = 0; j < 32; j++) asm volatile("" : "+r"(hold[j])::"memory");
        fence_async_smem();
        __syncwarp();
        if (lane == 0) mbar_arrive(bar + B_Y + 8 * wg);
        if (threadIdx.x == 0) PROF_T(2);
#pragma unroll
        for (int v = 32; v < 34; v++) {
          STAGE_BEGIN();
          if (P1M) STAGE_PLAIN1(v != 32); else STAGE_PLAIN0(v != 32);
          STAGE_PROF1();
        }
        mbar_wait(bar + B_YFREE + 8 * wg, 0);
#pragma unroll
        for (int j = 0; j < 8; j++)
          stsm4t(sb + OFF_XR + wg * 3 * 8192 + yad + (j >> 2) * 8192 + (j & 3) * 1024, hold[4 * j], hold[4 * j + 1], hold[4 * j + 2], hold[4 * j + 3]);
        fence_async_smem();
        __syncwarp();
        if (lane == 0) mbar_arrive(bar + B_Y + 8 * wg);
#pragma unroll
        for (int j = 0; j < 32; j++) t[j] = __uint_as_float(hold[j]);
      }
#pragma unroll 1
      for (int v = 34; v < 64; v++) {
        const int m = (v >> 1) + LW;
        STAGE_BEGIN();
        if (!(v & 1) && m < 32) {
          if (P1M) STAGE_W1(m, 1); else STAGE_W0(m, 1);
        } else {
          if (P1M) STAGE_PLAIN1(1); else STAGE_PLAIN0(1);
          if (v == 49 && wg == 0) g_part[bid * 128 + w * 32 + lane] = ~0ull;
        }
        STAGE_PROF1();
      }
      wg_wait<0>();
      fence_regs(yr);
      fence_regs(yi);
      asm volatile("bar.sync 3, 256;" ::: "memory");
#pragma unroll
      for (int j = 0; j < 20; j++)
        stsm4t(sb + wg * 8192 + yad + (j >> 2) * 16384 + (j & 3) * 1024, pack2(yr[4 * j], yr[4 * j + 1]), pack2(yr[4 * j + 2], yr[4 * j + 3]),
               pack2(yi[4 * j], yi[4 * j + 1]), pack2(yi[4 * j + 2], yi[4 * j + 3]));
      fence_async_smem();
      __syncwarp();
      if (lane == 0) mbar_arrive(bar + B_Y + 8 * wg);
      if (threadIdx.x == 0) PROF_T(3);
    }
    lane = lane_id();
    const int tid = warp * 32 + lane, b = id >> 6, u = (id >> 1) & 31;
    const int dq = rank * 2 + (u & 1), tr = u >> 1;
    const int a = lane & 3, d0 = 16 * w + (lane >> 2);
    float2* s_red = (float2*)(smem_raw + OFF_WRAW);
#pragma unroll 1
    for (int hf = 0; hf < 2; hf++) {
      const uint32_t base = sb + (hf ? 0 : OFF_XR), last = hf ? 0 : OFF_H0B - 65536 - OFF_XR;
      float acc[5][28];
      float s1[2] = {0.f, 0.f}, s2[2] = {0.f, 0.f};
      if (hf == 0) { mbar_wait(bar + B_H0, 0); mbar_wait(bar + B_H0C, 0); }
      const float* se = (const float*)(smem_raw + OFF_E + hf * 2560) + wg * 64 + d0;
#pragma unroll
      for (int k2 = 0; k2 < 4; k2++) {
        if (k2 < 3) {
          if (hf) mbar_wait(bar + B_H1 + 8 * k2, 0);
          else if (k2 == 2) mbar_wait(bar + B_H0 + 8, 0);
          const uint64_t da = mk_desc(base + (4 * k2 + wg) * 8192 + (k2 == 2 ? last : 0)), db = mk_desc(sb + OFF_F);
          wg_fence();
#pragma unroll
          for (int kk = 0; kk < 4; kk++) {
            wgmma_inv<1>(acc[2 * k2], da + 128 * kk, db + 2 * kk, kk);
            if (k2 < 2) wgmma_inv<1>(acc[2 * k2 + 1], da + 1024 + 128 * kk, db + 2 * kk, kk);
          }
          wg_commit();
        }
        if (k2 > 0) {
          if (k2 < 3) wg_wait<1>(); else wg_wait<0>();
#pragma unroll
          for (int k = 2 * k2 - 2; k < 2 * k2 && k < 5; k++) {
            fence_regs(acc[k]);
            if (a == 0) {
              acc[k][25] += se[k * 128];
              acc[k][27] += se[k * 128 + 8];
            }
            if (k == 4 && tr == 15 && wg == 1) {
#pragma unroll
              for (int i = 16; i < 28; i++)
                if (8 * (i >> 2) + (i & 1) + 2 * a >= LOUT - (NT - 1) * MT) acc[k][i] = 0.f;
            }
#pragma unroll
            for (int i = 0; i < 28; i += 2) {
              s1[(i >> 1) & 1] += acc[k][i] + acc[k][i + 1];
              s2[(i >> 1) & 1] += fmaf(acc[k][i], acc[k][i], acc[k][i + 1] * acc[k][i + 1]);
            }
          }
        }
      }
#pragma unroll
      for (int i = 0; i < 2; i++) {
#pragma unroll
        for (int o = 1; o < 4; o <<= 1) {
          s1[i] += __shfl_xor_sync(0xffffffffu, s1[i], o);
          s2[i] += __shfl_xor_sync(0xffffffffu, s2[i], o);
        }
      }
      if (a == 0) {
        s_red[wg * 64 + d0] = make_float2(s1[0], s2[0]);
        s_red[wg * 64 + d0 + 8] = make_float2(s1[1], s2[1]);
      }
      asm volatile("bar.sync 3, 256;" ::: "memory");
      if (tid == 0) PROF_T(6 + 3 * hf);
      unsigned long long* part = g_part + ((hf * 2 + b) * 4 + dq) * 1024;
      if (tid < 64) {
        const float2 p0 = s_red[tid], p1 = s_red[64 + tid];
        const float x1 = p0.x + p1.x, x2 = p0.y + p1.y;
        const unsigned long long v = ((unsigned long long)(__float_as_uint(x2) & 0x7fffffffu) << 32) | __float_as_uint(x1);
        asm volatile("st.relaxed.gpu.global.u64 [%0], %1;" ::"l"(part + tr * 64 + tid), "l"(v) : "memory");
      }
      {
        const unsigned long long* q = part + (tid >> 6) * 256 + (tid & 63);
        unsigned long long v[4];
        poll64x4(q, v);
        float x1 = 0.f, x2 = 0.f;
#pragma unroll
        for (int i = 0; i < 4; i++) {
          x1 += __uint_as_float((uint32_t)v[i]);
          x2 += __uint_as_float((uint32_t)(v[i] >> 32));
        }
        s_red[128 + tid] = make_float2(x1, x2);
      }
      asm volatile("bar.sync 3, 256;" ::: "memory");
      if (tid == 0) PROF_T(7 + 3 * hf);
#pragma unroll
      for (int i = 0; i < 2; i++) {
        const float2 q0 = s_red[128 + d0 + 8 * i], q1 = s_red[192 + d0 + 8 * i], q2 = s_red[256 + d0 + 8 * i], q3 = s_red[320 + d0 + 8 * i];
        const float mu = ((q0.x + q1.x) + (q2.x + q3.x)) * (1.f / LOUT);
        const float var = fmaxf(((q0.y + q1.y) + (q2.y + q3.y)) * (1.f / LOUT) - mu * mu, 0.f);
        const __nv_bfloat16* gb = (const __nv_bfloat16*)(smem_raw + OFF_GB + hf * 256) + d0 + 8 * i;
        s1[i] = 0.5f * __bfloat162float(gb[0]) / sqrtf(var + 1e-5f);
        s2[i] = 0.5f * __bfloat162float(gb[64]) - mu * s1[i];
      }
      const int m = lane >> 3, r = lane & 7;
      const uint32_t ad = base + wg * 8192 + ((m >> 1) * 8 + r) * 128 + (((2 * w + (m & 1)) ^ r) << 4);
#pragma unroll
      for (int k = 0; k < 5; k++) {
#pragma unroll
        for (int i = 0; i < 28; i++) {
          const float hz = fmaf(acc[k][i], s1[(i >> 1) & 1], s2[(i >> 1) & 1]);
          const float in = hz * fmaf(hz * hz, 8.f * 0.044715f * 0.7978845608028654f, 2.f * 0.7978845608028654f);
          float th;
          asm("tanh.approx.f32 %0, %1;" : "=f"(th) : "f"(in));
          acc[k][i] = fmaf(hz, th, hz);
        }
#pragma unroll
        for (int jj = 0; jj < 3; jj++) {
          const float* c = acc[k] + 8 * jj;
          stsm4t(ad + (k == 4 ? last : 0) + k * 16384 + jj * 2048, pack2(c[0], c[1]), pack2(c[2], c[3]), pack2(c[4], c[5]), pack2(c[6], c[7]));
        }
        stsm2t(ad + (k == 4 ? last : 0) + k * 16384 + 3 * 2048, pack2(acc[k][24], acc[k][25]), pack2(acc[k][26], acc[k][27]));
        if (k < 4) {
          float z;
          asm volatile("ld.volatile.shared.f32 %0, [%1];" : "=f"(z) : "r"(sb + OFF_F + 55 * 128) : "memory");
          s2[0] += z;
          s2[1] += z;
        }
        __syncwarp();
        if (lane == 0) mbar_arrive(bar + B_OUT + 8 * (wg * 5 + k));
      }
      if (tid == 0) PROF_T(8 + 3 * hf);
    }
    asm volatile("barrier.cluster.arrive.relaxed.aligned;\nbarrier.cluster.wait.aligned;" ::: "memory");
  }
}

typedef CUresult (*EncFn)(CUtensorMap*, CUtensorMapDataType, cuuint32_t, void*, const cuuint64_t*, const cuuint64_t*, const cuuint32_t*,
                          const cuuint32_t*, CUtensorMapInterleave, CUtensorMapSwizzle, CUtensorMapL2promotion, CUtensorMapFloatOOBfill);

void encode(EncFn fn, CUtensorMap* m, int rank, void* base, const cuuint64_t* dims, const cuuint64_t* strides, const cuuint32_t* box,
            CUtensorMapL2promotion promo) {
  cuuint32_t es[5] = {1, 1, 1, 1, 1};
  fn(m, CU_TENSOR_MAP_DATA_TYPE_BFLOAT16, rank, base, dims, strides, box, es, CU_TENSOR_MAP_INTERLEAVE_NONE, CU_TENSOR_MAP_SWIZZLE_128B, promo,
     CU_TENSOR_MAP_FLOAT_OOB_FILL_NONE);
}

}

extern "C" void kernel_launch(void* const* d_in, const int* in_sizes, int n_in, void* d_out, int out_size) {
  (void)in_sizes; (void)n_in; (void)out_size;
  const __nv_bfloat16* x = (const __nv_bfloat16*)d_in[0];
  const __nv_bfloat16* w = (const __nv_bfloat16*)d_in[1];
  const __nv_bfloat16* gamma = (const __nv_bfloat16*)d_in[2];
  const __nv_bfloat16* beta = (const __nv_bfloat16*)d_in[3];
  void* fnp = nullptr;
  cudaDriverEntryPointQueryResult qr;
  cudaGetDriverEntryPoint("cuTensorMapEncodeTiled", &fnp, cudaEnableDefault, &qr);
  EncFn fn = (EncFn)fnp;
  void *cptr = nullptr, *fptr = nullptr, *xptr = nullptr, *wptr = nullptr, *yptr = nullptr;
  cudaGetSymbolAddress(&cptr, g_ctr);
  cudaGetSymbolAddress(&fptr, g_Fimg);
  cudaGetSymbolAddress(&xptr, g_X);
  cudaGetSymbolAddress(&wptr, g_W);
  cudaGetSymbolAddress(&yptr, g_Y);
  xptr = (void*)(((uintptr_t)xptr + (1u << 21) - 1) & ~(uintptr_t)((1u << 21) - 1));
  const CUtensorMapL2promotion P0 = CU_TENSOR_MAP_L2_PROMOTION_NONE, P128 = CU_TENSOR_MAP_L2_PROMOTION_L2_128B;
  Maps m;
  {
    cuuint64_t d[3] = {1024, 8000, 2}, s[2] = {2048, 8000ull * 2048};
    cuuint32_t bx[3] = {64, 64, 1};
    encode(fn, &m.x, 3, (void*)x, d, s, bx, P128);
  }
  for (int ph = 0; ph < 2; ph++) {
    cuuint64_t d[3] = {64, (cuuint64_t)(16 - ph), 4096}, s[2] = {2ull * 262144 * 2, 128};
    cuuint32_t bx[3] = {64, 16, 1};
    encode(fn, ph ? &m.wo : &m.we, 3, (void*)(w + (size_t)ph * 262144), d, s, bx, P128);
  }
  for (int par = 0; par < 2; par++) {
    cuuint64_t d[5] = {(cuuint64_t)XPAGES << 20, 2, 4, 2, 2}, s[4] = {par ? 0x1000u : 0x3000u, 1u << 14, 1u << 18, 1u << 20};
    cuuint32_t bx[5] = {64, 2, 4, 2, 2};
    encode(fn, &m.xst[par], 5, xptr, d, s, bx, P0);
  }
  {
    cuuint64_t d[4] = {64, 32, 2, (cuuint64_t)WR * WCHUNK / 128}, s[3] = {4ull * WBLK, 4096, 128};
    cuuint32_t bx[4] = {64, 32, 2, 1};
    encode(fn, &m.wst, 4, wptr, d, s, bx, P0);
  }
  for (int p = 0; p < 2; p++) {
    void* base = p ? wptr : yptr;
    cuuint64_t d[4] = {64, NT, 64, 8}, s[3] = {8192, 128, (cuuint64_t)NT * 8192};
    cuuint32_t bx[4] = {64, 32, 2, 1};
    encode(fn, &m.yst[p], 4, base, d, s, bx, P0);
    cuuint64_t d2[2] = {64, 8ull * NT * 64}, s2[1] = {128};
    cuuint32_t bx2[2] = {64, 128};
    encode(fn, &m.yld[p], 2, base, d2, s2, bx2, P128);
  }
  {
    cuuint64_t d[3] = {512, LOUT, 2}, s[2] = {1024, (cuuint64_t)LOUT * 1024};
    cuuint32_t bx[3] = {64, MT, 1};
    encode(fn, &m.out, 3, d_out, d, s, bx, P0);
  }
  for (int q = 0; q < 2; q++) {
    cuuint64_t d[3] = {512, (cuuint64_t)(NT - q), 2}, s[2] = {MT * 2048, 8000ull * 2048};
    cuuint32_t bx[3] = {64, NT, 1};
    encode(fn, &m.xe[q], 3, (void*)(x + q * 64 * 1024), d, s, bx, P128);
  }
  {
    cuuint64_t d[2] = {512, 512}, s[1] = {1024};
    cuuint32_t bx[2] = {64, 64};
    encode(fn, &m.w30, 2, (void*)(w + 30 * 262144), d, s, bx, P128);
  }
  cudaFuncSetAttribute(k1_main, cudaFuncAttributeMaxDynamicSharedMemorySize, SMEM_BYTES);
  k1_main<<<132, 512, SMEM_BYTES>>>((uint8_t*)xptr, fptr, (unsigned*)cptr, gamma, beta, m);
}
```

```cpp
#include <cuda_runtime.h>
#include <cuda_bf16.h>
#include <cuda.h>
#include <stdint.h>

namespace {

#define WFIRST 1
#define HOLD 0
#define YPIECE 1
#define NPR 1
#define P0M 1
#define P1M 0
constexpr int LOUT = 7985;
constexpr int MT = 50;
constexpr int NT = 160;
constexpr int XBLK = NT * 128;
constexpr int WBLK = 16384;
#define LW_ 4
#define XK_ 9
constexpr int LW = LW_;
constexpr int WR = 5;
constexpr int WCHUNK = 32 * 4 * WBLK;
constexpr int XPAGES = 20;
constexpr int NFL = 2;
constexpr int XKEEP = XK_;
constexpr int YSTEP = 2;
constexpr int YFLUSH = 17 + LW + 3 * YSTEP, YSEEN = YFLUSH > 27 ? YFLUSH : 27;

__device__ __align__(1024) uint8_t g_X[(XPAGES + 2) << 21];
__device__ __align__(1024) uint8_t g_W[(size_t)WR * WCHUNK];
__device__ __align__(1024) uint8_t g_Y[8ull * NT * 8192];
__device__ __align__(128) float g_E[16 * NT * 64];
__device__ unsigned long long g_part[128 * 128];
constexpr int C_FLAG = 0, C_LOADED = 36, C_REG = 68, C_EXIT = 69, C_E = 70, C_NUM = 71;
__device__ __align__(128) unsigned g_ctr[C_NUM * 32];
#define PROF_T(i)
#define PROF_C(i)
#define PROF_V(i, v)
#define PROF_W(acc, stmt) stmt

__device__ __align__(128) const uint32_t g_Fimg[2048] = {
 0x3f803f80,0x3f7d3f7f,0x3f783f7b,0x3f713f75,0x3f673f6d,0x3f5c3f62,0x3f4e3f55,0x3f3e3f46,0x3f2c3f35,0x3f183f22,0x3f043f0e,0x3edb3ef1,0x3eac3ec4,0x3e793e95,0x3e163e48,0x3d493dc9,
 0xbd490000,0xbe16bdc9,0xbe79be48,0xbeacbe95,0xbedbbec4,0xbf04bef1,0xbf18bf0e,0xbf2cbf22,0xbf3ebf35,0xbf4ebf46,0xbf5cbf55,0xbf67bf62,0xbf71bf6d,0xbf78bf75,0xbf7dbf7b,0xbf80bf7f,
 0x3e793ec4,0xbd493dc9,0xbeacbe48,0xbf18bef1,0x3f7d3f80,0x3f673f75,0x3f3e3f55,0x3f043f22,0xbf5cbf6d,0xbf2cbf46,0xbedbbf0e,0xbe16be95,0xbf4ebf35,0xbf71bf62,0xbf80bf7b,0xbf78bf7f,
 0x3f783f6d,0x3f803f7f,0x3f713f7b,0x3f4e3f62,0x3e160000,0x3edb3e95,0x3f2c3f0e,0x3f5c3f46,0xbf04bec4,0xbf3ebf22,0xbf67bf55,0xbf7dbf75,0x3f183f35,0x3eac3ef1,0x3d493e48,0xbe79bdc9,
 0xbf04bf35,0xbd49be95,0x3edb3e48,0x3f4e3f22,0x3f7d3f6d,0x3f713f7f,0x3f2c3f55,0x3e793ef1,0x3f783f80,0x3f3e3f62,0x3eac3f0e,0xbe163dc9,0xbf18bec4,0xbf67bf46,0xbf80bf7b,0xbf5cbf75,
 0x3f5c3f35,0x3f803f75,0x3f673f7b,0x3f183f46,0x3e163ec4,0xbeacbdc9,0xbf3ebf0e,0xbf78bf62,0xbe790000,0xbf2cbef1,0xbf71bf55,0xbf7dbf7f,0xbf4ebf6d,0xbedbbf22,0x3d49be48,0x3f043e95,
 0xbf2cbec4,0xbf7dbf62,0xbf5cbf7b,0xbeacbf22,0x3f673f35,0x3f783f7f,0x3f183f55,0xbd493e95,0xbf80bf6d,0xbf4ebf75,0xbe79bf0e,0x3edb3dc9,0x3f713f80,0x3f043f46,0xbe163e48,0xbf3ebef1,
 0x3f3e3f6d,0x3e163ef1,0xbf04be48,0xbf71bf46,0xbedbbf35,0x3e79bdc9,0x3f4e3f0e,0x3f803f75,0x3d493ec4,0xbf18be95,0xbf78bf55,0xbf67bf7f,0x3eac0000,0x3f5c3f22,0x3f7d3f7b,0x3f2c3f62,
 0xbedb0000,0xbf78bf46,0xbf4ebf7b,0xbd49bef1,0x3f3e3ec4,0x3f7d3f75,0x3f043f55,0xbeac3dc9,0xbf71bf35,0xbf5cbf7f,0xbe16bf0e,0x3f2c3e95,0x3f803f6d,0x3f183f62,0xbe793e48,0xbf67bf22,
 0x3f673f80,0x3e793f22,0xbf18be48,0xbf80bf62,0xbf2cbf6d,0x3e16be95,0x3f5c3f0e,0x3f713f7f,0x3eac3f35,0xbf04bdc9,0xbf7dbf55,0xbf3ebf75,0x3d49bec4,0x3f4e3ef1,0x3f783f7b,0x3edb3f46,
 0xbf7dbf6d,0xbeacbf46,0x3f2c3e48,0x3f783f75,0x3f040000,0x3f803f62,0x3edb3f55,0xbf18bdc9,0x3f4e3ec4,0x3f673f7f,0x3d493f0e,0xbf5cbef1,0x3e793f35,0xbf3ebe95,0xbf71bf7b,0xbe16bf22,
 0x3e16bec4,0x3f713f22,0x3f3e3f7b,0xbe793e95,0x3f5c3f80,0xbd493ef1,0xbf67bf0e,0xbf4ebf7f,0x3f183f6d,0xbedb3dc9,0xbf80bf55,0xbf04bf62,0xbf78bf35,0xbf2cbf75,0x3eacbe48,0x3f7d3f46,
 0x3f7d3f35,0x3edb3f62,0xbf3ebe48,0xbf5cbf7f,0x3e79bec4,0x3f803f46,0x3eac3f55,0xbf4ebe95,0xbf180000,0xbf71bf75,0x3d49bf0e,0x3f783f22,0x3f043f6d,0xbf2cbdc9,0xbf67bf7b,0x3e16bef1,
 0xbe16bf35,0x3f673ef1,0x3f2c3f7b,0xbf043dc9,0xbf78bf6d,0xbd49bf22,0x3f713f0e,0x3f183f75,0x3f4e3f80,0xbeac3e95,0xbf80bf55,0xbe79bf46,0x3f5c3ec4,0x3f3e3f7f,0xbedb3e48,0xbf7dbf62,
 0xbedbbf6d,0x3f5c3e95,0x3f183f7b,0xbf3ebdc9,0xbd49bf35,0x3f7d3f22,0x3e793f55,0xbf71bef1,0x3eacbec4,0x3f783f62,0xbe163f0e,0xbf80bf46,0x3f2c0000,0x3f4e3f7f,0xbf043e48,0xbf67bf75,
 0x3f673ec4,0x3f043f75,0xbf4ebe48,0xbf2cbf7f,0x3f803f35,0x3e163f46,0xbf78bf0e,0xbeacbf62,0x3f713f6d,0xbe793ef1,0xbf7dbf55,0x3d49bf22,0x3f3e3f80,0xbf183dc9,0xbf5cbf7b,0x3edbbe95,
 0xbd490000,0xbe16bdc9,0xbe79be48,0xbeacbe95,0xbedbbec4,0xbf04bef1,0xbf18bf0e,0xbf2cbf22,0xbf3ebf35,0xbf4ebf46,0xbf5cbf55,0xbf67bf62,0xbf71bf6d,0xbf78bf75,0xbf7dbf7b,0xbf80bf7f,
 0xbf80bf80,0xbf7dbf7f,0xbf78bf7b,0xbf71bf75,0xbf67bf6d,0xbf5cbf62,0xbf4ebf55,0xbf3ebf46,0xbf2cbf35,0xbf18bf22,0xbf04bf0e,0xbedbbef1,0xbeacbec4,0xbe79be95,0xbe16be48,0xbd49bdc9,
 0xbf78bf6d,0xbf80bf7f,0xbf71bf7b,0xbf4ebf62,0xbe160000,0xbedbbe95,0xbf2cbf0e,0xbf5cbf46,0x3f043ec4,0x3f3e3f22,0x3f673f55,0x3f7d3f75,0xbf18bf35,0xbeacbef1,0xbd49be48,0x3e793dc9,
 0x3e793ec4,0xbd493dc9,0xbeacbe48,0xbf18bef1,0x3f7d3f80,0x3f673f75,0x3f3e3f55,0x3f043f22,0xbf5cbf6d,0xbf2cbf46,0xbedbbf0e,0xbe16be95,0xbf4ebf35,0xbf71bf62,0xbf80bf7b,0xbf78bf7f,
 0x3f5c3f35,0x3f803f75,0x3f673f7b,0x3f183f46,0x3e163ec4,0xbeacbdc9,0xbf3ebf0e,0xbf78bf62,0xbe790000,0xbf2cbef1,0xbf71bf55,0xbf7dbf7f,0xbf4ebf6d,0xbedbbf22,0x3d49be48,0x3f043e95,
 0x3f043f35,0x3d493e95,0xbedbbe48,0xbf4ebf22,0xbf7dbf6d,0xbf71bf7f,0xbf2cbf55,0xbe79bef1,0xbf78bf80,0xbf3ebf62,0xbeacbf0e,0x3e16bdc9,0x3f183ec4,0x3f673f46,0x3f803f7b,0x3f5c3f75,
 0xbf3ebf6d,0xbe16bef1,0x3f043e48,0x3f713f46,0x3edb3f35,0xbe793dc9,0xbf4ebf0e,0xbf80bf75,0xbd49bec4,0x3f183e95,0x3f783f55,0x3f673f7f,0xbeac0000,0xbf5cbf22,0xbf7dbf7b,0xbf2cbf62,
 0xbf2cbec4,0xbf7dbf62,0xbf5cbf7b,0xbeacbf22,0x3f673f35,0x3f783f7f,0x3f183f55,0xbd493e95,0xbf80bf6d,0xbf4ebf75,0xbe79bf0e,0x3edb3dc9,0x3f713f80,0x3f043f46,0xbe163e48,0xbf3ebef1,
 0xbf67bf80,0xbe79bf22,0x3f183e48,0x3f803f62,0x3f2c3f6d,0xbe163e95,0xbf5cbf0e,0xbf71bf7f,0xbeacbf35,0x3f043dc9,0x3f7d3f55,0x3f3e3f75,0xbd493ec4,0xbf4ebef1,0xbf78bf7b,0xbedbbf46,
 0xbedb0000,0xbf78bf46,0xbf4ebf7b,0xbd49bef1,0x3f3e3ec4,0x3f7d3f75,0x3f043f55,0xbeac3dc9,0xbf71bf35,0xbf5cbf7f,0xbe16bf0e,0x3f2c3e95,0x3f803f6d,0x3f183f62,0xbe793e48,0xbf67bf22,
 0x3e16bec4,0x3f713f22,0x3f3e3f7b,0xbe793e95,0x3f5c3f80,0xbd493ef1,0xbf67bf0e,0xbf4ebf7f,0x3f183f6d,0xbedb3dc9,0xbf80bf55,0xbf04bf62,0xbf78bf35,0xbf2cbf75,0x3eacbe48,0x3f7d3f46,
 0x3f7d3f6d,0x3eac3f46,0xbf2cbe48,0xbf78bf75,0xbf040000,0xbf80bf62,0xbedbbf55,0x3f183dc9,0xbf4ebec4,0xbf67bf7f,0xbd49bf0e,0x3f5c3ef1,0xbe79bf35,0x3f3e3e95,0x3f713f7b,0x3e163f22,
 0x3e163f35,0xbf67bef1,0xbf2cbf7b,0x3f04bdc9,0x3f783f6d,0x3d493f22,0xbf71bf0e,0xbf18bf75,0xbf4ebf80,0x3eacbe95,0x3f803f55,0x3e793f46,0xbf5cbec4,0xbf3ebf7f,0x3edbbe48,0x3f7d3f62,
 0x3f7d3f35,0x3edb3f62,0xbf3ebe48,0xbf5cbf7f,0x3e79bec4,0x3f803f46,0x3eac3f55,0xbf4ebe95,0xbf180000,0xbf71bf75,0x3d49bf0e,0x3f783f22,0x3f043f6d,0xbf2cbdc9,0xbf67bf7b,0x3e16bef1,
 0x3f673ec4,0x3f043f75,0xbf4ebe48,0xbf2cbf7f,0x3f803f35,0x3e163f46,0xbf78bf0e,0xbeacbf62,0x3f713f6d,0xbe793ef1,0xbf7dbf55,0x3d49bf22,0x3f3e3f80,0xbf183dc9,0xbf5cbf7b,0x3edbbe95,
 0x3edb3f6d,0xbf5cbe95,0xbf18bf7b,0x3f3e3dc9,0x3d493f35,0xbf7dbf22,0xbe79bf55,0x3f713ef1,0xbeac3ec4,0xbf78bf62,0x3e16bf0e,0x3f803f46,0xbf2c0000,0xbf4ebf7f,0x3f04be48,0x3f673f75,
 0x3f2c3f80,0xbf4ebdc9,0xbf04bf7b,0x3f673e95,0x3eac3f6d,0xbf78bef1,0xbe16bf55,0x3f803f22,0xbd493f35,0xbf7dbf46,0x3e79bf0e,0x3f713f62,0xbedb3ec4,0xbf5cbf75,0x3f18be48,0x3f3e3f7f,
 0xbf3e0000,0xbf18bf7f,0x3f5c3e48,0x3edb3f75,0xbf71bec4,0xbe79bf62,0x3f7d3f0e,0x3d493f46,0xbf80bf35,0x3e16bf22,0x3f783f55,0xbeac3ef1,0xbf67bf6d,0x3f04be95,0x3f4e3f7b,0xbf2c3dc9,
 0xbf043ec4,0xbf2cbf7f,0x3f673e48,0x3e163f62,0x3f183f80,0xbf71be95,0xbd49bf55,0x3f783f46,0xbe79bf6d,0x3f803f22,0xbeac3f0e,0xbf4ebf75,0xbf7dbf35,0x3edbbef1,0x3f3e3f7b,0xbf5cbdc9,
 0x3f5c3f6d,0xbf3e3dc9,0xbedbbf7b,0x3f7d3ef1,0x3f4e0000,0x3eac3f75,0xbf80bf0e,0x3e79bf22,0xbf78bec4,0x3d49bf46,0x3f713f55,0xbf183e95,0xbe163f35,0xbf67bf62,0x3f2cbe48,0x3f043f7f,
 0x3e79bf35,0x3f3e3f75,0xbf71be48,0x3e16bf46,0x3f4e3f6d,0xbf67bdc9,0x3d49bf55,0x3f5c3f62,0x3f043f80,0xbf80bef1,0x3edbbf0e,0x3f183f7f,0xbf7dbec4,0x3eacbf22,0x3f2c3f7b,0xbf78be95,
 0x3f783f35,0xbf2c3e95,0xbeacbf7b,0x3f7d3f22,0xbf183ec4,0xbedbbf7f,0x3f803f0e,0xbf043ef1,0xbf5c0000,0xbd49bf62,0x3f673f55,0xbf4e3dc9,0xbe16bf6d,0x3f713f46,0xbf3e3e48,0xbe79bf75,
 0xbf80bec4,0x3f18bef1,0x3e793f7b,0xbf67bf46,0x3f713f35,0xbf5c3dc9,0x3e16bf55,0x3f2c3f75,0xbf3ebf6d,0x3f7d3e95,0xbf043f0e,0xbeacbf7f,0x3edb3f80,0xbf78bf22,0x3f4ebe48,0xbd493f62,
 0x3d493f6d,0xbf4ebf62,0x3f783e48,0xbedb3f22,0x3eacbf35,0x3f043f7f,0xbf7dbf0e,0x3f3ebe95,0xbf2c3ec4,0xbe16bf75,0x3f5c3f55,0xbf71bdc9,0x3f670000,0xbe793f46,0xbf18bf7b,0x3f803ef1,
 0xbf710000,0x3f04bf22,0x3e163f7b,0xbf3ebf62,0x3f803ec4,0xbf4e3e95,0x3e79bf55,0x3edb3f7f,0xbf67bf35,0x3f783dc9,0xbf183f0e,0xbd49bf75,0x3f2c3f6d,0xbf7dbef1,0x3f5cbe48,0xbeac3f46,
 0x3eac3f80,0xbf5cbf46,0x3f7d3e48,0xbf2c3ef1,0x3d49bf6d,0x3f183f75,0xbf78bf0e,0x3f67bdc9,0xbedb3f35,0xbe79bf7f,0x3f4e3f55,0xbf80be95,0x3f3ebec4,0xbe163f62,0xbf04bf7b,0x3f713f22,
 0xbf18bf6d,0x3f673f22,0xbf80be48,0x3f5cbe95,0x3f780000,0xbf3e3ef1,0x3eacbf55,0x3e163f7f,0x3f7d3ec4,0xbf713dc9,0x3f2cbf0e,0xbe793f62,0xbf043f35,0x3d49bf75,0x3edb3f7b,0xbf4ebf46,
 0x3f4ebec4,0xbedb3f46,0xbd49bf7b,0x3f043f75,0x3e793f80,0xbf2cbf62,0x3f713f0e,0xbf7dbdc9,0xbe163f6d,0xbeacbf7f,0x3f3e3f55,0xbf78bef1,0xbf5cbf35,0x3f803e95,0xbf673e48,0x3f18bf22,
 0x3f4e3f35,0xbf71bef1,0x3f803e48,0xbf783dc9,0x3f5cbec4,0xbf2c3f22,0x3edbbf55,0xbe163f75,0xbf7d0000,0x3f67be95,0xbf3e3f0e,0x3f04bf46,0xbe793f6d,0xbd49bf7f,0x3eac3f7b,0xbf18bf62,
 0x3f18bf35,0xbeac3f62,0x3d49bf7b,0x3e793f7f,0xbf04bf6d,0x3f3e3f46,0xbf67bf0e,0x3f7d3e95,0x3e163f80,0xbedbbf75,0x3f2c3f55,0xbf5cbf22,0x3f783ec4,0xbf80bdc9,0x3f71be48,0xbf4e3ef1,
 0x3eacbf6d,0xbe793f75,0x3e16bf7b,0xbd493f7f,0x3f2cbf35,0xbf183f46,0x3f04bf55,0xbedb3f62,0x3f67bec4,0xbf5c3ef1,0x3f4ebf0e,0xbf3e3f22,0x3f800000,0xbf7d3dc9,0x3f78be48,0xbf713e95,
 0x3f713ec4,0xbf78be95,0x3f7d3e48,0xbf80bdc9,0x3f3e3f35,0xbf4ebf22,0x3f5c3f0e,0xbf67bef1,0x3edb3f6d,0xbf04bf62,0x3f183f55,0xbf2cbf46,0x3d493f80,0xbe16bf7f,0x3e793f7b,0xbeacbf75,
 0xbf3e0000,0xbf18bf7f,0x3f5c3e48,0x3edb3f75,0xbf71bec4,0xbe79bf62,0x3f7d3f0e,0x3d493f46,0xbf80bf35,0x3e16bf22,0x3f783f55,0xbeac3ef1,0xbf67bf6d,0x3f04be95,0x3f4e3f7b,0xbf2c3dc9,
 0xbf2cbf80,0x3f4e3dc9,0x3f043f7b,0xbf67be95,0xbeacbf6d,0x3f783ef1,0x3e163f55,0xbf80bf22,0x3d49bf35,0x3f7d3f46,0xbe793f0e,0xbf71bf62,0x3edbbec4,0x3f5c3f75,0xbf183e48,0xbf3ebf7f,
 0xbf5cbf6d,0x3f3ebdc9,0x3edb3f7b,0xbf7dbef1,0xbf4e0000,0xbeacbf75,0x3f803f0e,0xbe793f22,0x3f783ec4,0xbd493f46,0xbf71bf55,0x3f18be95,0x3e16bf35,0x3f673f62,0xbf2c3e48,0xbf04bf7f,
 0xbf043ec4,0xbf2cbf7f,0x3f673e48,0x3e163f62,0x3f183f80,0xbf71be95,0xbd49bf55,0x3f783f46,0xbe79bf6d,0x3f803f22,0xbeac3f0e,0xbf4ebf75,0xbf7dbf35,0x3edbbef1,0x3f3e3f7b,0xbf5cbdc9,
 0x3f783f35,0xbf2c3e95,0xbeacbf7b,0x3f7d3f22,0xbf183ec4,0xbedbbf7f,0x3f803f0e,0xbf043ef1,0xbf5c0000,0xbd49bf62,0x3f673f55,0xbf4e3dc9,0xbe16bf6d,0x3f713f46,0xbf3e3e48,0xbe79bf75,
 0xbe793f35,0xbf3ebf75,0x3f713e48,0xbe163f46,0xbf4ebf6d,0x3f673dc9,0xbd493f55,0xbf5cbf62,0xbf04bf80,0x3f803ef1,0xbedb3f0e,0xbf18bf7f,0x3f7d3ec4,0xbeac3f22,0xbf2cbf7b,0x3f783e95,
 0xbd49bf6d,0x3f4e3f62,0xbf78be48,0x3edbbf22,0xbeac3f35,0xbf04bf7f,0x3f7d3f0e,0xbf3e3e95,0x3f2cbec4,0x3e163f75,0xbf5cbf55,0x3f713dc9,0xbf670000,0x3e79bf46,0x3f183f7b,0xbf80bef1,
 0xbf80bec4,0x3f18bef1,0x3e793f7b,0xbf67bf46,0x3f713f35,0xbf5c3dc9,0x3e16bf55,0x3f2c3f75,0xbf3ebf6d,0x3f7d3e95,0xbf043f0e,0xbeacbf7f,0x3edb3f80,0xbf78bf22,0x3f4ebe48,0xbd493f62,
 0xbeacbf80,0x3f5c3f46,0xbf7dbe48,0x3f2cbef1,0xbd493f6d,0xbf18bf75,0x3f783f0e,0xbf673dc9,0x3edbbf35,0x3e793f7f,0xbf4ebf55,0x3f803e95,0xbf3e3ec4,0x3e16bf62,0x3f043f7b,0xbf71bf22,
 0xbf710000,0x3f04bf22,0x3e163f7b,0xbf3ebf62,0x3f803ec4,0xbf4e3e95,0x3e79bf55,0x3edb3f7f,0xbf67bf35,0x3f783dc9,0xbf183f0e,0xbd49bf75,0x3f2c3f6d,0xbf7dbef1,0x3f5cbe48,0xbeac3f46,
 0x3f4ebec4,0xbedb3f46,0xbd49bf7b,0x3f043f75,0x3e793f80,0xbf2cbf62,0x3f713f0e,0xbf7dbdc9,0xbe163f6d,0xbeacbf7f,0x3f3e3f55,0xbf78bef1,0xbf5cbf35,0x3f803e95,0xbf673e48,0x3f18bf22,
 0x3f183f6d,0xbf67bf22,0x3f803e48,0xbf5c3e95,0xbf780000,0x3f3ebef1,0xbeac3f55,0xbe16bf7f,0xbf7dbec4,0x3f71bdc9,0xbf2c3f0e,0x3e79bf62,0x3f04bf35,0xbd493f75,0xbedbbf7b,0x3f4e3f46,
 0xbf183f35,0x3eacbf62,0xbd493f7b,0xbe79bf7f,0x3f043f6d,0xbf3ebf46,0x3f673f0e,0xbf7dbe95,0xbe16bf80,0x3edb3f75,0xbf2cbf55,0x3f5c3f22,0xbf78bec4,0x3f803dc9,0xbf713e48,0x3f4ebef1,
 0x3f4e3f35,0xbf71bef1,0x3f803e48,0xbf783dc9,0x3f5cbec4,0xbf2c3f22,0x3edbbf55,0xbe163f75,0xbf7d0000,0x3f67be95,0xbf3e3f0e,0x3f04bf46,0xbe793f6d,0xbd49bf7f,0x3eac3f7b,0xbf18bf62,
 0x3f713ec4,0xbf78be95,0x3f7d3e48,0xbf80bdc9,0x3f3e3f35,0xbf4ebf22,0x3f5c3f0e,0xbf67bef1,0x3edb3f6d,0xbf04bf62,0x3f183f55,0xbf2cbf46,0x3d493f80,0xbe16bf7f,0x3e793f7b,0xbeacbf75,
 0xbeac3f6d,0x3e79bf75,0xbe163f7b,0x3d49bf7f,0xbf2c3f35,0x3f18bf46,0xbf043f55,0x3edbbf62,0xbf673ec4,0x3f5cbef1,0xbf4e3f0e,0x3f3ebf22,0xbf800000,0x3f7dbdc9,0xbf783e48,0x3f71be95,
 0xbd493f80,0x3e16bf7f,0xbe793f7b,0x3eacbf75,0xbedb3f6d,0x3f04bf62,0xbf183f55,0x3f2cbf46,0xbf3e3f35,0x3f4ebf22,0xbf5c3f0e,0x3f67bef1,0xbf713ec4,0x3f78be95,0xbf7d3e48,0x3f80bdc9,
 0xbf800000,0x3f7d3dc9,0xbf78be48,0x3f713e95,0xbf67bec4,0x3f5c3ef1,0xbf4ebf0e,0x3f3e3f22,0xbf2cbf35,0x3f183f46,0xbf04bf55,0x3edb3f62,0xbeacbf6d,0x3e793f75,0xbe16bf7b,0x3d493f7f,
 0xbf783ec4,0x3f80bdc9,0xbf71be48,0x3f4e3ef1,0xbe163f80,0x3edbbf75,0xbf2c3f55,0x3f5cbf22,0x3f04bf6d,0xbf3e3f46,0x3f67bf0e,0xbf7d3e95,0xbf18bf35,0x3eac3f62,0xbd49bf7b,0xbe793f7f,
 0x3e793f6d,0x3d49bf7f,0xbeac3f7b,0x3f18bf62,0x3f7d0000,0xbf67be95,0x3f3e3f0e,0xbf04bf46,0xbf5cbec4,0x3f2c3f22,0xbedbbf55,0x3e163f75,0xbf4e3f35,0x3f71bef1,0xbf803e48,0x3f783dc9,
 0x3f5cbf35,0xbf803e95,0x3f673e48,0xbf18bf22,0x3e163f6d,0x3eacbf7f,0xbf3e3f55,0x3f78bef1,0xbe793f80,0x3f2cbf62,0xbf713f0e,0x3f7dbdc9,0xbf4ebec4,0x3edb3f46,0x3d49bf7b,0xbf043f75,
 0x3f043f35,0xbd49bf75,0xbedb3f7b,0x3f4ebf46,0xbf7d3ec4,0x3f713dc9,0xbf2cbf0e,0x3e793f62,0xbf780000,0x3f3e3ef1,0xbeacbf55,0xbe163f7f,0x3f18bf6d,0xbf673f22,0x3f80be48,0xbf5cbe95,
 0xbf3ebec4,0x3e163f62,0x3f04bf7b,0xbf713f22,0x3edb3f35,0x3e79bf7f,0xbf4e3f55,0x3f80be95,0xbd49bf6d,0xbf183f75,0x3f78bf0e,0xbf67bdc9,0xbeac3f80,0x3f5cbf46,0xbf7d3e48,0x3f2c3ef1,
 0xbf2c3f6d,0x3f7dbef1,0xbf5cbe48,0x3eac3f46,0x3f67bf35,0xbf783dc9,0x3f183f0e,0x3d49bf75,0xbf803ec4,0x3f4e3e95,0xbe79bf55,0xbedb3f7f,0x3f710000,0xbf04bf22,0xbe163f7b,0x3f3ebf62,
 0xbf670000,0x3e793f46,0x3f18bf7b,0xbf803ef1,0x3f2c3ec4,0x3e16bf75,0xbf5c3f55,0x3f71bdc9,0xbeacbf35,0xbf043f7f,0x3f7dbf0e,0xbf3ebe95,0xbd493f6d,0x3f4ebf62,0xbf783e48,0x3edb3f22,
 0xbedb3f80,0x3f78bf22,0xbf4ebe48,0x3d493f62,0x3f3ebf6d,0xbf7d3e95,0x3f043f0e,0x3eacbf7f,0xbf713f35,0x3f5c3dc9,0xbe16bf55,0xbf2c3f75,0x3f80bec4,0xbf18bef1,0xbe793f7b,0x3f67bf46,
 0x3e16bf6d,0xbf713f46,0x3f3e3e48,0x3e79bf75,0x3f5c0000,0x3d49bf62,0xbf673f55,0x3f4e3dc9,0x3f183ec4,0x3edbbf7f,0xbf803f0e,0x3f043ef1,0xbf783f35,0x3f2c3e95,0x3eacbf7b,0xbf7d3f22,
 0x3f7dbec4,0xbeacbf22,0xbf2c3f7b,0x3f78be95,0xbf043f80,0x3f80bef1,0xbedbbf0e,0xbf183f7f,0xbf4e3f6d,0x3f67bdc9,0xbd49bf55,0xbf5c3f62,0xbe79bf35,0xbf3e3f75,0x3f71be48,0xbe16bf46,
 0x3e163f35,0x3f67bf62,0xbf2cbe48,0xbf043f7f,0x3f78bec4,0xbd49bf46,0xbf713f55,0x3f183e95,0xbf4e0000,0xbeac3f75,0x3f80bf0e,0xbe79bf22,0xbf5c3f6d,0x3f3e3dc9,0x3edbbf7b,0xbf7d3ef1,
 0x3f7dbf35,0xbedbbef1,0xbf3e3f7b,0x3f5cbdc9,0x3e79bf6d,0xbf803f22,0x3eac3f0e,0x3f4ebf75,0xbf183f80,0x3f71be95,0x3d49bf55,0xbf783f46,0x3f043ec4,0x3f2cbf7f,0xbf673e48,0xbe163f62,
 0x3f67bf6d,0xbf04be95,0xbf4e3f7b,0x3f2c3dc9,0x3f80bf35,0xbe16bf22,0xbf783f55,0x3eac3ef1,0x3f71bec4,0x3e79bf62,0xbf7d3f0e,0xbd493f46,0x3f3e0000,0x3f18bf7f,0xbf5c3e48,0xbedb3f75,
 0x3edb3ec4,0x3f5cbf75,0xbf18be48,0xbf3e3f7f,0x3d493f35,0x3f7dbf46,0xbe79bf0e,0xbf713f62,0xbeac3f6d,0x3f78bef1,0x3e16bf55,0xbf803f22,0xbf2c3f80,0x3f4ebdc9,0x3f04bf7b,0xbf673e95,
 0xbf800000,0x3f7d3dc9,0xbf78be48,0x3f713e95,0xbf67bec4,0x3f5c3ef1,0xbf4ebf0e,0x3f3e3f22,0xbf2cbf35,0x3f183f46,0xbf04bf55,0x3edb3f62,0xbeacbf6d,0x3e793f75,0xbe16bf7b,0x3d493f7f,
 0x3d49bf80,0xbe163f7f,0x3e79bf7b,0xbeac3f75,0x3edbbf6d,0xbf043f62,0x3f18bf55,0xbf2c3f46,0x3f3ebf35,0xbf4e3f22,0x3f5cbf0e,0xbf673ef1,0x3f71bec4,0xbf783e95,0x3f7dbe48,0xbf803dc9,
 0xbe79bf6d,0xbd493f7f,0x3eacbf7b,0xbf183f62,0xbf7d0000,0x3f673e95,0xbf3ebf0e,0x3f043f46,0x3f5c3ec4,0xbf2cbf22,0x3edb3f55,0xbe16bf75,0x3f4ebf35,0xbf713ef1,0x3f80be48,0xbf78bdc9,
 0xbf783ec4,0x3f80bdc9,0xbf71be48,0x3f4e3ef1,0xbe163f80,0x3edbbf75,0xbf2c3f55,0x3f5cbf22,0x3f04bf6d,0xbf3e3f46,0x3f67bf0e,0xbf7d3e95,0xbf18bf35,0x3eac3f62,0xbd49bf7b,0xbe793f7f,
 0x3f043f35,0xbd49bf75,0xbedb3f7b,0x3f4ebf46,0xbf7d3ec4,0x3f713dc9,0xbf2cbf0e,0x3e793f62,0xbf780000,0x3f3e3ef1,0xbeacbf55,0xbe163f7f,0x3f18bf6d,0xbf673f22,0x3f80be48,0xbf5cbe95,
 0xbf5c3f35,0x3f80be95,0xbf67be48,0x3f183f22,0xbe16bf6d,0xbeac3f7f,0x3f3ebf55,0xbf783ef1,0x3e79bf80,0xbf2c3f62,0x3f71bf0e,0xbf7d3dc9,0x3f4e3ec4,0xbedbbf46,0xbd493f7b,0x3f04bf75,
 0x3f2cbf6d,0xbf7d3ef1,0x3f5c3e48,0xbeacbf46,0xbf673f35,0x3f78bdc9,0xbf18bf0e,0xbd493f75,0x3f80bec4,0xbf4ebe95,0x3e793f55,0x3edbbf7f,0xbf710000,0x3f043f22,0x3e16bf7b,0xbf3e3f62,
 0xbf3ebec4,0x3e163f62,0x3f04bf7b,0xbf713f22,0x3edb3f35,0x3e79bf7f,0xbf4e3f55,0x3f80be95,0xbd49bf6d,0xbf183f75,0x3f78bf0e,0xbf67bdc9,0xbeac3f80,0x3f5cbf46,0xbf7d3e48,0x3f2c3ef1,
 0x3edbbf80,0xbf783f22,0x3f4e3e48,0xbd49bf62,0xbf3e3f6d,0x3f7dbe95,0xbf04bf0e,0xbeac3f7f,0x3f71bf35,0xbf5cbdc9,0x3e163f55,0x3f2cbf75,0xbf803ec4,0x3f183ef1,0x3e79bf7b,0xbf673f46,
 0xbf670000,0x3e793f46,0x3f18bf7b,0xbf803ef1,0x3f2c3ec4,0x3e16bf75,0xbf5c3f55,0x3f71bdc9,0xbeacbf35,0xbf043f7f,0x3f7dbf0e,0xbf3ebe95,0xbd493f6d,0x3f4ebf62,0xbf783e48,0x3edb3f22,
 0x3f7dbec4,0xbeacbf22,0xbf2c3f7b,0x3f78be95,0xbf043f80,0x3f80bef1,0xbedbbf0e,0xbf183f7f,0xbf4e3f6d,0x3f67bdc9,0xbd49bf55,0xbf5c3f62,0xbe79bf35,0xbf3e3f75,0x3f71be48,0xbe16bf46,
 0xbe163f6d,0x3f71bf46,0xbf3ebe48,0xbe793f75,0xbf5c0000,0xbd493f62,0x3f67bf55,0xbf4ebdc9,0xbf18bec4,0xbedb3f7f,0x3f80bf0e,0xbf04bef1,0x3f78bf35,0xbf2cbe95,0xbeac3f7b,0x3f7dbf22,
 0xbf7d3f35,0x3edb3ef1,0x3f3ebf7b,0xbf5c3dc9,0xbe793f6d,0x3f80bf22,0xbeacbf0e,0xbf4e3f75,0x3f18bf80,0xbf713e95,0xbd493f55,0x3f78bf46,0xbf04bec4,0xbf2c3f7f,0x3f67be48,0x3e16bf62,
 0x3e163f35,0x3f67bf62,0xbf2cbe48,0xbf043f7f,0x3f78bec4,0xbd49bf46,0xbf713f55,0x3f183e95,0xbf4e0000,0xbeac3f75,0x3f80bf0e,0xbe79bf22,0xbf5c3f6d,0x3f3e3dc9,0x3edbbf7b,0xbf7d3ef1,
 0x3edb3ec4,0x3f5cbf75,0xbf18be48,0xbf3e3f7f,0x3d493f35,0x3f7dbf46,0xbe79bf0e,0xbf713f62,0xbeac3f6d,0x3f78bef1,0x3e16bf55,0xbf803f22,0xbf2c3f80,0x3f4ebdc9,0x3f04bf7b,0xbf673e95,
 0xbf673f6d,0x3f043e95,0x3f4ebf7b,0xbf2cbdc9,0xbf803f35,0x3e163f22,0x3f78bf55,0xbeacbef1,0xbf713ec4,0xbe793f62,0x3f7dbf0e,0x3d49bf46,0xbf3e0000,0xbf183f7f,0x3f5cbe48,0x3edbbf75,
 0xbf3e3f80,0x3f183dc9,0x3f5cbf7b,0xbedbbe95,0xbf713f6d,0x3e793ef1,0x3f7dbf55,0xbd49bf22,0xbf803f35,0xbe163f46,0x3f78bf0e,0x3eacbf62,0xbf673ec4,0xbf043f75,0x3f4ebe48,0x3f2cbf7f,
 0xbf2c0000,0xbf4e3f7f,0x3f043e48,0x3f67bf75,0xbeacbec4,0xbf783f62,0x3e163f0e,0x3f80bf46,0x3d49bf35,0xbf7d3f22,0xbe793f55,0x3f71bef1,0x3edbbf6d,0xbf5c3e95,0xbf183f7b,0x3f3ebdc9,
 0xbf5c3ec4,0xbf3e3f7f,0x3edb3e48,0x3f7dbf62,0xbf4e3f80,0x3eac3e95,0x3f80bf55,0x3e79bf46,0x3f78bf6d,0x3d49bf22,0xbf713f0e,0xbf183f75,0x3e16bf35,0xbf673ef1,0xbf2c3f7b,0x3f043dc9,
 0xbf043f6d,0x3f2cbdc9,0x3f67bf7b,0xbe16bef1,0x3f180000,0x3f71bf75,0xbd49bf0e,0xbf783f22,0xbe79bec4,0xbf803f46,0xbeac3f55,0x3f4ebe95,0xbf7d3f35,0xbedb3f62,0x3f3ebe48,0x3f5cbf7f,
 0x3f78bf35,0x3f2cbf75,0xbeacbe48,0xbf7d3f46,0xbf183f6d,0x3edb3dc9,0x3f80bf55,0x3f04bf62,0xbf5c3f80,0x3d493ef1,0x3f67bf0e,0x3f4ebf7f,0xbe16bec4,0xbf713f22,0xbf3e3f7b,0x3e793e95,
 0xbe793f35,0x3f3ebe95,0x3f71bf7b,0x3e16bf22,0xbf4e3ec4,0xbf673f7f,0xbd493f0e,0x3f5cbef1,0xbf040000,0xbf803f62,0xbedb3f55,0x3f18bdc9,0x3f7dbf6d,0x3eacbf46,0xbf2c3e48,0xbf783f75,
 0xbd49bec4,0xbf4e3ef1,0xbf783f7b,0xbedb3f46,0xbeac3f35,0x3f04bdc9,0x3f7dbf55,0x3f3ebf75,0x3f2cbf6d,0xbe16be95,0xbf5c3f0e,0xbf713f7f,0xbf673f80,0xbe793f22,0x3f18be48,0x3f80bf62,
 0xbf803f6d,0xbf183f62,0x3e793e48,0x3f67bf22,0x3f71bf35,0x3f5cbf7f,0x3e16bf0e,0xbf2c3e95,0xbf3e3ec4,0xbf7d3f75,0xbf043f55,0x3eac3dc9,0x3edb0000,0x3f78bf46,0x3f4ebf7b,0x3d49bef1,
 0xbeac0000,0xbf5c3f22,0xbf7d3f7b,0xbf2c3f62,0xbd493ec4,0x3f18be95,0x3f78bf55,0x3f67bf7f,0x3edbbf35,0xbe79bdc9,0xbf4e3f0e,0xbf803f75,0xbf3e3f6d,0xbe163ef1,0x3f04be48,0x3f71bf46,
 0xbf713f80,0xbf043f46,0x3e163e48,0x3f3ebef1,0x3f80bf6d,0x3f4ebf75,0x3e79bf0e,0xbedb3dc9,0xbf673f35,0xbf783f7f,0xbf183f55,0x3d493e95,0x3f2cbec4,0x3f7dbf62,0x3f5cbf7b,0x3eacbf22,
 0x3f4ebf6d,0x3edbbf22,0xbd49be48,0xbf043e95,0x3e790000,0x3f2cbef1,0x3f71bf55,0x3f7dbf7f,0xbe163ec4,0x3eacbdc9,0x3f3ebf0e,0x3f78bf62,0xbf5c3f35,0xbf803f75,0xbf673f7b,0xbf183f46,
 0x3f18bec4,0x3f67bf46,0x3f80bf7b,0x3f5cbf75,0xbf783f80,0xbf3e3f62,0xbeac3f0e,0x3e163dc9,0xbf7d3f6d,0xbf713f7f,0xbf2c3f55,0xbe793ef1,0x3f04bf35,0x3d49be95,0xbedb3e48,0xbf4e3f22,
 0xbf183f35,0xbeac3ef1,0xbd493e48,0x3e79bdc9,0x3f04bec4,0x3f3ebf22,0x3f67bf55,0x3f7dbf75,0xbe160000,0xbedb3e95,0xbf2c3f0e,0xbf5c3f46,0xbf783f6d,0xbf803f7f,0xbf713f7b,0xbf4e3f62,
 0x3f4ebf35,0x3f71bf62,0x3f80bf7b,0x3f78bf7f,0x3f5cbf6d,0x3f2cbf46,0x3edbbf0e,0x3e16be95,0xbf7d3f80,0xbf673f75,0xbf3e3f55,0xbf043f22,0xbe793ec4,0x3d493dc9,0x3eacbe48,0x3f18bef1,
 0x3f71bf6d,0x3f78bf75,0x3f7dbf7b,0x3f80bf7f,0x3f3ebf35,0x3f4ebf46,0x3f5cbf55,0x3f67bf62,0x3edbbec4,0x3f04bef1,0x3f18bf0e,0x3f2cbf22,0x3d490000,0x3e16bdc9,0x3e79be48,0x3eacbe95,
 0xbeac3ec4,0xbe793e95,0xbe163e48,0xbd493dc9,0xbf2c3f35,0xbf183f22,0xbf043f0e,0xbedb3ef1,0xbf673f6d,0xbf5c3f62,0xbf4e3f55,0xbf3e3f46,0xbf803f80,0xbf7d3f7f,0xbf783f7b,0xbf713f75,
 0xbf2c0000,0xbf4e3f7f,0x3f043e48,0x3f67bf75,0xbeacbec4,0xbf783f62,0x3e163f0e,0x3f80bf46,0x3d49bf35,0xbf7d3f22,0xbe793f55,0x3f71bef1,0x3edbbf6d,0xbf5c3e95,0xbf183f7b,0x3f3ebdc9,
 0x3f3ebf80,0xbf18bdc9,0xbf5c3f7b,0x3edb3e95,0x3f71bf6d,0xbe79bef1,0xbf7d3f55,0x3d493f22,0x3f80bf35,0x3e16bf46,0xbf783f0e,0xbeac3f62,0x3f67bec4,0x3f04bf75,0xbf4e3e48,0xbf2c3f7f,
 0x3f04bf6d,0xbf2c3dc9,0xbf673f7b,0x3e163ef1,0xbf180000,0xbf713f75,0x3d493f0e,0x3f78bf22,0x3e793ec4,0x3f80bf46,0x3eacbf55,0xbf4e3e95,0x3f7dbf35,0x3edbbf62,0xbf3e3e48,0xbf5c3f7f,
 0xbf5c3ec4,0xbf3e3f7f,0x3edb3e48,0x3f7dbf62,0xbf4e3f80,0x3eac3e95,0x3f80bf55,0x3e79bf46,0x3f78bf6d,0x3d49bf22,0xbf713f0e,0xbf183f75,0x3e16bf35,0xbf673ef1,0xbf2c3f7b,0x3f043dc9,
 0xbe793f35,0x3f3ebe95,0x3f71bf7b,0x3e16bf22,0xbf4e3ec4,0xbf673f7f,0xbd493f0e,0x3f5cbef1,0xbf040000,0xbf803f62,0xbedb3f55,0x3f18bdc9,0x3f7dbf6d,0x3eacbf46,0xbf2c3e48,0xbf783f75,
 0xbf783f35,0xbf2c3f75,0x3eac3e48,0x3f7dbf46,0x3f18bf6d,0xbedbbdc9,0xbf803f55,0xbf043f62,0x3f5cbf80,0xbd49bef1,0xbf673f0e,0xbf4e3f7f,0x3e163ec4,0x3f71bf22,0x3f3ebf7b,0xbe79be95,
 0x3f80bf6d,0x3f18bf62,0xbe79be48,0xbf673f22,0xbf713f35,0xbf5c3f7f,0xbe163f0e,0x3f2cbe95,0x3f3ebec4,0x3f7dbf75,0x3f04bf55,0xbeacbdc9,0xbedb0000,0xbf783f46,0xbf4e3f7b,0xbd493ef1,
 0xbd49bec4,0xbf4e3ef1,0xbf783f7b,0xbedb3f46,0xbeac3f35,0x3f04bdc9,0x3f7dbf55,0x3f3ebf75,0x3f2cbf6d,0xbe16be95,0xbf5c3f0e,0xbf713f7f,0xbf673f80,0xbe793f22,0x3f18be48,0x3f80bf62,
 0x3f71bf80,0x3f04bf46,0xbe16be48,0xbf3e3ef1,0xbf803f6d,0xbf4e3f75,0xbe793f0e,0x3edbbdc9,0x3f67bf35,0x3f78bf7f,0x3f18bf55,0xbd49be95,0xbf2c3ec4,0xbf7d3f62,0xbf5c3f7b,0xbeac3f22,
 0xbeac0000,0xbf5c3f22,0xbf7d3f7b,0xbf2c3f62,0xbd493ec4,0x3f18be95,0x3f78bf55,0x3f67bf7f,0x3edbbf35,0xbe79bdc9,0xbf4e3f0e,0xbf803f75,0xbf3e3f6d,0xbe163ef1,0x3f04be48,0x3f71bf46,
 0x3f18bec4,0x3f67bf46,0x3f80bf7b,0x3f5cbf75,0xbf783f80,0xbf3e3f62,0xbeac3f0e,0x3e163dc9,0xbf7d3f6d,0xbf713f7f,0xbf2c3f55,0xbe793ef1,0x3f04bf35,0x3d49be95,0xbedb3e48,0xbf4e3f22,
 0xbf4e3f6d,0xbedb3f22,0x3d493e48,0x3f04be95,0xbe790000,0xbf2c3ef1,0xbf713f55,0xbf7d3f7f,0x3e16bec4,0xbeac3dc9,0xbf3e3f0e,0xbf783f62,0x3f5cbf35,0x3f80bf75,0x3f67bf7b,0x3f18bf46,
 0xbf4e3f35,0xbf713f62,0xbf803f7b,0xbf783f7f,0xbf5c3f6d,0xbf2c3f46,0xbedb3f0e,0xbe163e95,0x3f7dbf80,0x3f67bf75,0x3f3ebf55,0x3f04bf22,0x3e79bec4,0xbd49bdc9,0xbeac3e48,0xbf183ef1,
 0xbf183f35,0xbeac3ef1,0xbd493e48,0x3e79bdc9,0x3f04bec4,0x3f3ebf22,0x3f67bf55,0x3f7dbf75,0xbe160000,0xbedb3e95,0xbf2c3f0e,0xbf5c3f46,0xbf783f6d,0xbf803f7f,0xbf713f7b,0xbf4e3f62,
 0xbeac3ec4,0xbe793e95,0xbe163e48,0xbd493dc9,0xbf2c3f35,0xbf183f22,0xbf043f0e,0xbedb3ef1,0xbf673f6d,0xbf5c3f62,0xbf4e3f55,0xbf3e3f46,0xbf803f80,0xbf7d3f7f,0xbf783f7b,0xbf713f75,
 0xbf713f6d,0xbf783f75,0xbf7d3f7b,0xbf803f7f,0xbf3e3f35,0xbf4e3f46,0xbf5c3f55,0xbf673f62,0xbedb3ec4,0xbf043ef1,0xbf183f0e,0xbf2c3f22,0xbd490000,0xbe163dc9,0xbe793e48,0xbeac3e95,
};
__device__ __align__(128) const uint32_t g_Gimg[1792] = {
 0x00003d00,0x00003d00,0x00003d00,0x00003d00,0x00003d00,0x00003d00,0x00003d00,0x00003d00,0x00003d00,0x00003d00,0x00003d00,0x00003d00,0x00003d00,0x00003d00,0x00003d00,0x00003d00,
 0x00003d00,0x00003d00,0x00003d00,0x00003d00,0x00003d00,0x00003d00,0x00003d00,0x00003d00,0x00003d00,0x00003d00,0x00003d00,0x00003d00,0x00003d00,0x00003d00,0x00003d00,0x00003d00,
 0xbc5b3ce7,0xbc843cdc,0xbc983cce,0xbcac3cbe,0xbac93d00,0xbb963cfd,0xbbf93cf8,0xbc2c3cf1,0xbcf13c2c,0xbcf83bf9,0xbcfd3b96,0xbd003ac9,0xbcbe3cac,0xbcce3c98,0xbcdc3c84,0xbce73c5b,
 0xbce7bc5b,0xbcdcbc84,0xbccebc98,0xbcbebcac,0xbd00bac9,0xbcfdbb96,0xbcf8bbf9,0xbcf1bc2c,0xbc2cbcf1,0xbbf9bcf8,0xbb96bcfd,0xbac9bd00,0xbcacbcbe,0xbc98bcce,0xbc84bcdc,0xbc5bbce7,
 0xbcffbb49,0xbcf5bc15,0xbce2bc71,0xbcc6bca2,0xbca2bcc6,0xbc71bce2,0xbc15bcf5,0xbb49bcff,0xbb493cff,0xbc153cf5,0xbc713ce2,0xbca23cc6,0xbcc63ca2,0xbce23c71,0xbcf53c15,0xbcff3b49,
 0x3cff3b49,0x3cf53c15,0x3ce23c71,0x3cc63ca2,0x3ca23cc6,0x3c713ce2,0x3c153cf5,0x3b493cff,0x3b49bcff,0x3c15bcf5,0x3c71bce2,0x3ca2bcc6,0x3cc6bca2,0x3ce2bc71,0x3cf5bc15,0x3cffbb49,
 0x3c84bcdc,0x3cbebcac,0x3ce7bc5b,0x3cfdbb96,0xbc98bcce,0xbc2cbcf1,0xbac9bd00,0x3bf9bcf8,0xbcf83bf9,0xbd00bac9,0xbcf1bc2c,0xbccebc98,0xbb963cfd,0xbc5b3ce7,0xbcac3cbe,0xbcdc3c84,
 0xbcdcbc84,0xbcacbcbe,0xbc5bbce7,0xbb96bcfd,0xbcce3c98,0xbcf13c2c,0xbd003ac9,0xbcf8bbf9,0x3bf93cf8,0xbac93d00,0xbc2c3cf1,0xbc983cce,0x3cfd3b96,0x3ce73c5b,0x3cbe3cac,0x3c843cdc,
 0xbbc83cfb,0xbc8e3cd5,0xbcd53c8e,0xbcfb3bc8,0xbcfbbbc8,0xbcd5bc8e,0xbc8ebcd5,0xbbc8bcfb,0x3bc8bcfb,0x3c8ebcd5,0x3cd5bc8e,0x3cfbbbc8,0x3cfb3bc8,0x3cd53c8e,0x3c8e3cd5,0x3bc83cfb,
 0xbbc83cfb,0xbc8e3cd5,0xbcd53c8e,0xbcfb3bc8,0xbcfbbbc8,0xbcd5bc8e,0xbc8ebcd5,0xbbc8bcfb,0x3bc8bcfb,0x3c8ebcd5,0x3cd5bc8e,0x3cfbbbc8,0x3cfb3bc8,0x3cd53c8e,0x3c8e3cd5,0x3bc83cfb,
 0x3c98bcce,0x3ce7bc5b,0x3d003ac9,0x3cdc3c84,0xbcf8bbf9,0xbcbebcac,0xbc2cbcf1,0x3b96bcfd,0xbcfd3b96,0xbcf1bc2c,0xbcacbcbe,0xbbf9bcf8,0x3c843cdc,0x3ac93d00,0xbc5b3ce7,0xbcce3c98,
 0xbccebc98,0xbc5bbce7,0x3ac9bd00,0x3c84bcdc,0xbbf93cf8,0xbcac3cbe,0xbcf13c2c,0xbcfdbb96,0x3b963cfd,0xbc2c3cf1,0xbcbe3cac,0xbcf83bf9,0x3cdcbc84,0x3d00bac9,0x3ce73c5b,0x3c983cce,
 0xbcf5bc15,0xbca2bcc6,0xbb49bcff,0x3c71bce2,0x3ce2bc71,0x3cff3b49,0x3cc63ca2,0x3c153cf5,0x3c15bcf5,0x3cc6bca2,0x3cffbb49,0x3ce23c71,0x3c713ce2,0xbb493cff,0xbca23cc6,0xbcf53c15,
 0x3cf53c15,0x3ca23cc6,0x3b493cff,0xbc713ce2,0xbce23c71,0xbcffbb49,0xbcc6bca2,0xbc15bcf5,0xbc153cf5,0xbcc63ca2,0xbcff3b49,0xbce2bc71,0xbc71bce2,0x3b49bcff,0x3ca2bcc6,0x3cf5bc15,
 0xbcac3cbe,0xbcfd3b96,0xbcdcbc84,0xbc2cbcf1,0x3ce7bc5b,0x3cf83bf9,0x3c983cce,0xbac93d00,0xbd003ac9,0xbccebc98,0xbbf9bcf8,0x3c5bbce7,0x3cf13c2c,0x3c843cdc,0xbb963cfd,0xbcbe3cac,
 0xbcbebcac,0xbb96bcfd,0x3c84bcdc,0x3cf1bc2c,0x3c5b3ce7,0xbbf93cf8,0xbcce3c98,0xbd00bac9,0xbac9bd00,0x3c98bcce,0x3cf8bbf9,0x3ce73c5b,0xbc2c3cf1,0xbcdc3c84,0xbcfdbb96,0xbcacbcbe,
 0xbc443ced,0xbced3c44,0xbcedbc44,0xbc44bced,0x3c44bced,0x3cedbc44,0x3ced3c44,0x3c443ced,0xbc443ced,0xbced3c44,0xbcedbc44,0xbc44bced,0x3c44bced,0x3cedbc44,0x3ced3c44,0x3c443ced,
 0xbc443ced,0xbced3c44,0xbcedbc44,0xbc44bced,0x3c44bced,0x3cedbc44,0x3ced3c44,0x3c443ced,0xbc443ced,0xbced3c44,0xbcedbc44,0xbc44bced,0x3c44bced,0x3cedbc44,0x3ced3c44,0x3c443ced,
 0x3cbebcac,0x3cfd3b96,0x3c843cdc,0xbc2c3cf1,0xbc5b3ce7,0xbcf83bf9,0xbccebc98,0xbac9bd00,0x3d003ac9,0x3c983cce,0xbbf93cf8,0xbce73c5b,0xbcf13c2c,0xbcdcbc84,0xbb96bcfd,0x3cacbcbe,
 0x3cac3cbe,0xbb963cfd,0xbcdc3c84,0xbcf1bc2c,0xbce7bc5b,0xbbf9bcf8,0x3c98bcce,0x3d00bac9,0xbac93d00,0xbcce3c98,0xbcf8bbf9,0xbc5bbce7,0xbc2cbcf1,0x3c84bcdc,0x3cfdbb96,0x3cbe3cac,
 0xbce2bc71,0xbb49bcff,0x3cc6bca2,0x3cf53c15,0x3c153cf5,0xbca23cc6,0xbcffbb49,0xbc71bce2,0xbc713ce2,0xbcff3b49,0xbca2bcc6,0x3c15bcf5,0x3cf5bc15,0x3cc63ca2,0xbb493cff,0xbce23c71,
 0x3ce23c71,0x3b493cff,0xbcc63ca2,0xbcf5bc15,0xbc15bcf5,0x3ca2bcc6,0x3cff3b49,0x3c713ce2,0x3c71bce2,0x3cffbb49,0x3ca23cc6,0xbc153cf5,0xbcf53c15,0xbcc6bca2,0x3b49bcff,0x3ce2bc71,
 0xbcce3c98,0xbce7bc5b,0xbac9bd00,0x3cdcbc84,0xbbf9bcf8,0x3cbebcac,0x3cf13c2c,0x3b963cfd,0x3cfd3b96,0x3c2c3cf1,0xbcac3cbe,0xbcf8bbf9,0xbc843cdc,0xbd00bac9,0xbc5bbce7,0x3c98bcce,
 0x3c983cce,0xbc5b3ce7,0xbd003ac9,0xbc84bcdc,0xbcf83bf9,0xbcacbcbe,0x3c2cbcf1,0x3cfdbb96,0x3b96bcfd,0x3cf1bc2c,0x3cbe3cac,0xbbf93cf8,0x3cdc3c84,0xbac93d00,0xbce73c5b,0xbccebc98,
 0xbc8e3cd5,0xbcfbbbc8,0xbbc8bcfb,0x3cd5bc8e,0x3cd53c8e,0xbbc83cfb,0xbcfb3bc8,0xbc8ebcd5,0x3c8ebcd5,0x3cfb3bc8,0x3bc83cfb,0xbcd53c8e,0xbcd5bc8e,0x3bc8bcfb,0x3cfbbbc8,0x3c8e3cd5,
 0xbc8e3cd5,0xbcfbbbc8,0xbbc8bcfb,0x3cd5bc8e,0x3cd53c8e,0xbbc83cfb,0xbcfb3bc8,0xbc8ebcd5,0x3c8ebcd5,0x3cfb3bc8,0x3bc83cfb,0xbcd53c8e,0xbcd5bc8e,0x3bc8bcfb,0x3cfbbbc8,0x3c8e3cd5,
 0xbcdc3c84,0xbcbebcac,0x3c5bbce7,0x3cfd3b96,0xbccebc98,0x3c2cbcf1,0x3d003ac9,0x3bf93cf8,0x3cf83bf9,0x3ac93d00,0xbcf13c2c,0xbc98bcce,0x3b963cfd,0xbce73c5b,0xbcacbcbe,0x3c84bcdc,
 0x3c843cdc,0xbcac3cbe,0xbce7bc5b,0x3b96bcfd,0xbc983cce,0xbcf1bc2c,0x3ac9bd00,0x3cf8bbf9,0x3bf9bcf8,0x3d00bac9,0x3c2c3cf1,0xbcce3c98,0x3cfdbb96,0x3c5b3ce7,0xbcbe3cac,0xbcdcbc84,
 0xbcc6bca2,0x3c71bce2,0x3cf53c15,0xbb493cff,0xbcff3b49,0xbc15bcf5,0x3ce2bc71,0x3ca23cc6,0x3ca2bcc6,0x3ce23c71,0xbc153cf5,0xbcffbb49,0xbb49bcff,0x3cf5bc15,0x3c713ce2,0xbcc63ca2,
 0x3cc63ca2,0xbc713ce2,0xbcf5bc15,0x3b49bcff,0x3cffbb49,0x3c153cf5,0xbce23c71,0xbca2bcc6,0xbca23cc6,0xbce2bc71,0x3c15bcf5,0x3cff3b49,0x3b493cff,0xbcf53c15,0xbc71bce2,0x3cc6bca2,
 0x3ce7bc5b,0x3c843cdc,0xbcce3c98,0xbcacbcbe,0x3d00bac9,0x3b963cfd,0xbcf83bf9,0xbc2cbcf1,0x3cf13c2c,0xbbf93cf8,0xbcfdbb96,0x3ac9bd00,0x3cbe3cac,0xbc983cce,0xbcdcbc84,0x3c5bbce7,
 0x3c5b3ce7,0xbcdc3c84,0xbc98bcce,0x3cbebcac,0x3ac93d00,0xbcfd3b96,0xbbf9bcf8,0x3cf1bc2c,0xbc2c3cf1,0xbcf8bbf9,0x3b96bcfd,0x3d003ac9,0xbcac3cbe,0xbccebc98,0x3c84bcdc,0x3ce73c5b,
 0xbcb53cb5,0xbcb5bcb5,0x3cb5bcb5,0x3cb53cb5,0xbcb53cb5,0xbcb5bcb5,0x3cb5bcb5,0x3cb53cb5,0xbcb53cb5,0xbcb5bcb5,0x3cb5bcb5,0x3cb53cb5,0xbcb53cb5,0xbcb5bcb5,0x3cb5bcb5,0x3cb53cb5,
 0xbcb53cb5,0xbcb5bcb5,0x3cb5bcb5,0x3cb53cb5,0xbcb53cb5,0xbcb5bcb5,0x3cb5bcb5,0x3cb53cb5,0xbcb53cb5,0xbcb5bcb5,0x3cb5bcb5,0x3cb53cb5,0xbcb53cb5,0xbcb5bcb5,0x3cb5bcb5,0x3cb53cb5,
 0xbcf13c2c,0xbbf9bcf8,0x3cfdbb96,0x3ac93d00,0xbcbe3cac,0xbc98bcce,0x3cdcbc84,0x3c5b3ce7,0xbce7bc5b,0x3c84bcdc,0x3cce3c98,0xbcac3cbe,0xbd00bac9,0x3b96bcfd,0x3cf83bf9,0xbc2c3cf1,
 0xbc2cbcf1,0x3cf8bbf9,0x3b963cfd,0xbd003ac9,0xbcacbcbe,0x3ccebc98,0x3c843cdc,0xbce73c5b,0x3c5bbce7,0x3cdc3c84,0xbc983cce,0xbcbebcac,0x3ac9bd00,0x3cfd3b96,0xbbf93cf8,0xbcf1bc2c,
 0xbca2bcc6,0x3ce2bc71,0x3c153cf5,0xbcff3b49,0x3b49bcff,0x3cf53c15,0xbc713ce2,0xbcc6bca2,0xbcc63ca2,0xbc71bce2,0x3cf5bc15,0x3b493cff,0xbcffbb49,0x3c15bcf5,0x3ce23c71,0xbca23cc6,
 0x3ca23cc6,0xbce23c71,0xbc15bcf5,0x3cffbb49,0xbb493cff,0xbcf5bc15,0x3c71bce2,0x3cc63ca2,0x3cc6bca2,0x3c713ce2,0xbcf53c15,0xbb49bcff,0x3cff3b49,0xbc153cf5,0xbce2bc71,0x3ca2bcc6,
 0x3cf8bbf9,0xbac93d00,0xbcf1bc2c,0x3c98bcce,0x3b96bcfd,0x3ce73c5b,0xbcac3cbe,0xbc84bcdc,0xbcdcbc84,0x3cbebcac,0x3c5b3ce7,0xbcfd3b96,0xbcce3c98,0xbc2cbcf1,0x3d00bac9,0xbbf93cf8,
 0xbbf9bcf8,0x3d003ac9,0xbc2c3cf1,0xbccebc98,0xbcfdbb96,0x3c5bbce7,0x3cbe3cac,0xbcdc3c84,0xbc843cdc,0xbcacbcbe,0x3ce7bc5b,0x3b963cfd,0x3c983cce,0xbcf13c2c,0xbac9bd00,0x3cf83bf9,
 0xbcd53c8e,0xbbc8bcfb,0x3cfb3bc8,0xbc8e3cd5,0xbc8ebcd5,0x3cfbbbc8,0xbbc83cfb,0xbcd5bc8e,0x3cd5bc8e,0x3bc83cfb,0xbcfbbbc8,0x3c8ebcd5,0x3c8e3cd5,0xbcfb3bc8,0x3bc8bcfb,0x3cd53c8e,
 0xbcd53c8e,0xbbc8bcfb,0x3cfb3bc8,0xbc8e3cd5,0xbc8ebcd5,0x3cfbbbc8,0xbbc83cfb,0xbcd5bc8e,0x3cd5bc8e,0x3bc83cfb,0xbcfbbbc8,0x3c8ebcd5,0x3c8e3cd5,0xbcfb3bc8,0x3bc8bcfb,0x3cd53c8e,
 0x3cfdbb96,0xbc2c3cf1,0xbcacbcbe,0x3cf8bbf9,0xbc84bcdc,0x3d00bac9,0xbc5b3ce7,0xbc98bcce,0xbccebc98,0x3ce7bc5b,0xbac93d00,0xbcdcbc84,0xbbf93cf8,0xbcbebcac,0x3cf1bc2c,0xbb963cfd,
 0xbb96bcfd,0x3cf13c2c,0xbcbe3cac,0xbbf9bcf8,0xbcdc3c84,0xbac9bd00,0x3ce73c5b,0xbcce3c98,0xbc983cce,0xbc5bbce7,0x3d003ac9,0xbc843cdc,0x3cf83bf9,0xbcac3cbe,0xbc2cbcf1,0x3cfd3b96,
 0xbc71bce2,0x3cff3b49,0xbca23cc6,0xbc15bcf5,0x3cf53c15,0xbcc63ca2,0xbb49bcff,0x3ce23c71,0x3ce2bc71,0xbb493cff,0xbcc6bca2,0x3cf5bc15,0xbc153cf5,0xbca2bcc6,0x3cffbb49,0xbc713ce2,
 0x3c713ce2,0xbcffbb49,0x3ca2bcc6,0x3c153cf5,0xbcf5bc15,0x3cc6bca2,0x3b493cff,0xbce2bc71,0xbce23c71,0x3b49bcff,0x3cc63ca2,0xbcf53c15,0x3c15bcf5,0x3ca23cc6,0xbcff3b49,0x3c71bce2,
 0xbd003ac9,0x3c98bcce,0x3bf93cf8,0xbce7bc5b,0x3cf13c2c,0xbcdc3c84,0x3b96bcfd,0x3cac3cbe,0xbcbebcac,0x3cfdbb96,0xbc843cdc,0xbc2cbcf1,0x3c5b3ce7,0xbcf8bbf9,0x3ccebc98,0xbac93d00,
 0xbac9bd00,0x3cce3c98,0xbcf83bf9,0x3c5bbce7,0xbc2c3cf1,0xbc84bcdc,0x3cfd3b96,0xbcbe3cac,0x3cacbcbe,0x3b963cfd,0xbcdcbc84,0x3cf1bc2c,0xbce73c5b,0x3bf9bcf8,0x3c983cce,0xbd00bac9,
 0xbced3c44,0x3c44bced,0x3c443ced,0xbcedbc44,0x3cedbc44,0xbc443ced,0xbc44bced,0x3ced3c44,0xbced3c44,0x3c44bced,0x3c443ced,0xbcedbc44,0x3cedbc44,0xbc443ced,0xbc44bced,0x3ced3c44,
 0xbced3c44,0x3c44bced,0x3c443ced,0xbcedbc44,0x3cedbc44,0xbc443ced,0xbc44bced,0x3ced3c44,0xbced3c44,0x3c44bced,0x3c443ced,0xbcedbc44,0x3cedbc44,0xbc443ced,0xbc44bced,0x3ced3c44,
 0x3d003ac9,0xbcce3c98,0x3bf9bcf8,0x3c5b3ce7,0xbcf13c2c,0x3c84bcdc,0x3b963cfd,0xbcbebcac,0x3cac3cbe,0xbcfdbb96,0x3cdcbc84,0xbc2c3cf1,0xbce7bc5b,0x3cf8bbf9,0xbc983cce,0xbac9bd00,
 0xbac93d00,0xbc98bcce,0x3cf83bf9,0xbce73c5b,0xbc2cbcf1,0x3cdc3c84,0xbcfd3b96,0x3cacbcbe,0xbcbe3cac,0x3b96bcfd,0x3c843cdc,0xbcf1bc2c,0x3c5bbce7,0x3bf93cf8,0xbccebc98,0x3d00bac9,
 0xbc15bcf5,0x3cc63ca2,0xbcffbb49,0x3ce2bc71,0xbc713ce2,0xbb49bcff,0x3ca23cc6,0xbcf5bc15,0xbcf53c15,0x3ca2bcc6,0xbb493cff,0xbc71bce2,0x3ce23c71,0xbcff3b49,0x3cc6bca2,0xbc153cf5,
 0x3c153cf5,0xbcc6bca2,0x3cff3b49,0xbce23c71,0x3c71bce2,0x3b493cff,0xbca2bcc6,0x3cf53c15,0x3cf5bc15,0xbca23cc6,0x3b49bcff,0x3c713ce2,0xbce2bc71,0x3cffbb49,0xbcc63ca2,0x3c15bcf5,
 0xbcfdbb96,0x3cf1bc2c,0xbcac3cbe,0x3bf9bcf8,0x3c84bcdc,0xbac93d00,0xbc5bbce7,0x3cce3c98,0x3c983cce,0xbce7bc5b,0x3d00bac9,0xbcdc3c84,0xbcf83bf9,0x3cbebcac,0xbc2c3cf1,0xbb96bcfd,
 0xbb963cfd,0xbc2cbcf1,0x3cbe3cac,0xbcf8bbf9,0xbcdcbc84,0x3d003ac9,0xbce73c5b,0x3c98bcce,0x3ccebc98,0xbc5b3ce7,0xbac9bd00,0x3c843cdc,0x3bf93cf8,0xbcacbcbe,0x3cf13c2c,0xbcfd3b96,
 0xbcfb3bc8,0x3cd5bc8e,0xbc8e3cd5,0x3bc8bcfb,0x3bc83cfb,0xbc8ebcd5,0x3cd53c8e,0xbcfbbbc8,0x3cfbbbc8,0xbcd53c8e,0x3c8ebcd5,0xbbc83cfb,0xbbc8bcfb,0x3c8e3cd5,0xbcd5bc8e,0x3cfb3bc8,
 0xbcfb3bc8,0x3cd5bc8e,0xbc8e3cd5,0x3bc8bcfb,0x3bc83cfb,0xbc8ebcd5,0x3cd53c8e,0xbcfbbbc8,0x3cfbbbc8,0xbcd53c8e,0x3c8ebcd5,0xbbc83cfb,0xbbc8bcfb,0x3c8e3cd5,0xbcd5bc8e,0x3cfb3bc8,
 0xbcf8bbf9,0x3d00bac9,0xbcf13c2c,0x3ccebc98,0xbb96bcfd,0x3c5b3ce7,0xbcacbcbe,0x3cdc3c84,0x3c843cdc,0xbcbebcac,0x3ce73c5b,0xbcfdbb96,0xbc983cce,0x3c2cbcf1,0xbac93d00,0xbbf9bcf8,
 0xbbf93cf8,0xbac9bd00,0x3c2c3cf1,0xbc98bcce,0xbcfd3b96,0x3ce7bc5b,0xbcbe3cac,0x3c84bcdc,0x3cdcbc84,0xbcac3cbe,0x3c5bbce7,0xbb963cfd,0x3cce3c98,0xbcf1bc2c,0x3d003ac9,0xbcf83bf9,
 0xbb49bcff,0x3c153cf5,0xbc71bce2,0x3ca23cc6,0xbcc6bca2,0x3ce23c71,0xbcf5bc15,0x3cff3b49,0x3cffbb49,0xbcf53c15,0x3ce2bc71,0xbcc63ca2,0x3ca2bcc6,0xbc713ce2,0x3c15bcf5,0xbb493cff,
 0x3b493cff,0xbc15bcf5,0x3c713ce2,0xbca2bcc6,0x3cc63ca2,0xbce2bc71,0x3cf53c15,0xbcffbb49,0xbcff3b49,0x3cf5bc15,0xbce23c71,0x3cc6bca2,0xbca23cc6,0x3c71bce2,0xbc153cf5,0x3b49bcff,
 0x3cf13c2c,0xbcf8bbf9,0x3cfd3b96,0xbd00bac9,0x3cbe3cac,0xbccebc98,0x3cdc3c84,0xbce7bc5b,0x3c5b3ce7,0xbc84bcdc,0x3c983cce,0xbcacbcbe,0x3ac93d00,0xbb96bcfd,0x3bf93cf8,0xbc2cbcf1,
 0xbc2c3cf1,0x3bf9bcf8,0xbb963cfd,0x3ac9bd00,0xbcac3cbe,0x3c98bcce,0xbc843cdc,0x3c5bbce7,0xbce73c5b,0x3cdcbc84,0xbcce3c98,0x3cbebcac,0xbd003ac9,0x3cfdbb96,0xbcf83bf9,0x3cf1bc2c,
 0xbd000000,0x3d000000,0xbd000000,0x3d000000,0xbd000000,0x3d000000,0xbd000000,0x3d000000,0xbd000000,0x3d000000,0xbd000000,0x3d000000,0xbd000000,0x3d000000,0xbd000000,0x3d000000,
 0xbd000000,0x3d000000,0xbd000000,0x3d000000,0xbd000000,0x3d000000,0xbd000000,0x3d000000,0xbd000000,0x3d000000,0xbd000000,0x3d000000,0xbd000000,0x3d000000,0xbd000000,0x3d000000,
 0xbce7bc5b,0x3cdc3c84,0xbccebc98,0x3cbe3cac,0xbd00bac9,0x3cfd3b96,0xbcf8bbf9,0x3cf13c2c,0xbc2cbcf1,0x3bf93cf8,0xbb96bcfd,0x3ac93d00,0xbcacbcbe,0x3c983cce,0xbc84bcdc,0x3c5b3ce7,
 0x3c5bbce7,0xbc843cdc,0x3c98bcce,0xbcac3cbe,0x3ac9bd00,0xbb963cfd,0x3bf9bcf8,0xbc2c3cf1,0x3cf1bc2c,0xbcf83bf9,0x3cfdbb96,0xbd003ac9,0x3cbebcac,0xbcce3c98,0x3cdcbc84,0xbce73c5b,
 0x3b49bcff,0xbc153cf5,0x3c71bce2,0xbca23cc6,0x3cc6bca2,0xbce23c71,0x3cf5bc15,0xbcff3b49,0xbcffbb49,0x3cf53c15,0xbce2bc71,0x3cc63ca2,0xbca2bcc6,0x3c713ce2,0xbc15bcf5,0x3b493cff,
 0xbb493cff,0x3c15bcf5,0xbc713ce2,0x3ca2bcc6,0xbcc63ca2,0x3ce2bc71,0xbcf53c15,0x3cffbb49,0x3cff3b49,0xbcf5bc15,0x3ce23c71,0xbcc6bca2,0x3ca23cc6,0xbc71bce2,0x3c153cf5,0xbb49bcff,
 0x3cdc3c84,0xbcacbcbe,0x3c5b3ce7,0xbb96bcfd,0x3ccebc98,0xbcf13c2c,0x3d00bac9,0xbcf8bbf9,0xbbf9bcf8,0xbac93d00,0x3c2cbcf1,0xbc983cce,0xbcfdbb96,0x3ce73c5b,0xbcbebcac,0x3c843cdc,
 0x3c84bcdc,0xbcbe3cac,0x3ce7bc5b,0xbcfd3b96,0xbc98bcce,0x3c2c3cf1,0xbac9bd00,0xbbf93cf8,0xbcf83bf9,0x3d003ac9,0xbcf1bc2c,0x3cce3c98,0xbb963cfd,0x3c5bbce7,0xbcac3cbe,0x3cdcbc84,
 0xbcfbbbc8,0x3cd53c8e,0xbc8ebcd5,0x3bc83cfb,0x3bc8bcfb,0xbc8e3cd5,0x3cd5bc8e,0xbcfb3bc8,0x3cfb3bc8,0xbcd5bc8e,0x3c8e3cd5,0xbbc8bcfb,0xbbc83cfb,0x3c8ebcd5,0xbcd53c8e,0x3cfbbbc8,
 0xbcfbbbc8,0x3cd53c8e,0xbc8ebcd5,0x3bc83cfb,0x3bc8bcfb,0xbc8e3cd5,0x3cd5bc8e,0xbcfb3bc8,0x3cfb3bc8,0xbcd5bc8e,0x3c8e3cd5,0xbbc8bcfb,0xbbc83cfb,0x3c8ebcd5,0xbcd53c8e,0x3cfbbbc8,
 0x3cce3c98,0xbc5bbce7,0xbac93d00,0x3c84bcdc,0x3bf9bcf8,0xbcac3cbe,0x3cf1bc2c,0xbcfdbb96,0xbb96bcfd,0xbc2c3cf1,0x3cbebcac,0xbcf83bf9,0xbcdc3c84,0x3d00bac9,0xbce7bc5b,0x3c983cce,
 0x3c98bcce,0xbce73c5b,0x3d003ac9,0xbcdcbc84,0xbcf8bbf9,0x3cbe3cac,0xbc2cbcf1,0xbb963cfd,0xbcfd3b96,0x3cf13c2c,0xbcacbcbe,0x3bf93cf8,0x3c843cdc,0xbac9bd00,0xbc5b3ce7,0x3ccebc98,
 0x3c15bcf5,0xbcc63ca2,0x3cffbb49,0xbce2bc71,0x3c713ce2,0x3b49bcff,0xbca23cc6,0x3cf5bc15,0x3cf53c15,0xbca2bcc6,0x3b493cff,0x3c71bce2,0xbce23c71,0x3cff3b49,0xbcc6bca2,0x3c153cf5,
 0xbc153cf5,0x3cc6bca2,0xbcff3b49,0x3ce23c71,0xbc71bce2,0xbb493cff,0x3ca2bcc6,0xbcf53c15,0xbcf5bc15,0x3ca23cc6,0xbb49bcff,0xbc713ce2,0x3ce2bc71,0xbcffbb49,0x3cc63ca2,0xbc15bcf5,
 0xbcbebcac,0x3b963cfd,0x3c84bcdc,0xbcf13c2c,0x3c5b3ce7,0x3bf9bcf8,0xbcce3c98,0x3d003ac9,0xbac9bd00,0xbc983cce,0x3cf8bbf9,0xbce7bc5b,0xbc2c3cf1,0x3cdcbc84,0xbcfdbb96,0x3cac3cbe,
 0x3cacbcbe,0xbcfd3b96,0x3cdc3c84,0xbc2cbcf1,0xbce73c5b,0x3cf83bf9,0xbc98bcce,0xbac93d00,0x3d00bac9,0xbccebc98,0x3bf93cf8,0x3c5bbce7,0xbcf1bc2c,0x3c843cdc,0x3b96bcfd,0xbcbe3cac,
 0xbcedbc44,0x3c443ced,0x3c44bced,0xbced3c44,0x3ced3c44,0xbc44bced,0xbc443ced,0x3cedbc44,0xbcedbc44,0x3c443ced,0x3c44bced,0xbced3c44,0x3ced3c44,0xbc44bced,0xbc443ced,0x3cedbc44,
 0xbcedbc44,0x3c443ced,0x3c44bced,0xbced3c44,0x3ced3c44,0xbc44bced,0xbc443ced,0x3cedbc44,0xbcedbc44,0x3c443ced,0x3c44bced,0xbced3c44,0x3ced3c44,0xbc44bced,0xbc443ced,0x3cedbc44,
 0x3cac3cbe,0x3b96bcfd,0xbcdc3c84,0x3cf13c2c,0xbce7bc5b,0x3bf93cf8,0x3c98bcce,0xbd003ac9,0xbac93d00,0x3ccebc98,0xbcf8bbf9,0x3c5b3ce7,0xbc2cbcf1,0xbc843cdc,0x3cfdbb96,0xbcbebcac,
 0xbcbe3cac,0x3cfd3b96,0xbc84bcdc,0xbc2c3cf1,0x3c5bbce7,0xbcf83bf9,0x3cce3c98,0xbac9bd00,0xbd00bac9,0x3c983cce,0x3bf9bcf8,0xbce73c5b,0x3cf1bc2c,0xbcdcbc84,0x3b963cfd,0x3cacbcbe,
 0x3c71bce2,0xbcff3b49,0x3ca23cc6,0x3c15bcf5,0xbcf53c15,0x3cc63ca2,0x3b49bcff,0xbce23c71,0xbce2bc71,0x3b493cff,0x3cc6bca2,0xbcf5bc15,0x3c153cf5,0x3ca2bcc6,0xbcffbb49,0x3c713ce2,
 0xbc713ce2,0x3cffbb49,0xbca2bcc6,0xbc153cf5,0x3cf5bc15,0xbcc6bca2,0xbb493cff,0x3ce2bc71,0x3ce23c71,0xbb49bcff,0xbcc63ca2,0x3cf53c15,0xbc15bcf5,0xbca23cc6,0x3cff3b49,0xbc71bce2,
 0xbc98bcce,0xbc5b3ce7,0x3d00bac9,0xbc84bcdc,0x3cf8bbf9,0xbcacbcbe,0xbc2c3cf1,0x3cfdbb96,0xbb963cfd,0x3cf1bc2c,0xbcbebcac,0xbbf93cf8,0xbcdcbc84,0xbac93d00,0x3ce7bc5b,0xbccebc98,
 0xbcce3c98,0x3ce73c5b,0xbac9bd00,0xbcdc3c84,0xbbf9bcf8,0xbcbe3cac,0x3cf13c2c,0xbb96bcfd,0x3cfd3b96,0xbc2cbcf1,0xbcac3cbe,0x3cf83bf9,0xbc843cdc,0x3d003ac9,0xbc5bbce7,0xbc983cce,
 0xbcd5bc8e,0xbbc83cfb,0x3cfbbbc8,0xbc8ebcd5,0xbc8e3cd5,0x3cfb3bc8,0xbbc8bcfb,0xbcd53c8e,0x3cd53c8e,0x3bc8bcfb,0xbcfb3bc8,0x3c8e3cd5,0x3c8ebcd5,0xbcfbbbc8,0x3bc83cfb,0x3cd5bc8e,
 0xbcd5bc8e,0xbbc83cfb,0x3cfbbbc8,0xbc8ebcd5,0xbc8e3cd5,0x3cfb3bc8,0xbbc8bcfb,0xbcd53c8e,0x3cd53c8e,0x3bc8bcfb,0xbcfb3bc8,0x3c8e3cd5,0x3c8ebcd5,0xbcfbbbc8,0x3bc83cfb,0x3cd5bc8e,
 0xbc84bcdc,0xbcac3cbe,0x3ce73c5b,0x3b96bcfd,0x3c98bcce,0xbcf1bc2c,0xbac93d00,0x3cf8bbf9,0xbbf93cf8,0x3d00bac9,0xbc2cbcf1,0xbcce3c98,0xbcfd3b96,0x3c5b3ce7,0x3cbebcac,0xbcdcbc84,
 0xbcdc3c84,0x3cbe3cac,0x3c5bbce7,0xbcfdbb96,0xbccebc98,0xbc2c3cf1,0x3d003ac9,0xbbf9bcf8,0x3cf83bf9,0xbac9bd00,0xbcf13c2c,0x3c983cce,0x3b963cfd,0x3ce7bc5b,0xbcacbcbe,0xbc843cdc,
 0x3ca2bcc6,0xbce2bc71,0xbc153cf5,0x3cff3b49,0xbb49bcff,0xbcf53c15,0x3c713ce2,0x3cc6bca2,0x3cc63ca2,0x3c71bce2,0xbcf5bc15,0xbb493cff,0x3cffbb49,0xbc15bcf5,0xbce23c71,0x3ca23cc6,
 0xbca23cc6,0x3ce23c71,0x3c15bcf5,0xbcffbb49,0x3b493cff,0x3cf5bc15,0xbc71bce2,0xbcc63ca2,0xbcc6bca2,0xbc713ce2,0x3cf53c15,0x3b49bcff,0xbcff3b49,0x3c153cf5,0x3ce2bc71,0xbca2bcc6,
 0x3c5b3ce7,0x3cdcbc84,0xbc98bcce,0xbcbe3cac,0x3ac93d00,0x3cfdbb96,0xbbf9bcf8,0xbcf13c2c,0xbc2c3cf1,0x3cf83bf9,0x3b96bcfd,0xbd00bac9,0xbcac3cbe,0x3cce3c98,0x3c84bcdc,0xbce7bc5b,
 0xbce73c5b,0x3c843cdc,0x3ccebc98,0xbcacbcbe,0xbd003ac9,0x3b963cfd,0x3cf8bbf9,0xbc2cbcf1,0xbcf1bc2c,0xbbf93cf8,0x3cfd3b96,0x3ac9bd00,0xbcbebcac,0xbc983cce,0x3cdc3c84,0x3c5bbce7,
 0xbcb5bcb5,0xbcb53cb5,0x3cb53cb5,0x3cb5bcb5,0xbcb5bcb5,0xbcb53cb5,0x3cb53cb5,0x3cb5bcb5,0xbcb5bcb5,0xbcb53cb5,0x3cb53cb5,0x3cb5bcb5,0xbcb5bcb5,0xbcb53cb5,0x3cb53cb5,0x3cb5bcb5,
 0xbcb5bcb5,0xbcb53cb5,0x3cb53cb5,0x3cb5bcb5,0xbcb5bcb5,0xbcb53cb5,0x3cb53cb5,0x3cb5bcb5,0xbcb5bcb5,0xbcb53cb5,0x3cb53cb5,0x3cb5bcb5,0xbcb5bcb5,0xbcb53cb5,0x3cb53cb5,0x3cb5bcb5,
 0xbc2cbcf1,0xbcf83bf9,0x3b963cfd,0x3d00bac9,0xbcacbcbe,0xbcce3c98,0x3c843cdc,0x3ce7bc5b,0x3c5bbce7,0xbcdcbc84,0xbc983cce,0x3cbe3cac,0x3ac9bd00,0xbcfdbb96,0xbbf93cf8,0x3cf13c2c,
 0x3cf1bc2c,0xbbf9bcf8,0xbcfd3b96,0x3ac93d00,0x3cbebcac,0xbc98bcce,0xbcdc3c84,0x3c5b3ce7,0x3ce73c5b,0x3c84bcdc,0xbccebc98,0xbcac3cbe,0x3d003ac9,0x3b96bcfd,0xbcf8bbf9,0xbc2c3cf1,
 0x00000000,0x00000000,0x00000000,0x00000000,0x00000000,0x00000000,0x00000000,0x00000000,0x00000000,0x00000000,0x00000000,0x00000000,0x00000000,0x00000000,0x00000000,0x00000000,
 0x00000000,0x00000000,0x00000000,0x00000000,0x00000000,0x00000000,0x00000000,0x00000000,0x00000000,0x00000000,0x00000000,0x00000000,0x00000000,0x00000000,0x00000000,0x00000000,
 0x00000000,0x00000000,0x00000000,0x00000000,0x00000000,0x00000000,0x00000000,0x00000000,0x00000000,0x00000000,0x00000000,0x00000000,0x00000000,0x00000000,0x00000000,0x00000000,
 0x00000000,0x00000000,0x00000000,0x00000000,0x00000000,0x00000000,0x00000000,0x00000000,0x00000000,0x00000000,0x00000000,0x00000000,0x00000000,0x00000000,0x00000000,0x00000000,
 0x00000000,0x00000000,0x00000000,0x00000000,0x00000000,0x00000000,0x00000000,0x00000000,0x00000000,0x00000000,0x00000000,0x00000000,0x00000000,0x00000000,0x00000000,0x00000000,
 0x00000000,0x00000000,0x00000000,0x00000000,0x00000000,0x00000000,0x00000000,0x00000000,0x00000000,0x00000000,0x00000000,0x00000000,0x00000000,0x00000000,0x00000000,0x00000000,
 0x00000000,0x00000000,0x00000000,0x00000000,0x00000000,0x00000000,0x00000000,0x00000000,0x00000000,0x00000000,0x00000000,0x00000000,0x00000000,0x00000000,0x00000000,0x00000000,
 0x00000000,0x00000000,0x00000000,0x00000000,0x00000000,0x00000000,0x00000000,0x00000000,0x00000000,0x00000000,0x00000000,0x00000000,0x00000000,0x00000000,0x00000000,0x00000000,
 0x00000000,0x00000000,0x00000000,0x00000000,0x00000000,0x00000000,0x00000000,0x00000000,0x00000000,0x00000000,0x00000000,0x00000000,0x00000000,0x00000000,0x00000000,0x00000000,
 0x00000000,0x00000000,0x00000000,0x00000000,0x00000000,0x00000000,0x00000000,0x00000000,0x00000000,0x00000000,0x00000000,0x00000000,0x00000000,0x00000000,0x00000000,0x00000000,
 0x00000000,0x00000000,0x00000000,0x00000000,0x00000000,0x00000000,0x00000000,0x00000000,0x00000000,0x00000000,0x00000000,0x00000000,0x00000000,0x00000000,0x00000000,0x00000000,
 0x00000000,0x00000000,0x00000000,0x00000000,0x00000000,0x00000000,0x00000000,0x00000000,0x00000000,0x00000000,0x00000000,0x00000000,0x00000000,0x00000000,0x00000000,0x00000000,
};

template<int SA>
__device__ __forceinline__ void wgmma_main(float (&d)[80], uint64_t da, uint64_t db, int sd) {
  asm volatile("{\n.reg .pred p;\nsetp.ne.b32 p, %82, 0;\n"
    "wgmma.mma_async.sync.aligned.m64n160k16.f32.bf16.bf16 "
    "{%0, %1, %2, %3, %4, %5, %6, %7, %8, %9, %10, %11, %12, %13, %14, %15, %16, %17, %18, %19, %20, %21, %22, %23, %24, %25, %26, %27, %28, %29, %30, %31, %32, %33, %34, %35, %36, %37, %38, %39, %40, %41, %42, %43, %44, %45, %46, %47, %48, %49, %50, %51, %52, %53, %54, %55, %56, %57, %58, %59, %60, %61, %62, %63, %64, %65, %66, %67, %68, %69, %70, %71, %72, %73, %74, %75, %76, %77, %78, %79}, %80, %81, p, %83, 1, 1, 0;\n}\n"
    : "+f"(d[0]), "+f"(d[1]), "+f"(d[2]), "+f"(d[3]), "+f"(d[4]), "+f"(d[5]), "+f"(d[6]), "+f"(d[7]), "+f"(d[8]), "+f"(d[9]), "+f"(d[10]), "+f"(d[11]), "+f"(d[12]), "+f"(d[13]), "+f"(d[14]), "+f"(d[15]), "+f"(d[16]), "+f"(d[17]), "+f"(d[18]), "+f"(d[19]), "+f"(d[20]), "+f"(d[21]), "+f"(d[22]), "+f"(d[23]), "+f"(d[24]), "+f"(d[25]), "+f"(d[26]), "+f"(d[27]), "+f"(d[28]), "+f"(d[29]), "+f"(d[30]), "+f"(d[31]), "+f"(d[32]), "+f"(d[33]), "+f"(d[34]), "+f"(d[35]), "+f"(d[36]), "+f"(d[37]), "+f"(d[38]), "+f"(d[39]), "+f"(d[40]), "+f"(d[41]), "+f"(d[42]), "+f"(d[43]), "+f"(d[44]), "+f"(d[45]), "+f"(d[46]), "+f"(d[47]), "+f"(d[48]), "+f"(d[49]), "+f"(d[50]), "+f"(d[51]), "+f"(d[52]), "+f"(d[53]), "+f"(d[54]), "+f"(d[55]), "+f"(d[56]), "+f"(d[57]), "+f"(d[58]), "+f"(d[59]), "+f"(d[60]), "+f"(d[61]), "+f"(d[62]), "+f"(d[63]), "+f"(d[64]), "+f"(d[65]), "+f"(d[66]), "+f"(d[67]), "+f"(d[68]), "+f"(d[69]), "+f"(d[70]), "+f"(d[71]), "+f"(d[72]), "+f"(d[73]), "+f"(d[74]), "+f"(d[75]), "+f"(d[76]), "+f"(d[77]), "+f"(d[78]), "+f"(d[79])
    : "l"(da), "l"(db), "r"(sd), "n"(SA));
}
template<int SA>
__device__ __forceinline__ void wgmma_fwd(float (&d)[32], uint64_t da, uint64_t db, int sd) {
  asm volatile("{\n.reg .pred p;\nsetp.ne.b32 p, %34, 0;\n"
    "wgmma.mma_async.sync.aligned.m64n64k16.f32.bf16.bf16 "
    "{%0, %1, %2, %3, %4, %5, %6, %7, %8, %9, %10, %11, %12, %13, %14, %15, %16, %17, %18, %19, %20, %21, %22, %23, %24, %25, %26, %27, %28, %29, %30, %31}, %32, %33, p, %35, 1, 0, 1;\n}\n"
    : "+f"(d[0]), "+f"(d[1]), "+f"(d[2]), "+f"(d[3]), "+f"(d[4]), "+f"(d[5]), "+f"(d[6]), "+f"(d[7]), "+f"(d[8]), "+f"(d[9]), "+f"(d[10]), "+f"(d[11]), "+f"(d[12]), "+f"(d[13]), "+f"(d[14]), "+f"(d[15]), "+f"(d[16]), "+f"(d[17]), "+f"(d[18]), "+f"(d[19]), "+f"(d[20]), "+f"(d[21]), "+f"(d[22]), "+f"(d[23]), "+f"(d[24]), "+f"(d[25]), "+f"(d[26]), "+f"(d[27]), "+f"(d[28]), "+f"(d[29]), "+f"(d[30]), "+f"(d[31])
    : "l"(da), "l"(db), "r"(sd), "n"(SA));
}
template<int SA>
__device__ __forceinline__ void wgmma_inv(float (&d)[28], uint64_t da, uint64_t db, int sd) {
  asm volatile("{\n.reg .pred p;\nsetp.ne.b32 p, %30, 0;\n"
    "wgmma.mma_async.sync.aligned.m64n56k16.f32.bf16.bf16 "
    "{%0, %1, %2, %3, %4, %5, %6, %7, %8, %9, %10, %11, %12, %13, %14, %15, %16, %17, %18, %19, %20, %21, %22, %23, %24, %25, %26, %27}, %28, %29, p, %31, 1, 1, 0;\n}\n"
    : "+f"(d[0]), "+f"(d[1]), "+f"(d[2]), "+f"(d[3]), "+f"(d[4]), "+f"(d[5]), "+f"(d[6]), "+f"(d[7]), "+f"(d[8]), "+f"(d[9]), "+f"(d[10]), "+f"(d[11]), "+f"(d[12]), "+f"(d[13]), "+f"(d[14]), "+f"(d[15]), "+f"(d[16]), "+f"(d[17]), "+f"(d[18]), "+f"(d[19]), "+f"(d[20]), "+f"(d[21]), "+f"(d[22]), "+f"(d[23]), "+f"(d[24]), "+f"(d[25]), "+f"(d[26]), "+f"(d[27])
    : "l"(da), "l"(db), "r"(sd), "n"(SA));
}

__device__ __forceinline__ uint32_t s2u(const void* p) { return (uint32_t)__cvta_generic_to_shared(p); }
__device__ __forceinline__ void mbar_init(uint32_t a, int c) { asm volatile("mbarrier.init.shared::cta.b64 [%0], %1;" ::"r"(a), "r"(c)); }
__device__ __forceinline__ void mbar_expect(uint32_t a, int b) { asm volatile("mbarrier.arrive.expect_tx.shared::cta.b64 _, [%0], %1;" ::"r"(a), "r"(b) : "memory"); }
__device__ __forceinline__ void mbar_arrive(uint32_t a) { asm volatile("mbarrier.arrive.shared::cta.b64 _, [%0];" ::"r"(a) : "memory"); }
__device__ __forceinline__ void mbar_arrive_cluster(uint32_t a, uint32_t cta, uint32_t cnt) {
  asm volatile("{\n.reg .b32 r;\nmapa.shared::cluster.u32 r, %0, %1;\nmbarrier.arrive.shared::cluster.b64 _, [r], %2;\n}" ::"r"(a), "r"(cta), "r"(cnt) : "memory");
}
__device__ __forceinline__ void mbar_wait(uint32_t a, int ph) {
  asm volatile("{\n.reg .pred p;\n.reg .u32 c;\nmov.u32 c, 0;\nWAIT:\n"
               "mbarrier.try_wait.parity.shared::cta.b64 p, [%0], %1;\n@p bra DONE;\n"
               "add.u32 c, c, 1;\nsetp.lt.u32 p, c, 0x400000;\n@p bra WAIT;\ntrap;\nDONE:\n}" ::"r"(a), "r"(ph) : "memory");
}
__device__ __forceinline__ void flag_wait(const unsigned* p, unsigned target) {
  asm volatile("{\n.reg .pred p;\n.reg .u32 c, v;\nmov.u32 c, 0;\nWAIT:\n"
               "ld.acquire.gpu.global.u32 v, [%0];\nsetp.ge.u32 p, v, %1;\n@p bra DONE;\n"
               "add.u32 c, c, 1;\nsetp.lt.u32 p, c, 0x400000;\n@p bra WAIT;\ntrap;\nDONE:\n}" ::"l"(p), "r"(target) : "memory");
}
__device__ __forceinline__ bool elect_one() {
  uint32_t p;
  asm volatile("{\n.reg .pred P;\nelect.sync _|P, 0xffffffff;\nselp.u32 %0, 1, 0, P;\n}" : "=r"(p));
  return p != 0;
}
__device__ __forceinline__ void bulk_ld(uint32_t dst, const void* src, int bytes, uint32_t bar) {
  asm volatile("cp.async.bulk.shared::cluster.global.mbarrier::complete_tx::bytes [%0], [%1], %2, [%3];" ::"r"(dst), "l"(src), "r"(bytes), "r"(bar) : "memory");
}
__device__ __forceinline__ void bulk_ld_mc_h(uint32_t dst, const void* src, int bytes, uint32_t bar, uint16_t mask, uint64_t pol) {
  asm volatile("cp.async.bulk.shared::cluster.global.mbarrier::complete_tx::bytes.multicast::cluster.L2::cache_hint [%0], [%1], %2, [%3], %4, %5;" ::"r"(dst), "l"(src), "r"(bytes), "r"(bar), "h"(mask), "l"(pol) : "memory");
}
__device__ __forceinline__ uint64_t policy_evict_normal() {
  uint64_t p;
  asm("createpolicy.fractional.L2::evict_normal.b64 %0, 1.0;" : "=l"(p));
  return p;
}
__device__ __forceinline__ void tma_ld2(uint32_t dst, const CUtensorMap* tm, int c0, int c1, uint32_t bar) {
  asm volatile("cp.async.bulk.tensor.2d.shared::cluster.global.mbarrier::complete_tx::bytes [%0], [%1, {%3,%4}], [%2];" ::"r"(dst), "l"(tm), "r"(bar), "r"(c0), "r"(c1) : "memory");
}
__device__ __forceinline__ void tma_ld3(uint32_t dst, const CUtensorMap* tm, int c0, int c1, int c2, uint32_t bar) {
  asm volatile("cp.async.bulk.tensor.3d.shared::cluster.global.mbarrier::complete_tx::bytes [%0], [%1, {%3,%4,%5}], [%2];" ::"r"(dst), "l"(tm), "r"(bar), "r"(c0), "r"(c1), "r"(c2) : "memory");
}
__device__ __forceinline__ void tma_ld3h(uint32_t dst, const CUtensorMap* tm, int c0, int c1, int c2, uint32_t bar, uint64_t pol) {
  asm volatile("cp.async.bulk.tensor.3d.shared::cluster.global.mbarrier::complete_tx::bytes.L2::cache_hint [%0], [%1, {%3,%4,%5}], [%2], %6;" ::"r"(dst), "l"(tm), "r"(bar), "r"(c0), "r"(c1), "r"(c2), "l"(pol) : "memory");
}
__device__ __forceinline__ uint64_t policy_evict_first() {
  uint64_t p;
  asm("createpolicy.fractional.L2::evict_first.b64 %0, 1.0;" : "=l"(p));
  return p;
}
__device__ __forceinline__ void tma_st3(const CUtensorMap* tm, uint32_t src, int c0, int c1, int c2) {
  asm volatile("cp.async.bulk.tensor.3d.global.shared::cta.bulk_group [%0, {%2,%3,%4}], [%1];" ::"l"(tm), "r"(src), "r"(c0), "r"(c1), "r"(c2) : "memory");
}
__device__ __forceinline__ void tma_st4(const CUtensorMap* tm, uint32_t src, int c0, int c1, int c2, int c3) {
  asm volatile("cp.async.bulk.tensor.4d.global.shared::cta.bulk_group [%0, {%2,%3,%4,%5}], [%1];" ::"l"(tm), "r"(src), "r"(c0), "r"(c1), "r"(c2), "r"(c3) : "memory");
}
__device__ __forceinline__ void tma_st5(const CUtensorMap* tm, uint32_t src, int c0) {
  asm volatile("cp.async.bulk.tensor.5d.global.shared::cta.bulk_group [%0, {%2,%3,%3,%3,%3}], [%1];" ::"l"(tm), "r"(src), "r"(c0), "r"(0) : "memory");
}
__device__ __forceinline__ void bulk_commit() { asm volatile("cp.async.bulk.commit_group;" ::: "memory"); }
template <int N> __device__ __forceinline__ void bulk_wait_read() { asm volatile("cp.async.bulk.wait_group.read %0;" ::"n"(N) : "memory"); }
template <int N> __device__ __forceinline__ void bulk_wait() { asm volatile("cp.async.bulk.wait_group %0;" ::"n"(N) : "memory"); }
__device__ __forceinline__ void fence_async_smem() { asm volatile("fence.proxy.async.shared::cta;" ::: "memory"); }
__device__ __forceinline__ void wg_fence() { asm volatile("wgmma.fence.sync.aligned;" ::: "memory"); }
__device__ __forceinline__ void wg_commit() { asm volatile("wgmma.commit_group.sync.aligned;" ::: "memory"); }
template <int N> __device__ __forceinline__ void wg_wait() { asm volatile("wgmma.wait_group.sync.aligned %0;" ::"n"(N) : "memory"); }
template <int R> __device__ __forceinline__ void fence_regs(float (&d)[R]) {
#pragma unroll
  for (int i = 0; i < R; i++) asm volatile("" : "+f"(d[i])::"memory");
}
__device__ __forceinline__ uint64_t mk_desc(uint32_t addr) {
  return (uint64_t)((addr & 0x3FFFF) >> 4) | (1ull << 16) | (64ull << 32) | (1ull << 62);
}
__device__ __forceinline__ uint32_t pack2(float lo, float hi) {
  uint32_t r;
  asm("cvt.rn.bf16x2.f32 %0, %1, %2;" : "=r"(r) : "f"(hi), "f"(lo));
  return r;
}
__device__ __forceinline__ void stsm4(uint32_t ad, uint32_t a, uint32_t b, uint32_t c, uint32_t d) {
  asm volatile("stmatrix.sync.aligned.m8n8.x4.shared.b16 [%0], {%1,%2,%3,%4};" ::"r"(ad), "r"(a), "r"(b), "r"(c), "r"(d) : "memory");
}
__device__ __forceinline__ void stsm4t(uint32_t ad, uint32_t a, uint32_t b, uint32_t c, uint32_t d) {
  asm volatile("stmatrix.sync.aligned.m8n8.x4.trans.shared.b16 [%0], {%1,%2,%3,%4};" ::"r"(ad), "r"(a), "r"(b), "r"(c), "r"(d) : "memory");
}

__device__ __forceinline__ void stsm2t(uint32_t ad, uint32_t a, uint32_t b) {
  asm volatile("stmatrix.sync.aligned.m8n8.x2.trans.shared.b16 [%0], {%1,%2};" ::"r"(ad), "r"(a), "r"(b) : "memory");
}
__device__ __forceinline__ void red_add(unsigned* p) { asm volatile("red.relaxed.gpu.global.add.u32 [%0], 1;" ::"l"(p) : "memory"); }
__device__ __forceinline__ void fence_release() { asm volatile("fence.release.gpu;" ::: "memory"); }
__device__ __forceinline__ void fence_async_global() { asm volatile("fence.proxy.async.global;" ::: "memory"); }
__device__ __forceinline__ void tma_pf2(const CUtensorMap* tm, int c0, int c1) {
  asm volatile("cp.async.bulk.prefetch.tensor.2d.L2.global [%0, {%1,%2}];" ::"l"(tm), "r"(c0), "r"(c1) : "memory");
}
__device__ __forceinline__ void tma_pf3(const CUtensorMap* tm, int c0, int c1, int c2) {
  asm volatile("cp.async.bulk.prefetch.tensor.3d.L2.global [%0, {%1,%2,%3}];" ::"l"(tm), "r"(c0), "r"(c1), "r"(c2) : "memory");
}
__device__ __forceinline__ void bulk_ld_h(uint32_t dst, const void* src, int bytes, uint32_t bar, uint64_t pol) {
  asm volatile("cp.async.bulk.shared::cluster.global.mbarrier::complete_tx::bytes.L2::cache_hint [%0], [%1], %2, [%3], %4;" ::"r"(dst), "l"(src), "r"(bytes), "r"(bar), "l"(pol) : "memory");
}
__device__ __forceinline__ void bulk_ld_mc(uint32_t dst, const void* src, int bytes, uint32_t bar, uint16_t mask) {
  asm volatile("cp.async.bulk.shared::cluster.global.mbarrier::complete_tx::bytes.multicast::cluster [%0], [%1], %2, [%3], %4;" ::"r"(dst), "l"(src), "r"(bytes), "r"(bar), "h"(mask) : "memory");
}
__device__ __forceinline__ uint64_t policy_evict_unchanged() {
  uint64_t p;
  asm("createpolicy.fractional.L2::evict_unchanged.b64 %0, 1.0;" : "=l"(p));
  return p;
}

__device__ __forceinline__ int lane_id() {
  int l;
  asm volatile("mov.u32 %0, %%laneid;" : "=r"(l));
  return l;
}
__device__ __forceinline__ void poll64x4(const unsigned long long* p, unsigned long long (&v)[4]) {
  asm volatile("{\n.reg .pred p;\n.reg .u32 c;\n.reg .b64 t, u;\nmov.u32 c, 0;\nWAIT:\n"
               "ld.relaxed.gpu.global.u64 %0, [%4];\nld.relaxed.gpu.global.u64 %1, [%4+512];\n"
               "ld.relaxed.gpu.global.u64 %2, [%4+1024];\nld.relaxed.gpu.global.u64 %3, [%4+1536];\n"
               "or.b64 t, %0, %1;\nor.b64 u, %2, %3;\nor.b64 t, t, u;\nsetp.ge.s64 p, t, 0;\n@p bra DONE;\n"
               "add.u32 c, c, 1;\nsetp.lt.u32 p, c, 0x400000;\n@p bra WAIT;\ntrap;\nDONE:\n}"
               : "=l"(v[0]), "=l"(v[1]), "=l"(v[2]), "=l"(v[3]) : "l"(p) : "memory");
}

constexpr int G_STAGE = WBLK + XBLK;
constexpr int OFF_XR = 4 * G_STAGE;
constexpr int OFF_WS = OFF_XR + 6 * 8192;
constexpr int OFF_F = OFF_WS + 2 * 8192;
constexpr int OFF_WRAW = OFF_F + 8192;
constexpr int OFF_BAR = OFF_WRAW + 8192;
constexpr int OFF_GB = OFF_BAR + 1024;
constexpr int SMEM_BYTES = OFF_GB + 512;
constexpr int OFF_H0B = 10 * 8192;
constexpr int OFF_E = OFF_WRAW + 3072;
constexpr int B_RAWX = 0, B_F = 48, B_ROLE = 56, B_H0 = 80, B_H1 = 96, B_YFREE = 120, B_H0C = 136,
              B_EMPTY = 144, B_STGX = 176, B_STGW = 224, B_Y = 240, B_OUT = 256, B_YP = 336,
              B_FULL = 432, B_RAWW = 464, B_DONE = 496, S_ROLE = 576, S_PROBE = 592;

struct Maps { CUtensorMap x, we, wo, xst[2], wst, yst[2], yld[2], out, xe[2], w30; };

__device__ __forceinline__ int chunk_of(int n) { return n < 16 ? n : 31 - n; }
__device__ __forceinline__ bool has_x2(int id, int n, int g) { return (((id >> 5) ^ n) & 1) == 0 && ((n >> 1) & 1) == g; }
__device__ __forceinline__ uint32_t x_base(int s, int idx, uint32_t pgmask, int& par) {
  const int page = idx >> 3, o = idx & 7;
  par = (s ^ (pgmask >> page) ^ __popc(o)) & 1;
  return (page << 21) | ((o & 3) << 16) | ((o >> 2) << 19);
}
__device__ __forceinline__ uint32_t read_info(uint32_t bar, int i) {
  uint32_t v;
  mbar_wait(bar + B_ROLE + 8 * i, 0);
  asm volatile("ld.shared.b32 %0, [%1];" : "=r"(v) : "r"(bar + S_ROLE + 4 * i) : "memory");
  return v;
}
__device__ __forceinline__ void send_info(uint32_t bar, int i, uint32_t v) {
#pragma unroll
  for (int r = 0; r < 2; r++)
    asm volatile("{\n.reg .b32 a, m;\nmapa.shared::cluster.u32 a, %0, %2;\nmapa.shared::cluster.u32 m, %1, %2;\n"
                 "st.async.weak.shared::cluster.mbarrier::complete_tx::bytes.b32 [a], %3, [m];\n}"
                 ::"r"(bar + S_ROLE + 4 * i), "r"(bar + B_ROLE + 8 * i), "r"(r), "r"(v) : "memory");
}
__device__ __forceinline__ unsigned probe(uint8_t* p, int lane, int pb) {
  if (lane < 2) *(uint4*)(p + lane * 16) = make_uint4(0, 0, 0, 0);
  __syncwarp();
  unsigned v = 0, best = ~0u;
  if (lane == 0) {
#pragma unroll 1
    for (int r = 0; r < NPR; r++) {
      unsigned t0, t1;
      asm volatile("mov.u32 %0, %%clock;" : "=r"(t0) : "r"(v) : "memory");
      asm volatile("atom.relaxed.gpu.global.exch.b32 %0, [%1], 0;" : "=r"(v) : "l"(p) : "memory");
      asm volatile("{\n.reg .pred p;\nsetp.ne.u32 p, %1, 0xffffffff;\nmov.u32 %0, 0;\n@p mov.u32 %0, %%clock;\n}" : "=r"(t1) : "r"(v) : "memory");
      best = min(best, t1 - t0);
      if (r < 3) PROF_V(pb + r, t1 - t0);
    }
  }
  return best;
}

template <bool ISX>
__device__ __forceinline__ void t_issue(float (&t)[32], uint32_t sb, uint32_t raw) {
  const uint64_t da = mk_desc(sb + OFF_F), db = mk_desc(raw);
  wg_fence();
#pragma unroll
  for (int kk = 0; kk < (ISX ? 4 : 1); kk++) wgmma_fwd<1>(t, da + 2 * kk, db + 128 * kk, kk);
  wg_commit();
}
template <bool ISX>
__device__ __forceinline__ void t_finish(float (&t)[32], uint32_t dst, uint32_t sbar, int sw, int wg, int w, int lane) {
  fence_regs(t);
  if (ISX) asm volatile("bar.sync %0, 128;" ::"r"(1 + wg) : "memory");
  const int m = lane >> 3, r = lane & 7;
  uint32_t ad = dst + (8 * w + r) * 128;
  if (ISX) ad += ((((m & 1) * 4 + (m >> 1)) ^ sw ^ r) << 4);
  else ad += (m & 1) * 4096 + (((m >> 1) ^ sw ^ r) << 4);
#pragma unroll
  for (int i = 0; i < 4; i++) {
    const uint32_t a = ISX ? ((ad ^ ((i & 1) * 32)) + (i >> 1) * 4096) : (ad ^ (i * 32));
    stsm4(a, pack2(t[8 * i], t[8 * i + 1]), pack2(t[8 * i + 2], t[8 * i + 3]), pack2(t[8 * i + 4], t[8 * i + 5]), pack2(t[8 * i + 6], t[8 * i + 7]));
  }
  __syncwarp();
  if (lane == 0) mbar_arrive(sbar);
}
template <int NT, int K0, int K1>
__device__ __forceinline__ void batch(float (&yr)[80], float (&yi)[80], float (&t)[32], uint32_t st, int wg, int sd, uint32_t fa, uint32_t raw) {
  const uint64_t w0 = mk_desc(st + wg * 8192), x0 = mk_desc(st + WBLK);
  const uint64_t da = mk_desc(fa), db = mk_desc(raw);
  wg_fence();
  if (NT) {
#pragma unroll
    for (int kk = 0; kk < NT; kk++) wgmma_fwd<1>(t, da + 2 * kk, db + 128 * kk, kk);
    wg_commit();
  }
#pragma unroll
  for (int kk = K0; kk < K1; kk++) {
    const uint64_t wr = w0 + kk * 128, wi = wr + 256, xr = x0 + kk * 2, xi = xr + 4;
    wgmma_main<1>(yr, wr, xr, kk ? 1 : sd);
    wgmma_main<1>(yi, wr, xi, kk ? 1 : sd);
    wgmma_main<1>(yr, wi, xi, 1);
    wgmma_main<-1>(yi, wi, xr, 1);
  }
  wg_commit();
}

#define X_WAIT() PROF_W(wraw, mbar_wait(bar + B_RAWX + 8 * (wg * 3 + xs), xph))
#define X_ISSUE() t_issue<true>(t, sb, sb + OFF_XR + (wg * 3 + xs) * 8192)
#define X_FINISH(sw) do { t_finish<true>(t, sb + OFF_XR + (wg * 3 + xs) * 8192, bar + B_STGX + 8 * (wg * 3 + xs), sw, wg, w, lane); \
                          if (++xs == 3) { xs = 0; xph ^= 1; } } while (0)
#define W_WAIT(n) PROF_W(wraw, mbar_wait(bar + B_RAWW + 8 * (wg * 2 + ((n) & 1)), ((n) >> 1) & 1))
#define WRAW(n) (sb + OFF_WRAW + (wg * 2 + ((n) & 1)) * 2048)
#define W_FINISH() t_finish<false>(t, sb + OFF_WS + wg * 8192, bar + B_STGW + 8 * wg, (bid >> 1) & 7, wg, w, lane)

__device__ __forceinline__ void gelu_store(float (&hz)[28], uint32_t ad) {
#pragma unroll
  for (int i = 0; i < 28; i++) {
    const float in = hz[i] * fmaf(hz[i] * hz[i], 8.f * 0.044715f * 0.7978845608028654f, 2.f * 0.7978845608028654f);
    float th;
    asm("tanh.approx.f32 %0, %1;" : "=f"(th) : "f"(in));
    hz[i] = fmaf(hz[i], th, hz[i]);
  }
#pragma unroll
  for (int jj = 0; jj < 3; jj++) {
    const float* c = hz + 8 * jj;
    stsm4t(ad + jj * 2048, pack2(c[0], c[1]), pack2(c[2], c[3]), pack2(c[4], c[5]), pack2(c[6], c[7]));
  }
  stsm2t(ad + 3 * 2048, pack2(hz[24], hz[25]), pack2(hz[26], hz[27]));
}

template <int g>
__device__ __forceinline__ void manager(const Maps& tm, unsigned* ctr, const uint32_t sb, const int bid) {
  const uint32_t bar = sb + OFF_BAR, rank = bid & 1;
  const uint64_t pol = policy_evict_first();
  const int id = read_info(bar, 0) * 2 + rank;
  int li = 0;
  auto refill = [&](int sl) {
    if (li >= 32) return;
    const uint32_t fb = bar + B_RAWX + 8 * (g * 3 + sl);
    mbar_expect(fb, 8192);
    tma_ld3h(sb + OFF_XR + (g * 3 + sl) * 8192, &tm.x, (li >> 1) * 64, ((li & 1) ? 128 + (id & 31) : 2 * (id & 63) + g) * MT, id >> 6, fb, pol);
    li += (li & 1) || has_x2(id, li >> 1, g) ? 1 : 2;
  };
#pragma unroll 1
  for (int sl = 0; sl < 3; sl++) refill(sl);
  int xs = 0, xph = 0, yp = 0;
  int wrow = (rank * 2 + (bid >> 6)) * 128 + g * 64 + ((bid >> 1) & 31);
  if (WFIRST) {
    mbar_wait(bar + B_STGW + 8 * g, 0);
    fence_async_smem();
    tma_st4(&tm.wst, sb + OFF_WS + g * 8192, 0, 0, 0, wrow);
    bulk_commit();
  }
  const uint32_t pgmask = read_info(bar, 1);
#pragma unroll 1
  for (int n = 0; n < 32; n++) {
    unsigned freed = 128;
    if (n >= WR) asm volatile("ld.relaxed.gpu.global.u32 %0, [%1];" : "=r"(freed) : "l"(&ctr[(C_LOADED + n - WR) * 32]) : "memory");
    if (n < 16) {
#pragma unroll 1
      for (int j = 0; j < (has_x2(id, n, g) ? 2 : 1); j++) {
        const int t = j ? 128 + (id & 31) : 2 * (id & 63) + g;
        int par0, par1;
        const uint32_t off0 = x_base(id >> 6, n * 10 + (t >> 5), pgmask, par0), off1 = x_base(id >> 6, n * 10 + 5 + (t >> 5), pgmask, par1);
        const uint32_t buf = sb + OFF_XR + (g * 3 + xs) * 8192;
        mbar_wait(bar + B_STGX + 8 * (g * 3 + xs), xph);
        fence_async_smem();
        tma_st5(&tm.xst[par0], buf, (off0 + (par0 << 12) + (t & 31) * 128) >> 1);
        tma_st5(&tm.xst[par1], buf + 4096, (off1 + (par1 << 12) + (t & 31) * 128) >> 1);
        bulk_commit();
        bulk_wait_read<0>();
        refill(xs);
        if (++xs == 3) { xs = 0; xph ^= 1; }
      }
    }
    if (n > 16 + LW && n <= YFLUSH && (n - 17 - LW) % YSTEP == 0) {
      if (yp == 0 || yp == 3) mbar_wait(bar + B_Y + 8 * g, yp & 1);
#pragma unroll 1
      do {
        tma_st4(&tm.yst[0], sb + OFF_XR + (g * 3 + (yp < 3 ? yp : yp - 3)) * 8192, 0, yp * 32, id & 62, (id >> 6) * 4 + rank * 2 + g);
      } while (++yp < 2);
      bulk_commit();
      bulk_wait_read<0>();
      if (yp == 2) mbar_arrive(bar + B_YFREE + 8 * g);
    }
    if (freed < 128) flag_wait(&ctr[(C_LOADED + n - WR) * 32], 128);
    if (n || !WFIRST) {
      mbar_wait(bar + B_STGW + 8 * g, n & 1);
      fence_async_smem();
      tma_st4(&tm.wst, sb + OFF_WS + g * 8192, 0, 0, 0, wrow);
      bulk_commit();
    }
    wrow += WCHUNK / 128;
    if (wrow >= WR * WCHUNK / 128) wrow -= WR * WCHUNK / 128;
    if (n < 30) {
      const int cp = chunk_of(n + 2) * 64 + (bid >> 1), sl = g * 2 + (n & 1);
      mbar_expect(bar + B_RAWW + 8 * sl, 2048);
      tma_ld3h(sb + OFF_WRAW + sl * 2048, &tm.we + (cp >> 9), 0, 0, (cp & 511) * 8 + ((n + 2) >> 4) * 4 + rank * 2 + g, bar + B_RAWW + 8 * sl, pol);
    }
    if (n < 4) {
#pragma unroll 1
      for (int q = 4 + n; q < 16; q += 4) {
        const int cp = q * 64 + (bid >> 1);
        tma_pf3(&tm.we + (cp >> 9), 0, 0, (cp & 511) * 8 + rank * 2 + g);
      }
    }
    bulk_wait<0>();
    mbar_arrive(bar + B_DONE + 8 * (n & 3));
    mbar_arrive(bar + B_RAWW + 8 * (g * 2 + ((n + 1) & 1)));
  }
  const int b = id >> 6, u = (id >> 1) & 31;
  flag_wait(&ctr[(C_LOADED + 31) * 32], 128);
#pragma unroll 1
  for (int p = 0; p < 5; p++) {
    mbar_wait(bar + B_YP + 8 * (g * 5 + p), 0);
    fence_async_smem();
    tma_st4(&tm.yst[1], sb + (p * 2 + g) * 8192, 0, p * 32, 2 * u, b * 4 + rank * 2 + g);
  }
  bulk_commit();
  bulk_wait<0>();
  mbar_arrive(bar + B_DONE);
#pragma unroll 1
  for (int i = 0; i < 10; i++) {
    const int hf = i >= 5, k = i - 5 * hf;
    mbar_wait(bar + B_OUT + 8 * (g * 5 + k), hf);
    fence_async_smem();
    tma_st3(&tm.out, sb + (hf ? 0 : k < 4 ? OFF_XR : OFF_H0B - 65536) + (2 * k + g) * 8192, (hf * 4 + rank * 2 + (u & 1)) * 64, ((u >> 1) * 10 + 2 * k + g) * MT, b);
    bulk_commit();
  }
  bulk_wait_read<0>();
  if (g == 0) PROF_T(12);
}

__global__ void __cluster_dims__(2, 1, 1) __launch_bounds__(512, 1)
k1_main(uint8_t* __restrict__ xbuf, const void* __restrict__ fimg, unsigned* ctr, const __nv_bfloat16* __restrict__ gamma,
        const __nv_bfloat16* __restrict__ beta, const __grid_constant__ Maps tm) {
  extern __shared__ __align__(1024) uint8_t smem_raw[];
  const uint32_t sb = s2u(smem_raw);
  const uint32_t bar = sb + OFF_BAR;
  const int warp = __shfl_sync(0xffffffffu, threadIdx.x >> 5, 0);
  const int bid = (int)blockIdx.x - 4;
  const uint32_t rank = bid & 1;
  if (warp >= 12) {
    asm volatile("setmaxnreg.dec.sync.aligned.u32 24;");
    asm volatile("barrier.cluster.arrive.relaxed.aligned;" ::: "memory");
    if (bid >= 0) {
      const int lane = lane_id(), k = bid >> 1;
      if (rank == 0 || k < XPAGES) {
        const uint32_t off = rank ? (k << 21) + 0xb0000 : (XPAGES << 21) + ((k >> 4) << 14) + (k & 15) * 128;
        const unsigned lat = probe(xbuf + off + (warp & 1) * 4096 + (warp & 2) * 1024, lane, 400 + (warp & 2) * 5 + (warp & 1) * 3);
        if (lane == 0) asm volatile("st.shared.b32 [%0], %1;" ::"r"(bar + S_PROBE + 4 * (warp & 3)), "r"(lat) : "memory");
      }
      asm volatile("bar.sync 4, 128;" ::: "memory");
      asm volatile("barrier.cluster.wait.aligned;" ::: "memory");
      if (warp == 14 && lane == 0) {
        uint32_t l0, l1, l2, l3;
        asm volatile("ld.shared.v4.b32 {%0, %1, %2, %3}, [%4];" : "=r"(l0), "=r"(l1), "=r"(l2), "=r"(l3) : "r"(bar + S_PROBE) : "memory");
        const int near = min(l1, l3) < min(l0, l2);
        if (rank) {
          send_info(bar, 2, near);
        } else {
          unsigned long long add = 1ull << (8 * near), v, *reg = (unsigned long long*)&ctr[C_REG * 32];
          if (k < XPAGES) add += (unsigned long long)(read_info(bar, 2) ^ near ^ 1) << (16 + k);
          PROF_T(14);
          asm volatile("{\n.reg .pred p;\n.reg .u32 c;\nmov.u32 c, 0;\nAGAIN:\n"
                       "atom.relaxed.gpu.global.add.u64 %0, [%1], %2;\nsetp.lt.s64 p, %0, 0;\n@p bra DONE;\n"
                       "add.u32 c, c, 1;\nsetp.lt.u32 p, c, 0x100000;\n@p bra AGAIN;\ntrap;\nDONE:\n}" : "=l"(v) : "l"(reg), "l"(add) : "memory");
          const int ticket = (v >> (8 * near)) & 255;
          send_info(bar, 0, ticket < 32 ? near * 32 + ticket : (near ^ 1) * 32 + 63 - ticket);
          PROF_T(15); PROF_V(16, near); PROF_V(17, ticket < 32 ? near * 32 : (near ^ 1) * 32);
          asm volatile("{\n.reg .pred p;\n.reg .u32 c, a, b;\nmov.u32 c, 0;\nWAIT:\n"
                       "ld.relaxed.gpu.global.u64 %0, [%1];\ncvt.u32.u64 a, %0;\nbfe.u32 b, a, 8, 8;\nand.b32 a, a, 255;\nadd.u32 a, a, b;\n"
                       "setp.ge.u32 p, a, 64;\n@p bra DONE;\n"
                       "add.u32 c, c, 1;\nsetp.lt.u32 p, c, 0x400000;\n@p bra WAIT;\ntrap;\nDONE:\n}" : "=l"(v) : "l"(reg) : "memory");
          send_info(bar, 1, (uint32_t)(v >> 16));
          PROF_T(13);
        }
      }
      __syncwarp();
      if (warp - 12 < NFL && elect_one()) {
#pragma unroll 1
        for (int n = warp - 12; n < 33; n += NFL) {
          int f = n;
          if (n == 32) f += (read_info(bar, 0) >> 5) * 2 + rank;
          mbar_wait(bar + B_DONE + 8 * (n & 3), (n >> 2) & 1);
          fence_release();
          red_add(&ctr[(C_FLAG + f) * 32]);
          if (n < 32) { PROF_T(64 + n); PROF_V(192 + n, tm0); } else { PROF_V(4, tm0); }
        }
      }
      if (warp == 15 && elect_one()) {
#pragma unroll 1
        for (int v = 0; v < 64; v++) {
          mbar_wait(bar + B_FULL + 8 * (v & 3), (v >> 2) & 1);
          if ((v & 1) && (v < 2 * (32 - WR) || v == 63)) red_add(&ctr[(C_LOADED + (v >> 1)) * 32]);
        }
      }
      __syncwarp();
    } else {
      if (blockIdx.x == 0 && warp == 12 && lane_id() < 4)
        asm volatile("st.relaxed.gpu.global.u64 [%0], %1;" ::"l"(&ctr[C_REG * 32 + 2 * lane_id()]), "l"(1ull << 63) : "memory");
      __syncwarp();
      asm volatile("barrier.cluster.wait.aligned;" ::: "memory");
    }
    asm volatile("barrier.cluster.arrive.relaxed.aligned;\nbarrier.cluster.wait.aligned;" ::: "memory");
    return;
  } else {
    if (elect_one()) {
      if (warp == 0) PROF_T(0);
      if (warp >= 6) asm volatile("prefetch.tensormap [%0];" ::"l"(&tm.x + (warp - 6)) : "memory");
      const int cnt = warp < 3 ? 1 : warp < 9 ? 4 : 2;
#pragma unroll
      for (int i = 0; i < 6; i++) mbar_init(bar + warp * 48 + 8 * i, cnt);
      if (warp == 1) {
        if (bid >= 0) {
          mbar_expect(bar + B_F, 8192);
          bulk_ld(sb + OFF_F, fimg, 8192, bar + B_F);
        }
        mbar_expect(bar + B_ROLE, 4);
        mbar_expect(bar + B_ROLE + 8, 4);
        mbar_expect(bar + B_ROLE + 16, 4);
      }
      asm volatile("fence.mbarrier_init.release.cluster;" ::: "memory");
    }
    asm volatile("bar.sync 0, 384;" ::: "memory");
    asm volatile("barrier.cluster.arrive.relaxed.aligned;" ::: "memory");
    if (threadIdx.x == 64) PROF_T(20);
    if (bid >= 0 && warp < 6 && elect_one()) {
      const int g = warp & 1, q = warp >> 2;
      const uint64_t pol = policy_evict_first();
      if (warp < 2) {
        tma_pf3(&tm.x, 0, (2 * (bid & 63) + g) * MT, bid >> 6);
        if (has_x2(bid, 0, g)) tma_pf3(&tm.x, 0, (128 + (bid & 31)) * MT, bid >> 6);
      } else {
        const uint32_t fb = bar + B_RAWW + 8 * (g * 2 + q);
        mbar_expect(fb, 2048);
        tma_ld3h(sb + OFF_WRAW + (g * 2 + q) * 2048, &tm.we, 0, 0, (q * 64 + (bid >> 1)) * 8 + rank * 2 + g, fb, pol);
        if (!q) mbar_arrive(fb);
      }
    }
    __syncwarp();
  }
  if (warp >= 8) {
    asm volatile("setmaxnreg.dec.sync.aligned.u32 40;");
    if (bid < 0) {
      asm volatile("barrier.cluster.wait.aligned;" ::: "memory");
    } else if (warp == 9 || warp == 10) {
      if (elect_one()) {
        if (warp == 9) manager<0>(tm, ctr, sb, bid); else manager<1>(tm, ctr, sb, bid);
      }
      __syncwarp();
      asm volatile("barrier.cluster.wait.aligned;" ::: "memory");
    } else if (warp == 11) {
      asm volatile("barrier.cluster.wait.aligned;" ::: "memory");
      if (elect_one()) {
        const uint8_t* ws = g_W + (size_t)((read_info(bar, 0) & 31) * 2 + rank) * 2 * WBLK;
        int slot = 0;
#pragma unroll 1
        for (int n = 0; n < 32; n++) {
          const uint8_t* src = ws + (size_t)slot * WCHUNK;
          const uint32_t s8 = (n & 1) * 16, dst = sb + (n & 1) * 2 * G_STAGE;
          const int ph = ((n >> 1) & 1) ^ 1;
          if (++slot == WR) slot = 0;
          flag_wait(&ctr[(C_FLAG + n) * 32], 128);
          fence_async_global();
          PROF_T(32 + n);
#pragma unroll
          for (int h = 0; h < 2; h++) {
            mbar_wait(bar + B_EMPTY + s8 + 8 * h, ph);
            mbar_expect(bar + B_FULL + s8 + 8 * h, WBLK);
            bulk_ld(dst + h * G_STAGE, src + h * WBLK, WBLK, bar + B_FULL + s8 + 8 * h);
          }
        }
      }
      __syncwarp();
    } else {
      asm volatile("barrier.cluster.wait.aligned;" ::: "memory");
      if (elect_one()) {
        const int role = read_info(bar, 0);
        const uint32_t pgmask = read_info(bar, 1);
        PROF_T(1);
        const int b = role >> 5, u = role & 31;
        const int dq = rank * 2 + (u & 1), t0 = (u >> 1) * 10;
        const uint64_t pef = policy_evict_first(), pen = policy_evict_normal();
        const uint8_t* xs = xbuf + ((((u >> 1) & 3) << 14) | (((u >> 3) & 1) << 18) | ((u >> 4) << 20) | ((u & 1) << 13));
#pragma unroll 1
        for (int n = 0; n < 32; n++) {
          const int c = chunk_of(n);
          const uint64_t polx = (n < XKEEP || n >= 16) ? pef : pen;
          const uint32_t s8 = (n & 1) * 16, dst = sb + (n & 1) * 2 * G_STAGE + WBLK + rank * 8192;
          const int ph = ((n >> 1) & 1) ^ 1;
          uint32_t xo[6];
#pragma unroll
          for (int g = 0; g < 6; g++) {
            int par;
            xo[g] = x_base(b, c * 10 + (g / 3) * 5 + rank * 2 + g % 3, pgmask, par);
            xo[g] += ((par ^ u) & 1) << 12;
            asm volatile("" : "+r"(xo[g]));
          }
          if (n < 16) {
            flag_wait(&ctr[(C_FLAG + n) * 32], 128);
            fence_async_global();
          }
#pragma unroll
          for (int h = 0; h < 2; h++) {
            const uint32_t fb = bar + B_FULL + s8 + 8 * h;
            mbar_wait(bar + B_EMPTY + s8 + 8 * h, ph);
            mbar_expect(fb, XBLK);
#pragma unroll
            for (int g = 0; g < 3; g++) {
              const int skip = (g == 0 && rank) ? 2048 : 0, len = (g == (rank ? 0 : 2)) ? 2048 : 4096;
              bulk_ld_mc_h(dst + h * G_STAGE + g * 4096 + skip, xs + xo[3 * h + g] + skip, len, fb, 3, polx);
            }
          }
        }
        flag_wait(&ctr[C_E * 32], 4);
        flag_wait(&ctr[(C_FLAG + YFLUSH) * 32], 128);
        if (YSEEN != YFLUSH) flag_wait(&ctr[(C_FLAG + YSEEN) * 32], 128);
        fence_async_global();
        mbar_expect(bar + B_H0C, 6 * 8192);
        for (int i = 0; i < 3; i++) tma_ld2(sb + OFF_XR + i * 16384, &tm.yld[0], 0, ((b * 4 + dq) * NT + t0 + 2 * i) * 64, bar + B_H0C);
        static_assert(LW <= 4, "phases of the B_DONE ring");
        mbar_wait(bar + B_DONE + 8 * 3, 1);
        mbar_expect(bar + B_H0, 2 * 8192 + 7168 + 5120 + 512);
        bulk_ld(sb + OFF_F, g_Gimg, 7168, bar + B_H0);
        tma_ld2(sb + OFF_WS, &tm.yld[0], 0, ((b * 4 + dq) * NT + t0 + 6) * 64, bar + B_H0);
        tma_pf2(&tm.yld[0], 0, ((b * 4 + dq) * NT + t0 + 8) * 64);
        for (int hf = 0; hf < 2; hf++) {
          bulk_ld(sb + OFF_E + hf * 2560, g_E + ((b * 8 + hf * 4 + dq) * NT + t0) * 64, 2560, bar + B_H0);
          bulk_ld(sb + OFF_GB + hf * 256, gamma + (hf * 4 + dq) * 64, 128, bar + B_H0);
          bulk_ld(sb + OFF_GB + hf * 256 + 128, beta + (hf * 4 + dq) * 64, 128, bar + B_H0);
        }
        mbar_wait(bar + B_EMPTY + 8 * 2, 1);
        mbar_expect(bar + B_H0 + 8, 16384);
        tma_ld2(sb + OFF_H0B, &tm.yld[0], 0, ((b * 4 + dq) * NT + t0 + 8) * 64, bar + B_H0 + 8);
        flag_wait(&ctr[(C_FLAG + 32 + b * 2 + rank) * 32], 32);
        fence_async_global();
        PROF_T(5);
        for (int i = 0; i < 5; i++) {
          const uint32_t fb = bar + B_H1 + 8 * (i >> 1);
          if ((i & 1) == 0) mbar_expect(fb, i < 4 ? 32768 : 16384);
          tma_ld2(sb + i * 16384, &tm.yld[1], 0, ((b * 4 + dq) * NT + t0 + 2 * i) * 64, fb);
        }
      }
      __syncwarp();
      const int lane = lane_id();
      unsigned old = 0;
      if (lane == 0) old = atomicAdd(&ctr[C_EXIT * 32], 1);
      if (__shfl_sync(0xffffffffu, old, 0) == 127) {
        for (int i = lane; i < C_NUM; i += 32) *(uint4*)&ctr[i * 32] = make_uint4(0, 0, 0, 0);
      }
    }
    asm volatile("barrier.cluster.arrive.relaxed.aligned;\nbarrier.cluster.wait.aligned;" ::: "memory");
  } else {
    asm volatile("setmaxnreg.inc.sync.aligned.u32 224;");
    const int wg = warp >> 2, w = warp & 3;
    int lane = lane_id();
    asm volatile("barrier.cluster.wait.aligned;" ::: "memory");
    if (bid < 0) {
      float ea[80], eb[80];
      const int b = blockIdx.x >> 1;
      constexpr int ES = 32768 + 2 * XBLK;
#pragma unroll 1
      for (int k = -3; k < 8; k++) {
        const int sl = (k + 3) % 3;
        if (k >= 0) {
          mbar_wait(bar + B_RAWX + 8 * sl, (k / 3) & 1);
          const uint64_t da = mk_desc(sb + sl * ES + wg * 16384), db = mk_desc(sb + sl * ES + 32768);
          wg_fence();
#pragma unroll
          for (int kk = 0; kk < 8; kk++) {
            const uint64_t a0 = da + (kk & 3) * 128, b0 = db + (kk & 3) * 2 + (kk >> 2) * (XBLK >> 4);
            wgmma_main<1>(ea, a0, b0, (k | kk) != 0);
            wgmma_main<1>(eb, a0 + 512, b0, (k | kk) != 0);
          }
          wg_commit();
          wg_wait<0>();
          asm volatile("bar.sync 3, 256;" ::: "memory");
        }
        if (k + 3 < 8 && warp == 0 && elect_one()) {
          const uint32_t dst = sb + sl * ES, fb = bar + B_RAWX + 8 * sl;
          mbar_expect(fb, ES);
          for (int q = 0; q < 4; q++) tma_ld2(dst + q * 8192, &tm.w30, rank * 256 + q * 64, (k + 3) * 64, fb);
          for (int q = 0; q < 2; q++) tma_ld3(dst + 32768 + q * XBLK, &tm.xe[q], (k + 3) * 64, 0, b, fb);
        }
        __syncwarp();
      }
      fence_regs(ea);
      fence_regs(eb);
      float* e0 = g_E + ((b * 8 + rank * 4 + wg * 2) * NT + 2 * (lane & 3)) * 64 + 16 * w + (lane >> 2);
#pragma unroll
      for (int i = 0; i < 80; i++) {
        const int o = (8 * (i >> 2) + (i & 1)) * 64 + ((i >> 1) & 1) * 8;
        e0[o] = ea[i];
        e0[o + NT * 64] = eb[i];
      }
      asm volatile("bar.sync 3, 256;" ::: "memory");
      if (threadIdx.x == 0) {
        fence_release();
        red_add(&ctr[C_E * 32]);
        PROF_T(28);
      }
      asm volatile("barrier.cluster.arrive.relaxed.aligned;\nbarrier.cluster.wait.aligned;" ::: "memory");
      return;
    }
    int id;
    {
      float yr[80], yi[80], t[32];

      int xs = 0, xph = 0;
      if (threadIdx.x == 0) PROF_T(24);
      mbar_wait(bar + B_F, 0);
      W_WAIT(0);
      t_issue<false>(t, sb, WRAW(0));
      wg_wait<0>();
      W_FINISH();
      id = __shfl_sync(0xffffffffu, read_info(bar, 0), 0) * 2 + rank;
      if (threadIdx.x == 0) PROF_T(25);
#pragma unroll 1
      for (int m = 0; m <= LW; m++) {
        X_WAIT();
        X_ISSUE();
        wg_wait<0>();
        X_FINISH((2 * id + wg) & 7);
        if (threadIdx.x == 0 && m == 0) PROF_T(26);
        if (has_x2(id, m, wg)) {
          X_WAIT();
          X_ISSUE();
          wg_wait<0>();
          X_FINISH(id & 7);
        }
        if (m < LW && (m || !WFIRST)) {
          W_WAIT(m);
          t_issue<false>(t, sb, WRAW(m));
          wg_wait<0>();
          W_FINISH();
        }
      }
      if (threadIdx.x == 0) PROF_T(27);
      const int ym = lane >> 3, yr8 = lane & 7;
      const uint32_t yad = (ym >> 1) * 4096 + yr8 * 128 + (((2 * w + (ym & 1)) ^ yr8) << 4);
#define STAGE_PROF0()
#define STAGE_PROF1()
#define STAGE_BEGIN() PROF_W(wfull, mbar_wait(bar + B_FULL + 8 * (v & 3), (v >> 2) & 1)); STAGE_PROF0(); const uint32_t st = sb + (v & 3) * G_STAGE
#define RELEASE(vv) do { if (w == 0 && lane < 2) mbar_arrive_cluster(bar + B_EMPTY + 8 * ((vv) & 3), lane, 1); } while (0)
#define XRAW (sb + OFF_XR + (wg * 3 + xs) * 8192)
#define STAGE_W0(mw, sd) do { W_WAIT(mw); batch<1, 0, 2>(yr, yi, t, st, wg, sd, sb + OFF_F, WRAW(mw)); wg_wait<1>(); W_FINISH(); wg_wait<0>(); RELEASE(v); } while (0)
#define STAGE_PLAIN0(sd) do { batch<0, 0, 2>(yr, yi, t, st, wg, sd, 0, 0); wg_wait<0>(); RELEASE(v); } while (0)
#define STAGE_W1(mw, sd) do { W_WAIT(mw); batch<1, 0, 1>(yr, yi, t, st, wg, sd, sb + OFF_F, WRAW(mw)); wg_wait<1>(); if (sd) RELEASE(v - 1); \
                              W_FINISH(); batch<0, 1, 2>(yr, yi, t, st, wg, 1, 0, 0); } while (0)
#define STAGE_PLAIN1(sd) do { batch<0, 0, 1>(yr, yi, t, st, wg, sd, 0, 0); wg_wait<1>(); if (sd) RELEASE(v - 1); \
                              batch<0, 1, 2>(yr, yi, t, st, wg, 1, 0, 0); } while (0)
#pragma unroll 1
      for (int v = 0; v < 32; v++) {
        const int m = ((v + 1) >> 1) + LW;
        STAGE_BEGIN();
        if (!(v & 1) || v == 31) {
          if (P0M) STAGE_W1(m, v != 0); else STAGE_W0(m, v != 0);
        } else if (m >= 16) {
          if (P0M) STAGE_PLAIN1(1); else STAGE_PLAIN0(1);
        } else {
          X_WAIT();
          batch<4, 0, 1>(yr, yi, t, st, wg, 1, sb + OFF_F, XRAW);
          wg_wait<1>();
          if (P0M) RELEASE(v - 1);
          X_FINISH((2 * id + wg) & 7);
          if (has_x2(id, m, wg)) {
            X_WAIT();
            batch<4, 1, 2>(yr, yi, t, st, wg, 1, sb + OFF_F, XRAW);
            wg_wait<1>();
            X_FINISH(id & 7);
          } else {
            batch<0, 1, 2>(yr, yi, t, st, wg, 1, 0, 0);
          }
          if (!P0M) { wg_wait<0>(); RELEASE(v); }
        }
        STAGE_PROF1();
      }
      wg_wait<0>();
      fence_regs(yr);
      fence_regs(yi);
      if (P0M) RELEASE(31);
      {
        uint32_t hold[32];
#pragma unroll
        for (int j = 0; j < 20; j++) {
          const uint32_t p0 = pack2(yr[4 * j], yr[4 * j + 1]), p1 = pack2(yr[4 * j + 2], yr[4 * j + 3]);
          const uint32_t p2 = pack2(yi[4 * j], yi[4 * j + 1]), p3 = pack2(yi[4 * j + 2], yi[4 * j + 3]);
          if (j < 12) {
            stsm4t(sb + OFF_XR + wg * 3 * 8192 + yad + (j >> 2) * 8192 + (j & 3) * 1024, p0, p1, p2, p3);
          } else {
            hold[4 * j - 48] = p0; hold[4 * j - 47] = p1; hold[4 * j - 46] = p2; hold[4 * j - 45] = p3;
          }
        }
#pragma unroll
        for (int j = 0; j < 32; j++) asm volatile("" : "+r"(hold[j])::"memory");
        fence_async_smem();
        __syncwarp();
        if (lane == 0) mbar_arrive(bar + B_Y + 8 * wg);
        if (threadIdx.x == 0) PROF_T(2);
#pragma unroll
        for (int v = 32; v < 34; v++) {
          STAGE_BEGIN();
          if (P1M) STAGE_PLAIN1(v != 32); else STAGE_PLAIN0(v != 32);
          STAGE_PROF1();
        }
        mbar_wait(bar + B_YFREE + 8 * wg, 0);
#pragma unroll
        for (int j = 0; j < 8; j++)
          stsm4t(sb + OFF_XR + wg * 3 * 8192 + yad + (j >> 2) * 8192 + (j & 3) * 1024, hold[4 * j], hold[4 * j + 1], hold[4 * j + 2], hold[4 * j + 3]);
        fence_async_smem();
        __syncwarp();
        if (lane == 0) mbar_arrive(bar + B_Y + 8 * wg);
#pragma unroll
        for (int j = 0; j < 32; j++) t[j] = __uint_as_float(hold[j]);
      }
#pragma unroll 1
      for (int v = 34; v < 64; v++) {
        const int m = (v >> 1) + LW;
        STAGE_BEGIN();
        if (!(v & 1) && m < 32) {
          if (P1M) STAGE_W1(m, 1); else STAGE_W0(m, 1);
        } else {
          if (P1M) STAGE_PLAIN1(1); else STAGE_PLAIN0(1);
          if (v == 49 && wg == 0) g_part[bid * 128 + w * 32 + lane] = ~0ull;
        }
        STAGE_PROF1();
      }
      wg_wait<0>();
      fence_regs(yr);
      fence_regs(yi);
      asm volatile("bar.sync 3, 256;" ::: "memory");
#pragma unroll
      for (int j = 0; j < 20; j++) {
        stsm4t(sb + wg * 8192 + yad + (j >> 2) * 16384 + (j & 3) * 1024, pack2(yr[4 * j], yr[4 * j + 1]), pack2(yr[4 * j + 2], yr[4 * j + 3]),
               pack2(yi[4 * j], yi[4 * j + 1]), pack2(yi[4 * j + 2], yi[4 * j + 3]));
        if ((j & 3) == 3) {
          __syncwarp();
          if (lane == 0) mbar_arrive(bar + B_YP + 8 * (wg * 5 + (j >> 2)));
        }
      }
      if (threadIdx.x == 0) PROF_T(3);
    }
    lane = lane_id();
    const int tid = warp * 32 + lane, b = id >> 6, u = (id >> 1) & 31;
    const int dq = rank * 2 + (u & 1), tr = u >> 1;
    const int a = lane & 3, d0 = 16 * w + (lane >> 2);
    float2* s_red = (float2*)(smem_raw + OFF_WRAW);
    const uint32_t oad = wg * 8192 + ((lane >> 4) * 8 + (lane & 7)) * 128 + (((2 * w + ((lane >> 3) & 1)) ^ (lane & 7)) << 4);
    float held[28];
#pragma unroll
    for (int i = 0; i < 28; i++) held[i] = 0.f;
#pragma unroll 1
    for (int hf = 0; hf < 2; hf++) {
      const uint32_t base = sb + (hf ? 0 : OFF_XR), last = hf ? 0 : OFF_H0B - 65536 - OFF_XR;
      float acc[5][28];
      float q1[4] = {0.f, 0.f, 0.f, 0.f}, q2[4] = {0.f, 0.f, 0.f, 0.f};
      if (hf == 0) { mbar_wait(bar + B_H0, 0); mbar_wait(bar + B_H0C, 0); }
      const float* se = (const float*)(smem_raw + OFF_E + hf * 2560) + wg * 64 + d0;
#pragma unroll
      for (int k2 = 0; k2 < 4; k2++) {
        if (k2 < 3) {
          if (hf) mbar_wait(bar + B_H1 + 8 * k2, 0);
          else if (k2 == 2) mbar_wait(bar + B_H0 + 8, 0);
          const uint64_t da = mk_desc(base + (4 * k2 + wg) * 8192 + (k2 == 2 ? last : 0)), db = mk_desc(sb + OFF_F);
          wg_fence();
#pragma unroll
          for (int kk = 0; kk < 4; kk++) {
            wgmma_inv<1>(acc[2 * k2], da + 128 * kk, db + 2 * kk, kk);
            if (k2 < 2) wgmma_inv<1>(acc[2 * k2 + 1], da + 1024 + 128 * kk, db + 2 * kk, kk);
          }
          wg_commit();
        }
        if (k2 > 0) {
          if (k2 < 3) wg_wait<1>(); else wg_wait<0>();
#pragma unroll
          for (int k = 2 * k2 - 2; k < 2 * k2 && k < 5; k++) {
            fence_regs(acc[k]);
            if (a == 0) {
              acc[k][25] += se[k * 128];
              acc[k][27] += se[k * 128 + 8];
            }
            if (k == 4 && tr == 15 && wg == 1) {
#pragma unroll
              for (int i = 16; i < 28; i++)
                if (8 * (i >> 2) + (i & 1) + 2 * a >= LOUT - (NT - 1) * MT) acc[k][i] = 0.f;
            }
#pragma unroll
            for (int i = 0; i < 28; i++) {
              q1[i & 3] += acc[k][i];
              q2[i & 3] = fmaf(acc[k][i], acc[k][i], q2[i & 3]);
            }
            fence_regs(q1);
            fence_regs(q2);
          }
        }
      }
      float s1[2] = {q1[0] + q1[1], q1[2] + q1[3]}, s2[2] = {q2[0] + q2[1], q2[2] + q2[3]};
#pragma unroll
      for (int i = 0; i < 2; i++) {
#pragma unroll
        for (int o = 1; o < 4; o <<= 1) {
          s1[i] += __shfl_xor_sync(0xffffffffu, s1[i], o);
          s2[i] += __shfl_xor_sync(0xffffffffu, s2[i], o);
        }
      }
      if (a == 0) {
        s_red[wg * 64 + d0] = make_float2(s1[0], s2[0]);
        s_red[wg * 64 + d0 + 8] = make_float2(s1[1], s2[1]);
      }
      asm volatile("bar.sync 3, 256;" ::: "memory");
      if (tid == 0) PROF_T(6 + 3 * hf);
      unsigned long long* part = g_part + ((hf * 2 + b) * 4 + dq) * 1024;
      if (tid < 64) {
        const float2 p0 = s_red[tid], p1 = s_red[64 + tid];
        const float x1 = p0.x + p1.x, x2 = p0.y + p1.y;
        const unsigned long long v = ((unsigned long long)(__float_as_uint(x2) & 0x7fffffffu) << 32) | __float_as_uint(x1);
        asm volatile("st.relaxed.gpu.global.u64 [%0], %1;" ::"l"(part + tr * 64 + tid), "l"(v) : "memory");
      }
      if (HOLD && hf) {
        gelu_store(held, sb + OFF_H0B + oad);
        __syncwarp();
        if (lane == 0) mbar_arrive(bar + B_OUT + 8 * (wg * 5 + 4));
      }
      {
        const unsigned long long* q = part + (tid >> 6) * 256 + (tid & 63);
        unsigned long long v[4];
        poll64x4(q, v);
        float x1 = 0.f, x2 = 0.f;
#pragma unroll
        for (int i = 0; i < 4; i++) {
          x1 += __uint_as_float((uint32_t)v[i]);
          x2 += __uint_as_float((uint32_t)(v[i] >> 32));
        }
        s_red[128 + tid] = make_float2(x1, x2);
      }
      asm volatile("bar.sync 3, 256;" ::: "memory");
      if (tid == 0) PROF_T(7 + 3 * hf);
#pragma unroll
      for (int i = 0; i < 2; i++) {
        const float2 q0 = s_red[128 + d0 + 8 * i], q1 = s_red[192 + d0 + 8 * i], q2 = s_red[256 + d0 + 8 * i], q3 = s_red[320 + d0 + 8 * i];
        const float mu = ((q0.x + q1.x) + (q2.x + q3.x)) * (1.f / LOUT);
        const float var = fmaxf(((q0.y + q1.y) + (q2.y + q3.y)) * (1.f / LOUT) - mu * mu, 0.f);
        const __nv_bfloat16* gb = (const __nv_bfloat16*)(smem_raw + OFF_GB + hf * 256) + d0 + 8 * i;
        s1[i] = 0.5f * __bfloat162float(gb[0]) * rsqrtf(var + 1e-5f);
        s2[i] = 0.5f * __bfloat162float(gb[64]) - mu * s1[i];
      }
#pragma unroll
      for (int k = 0; k < 5; k++) {
#pragma unroll
        for (int i = 0; i < 28; i++) held[i] = fmaf(acc[k][i], s1[(i >> 1) & 1], s2[(i >> 1) & 1]);
        if (k < 5 - HOLD) {
          gelu_store(held, base + oad + k * 16384 + (k == 4 ? last : 0));
          float z;
          asm volatile("ld.volatile.shared.f32 %0, [%1];" : "=f"(z) : "r"(sb + OFF_F + 55 * 128) : "memory");
          s2[0] += z;
          s2[1] += z;
          __syncwarp();
          if (lane == 0) mbar_arrive(bar + B_OUT + 8 * (wg * 5 + k));
        }
      }
      if (tid == 0) PROF_T(8 + 3 * hf);
    }
    if (HOLD) {
      gelu_store(held, sb + 4 * 16384 + oad);
      __syncwarp();
      if (lane == 0) mbar_arrive(bar + B_OUT + 8 * (wg * 5 + 4));
    }
    asm volatile("barrier.cluster.arrive.relaxed.aligned;\nbarrier.cluster.wait.aligned;" ::: "memory");
  }
}

typedef CUresult (*EncFn)(CUtensorMap*, CUtensorMapDataType, cuuint32_t, void*, const cuuint64_t*, const cuuint64_t*, const cuuint32_t*,
                          const cuuint32_t*, CUtensorMapInterleave, CUtensorMapSwizzle, CUtensorMapL2promotion, CUtensorMapFloatOOBfill);

void encode(EncFn fn, CUtensorMap* m, int rank, void* base, const cuuint64_t* dims, const cuuint64_t* strides, const cuuint32_t* box,
            CUtensorMapL2promotion promo) {
  cuuint32_t es[5] = {1, 1, 1, 1, 1};
  fn(m, CU_TENSOR_MAP_DATA_TYPE_BFLOAT16, rank, base, dims, strides, box, es, CU_TENSOR_MAP_INTERLEAVE_NONE, CU_TENSOR_MAP_SWIZZLE_128B, promo,
     CU_TENSOR_MAP_FLOAT_OOB_FILL_NONE);
}

}

extern "C" void kernel_launch(void* const* d_in, const int* in_sizes, int n_in, void* d_out, int out_size) {
  (void)in_sizes; (void)n_in; (void)out_size;
  const __nv_bfloat16* x = (const __nv_bfloat16*)d_in[0];
  const __nv_bfloat16* w = (const __nv_bfloat16*)d_in[1];
  const __nv_bfloat16* gamma = (const __nv_bfloat16*)d_in[2];
  const __nv_bfloat16* beta = (const __nv_bfloat16*)d_in[3];
  void* fnp = nullptr;
  cudaDriverEntryPointQueryResult qr;
  cudaGetDriverEntryPoint("cuTensorMapEncodeTiled", &fnp, cudaEnableDefault, &qr);
  EncFn fn = (EncFn)fnp;
  void *cptr = nullptr, *fptr = nullptr, *xptr = nullptr, *wptr = nullptr, *yptr = nullptr;
  cudaGetSymbolAddress(&cptr, g_ctr);
  cudaGetSymbolAddress(&fptr, g_Fimg);
  cudaGetSymbolAddress(&xptr, g_X);
  cudaGetSymbolAddress(&wptr, g_W);
  cudaGetSymbolAddress(&yptr, g_Y);
  xptr = (void*)(((uintptr_t)xptr + (1u << 21) - 1) & ~(uintptr_t)((1u << 21) - 1));
  const CUtensorMapL2promotion P0 = CU_TENSOR_MAP_L2_PROMOTION_NONE, P128 = CU_TENSOR_MAP_L2_PROMOTION_L2_128B;
  Maps m;
  {
    cuuint64_t d[3] = {1024, 8000, 2}, s[2] = {2048, 8000ull * 2048};
    cuuint32_t bx[3] = {64, 64, 1};
    encode(fn, &m.x, 3, (void*)x, d, s, bx, P128);
  }
  for (int ph = 0; ph < 2; ph++) {
    cuuint64_t d[3] = {64, (cuuint64_t)(16 - ph), 4096}, s[2] = {2ull * 262144 * 2, 128};
    cuuint32_t bx[3] = {64, 16, 1};
    encode(fn, ph ? &m.wo : &m.we, 3, (void*)(w + (size_t)ph * 262144), d, s, bx, P128);
  }
  for (int par = 0; par < 2; par++) {
    cuuint64_t d[5] = {(cuuint64_t)XPAGES << 20, 2, 4, 2, 2}, s[4] = {par ? 0x1000u : 0x3000u, 1u << 14, 1u << 18, 1u << 20};
    cuuint32_t bx[5] = {64, 2, 4, 2, 2};
    encode(fn, &m.xst[par], 5, xptr, d, s, bx, P0);
  }
  {
    cuuint64_t d[4] = {64, 32, 2, (cuuint64_t)WR * WCHUNK / 128}, s[3] = {4ull * WBLK, 4096, 128};
    cuuint32_t bx[4] = {64, 32, 2, 1};
    encode(fn, &m.wst, 4, wptr, d, s, bx, P0);
  }
  for (int p = 0; p < 2; p++) {
    void* base = p ? wptr : yptr;
    cuuint64_t d[4] = {64, NT, 64, 8}, s[3] = {8192, 128, (cuuint64_t)NT * 8192};
    cuuint32_t bx[4] = {64, 32, 2, 1};
    encode(fn, &m.yst[p], 4, base, d, s, bx, P0);
    cuuint64_t d2[2] = {64, 8ull * NT * 64}, s2[1] = {128};
    cuuint32_t bx2[2] = {64, 128};
    encode(fn, &m.yld[p], 2, base, d2, s2, bx2, P128);
  }
  {
    cuuint64_t d[3] = {512, LOUT, 2}, s[2] = {1024, (cuuint64_t)LOUT * 1024};
    cuuint32_t bx[3] = {64, MT, 1};
    encode(fn, &m.out, 3, d_out, d, s, bx, P0);
  }
  for (int q = 0; q < 2; q++) {
    cuuint64_t d[3] = {512, (cuuint64_t)(NT - q), 2}, s[2] = {MT * 2048, 8000ull * 2048};
    cuuint32_t bx[3] = {64, NT, 1};
    encode(fn, &m.xe[q], 3, (void*)(x + q * 64 * 1024), d, s, bx, P128);
  }
  {
    cuuint64_t d[2] = {512, 512}, s[1] = {1024};
    cuuint32_t bx[2] = {64, 64};
    encode(fn, &m.w30, 2, (void*)(w + 30 * 262144), d, s, bx, P128);
  }
  cudaFuncSetAttribute(k1_main, cudaFuncAttributeMaxDynamicSharedMemorySize, SMEM_BYTES);
  k1_main<<<132, 512, SMEM_BYTES>>>((uint8_t*)xptr, fptr, (unsigned*)cptr, gamma, beta, m);
}
```

```cpp
#include <cuda_runtime.h>
#include <cuda_bf16.h>
#include <cuda.h>
#include <stdint.h>

namespace {

constexpr int LOUT = 7985;
constexpr int MT = 50;
constexpr int NT = 160;
constexpr int XBLK = NT * 128;
constexpr int WBLK = 16384;
constexpr int LW = 4;
constexpr int WR = 5;
constexpr int WCHUNK = 32 * 4 * WBLK;
constexpr int XPAGES = 20;
constexpr int NFL = 2;
constexpr int XKEEP = 9;
constexpr int YSTEP = 2;
constexpr int YFLUSH = 17 + LW + 3 * YSTEP;

__device__ __align__(1024) uint8_t g_X[(XPAGES + 2) << 21];
__device__ __align__(1024) uint8_t g_W[(size_t)WR * WCHUNK];
__device__ __align__(1024) uint8_t g_Y[8ull * NT * 8192];
__device__ __align__(128) float g_E[16 * NT * 64];
__device__ unsigned long long g_part[128 * 128];
constexpr int C_FLAG = 0, C_LOADED = 36, C_REG = 68, C_EXIT = 69, C_E = 70, C_NUM = 71;
__device__ __align__(128) unsigned g_ctr[C_NUM * 32];
#define PROF_T(i)
#define PROF_C(i)
#define PROF_V(i, v)
#define PROF_W(acc, stmt) stmt

__device__ __align__(128) const uint32_t g_Fimg[2048] = {
 0x3f803f80,0x3f7d3f7f,0x3f783f7b,0x3f713f75,0x3f673f6d,0x3f5c3f62,0x3f4e3f55,0x3f3e3f46,0x3f2c3f35,0x3f183f22,0x3f043f0e,0x3edb3ef1,0x3eac3ec4,0x3e793e95,0x3e163e48,0x3d493dc9,
 0xbd490000,0xbe16bdc9,0xbe79be48,0xbeacbe95,0xbedbbec4,0xbf04bef1,0xbf18bf0e,0xbf2cbf22,0xbf3ebf35,0xbf4ebf46,0xbf5cbf55,0xbf67bf62,0xbf71bf6d,0xbf78bf75,0xbf7dbf7b,0xbf80bf7f,
 0x3e793ec4,0xbd493dc9,0xbeacbe48,0xbf18bef1,0x3f7d3f80,0x3f673f75,0x3f3e3f55,0x3f043f22,0xbf5cbf6d,0xbf2cbf46,0xbedbbf0e,0xbe16be95,0xbf4ebf35,0xbf71bf62,0xbf80bf7b,0xbf78bf7f,
 0x3f783f6d,0x3f803f7f,0x3f713f7b,0x3f4e3f62,0x3e160000,0x3edb3e95,0x3f2c3f0e,0x3f5c3f46,0xbf04bec4,0xbf3ebf22,0xbf67bf55,0xbf7dbf75,0x3f183f35,0x3eac3ef1,0x3d493e48,0xbe79bdc9,
 0xbf04bf35,0xbd49be95,0x3edb3e48,0x3f4e3f22,0x3f7d3f6d,0x3f713f7f,0x3f2c3f55,0x3e793ef1,0x3f783f80,0x3f3e3f62,0x3eac3f0e,0xbe163dc9,0xbf18bec4,0xbf67bf46,0xbf80bf7b,0xbf5cbf75,
 0x3f5c3f35,0x3f803f75,0x3f673f7b,0x3f183f46,0x3e163ec4,0xbeacbdc9,0xbf3ebf0e,0xbf78bf62,0xbe790000,0xbf2cbef1,0xbf71bf55,0xbf7dbf7f,0xbf4ebf6d,0xbedbbf22,0x3d49be48,0x3f043e95,
 0xbf2cbec4,0xbf7dbf62,0xbf5cbf7b,0xbeacbf22,0x3f673f35,0x3f783f7f,0x3f183f55,0xbd493e95,0xbf80bf6d,0xbf4ebf75,0xbe79bf0e,0x3edb3dc9,0x3f713f80,0x3f043f46,0xbe163e48,0xbf3ebef1,
 0x3f3e3f6d,0x3e163ef1,0xbf04be48,0xbf71bf46,0xbedbbf35,0x3e79bdc9,0x3f4e3f0e,0x3f803f75,0x3d493ec4,0xbf18be95,0xbf78bf55,0xbf67bf7f,0x3eac0000,0x3f5c3f22,0x3f7d3f7b,0x3f2c3f62,
 0xbedb0000,0xbf78bf46,0xbf4ebf7b,0xbd49bef1,0x3f3e3ec4,0x3f7d3f75,0x3f043f55,0xbeac3dc9,0xbf71bf35,0xbf5cbf7f,0xbe16bf0e,0x3f2c3e95,0x3f803f6d,0x3f183f62,0xbe793e48,0xbf67bf22,
 0x3f673f80,0x3e793f22,0xbf18be48,0xbf80bf62,0xbf2cbf6d,0x3e16be95,0x3f5c3f0e,0x3f713f7f,0x3eac3f35,0xbf04bdc9,0xbf7dbf55,0xbf3ebf75,0x3d49bec4,0x3f4e3ef1,0x3f783f7b,0x3edb3f46,
 0xbf7dbf6d,0xbeacbf46,0x3f2c3e48,0x3f783f75,0x3f040000,0x3f803f62,0x3edb3f55,0xbf18bdc9,0x3f4e3ec4,0x3f673f7f,0x3d493f0e,0xbf5cbef1,0x3e793f35,0xbf3ebe95,0xbf71bf7b,0xbe16bf22,
 0x3e16bec4,0x3f713f22,0x3f3e3f7b,0xbe793e95,0x3f5c3f80,0xbd493ef1,0xbf67bf0e,0xbf4ebf7f,0x3f183f6d,0xbedb3dc9,0xbf80bf55,0xbf04bf62,0xbf78bf35,0xbf2cbf75,0x3eacbe48,0x3f7d3f46,
 0x3f7d3f35,0x3edb3f62,0xbf3ebe48,0xbf5cbf7f,0x3e79bec4,0x3f803f46,0x3eac3f55,0xbf4ebe95,0xbf180000,0xbf71bf75,0x3d49bf0e,0x3f783f22,0x3f043f6d,0xbf2cbdc9,0xbf67bf7b,0x3e16bef1,
 0xbe16bf35,0x3f673ef1,0x3f2c3f7b,0xbf043dc9,0xbf78bf6d,0xbd49bf22,0x3f713f0e,0x3f183f75,0x3f4e3f80,0xbeac3e95,0xbf80bf55,0xbe79bf46,0x3f5c3ec4,0x3f3e3f7f,0xbedb3e48,0xbf7dbf62,
 0xbedbbf6d,0x3f5c3e95,0x3f183f7b,0xbf3ebdc9,0xbd49bf35,0x3f7d3f22,0x3e793f55,0xbf71bef1,0x3eacbec4,0x3f783f62,0xbe163f0e,0xbf80bf46,0x3f2c0000,0x3f4e3f7f,0xbf043e48,0xbf67bf75,
 0x3f673ec4,0x3f043f75,0xbf4ebe48,0xbf2cbf7f,0x3f803f35,0x3e163f46,0xbf78bf0e,0xbeacbf62,0x3f713f6d,0xbe793ef1,0xbf7dbf55,0x3d49bf22,0x3f3e3f80,0xbf183dc9,0xbf5cbf7b,0x3edbbe95,
 0xbd490000,0xbe16bdc9,0xbe79be48,0xbeacbe95,0xbedbbec4,0xbf04bef1,0xbf18bf0e,0xbf2cbf22,0xbf3ebf35,0xbf4ebf46,0xbf5cbf55,0xbf67bf62,0xbf71bf6d,0xbf78bf75,0xbf7dbf7b,0xbf80bf7f,
 0xbf80bf80,0xbf7dbf7f,0xbf78bf7b,0xbf71bf75,0xbf67bf6d,0xbf5cbf62,0xbf4ebf55,0xbf3ebf46,0xbf2cbf35,0xbf18bf22,0xbf04bf0e,0xbedbbef1,0xbeacbec4,0xbe79be95,0xbe16be48,0xbd49bdc9,
 0xbf78bf6d,0xbf80bf7f,0xbf71bf7b,0xbf4ebf62,0xbe160000,0xbedbbe95,0xbf2cbf0e,0xbf5cbf46,0x3f043ec4,0x3f3e3f22,0x3f673f55,0x3f7d3f75,0xbf18bf35,0xbeacbef1,0xbd49be48,0x3e793dc9,
 0x3e793ec4,0xbd493dc9,0xbeacbe48,0xbf18bef1,0x3f7d3f80,0x3f673f75,0x3f3e3f55,0x3f043f22,0xbf5cbf6d,0xbf2cbf46,0xbedbbf0e,0xbe16be95,0xbf4ebf35,0xbf71bf62,0xbf80bf7b,0xbf78bf7f,
 0x3f5c3f35,0x3f803f75,0x3f673f7b,0x3f183f46,0x3e163ec4,0xbeacbdc9,0xbf3ebf0e,0xbf78bf62,0xbe790000,0xbf2cbef1,0xbf71bf55,0xbf7dbf7f,0xbf4ebf6d,0xbedbbf22,0x3d49be48,0x3f043e95,
 0x3f043f35,0x3d493e95,0xbedbbe48,0xbf4ebf22,0xbf7dbf6d,0xbf71bf7f,0xbf2cbf55,0xbe79bef1,0xbf78bf80,0xbf3ebf62,0xbeacbf0e,0x3e16bdc9,0x3f183ec4,0x3f673f46,0x3f803f7b,0x3f5c3f75,
 0xbf3ebf6d,0xbe16bef1,0x3f043e48,0x3f713f46,0x3edb3f35,0xbe793dc9,0xbf4ebf0e,0xbf80bf75,0xbd49bec4,0x3f183e95,0x3f783f55,0x3f673f7f,0xbeac0000,0xbf5cbf22,0xbf7dbf7b,0xbf2cbf62,
 0xbf2cbec4,0xbf7dbf62,0xbf5cbf7b,0xbeacbf22,0x3f673f35,0x3f783f7f,0x3f183f55,0xbd493e95,0xbf80bf6d,0xbf4ebf75,0xbe79bf0e,0x3edb3dc9,0x3f713f80,0x3f043f46,0xbe163e48,0xbf3ebef1,
 0xbf67bf80,0xbe79bf22,0x3f183e48,0x3f803f62,0x3f2c3f6d,0xbe163e95,0xbf5cbf0e,0xbf71bf7f,0xbeacbf35,0x3f043dc9,0x3f7d3f55,0x3f3e3f75,0xbd493ec4,0xbf4ebef1,0xbf78bf7b,0xbedbbf46,
 0xbedb0000,0xbf78bf46,0xbf4ebf7b,0xbd49bef1,0x3f3e3ec4,0x3f7d3f75,0x3f043f55,0xbeac3dc9,0xbf71bf35,0xbf5cbf7f,0xbe16bf0e,0x3f2c3e95,0x3f803f6d,0x3f183f62,0xbe793e48,0xbf67bf22,
 0x3e16bec4,0x3f713f22,0x3f3e3f7b,0xbe793e95,0x3f5c3f80,0xbd493ef1,0xbf67bf0e,0xbf4ebf7f,0x3f183f6d,0xbedb3dc9,0xbf80bf55,0xbf04bf62,0xbf78bf35,0xbf2cbf75,0x3eacbe48,0x3f7d3f46,
 0x3f7d3f6d,0x3eac3f46,0xbf2cbe48,0xbf78bf75,0xbf040000,0xbf80bf62,0xbedbbf55,0x3f183dc9,0xbf4ebec4,0xbf67bf7f,0xbd49bf0e,0x3f5c3ef1,0xbe79bf35,0x3f3e3e95,0x3f713f7b,0x3e163f22,
 0x3e163f35,0xbf67bef1,0xbf2cbf7b,0x3f04bdc9,0x3f783f6d,0x3d493f22,0xbf71bf0e,0xbf18bf75,0xbf4ebf80,0x3eacbe95,0x3f803f55,0x3e793f46,0xbf5cbec4,0xbf3ebf7f,0x3edbbe48,0x3f7d3f62,
 0x3f7d3f35,0x3edb3f62,0xbf3ebe48,0xbf5cbf7f,0x3e79bec4,0x3f803f46,0x3eac3f55,0xbf4ebe95,0xbf180000,0xbf71bf75,0x3d49bf0e,0x3f783f22,0x3f043f6d,0xbf2cbdc9,0xbf67bf7b,0x3e16bef1,
 0x3f673ec4,0x3f043f75,0xbf4ebe48,0xbf2cbf7f,0x3f803f35,0x3e163f46,0xbf78bf0e,0xbeacbf62,0x3f713f6d,0xbe793ef1,0xbf7dbf55,0x3d49bf22,0x3f3e3f80,0xbf183dc9,0xbf5cbf7b,0x3edbbe95,
 0x3edb3f6d,0xbf5cbe95,0xbf18bf7b,0x3f3e3dc9,0x3d493f35,0xbf7dbf22,0xbe79bf55,0x3f713ef1,0xbeac3ec4,0xbf78bf62,0x3e16bf0e,0x3f803f46,0xbf2c0000,0xbf4ebf7f,0x3f04be48,0x3f673f75,
 0x3f2c3f80,0xbf4ebdc9,0xbf04bf7b,0x3f673e95,0x3eac3f6d,0xbf78bef1,0xbe16bf55,0x3f803f22,0xbd493f35,0xbf7dbf46,0x3e79bf0e,0x3f713f62,0xbedb3ec4,0xbf5cbf75,0x3f18be48,0x3f3e3f7f,
 0xbf3e0000,0xbf18bf7f,0x3f5c3e48,0x3edb3f75,0xbf71bec4,0xbe79bf62,0x3f7d3f0e,0x3d493f46,0xbf80bf35,0x3e16bf22,0x3f783f55,0xbeac3ef1,0xbf67bf6d,0x3f04be95,0x3f4e3f7b,0xbf2c3dc9,
 0xbf043ec4,0xbf2cbf7f,0x3f673e48,0x3e163f62,0x3f183f80,0xbf71be95,0xbd49bf55,0x3f783f46,0xbe79bf6d,0x3f803f22,0xbeac3f0e,0xbf4ebf75,0xbf7dbf35,0x3edbbef1,0x3f3e3f7b,0xbf5cbdc9,
 0x3f5c3f6d,0xbf3e3dc9,0xbedbbf7b,0x3f7d3ef1,0x3f4e0000,0x3eac3f75,0xbf80bf0e,0x3e79bf22,0xbf78bec4,0x3d49bf46,0x3f713f55,0xbf183e95,0xbe163f35,0xbf67bf62,0x3f2cbe48,0x3f043f7f,
 0x3e79bf35,0x3f3e3f75,0xbf71be48,0x3e16bf46,0x3f4e3f6d,0xbf67bdc9,0x3d49bf55,0x3f5c3f62,0x3f043f80,0xbf80bef1,0x3edbbf0e,0x3f183f7f,0xbf7dbec4,0x3eacbf22,0x3f2c3f7b,0xbf78be95,
 0x3f783f35,0xbf2c3e95,0xbeacbf7b,0x3f7d3f22,0xbf183ec4,0xbedbbf7f,0x3f803f0e,0xbf043ef1,0xbf5c0000,0xbd49bf62,0x3f673f55,0xbf4e3dc9,0xbe16bf6d,0x3f713f46,0xbf3e3e48,0xbe79bf75,
 0xbf80bec4,0x3f18bef1,0x3e793f7b,0xbf67bf46,0x3f713f35,0xbf5c3dc9,0x3e16bf55,0x3f2c3f75,0xbf3ebf6d,0x3f7d3e95,0xbf043f0e,0xbeacbf7f,0x3edb3f80,0xbf78bf22,0x3f4ebe48,0xbd493f62,
 0x3d493f6d,0xbf4ebf62,0x3f783e48,0xbedb3f22,0x3eacbf35,0x3f043f7f,0xbf7dbf0e,0x3f3ebe95,0xbf2c3ec4,0xbe16bf75,0x3f5c3f55,0xbf71bdc9,0x3f670000,0xbe793f46,0xbf18bf7b,0x3f803ef1,
 0xbf710000,0x3f04bf22,0x3e163f7b,0xbf3ebf62,0x3f803ec4,0xbf4e3e95,0x3e79bf55,0x3edb3f7f,0xbf67bf35,0x3f783dc9,0xbf183f0e,0xbd49bf75,0x3f2c3f6d,0xbf7dbef1,0x3f5cbe48,0xbeac3f46,
 0x3eac3f80,0xbf5cbf46,0x3f7d3e48,0xbf2c3ef1,0x3d49bf6d,0x3f183f75,0xbf78bf0e,0x3f67bdc9,0xbedb3f35,0xbe79bf7f,0x3f4e3f55,0xbf80be95,0x3f3ebec4,0xbe163f62,0xbf04bf7b,0x3f713f22,
 0xbf18bf6d,0x3f673f22,0xbf80be48,0x3f5cbe95,0x3f780000,0xbf3e3ef1,0x3eacbf55,0x3e163f7f,0x3f7d3ec4,0xbf713dc9,0x3f2cbf0e,0xbe793f62,0xbf043f35,0x3d49bf75,0x3edb3f7b,0xbf4ebf46,
 0x3f4ebec4,0xbedb3f46,0xbd49bf7b,0x3f043f75,0x3e793f80,0xbf2cbf62,0x3f713f0e,0xbf7dbdc9,0xbe163f6d,0xbeacbf7f,0x3f3e3f55,0xbf78bef1,0xbf5cbf35,0x3f803e95,0xbf673e48,0x3f18bf22,
 0x3f4e3f35,0xbf71bef1,0x3f803e48,0xbf783dc9,0x3f5cbec4,0xbf2c3f22,0x3edbbf55,0xbe163f75,0xbf7d0000,0x3f67be95,0xbf3e3f0e,0x3f04bf46,0xbe793f6d,0xbd49bf7f,0x3eac3f7b,0xbf18bf62,
 0x3f18bf35,0xbeac3f62,0x3d49bf7b,0x3e793f7f,0xbf04bf6d,0x3f3e3f46,0xbf67bf0e,0x3f7d3e95,0x3e163f80,0xbedbbf75,0x3f2c3f55,0xbf5cbf22,0x3f783ec4,0xbf80bdc9,0x3f71be48,0xbf4e3ef1,
 0x3eacbf6d,0xbe793f75,0x3e16bf7b,0xbd493f7f,0x3f2cbf35,0xbf183f46,0x3f04bf55,0xbedb3f62,0x3f67bec4,0xbf5c3ef1,0x3f4ebf0e,0xbf3e3f22,0x3f800000,0xbf7d3dc9,0x3f78be48,0xbf713e95,
 0x3f713ec4,0xbf78be95,0x3f7d3e48,0xbf80bdc9,0x3f3e3f35,0xbf4ebf22,0x3f5c3f0e,0xbf67bef1,0x3edb3f6d,0xbf04bf62,0x3f183f55,0xbf2cbf46,0x3d493f80,0xbe16bf7f,0x3e793f7b,0xbeacbf75,
 0xbf3e0000,0xbf18bf7f,0x3f5c3e48,0x3edb3f75,0xbf71bec4,0xbe79bf62,0x3f7d3f0e,0x3d493f46,0xbf80bf35,0x3e16bf22,0x3f783f55,0xbeac3ef1,0xbf67bf6d,0x3f04be95,0x3f4e3f7b,0xbf2c3dc9,
 0xbf2cbf80,0x3f4e3dc9,0x3f043f7b,0xbf67be95,0xbeacbf6d,0x3f783ef1,0x3e163f55,0xbf80bf22,0x3d49bf35,0x3f7d3f46,0xbe793f0e,0xbf71bf62,0x3edbbec4,0x3f5c3f75,0xbf183e48,0xbf3ebf7f,
 0xbf5cbf6d,0x3f3ebdc9,0x3edb3f7b,0xbf7dbef1,0xbf4e0000,0xbeacbf75,0x3f803f0e,0xbe793f22,0x3f783ec4,0xbd493f46,0xbf71bf55,0x3f18be95,0x3e16bf35,0x3f673f62,0xbf2c3e48,0xbf04bf7f,
 0xbf043ec4,0xbf2cbf7f,0x3f673e48,0x3e163f62,0x3f183f80,0xbf71be95,0xbd49bf55,0x3f783f46,0xbe79bf6d,0x3f803f22,0xbeac3f0e,0xbf4ebf75,0xbf7dbf35,0x3edbbef1,0x3f3e3f7b,0xbf5cbdc9,
 0x3f783f35,0xbf2c3e95,0xbeacbf7b,0x3f7d3f22,0xbf183ec4,0xbedbbf7f,0x3f803f0e,0xbf043ef1,0xbf5c0000,0xbd49bf62,0x3f673f55,0xbf4e3dc9,0xbe16bf6d,0x3f713f46,0xbf3e3e48,0xbe79bf75,
 0xbe793f35,0xbf3ebf75,0x3f713e48,0xbe163f46,0xbf4ebf6d,0x3f673dc9,0xbd493f55,0xbf5cbf62,0xbf04bf80,0x3f803ef1,0xbedb3f0e,0xbf18bf7f,0x3f7d3ec4,0xbeac3f22,0xbf2cbf7b,0x3f783e95,
 0xbd49bf6d,0x3f4e3f62,0xbf78be48,0x3edbbf22,0xbeac3f35,0xbf04bf7f,0x3f7d3f0e,0xbf3e3e95,0x3f2cbec4,0x3e163f75,0xbf5cbf55,0x3f713dc9,0xbf670000,0x3e79bf46,0x3f183f7b,0xbf80bef1,
 0xbf80bec4,0x3f18bef1,0x3e793f7b,0xbf67bf46,0x3f713f35,0xbf5c3dc9,0x3e16bf55,0x3f2c3f75,0xbf3ebf6d,0x3f7d3e95,0xbf043f0e,0xbeacbf7f,0x3edb3f80,0xbf78bf22,0x3f4ebe48,0xbd493f62,
 0xbeacbf80,0x3f5c3f46,0xbf7dbe48,0x3f2cbef1,0xbd493f6d,0xbf18bf75,0x3f783f0e,0xbf673dc9,0x3edbbf35,0x3e793f7f,0xbf4ebf55,0x3f803e95,0xbf3e3ec4,0x3e16bf62,0x3f043f7b,0xbf71bf22,
 0xbf710000,0x3f04bf22,0x3e163f7b,0xbf3ebf62,0x3f803ec4,0xbf4e3e95,0x3e79bf55,0x3edb3f7f,0xbf67bf35,0x3f783dc9,0xbf183f0e,0xbd49bf75,0x3f2c3f6d,0xbf7dbef1,0x3f5cbe48,0xbeac3f46,
 0x3f4ebec4,0xbedb3f46,0xbd49bf7b,0x3f043f75,0x3e793f80,0xbf2cbf62,0x3f713f0e,0xbf7dbdc9,0xbe163f6d,0xbeacbf7f,0x3f3e3f55,0xbf78bef1,0xbf5cbf35,0x3f803e95,0xbf673e48,0x3f18bf22,
 0x3f183f6d,0xbf67bf22,0x3f803e48,0xbf5c3e95,0xbf780000,0x3f3ebef1,0xbeac3f55,0xbe16bf7f,0xbf7dbec4,0x3f71bdc9,0xbf2c3f0e,0x3e79bf62,0x3f04bf35,0xbd493f75,0xbedbbf7b,0x3f4e3f46,
 0xbf183f35,0x3eacbf62,0xbd493f7b,0xbe79bf7f,0x3f043f6d,0xbf3ebf46,0x3f673f0e,0xbf7dbe95,0xbe16bf80,0x3edb3f75,0xbf2cbf55,0x3f5c3f22,0xbf78bec4,0x3f803dc9,0xbf713e48,0x3f4ebef1,
 0x3f4e3f35,0xbf71bef1,0x3f803e48,0xbf783dc9,0x3f5cbec4,0xbf2c3f22,0x3edbbf55,0xbe163f75,0xbf7d0000,0x3f67be95,0xbf3e3f0e,0x3f04bf46,0xbe793f6d,0xbd49bf7f,0x3eac3f7b,0xbf18bf62,
 0x3f713ec4,0xbf78be95,0x3f7d3e48,0xbf80bdc9,0x3f3e3f35,0xbf4ebf22,0x3f5c3f0e,0xbf67bef1,0x3edb3f6d,0xbf04bf62,0x3f183f55,0xbf2cbf46,0x3d493f80,0xbe16bf7f,0x3e793f7b,0xbeacbf75,
 0xbeac3f6d,0x3e79bf75,0xbe163f7b,0x3d49bf7f,0xbf2c3f35,0x3f18bf46,0xbf043f55,0x3edbbf62,0xbf673ec4,0x3f5cbef1,0xbf4e3f0e,0x3f3ebf22,0xbf800000,0x3f7dbdc9,0xbf783e48,0x3f71be95,
 0xbd493f80,0x3e16bf7f,0xbe793f7b,0x3eacbf75,0xbedb3f6d,0x3f04bf62,0xbf183f55,0x3f2cbf46,0xbf3e3f35,0x3f4ebf22,0xbf5c3f0e,0x3f67bef1,0xbf713ec4,0x3f78be95,0xbf7d3e48,0x3f80bdc9,
 0xbf800000,0x3f7d3dc9,0xbf78be48,0x3f713e95,0xbf67bec4,0x3f5c3ef1,0xbf4ebf0e,0x3f3e3f22,0xbf2cbf35,0x3f183f46,0xbf04bf55,0x3edb3f62,0xbeacbf6d,0x3e793f75,0xbe16bf7b,0x3d493f7f,
 0xbf783ec4,0x3f80bdc9,0xbf71be48,0x3f4e3ef1,0xbe163f80,0x3edbbf75,0xbf2c3f55,0x3f5cbf22,0x3f04bf6d,0xbf3e3f46,0x3f67bf0e,0xbf7d3e95,0xbf18bf35,0x3eac3f62,0xbd49bf7b,0xbe793f7f,
 0x3e793f6d,0x3d49bf7f,0xbeac3f7b,0x3f18bf62,0x3f7d0000,0xbf67be95,0x3f3e3f0e,0xbf04bf46,0xbf5cbec4,0x3f2c3f22,0xbedbbf55,0x3e163f75,0xbf4e3f35,0x3f71bef1,0xbf803e48,0x3f783dc9,
 0x3f5cbf35,0xbf803e95,0x3f673e48,0xbf18bf22,0x3e163f6d,0x3eacbf7f,0xbf3e3f55,0x3f78bef1,0xbe793f80,0x3f2cbf62,0xbf713f0e,0x3f7dbdc9,0xbf4ebec4,0x3edb3f46,0x3d49bf7b,0xbf043f75,
 0x3f043f35,0xbd49bf75,0xbedb3f7b,0x3f4ebf46,0xbf7d3ec4,0x3f713dc9,0xbf2cbf0e,0x3e793f62,0xbf780000,0x3f3e3ef1,0xbeacbf55,0xbe163f7f,0x3f18bf6d,0xbf673f22,0x3f80be48,0xbf5cbe95,
 0xbf3ebec4,0x3e163f62,0x3f04bf7b,0xbf713f22,0x3edb3f35,0x3e79bf7f,0xbf4e3f55,0x3f80be95,0xbd49bf6d,0xbf183f75,0x3f78bf0e,0xbf67bdc9,0xbeac3f80,0x3f5cbf46,0xbf7d3e48,0x3f2c3ef1,
 0xbf2c3f6d,0x3f7dbef1,0xbf5cbe48,0x3eac3f46,0x3f67bf35,0xbf783dc9,0x3f183f0e,0x3d49bf75,0xbf803ec4,0x3f4e3e95,0xbe79bf55,0xbedb3f7f,0x3f710000,0xbf04bf22,0xbe163f7b,0x3f3ebf62,
 0xbf670000,0x3e793f46,0x3f18bf7b,0xbf803ef1,0x3f2c3ec4,0x3e16bf75,0xbf5c3f55,0x3f71bdc9,0xbeacbf35,0xbf043f7f,0x3f7dbf0e,0xbf3ebe95,0xbd493f6d,0x3f4ebf62,0xbf783e48,0x3edb3f22,
 0xbedb3f80,0x3f78bf22,0xbf4ebe48,0x3d493f62,0x3f3ebf6d,0xbf7d3e95,0x3f043f0e,0x3eacbf7f,0xbf713f35,0x3f5c3dc9,0xbe16bf55,0xbf2c3f75,0x3f80bec4,0xbf18bef1,0xbe793f7b,0x3f67bf46,
 0x3e16bf6d,0xbf713f46,0x3f3e3e48,0x3e79bf75,0x3f5c0000,0x3d49bf62,0xbf673f55,0x3f4e3dc9,0x3f183ec4,0x3edbbf7f,0xbf803f0e,0x3f043ef1,0xbf783f35,0x3f2c3e95,0x3eacbf7b,0xbf7d3f22,
 0x3f7dbec4,0xbeacbf22,0xbf2c3f7b,0x3f78be95,0xbf043f80,0x3f80bef1,0xbedbbf0e,0xbf183f7f,0xbf4e3f6d,0x3f67bdc9,0xbd49bf55,0xbf5c3f62,0xbe79bf35,0xbf3e3f75,0x3f71be48,0xbe16bf46,
 0x3e163f35,0x3f67bf62,0xbf2cbe48,0xbf043f7f,0x3f78bec4,0xbd49bf46,0xbf713f55,0x3f183e95,0xbf4e0000,0xbeac3f75,0x3f80bf0e,0xbe79bf22,0xbf5c3f6d,0x3f3e3dc9,0x3edbbf7b,0xbf7d3ef1,
 0x3f7dbf35,0xbedbbef1,0xbf3e3f7b,0x3f5cbdc9,0x3e79bf6d,0xbf803f22,0x3eac3f0e,0x3f4ebf75,0xbf183f80,0x3f71be95,0x3d49bf55,0xbf783f46,0x3f043ec4,0x3f2cbf7f,0xbf673e48,0xbe163f62,
 0x3f67bf6d,0xbf04be95,0xbf4e3f7b,0x3f2c3dc9,0x3f80bf35,0xbe16bf22,0xbf783f55,0x3eac3ef1,0x3f71bec4,0x3e79bf62,0xbf7d3f0e,0xbd493f46,0x3f3e0000,0x3f18bf7f,0xbf5c3e48,0xbedb3f75,
 0x3edb3ec4,0x3f5cbf75,0xbf18be48,0xbf3e3f7f,0x3d493f35,0x3f7dbf46,0xbe79bf0e,0xbf713f62,0xbeac3f6d,0x3f78bef1,0x3e16bf55,0xbf803f22,0xbf2c3f80,0x3f4ebdc9,0x3f04bf7b,0xbf673e95,
 0xbf800000,0x3f7d3dc9,0xbf78be48,0x3f713e95,0xbf67bec4,0x3f5c3ef1,0xbf4ebf0e,0x3f3e3f22,0xbf2cbf35,0x3f183f46,0xbf04bf55,0x3edb3f62,0xbeacbf6d,0x3e793f75,0xbe16bf7b,0x3d493f7f,
 0x3d49bf80,0xbe163f7f,0x3e79bf7b,0xbeac3f75,0x3edbbf6d,0xbf043f62,0x3f18bf55,0xbf2c3f46,0x3f3ebf35,0xbf4e3f22,0x3f5cbf0e,0xbf673ef1,0x3f71bec4,0xbf783e95,0x3f7dbe48,0xbf803dc9,
 0xbe79bf6d,0xbd493f7f,0x3eacbf7b,0xbf183f62,0xbf7d0000,0x3f673e95,0xbf3ebf0e,0x3f043f46,0x3f5c3ec4,0xbf2cbf22,0x3edb3f55,0xbe16bf75,0x3f4ebf35,0xbf713ef1,0x3f80be48,0xbf78bdc9,
 0xbf783ec4,0x3f80bdc9,0xbf71be48,0x3f4e3ef1,0xbe163f80,0x3edbbf75,0xbf2c3f55,0x3f5cbf22,0x3f04bf6d,0xbf3e3f46,0x3f67bf0e,0xbf7d3e95,0xbf18bf35,0x3eac3f62,0xbd49bf7b,0xbe793f7f,
 0x3f043f35,0xbd49bf75,0xbedb3f7b,0x3f4ebf46,0xbf7d3ec4,0x3f713dc9,0xbf2cbf0e,0x3e793f62,0xbf780000,0x3f3e3ef1,0xbeacbf55,0xbe163f7f,0x3f18bf6d,0xbf673f22,0x3f80be48,0xbf5cbe95,
 0xbf5c3f35,0x3f80be95,0xbf67be48,0x3f183f22,0xbe16bf6d,0xbeac3f7f,0x3f3ebf55,0xbf783ef1,0x3e79bf80,0xbf2c3f62,0x3f71bf0e,0xbf7d3dc9,0x3f4e3ec4,0xbedbbf46,0xbd493f7b,0x3f04bf75,
 0x3f2cbf6d,0xbf7d3ef1,0x3f5c3e48,0xbeacbf46,0xbf673f35,0x3f78bdc9,0xbf18bf0e,0xbd493f75,0x3f80bec4,0xbf4ebe95,0x3e793f55,0x3edbbf7f,0xbf710000,0x3f043f22,0x3e16bf7b,0xbf3e3f62,
 0xbf3ebec4,0x3e163f62,0x3f04bf7b,0xbf713f22,0x3edb3f35,0x3e79bf7f,0xbf4e3f55,0x3f80be95,0xbd49bf6d,0xbf183f75,0x3f78bf0e,0xbf67bdc9,0xbeac3f80,0x3f5cbf46,0xbf7d3e48,0x3f2c3ef1,
 0x3edbbf80,0xbf783f22,0x3f4e3e48,0xbd49bf62,0xbf3e3f6d,0x3f7dbe95,0xbf04bf0e,0xbeac3f7f,0x3f71bf35,0xbf5cbdc9,0x3e163f55,0x3f2cbf75,0xbf803ec4,0x3f183ef1,0x3e79bf7b,0xbf673f46,
 0xbf670000,0x3e793f46,0x3f18bf7b,0xbf803ef1,0x3f2c3ec4,0x3e16bf75,0xbf5c3f55,0x3f71bdc9,0xbeacbf35,0xbf043f7f,0x3f7dbf0e,0xbf3ebe95,0xbd493f6d,0x3f4ebf62,0xbf783e48,0x3edb3f22,
 0x3f7dbec4,0xbeacbf22,0xbf2c3f7b,0x3f78be95,0xbf043f80,0x3f80bef1,0xbedbbf0e,0xbf183f7f,0xbf4e3f6d,0x3f67bdc9,0xbd49bf55,0xbf5c3f62,0xbe79bf35,0xbf3e3f75,0x3f71be48,0xbe16bf46,
 0xbe163f6d,0x3f71bf46,0xbf3ebe48,0xbe793f75,0xbf5c0000,0xbd493f62,0x3f67bf55,0xbf4ebdc9,0xbf18bec4,0xbedb3f7f,0x3f80bf0e,0xbf04bef1,0x3f78bf35,0xbf2cbe95,0xbeac3f7b,0x3f7dbf22,
 0xbf7d3f35,0x3edb3ef1,0x3f3ebf7b,0xbf5c3dc9,0xbe793f6d,0x3f80bf22,0xbeacbf0e,0xbf4e3f75,0x3f18bf80,0xbf713e95,0xbd493f55,0x3f78bf46,0xbf04bec4,0xbf2c3f7f,0x3f67be48,0x3e16bf62,
 0x3e163f35,0x3f67bf62,0xbf2cbe48,0xbf043f7f,0x3f78bec4,0xbd49bf46,0xbf713f55,0x3f183e95,0xbf4e0000,0xbeac3f75,0x3f80bf0e,0xbe79bf22,0xbf5c3f6d,0x3f3e3dc9,0x3edbbf7b,0xbf7d3ef1,
 0x3edb3ec4,0x3f5cbf75,0xbf18be48,0xbf3e3f7f,0x3d493f35,0x3f7dbf46,0xbe79bf0e,0xbf713f62,0xbeac3f6d,0x3f78bef1,0x3e16bf55,0xbf803f22,0xbf2c3f80,0x3f4ebdc9,0x3f04bf7b,0xbf673e95,
 0xbf673f6d,0x3f043e95,0x3f4ebf7b,0xbf2cbdc9,0xbf803f35,0x3e163f22,0x3f78bf55,0xbeacbef1,0xbf713ec4,0xbe793f62,0x3f7dbf0e,0x3d49bf46,0xbf3e0000,0xbf183f7f,0x3f5cbe48,0x3edbbf75,
 0xbf3e3f80,0x3f183dc9,0x3f5cbf7b,0xbedbbe95,0xbf713f6d,0x3e793ef1,0x3f7dbf55,0xbd49bf22,0xbf803f35,0xbe163f46,0x3f78bf0e,0x3eacbf62,0xbf673ec4,0xbf043f75,0x3f4ebe48,0x3f2cbf7f,
 0xbf2c0000,0xbf4e3f7f,0x3f043e48,0x3f67bf75,0xbeacbec4,0xbf783f62,0x3e163f0e,0x3f80bf46,0x3d49bf35,0xbf7d3f22,0xbe793f55,0x3f71bef1,0x3edbbf6d,0xbf5c3e95,0xbf183f7b,0x3f3ebdc9,
 0xbf5c3ec4,0xbf3e3f7f,0x3edb3e48,0x3f7dbf62,0xbf4e3f80,0x3eac3e95,0x3f80bf55,0x3e79bf46,0x3f78bf6d,0x3d49bf22,0xbf713f0e,0xbf183f75,0x3e16bf35,0xbf673ef1,0xbf2c3f7b,0x3f043dc9,
 0xbf043f6d,0x3f2cbdc9,0x3f67bf7b,0xbe16bef1,0x3f180000,0x3f71bf75,0xbd49bf0e,0xbf783f22,0xbe79bec4,0xbf803f46,0xbeac3f55,0x3f4ebe95,0xbf7d3f35,0xbedb3f62,0x3f3ebe48,0x3f5cbf7f,
 0x3f78bf35,0x3f2cbf75,0xbeacbe48,0xbf7d3f46,0xbf183f6d,0x3edb3dc9,0x3f80bf55,0x3f04bf62,0xbf5c3f80,0x3d493ef1,0x3f67bf0e,0x3f4ebf7f,0xbe16bec4,0xbf713f22,0xbf3e3f7b,0x3e793e95,
 0xbe793f35,0x3f3ebe95,0x3f71bf7b,0x3e16bf22,0xbf4e3ec4,0xbf673f7f,0xbd493f0e,0x3f5cbef1,0xbf040000,0xbf803f62,0xbedb3f55,0x3f18bdc9,0x3f7dbf6d,0x3eacbf46,0xbf2c3e48,0xbf783f75,
 0xbd49bec4,0xbf4e3ef1,0xbf783f7b,0xbedb3f46,0xbeac3f35,0x3f04bdc9,0x3f7dbf55,0x3f3ebf75,0x3f2cbf6d,0xbe16be95,0xbf5c3f0e,0xbf713f7f,0xbf673f80,0xbe793f22,0x3f18be48,0x3f80bf62,
 0xbf803f6d,0xbf183f62,0x3e793e48,0x3f67bf22,0x3f71bf35,0x3f5cbf7f,0x3e16bf0e,0xbf2c3e95,0xbf3e3ec4,0xbf7d3f75,0xbf043f55,0x3eac3dc9,0x3edb0000,0x3f78bf46,0x3f4ebf7b,0x3d49bef1,
 0xbeac0000,0xbf5c3f22,0xbf7d3f7b,0xbf2c3f62,0xbd493ec4,0x3f18be95,0x3f78bf55,0x3f67bf7f,0x3edbbf35,0xbe79bdc9,0xbf4e3f0e,0xbf803f75,0xbf3e3f6d,0xbe163ef1,0x3f04be48,0x3f71bf46,
 0xbf713f80,0xbf043f46,0x3e163e48,0x3f3ebef1,0x3f80bf6d,0x3f4ebf75,0x3e79bf0e,0xbedb3dc9,0xbf673f35,0xbf783f7f,0xbf183f55,0x3d493e95,0x3f2cbec4,0x3f7dbf62,0x3f5cbf7b,0x3eacbf22,
 0x3f4ebf6d,0x3edbbf22,0xbd49be48,0xbf043e95,0x3e790000,0x3f2cbef1,0x3f71bf55,0x3f7dbf7f,0xbe163ec4,0x3eacbdc9,0x3f3ebf0e,0x3f78bf62,0xbf5c3f35,0xbf803f75,0xbf673f7b,0xbf183f46,
 0x3f18bec4,0x3f67bf46,0x3f80bf7b,0x3f5cbf75,0xbf783f80,0xbf3e3f62,0xbeac3f0e,0x3e163dc9,0xbf7d3f6d,0xbf713f7f,0xbf2c3f55,0xbe793ef1,0x3f04bf35,0x3d49be95,0xbedb3e48,0xbf4e3f22,
 0xbf183f35,0xbeac3ef1,0xbd493e48,0x3e79bdc9,0x3f04bec4,0x3f3ebf22,0x3f67bf55,0x3f7dbf75,0xbe160000,0xbedb3e95,0xbf2c3f0e,0xbf5c3f46,0xbf783f6d,0xbf803f7f,0xbf713f7b,0xbf4e3f62,
 0x3f4ebf35,0x3f71bf62,0x3f80bf7b,0x3f78bf7f,0x3f5cbf6d,0x3f2cbf46,0x3edbbf0e,0x3e16be95,0xbf7d3f80,0xbf673f75,0xbf3e3f55,0xbf043f22,0xbe793ec4,0x3d493dc9,0x3eacbe48,0x3f18bef1,
 0x3f71bf6d,0x3f78bf75,0x3f7dbf7b,0x3f80bf7f,0x3f3ebf35,0x3f4ebf46,0x3f5cbf55,0x3f67bf62,0x3edbbec4,0x3f04bef1,0x3f18bf0e,0x3f2cbf22,0x3d490000,0x3e16bdc9,0x3e79be48,0x3eacbe95,
 0xbeac3ec4,0xbe793e95,0xbe163e48,0xbd493dc9,0xbf2c3f35,0xbf183f22,0xbf043f0e,0xbedb3ef1,0xbf673f6d,0xbf5c3f62,0xbf4e3f55,0xbf3e3f46,0xbf803f80,0xbf7d3f7f,0xbf783f7b,0xbf713f75,
 0xbf2c0000,0xbf4e3f7f,0x3f043e48,0x3f67bf75,0xbeacbec4,0xbf783f62,0x3e163f0e,0x3f80bf46,0x3d49bf35,0xbf7d3f22,0xbe793f55,0x3f71bef1,0x3edbbf6d,0xbf5c3e95,0xbf183f7b,0x3f3ebdc9,
 0x3f3ebf80,0xbf18bdc9,0xbf5c3f7b,0x3edb3e95,0x3f71bf6d,0xbe79bef1,0xbf7d3f55,0x3d493f22,0x3f80bf35,0x3e16bf46,0xbf783f0e,0xbeac3f62,0x3f67bec4,0x3f04bf75,0xbf4e3e48,0xbf2c3f7f,
 0x3f04bf6d,0xbf2c3dc9,0xbf673f7b,0x3e163ef1,0xbf180000,0xbf713f75,0x3d493f0e,0x3f78bf22,0x3e793ec4,0x3f80bf46,0x3eacbf55,0xbf4e3e95,0x3f7dbf35,0x3edbbf62,0xbf3e3e48,0xbf5c3f7f,
 0xbf5c3ec4,0xbf3e3f7f,0x3edb3e48,0x3f7dbf62,0xbf4e3f80,0x3eac3e95,0x3f80bf55,0x3e79bf46,0x3f78bf6d,0x3d49bf22,0xbf713f0e,0xbf183f75,0x3e16bf35,0xbf673ef1,0xbf2c3f7b,0x3f043dc9,
 0xbe793f35,0x3f3ebe95,0x3f71bf7b,0x3e16bf22,0xbf4e3ec4,0xbf673f7f,0xbd493f0e,0x3f5cbef1,0xbf040000,0xbf803f62,0xbedb3f55,0x3f18bdc9,0x3f7dbf6d,0x3eacbf46,0xbf2c3e48,0xbf783f75,
 0xbf783f35,0xbf2c3f75,0x3eac3e48,0x3f7dbf46,0x3f18bf6d,0xbedbbdc9,0xbf803f55,0xbf043f62,0x3f5cbf80,0xbd49bef1,0xbf673f0e,0xbf4e3f7f,0x3e163ec4,0x3f71bf22,0x3f3ebf7b,0xbe79be95,
 0x3f80bf6d,0x3f18bf62,0xbe79be48,0xbf673f22,0xbf713f35,0xbf5c3f7f,0xbe163f0e,0x3f2cbe95,0x3f3ebec4,0x3f7dbf75,0x3f04bf55,0xbeacbdc9,0xbedb0000,0xbf783f46,0xbf4e3f7b,0xbd493ef1,
 0xbd49bec4,0xbf4e3ef1,0xbf783f7b,0xbedb3f46,0xbeac3f35,0x3f04bdc9,0x3f7dbf55,0x3f3ebf75,0x3f2cbf6d,0xbe16be95,0xbf5c3f0e,0xbf713f7f,0xbf673f80,0xbe793f22,0x3f18be48,0x3f80bf62,
 0x3f71bf80,0x3f04bf46,0xbe16be48,0xbf3e3ef1,0xbf803f6d,0xbf4e3f75,0xbe793f0e,0x3edbbdc9,0x3f67bf35,0x3f78bf7f,0x3f18bf55,0xbd49be95,0xbf2c3ec4,0xbf7d3f62,0xbf5c3f7b,0xbeac3f22,
 0xbeac0000,0xbf5c3f22,0xbf7d3f7b,0xbf2c3f62,0xbd493ec4,0x3f18be95,0x3f78bf55,0x3f67bf7f,0x3edbbf35,0xbe79bdc9,0xbf4e3f0e,0xbf803f75,0xbf3e3f6d,0xbe163ef1,0x3f04be48,0x3f71bf46,
 0x3f18bec4,0x3f67bf46,0x3f80bf7b,0x3f5cbf75,0xbf783f80,0xbf3e3f62,0xbeac3f0e,0x3e163dc9,0xbf7d3f6d,0xbf713f7f,0xbf2c3f55,0xbe793ef1,0x3f04bf35,0x3d49be95,0xbedb3e48,0xbf4e3f22,
 0xbf4e3f6d,0xbedb3f22,0x3d493e48,0x3f04be95,0xbe790000,0xbf2c3ef1,0xbf713f55,0xbf7d3f7f,0x3e16bec4,0xbeac3dc9,0xbf3e3f0e,0xbf783f62,0x3f5cbf35,0x3f80bf75,0x3f67bf7b,0x3f18bf46,
 0xbf4e3f35,0xbf713f62,0xbf803f7b,0xbf783f7f,0xbf5c3f6d,0xbf2c3f46,0xbedb3f0e,0xbe163e95,0x3f7dbf80,0x3f67bf75,0x3f3ebf55,0x3f04bf22,0x3e79bec4,0xbd49bdc9,0xbeac3e48,0xbf183ef1,
 0xbf183f35,0xbeac3ef1,0xbd493e48,0x3e79bdc9,0x3f04bec4,0x3f3ebf22,0x3f67bf55,0x3f7dbf75,0xbe160000,0xbedb3e95,0xbf2c3f0e,0xbf5c3f46,0xbf783f6d,0xbf803f7f,0xbf713f7b,0xbf4e3f62,
 0xbeac3ec4,0xbe793e95,0xbe163e48,0xbd493dc9,0xbf2c3f35,0xbf183f22,0xbf043f0e,0xbedb3ef1,0xbf673f6d,0xbf5c3f62,0xbf4e3f55,0xbf3e3f46,0xbf803f80,0xbf7d3f7f,0xbf783f7b,0xbf713f75,
 0xbf713f6d,0xbf783f75,0xbf7d3f7b,0xbf803f7f,0xbf3e3f35,0xbf4e3f46,0xbf5c3f55,0xbf673f62,0xbedb3ec4,0xbf043ef1,0xbf183f0e,0xbf2c3f22,0xbd490000,0xbe163dc9,0xbe793e48,0xbeac3e95,
};
__device__ __align__(128) const uint32_t g_Gimg[1792] = {
 0x00003d00,0x00003d00,0x00003d00,0x00003d00,0x00003d00,0x00003d00,0x00003d00,0x00003d00,0x00003d00,0x00003d00,0x00003d00,0x00003d00,0x00003d00,0x00003d00,0x00003d00,0x00003d00,
 0x00003d00,0x00003d00,0x00003d00,0x00003d00,0x00003d00,0x00003d00,0x00003d00,0x00003d00,0x00003d00,0x00003d00,0x00003d00,0x00003d00,0x00003d00,0x00003d00,0x00003d00,0x00003d00,
 0xbc5b3ce7,0xbc843cdc,0xbc983cce,0xbcac3cbe,0xbac93d00,0xbb963cfd,0xbbf93cf8,0xbc2c3cf1,0xbcf13c2c,0xbcf83bf9,0xbcfd3b96,0xbd003ac9,0xbcbe3cac,0xbcce3c98,0xbcdc3c84,0xbce73c5b,
 0xbce7bc5b,0xbcdcbc84,0xbccebc98,0xbcbebcac,0xbd00bac9,0xbcfdbb96,0xbcf8bbf9,0xbcf1bc2c,0xbc2cbcf1,0xbbf9bcf8,0xbb96bcfd,0xbac9bd00,0xbcacbcbe,0xbc98bcce,0xbc84bcdc,0xbc5bbce7,
 0xbcffbb49,0xbcf5bc15,0xbce2bc71,0xbcc6bca2,0xbca2bcc6,0xbc71bce2,0xbc15bcf5,0xbb49bcff,0xbb493cff,0xbc153cf5,0xbc713ce2,0xbca23cc6,0xbcc63ca2,0xbce23c71,0xbcf53c15,0xbcff3b49,
 0x3cff3b49,0x3cf53c15,0x3ce23c71,0x3cc63ca2,0x3ca23cc6,0x3c713ce2,0x3c153cf5,0x3b493cff,0x3b49bcff,0x3c15bcf5,0x3c71bce2,0x3ca2bcc6,0x3cc6bca2,0x3ce2bc71,0x3cf5bc15,0x3cffbb49,
 0x3c84bcdc,0x3cbebcac,0x3ce7bc5b,0x3cfdbb96,0xbc98bcce,0xbc2cbcf1,0xbac9bd00,0x3bf9bcf8,0xbcf83bf9,0xbd00bac9,0xbcf1bc2c,0xbccebc98,0xbb963cfd,0xbc5b3ce7,0xbcac3cbe,0xbcdc3c84,
 0xbcdcbc84,0xbcacbcbe,0xbc5bbce7,0xbb96bcfd,0xbcce3c98,0xbcf13c2c,0xbd003ac9,0xbcf8bbf9,0x3bf93cf8,0xbac93d00,0xbc2c3cf1,0xbc983cce,0x3cfd3b96,0x3ce73c5b,0x3cbe3cac,0x3c843cdc,
 0xbbc83cfb,0xbc8e3cd5,0xbcd53c8e,0xbcfb3bc8,0xbcfbbbc8,0xbcd5bc8e,0xbc8ebcd5,0xbbc8bcfb,0x3bc8bcfb,0x3c8ebcd5,0x3cd5bc8e,0x3cfbbbc8,0x3cfb3bc8,0x3cd53c8e,0x3c8e3cd5,0x3bc83cfb,
 0xbbc83cfb,0xbc8e3cd5,0xbcd53c8e,0xbcfb3bc8,0xbcfbbbc8,0xbcd5bc8e,0xbc8ebcd5,0xbbc8bcfb,0x3bc8bcfb,0x3c8ebcd5,0x3cd5bc8e,0x3cfbbbc8,0x3cfb3bc8,0x3cd53c8e,0x3c8e3cd5,0x3bc83cfb,
 0x3c98bcce,0x3ce7bc5b,0x3d003ac9,0x3cdc3c84,0xbcf8bbf9,0xbcbebcac,0xbc2cbcf1,0x3b96bcfd,0xbcfd3b96,0xbcf1bc2c,0xbcacbcbe,0xbbf9bcf8,0x3c843cdc,0x3ac93d00,0xbc5b3ce7,0xbcce3c98,
 0xbccebc98,0xbc5bbce7,0x3ac9bd00,0x3c84bcdc,0xbbf93cf8,0xbcac3cbe,0xbcf13c2c,0xbcfdbb96,0x3b963cfd,0xbc2c3cf1,0xbcbe3cac,0xbcf83bf9,0x3cdcbc84,0x3d00bac9,0x3ce73c5b,0x3c983cce,
 0xbcf5bc15,0xbca2bcc6,0xbb49bcff,0x3c71bce2,0x3ce2bc71,0x3cff3b49,0x3cc63ca2,0x3c153cf5,0x3c15bcf5,0x3cc6bca2,0x3cffbb49,0x3ce23c71,0x3c713ce2,0xbb493cff,0xbca23cc6,0xbcf53c15,
 0x3cf53c15,0x3ca23cc6,0x3b493cff,0xbc713ce2,0xbce23c71,0xbcffbb49,0xbcc6bca2,0xbc15bcf5,0xbc153cf5,0xbcc63ca2,0xbcff3b49,0xbce2bc71,0xbc71bce2,0x3b49bcff,0x3ca2bcc6,0x3cf5bc15,
 0xbcac3cbe,0xbcfd3b96,0xbcdcbc84,0xbc2cbcf1,0x3ce7bc5b,0x3cf83bf9,0x3c983cce,0xbac93d00,0xbd003ac9,0xbccebc98,0xbbf9bcf8,0x3c5bbce7,0x3cf13c2c,0x3c843cdc,0xbb963cfd,0xbcbe3cac,
 0xbcbebcac,0xbb96bcfd,0x3c84bcdc,0x3cf1bc2c,0x3c5b3ce7,0xbbf93cf8,0xbcce3c98,0xbd00bac9,0xbac9bd00,0x3c98bcce,0x3cf8bbf9,0x3ce73c5b,0xbc2c3cf1,0xbcdc3c84,0xbcfdbb96,0xbcacbcbe,
 0xbc443ced,0xbced3c44,0xbcedbc44,0xbc44bced,0x3c44bced,0x3cedbc44,0x3ced3c44,0x3c443ced,0xbc443ced,0xbced3c44,0xbcedbc44,0xbc44bced,0x3c44bced,0x3cedbc44,0x3ced3c44,0x3c443ced,
 0xbc443ced,0xbced3c44,0xbcedbc44,0xbc44bced,0x3c44bced,0x3cedbc44,0x3ced3c44,0x3c443ced,0xbc443ced,0xbced3c44,0xbcedbc44,0xbc44bced,0x3c44bced,0x3cedbc44,0x3ced3c44,0x3c443ced,
 0x3cbebcac,0x3cfd3b96,0x3c843cdc,0xbc2c3cf1,0xbc5b3ce7,0xbcf83bf9,0xbccebc98,0xbac9bd00,0x3d003ac9,0x3c983cce,0xbbf93cf8,0xbce73c5b,0xbcf13c2c,0xbcdcbc84,0xbb96bcfd,0x3cacbcbe,
 0x3cac3cbe,0xbb963cfd,0xbcdc3c84,0xbcf1bc2c,0xbce7bc5b,0xbbf9bcf8,0x3c98bcce,0x3d00bac9,0xbac93d00,0xbcce3c98,0xbcf8bbf9,0xbc5bbce7,0xbc2cbcf1,0x3c84bcdc,0x3cfdbb96,0x3cbe3cac,
 0xbce2bc71,0xbb49bcff,0x3cc6bca2,0x3cf53c15,0x3c153cf5,0xbca23cc6,0xbcffbb49,0xbc71bce2,0xbc713ce2,0xbcff3b49,0xbca2bcc6,0x3c15bcf5,0x3cf5bc15,0x3cc63ca2,0xbb493cff,0xbce23c71,
 0x3ce23c71,0x3b493cff,0xbcc63ca2,0xbcf5bc15,0xbc15bcf5,0x3ca2bcc6,0x3cff3b49,0x3c713ce2,0x3c71bce2,0x3cffbb49,0x3ca23cc6,0xbc153cf5,0xbcf53c15,0xbcc6bca2,0x3b49bcff,0x3ce2bc71,
 0xbcce3c98,0xbce7bc5b,0xbac9bd00,0x3cdcbc84,0xbbf9bcf8,0x3cbebcac,0x3cf13c2c,0x3b963cfd,0x3cfd3b96,0x3c2c3cf1,0xbcac3cbe,0xbcf8bbf9,0xbc843cdc,0xbd00bac9,0xbc5bbce7,0x3c98bcce,
 0x3c983cce,0xbc5b3ce7,0xbd003ac9,0xbc84bcdc,0xbcf83bf9,0xbcacbcbe,0x3c2cbcf1,0x3cfdbb96,0x3b96bcfd,0x3cf1bc2c,0x3cbe3cac,0xbbf93cf8,0x3cdc3c84,0xbac93d00,0xbce73c5b,0xbccebc98,
 0xbc8e3cd5,0xbcfbbbc8,0xbbc8bcfb,0x3cd5bc8e,0x3cd53c8e,0xbbc83cfb,0xbcfb3bc8,0xbc8ebcd5,0x3c8ebcd5,0x3cfb3bc8,0x3bc83cfb,0xbcd53c8e,0xbcd5bc8e,0x3bc8bcfb,0x3cfbbbc8,0x3c8e3cd5,
 0xbc8e3cd5,0xbcfbbbc8,0xbbc8bcfb,0x3cd5bc8e,0x3cd53c8e,0xbbc83cfb,0xbcfb3bc8,0xbc8ebcd5,0x3c8ebcd5,0x3cfb3bc8,0x3bc83cfb,0xbcd53c8e,0xbcd5bc8e,0x3bc8bcfb,0x3cfbbbc8,0x3c8e3cd5,
 0xbcdc3c84,0xbcbebcac,0x3c5bbce7,0x3cfd3b96,0xbccebc98,0x3c2cbcf1,0x3d003ac9,0x3bf93cf8,0x3cf83bf9,0x3ac93d00,0xbcf13c2c,0xbc98bcce,0x3b963cfd,0xbce73c5b,0xbcacbcbe,0x3c84bcdc,
 0x3c843cdc,0xbcac3cbe,0xbce7bc5b,0x3b96bcfd,0xbc983cce,0xbcf1bc2c,0x3ac9bd00,0x3cf8bbf9,0x3bf9bcf8,0x3d00bac9,0x3c2c3cf1,0xbcce3c98,0x3cfdbb96,0x3c5b3ce7,0xbcbe3cac,0xbcdcbc84,
 0xbcc6bca2,0x3c71bce2,0x3cf53c15,0xbb493cff,0xbcff3b49,0xbc15bcf5,0x3ce2bc71,0x3ca23cc6,0x3ca2bcc6,0x3ce23c71,0xbc153cf5,0xbcffbb49,0xbb49bcff,0x3cf5bc15,0x3c713ce2,0xbcc63ca2,
 0x3cc63ca2,0xbc713ce2,0xbcf5bc15,0x3b49bcff,0x3cffbb49,0x3c153cf5,0xbce23c71,0xbca2bcc6,0xbca23cc6,0xbce2bc71,0x3c15bcf5,0x3cff3b49,0x3b493cff,0xbcf53c15,0xbc71bce2,0x3cc6bca2,
 0x3ce7bc5b,0x3c843cdc,0xbcce3c98,0xbcacbcbe,0x3d00bac9,0x3b963cfd,0xbcf83bf9,0xbc2cbcf1,0x3cf13c2c,0xbbf93cf8,0xbcfdbb96,0x3ac9bd00,0x3cbe3cac,0xbc983cce,0xbcdcbc84,0x3c5bbce7,
 0x3c5b3ce7,0xbcdc3c84,0xbc98bcce,0x3cbebcac,0x3ac93d00,0xbcfd3b96,0xbbf9bcf8,0x3cf1bc2c,0xbc2c3cf1,0xbcf8bbf9,0x3b96bcfd,0x3d003ac9,0xbcac3cbe,0xbccebc98,0x3c84bcdc,0x3ce73c5b,
 0xbcb53cb5,0xbcb5bcb5,0x3cb5bcb5,0x3cb53cb5,0xbcb53cb5,0xbcb5bcb5,0x3cb5bcb5,0x3cb53cb5,0xbcb53cb5,0xbcb5bcb5,0x3cb5bcb5,0x3cb53cb5,0xbcb53cb5,0xbcb5bcb5,0x3cb5bcb5,0x3cb53cb5,
 0xbcb53cb5,0xbcb5bcb5,0x3cb5bcb5,0x3cb53cb5,0xbcb53cb5,0xbcb5bcb5,0x3cb5bcb5,0x3cb53cb5,0xbcb53cb5,0xbcb5bcb5,0x3cb5bcb5,0x3cb53cb5,0xbcb53cb5,0xbcb5bcb5,0x3cb5bcb5,0x3cb53cb5,
 0xbcf13c2c,0xbbf9bcf8,0x3cfdbb96,0x3ac93d00,0xbcbe3cac,0xbc98bcce,0x3cdcbc84,0x3c5b3ce7,0xbce7bc5b,0x3c84bcdc,0x3cce3c98,0xbcac3cbe,0xbd00bac9,0x3b96bcfd,0x3cf83bf9,0xbc2c3cf1,
 0xbc2cbcf1,0x3cf8bbf9,0x3b963cfd,0xbd003ac9,0xbcacbcbe,0x3ccebc98,0x3c843cdc,0xbce73c5b,0x3c5bbce7,0x3cdc3c84,0xbc983cce,0xbcbebcac,0x3ac9bd00,0x3cfd3b96,0xbbf93cf8,0xbcf1bc2c,
 0xbca2bcc6,0x3ce2bc71,0x3c153cf5,0xbcff3b49,0x3b49bcff,0x3cf53c15,0xbc713ce2,0xbcc6bca2,0xbcc63ca2,0xbc71bce2,0x3cf5bc15,0x3b493cff,0xbcffbb49,0x3c15bcf5,0x3ce23c71,0xbca23cc6,
 0x3ca23cc6,0xbce23c71,0xbc15bcf5,0x3cffbb49,0xbb493cff,0xbcf5bc15,0x3c71bce2,0x3cc63ca2,0x3cc6bca2,0x3c713ce2,0xbcf53c15,0xbb49bcff,0x3cff3b49,0xbc153cf5,0xbce2bc71,0x3ca2bcc6,
 0x3cf8bbf9,0xbac93d00,0xbcf1bc2c,0x3c98bcce,0x3b96bcfd,0x3ce73c5b,0xbcac3cbe,0xbc84bcdc,0xbcdcbc84,0x3cbebcac,0x3c5b3ce7,0xbcfd3b96,0xbcce3c98,0xbc2cbcf1,0x3d00bac9,0xbbf93cf8,
 0xbbf9bcf8,0x3d003ac9,0xbc2c3cf1,0xbccebc98,0xbcfdbb96,0x3c5bbce7,0x3cbe3cac,0xbcdc3c84,0xbc843cdc,0xbcacbcbe,0x3ce7bc5b,0x3b963cfd,0x3c983cce,0xbcf13c2c,0xbac9bd00,0x3cf83bf9,
 0xbcd53c8e,0xbbc8bcfb,0x3cfb3bc8,0xbc8e3cd5,0xbc8ebcd5,0x3cfbbbc8,0xbbc83cfb,0xbcd5bc8e,0x3cd5bc8e,0x3bc83cfb,0xbcfbbbc8,0x3c8ebcd5,0x3c8e3cd5,0xbcfb3bc8,0x3bc8bcfb,0x3cd53c8e,
 0xbcd53c8e,0xbbc8bcfb,0x3cfb3bc8,0xbc8e3cd5,0xbc8ebcd5,0x3cfbbbc8,0xbbc83cfb,0xbcd5bc8e,0x3cd5bc8e,0x3bc83cfb,0xbcfbbbc8,0x3c8ebcd5,0x3c8e3cd5,0xbcfb3bc8,0x3bc8bcfb,0x3cd53c8e,
 0x3cfdbb96,0xbc2c3cf1,0xbcacbcbe,0x3cf8bbf9,0xbc84bcdc,0x3d00bac9,0xbc5b3ce7,0xbc98bcce,0xbccebc98,0x3ce7bc5b,0xbac93d00,0xbcdcbc84,0xbbf93cf8,0xbcbebcac,0x3cf1bc2c,0xbb963cfd,
 0xbb96bcfd,0x3cf13c2c,0xbcbe3cac,0xbbf9bcf8,0xbcdc3c84,0xbac9bd00,0x3ce73c5b,0xbcce3c98,0xbc983cce,0xbc5bbce7,0x3d003ac9,0xbc843cdc,0x3cf83bf9,0xbcac3cbe,0xbc2cbcf1,0x3cfd3b96,
 0xbc71bce2,0x3cff3b49,0xbca23cc6,0xbc15bcf5,0x3cf53c15,0xbcc63ca2,0xbb49bcff,0x3ce23c71,0x3ce2bc71,0xbb493cff,0xbcc6bca2,0x3cf5bc15,0xbc153cf5,0xbca2bcc6,0x3cffbb49,0xbc713ce2,
 0x3c713ce2,0xbcffbb49,0x3ca2bcc6,0x3c153cf5,0xbcf5bc15,0x3cc6bca2,0x3b493cff,0xbce2bc71,0xbce23c71,0x3b49bcff,0x3cc63ca2,0xbcf53c15,0x3c15bcf5,0x3ca23cc6,0xbcff3b49,0x3c71bce2,
 0xbd003ac9,0x3c98bcce,0x3bf93cf8,0xbce7bc5b,0x3cf13c2c,0xbcdc3c84,0x3b96bcfd,0x3cac3cbe,0xbcbebcac,0x3cfdbb96,0xbc843cdc,0xbc2cbcf1,0x3c5b3ce7,0xbcf8bbf9,0x3ccebc98,0xbac93d00,
 0xbac9bd00,0x3cce3c98,0xbcf83bf9,0x3c5bbce7,0xbc2c3cf1,0xbc84bcdc,0x3cfd3b96,0xbcbe3cac,0x3cacbcbe,0x3b963cfd,0xbcdcbc84,0x3cf1bc2c,0xbce73c5b,0x3bf9bcf8,0x3c983cce,0xbd00bac9,
 0xbced3c44,0x3c44bced,0x3c443ced,0xbcedbc44,0x3cedbc44,0xbc443ced,0xbc44bced,0x3ced3c44,0xbced3c44,0x3c44bced,0x3c443ced,0xbcedbc44,0x3cedbc44,0xbc443ced,0xbc44bced,0x3ced3c44,
 0xbced3c44,0x3c44bced,0x3c443ced,0xbcedbc44,0x3cedbc44,0xbc443ced,0xbc44bced,0x3ced3c44,0xbced3c44,0x3c44bced,0x3c443ced,0xbcedbc44,0x3cedbc44,0xbc443ced,0xbc44bced,0x3ced3c44,
 0x3d003ac9,0xbcce3c98,0x3bf9bcf8,0x3c5b3ce7,0xbcf13c2c,0x3c84bcdc,0x3b963cfd,0xbcbebcac,0x3cac3cbe,0xbcfdbb96,0x3cdcbc84,0xbc2c3cf1,0xbce7bc5b,0x3cf8bbf9,0xbc983cce,0xbac9bd00,
 0xbac93d00,0xbc98bcce,0x3cf83bf9,0xbce73c5b,0xbc2cbcf1,0x3cdc3c84,0xbcfd3b96,0x3cacbcbe,0xbcbe3cac,0x3b96bcfd,0x3c843cdc,0xbcf1bc2c,0x3c5bbce7,0x3bf93cf8,0xbccebc98,0x3d00bac9,
 0xbc15bcf5,0x3cc63ca2,0xbcffbb49,0x3ce2bc71,0xbc713ce2,0xbb49bcff,0x3ca23cc6,0xbcf5bc15,0xbcf53c15,0x3ca2bcc6,0xbb493cff,0xbc71bce2,0x3ce23c71,0xbcff3b49,0x3cc6bca2,0xbc153cf5,
 0x3c153cf5,0xbcc6bca2,0x3cff3b49,0xbce23c71,0x3c71bce2,0x3b493cff,0xbca2bcc6,0x3cf53c15,0x3cf5bc15,0xbca23cc6,0x3b49bcff,0x3c713ce2,0xbce2bc71,0x3cffbb49,0xbcc63ca2,0x3c15bcf5,
 0xbcfdbb96,0x3cf1bc2c,0xbcac3cbe,0x3bf9bcf8,0x3c84bcdc,0xbac93d00,0xbc5bbce7,0x3cce3c98,0x3c983cce,0xbce7bc5b,0x3d00bac9,0xbcdc3c84,0xbcf83bf9,0x3cbebcac,0xbc2c3cf1,0xbb96bcfd,
 0xbb963cfd,0xbc2cbcf1,0x3cbe3cac,0xbcf8bbf9,0xbcdcbc84,0x3d003ac9,0xbce73c5b,0x3c98bcce,0x3ccebc98,0xbc5b3ce7,0xbac9bd00,0x3c843cdc,0x3bf93cf8,0xbcacbcbe,0x3cf13c2c,0xbcfd3b96,
 0xbcfb3bc8,0x3cd5bc8e,0xbc8e3cd5,0x3bc8bcfb,0x3bc83cfb,0xbc8ebcd5,0x3cd53c8e,0xbcfbbbc8,0x3cfbbbc8,0xbcd53c8e,0x3c8ebcd5,0xbbc83cfb,0xbbc8bcfb,0x3c8e3cd5,0xbcd5bc8e,0x3cfb3bc8,
 0xbcfb3bc8,0x3cd5bc8e,0xbc8e3cd5,0x3bc8bcfb,0x3bc83cfb,0xbc8ebcd5,0x3cd53c8e,0xbcfbbbc8,0x3cfbbbc8,0xbcd53c8e,0x3c8ebcd5,0xbbc83cfb,0xbbc8bcfb,0x3c8e3cd5,0xbcd5bc8e,0x3cfb3bc8,
 0xbcf8bbf9,0x3d00bac9,0xbcf13c2c,0x3ccebc98,0xbb96bcfd,0x3c5b3ce7,0xbcacbcbe,0x3cdc3c84,0x3c843cdc,0xbcbebcac,0x3ce73c5b,0xbcfdbb96,0xbc983cce,0x3c2cbcf1,0xbac93d00,0xbbf9bcf8,
 0xbbf93cf8,0xbac9bd00,0x3c2c3cf1,0xbc98bcce,0xbcfd3b96,0x3ce7bc5b,0xbcbe3cac,0x3c84bcdc,0x3cdcbc84,0xbcac3cbe,0x3c5bbce7,0xbb963cfd,0x3cce3c98,0xbcf1bc2c,0x3d003ac9,0xbcf83bf9,
 0xbb49bcff,0x3c153cf5,0xbc71bce2,0x3ca23cc6,0xbcc6bca2,0x3ce23c71,0xbcf5bc15,0x3cff3b49,0x3cffbb49,0xbcf53c15,0x3ce2bc71,0xbcc63ca2,0x3ca2bcc6,0xbc713ce2,0x3c15bcf5,0xbb493cff,
 0x3b493cff,0xbc15bcf5,0x3c713ce2,0xbca2bcc6,0x3cc63ca2,0xbce2bc71,0x3cf53c15,0xbcffbb49,0xbcff3b49,0x3cf5bc15,0xbce23c71,0x3cc6bca2,0xbca23cc6,0x3c71bce2,0xbc153cf5,0x3b49bcff,
 0x3cf13c2c,0xbcf8bbf9,0x3cfd3b96,0xbd00bac9,0x3cbe3cac,0xbccebc98,0x3cdc3c84,0xbce7bc5b,0x3c5b3ce7,0xbc84bcdc,0x3c983cce,0xbcacbcbe,0x3ac93d00,0xbb96bcfd,0x3bf93cf8,0xbc2cbcf1,
 0xbc2c3cf1,0x3bf9bcf8,0xbb963cfd,0x3ac9bd00,0xbcac3cbe,0x3c98bcce,0xbc843cdc,0x3c5bbce7,0xbce73c5b,0x3cdcbc84,0xbcce3c98,0x3cbebcac,0xbd003ac9,0x3cfdbb96,0xbcf83bf9,0x3cf1bc2c,
 0xbd000000,0x3d000000,0xbd000000,0x3d000000,0xbd000000,0x3d000000,0xbd000000,0x3d000000,0xbd000000,0x3d000000,0xbd000000,0x3d000000,0xbd000000,0x3d000000,0xbd000000,0x3d000000,
 0xbd000000,0x3d000000,0xbd000000,0x3d000000,0xbd000000,0x3d000000,0xbd000000,0x3d000000,0xbd000000,0x3d000000,0xbd000000,0x3d000000,0xbd000000,0x3d000000,0xbd000000,0x3d000000,
 0xbce7bc5b,0x3cdc3c84,0xbccebc98,0x3cbe3cac,0xbd00bac9,0x3cfd3b96,0xbcf8bbf9,0x3cf13c2c,0xbc2cbcf1,0x3bf93cf8,0xbb96bcfd,0x3ac93d00,0xbcacbcbe,0x3c983cce,0xbc84bcdc,0x3c5b3ce7,
 0x3c5bbce7,0xbc843cdc,0x3c98bcce,0xbcac3cbe,0x3ac9bd00,0xbb963cfd,0x3bf9bcf8,0xbc2c3cf1,0x3cf1bc2c,0xbcf83bf9,0x3cfdbb96,0xbd003ac9,0x3cbebcac,0xbcce3c98,0x3cdcbc84,0xbce73c5b,
 0x3b49bcff,0xbc153cf5,0x3c71bce2,0xbca23cc6,0x3cc6bca2,0xbce23c71,0x3cf5bc15,0xbcff3b49,0xbcffbb49,0x3cf53c15,0xbce2bc71,0x3cc63ca2,0xbca2bcc6,0x3c713ce2,0xbc15bcf5,0x3b493cff,
 0xbb493cff,0x3c15bcf5,0xbc713ce2,0x3ca2bcc6,0xbcc63ca2,0x3ce2bc71,0xbcf53c15,0x3cffbb49,0x3cff3b49,0xbcf5bc15,0x3ce23c71,0xbcc6bca2,0x3ca23cc6,0xbc71bce2,0x3c153cf5,0xbb49bcff,
 0x3cdc3c84,0xbcacbcbe,0x3c5b3ce7,0xbb96bcfd,0x3ccebc98,0xbcf13c2c,0x3d00bac9,0xbcf8bbf9,0xbbf9bcf8,0xbac93d00,0x3c2cbcf1,0xbc983cce,0xbcfdbb96,0x3ce73c5b,0xbcbebcac,0x3c843cdc,
 0x3c84bcdc,0xbcbe3cac,0x3ce7bc5b,0xbcfd3b96,0xbc98bcce,0x3c2c3cf1,0xbac9bd00,0xbbf93cf8,0xbcf83bf9,0x3d003ac9,0xbcf1bc2c,0x3cce3c98,0xbb963cfd,0x3c5bbce7,0xbcac3cbe,0x3cdcbc84,
 0xbcfbbbc8,0x3cd53c8e,0xbc8ebcd5,0x3bc83cfb,0x3bc8bcfb,0xbc8e3cd5,0x3cd5bc8e,0xbcfb3bc8,0x3cfb3bc8,0xbcd5bc8e,0x3c8e3cd5,0xbbc8bcfb,0xbbc83cfb,0x3c8ebcd5,0xbcd53c8e,0x3cfbbbc8,
 0xbcfbbbc8,0x3cd53c8e,0xbc8ebcd5,0x3bc83cfb,0x3bc8bcfb,0xbc8e3cd5,0x3cd5bc8e,0xbcfb3bc8,0x3cfb3bc8,0xbcd5bc8e,0x3c8e3cd5,0xbbc8bcfb,0xbbc83cfb,0x3c8ebcd5,0xbcd53c8e,0x3cfbbbc8,
 0x3cce3c98,0xbc5bbce7,0xbac93d00,0x3c84bcdc,0x3bf9bcf8,0xbcac3cbe,0x3cf1bc2c,0xbcfdbb96,0xbb96bcfd,0xbc2c3cf1,0x3cbebcac,0xbcf83bf9,0xbcdc3c84,0x3d00bac9,0xbce7bc5b,0x3c983cce,
 0x3c98bcce,0xbce73c5b,0x3d003ac9,0xbcdcbc84,0xbcf8bbf9,0x3cbe3cac,0xbc2cbcf1,0xbb963cfd,0xbcfd3b96,0x3cf13c2c,0xbcacbcbe,0x3bf93cf8,0x3c843cdc,0xbac9bd00,0xbc5b3ce7,0x3ccebc98,
 0x3c15bcf5,0xbcc63ca2,0x3cffbb49,0xbce2bc71,0x3c713ce2,0x3b49bcff,0xbca23cc6,0x3cf5bc15,0x3cf53c15,0xbca2bcc6,0x3b493cff,0x3c71bce2,0xbce23c71,0x3cff3b49,0xbcc6bca2,0x3c153cf5,
 0xbc153cf5,0x3cc6bca2,0xbcff3b49,0x3ce23c71,0xbc71bce2,0xbb493cff,0x3ca2bcc6,0xbcf53c15,0xbcf5bc15,0x3ca23cc6,0xbb49bcff,0xbc713ce2,0x3ce2bc71,0xbcffbb49,0x3cc63ca2,0xbc15bcf5,
 0xbcbebcac,0x3b963cfd,0x3c84bcdc,0xbcf13c2c,0x3c5b3ce7,0x3bf9bcf8,0xbcce3c98,0x3d003ac9,0xbac9bd00,0xbc983cce,0x3cf8bbf9,0xbce7bc5b,0xbc2c3cf1,0x3cdcbc84,0xbcfdbb96,0x3cac3cbe,
 0x3cacbcbe,0xbcfd3b96,0x3cdc3c84,0xbc2cbcf1,0xbce73c5b,0x3cf83bf9,0xbc98bcce,0xbac93d00,0x3d00bac9,0xbccebc98,0x3bf93cf8,0x3c5bbce7,0xbcf1bc2c,0x3c843cdc,0x3b96bcfd,0xbcbe3cac,
 0xbcedbc44,0x3c443ced,0x3c44bced,0xbced3c44,0x3ced3c44,0xbc44bced,0xbc443ced,0x3cedbc44,0xbcedbc44,0x3c443ced,0x3c44bced,0xbced3c44,0x3ced3c44,0xbc44bced,0xbc443ced,0x3cedbc44,
 0xbcedbc44,0x3c443ced,0x3c44bced,0xbced3c44,0x3ced3c44,0xbc44bced,0xbc443ced,0x3cedbc44,0xbcedbc44,0x3c443ced,0x3c44bced,0xbced3c44,0x3ced3c44,0xbc44bced,0xbc443ced,0x3cedbc44,
 0x3cac3cbe,0x3b96bcfd,0xbcdc3c84,0x3cf13c2c,0xbce7bc5b,0x3bf93cf8,0x3c98bcce,0xbd003ac9,0xbac93d00,0x3ccebc98,0xbcf8bbf9,0x3c5b3ce7,0xbc2cbcf1,0xbc843cdc,0x3cfdbb96,0xbcbebcac,
 0xbcbe3cac,0x3cfd3b96,0xbc84bcdc,0xbc2c3cf1,0x3c5bbce7,0xbcf83bf9,0x3cce3c98,0xbac9bd00,0xbd00bac9,0x3c983cce,0x3bf9bcf8,0xbce73c5b,0x3cf1bc2c,0xbcdcbc84,0x3b963cfd,0x3cacbcbe,
 0x3c71bce2,0xbcff3b49,0x3ca23cc6,0x3c15bcf5,0xbcf53c15,0x3cc63ca2,0x3b49bcff,0xbce23c71,0xbce2bc71,0x3b493cff,0x3cc6bca2,0xbcf5bc15,0x3c153cf5,0x3ca2bcc6,0xbcffbb49,0x3c713ce2,
 0xbc713ce2,0x3cffbb49,0xbca2bcc6,0xbc153cf5,0x3cf5bc15,0xbcc6bca2,0xbb493cff,0x3ce2bc71,0x3ce23c71,0xbb49bcff,0xbcc63ca2,0x3cf53c15,0xbc15bcf5,0xbca23cc6,0x3cff3b49,0xbc71bce2,
 0xbc98bcce,0xbc5b3ce7,0x3d00bac9,0xbc84bcdc,0x3cf8bbf9,0xbcacbcbe,0xbc2c3cf1,0x3cfdbb96,0xbb963cfd,0x3cf1bc2c,0xbcbebcac,0xbbf93cf8,0xbcdcbc84,0xbac93d00,0x3ce7bc5b,0xbccebc98,
 0xbcce3c98,0x3ce73c5b,0xbac9bd00,0xbcdc3c84,0xbbf9bcf8,0xbcbe3cac,0x3cf13c2c,0xbb96bcfd,0x3cfd3b96,0xbc2cbcf1,0xbcac3cbe,0x3cf83bf9,0xbc843cdc,0x3d003ac9,0xbc5bbce7,0xbc983cce,
 0xbcd5bc8e,0xbbc83cfb,0x3cfbbbc8,0xbc8ebcd5,0xbc8e3cd5,0x3cfb3bc8,0xbbc8bcfb,0xbcd53c8e,0x3cd53c8e,0x3bc8bcfb,0xbcfb3bc8,0x3c8e3cd5,0x3c8ebcd5,0xbcfbbbc8,0x3bc83cfb,0x3cd5bc8e,
 0xbcd5bc8e,0xbbc83cfb,0x3cfbbbc8,0xbc8ebcd5,0xbc8e3cd5,0x3cfb3bc8,0xbbc8bcfb,0xbcd53c8e,0x3cd53c8e,0x3bc8bcfb,0xbcfb3bc8,0x3c8e3cd5,0x3c8ebcd5,0xbcfbbbc8,0x3bc83cfb,0x3cd5bc8e,
 0xbc84bcdc,0xbcac3cbe,0x3ce73c5b,0x3b96bcfd,0x3c98bcce,0xbcf1bc2c,0xbac93d00,0x3cf8bbf9,0xbbf93cf8,0x3d00bac9,0xbc2cbcf1,0xbcce3c98,0xbcfd3b96,0x3c5b3ce7,0x3cbebcac,0xbcdcbc84,
 0xbcdc3c84,0x3cbe3cac,0x3c5bbce7,0xbcfdbb96,0xbccebc98,0xbc2c3cf1,0x3d003ac9,0xbbf9bcf8,0x3cf83bf9,0xbac9bd00,0xbcf13c2c,0x3c983cce,0x3b963cfd,0x3ce7bc5b,0xbcacbcbe,0xbc843cdc,
 0x3ca2bcc6,0xbce2bc71,0xbc153cf5,0x3cff3b49,0xbb49bcff,0xbcf53c15,0x3c713ce2,0x3cc6bca2,0x3cc63ca2,0x3c71bce2,0xbcf5bc15,0xbb493cff,0x3cffbb49,0xbc15bcf5,0xbce23c71,0x3ca23cc6,
 0xbca23cc6,0x3ce23c71,0x3c15bcf5,0xbcffbb49,0x3b493cff,0x3cf5bc15,0xbc71bce2,0xbcc63ca2,0xbcc6bca2,0xbc713ce2,0x3cf53c15,0x3b49bcff,0xbcff3b49,0x3c153cf5,0x3ce2bc71,0xbca2bcc6,
 0x3c5b3ce7,0x3cdcbc84,0xbc98bcce,0xbcbe3cac,0x3ac93d00,0x3cfdbb96,0xbbf9bcf8,0xbcf13c2c,0xbc2c3cf1,0x3cf83bf9,0x3b96bcfd,0xbd00bac9,0xbcac3cbe,0x3cce3c98,0x3c84bcdc,0xbce7bc5b,
 0xbce73c5b,0x3c843cdc,0x3ccebc98,0xbcacbcbe,0xbd003ac9,0x3b963cfd,0x3cf8bbf9,0xbc2cbcf1,0xbcf1bc2c,0xbbf93cf8,0x3cfd3b96,0x3ac9bd00,0xbcbebcac,0xbc983cce,0x3cdc3c84,0x3c5bbce7,
 0xbcb5bcb5,0xbcb53cb5,0x3cb53cb5,0x3cb5bcb5,0xbcb5bcb5,0xbcb53cb5,0x3cb53cb5,0x3cb5bcb5,0xbcb5bcb5,0xbcb53cb5,0x3cb53cb5,0x3cb5bcb5,0xbcb5bcb5,0xbcb53cb5,0x3cb53cb5,0x3cb5bcb5,
 0xbcb5bcb5,0xbcb53cb5,0x3cb53cb5,0x3cb5bcb5,0xbcb5bcb5,0xbcb53cb5,0x3cb53cb5,0x3cb5bcb5,0xbcb5bcb5,0xbcb53cb5,0x3cb53cb5,0x3cb5bcb5,0xbcb5bcb5,0xbcb53cb5,0x3cb53cb5,0x3cb5bcb5,
 0xbc2cbcf1,0xbcf83bf9,0x3b963cfd,0x3d00bac9,0xbcacbcbe,0xbcce3c98,0x3c843cdc,0x3ce7bc5b,0x3c5bbce7,0xbcdcbc84,0xbc983cce,0x3cbe3cac,0x3ac9bd00,0xbcfdbb96,0xbbf93cf8,0x3cf13c2c,
 0x3cf1bc2c,0xbbf9bcf8,0xbcfd3b96,0x3ac93d00,0x3cbebcac,0xbc98bcce,0xbcdc3c84,0x3c5b3ce7,0x3ce73c5b,0x3c84bcdc,0xbccebc98,0xbcac3cbe,0x3d003ac9,0x3b96bcfd,0xbcf8bbf9,0xbc2c3cf1,
 0x00000000,0x00000000,0x00000000,0x00000000,0x00000000,0x00000000,0x00000000,0x00000000,0x00000000,0x00000000,0x00000000,0x00000000,0x00000000,0x00000000,0x00000000,0x00000000,
 0x00000000,0x00000000,0x00000000,0x00000000,0x00000000,0x00000000,0x00000000,0x00000000,0x00000000,0x00000000,0x00000000,0x00000000,0x00000000,0x00000000,0x00000000,0x00000000,
 0x00000000,0x00000000,0x00000000,0x00000000,0x00000000,0x00000000,0x00000000,0x00000000,0x00000000,0x00000000,0x00000000,0x00000000,0x00000000,0x00000000,0x00000000,0x00000000,
 0x00000000,0x00000000,0x00000000,0x00000000,0x00000000,0x00000000,0x00000000,0x00000000,0x00000000,0x00000000,0x00000000,0x00000000,0x00000000,0x00000000,0x00000000,0x00000000,
 0x00000000,0x00000000,0x00000000,0x00000000,0x00000000,0x00000000,0x00000000,0x00000000,0x00000000,0x00000000,0x00000000,0x00000000,0x00000000,0x00000000,0x00000000,0x00000000,
 0x00000000,0x00000000,0x00000000,0x00000000,0x00000000,0x00000000,0x00000000,0x00000000,0x00000000,0x00000000,0x00000000,0x00000000,0x00000000,0x00000000,0x00000000,0x00000000,
 0x00000000,0x00000000,0x00000000,0x00000000,0x00000000,0x00000000,0x00000000,0x00000000,0x00000000,0x00000000,0x00000000,0x00000000,0x00000000,0x00000000,0x00000000,0x00000000,
 0x00000000,0x00000000,0x00000000,0x00000000,0x00000000,0x00000000,0x00000000,0x00000000,0x00000000,0x00000000,0x00000000,0x00000000,0x00000000,0x00000000,0x00000000,0x00000000,
 0x00000000,0x00000000,0x00000000,0x00000000,0x00000000,0x00000000,0x00000000,0x00000000,0x00000000,0x00000000,0x00000000,0x00000000,0x00000000,0x00000000,0x00000000,0x00000000,
 0x00000000,0x00000000,0x00000000,0x00000000,0x00000000,0x00000000,0x00000000,0x00000000,0x00000000,0x00000000,0x00000000,0x00000000,0x00000000,0x00000000,0x00000000,0x00000000,
 0x00000000,0x00000000,0x00000000,0x00000000,0x00000000,0x00000000,0x00000000,0x00000000,0x00000000,0x00000000,0x00000000,0x00000000,0x00000000,0x00000000,0x00000000,0x00000000,
 0x00000000,0x00000000,0x00000000,0x00000000,0x00000000,0x00000000,0x00000000,0x00000000,0x00000000,0x00000000,0x00000000,0x00000000,0x00000000,0x00000000,0x00000000,0x00000000,
};

template<int SA>
__device__ __forceinline__ void wgmma_main(float (&d)[80], uint64_t da, uint64_t db, int sd) {
  asm volatile("{\n.reg .pred p;\nsetp.ne.b32 p, %82, 0;\n"
    "wgmma.mma_async.sync.aligned.m64n160k16.f32.bf16.bf16 "
    "{%0, %1, %2, %3, %4, %5, %6, %7, %8, %9, %10, %11, %12, %13, %14, %15, %16, %17, %18, %19, %20, %21, %22, %23, %24, %25, %26, %27, %28, %29, %30, %31, %32, %33, %34, %35, %36, %37, %38, %39, %40, %41, %42, %43, %44, %45, %46, %47, %48, %49, %50, %51, %52, %53, %54, %55, %56, %57, %58, %59, %60, %61, %62, %63, %64, %65, %66, %67, %68, %69, %70, %71, %72, %73, %74, %75, %76, %77, %78, %79}, %80, %81, p, %83, 1, 1, 0;\n}\n"
    : "+f"(d[0]), "+f"(d[1]), "+f"(d[2]), "+f"(d[3]), "+f"(d[4]), "+f"(d[5]), "+f"(d[6]), "+f"(d[7]), "+f"(d[8]), "+f"(d[9]), "+f"(d[10]), "+f"(d[11]), "+f"(d[12]), "+f"(d[13]), "+f"(d[14]), "+f"(d[15]), "+f"(d[16]), "+f"(d[17]), "+f"(d[18]), "+f"(d[19]), "+f"(d[20]), "+f"(d[21]), "+f"(d[22]), "+f"(d[23]), "+f"(d[24]), "+f"(d[25]), "+f"(d[26]), "+f"(d[27]), "+f"(d[28]), "+f"(d[29]), "+f"(d[30]), "+f"(d[31]), "+f"(d[32]), "+f"(d[33]), "+f"(d[34]), "+f"(d[35]), "+f"(d[36]), "+f"(d[37]), "+f"(d[38]), "+f"(d[39]), "+f"(d[40]), "+f"(d[41]), "+f"(d[42]), "+f"(d[43]), "+f"(d[44]), "+f"(d[45]), "+f"(d[46]), "+f"(d[47]), "+f"(d[48]), "+f"(d[49]), "+f"(d[50]), "+f"(d[51]), "+f"(d[52]), "+f"(d[53]), "+f"(d[54]), "+f"(d[55]), "+f"(d[56]), "+f"(d[57]), "+f"(d[58]), "+f"(d[59]), "+f"(d[60]), "+f"(d[61]), "+f"(d[62]), "+f"(d[63]), "+f"(d[64]), "+f"(d[65]), "+f"(d[66]), "+f"(d[67]), "+f"(d[68]), "+f"(d[69]), "+f"(d[70]), "+f"(d[71]), "+f"(d[72]), "+f"(d[73]), "+f"(d[74]), "+f"(d[75]), "+f"(d[76]), "+f"(d[77]), "+f"(d[78]), "+f"(d[79])
    : "l"(da), "l"(db), "r"(sd), "n"(SA));
}
template<int SA>
__device__ __forceinline__ void wgmma_fwd(float (&d)[32], uint64_t da, uint64_t db, int sd) {
  asm volatile("{\n.reg .pred p;\nsetp.ne.b32 p, %34, 0;\n"
    "wgmma.mma_async.sync.aligned.m64n64k16.f32.bf16.bf16 "
    "{%0, %1, %2, %3, %4, %5, %6, %7, %8, %9, %10, %11, %12, %13, %14, %15, %16, %17, %18, %19, %20, %21, %22, %23, %24, %25, %26, %27, %28, %29, %30, %31}, %32, %33, p, %35, 1, 0, 1;\n}\n"
    : "+f"(d[0]), "+f"(d[1]), "+f"(d[2]), "+f"(d[3]), "+f"(d[4]), "+f"(d[5]), "+f"(d[6]), "+f"(d[7]), "+f"(d[8]), "+f"(d[9]), "+f"(d[10]), "+f"(d[11]), "+f"(d[12]), "+f"(d[13]), "+f"(d[14]), "+f"(d[15]), "+f"(d[16]), "+f"(d[17]), "+f"(d[18]), "+f"(d[19]), "+f"(d[20]), "+f"(d[21]), "+f"(d[22]), "+f"(d[23]), "+f"(d[24]), "+f"(d[25]), "+f"(d[26]), "+f"(d[27]), "+f"(d[28]), "+f"(d[29]), "+f"(d[30]), "+f"(d[31])
    : "l"(da), "l"(db), "r"(sd), "n"(SA));
}
template<int SA>
__device__ __forceinline__ void wgmma_inv(float (&d)[28], uint64_t da, uint64_t db, int sd) {
  asm volatile("{\n.reg .pred p;\nsetp.ne.b32 p, %30, 0;\n"
    "wgmma.mma_async.sync.aligned.m64n56k16.f32.bf16.bf16 "
    "{%0, %1, %2, %3, %4, %5, %6, %7, %8, %9, %10, %11, %12, %13, %14, %15, %16, %17, %18, %19, %20, %21, %22, %23, %24, %25, %26, %27}, %28, %29, p, %31, 1, 1, 0;\n}\n"
    : "+f"(d[0]), "+f"(d[1]), "+f"(d[2]), "+f"(d[3]), "+f"(d[4]), "+f"(d[5]), "+f"(d[6]), "+f"(d[7]), "+f"(d[8]), "+f"(d[9]), "+f"(d[10]), "+f"(d[11]), "+f"(d[12]), "+f"(d[13]), "+f"(d[14]), "+f"(d[15]), "+f"(d[16]), "+f"(d[17]), "+f"(d[18]), "+f"(d[19]), "+f"(d[20]), "+f"(d[21]), "+f"(d[22]), "+f"(d[23]), "+f"(d[24]), "+f"(d[25]), "+f"(d[26]), "+f"(d[27])
    : "l"(da), "l"(db), "r"(sd), "n"(SA));
}

__device__ __forceinline__ uint32_t s2u(const void* p) { return (uint32_t)__cvta_generic_to_shared(p); }
__device__ __forceinline__ void mbar_init(uint32_t a, int c) { asm volatile("mbarrier.init.shared::cta.b64 [%0], %1;" ::"r"(a), "r"(c)); }
__device__ __forceinline__ void mbar_expect(uint32_t a, int b) { asm volatile("mbarrier.arrive.expect_tx.shared::cta.b64 _, [%0], %1;" ::"r"(a), "r"(b) : "memory"); }
__device__ __forceinline__ void mbar_arrive(uint32_t a) { asm volatile("mbarrier.arrive.shared::cta.b64 _, [%0];" ::"r"(a) : "memory"); }
__device__ __forceinline__ void mbar_arrive_cluster(uint32_t a, uint32_t cta, uint32_t cnt) {
  asm volatile("{\n.reg .b32 r;\nmapa.shared::cluster.u32 r, %0, %1;\nmbarrier.arrive.shared::cluster.b64 _, [r], %2;\n}" ::"r"(a), "r"(cta), "r"(cnt) : "memory");
}
__device__ __forceinline__ void mbar_wait(uint32_t a, int ph) {
  asm volatile("{\n.reg .pred p;\n.reg .u32 c;\nmov.u32 c, 0;\nWAIT:\n"
               "mbarrier.try_wait.parity.shared::cta.b64 p, [%0], %1;\n@p bra DONE;\n"
               "add.u32 c, c, 1;\nsetp.lt.u32 p, c, 0x400000;\n@p bra WAIT;\ntrap;\nDONE:\n}" ::"r"(a), "r"(ph) : "memory");
}
__device__ __forceinline__ void flag_wait(const unsigned* p, unsigned target) {
  asm volatile("{\n.reg .pred p;\n.reg .u32 c, v;\nmov.u32 c, 0;\nWAIT:\n"
               "ld.acquire.gpu.global.u32 v, [%0];\nsetp.ge.u32 p, v, %1;\n@p bra DONE;\n"
               "add.u32 c, c, 1;\nsetp.lt.u32 p, c, 0x400000;\n@p bra WAIT;\ntrap;\nDONE:\n}" ::"l"(p), "r"(target) : "memory");
}
__device__ __forceinline__ bool elect_one() {
  uint32_t p;
  asm volatile("{\n.reg .pred P;\nelect.sync _|P, 0xffffffff;\nselp.u32 %0, 1, 0, P;\n}" : "=r"(p));
  return p != 0;
}
__device__ __forceinline__ void bulk_ld(uint32_t dst, const void* src, int bytes, uint32_t bar) {
  asm volatile("cp.async.bulk.shared::cluster.global.mbarrier::complete_tx::bytes [%0], [%1], %2, [%3];" ::"r"(dst), "l"(src), "r"(bytes), "r"(bar) : "memory");
}
__device__ __forceinline__ void bulk_ld_mc_h(uint32_t dst, const void* src, int bytes, uint32_t bar, uint16_t mask, uint64_t pol) {
  asm volatile("cp.async.bulk.shared::cluster.global.mbarrier::complete_tx::bytes.multicast::cluster.L2::cache_hint [%0], [%1], %2, [%3], %4, %5;" ::"r"(dst), "l"(src), "r"(bytes), "r"(bar), "h"(mask), "l"(pol) : "memory");
}
__device__ __forceinline__ void tma_ld2(uint32_t dst, const CUtensorMap* tm, int c0, int c1, uint32_t bar) {
  asm volatile("cp.async.bulk.tensor.2d.shared::cluster.global.mbarrier::complete_tx::bytes [%0], [%1, {%3,%4}], [%2];" ::"r"(dst), "l"(tm), "r"(bar), "r"(c0), "r"(c1) : "memory");
}
__device__ __forceinline__ void tma_ld3(uint32_t dst, const CUtensorMap* tm, int c0, int c1, int c2, uint32_t bar) {
  asm volatile("cp.async.bulk.tensor.3d.shared::cluster.global.mbarrier::complete_tx::bytes [%0], [%1, {%3,%4,%5}], [%2];" ::"r"(dst), "l"(tm), "r"(bar), "r"(c0), "r"(c1), "r"(c2) : "memory");
}
__device__ __forceinline__ void tma_ld3h(uint32_t dst, const CUtensorMap* tm, int c0, int c1, int c2, uint32_t bar, uint64_t pol) {
  asm volatile("cp.async.bulk.tensor.3d.shared::cluster.global.mbarrier::complete_tx::bytes.L2::cache_hint [%0], [%1, {%3,%4,%5}], [%2], %6;" ::"r"(dst), "l"(tm), "r"(bar), "r"(c0), "r"(c1), "r"(c2), "l"(pol) : "memory");
}
__device__ __forceinline__ uint64_t policy_evict_first() {
  uint64_t p;
  asm("createpolicy.fractional.L2::evict_first.b64 %0, 1.0;" : "=l"(p));
  return p;
}
__device__ __forceinline__ void tma_st3(const CUtensorMap* tm, uint32_t src, int c0, int c1, int c2) {
  asm volatile("cp.async.bulk.tensor.3d.global.shared::cta.bulk_group [%0, {%2,%3,%4}], [%1];" ::"l"(tm), "r"(src), "r"(c0), "r"(c1), "r"(c2) : "memory");
}
__device__ __forceinline__ void tma_st4(const CUtensorMap* tm, uint32_t src, int c0, int c1, int c2, int c3) {
  asm volatile("cp.async.bulk.tensor.4d.global.shared::cta.bulk_group [%0, {%2,%3,%4,%5}], [%1];" ::"l"(tm), "r"(src), "r"(c0), "r"(c1), "r"(c2), "r"(c3) : "memory");
}
__device__ __forceinline__ void tma_st5(const CUtensorMap* tm, uint32_t src, int c0) {
  asm volatile("cp.async.bulk.tensor.5d.global.shared::cta.bulk_group [%0, {%2,%3,%3,%3,%3}], [%1];" ::"l"(tm), "r"(src), "r"(c0), "r"(0) : "memory");
}
__device__ __forceinline__ void bulk_commit() { asm volatile("cp.async.bulk.commit_group;" ::: "memory"); }
template <int N> __device__ __forceinline__ void bulk_wait_read() { asm volatile("cp.async.bulk.wait_group.read %0;" ::"n"(N) : "memory"); }
template <int N> __device__ __forceinline__ void bulk_wait() { asm volatile("cp.async.bulk.wait_group %0;" ::"n"(N) : "memory"); }
__device__ __forceinline__ void fence_async_smem() { asm volatile("fence.proxy.async.shared::cta;" ::: "memory"); }
__device__ __forceinline__ void wg_fence() { asm volatile("wgmma.fence.sync.aligned;" ::: "memory"); }
__device__ __forceinline__ void wg_commit() { asm volatile("wgmma.commit_group.sync.aligned;" ::: "memory"); }
template <int N> __device__ __forceinline__ void wg_wait() { asm volatile("wgmma.wait_group.sync.aligned %0;" ::"n"(N) : "memory"); }
template <int R> __device__ __forceinline__ void fence_regs(float (&d)[R]) {
#pragma unroll
  for (int i = 0; i < R; i++) asm volatile("" : "+f"(d[i])::"memory");
}
__device__ __forceinline__ uint64_t mk_desc(uint32_t addr) {
  return (uint64_t)((addr & 0x3FFFF) >> 4) | (1ull << 16) | (64ull << 32) | (1ull << 62);
}
__device__ __forceinline__ uint32_t pack2(float lo, float hi) {
  uint32_t r;
  asm("cvt.rn.bf16x2.f32 %0, %1, %2;" : "=r"(r) : "f"(hi), "f"(lo));
  return r;
}
__device__ __forceinline__ void stsm4(uint32_t ad, uint32_t a, uint32_t b, uint32_t c, uint32_t d) {
  asm volatile("stmatrix.sync.aligned.m8n8.x4.shared.b16 [%0], {%1,%2,%3,%4};" ::"r"(ad), "r"(a), "r"(b), "r"(c), "r"(d) : "memory");
}
__device__ __forceinline__ void stsm4t(uint32_t ad, uint32_t a, uint32_t b, uint32_t c, uint32_t d) {
  asm volatile("stmatrix.sync.aligned.m8n8.x4.trans.shared.b16 [%0], {%1,%2,%3,%4};" ::"r"(ad), "r"(a), "r"(b), "r"(c), "r"(d) : "memory");
}

__device__ __forceinline__ void stsm2t(uint32_t ad, uint32_t a, uint32_t b) {
  asm volatile("stmatrix.sync.aligned.m8n8.x2.trans.shared.b16 [%0], {%1,%2};" ::"r"(ad), "r"(a), "r"(b) : "memory");
}
__device__ __forceinline__ void red_add(unsigned* p) { asm volatile("red.relaxed.gpu.global.add.u32 [%0], 1;" ::"l"(p) : "memory"); }
__device__ __forceinline__ void fence_release() { asm volatile("fence.release.gpu;" ::: "memory"); }
__device__ __forceinline__ void fence_async_global() { asm volatile("fence.proxy.async.global;" ::: "memory"); }
__device__ __forceinline__ void tma_pf2(const CUtensorMap* tm, int c0, int c1) {
  asm volatile("cp.async.bulk.prefetch.tensor.2d.L2.global [%0, {%1,%2}];" ::"l"(tm), "r"(c0), "r"(c1) : "memory");
}
__device__ __forceinline__ void tma_pf3(const CUtensorMap* tm, int c0, int c1, int c2) {
  asm volatile("cp.async.bulk.prefetch.tensor.3d.L2.global [%0, {%1,%2,%3}];" ::"l"(tm), "r"(c0), "r"(c1), "r"(c2) : "memory");
}
__device__ __forceinline__ uint64_t policy_evict_unchanged() {
  uint64_t p;
  asm("createpolicy.fractional.L2::evict_unchanged.b64 %0, 1.0;" : "=l"(p));
  return p;
}

__device__ __forceinline__ int lane_id() {
  int l;
  asm volatile("mov.u32 %0, %%laneid;" : "=r"(l));
  return l;
}
__device__ __forceinline__ void poll64x4(const unsigned long long* p, unsigned long long (&v)[4]) {
  asm volatile("{\n.reg .pred p;\n.reg .u32 c;\n.reg .b64 t, u;\nmov.u32 c, 0;\nWAIT:\n"
               "ld.relaxed.gpu.global.u64 %0, [%4];\nld.relaxed.gpu.global.u64 %1, [%4+512];\n"
               "ld.relaxed.gpu.global.u64 %2, [%4+1024];\nld.relaxed.gpu.global.u64 %3, [%4+1536];\n"
               "or.b64 t, %0, %1;\nor.b64 u, %2, %3;\nor.b64 t, t, u;\nsetp.ge.s64 p, t, 0;\n@p bra DONE;\n"
               "add.u32 c, c, 1;\nsetp.lt.u32 p, c, 0x400000;\n@p bra WAIT;\ntrap;\nDONE:\n}"
               : "=l"(v[0]), "=l"(v[1]), "=l"(v[2]), "=l"(v[3]) : "l"(p) : "memory");
}

constexpr int G_STAGE = WBLK + XBLK;
constexpr int OFF_XR = 4 * G_STAGE;
constexpr int OFF_WS = OFF_XR + 6 * 8192;
constexpr int OFF_F = OFF_WS + 2 * 8192;
constexpr int OFF_WRAW = OFF_F + 8192;
constexpr int OFF_BAR = OFF_WRAW + 8192;
constexpr int OFF_GB = OFF_BAR + 1024;
constexpr int SMEM_BYTES = OFF_GB + 512;
constexpr int OFF_H0B = 10 * 8192;
constexpr int OFF_E = OFF_WRAW + 3072;
constexpr int B_RAWX = 0, B_F = 48, B_ROLE = 56, B_H0 = 80, B_H1 = 96, B_YFREE = 120, B_H0C = 136,
              B_EMPTY = 144,
              B_STGX = 192, B_STGW = 240, B_Y = 256, B_OUT = 272, B_YP = 352,
              B_FULL = 432, B_RAWW = 464, B_DONE = 496, S_ROLE = 576, S_PROBE = 592;

struct Maps { CUtensorMap x, we, wo, xst[2], wst, yst[2], yld[2], out, xe[2], w30; };

__device__ __forceinline__ int chunk_of(int n) { return n < 16 ? n : 31 - n; }
__device__ __forceinline__ bool has_x2(int id, int n, int g) { return (((id >> 5) ^ n) & 1) == 0 && ((n >> 1) & 1) == g; }
__device__ __forceinline__ uint32_t x_base(int s, int idx, uint32_t pgmask, int& par) {
  const int page = idx >> 3, o = idx & 7;
  par = (s ^ (pgmask >> page) ^ __popc(o)) & 1;
  return (page << 21) | ((o & 3) << 16) | ((o >> 2) << 19);
}
__device__ __forceinline__ uint32_t read_info(uint32_t bar, int i) {
  uint32_t v;
  mbar_wait(bar + B_ROLE + 8 * i, 0);
  asm volatile("ld.shared.b32 %0, [%1];" : "=r"(v) : "r"(bar + S_ROLE + 4 * i) : "memory");
  return v;
}
__device__ __forceinline__ void send_info(uint32_t bar, int i, uint32_t v) {
#pragma unroll
  for (int r = 0; r < 2; r++)
    asm volatile("{\n.reg .b32 a, m;\nmapa.shared::cluster.u32 a, %0, %2;\nmapa.shared::cluster.u32 m, %1, %2;\n"
                 "st.async.weak.shared::cluster.mbarrier::complete_tx::bytes.b32 [a], %3, [m];\n}"
                 ::"r"(bar + S_ROLE + 4 * i), "r"(bar + B_ROLE + 8 * i), "r"(r), "r"(v) : "memory");
}
__device__ __forceinline__ unsigned probe(uint8_t* p, int lane) {
  if (lane < 2) *(uint4*)(p + lane * 16) = make_uint4(0, 0, 0, 0);
  __syncwarp();
  unsigned v, t0 = 0, t1 = 0;
  if (lane == 0) {
    asm volatile("mov.u32 %0, %%clock;" : "=r"(t0)::"memory");
    asm volatile("atom.relaxed.gpu.global.exch.b32 %0, [%1], 0;" : "=r"(v) : "l"(p) : "memory");
    asm volatile("{\n.reg .pred p;\nsetp.ne.u32 p, %1, 0xffffffff;\nmov.u32 %0, 0;\n@p mov.u32 %0, %%clock;\n}" : "=r"(t1) : "r"(v) : "memory");
  }
  return t1 - t0;
}

template <bool ISX>
__device__ __forceinline__ void t_issue(float (&t)[32], uint32_t sb, uint32_t raw) {
  const uint64_t da = mk_desc(sb + OFF_F), db = mk_desc(raw);
  wg_fence();
#pragma unroll
  for (int kk = 0; kk < (ISX ? 4 : 1); kk++) wgmma_fwd<1>(t, da + 2 * kk, db + 128 * kk, kk);
  wg_commit();
}
template <bool ISX>
__device__ __forceinline__ void t_finish(float (&t)[32], uint32_t dst, uint32_t sbar, int sw, int wg, int w, int lane) {
  fence_regs(t);
  if (ISX) asm volatile("bar.sync %0, 128;" ::"r"(1 + wg) : "memory");
  const int m = lane >> 3, r = lane & 7;
  uint32_t ad = dst + (8 * w + r) * 128;
  if (ISX) ad += ((((m & 1) * 4 + (m >> 1)) ^ sw ^ r) << 4);
  else ad += (m & 1) * 4096 + (((m >> 1) ^ sw ^ r) << 4);
#pragma unroll
  for (int i = 0; i < 4; i++) {
    const uint32_t a = ISX ? ((ad ^ ((i & 1) * 32)) + (i >> 1) * 4096) : (ad ^ (i * 32));
    stsm4(a, pack2(t[8 * i], t[8 * i + 1]), pack2(t[8 * i + 2], t[8 * i + 3]), pack2(t[8 * i + 4], t[8 * i + 5]), pack2(t[8 * i + 6], t[8 * i + 7]));
  }
  __syncwarp();
  if (lane == 0) mbar_arrive(sbar);
}
template <int NT, int K0, int K1>
__device__ __forceinline__ void batch(float (&yr)[80], float (&yi)[80], float (&t)[32], uint32_t st, int wg, int sd, uint32_t fa, uint32_t raw) {
  const uint64_t w0 = mk_desc(st + wg * 8192), x0 = mk_desc(st + WBLK);
  const uint64_t da = mk_desc(fa), db = mk_desc(raw);
  wg_fence();
  if (NT) {
#pragma unroll
    for (int kk = 0; kk < NT; kk++) wgmma_fwd<1>(t, da + 2 * kk, db + 128 * kk, kk);
    wg_commit();
  }
#pragma unroll
  for (int kk = K0; kk < K1; kk++) {
    const uint64_t wr = w0 + kk * 128, wi = wr + 256, xr = x0 + kk * 2, xi = xr + 4;
    wgmma_main<1>(yr, wr, xr, kk ? 1 : sd);
    wgmma_main<1>(yi, wr, xi, kk ? 1 : sd);
    wgmma_main<1>(yr, wi, xi, 1);
    wgmma_main<-1>(yi, wi, xr, 1);
  }
  wg_commit();
}

#define X_WAIT() PROF_W(wraw, mbar_wait(bar + B_RAWX + 8 * (wg * 3 + xs), xph))
#define X_ISSUE() t_issue<true>(t, sb, sb + OFF_XR + (wg * 3 + xs) * 8192)
#define X_FINISH(sw) do { t_finish<true>(t, sb + OFF_XR + (wg * 3 + xs) * 8192, bar + B_STGX + 8 * (wg * 3 + xs), sw, wg, w, lane); \
                          if (++xs == 3) { xs = 0; xph ^= 1; } } while (0)
#define W_WAIT(n) PROF_W(wraw, mbar_wait(bar + B_RAWW + 8 * (wg * 2 + ((n) & 1)), ((n) >> 1) & 1))
#define WRAW(n) (sb + OFF_WRAW + (wg * 2 + ((n) & 1)) * 2048)
#define W_FINISH() t_finish<false>(t, sb + OFF_WS + wg * 8192, bar + B_STGW + 8 * wg, (bid >> 1) & 7, wg, w, lane)

__device__ __forceinline__ void gelu_store(float (&hz)[28], uint32_t ad) {
#pragma unroll
  for (int i = 0; i < 28; i++) {
    const float in = hz[i] * fmaf(hz[i] * hz[i], 8.f * 0.044715f * 0.7978845608028654f, 2.f * 0.7978845608028654f);
    float th;
    asm("tanh.approx.f32 %0, %1;" : "=f"(th) : "f"(in));
    hz[i] = fmaf(hz[i], th, hz[i]);
  }
#pragma unroll
  for (int jj = 0; jj < 3; jj++) {
    const float* c = hz + 8 * jj;
    stsm4t(ad + jj * 2048, pack2(c[0], c[1]), pack2(c[2], c[3]), pack2(c[4], c[5]), pack2(c[6], c[7]));
  }
  stsm2t(ad + 3 * 2048, pack2(hz[24], hz[25]), pack2(hz[26], hz[27]));
}

template <int g>
__device__ __forceinline__ void manager(const Maps& tm, unsigned* ctr, const uint32_t sb, const int bid) {
  const uint32_t bar = sb + OFF_BAR, rank = bid & 1;
  const uint64_t pol = policy_evict_first();
  const int id = read_info(bar, 0) * 2 + rank;
  int li = 0;
  auto refill = [&](int sl) {
    if (li >= 32) return;
    const uint32_t fb = bar + B_RAWX + 8 * (g * 3 + sl);
    mbar_expect(fb, 8192);
    tma_ld3h(sb + OFF_XR + (g * 3 + sl) * 8192, &tm.x, (li >> 1) * 64, ((li & 1) ? 128 + (id & 31) : 2 * (id & 63) + g) * MT, id >> 6, fb, pol);
    li += (li & 1) || has_x2(id, li >> 1, g) ? 1 : 2;
  };
#pragma unroll 1
  for (int sl = 0; sl < 3; sl++) refill(sl);
  int xs = 0, xph = 0, yp = 0;
  int wrow = (rank * 2 + (bid >> 6)) * 128 + g * 64 + ((bid >> 1) & 31);
  mbar_wait(bar + B_STGW + 8 * g, 0);
  fence_async_smem();
  tma_st4(&tm.wst, sb + OFF_WS + g * 8192, 0, 0, 0, wrow);
  bulk_commit();
  const uint32_t pgmask = read_info(bar, 1);
#pragma unroll 1
  for (int n = 0; n < 32; n++) {
    unsigned freed = 128;
    if (n >= WR) asm volatile("ld.relaxed.gpu.global.u32 %0, [%1];" : "=r"(freed) : "l"(&ctr[(C_LOADED + n - WR) * 32]) : "memory");
    if (n < 16) {
#pragma unroll 1
      for (int j = 0; j < (has_x2(id, n, g) ? 2 : 1); j++) {
        const int t = j ? 128 + (id & 31) : 2 * (id & 63) + g;
        int par0, par1;
        const uint32_t off0 = x_base(id >> 6, n * 10 + (t >> 5), pgmask, par0), off1 = x_base(id >> 6, n * 10 + 5 + (t >> 5), pgmask, par1);
        const uint32_t buf = sb + OFF_XR + (g * 3 + xs) * 8192;
        mbar_wait(bar + B_STGX + 8 * (g * 3 + xs), xph);
        fence_async_smem();
        tma_st5(&tm.xst[par0], buf, (off0 + (par0 << 12) + (t & 31) * 128) >> 1);
        tma_st5(&tm.xst[par1], buf + 4096, (off1 + (par1 << 12) + (t & 31) * 128) >> 1);
        bulk_commit();
        bulk_wait_read<0>();
        refill(xs);
        if (++xs == 3) { xs = 0; xph ^= 1; }
      }
    }
    if (n > 16 + LW && n <= YFLUSH && (n - 17 - LW) % YSTEP == 0) {
      if (yp == 0 || yp == 3) mbar_wait(bar + B_Y + 8 * g, yp & 1);
#pragma unroll 1
      do {
        tma_st4(&tm.yst[0], sb + OFF_XR + (g * 3 + (yp < 3 ? yp : yp - 3)) * 8192, 0, yp * 32, id & 62, (id >> 6) * 4 + rank * 2 + g);
      } while (++yp < 2);
      bulk_commit();
      bulk_wait_read<0>();
      if (yp == 2) mbar_arrive(bar + B_YFREE + 8 * g);
    }
    if (freed < 128) flag_wait(&ctr[(C_LOADED + n - WR) * 32], 128);
    if (n) {
      mbar_wait(bar + B_STGW + 8 * g, n & 1);
      fence_async_smem();
      tma_st4(&tm.wst, sb + OFF_WS + g * 8192, 0, 0, 0, wrow);
      bulk_commit();
    }
    wrow += WCHUNK / 128;
    if (wrow >= WR * WCHUNK / 128) wrow -= WR * WCHUNK / 128;
    if (n < 30) {
      const int cp = chunk_of(n + 2) * 64 + (bid >> 1), sl = g * 2 + (n & 1);
      mbar_expect(bar + B_RAWW + 8 * sl, 2048);
      tma_ld3h(sb + OFF_WRAW + sl * 2048, &tm.we + (cp >> 9), 0, 0, (cp & 511) * 8 + ((n + 2) >> 4) * 4 + rank * 2 + g, bar + B_RAWW + 8 * sl, pol);
    }
    if (n < 4) {
#pragma unroll 1
      for (int q = 4 + n; q < 16; q += 4) {
        const int cp = q * 64 + (bid >> 1);
        tma_pf3(&tm.we + (cp >> 9), 0, 0, (cp & 511) * 8 + rank * 2 + g);
      }
    }
    bulk_wait<0>();
    mbar_arrive(bar + B_DONE + 8 * (n & 7));
    mbar_arrive(bar + B_RAWW + 8 * (g * 2 + ((n + 1) & 1)));
  }
  const int b = id >> 6, u = (id >> 1) & 31;
  flag_wait(&ctr[(C_LOADED + 31) * 32], 128);
#pragma unroll 1
  for (int p = 0; p < 5; p++) {
    mbar_wait(bar + B_YP + 8 * (g * 5 + p), 0);
    fence_async_smem();
    tma_st4(&tm.yst[1], sb + (p * 2 + g) * 8192, 0, p * 32, 2 * u, b * 4 + rank * 2 + g);
  }
  bulk_commit();
  bulk_wait<0>();
  mbar_arrive(bar + B_DONE);
#pragma unroll 1
  for (int i = 0; i < 10; i++) {
    const int hf = i >= 5, k = i - 5 * hf;
    mbar_wait(bar + B_OUT + 8 * (g * 5 + k), hf);
    fence_async_smem();
    tma_st3(&tm.out, sb + (hf ? 0 : k < 4 ? OFF_XR : OFF_H0B - 65536) + (2 * k + g) * 8192, (hf * 4 + rank * 2 + (u & 1)) * 64, ((u >> 1) * 10 + 2 * k + g) * MT, b);
    bulk_commit();
  }
  bulk_wait_read<0>();
  if (g == 0) PROF_T(12);
}

__global__ void __cluster_dims__(2, 1, 1) __launch_bounds__(512, 1)
k1_main(uint8_t* __restrict__ xbuf, const void* __restrict__ fimg, unsigned* ctr, const __nv_bfloat16* __restrict__ gamma,
        const __nv_bfloat16* __restrict__ beta, const __grid_constant__ Maps tm) {
  extern __shared__ __align__(1024) uint8_t smem_raw[];
  const uint32_t sb = s2u(smem_raw);
  const uint32_t bar = sb + OFF_BAR;
  const int warp = __shfl_sync(0xffffffffu, threadIdx.x >> 5, 0);
  const int bid = (int)blockIdx.x - 4;
  const uint32_t rank = bid & 1;
  if (warp >= 12) {
    asm volatile("setmaxnreg.dec.sync.aligned.u32 24;");
    asm volatile("barrier.cluster.arrive.relaxed.aligned;" ::: "memory");
    if (bid >= 0) {
      const int lane = lane_id(), k = bid >> 1;
      if (rank == 0 || k < XPAGES) {
        const uint32_t off = rank ? (k << 21) + 0xb0000 : (XPAGES << 21) + ((k >> 4) << 14) + (k & 15) * 128;
        const unsigned lat = probe(xbuf + off + (warp & 1) * 4096 + (warp & 2) * 1024, lane);
        if (lane == 0) asm volatile("st.shared.b32 [%0], %1;" ::"r"(bar + S_PROBE + 4 * (warp & 3)), "r"(lat) : "memory");
      }
      asm volatile("bar.sync 4, 128;" ::: "memory");
      asm volatile("barrier.cluster.wait.aligned;" ::: "memory");
      if (warp == 14 && lane == 0) {
        uint32_t l0, l1, l2, l3;
        asm volatile("ld.shared.v4.b32 {%0, %1, %2, %3}, [%4];" : "=r"(l0), "=r"(l1), "=r"(l2), "=r"(l3) : "r"(bar + S_PROBE) : "memory");
        const int near = min(l1, l3) < min(l0, l2);
        if (rank) {
          send_info(bar, 2, near);
        } else {
          unsigned long long add = 1ull << (8 * near), v, *reg = (unsigned long long*)&ctr[C_REG * 32];
          if (k < XPAGES) add += (unsigned long long)(read_info(bar, 2) ^ near ^ 1) << (16 + k);
          PROF_T(14);
          asm volatile("{\n.reg .pred p;\n.reg .u32 c;\nmov.u32 c, 0;\nAGAIN:\n"
                       "atom.relaxed.gpu.global.add.u64 %0, [%1], %2;\nsetp.lt.s64 p, %0, 0;\n@p bra DONE;\n"
                       "add.u32 c, c, 1;\nsetp.lt.u32 p, c, 0x100000;\n@p bra AGAIN;\ntrap;\nDONE:\n}" : "=l"(v) : "l"(reg), "l"(add) : "memory");
          const int ticket = (v >> (8 * near)) & 255;
          send_info(bar, 0, ticket < 32 ? near * 32 + ticket : (near ^ 1) * 32 + 63 - ticket);
          PROF_T(15); PROF_V(16, near); PROF_V(17, ticket < 32 ? near * 32 : (near ^ 1) * 32);
          asm volatile("{\n.reg .pred p;\n.reg .u32 c, a, b;\nmov.u32 c, 0;\nWAIT:\n"
                       "ld.relaxed.gpu.global.u64 %0, [%1];\ncvt.u32.u64 a, %0;\nbfe.u32 b, a, 8, 8;\nand.b32 a, a, 255;\nadd.u32 a, a, b;\n"
                       "setp.ge.u32 p, a, 64;\n@p bra DONE;\n"
                       "add.u32 c, c, 1;\nsetp.lt.u32 p, c, 0x400000;\n@p bra WAIT;\ntrap;\nDONE:\n}" : "=l"(v) : "l"(reg) : "memory");
          send_info(bar, 1, (uint32_t)(v >> 16));
          PROF_T(13);
        }
      }
      __syncwarp();
      if (warp - 12 < NFL && elect_one()) {
#pragma unroll 1
        for (int n = warp - 12; n < 33; n += NFL) {
          int f = n;
          if (n == 32) f += (read_info(bar, 0) >> 5) * 2 + rank;
          mbar_wait(bar + B_DONE + 8 * (n & 7), (n >> 3) & 1);
          fence_release();
          red_add(&ctr[(C_FLAG + f) * 32]);
          if (n < 32) { PROF_T(64 + n); PROF_V(192 + n, tm0); } else { PROF_V(4, tm0); }
        }
      }
      if (warp == 15 && elect_one()) {
#pragma unroll 1
        for (int v = 0; v < 64; v++) {
          mbar_wait(bar + B_FULL + 8 * (v & 3), (v >> 2) & 1);
          mbar_arrive(bar + B_EMPTY + 8 * (v & 3));
          if ((v & 1) && (v < 2 * (32 - WR) || v == 63)) red_add(&ctr[(C_LOADED + (v >> 1)) * 32]);
        }
      }
      __syncwarp();
    } else {
      if (blockIdx.x == 0 && warp == 12 && lane_id() < 4)
        asm volatile("st.relaxed.gpu.global.u64 [%0], %1;" ::"l"(&ctr[C_REG * 32 + 2 * lane_id()]), "l"(1ull << 63) : "memory");
      __syncwarp();
      asm volatile("barrier.cluster.wait.aligned;" ::: "memory");
    }
    asm volatile("barrier.cluster.arrive.relaxed.aligned;\nbarrier.cluster.wait.aligned;" ::: "memory");
    return;
  } else {
    if (elect_one()) {
      if (warp == 0) PROF_T(0);
      if (warp >= 6) asm volatile("prefetch.tensormap [%0];" ::"l"(&tm.x + (warp - 6)) : "memory");
      const int cnt = warp < 3 ? 1 : warp == 3 ? 5 : warp < 9 ? 4 : 2;
#pragma unroll
      for (int i = 0; i < 6; i++) mbar_init(bar + warp * 48 + 8 * i, cnt);
      if (warp == 1) {
        if (bid >= 0) {
          mbar_expect(bar + B_F, 8192);
          bulk_ld(sb + OFF_F, fimg, 8192, bar + B_F);
        }
        mbar_expect(bar + B_ROLE, 4);
        mbar_expect(bar + B_ROLE + 8, 4);
        mbar_expect(bar + B_ROLE + 16, 4);
      }
      asm volatile("fence.mbarrier_init.release.cluster;" ::: "memory");
    }
    asm volatile("bar.sync 0, 384;" ::: "memory");
    asm volatile("barrier.cluster.arrive.relaxed.aligned;" ::: "memory");
    if (threadIdx.x == 64) PROF_T(20);
    if (bid >= 0 && warp < 6 && elect_one()) {
      const int g = warp & 1, q = warp >> 2;
      const uint64_t pol = policy_evict_first();
      if (warp < 2) {
        tma_pf3(&tm.x, 0, (2 * (bid & 63) + g) * MT, bid >> 6);
        if (has_x2(bid, 0, g)) tma_pf3(&tm.x, 0, (128 + (bid & 31)) * MT, bid >> 6);
      } else {
        const uint32_t fb = bar + B_RAWW + 8 * (g * 2 + q);
        mbar_expect(fb, 2048);
        tma_ld3h(sb + OFF_WRAW + (g * 2 + q) * 2048, &tm.we, 0, 0, (q * 64 + (bid >> 1)) * 8 + rank * 2 + g, fb, pol);
        if (!q) mbar_arrive(fb);
      }
    }
    __syncwarp();
  }
  if (warp >= 8) {
    asm volatile("setmaxnreg.dec.sync.aligned.u32 40;");
    if (bid < 0) {
      asm volatile("barrier.cluster.wait.aligned;" ::: "memory");
    } else if (warp == 9 || warp == 10) {
      asm volatile("barrier.cluster.wait.aligned;\nbarrier.cluster.arrive.relaxed.aligned;" ::: "memory");
      if (elect_one()) {
        if (warp == 9) manager<0>(tm, ctr, sb, bid); else manager<1>(tm, ctr, sb, bid);
      }
      __syncwarp();
      asm volatile("barrier.cluster.wait.aligned;" ::: "memory");
      return;
    } else if (warp == 11) {
      asm volatile("barrier.cluster.wait.aligned;" ::: "memory");
      if (elect_one()) {
        const uint8_t* ws = g_W + (size_t)((read_info(bar, 0) & 31) * 2 + rank) * 2 * WBLK;
        int slot = 0;
#pragma unroll 1
        for (int n = 0; n < 32; n++) {
          const uint8_t* src = ws + (size_t)slot * WCHUNK;
          const uint32_t s8 = (n & 1) * 16, dst = sb + (n & 1) * 2 * G_STAGE;
          const int ph = ((n >> 1) & 1) ^ 1;
          if (++slot == WR) slot = 0;
          flag_wait(&ctr[(C_FLAG + n) * 32], 128);
          fence_async_global();
          PROF_T(32 + n);
#pragma unroll
          for (int h = 0; h < 2; h++) {
            mbar_wait(bar + B_EMPTY + s8 + 8 * h, ph);
            mbar_expect(bar + B_FULL + s8 + 8 * h, WBLK);
            bulk_ld(dst + h * G_STAGE, src + h * WBLK, WBLK, bar + B_FULL + s8 + 8 * h);
          }
        }
      }
      __syncwarp();
    } else {
      asm volatile("barrier.cluster.wait.aligned;" ::: "memory");
      if (elect_one()) {
        const int role = read_info(bar, 0);
        const uint32_t pgmask = read_info(bar, 1);
        PROF_T(1);
        const int b = role >> 5, u = role & 31;
        const int dq = rank * 2 + (u & 1), t0 = (u >> 1) * 10;
        const uint64_t pef = policy_evict_first(), pen = policy_evict_unchanged();
        const uint8_t* xs = xbuf + ((((u >> 1) & 3) << 14) | (((u >> 3) & 1) << 18) | ((u >> 4) << 20) | ((u & 1) << 13));
#pragma unroll 1
        for (int n = 0; n < 32; n++) {
          const int c = chunk_of(n);
          const uint64_t polx = (n < XKEEP || n >= 16) ? pef : pen;
          const uint32_t s8 = (n & 1) * 16, dst = sb + (n & 1) * 2 * G_STAGE + WBLK + rank * 8192;
          const int ph = ((n >> 1) & 1) ^ 1;
          uint32_t xo[6];
#pragma unroll
          for (int g = 0; g < 6; g++) {
            int par;
            xo[g] = x_base(b, c * 10 + (g / 3) * 5 + rank * 2 + g % 3, pgmask, par);
            xo[g] += ((par ^ u) & 1) << 12;
            asm volatile("" : "+r"(xo[g]));
          }
          if (n < 16) {
            flag_wait(&ctr[(C_FLAG + n) * 32], 128);
            fence_async_global();
          }
#pragma unroll
          for (int h = 0; h < 2; h++) {
            const uint32_t fb = bar + B_FULL + s8 + 8 * h;
            mbar_wait(bar + B_EMPTY + s8 + 8 * h, ph);
            mbar_expect(fb, XBLK);
#pragma unroll
            for (int g = 0; g < 3; g++) {
              const int skip = (g == 0 && rank) ? 2048 : 0, len = (g == (rank ? 0 : 2)) ? 2048 : 4096;
              bulk_ld_mc_h(dst + h * G_STAGE + g * 4096 + skip, xs + xo[3 * h + g] + skip, len, fb, 3, polx);
            }
          }
        }
        flag_wait(&ctr[C_E * 32], 4);
        flag_wait(&ctr[(C_FLAG + YFLUSH) * 32], 128);
        fence_async_global();
        mbar_expect(bar + B_H0C, 6 * 8192);
        for (int i = 0; i < 3; i++) tma_ld2(sb + OFF_XR + i * 16384, &tm.yld[0], 0, ((b * 4 + dq) * NT + t0 + 2 * i) * 64, bar + B_H0C);
        static_assert(YFLUSH >= 23, "phase of the B_DONE ring");
        mbar_wait(bar + B_DONE + 8 * 7, 1);
        mbar_expect(bar + B_H0, 2 * 8192 + 7168 + 5120 + 512);
        bulk_ld(sb + OFF_F, g_Gimg, 7168, bar + B_H0);
        tma_ld2(sb + OFF_WS, &tm.yld[0], 0, ((b * 4 + dq) * NT + t0 + 6) * 64, bar + B_H0);
        tma_pf2(&tm.yld[0], 0, ((b * 4 + dq) * NT + t0 + 8) * 64);
        for (int hf = 0; hf < 2; hf++) {
          bulk_ld(sb + OFF_E + hf * 2560, g_E + ((b * 8 + hf * 4 + dq) * NT + t0) * 64, 2560, bar + B_H0);
          bulk_ld(sb + OFF_GB + hf * 256, gamma + (hf * 4 + dq) * 64, 128, bar + B_H0);
          bulk_ld(sb + OFF_GB + hf * 256 + 128, beta + (hf * 4 + dq) * 64, 128, bar + B_H0);
        }
        mbar_wait(bar + B_EMPTY + 8 * 2, 1);
        mbar_expect(bar + B_H0 + 8, 16384);
        tma_ld2(sb + OFF_H0B, &tm.yld[0], 0, ((b * 4 + dq) * NT + t0 + 8) * 64, bar + B_H0 + 8);
        flag_wait(&ctr[(C_FLAG + 32 + b * 2 + rank) * 32], 32);
        fence_async_global();
        PROF_T(5);
        for (int i = 0; i < 5; i++) {
          const uint32_t fb = bar + B_H1 + 8 * (i >> 1);
          if ((i & 1) == 0) mbar_expect(fb, i < 4 ? 32768 : 16384);
          tma_ld2(sb + i * 16384, &tm.yld[1], 0, ((b * 4 + dq) * NT + t0 + 2 * i) * 64, fb);
        }
      }
      __syncwarp();
      const int lane = lane_id();
      unsigned old = 0;
      if (lane == 0) old = atomicAdd(&ctr[C_EXIT * 32], 1);
      if (__shfl_sync(0xffffffffu, old, 0) == 127) {
        for (int i = lane; i < C_NUM; i += 32) *(uint4*)&ctr[i * 32] = make_uint4(0, 0, 0, 0);
      }
    }
    asm volatile("barrier.cluster.arrive.relaxed.aligned;\nbarrier.cluster.wait.aligned;" ::: "memory");
  } else {
    asm volatile("setmaxnreg.inc.sync.aligned.u32 224;");
    const int wg = warp >> 2, w = warp & 3;
    int lane = lane_id();
    asm volatile("barrier.cluster.wait.aligned;" ::: "memory");
    if (bid < 0) {
      float ea[80], eb[80];
      const int b = blockIdx.x >> 1;
      constexpr int ES = 32768 + 2 * XBLK;
#pragma unroll 1
      for (int k = -3; k < 8; k++) {
        const int sl = (k + 3) % 3;
        if (k >= 0) {
          mbar_wait(bar + B_RAWX + 8 * sl, (k / 3) & 1);
          const uint64_t da = mk_desc(sb + sl * ES + wg * 16384), db = mk_desc(sb + sl * ES + 32768);
          wg_fence();
#pragma unroll
          for (int kk = 0; kk < 8; kk++) {
            const uint64_t a0 = da + (kk & 3) * 128, b0 = db + (kk & 3) * 2 + (kk >> 2) * (XBLK >> 4);
            wgmma_main<1>(ea, a0, b0, (k | kk) != 0);
            wgmma_main<1>(eb, a0 + 512, b0, (k | kk) != 0);
          }
          wg_commit();
          wg_wait<0>();
          asm volatile("bar.sync 3, 256;" ::: "memory");
        }
        if (k + 3 < 8 && warp == 0 && elect_one()) {
          if (k == -3) {
            for (int i = 0; i < 64; i++) {
              unsigned v;
              asm volatile("ld.relaxed.gpu.global.u32 %0, [%1];" : "=r"(v) : "l"(&ctr[(C_FLAG + 14) * 32]) : "memory");
              if (v >= 128) break;
              __nanosleep(500);
            }
          }
          const uint32_t dst = sb + sl * ES, fb = bar + B_RAWX + 8 * sl;
          mbar_expect(fb, ES);
          for (int q = 0; q < 4; q++) tma_ld2(dst + q * 8192, &tm.w30, rank * 256 + q * 64, (k + 3) * 64, fb);
          for (int q = 0; q < 2; q++) tma_ld3(dst + 32768 + q * XBLK, &tm.xe[q], (k + 3) * 64, 0, b, fb);
        }
        __syncwarp();
      }
      fence_regs(ea);
      fence_regs(eb);
      float* e0 = g_E + ((b * 8 + rank * 4 + wg * 2) * NT + 2 * (lane & 3)) * 64 + 16 * w + (lane >> 2);
#pragma unroll
      for (int i = 0; i < 80; i++) {
        const int o = (8 * (i >> 2) + (i & 1)) * 64 + ((i >> 1) & 1) * 8;
        e0[o] = ea[i];
        e0[o + NT * 64] = eb[i];
      }
      asm volatile("bar.sync 3, 256;" ::: "memory");
      if (threadIdx.x == 0) {
        fence_release();
        red_add(&ctr[C_E * 32]);
        PROF_T(28);
      }
      asm volatile("barrier.cluster.arrive.relaxed.aligned;\nbarrier.cluster.wait.aligned;" ::: "memory");
      return;
    }
    int id;
    {
      float yr[80], yi[80], t[32];

      int xs = 0, xph = 0;
      if (threadIdx.x == 0) PROF_T(24);
      mbar_wait(bar + B_F, 0);
      W_WAIT(0);
      t_issue<false>(t, sb, WRAW(0));
      wg_wait<0>();
      W_FINISH();
      id = __shfl_sync(0xffffffffu, read_info(bar, 0), 0) * 2 + rank;
      if (threadIdx.x == 0) PROF_T(25);
#pragma unroll 1
      for (int m = 0; m <= LW; m++) {
        X_WAIT();
        X_ISSUE();
        wg_wait<0>();
        X_FINISH((2 * id + wg) & 7);
        if (threadIdx.x == 0 && m == 0) PROF_T(26);
        if (has_x2(id, m, wg)) {
          X_WAIT();
          X_ISSUE();
          wg_wait<0>();
          X_FINISH(id & 7);
        }
        if (m < LW && m) {
          W_WAIT(m);
          t_issue<false>(t, sb, WRAW(m));
          wg_wait<0>();
          W_FINISH();
        }
      }
      if (threadIdx.x == 0) PROF_T(27);
      const int ym = lane >> 3, yr8 = lane & 7;
      const uint32_t yad = (ym >> 1) * 4096 + yr8 * 128 + (((2 * w + (ym & 1)) ^ yr8) << 4);
#define STAGE_PROF0()
#define STAGE_PROF1()
#define STAGE_BEGIN() PROF_W(wfull, mbar_wait(bar + B_FULL + 8 * (v & 3), (v >> 2) & 1)); STAGE_PROF0(); const uint32_t st = sb + (v & 3) * G_STAGE
#define RELEASE(vv) do { if (w == 0 && lane < 2) mbar_arrive_cluster(bar + B_EMPTY + 8 * ((vv) & 3), lane, 1); } while (0)
#define XRAW (sb + OFF_XR + (wg * 3 + xs) * 8192)
#define STAGE_W0(mw, sd) do { W_WAIT(mw); batch<1, 0, 2>(yr, yi, t, st, wg, sd, sb + OFF_F, WRAW(mw)); wg_wait<1>(); W_FINISH(); wg_wait<0>(); RELEASE(v); } while (0)
#define STAGE_PLAIN0(sd) do { batch<0, 0, 2>(yr, yi, t, st, wg, sd, 0, 0); wg_wait<0>(); RELEASE(v); } while (0)
#define STAGE_W1(mw, sd) do { W_WAIT(mw); batch<1, 0, 1>(yr, yi, t, st, wg, sd, sb + OFF_F, WRAW(mw)); wg_wait<1>(); if (sd) RELEASE(v - 1); \
                              W_FINISH(); batch<0, 1, 2>(yr, yi, t, st, wg, 1, 0, 0); } while (0)
#define STAGE_PLAIN1(sd) do { batch<0, 0, 1>(yr, yi, t, st, wg, sd, 0, 0); wg_wait<1>(); if (sd) RELEASE(v - 1); \
                              batch<0, 1, 2>(yr, yi, t, st, wg, 1, 0, 0); } while (0)
#pragma unroll 1
      for (int v = 0; v < 32; v++) {
        const int m = ((v + 1) >> 1) + LW;
        STAGE_BEGIN();
        if (!(v & 1) || v == 31) {
          STAGE_W1(m, v != 0);
        } else if (m >= 16) {
          STAGE_PLAIN1(1);
        } else {
          X_WAIT();
          batch<4, 0, 1>(yr, yi, t, st, wg, 1, sb + OFF_F, XRAW);
          wg_wait<1>();
          RELEASE(v - 1);
          X_FINISH((2 * id + wg) & 7);
          if (has_x2(id, m, wg)) {
            X_WAIT();
            batch<4, 1, 2>(yr, yi, t, st, wg, 1, sb + OFF_F, XRAW);
            wg_wait<1>();
            X_FINISH(id & 7);
          } else {
            batch<0, 1, 2>(yr, yi, t, st, wg, 1, 0, 0);
          }
        }
        STAGE_PROF1();
      }
      wg_wait<0>();
      fence_regs(yr);
      fence_regs(yi);
      RELEASE(31);
      {
        uint32_t hold[32];
#pragma unroll
        for (int j = 0; j < 20; j++) {
          const uint32_t p0 = pack2(yr[4 * j], yr[4 * j + 1]), p1 = pack2(yr[4 * j + 2], yr[4 * j + 3]);
          const uint32_t p2 = pack2(yi[4 * j], yi[4 * j + 1]), p3 = pack2(yi[4 * j + 2], yi[4 * j + 3]);
          if (j < 12) {
            stsm4t(sb + OFF_XR + wg * 3 * 8192 + yad + (j >> 2) * 8192 + (j & 3) * 1024, p0, p1, p2, p3);
          } else {
            hold[4 * j - 48] = p0; hold[4 * j - 47] = p1; hold[4 * j - 46] = p2; hold[4 * j - 45] = p3;
          }
        }
#pragma unroll
        for (int j = 0; j < 32; j++) asm volatile("" : "+r"(hold[j])::"memory");
        fence_async_smem();
        __syncwarp();
        if (lane == 0) mbar_arrive(bar + B_Y + 8 * wg);
        if (threadIdx.x == 0) PROF_T(2);
#pragma unroll
        for (int v = 32; v < 34; v++) {
          STAGE_BEGIN();
          STAGE_PLAIN0(v != 32);
          STAGE_PROF1();
        }
        mbar_wait(bar + B_YFREE + 8 * wg, 0);
#pragma unroll
        for (int j = 0; j < 8; j++)
          stsm4t(sb + OFF_XR + wg * 3 * 8192 + yad + (j >> 2) * 8192 + (j & 3) * 1024, hold[4 * j], hold[4 * j + 1], hold[4 * j + 2], hold[4 * j + 3]);
        fence_async_smem();
        __syncwarp();
        if (lane == 0) mbar_arrive(bar + B_Y + 8 * wg);
#pragma unroll
        for (int j = 0; j < 32; j++) t[j] = __uint_as_float(hold[j]);
      }
#pragma unroll 1
      for (int v = 34; v < 64; v++) {
        const int m = (v >> 1) + LW;
        STAGE_BEGIN();
        if (!(v & 1) && m < 32) {
          STAGE_W0(m, 1);
        } else {
          STAGE_PLAIN0(1);
          if (v == 49 && wg == 0) g_part[bid * 128 + w * 32 + lane] = ~0ull;
        }
        STAGE_PROF1();
      }
      wg_wait<0>();
      fence_regs(yr);
      fence_regs(yi);
      asm volatile("bar.sync 3, 256;" ::: "memory");
#pragma unroll
      for (int j = 0; j < 20; j++) {
        stsm4t(sb + wg * 8192 + yad + (j >> 2) * 16384 + (j & 3) * 1024, pack2(yr[4 * j], yr[4 * j + 1]), pack2(yr[4 * j + 2], yr[4 * j + 3]),
               pack2(yi[4 * j], yi[4 * j + 1]), pack2(yi[4 * j + 2], yi[4 * j + 3]));
        if ((j & 3) == 3) {
          __syncwarp();
          if (lane == 0) mbar_arrive(bar + B_YP + 8 * (wg * 5 + (j >> 2)));
        }
      }
      if (threadIdx.x == 0) PROF_T(3);
    }
    asm volatile("barrier.cluster.arrive.relaxed.aligned;" ::: "memory");
    lane = lane_id();
    const int tid = warp * 32 + lane, b = id >> 6, u = (id >> 1) & 31;
    const int dq = rank * 2 + (u & 1), tr = u >> 1;
    const int a = lane & 3, d0 = 16 * w + (lane >> 2);
    float2* s_red = (float2*)(smem_raw + OFF_WRAW);
    const uint32_t oad = wg * 8192 + ((lane >> 4) * 8 + (lane & 7)) * 128 + (((2 * w + ((lane >> 3) & 1)) ^ (lane & 7)) << 4);
#pragma unroll 1
    for (int hf = 0; hf < 2; hf++) {
      const uint32_t base = sb + (hf ? 0 : OFF_XR), last = hf ? 0 : OFF_H0B - 65536 - OFF_XR;
      float acc[5][28];
      float q1[4] = {0.f, 0.f, 0.f, 0.f}, q2[4] = {0.f, 0.f, 0.f, 0.f};
      if (hf == 0) { mbar_wait(bar + B_H0, 0); mbar_wait(bar + B_H0C, 0); }
      const float* se = (const float*)(smem_raw + OFF_E + hf * 2560) + wg * 64 + d0;
#pragma unroll
      for (int k2 = 0; k2 < 4; k2++) {
        if (k2 < 3) {
          if (hf) mbar_wait(bar + B_H1 + 8 * k2, 0);
          else if (k2 == 2) mbar_wait(bar + B_H0 + 8, 0);
          const uint64_t da = mk_desc(base + (4 * k2 + wg) * 8192 + (k2 == 2 ? last : 0)), db = mk_desc(sb + OFF_F);
          wg_fence();
#pragma unroll
          for (int kk = 0; kk < 4; kk++) {
            wgmma_inv<1>(acc[2 * k2], da + 128 * kk, db + 2 * kk, kk);
            if (k2 < 2) wgmma_inv<1>(acc[2 * k2 + 1], da + 1024 + 128 * kk, db + 2 * kk, kk);
          }
          wg_commit();
        }
        if (k2 > 0) {
          if (k2 < 3) wg_wait<1>(); else wg_wait<0>();
#pragma unroll
          for (int k = 2 * k2 - 2; k < 2 * k2 && k < 5; k++) {
            fence_regs(acc[k]);
            if (a == 0) {
              acc[k][25] += se[k * 128];
              acc[k][27] += se[k * 128 + 8];
            }
            if (k == 4 && tr == 15 && wg == 1) {
#pragma unroll
              for (int i = 16; i < 28; i++)
                if (8 * (i >> 2) + (i & 1) + 2 * a >= LOUT - (NT - 1) * MT) acc[k][i] = 0.f;
            }
#pragma unroll
            for (int i = 0; i < 28; i++) {
              q1[i & 3] += acc[k][i];
              q2[i & 3] = fmaf(acc[k][i], acc[k][i], q2[i & 3]);
            }
            fence_regs(q1);
            fence_regs(q2);
          }
        }
      }
      float s1[2] = {q1[0] + q1[1], q1[2] + q1[3]}, s2[2] = {q2[0] + q2[1], q2[2] + q2[3]};
#pragma unroll
      for (int i = 0; i < 2; i++) {
#pragma unroll
        for (int o = 1; o < 4; o <<= 1) {
          s1[i] += __shfl_xor_sync(0xffffffffu, s1[i], o);
          s2[i] += __shfl_xor_sync(0xffffffffu, s2[i], o);
        }
      }
      if (a == 0) {
        s_red[wg * 64 + d0] = make_float2(s1[0], s2[0]);
        s_red[wg * 64 + d0 + 8] = make_float2(s1[1], s2[1]);
      }
      asm volatile("bar.sync 3, 256;" ::: "memory");
      if (tid == 0) PROF_T(6 + 3 * hf);
      unsigned long long* part = g_part + ((hf * 2 + b) * 4 + dq) * 1024;
      if (tid < 64) {
        const float2 p0 = s_red[tid], p1 = s_red[64 + tid];
        const float x1 = p0.x + p1.x, x2 = p0.y + p1.y;
        const unsigned long long v = ((unsigned long long)(__float_as_uint(x2) & 0x7fffffffu) << 32) | __float_as_uint(x1);
        asm volatile("st.relaxed.gpu.global.u64 [%0], %1;" ::"l"(part + tr * 64 + tid), "l"(v) : "memory");
      }
      {
        const unsigned long long* q = part + (tid >> 6) * 256 + (tid & 63);
        unsigned long long v[4];
        poll64x4(q, v);
        float x1 = 0.f, x2 = 0.f;
#pragma unroll
        for (int i = 0; i < 4; i++) {
          x1 += __uint_as_float((uint32_t)v[i]);
          x2 += __uint_as_float((uint32_t)(v[i] >> 32));
        }
        s_red[128 + tid] = make_float2(x1, x2);
      }
      asm volatile("bar.sync 3, 256;" ::: "memory");
      if (tid == 0) PROF_T(7 + 3 * hf);
#pragma unroll
      for (int i = 0; i < 2; i++) {
        const float2 q0 = s_red[128 + d0 + 8 * i], q1 = s_red[192 + d0 + 8 * i], q2 = s_red[256 + d0 + 8 * i], q3 = s_red[320 + d0 + 8 * i];
        const float mu = ((q0.x + q1.x) + (q2.x + q3.x)) * (1.f / LOUT);
        const float var = fmaxf(((q0.y + q1.y) + (q2.y + q3.y)) * (1.f / LOUT) - mu * mu, 0.f);
        const __nv_bfloat16* gb = (const __nv_bfloat16*)(smem_raw + OFF_GB + hf * 256) + d0 + 8 * i;
        s1[i] = 0.5f * __bfloat162float(gb[0]) * rsqrtf(var + 1e-5f);
        s2[i] = 0.5f * __bfloat162float(gb[64]) - mu * s1[i];
      }
#pragma unroll
      for (int k = 0; k < 5; k++) {
        float hz[28];
#pragma unroll
        for (int i = 0; i < 28; i++) hz[i] = fmaf(acc[k][i], s1[(i >> 1) & 1], s2[(i >> 1) & 1]);
        gelu_store(hz, base + oad + k * 16384 + (k == 4 ? last : 0));
        float z;
        asm volatile("ld.volatile.shared.f32 %0, [%1];" : "=f"(z) : "r"(sb + OFF_F + 55 * 128) : "memory");
        s2[0] += z;
        s2[1] += z;
        __syncwarp();
        if (lane == 0) mbar_arrive(bar + B_OUT + 8 * (wg * 5 + k));
      }
      if (tid == 0) PROF_T(8 + 3 * hf);
    }
    asm volatile("barrier.cluster.wait.aligned;" ::: "memory");
  }
}

typedef CUresult (*EncFn)(CUtensorMap*, CUtensorMapDataType, cuuint32_t, void*, const cuuint64_t*, const cuuint64_t*, const cuuint32_t*,
                          const cuuint32_t*, CUtensorMapInterleave, CUtensorMapSwizzle, CUtensorMapL2promotion, CUtensorMapFloatOOBfill);

void encode(EncFn fn, CUtensorMap* m, int rank, void* base, const cuuint64_t* dims, const cuuint64_t* strides, const cuuint32_t* box,
            CUtensorMapL2promotion promo) {
  cuuint32_t es[5] = {1, 1, 1, 1, 1};
  fn(m, CU_TENSOR_MAP_DATA_TYPE_BFLOAT16, rank, base, dims, strides, box, es, CU_TENSOR_MAP_INTERLEAVE_NONE, CU_TENSOR_MAP_SWIZZLE_128B, promo,
     CU_TENSOR_MAP_FLOAT_OOB_FILL_NONE);
}

}

extern "C" void kernel_launch(void* const* d_in, const int* in_sizes, int n_in, void* d_out, int out_size) {
  (void)in_sizes; (void)n_in; (void)out_size;
  const __nv_bfloat16* x = (const __nv_bfloat16*)d_in[0];
  const __nv_bfloat16* w = (const __nv_bfloat16*)d_in[1];
  const __nv_bfloat16* gamma = (const __nv_bfloat16*)d_in[2];
  const __nv_bfloat16* beta = (const __nv_bfloat16*)d_in[3];
  void* fnp = nullptr;
  cudaDriverEntryPointQueryResult qr;
  cudaGetDriverEntryPoint("cuTensorMapEncodeTiled", &fnp, cudaEnableDefault, &qr);
  EncFn fn = (EncFn)fnp;
  void *cptr = nullptr, *fptr = nullptr, *xptr = nullptr, *wptr = nullptr, *yptr = nullptr;
  cudaGetSymbolAddress(&cptr, g_ctr);
  cudaGetSymbolAddress(&fptr, g_Fimg);
  cudaGetSymbolAddress(&xptr, g_X);
  cudaGetSymbolAddress(&wptr, g_W);
  cudaGetSymbolAddress(&yptr, g_Y);
  xptr = (void*)(((uintptr_t)xptr + (1u << 21) - 1) & ~(uintptr_t)((1u << 21) - 1));
  const CUtensorMapL2promotion P0 = CU_TENSOR_MAP_L2_PROMOTION_NONE, P128 = CU_TENSOR_MAP_L2_PROMOTION_L2_128B;
  Maps m;
  {
    cuuint64_t d[3] = {1024, 8000, 2}, s[2] = {2048, 8000ull * 2048};
    cuuint32_t bx[3] = {64, 64, 1};
    encode(fn, &m.x, 3, (void*)x, d, s, bx, P128);
  }
  for (int ph = 0; ph < 2; ph++) {
    cuuint64_t d[3] = {64, (cuuint64_t)(16 - ph), 4096}, s[2] = {2ull * 262144 * 2, 128};
    cuuint32_t bx[3] = {64, 16, 1};
    encode(fn, ph ? &m.wo : &m.we, 3, (void*)(w + (size_t)ph * 262144), d, s, bx, P128);
  }
  for (int par = 0; par < 2; par++) {
    cuuint64_t d[5] = {(cuuint64_t)XPAGES << 20, 2, 4, 2, 2}, s[4] = {par ? 0x1000u : 0x3000u, 1u << 14, 1u << 18, 1u << 20};
    cuuint32_t bx[5] = {64, 2, 4, 2, 2};
    encode(fn, &m.xst[par], 5, xptr, d, s, bx, P0);
  }
  {
    cuuint64_t d[4] = {64, 32, 2, (cuuint64_t)WR * WCHUNK / 128}, s[3] = {4ull * WBLK, 4096, 128};
    cuuint32_t bx[4] = {64, 32, 2, 1};
    encode(fn, &m.wst, 4, wptr, d, s, bx, P0);
  }
  for (int p = 0; p < 2; p++) {
    void* base = p ? wptr : yptr;
    cuuint64_t d[4] = {64, NT, 64, 8}, s[3] = {8192, 128, (cuuint64_t)NT * 8192};
    cuuint32_t bx[4] = {64, 32, 2, 1};
    encode(fn, &m.yst[p], 4, base, d, s, bx, P0);
    cuuint64_t d2[2] = {64, 8ull * NT * 64}, s2[1] = {128};
    cuuint32_t bx2[2] = {64, 128};
    encode(fn, &m.yld[p], 2, base, d2, s2, bx2, P128);
  }
  {
    cuuint64_t d[3] = {512, LOUT, 2}, s[2] = {1024, (cuuint64_t)LOUT * 1024};
    cuuint32_t bx[3] = {64, MT, 1};
    encode(fn, &m.out, 3, d_out, d, s, bx, P0);
  }
  for (int q = 0; q < 2; q++) {
    cuuint64_t d[3] = {512, (cuuint64_t)(NT - q), 2}, s[2] = {MT * 2048, 8000ull * 2048};
    cuuint32_t bx[3] = {64, NT, 1};
    encode(fn, &m.xe[q], 3, (void*)(x + q * 64 * 1024), d, s, bx, P128);
  }
  {
    cuuint64_t d[2] = {512, 512}, s[1] = {1024};
    cuuint32_t bx[2] = {64, 64};
    encode(fn, &m.w30, 2, (void*)(w + 30 * 262144), d, s, bx, P128);
  }
  cudaFuncSetAttribute(k1_main, cudaFuncAttributeMaxDynamicSharedMemorySize, SMEM_BYTES);
  k1_main<<<132, 512, SMEM_BYTES>>>((uint8_t*)xptr, fptr, (unsigned*)cptr, gamma, beta, m);
}
```

```cpp
#include <cuda_runtime.h>
#include <cuda_bf16.h>
#include <cuda.h>
#include <stdint.h>

namespace {

constexpr int LOUT = 7985;
constexpr int MT = 50;
constexpr int NT = 160;
constexpr int XBLK = NT * 128;
constexpr int WBLK = 16384;
constexpr int LW = 4;
constexpr int WR = 5;
constexpr int WCHUNK = 32 * 4 * WBLK;
constexpr int XPAGES = 20;
constexpr int NFL = 2;
constexpr int XKEEP = 9;
constexpr int YSTEP = 2;
constexpr int YFLUSH = 17 + LW + 3 * YSTEP;

__device__ __align__(1024) uint8_t g_X[(XPAGES + 2) << 21];
__device__ __align__(1024) uint8_t g_W[(size_t)WR * WCHUNK];
__device__ __align__(1024) uint8_t g_Y[8ull * NT * 8192];
__device__ __align__(128) float g_E[16 * NT * 64];
__device__ unsigned long long g_part[128 * 128];
constexpr int C_FLAG = 0, C_LOADED = 36, C_REG = 68, C_EXIT = 69, C_E = 70, C_NUM = 71;
__device__ __align__(128) unsigned g_ctr[C_NUM * 32];
#define PROF_T(i)
#define PROF_C(i)
#define PROF_V(i, v)
#define PROF_W(acc, stmt) stmt

__device__ __align__(128) const uint32_t g_Fimg[2048] = {
 0x3f803f80,0x3f7d3f7f,0x3f783f7b,0x3f713f75,0x3f673f6d,0x3f5c3f62,0x3f4e3f55,0x3f3e3f46,0x3f2c3f35,0x3f183f22,0x3f043f0e,0x3edb3ef1,0x3eac3ec4,0x3e793e95,0x3e163e48,0x3d493dc9,
 0xbd490000,0xbe16bdc9,0xbe79be48,0xbeacbe95,0xbedbbec4,0xbf04bef1,0xbf18bf0e,0xbf2cbf22,0xbf3ebf35,0xbf4ebf46,0xbf5cbf55,0xbf67bf62,0xbf71bf6d,0xbf78bf75,0xbf7dbf7b,0xbf80bf7f,
 0x3e793ec4,0xbd493dc9,0xbeacbe48,0xbf18bef1,0x3f7d3f80,0x3f673f75,0x3f3e3f55,0x3f043f22,0xbf5cbf6d,0xbf2cbf46,0xbedbbf0e,0xbe16be95,0xbf4ebf35,0xbf71bf62,0xbf80bf7b,0xbf78bf7f,
 0x3f783f6d,0x3f803f7f,0x3f713f7b,0x3f4e3f62,0x3e160000,0x3edb3e95,0x3f2c3f0e,0x3f5c3f46,0xbf04bec4,0xbf3ebf22,0xbf67bf55,0xbf7dbf75,0x3f183f35,0x3eac3ef1,0x3d493e48,0xbe79bdc9,
 0xbf04bf35,0xbd49be95,0x3edb3e48,0x3f4e3f22,0x3f7d3f6d,0x3f713f7f,0x3f2c3f55,0x3e793ef1,0x3f783f80,0x3f3e3f62,0x3eac3f0e,0xbe163dc9,0xbf18bec4,0xbf67bf46,0xbf80bf7b,0xbf5cbf75,
 0x3f5c3f35,0x3f803f75,0x3f673f7b,0x3f183f46,0x3e163ec4,0xbeacbdc9,0xbf3ebf0e,0xbf78bf62,0xbe790000,0xbf2cbef1,0xbf71bf55,0xbf7dbf7f,0xbf4ebf6d,0xbedbbf22,0x3d49be48,0x3f043e95,
 0xbf2cbec4,0xbf7dbf62,0xbf5cbf7b,0xbeacbf22,0x3f673f35,0x3f783f7f,0x3f183f55,0xbd493e95,0xbf80bf6d,0xbf4ebf75,0xbe79bf0e,0x3edb3dc9,0x3f713f80,0x3f043f46,0xbe163e48,0xbf3ebef1,
 0x3f3e3f6d,0x3e163ef1,0xbf04be48,0xbf71bf46,0xbedbbf35,0x3e79bdc9,0x3f4e3f0e,0x3f803f75,0x3d493ec4,0xbf18be95,0xbf78bf55,0xbf67bf7f,0x3eac0000,0x3f5c3f22,0x3f7d3f7b,0x3f2c3f62,
 0xbedb0000,0xbf78bf46,0xbf4ebf7b,0xbd49bef1,0x3f3e3ec4,0x3f7d3f75,0x3f043f55,0xbeac3dc9,0xbf71bf35,0xbf5cbf7f,0xbe16bf0e,0x3f2c3e95,0x3f803f6d,0x3f183f62,0xbe793e48,0xbf67bf22,
 0x3f673f80,0x3e793f22,0xbf18be48,0xbf80bf62,0xbf2cbf6d,0x3e16be95,0x3f5c3f0e,0x3f713f7f,0x3eac3f35,0xbf04bdc9,0xbf7dbf55,0xbf3ebf75,0x3d49bec4,0x3f4e3ef1,0x3f783f7b,0x3edb3f46,
 0xbf7dbf6d,0xbeacbf46,0x3f2c3e48,0x3f783f75,0x3f040000,0x3f803f62,0x3edb3f55,0xbf18bdc9,0x3f4e3ec4,0x3f673f7f,0x3d493f0e,0xbf5cbef1,0x3e793f35,0xbf3ebe95,0xbf71bf7b,0xbe16bf22,
 0x3e16bec4,0x3f713f22,0x3f3e3f7b,0xbe793e95,0x3f5c3f80,0xbd493ef1,0xbf67bf0e,0xbf4ebf7f,0x3f183f6d,0xbedb3dc9,0xbf80bf55,0xbf04bf62,0xbf78bf35,0xbf2cbf75,0x3eacbe48,0x3f7d3f46,
 0x3f7d3f35,0x3edb3f62,0xbf3ebe48,0xbf5cbf7f,0x3e79bec4,0x3f803f46,0x3eac3f55,0xbf4ebe95,0xbf180000,0xbf71bf75,0x3d49bf0e,0x3f783f22,0x3f043f6d,0xbf2cbdc9,0xbf67bf7b,0x3e16bef1,
 0xbe16bf35,0x3f673ef1,0x3f2c3f7b,0xbf043dc9,0xbf78bf6d,0xbd49bf22,0x3f713f0e,0x3f183f75,0x3f4e3f80,0xbeac3e95,0xbf80bf55,0xbe79bf46,0x3f5c3ec4,0x3f3e3f7f,0xbedb3e48,0xbf7dbf62,
 0xbedbbf6d,0x3f5c3e95,0x3f183f7b,0xbf3ebdc9,0xbd49bf35,0x3f7d3f22,0x3e793f55,0xbf71bef1,0x3eacbec4,0x3f783f62,0xbe163f0e,0xbf80bf46,0x3f2c0000,0x3f4e3f7f,0xbf043e48,0xbf67bf75,
 0x3f673ec4,0x3f043f75,0xbf4ebe48,0xbf2cbf7f,0x3f803f35,0x3e163f46,0xbf78bf0e,0xbeacbf62,0x3f713f6d,0xbe793ef1,0xbf7dbf55,0x3d49bf22,0x3f3e3f80,0xbf183dc9,0xbf5cbf7b,0x3edbbe95,
 0xbd490000,0xbe16bdc9,0xbe79be48,0xbeacbe95,0xbedbbec4,0xbf04bef1,0xbf18bf0e,0xbf2cbf22,0xbf3ebf35,0xbf4ebf46,0xbf5cbf55,0xbf67bf62,0xbf71bf6d,0xbf78bf75,0xbf7dbf7b,0xbf80bf7f,
 0xbf80bf80,0xbf7dbf7f,0xbf78bf7b,0xbf71bf75,0xbf67bf6d,0xbf5cbf62,0xbf4ebf55,0xbf3ebf46,0xbf2cbf35,0xbf18bf22,0xbf04bf0e,0xbedbbef1,0xbeacbec4,0xbe79be95,0xbe16be48,0xbd49bdc9,
 0xbf78bf6d,0xbf80bf7f,0xbf71bf7b,0xbf4ebf62,0xbe160000,0xbedbbe95,0xbf2cbf0e,0xbf5cbf46,0x3f043ec4,0x3f3e3f22,0x3f673f55,0x3f7d3f75,0xbf18bf35,0xbeacbef1,0xbd49be48,0x3e793dc9,
 0x3e793ec4,0xbd493dc9,0xbeacbe48,0xbf18bef1,0x3f7d3f80,0x3f673f75,0x3f3e3f55,0x3f043f22,0xbf5cbf6d,0xbf2cbf46,0xbedbbf0e,0xbe16be95,0xbf4ebf35,0xbf71bf62,0xbf80bf7b,0xbf78bf7f,
 0x3f5c3f35,0x3f803f75,0x3f673f7b,0x3f183f46,0x3e163ec4,0xbeacbdc9,0xbf3ebf0e,0xbf78bf62,0xbe790000,0xbf2cbef1,0xbf71bf55,0xbf7dbf7f,0xbf4ebf6d,0xbedbbf22,0x3d49be48,0x3f043e95,
 0x3f043f35,0x3d493e95,0xbedbbe48,0xbf4ebf22,0xbf7dbf6d,0xbf71bf7f,0xbf2cbf55,0xbe79bef1,0xbf78bf80,0xbf3ebf62,0xbeacbf0e,0x3e16bdc9,0x3f183ec4,0x3f673f46,0x3f803f7b,0x3f5c3f75,
 0xbf3ebf6d,0xbe16bef1,0x3f043e48,0x3f713f46,0x3edb3f35,0xbe793dc9,0xbf4ebf0e,0xbf80bf75,0xbd49bec4,0x3f183e95,0x3f783f55,0x3f673f7f,0xbeac0000,0xbf5cbf22,0xbf7dbf7b,0xbf2cbf62,
 0xbf2cbec4,0xbf7dbf62,0xbf5cbf7b,0xbeacbf22,0x3f673f35,0x3f783f7f,0x3f183f55,0xbd493e95,0xbf80bf6d,0xbf4ebf75,0xbe79bf0e,0x3edb3dc9,0x3f713f80,0x3f043f46,0xbe163e48,0xbf3ebef1,
 0xbf67bf80,0xbe79bf22,0x3f183e48,0x3f803f62,0x3f2c3f6d,0xbe163e95,0xbf5cbf0e,0xbf71bf7f,0xbeacbf35,0x3f043dc9,0x3f7d3f55,0x3f3e3f75,0xbd493ec4,0xbf4ebef1,0xbf78bf7b,0xbedbbf46,
 0xbedb0000,0xbf78bf46,0xbf4ebf7b,0xbd49bef1,0x3f3e3ec4,0x3f7d3f75,0x3f043f55,0xbeac3dc9,0xbf71bf35,0xbf5cbf7f,0xbe16bf0e,0x3f2c3e95,0x3f803f6d,0x3f183f62,0xbe793e48,0xbf67bf22,
 0x3e16bec4,0x3f713f22,0x3f3e3f7b,0xbe793e95,0x3f5c3f80,0xbd493ef1,0xbf67bf0e,0xbf4ebf7f,0x3f183f6d,0xbedb3dc9,0xbf80bf55,0xbf04bf62,0xbf78bf35,0xbf2cbf75,0x3eacbe48,0x3f7d3f46,
 0x3f7d3f6d,0x3eac3f46,0xbf2cbe48,0xbf78bf75,0xbf040000,0xbf80bf62,0xbedbbf55,0x3f183dc9,0xbf4ebec4,0xbf67bf7f,0xbd49bf0e,0x3f5c3ef1,0xbe79bf35,0x3f3e3e95,0x3f713f7b,0x3e163f22,
 0x3e163f35,0xbf67bef1,0xbf2cbf7b,0x3f04bdc9,0x3f783f6d,0x3d493f22,0xbf71bf0e,0xbf18bf75,0xbf4ebf80,0x3eacbe95,0x3f803f55,0x3e793f46,0xbf5cbec4,0xbf3ebf7f,0x3edbbe48,0x3f7d3f62,
 0x3f7d3f35,0x3edb3f62,0xbf3ebe48,0xbf5cbf7f,0x3e79bec4,0x3f803f46,0x3eac3f55,0xbf4ebe95,0xbf180000,0xbf71bf75,0x3d49bf0e,0x3f783f22,0x3f043f6d,0xbf2cbdc9,0xbf67bf7b,0x3e16bef1,
 0x3f673ec4,0x3f043f75,0xbf4ebe48,0xbf2cbf7f,0x3f803f35,0x3e163f46,0xbf78bf0e,0xbeacbf62,0x3f713f6d,0xbe793ef1,0xbf7dbf55,0x3d49bf22,0x3f3e3f80,0xbf183dc9,0xbf5cbf7b,0x3edbbe95,
 0x3edb3f6d,0xbf5cbe95,0xbf18bf7b,0x3f3e3dc9,0x3d493f35,0xbf7dbf22,0xbe79bf55,0x3f713ef1,0xbeac3ec4,0xbf78bf62,0x3e16bf0e,0x3f803f46,0xbf2c0000,0xbf4ebf7f,0x3f04be48,0x3f673f75,
 0x3f2c3f80,0xbf4ebdc9,0xbf04bf7b,0x3f673e95,0x3eac3f6d,0xbf78bef1,0xbe16bf55,0x3f803f22,0xbd493f35,0xbf7dbf46,0x3e79bf0e,0x3f713f62,0xbedb3ec4,0xbf5cbf75,0x3f18be48,0x3f3e3f7f,
 0xbf3e0000,0xbf18bf7f,0x3f5c3e48,0x3edb3f75,0xbf71bec4,0xbe79bf62,0x3f7d3f0e,0x3d493f46,0xbf80bf35,0x3e16bf22,0x3f783f55,0xbeac3ef1,0xbf67bf6d,0x3f04be95,0x3f4e3f7b,0xbf2c3dc9,
 0xbf043ec4,0xbf2cbf7f,0x3f673e48,0x3e163f62,0x3f183f80,0xbf71be95,0xbd49bf55,0x3f783f46,0xbe79bf6d,0x3f803f22,0xbeac3f0e,0xbf4ebf75,0xbf7dbf35,0x3edbbef1,0x3f3e3f7b,0xbf5cbdc9,
 0x3f5c3f6d,0xbf3e3dc9,0xbedbbf7b,0x3f7d3ef1,0x3f4e0000,0x3eac3f75,0xbf80bf0e,0x3e79bf22,0xbf78bec4,0x3d49bf46,0x3f713f55,0xbf183e95,0xbe163f35,0xbf67bf62,0x3f2cbe48,0x3f043f7f,
 0x3e79bf35,0x3f3e3f75,0xbf71be48,0x3e16bf46,0x3f4e3f6d,0xbf67bdc9,0x3d49bf55,0x3f5c3f62,0x3f043f80,0xbf80bef1,0x3edbbf0e,0x3f183f7f,0xbf7dbec4,0x3eacbf22,0x3f2c3f7b,0xbf78be95,
 0x3f783f35,0xbf2c3e95,0xbeacbf7b,0x3f7d3f22,0xbf183ec4,0xbedbbf7f,0x3f803f0e,0xbf043ef1,0xbf5c0000,0xbd49bf62,0x3f673f55,0xbf4e3dc9,0xbe16bf6d,0x3f713f46,0xbf3e3e48,0xbe79bf75,
 0xbf80bec4,0x3f18bef1,0x3e793f7b,0xbf67bf46,0x3f713f35,0xbf5c3dc9,0x3e16bf55,0x3f2c3f75,0xbf3ebf6d,0x3f7d3e95,0xbf043f0e,0xbeacbf7f,0x3edb3f80,0xbf78bf22,0x3f4ebe48,0xbd493f62,
 0x3d493f6d,0xbf4ebf62,0x3f783e48,0xbedb3f22,0x3eacbf35,0x3f043f7f,0xbf7dbf0e,0x3f3ebe95,0xbf2c3ec4,0xbe16bf75,0x3f5c3f55,0xbf71bdc9,0x3f670000,0xbe793f46,0xbf18bf7b,0x3f803ef1,
 0xbf710000,0x3f04bf22,0x3e163f7b,0xbf3ebf62,0x3f803ec4,0xbf4e3e95,0x3e79bf55,0x3edb3f7f,0xbf67bf35,0x3f783dc9,0xbf183f0e,0xbd49bf75,0x3f2c3f6d,0xbf7dbef1,0x3f5cbe48,0xbeac3f46,
 0x3eac3f80,0xbf5cbf46,0x3f7d3e48,0xbf2c3ef1,0x3d49bf6d,0x3f183f75,0xbf78bf0e,0x3f67bdc9,0xbedb3f35,0xbe79bf7f,0x3f4e3f55,0xbf80be95,0x3f3ebec4,0xbe163f62,0xbf04bf7b,0x3f713f22,
 0xbf18bf6d,0x3f673f22,0xbf80be48,0x3f5cbe95,0x3f780000,0xbf3e3ef1,0x3eacbf55,0x3e163f7f,0x3f7d3ec4,0xbf713dc9,0x3f2cbf0e,0xbe793f62,0xbf043f35,0x3d49bf75,0x3edb3f7b,0xbf4ebf46,
 0x3f4ebec4,0xbedb3f46,0xbd49bf7b,0x3f043f75,0x3e793f80,0xbf2cbf62,0x3f713f0e,0xbf7dbdc9,0xbe163f6d,0xbeacbf7f,0x3f3e3f55,0xbf78bef1,0xbf5cbf35,0x3f803e95,0xbf673e48,0x3f18bf22,
 0x3f4e3f35,0xbf71bef1,0x3f803e48,0xbf783dc9,0x3f5cbec4,0xbf2c3f22,0x3edbbf55,0xbe163f75,0xbf7d0000,0x3f67be95,0xbf3e3f0e,0x3f04bf46,0xbe793f6d,0xbd49bf7f,0x3eac3f7b,0xbf18bf62,
 0x3f18bf35,0xbeac3f62,0x3d49bf7b,0x3e793f7f,0xbf04bf6d,0x3f3e3f46,0xbf67bf0e,0x3f7d3e95,0x3e163f80,0xbedbbf75,0x3f2c3f55,0xbf5cbf22,0x3f783ec4,0xbf80bdc9,0x3f71be48,0xbf4e3ef1,
 0x3eacbf6d,0xbe793f75,0x3e16bf7b,0xbd493f7f,0x3f2cbf35,0xbf183f46,0x3f04bf55,0xbedb3f62,0x3f67bec4,0xbf5c3ef1,0x3f4ebf0e,0xbf3e3f22,0x3f800000,0xbf7d3dc9,0x3f78be48,0xbf713e95,
 0x3f713ec4,0xbf78be95,0x3f7d3e48,0xbf80bdc9,0x3f3e3f35,0xbf4ebf22,0x3f5c3f0e,0xbf67bef1,0x3edb3f6d,0xbf04bf62,0x3f183f55,0xbf2cbf46,0x3d493f80,0xbe16bf7f,0x3e793f7b,0xbeacbf75,
 0xbf3e0000,0xbf18bf7f,0x3f5c3e48,0x3edb3f75,0xbf71bec4,0xbe79bf62,0x3f7d3f0e,0x3d493f46,0xbf80bf35,0x3e16bf22,0x3f783f55,0xbeac3ef1,0xbf67bf6d,0x3f04be95,0x3f4e3f7b,0xbf2c3dc9,
 0xbf2cbf80,0x3f4e3dc9,0x3f043f7b,0xbf67be95,0xbeacbf6d,0x3f783ef1,0x3e163f55,0xbf80bf22,0x3d49bf35,0x3f7d3f46,0xbe793f0e,0xbf71bf62,0x3edbbec4,0x3f5c3f75,0xbf183e48,0xbf3ebf7f,
 0xbf5cbf6d,0x3f3ebdc9,0x3edb3f7b,0xbf7dbef1,0xbf4e0000,0xbeacbf75,0x3f803f0e,0xbe793f22,0x3f783ec4,0xbd493f46,0xbf71bf55,0x3f18be95,0x3e16bf35,0x3f673f62,0xbf2c3e48,0xbf04bf7f,
 0xbf043ec4,0xbf2cbf7f,0x3f673e48,0x3e163f62,0x3f183f80,0xbf71be95,0xbd49bf55,0x3f783f46,0xbe79bf6d,0x3f803f22,0xbeac3f0e,0xbf4ebf75,0xbf7dbf35,0x3edbbef1,0x3f3e3f7b,0xbf5cbdc9,
 0x3f783f35,0xbf2c3e95,0xbeacbf7b,0x3f7d3f22,0xbf183ec4,0xbedbbf7f,0x3f803f0e,0xbf043ef1,0xbf5c0000,0xbd49bf62,0x3f673f55,0xbf4e3dc9,0xbe16bf6d,0x3f713f46,0xbf3e3e48,0xbe79bf75,
 0xbe793f35,0xbf3ebf75,0x3f713e48,0xbe163f46,0xbf4ebf6d,0x3f673dc9,0xbd493f55,0xbf5cbf62,0xbf04bf80,0x3f803ef1,0xbedb3f0e,0xbf18bf7f,0x3f7d3ec4,0xbeac3f22,0xbf2cbf7b,0x3f783e95,
 0xbd49bf6d,0x3f4e3f62,0xbf78be48,0x3edbbf22,0xbeac3f35,0xbf04bf7f,0x3f7d3f0e,0xbf3e3e95,0x3f2cbec4,0x3e163f75,0xbf5cbf55,0x3f713dc9,0xbf670000,0x3e79bf46,0x3f183f7b,0xbf80bef1,
 0xbf80bec4,0x3f18bef1,0x3e793f7b,0xbf67bf46,0x3f713f35,0xbf5c3dc9,0x3e16bf55,0x3f2c3f75,0xbf3ebf6d,0x3f7d3e95,0xbf043f0e,0xbeacbf7f,0x3edb3f80,0xbf78bf22,0x3f4ebe48,0xbd493f62,
 0xbeacbf80,0x3f5c3f46,0xbf7dbe48,0x3f2cbef1,0xbd493f6d,0xbf18bf75,0x3f783f0e,0xbf673dc9,0x3edbbf35,0x3e793f7f,0xbf4ebf55,0x3f803e95,0xbf3e3ec4,0x3e16bf62,0x3f043f7b,0xbf71bf22,
 0xbf710000,0x3f04bf22,0x3e163f7b,0xbf3ebf62,0x3f803ec4,0xbf4e3e95,0x3e79bf55,0x3edb3f7f,0xbf67bf35,0x3f783dc9,0xbf183f0e,0xbd49bf75,0x3f2c3f6d,0xbf7dbef1,0x3f5cbe48,0xbeac3f46,
 0x3f4ebec4,0xbedb3f46,0xbd49bf7b,0x3f043f75,0x3e793f80,0xbf2cbf62,0x3f713f0e,0xbf7dbdc9,0xbe163f6d,0xbeacbf7f,0x3f3e3f55,0xbf78bef1,0xbf5cbf35,0x3f803e95,0xbf673e48,0x3f18bf22,
 0x3f183f6d,0xbf67bf22,0x3f803e48,0xbf5c3e95,0xbf780000,0x3f3ebef1,0xbeac3f55,0xbe16bf7f,0xbf7dbec4,0x3f71bdc9,0xbf2c3f0e,0x3e79bf62,0x3f04bf35,0xbd493f75,0xbedbbf7b,0x3f4e3f46,
 0xbf183f35,0x3eacbf62,0xbd493f7b,0xbe79bf7f,0x3f043f6d,0xbf3ebf46,0x3f673f0e,0xbf7dbe95,0xbe16bf80,0x3edb3f75,0xbf2cbf55,0x3f5c3f22,0xbf78bec4,0x3f803dc9,0xbf713e48,0x3f4ebef1,
 0x3f4e3f35,0xbf71bef1,0x3f803e48,0xbf783dc9,0x3f5cbec4,0xbf2c3f22,0x3edbbf55,0xbe163f75,0xbf7d0000,0x3f67be95,0xbf3e3f0e,0x3f04bf46,0xbe793f6d,0xbd49bf7f,0x3eac3f7b,0xbf18bf62,
 0x3f713ec4,0xbf78be95,0x3f7d3e48,0xbf80bdc9,0x3f3e3f35,0xbf4ebf22,0x3f5c3f0e,0xbf67bef1,0x3edb3f6d,0xbf04bf62,0x3f183f55,0xbf2cbf46,0x3d493f80,0xbe16bf7f,0x3e793f7b,0xbeacbf75,
 0xbeac3f6d,0x3e79bf75,0xbe163f7b,0x3d49bf7f,0xbf2c3f35,0x3f18bf46,0xbf043f55,0x3edbbf62,0xbf673ec4,0x3f5cbef1,0xbf4e3f0e,0x3f3ebf22,0xbf800000,0x3f7dbdc9,0xbf783e48,0x3f71be95,
 0xbd493f80,0x3e16bf7f,0xbe793f7b,0x3eacbf75,0xbedb3f6d,0x3f04bf62,0xbf183f55,0x3f2cbf46,0xbf3e3f35,0x3f4ebf22,0xbf5c3f0e,0x3f67bef1,0xbf713ec4,0x3f78be95,0xbf7d3e48,0x3f80bdc9,
 0xbf800000,0x3f7d3dc9,0xbf78be48,0x3f713e95,0xbf67bec4,0x3f5c3ef1,0xbf4ebf0e,0x3f3e3f22,0xbf2cbf35,0x3f183f46,0xbf04bf55,0x3edb3f62,0xbeacbf6d,0x3e793f75,0xbe16bf7b,0x3d493f7f,
 0xbf783ec4,0x3f80bdc9,0xbf71be48,0x3f4e3ef1,0xbe163f80,0x3edbbf75,0xbf2c3f55,0x3f5cbf22,0x3f04bf6d,0xbf3e3f46,0x3f67bf0e,0xbf7d3e95,0xbf18bf35,0x3eac3f62,0xbd49bf7b,0xbe793f7f,
 0x3e793f6d,0x3d49bf7f,0xbeac3f7b,0x3f18bf62,0x3f7d0000,0xbf67be95,0x3f3e3f0e,0xbf04bf46,0xbf5cbec4,0x3f2c3f22,0xbedbbf55,0x3e163f75,0xbf4e3f35,0x3f71bef1,0xbf803e48,0x3f783dc9,
 0x3f5cbf35,0xbf803e95,0x3f673e48,0xbf18bf22,0x3e163f6d,0x3eacbf7f,0xbf3e3f55,0x3f78bef1,0xbe793f80,0x3f2cbf62,0xbf713f0e,0x3f7dbdc9,0xbf4ebec4,0x3edb3f46,0x3d49bf7b,0xbf043f75,
 0x3f043f35,0xbd49bf75,0xbedb3f7b,0x3f4ebf46,0xbf7d3ec4,0x3f713dc9,0xbf2cbf0e,0x3e793f62,0xbf780000,0x3f3e3ef1,0xbeacbf55,0xbe163f7f,0x3f18bf6d,0xbf673f22,0x3f80be48,0xbf5cbe95,
 0xbf3ebec4,0x3e163f62,0x3f04bf7b,0xbf713f22,0x3edb3f35,0x3e79bf7f,0xbf4e3f55,0x3f80be95,0xbd49bf6d,0xbf183f75,0x3f78bf0e,0xbf67bdc9,0xbeac3f80,0x3f5cbf46,0xbf7d3e48,0x3f2c3ef1,
 0xbf2c3f6d,0x3f7dbef1,0xbf5cbe48,0x3eac3f46,0x3f67bf35,0xbf783dc9,0x3f183f0e,0x3d49bf75,0xbf803ec4,0x3f4e3e95,0xbe79bf55,0xbedb3f7f,0x3f710000,0xbf04bf22,0xbe163f7b,0x3f3ebf62,
 0xbf670000,0x3e793f46,0x3f18bf7b,0xbf803ef1,0x3f2c3ec4,0x3e16bf75,0xbf5c3f55,0x3f71bdc9,0xbeacbf35,0xbf043f7f,0x3f7dbf0e,0xbf3ebe95,0xbd493f6d,0x3f4ebf62,0xbf783e48,0x3edb3f22,
 0xbedb3f80,0x3f78bf22,0xbf4ebe48,0x3d493f62,0x3f3ebf6d,0xbf7d3e95,0x3f043f0e,0x3eacbf7f,0xbf713f35,0x3f5c3dc9,0xbe16bf55,0xbf2c3f75,0x3f80bec4,0xbf18bef1,0xbe793f7b,0x3f67bf46,
 0x3e16bf6d,0xbf713f46,0x3f3e3e48,0x3e79bf75,0x3f5c0000,0x3d49bf62,0xbf673f55,0x3f4e3dc9,0x3f183ec4,0x3edbbf7f,0xbf803f0e,0x3f043ef1,0xbf783f35,0x3f2c3e95,0x3eacbf7b,0xbf7d3f22,
 0x3f7dbec4,0xbeacbf22,0xbf2c3f7b,0x3f78be95,0xbf043f80,0x3f80bef1,0xbedbbf0e,0xbf183f7f,0xbf4e3f6d,0x3f67bdc9,0xbd49bf55,0xbf5c3f62,0xbe79bf35,0xbf3e3f75,0x3f71be48,0xbe16bf46,
 0x3e163f35,0x3f67bf62,0xbf2cbe48,0xbf043f7f,0x3f78bec4,0xbd49bf46,0xbf713f55,0x3f183e95,0xbf4e0000,0xbeac3f75,0x3f80bf0e,0xbe79bf22,0xbf5c3f6d,0x3f3e3dc9,0x3edbbf7b,0xbf7d3ef1,
 0x3f7dbf35,0xbedbbef1,0xbf3e3f7b,0x3f5cbdc9,0x3e79bf6d,0xbf803f22,0x3eac3f0e,0x3f4ebf75,0xbf183f80,0x3f71be95,0x3d49bf55,0xbf783f46,0x3f043ec4,0x3f2cbf7f,0xbf673e48,0xbe163f62,
 0x3f67bf6d,0xbf04be95,0xbf4e3f7b,0x3f2c3dc9,0x3f80bf35,0xbe16bf22,0xbf783f55,0x3eac3ef1,0x3f71bec4,0x3e79bf62,0xbf7d3f0e,0xbd493f46,0x3f3e0000,0x3f18bf7f,0xbf5c3e48,0xbedb3f75,
 0x3edb3ec4,0x3f5cbf75,0xbf18be48,0xbf3e3f7f,0x3d493f35,0x3f7dbf46,0xbe79bf0e,0xbf713f62,0xbeac3f6d,0x3f78bef1,0x3e16bf55,0xbf803f22,0xbf2c3f80,0x3f4ebdc9,0x3f04bf7b,0xbf673e95,
 0xbf800000,0x3f7d3dc9,0xbf78be48,0x3f713e95,0xbf67bec4,0x3f5c3ef1,0xbf4ebf0e,0x3f3e3f22,0xbf2cbf35,0x3f183f46,0xbf04bf55,0x3edb3f62,0xbeacbf6d,0x3e793f75,0xbe16bf7b,0x3d493f7f,
 0x3d49bf80,0xbe163f7f,0x3e79bf7b,0xbeac3f75,0x3edbbf6d,0xbf043f62,0x3f18bf55,0xbf2c3f46,0x3f3ebf35,0xbf4e3f22,0x3f5cbf0e,0xbf673ef1,0x3f71bec4,0xbf783e95,0x3f7dbe48,0xbf803dc9,
 0xbe79bf6d,0xbd493f7f,0x3eacbf7b,0xbf183f62,0xbf7d0000,0x3f673e95,0xbf3ebf0e,0x3f043f46,0x3f5c3ec4,0xbf2cbf22,0x3edb3f55,0xbe16bf75,0x3f4ebf35,0xbf713ef1,0x3f80be48,0xbf78bdc9,
 0xbf783ec4,0x3f80bdc9,0xbf71be48,0x3f4e3ef1,0xbe163f80,0x3edbbf75,0xbf2c3f55,0x3f5cbf22,0x3f04bf6d,0xbf3e3f46,0x3f67bf0e,0xbf7d3e95,0xbf18bf35,0x3eac3f62,0xbd49bf7b,0xbe793f7f,
 0x3f043f35,0xbd49bf75,0xbedb3f7b,0x3f4ebf46,0xbf7d3ec4,0x3f713dc9,0xbf2cbf0e,0x3e793f62,0xbf780000,0x3f3e3ef1,0xbeacbf55,0xbe163f7f,0x3f18bf6d,0xbf673f22,0x3f80be48,0xbf5cbe95,
 0xbf5c3f35,0x3f80be95,0xbf67be48,0x3f183f22,0xbe16bf6d,0xbeac3f7f,0x3f3ebf55,0xbf783ef1,0x3e79bf80,0xbf2c3f62,0x3f71bf0e,0xbf7d3dc9,0x3f4e3ec4,0xbedbbf46,0xbd493f7b,0x3f04bf75,
 0x3f2cbf6d,0xbf7d3ef1,0x3f5c3e48,0xbeacbf46,0xbf673f35,0x3f78bdc9,0xbf18bf0e,0xbd493f75,0x3f80bec4,0xbf4ebe95,0x3e793f55,0x3edbbf7f,0xbf710000,0x3f043f22,0x3e16bf7b,0xbf3e3f62,
 0xbf3ebec4,0x3e163f62,0x3f04bf7b,0xbf713f22,0x3edb3f35,0x3e79bf7f,0xbf4e3f55,0x3f80be95,0xbd49bf6d,0xbf183f75,0x3f78bf0e,0xbf67bdc9,0xbeac3f80,0x3f5cbf46,0xbf7d3e48,0x3f2c3ef1,
 0x3edbbf80,0xbf783f22,0x3f4e3e48,0xbd49bf62,0xbf3e3f6d,0x3f7dbe95,0xbf04bf0e,0xbeac3f7f,0x3f71bf35,0xbf5cbdc9,0x3e163f55,0x3f2cbf75,0xbf803ec4,0x3f183ef1,0x3e79bf7b,0xbf673f46,
 0xbf670000,0x3e793f46,0x3f18bf7b,0xbf803ef1,0x3f2c3ec4,0x3e16bf75,0xbf5c3f55,0x3f71bdc9,0xbeacbf35,0xbf043f7f,0x3f7dbf0e,0xbf3ebe95,0xbd493f6d,0x3f4ebf62,0xbf783e48,0x3edb3f22,
 0x3f7dbec4,0xbeacbf22,0xbf2c3f7b,0x3f78be95,0xbf043f80,0x3f80bef1,0xbedbbf0e,0xbf183f7f,0xbf4e3f6d,0x3f67bdc9,0xbd49bf55,0xbf5c3f62,0xbe79bf35,0xbf3e3f75,0x3f71be48,0xbe16bf46,
 0xbe163f6d,0x3f71bf46,0xbf3ebe48,0xbe793f75,0xbf5c0000,0xbd493f62,0x3f67bf55,0xbf4ebdc9,0xbf18bec4,0xbedb3f7f,0x3f80bf0e,0xbf04bef1,0x3f78bf35,0xbf2cbe95,0xbeac3f7b,0x3f7dbf22,
 0xbf7d3f35,0x3edb3ef1,0x3f3ebf7b,0xbf5c3dc9,0xbe793f6d,0x3f80bf22,0xbeacbf0e,0xbf4e3f75,0x3f18bf80,0xbf713e95,0xbd493f55,0x3f78bf46,0xbf04bec4,0xbf2c3f7f,0x3f67be48,0x3e16bf62,
 0x3e163f35,0x3f67bf62,0xbf2cbe48,0xbf043f7f,0x3f78bec4,0xbd49bf46,0xbf713f55,0x3f183e95,0xbf4e0000,0xbeac3f75,0x3f80bf0e,0xbe79bf22,0xbf5c3f6d,0x3f3e3dc9,0x3edbbf7b,0xbf7d3ef1,
 0x3edb3ec4,0x3f5cbf75,0xbf18be48,0xbf3e3f7f,0x3d493f35,0x3f7dbf46,0xbe79bf0e,0xbf713f62,0xbeac3f6d,0x3f78bef1,0x3e16bf55,0xbf803f22,0xbf2c3f80,0x3f4ebdc9,0x3f04bf7b,0xbf673e95,
 0xbf673f6d,0x3f043e95,0x3f4ebf7b,0xbf2cbdc9,0xbf803f35,0x3e163f22,0x3f78bf55,0xbeacbef1,0xbf713ec4,0xbe793f62,0x3f7dbf0e,0x3d49bf46,0xbf3e0000,0xbf183f7f,0x3f5cbe48,0x3edbbf75,
 0xbf3e3f80,0x3f183dc9,0x3f5cbf7b,0xbedbbe95,0xbf713f6d,0x3e793ef1,0x3f7dbf55,0xbd49bf22,0xbf803f35,0xbe163f46,0x3f78bf0e,0x3eacbf62,0xbf673ec4,0xbf043f75,0x3f4ebe48,0x3f2cbf7f,
 0xbf2c0000,0xbf4e3f7f,0x3f043e48,0x3f67bf75,0xbeacbec4,0xbf783f62,0x3e163f0e,0x3f80bf46,0x3d49bf35,0xbf7d3f22,0xbe793f55,0x3f71bef1,0x3edbbf6d,0xbf5c3e95,0xbf183f7b,0x3f3ebdc9,
 0xbf5c3ec4,0xbf3e3f7f,0x3edb3e48,0x3f7dbf62,0xbf4e3f80,0x3eac3e95,0x3f80bf55,0x3e79bf46,0x3f78bf6d,0x3d49bf22,0xbf713f0e,0xbf183f75,0x3e16bf35,0xbf673ef1,0xbf2c3f7b,0x3f043dc9,
 0xbf043f6d,0x3f2cbdc9,0x3f67bf7b,0xbe16bef1,0x3f180000,0x3f71bf75,0xbd49bf0e,0xbf783f22,0xbe79bec4,0xbf803f46,0xbeac3f55,0x3f4ebe95,0xbf7d3f35,0xbedb3f62,0x3f3ebe48,0x3f5cbf7f,
 0x3f78bf35,0x3f2cbf75,0xbeacbe48,0xbf7d3f46,0xbf183f6d,0x3edb3dc9,0x3f80bf55,0x3f04bf62,0xbf5c3f80,0x3d493ef1,0x3f67bf0e,0x3f4ebf7f,0xbe16bec4,0xbf713f22,0xbf3e3f7b,0x3e793e95,
 0xbe793f35,0x3f3ebe95,0x3f71bf7b,0x3e16bf22,0xbf4e3ec4,0xbf673f7f,0xbd493f0e,0x3f5cbef1,0xbf040000,0xbf803f62,0xbedb3f55,0x3f18bdc9,0x3f7dbf6d,0x3eacbf46,0xbf2c3e48,0xbf783f75,
 0xbd49bec4,0xbf4e3ef1,0xbf783f7b,0xbedb3f46,0xbeac3f35,0x3f04bdc9,0x3f7dbf55,0x3f3ebf75,0x3f2cbf6d,0xbe16be95,0xbf5c3f0e,0xbf713f7f,0xbf673f80,0xbe793f22,0x3f18be48,0x3f80bf62,
 0xbf803f6d,0xbf183f62,0x3e793e48,0x3f67bf22,0x3f71bf35,0x3f5cbf7f,0x3e16bf0e,0xbf2c3e95,0xbf3e3ec4,0xbf7d3f75,0xbf043f55,0x3eac3dc9,0x3edb0000,0x3f78bf46,0x3f4ebf7b,0x3d49bef1,
 0xbeac0000,0xbf5c3f22,0xbf7d3f7b,0xbf2c3f62,0xbd493ec4,0x3f18be95,0x3f78bf55,0x3f67bf7f,0x3edbbf35,0xbe79bdc9,0xbf4e3f0e,0xbf803f75,0xbf3e3f6d,0xbe163ef1,0x3f04be48,0x3f71bf46,
 0xbf713f80,0xbf043f46,0x3e163e48,0x3f3ebef1,0x3f80bf6d,0x3f4ebf75,0x3e79bf0e,0xbedb3dc9,0xbf673f35,0xbf783f7f,0xbf183f55,0x3d493e95,0x3f2cbec4,0x3f7dbf62,0x3f5cbf7b,0x3eacbf22,
 0x3f4ebf6d,0x3edbbf22,0xbd49be48,0xbf043e95,0x3e790000,0x3f2cbef1,0x3f71bf55,0x3f7dbf7f,0xbe163ec4,0x3eacbdc9,0x3f3ebf0e,0x3f78bf62,0xbf5c3f35,0xbf803f75,0xbf673f7b,0xbf183f46,
 0x3f18bec4,0x3f67bf46,0x3f80bf7b,0x3f5cbf75,0xbf783f80,0xbf3e3f62,0xbeac3f0e,0x3e163dc9,0xbf7d3f6d,0xbf713f7f,0xbf2c3f55,0xbe793ef1,0x3f04bf35,0x3d49be95,0xbedb3e48,0xbf4e3f22,
 0xbf183f35,0xbeac3ef1,0xbd493e48,0x3e79bdc9,0x3f04bec4,0x3f3ebf22,0x3f67bf55,0x3f7dbf75,0xbe160000,0xbedb3e95,0xbf2c3f0e,0xbf5c3f46,0xbf783f6d,0xbf803f7f,0xbf713f7b,0xbf4e3f62,
 0x3f4ebf35,0x3f71bf62,0x3f80bf7b,0x3f78bf7f,0x3f5cbf6d,0x3f2cbf46,0x3edbbf0e,0x3e16be95,0xbf7d3f80,0xbf673f75,0xbf3e3f55,0xbf043f22,0xbe793ec4,0x3d493dc9,0x3eacbe48,0x3f18bef1,
 0x3f71bf6d,0x3f78bf75,0x3f7dbf7b,0x3f80bf7f,0x3f3ebf35,0x3f4ebf46,0x3f5cbf55,0x3f67bf62,0x3edbbec4,0x3f04bef1,0x3f18bf0e,0x3f2cbf22,0x3d490000,0x3e16bdc9,0x3e79be48,0x3eacbe95,
 0xbeac3ec4,0xbe793e95,0xbe163e48,0xbd493dc9,0xbf2c3f35,0xbf183f22,0xbf043f0e,0xbedb3ef1,0xbf673f6d,0xbf5c3f62,0xbf4e3f55,0xbf3e3f46,0xbf803f80,0xbf7d3f7f,0xbf783f7b,0xbf713f75,
 0xbf2c0000,0xbf4e3f7f,0x3f043e48,0x3f67bf75,0xbeacbec4,0xbf783f62,0x3e163f0e,0x3f80bf46,0x3d49bf35,0xbf7d3f22,0xbe793f55,0x3f71bef1,0x3edbbf6d,0xbf5c3e95,0xbf183f7b,0x3f3ebdc9,
 0x3f3ebf80,0xbf18bdc9,0xbf5c3f7b,0x3edb3e95,0x3f71bf6d,0xbe79bef1,0xbf7d3f55,0x3d493f22,0x3f80bf35,0x3e16bf46,0xbf783f0e,0xbeac3f62,0x3f67bec4,0x3f04bf75,0xbf4e3e48,0xbf2c3f7f,
 0x3f04bf6d,0xbf2c3dc9,0xbf673f7b,0x3e163ef1,0xbf180000,0xbf713f75,0x3d493f0e,0x3f78bf22,0x3e793ec4,0x3f80bf46,0x3eacbf55,0xbf4e3e95,0x3f7dbf35,0x3edbbf62,0xbf3e3e48,0xbf5c3f7f,
 0xbf5c3ec4,0xbf3e3f7f,0x3edb3e48,0x3f7dbf62,0xbf4e3f80,0x3eac3e95,0x3f80bf55,0x3e79bf46,0x3f78bf6d,0x3d49bf22,0xbf713f0e,0xbf183f75,0x3e16bf35,0xbf673ef1,0xbf2c3f7b,0x3f043dc9,
 0xbe793f35,0x3f3ebe95,0x3f71bf7b,0x3e16bf22,0xbf4e3ec4,0xbf673f7f,0xbd493f0e,0x3f5cbef1,0xbf040000,0xbf803f62,0xbedb3f55,0x3f18bdc9,0x3f7dbf6d,0x3eacbf46,0xbf2c3e48,0xbf783f75,
 0xbf783f35,0xbf2c3f75,0x3eac3e48,0x3f7dbf46,0x3f18bf6d,0xbedbbdc9,0xbf803f55,0xbf043f62,0x3f5cbf80,0xbd49bef1,0xbf673f0e,0xbf4e3f7f,0x3e163ec4,0x3f71bf22,0x3f3ebf7b,0xbe79be95,
 0x3f80bf6d,0x3f18bf62,0xbe79be48,0xbf673f22,0xbf713f35,0xbf5c3f7f,0xbe163f0e,0x3f2cbe95,0x3f3ebec4,0x3f7dbf75,0x3f04bf55,0xbeacbdc9,0xbedb0000,0xbf783f46,0xbf4e3f7b,0xbd493ef1,
 0xbd49bec4,0xbf4e3ef1,0xbf783f7b,0xbedb3f46,0xbeac3f35,0x3f04bdc9,0x3f7dbf55,0x3f3ebf75,0x3f2cbf6d,0xbe16be95,0xbf5c3f0e,0xbf713f7f,0xbf673f80,0xbe793f22,0x3f18be48,0x3f80bf62,
 0x3f71bf80,0x3f04bf46,0xbe16be48,0xbf3e3ef1,0xbf803f6d,0xbf4e3f75,0xbe793f0e,0x3edbbdc9,0x3f67bf35,0x3f78bf7f,0x3f18bf55,0xbd49be95,0xbf2c3ec4,0xbf7d3f62,0xbf5c3f7b,0xbeac3f22,
 0xbeac0000,0xbf5c3f22,0xbf7d3f7b,0xbf2c3f62,0xbd493ec4,0x3f18be95,0x3f78bf55,0x3f67bf7f,0x3edbbf35,0xbe79bdc9,0xbf4e3f0e,0xbf803f75,0xbf3e3f6d,0xbe163ef1,0x3f04be48,0x3f71bf46,
 0x3f18bec4,0x3f67bf46,0x3f80bf7b,0x3f5cbf75,0xbf783f80,0xbf3e3f62,0xbeac3f0e,0x3e163dc9,0xbf7d3f6d,0xbf713f7f,0xbf2c3f55,0xbe793ef1,0x3f04bf35,0x3d49be95,0xbedb3e48,0xbf4e3f22,
 0xbf4e3f6d,0xbedb3f22,0x3d493e48,0x3f04be95,0xbe790000,0xbf2c3ef1,0xbf713f55,0xbf7d3f7f,0x3e16bec4,0xbeac3dc9,0xbf3e3f0e,0xbf783f62,0x3f5cbf35,0x3f80bf75,0x3f67bf7b,0x3f18bf46,
 0xbf4e3f35,0xbf713f62,0xbf803f7b,0xbf783f7f,0xbf5c3f6d,0xbf2c3f46,0xbedb3f0e,0xbe163e95,0x3f7dbf80,0x3f67bf75,0x3f3ebf55,0x3f04bf22,0x3e79bec4,0xbd49bdc9,0xbeac3e48,0xbf183ef1,
 0xbf183f35,0xbeac3ef1,0xbd493e48,0x3e79bdc9,0x3f04bec4,0x3f3ebf22,0x3f67bf55,0x3f7dbf75,0xbe160000,0xbedb3e95,0xbf2c3f0e,0xbf5c3f46,0xbf783f6d,0xbf803f7f,0xbf713f7b,0xbf4e3f62,
 0xbeac3ec4,0xbe793e95,0xbe163e48,0xbd493dc9,0xbf2c3f35,0xbf183f22,0xbf043f0e,0xbedb3ef1,0xbf673f6d,0xbf5c3f62,0xbf4e3f55,0xbf3e3f46,0xbf803f80,0xbf7d3f7f,0xbf783f7b,0xbf713f75,
 0xbf713f6d,0xbf783f75,0xbf7d3f7b,0xbf803f7f,0xbf3e3f35,0xbf4e3f46,0xbf5c3f55,0xbf673f62,0xbedb3ec4,0xbf043ef1,0xbf183f0e,0xbf2c3f22,0xbd490000,0xbe163dc9,0xbe793e48,0xbeac3e95,
};
__device__ __align__(128) const uint32_t g_Gimg[1792] = {
 0x00003d00,0x00003d00,0x00003d00,0x00003d00,0x00003d00,0x00003d00,0x00003d00,0x00003d00,0x00003d00,0x00003d00,0x00003d00,0x00003d00,0x00003d00,0x00003d00,0x00003d00,0x00003d00,
 0x00003d00,0x00003d00,0x00003d00,0x00003d00,0x00003d00,0x00003d00,0x00003d00,0x00003d00,0x00003d00,0x00003d00,0x00003d00,0x00003d00,0x00003d00,0x00003d00,0x00003d00,0x00003d00,
 0xbc5b3ce7,0xbc843cdc,0xbc983cce,0xbcac3cbe,0xbac93d00,0xbb963cfd,0xbbf93cf8,0xbc2c3cf1,0xbcf13c2c,0xbcf83bf9,0xbcfd3b96,0xbd003ac9,0xbcbe3cac,0xbcce3c98,0xbcdc3c84,0xbce73c5b,
 0xbce7bc5b,0xbcdcbc84,0xbccebc98,0xbcbebcac,0xbd00bac9,0xbcfdbb96,0xbcf8bbf9,0xbcf1bc2c,0xbc2cbcf1,0xbbf9bcf8,0xbb96bcfd,0xbac9bd00,0xbcacbcbe,0xbc98bcce,0xbc84bcdc,0xbc5bbce7,
 0xbcffbb49,0xbcf5bc15,0xbce2bc71,0xbcc6bca2,0xbca2bcc6,0xbc71bce2,0xbc15bcf5,0xbb49bcff,0xbb493cff,0xbc153cf5,0xbc713ce2,0xbca23cc6,0xbcc63ca2,0xbce23c71,0xbcf53c15,0xbcff3b49,
 0x3cff3b49,0x3cf53c15,0x3ce23c71,0x3cc63ca2,0x3ca23cc6,0x3c713ce2,0x3c153cf5,0x3b493cff,0x3b49bcff,0x3c15bcf5,0x3c71bce2,0x3ca2bcc6,0x3cc6bca2,0x3ce2bc71,0x3cf5bc15,0x3cffbb49,
 0x3c84bcdc,0x3cbebcac,0x3ce7bc5b,0x3cfdbb96,0xbc98bcce,0xbc2cbcf1,0xbac9bd00,0x3bf9bcf8,0xbcf83bf9,0xbd00bac9,0xbcf1bc2c,0xbccebc98,0xbb963cfd,0xbc5b3ce7,0xbcac3cbe,0xbcdc3c84,
 0xbcdcbc84,0xbcacbcbe,0xbc5bbce7,0xbb96bcfd,0xbcce3c98,0xbcf13c2c,0xbd003ac9,0xbcf8bbf9,0x3bf93cf8,0xbac93d00,0xbc2c3cf1,0xbc983cce,0x3cfd3b96,0x3ce73c5b,0x3cbe3cac,0x3c843cdc,
 0xbbc83cfb,0xbc8e3cd5,0xbcd53c8e,0xbcfb3bc8,0xbcfbbbc8,0xbcd5bc8e,0xbc8ebcd5,0xbbc8bcfb,0x3bc8bcfb,0x3c8ebcd5,0x3cd5bc8e,0x3cfbbbc8,0x3cfb3bc8,0x3cd53c8e,0x3c8e3cd5,0x3bc83cfb,
 0xbbc83cfb,0xbc8e3cd5,0xbcd53c8e,0xbcfb3bc8,0xbcfbbbc8,0xbcd5bc8e,0xbc8ebcd5,0xbbc8bcfb,0x3bc8bcfb,0x3c8ebcd5,0x3cd5bc8e,0x3cfbbbc8,0x3cfb3bc8,0x3cd53c8e,0x3c8e3cd5,0x3bc83cfb,
 0x3c98bcce,0x3ce7bc5b,0x3d003ac9,0x3cdc3c84,0xbcf8bbf9,0xbcbebcac,0xbc2cbcf1,0x3b96bcfd,0xbcfd3b96,0xbcf1bc2c,0xbcacbcbe,0xbbf9bcf8,0x3c843cdc,0x3ac93d00,0xbc5b3ce7,0xbcce3c98,
 0xbccebc98,0xbc5bbce7,0x3ac9bd00,0x3c84bcdc,0xbbf93cf8,0xbcac3cbe,0xbcf13c2c,0xbcfdbb96,0x3b963cfd,0xbc2c3cf1,0xbcbe3cac,0xbcf83bf9,0x3cdcbc84,0x3d00bac9,0x3ce73c5b,0x3c983cce,
 0xbcf5bc15,0xbca2bcc6,0xbb49bcff,0x3c71bce2,0x3ce2bc71,0x3cff3b49,0x3cc63ca2,0x3c153cf5,0x3c15bcf5,0x3cc6bca2,0x3cffbb49,0x3ce23c71,0x3c713ce2,0xbb493cff,0xbca23cc6,0xbcf53c15,
 0x3cf53c15,0x3ca23cc6,0x3b493cff,0xbc713ce2,0xbce23c71,0xbcffbb49,0xbcc6bca2,0xbc15bcf5,0xbc153cf5,0xbcc63ca2,0xbcff3b49,0xbce2bc71,0xbc71bce2,0x3b49bcff,0x3ca2bcc6,0x3cf5bc15,
 0xbcac3cbe,0xbcfd3b96,0xbcdcbc84,0xbc2cbcf1,0x3ce7bc5b,0x3cf83bf9,0x3c983cce,0xbac93d00,0xbd003ac9,0xbccebc98,0xbbf9bcf8,0x3c5bbce7,0x3cf13c2c,0x3c843cdc,0xbb963cfd,0xbcbe3cac,
 0xbcbebcac,0xbb96bcfd,0x3c84bcdc,0x3cf1bc2c,0x3c5b3ce7,0xbbf93cf8,0xbcce3c98,0xbd00bac9,0xbac9bd00,0x3c98bcce,0x3cf8bbf9,0x3ce73c5b,0xbc2c3cf1,0xbcdc3c84,0xbcfdbb96,0xbcacbcbe,
 0xbc443ced,0xbced3c44,0xbcedbc44,0xbc44bced,0x3c44bced,0x3cedbc44,0x3ced3c44,0x3c443ced,0xbc443ced,0xbced3c44,0xbcedbc44,0xbc44bced,0x3c44bced,0x3cedbc44,0x3ced3c44,0x3c443ced,
 0xbc443ced,0xbced3c44,0xbcedbc44,0xbc44bced,0x3c44bced,0x3cedbc44,0x3ced3c44,0x3c443ced,0xbc443ced,0xbced3c44,0xbcedbc44,0xbc44bced,0x3c44bced,0x3cedbc44,0x3ced3c44,0x3c443ced,
 0x3cbebcac,0x3cfd3b96,0x3c843cdc,0xbc2c3cf1,0xbc5b3ce7,0xbcf83bf9,0xbccebc98,0xbac9bd00,0x3d003ac9,0x3c983cce,0xbbf93cf8,0xbce73c5b,0xbcf13c2c,0xbcdcbc84,0xbb96bcfd,0x3cacbcbe,
 0x3cac3cbe,0xbb963cfd,0xbcdc3c84,0xbcf1bc2c,0xbce7bc5b,0xbbf9bcf8,0x3c98bcce,0x3d00bac9,0xbac93d00,0xbcce3c98,0xbcf8bbf9,0xbc5bbce7,0xbc2cbcf1,0x3c84bcdc,0x3cfdbb96,0x3cbe3cac,
 0xbce2bc71,0xbb49bcff,0x3cc6bca2,0x3cf53c15,0x3c153cf5,0xbca23cc6,0xbcffbb49,0xbc71bce2,0xbc713ce2,0xbcff3b49,0xbca2bcc6,0x3c15bcf5,0x3cf5bc15,0x3cc63ca2,0xbb493cff,0xbce23c71,
 0x3ce23c71,0x3b493cff,0xbcc63ca2,0xbcf5bc15,0xbc15bcf5,0x3ca2bcc6,0x3cff3b49,0x3c713ce2,0x3c71bce2,0x3cffbb49,0x3ca23cc6,0xbc153cf5,0xbcf53c15,0xbcc6bca2,0x3b49bcff,0x3ce2bc71,
 0xbcce3c98,0xbce7bc5b,0xbac9bd00,0x3cdcbc84,0xbbf9bcf8,0x3cbebcac,0x3cf13c2c,0x3b963cfd,0x3cfd3b96,0x3c2c3cf1,0xbcac3cbe,0xbcf8bbf9,0xbc843cdc,0xbd00bac9,0xbc5bbce7,0x3c98bcce,
 0x3c983cce,0xbc5b3ce7,0xbd003ac9,0xbc84bcdc,0xbcf83bf9,0xbcacbcbe,0x3c2cbcf1,0x3cfdbb96,0x3b96bcfd,0x3cf1bc2c,0x3cbe3cac,0xbbf93cf8,0x3cdc3c84,0xbac93d00,0xbce73c5b,0xbccebc98,
 0xbc8e3cd5,0xbcfbbbc8,0xbbc8bcfb,0x3cd5bc8e,0x3cd53c8e,0xbbc83cfb,0xbcfb3bc8,0xbc8ebcd5,0x3c8ebcd5,0x3cfb3bc8,0x3bc83cfb,0xbcd53c8e,0xbcd5bc8e,0x3bc8bcfb,0x3cfbbbc8,0x3c8e3cd5,
 0xbc8e3cd5,0xbcfbbbc8,0xbbc8bcfb,0x3cd5bc8e,0x3cd53c8e,0xbbc83cfb,0xbcfb3bc8,0xbc8ebcd5,0x3c8ebcd5,0x3cfb3bc8,0x3bc83cfb,0xbcd53c8e,0xbcd5bc8e,0x3bc8bcfb,0x3cfbbbc8,0x3c8e3cd5,
 0xbcdc3c84,0xbcbebcac,0x3c5bbce7,0x3cfd3b96,0xbccebc98,0x3c2cbcf1,0x3d003ac9,0x3bf93cf8,0x3cf83bf9,0x3ac93d00,0xbcf13c2c,0xbc98bcce,0x3b963cfd,0xbce73c5b,0xbcacbcbe,0x3c84bcdc,
 0x3c843cdc,0xbcac3cbe,0xbce7bc5b,0x3b96bcfd,0xbc983cce,0xbcf1bc2c,0x3ac9bd00,0x3cf8bbf9,0x3bf9bcf8,0x3d00bac9,0x3c2c3cf1,0xbcce3c98,0x3cfdbb96,0x3c5b3ce7,0xbcbe3cac,0xbcdcbc84,
 0xbcc6bca2,0x3c71bce2,0x3cf53c15,0xbb493cff,0xbcff3b49,0xbc15bcf5,0x3ce2bc71,0x3ca23cc6,0x3ca2bcc6,0x3ce23c71,0xbc153cf5,0xbcffbb49,0xbb49bcff,0x3cf5bc15,0x3c713ce2,0xbcc63ca2,
 0x3cc63ca2,0xbc713ce2,0xbcf5bc15,0x3b49bcff,0x3cffbb49,0x3c153cf5,0xbce23c71,0xbca2bcc6,0xbca23cc6,0xbce2bc71,0x3c15bcf5,0x3cff3b49,0x3b493cff,0xbcf53c15,0xbc71bce2,0x3cc6bca2,
 0x3ce7bc5b,0x3c843cdc,0xbcce3c98,0xbcacbcbe,0x3d00bac9,0x3b963cfd,0xbcf83bf9,0xbc2cbcf1,0x3cf13c2c,0xbbf93cf8,0xbcfdbb96,0x3ac9bd00,0x3cbe3cac,0xbc983cce,0xbcdcbc84,0x3c5bbce7,
 0x3c5b3ce7,0xbcdc3c84,0xbc98bcce,0x3cbebcac,0x3ac93d00,0xbcfd3b96,0xbbf9bcf8,0x3cf1bc2c,0xbc2c3cf1,0xbcf8bbf9,0x3b96bcfd,0x3d003ac9,0xbcac3cbe,0xbccebc98,0x3c84bcdc,0x3ce73c5b,
 0xbcb53cb5,0xbcb5bcb5,0x3cb5bcb5,0x3cb53cb5,0xbcb53cb5,0xbcb5bcb5,0x3cb5bcb5,0x3cb53cb5,0xbcb53cb5,0xbcb5bcb5,0x3cb5bcb5,0x3cb53cb5,0xbcb53cb5,0xbcb5bcb5,0x3cb5bcb5,0x3cb53cb5,
 0xbcb53cb5,0xbcb5bcb5,0x3cb5bcb5,0x3cb53cb5,0xbcb53cb5,0xbcb5bcb5,0x3cb5bcb5,0x3cb53cb5,0xbcb53cb5,0xbcb5bcb5,0x3cb5bcb5,0x3cb53cb5,0xbcb53cb5,0xbcb5bcb5,0x3cb5bcb5,0x3cb53cb5,
 0xbcf13c2c,0xbbf9bcf8,0x3cfdbb96,0x3ac93d00,0xbcbe3cac,0xbc98bcce,0x3cdcbc84,0x3c5b3ce7,0xbce7bc5b,0x3c84bcdc,0x3cce3c98,0xbcac3cbe,0xbd00bac9,0x3b96bcfd,0x3cf83bf9,0xbc2c3cf1,
 0xbc2cbcf1,0x3cf8bbf9,0x3b963cfd,0xbd003ac9,0xbcacbcbe,0x3ccebc98,0x3c843cdc,0xbce73c5b,0x3c5bbce7,0x3cdc3c84,0xbc983cce,0xbcbebcac,0x3ac9bd00,0x3cfd3b96,0xbbf93cf8,0xbcf1bc2c,
 0xbca2bcc6,0x3ce2bc71,0x3c153cf5,0xbcff3b49,0x3b49bcff,0x3cf53c15,0xbc713ce2,0xbcc6bca2,0xbcc63ca2,0xbc71bce2,0x3cf5bc15,0x3b493cff,0xbcffbb49,0x3c15bcf5,0x3ce23c71,0xbca23cc6,
 0x3ca23cc6,0xbce23c71,0xbc15bcf5,0x3cffbb49,0xbb493cff,0xbcf5bc15,0x3c71bce2,0x3cc63ca2,0x3cc6bca2,0x3c713ce2,0xbcf53c15,0xbb49bcff,0x3cff3b49,0xbc153cf5,0xbce2bc71,0x3ca2bcc6,
 0x3cf8bbf9,0xbac93d00,0xbcf1bc2c,0x3c98bcce,0x3b96bcfd,0x3ce73c5b,0xbcac3cbe,0xbc84bcdc,0xbcdcbc84,0x3cbebcac,0x3c5b3ce7,0xbcfd3b96,0xbcce3c98,0xbc2cbcf1,0x3d00bac9,0xbbf93cf8,
 0xbbf9bcf8,0x3d003ac9,0xbc2c3cf1,0xbccebc98,0xbcfdbb96,0x3c5bbce7,0x3cbe3cac,0xbcdc3c84,0xbc843cdc,0xbcacbcbe,0x3ce7bc5b,0x3b963cfd,0x3c983cce,0xbcf13c2c,0xbac9bd00,0x3cf83bf9,
 0xbcd53c8e,0xbbc8bcfb,0x3cfb3bc8,0xbc8e3cd5,0xbc8ebcd5,0x3cfbbbc8,0xbbc83cfb,0xbcd5bc8e,0x3cd5bc8e,0x3bc83cfb,0xbcfbbbc8,0x3c8ebcd5,0x3c8e3cd5,0xbcfb3bc8,0x3bc8bcfb,0x3cd53c8e,
 0xbcd53c8e,0xbbc8bcfb,0x3cfb3bc8,0xbc8e3cd5,0xbc8ebcd5,0x3cfbbbc8,0xbbc83cfb,0xbcd5bc8e,0x3cd5bc8e,0x3bc83cfb,0xbcfbbbc8,0x3c8ebcd5,0x3c8e3cd5,0xbcfb3bc8,0x3bc8bcfb,0x3cd53c8e,
 0x3cfdbb96,0xbc2c3cf1,0xbcacbcbe,0x3cf8bbf9,0xbc84bcdc,0x3d00bac9,0xbc5b3ce7,0xbc98bcce,0xbccebc98,0x3ce7bc5b,0xbac93d00,0xbcdcbc84,0xbbf93cf8,0xbcbebcac,0x3cf1bc2c,0xbb963cfd,
 0xbb96bcfd,0x3cf13c2c,0xbcbe3cac,0xbbf9bcf8,0xbcdc3c84,0xbac9bd00,0x3ce73c5b,0xbcce3c98,0xbc983cce,0xbc5bbce7,0x3d003ac9,0xbc843cdc,0x3cf83bf9,0xbcac3cbe,0xbc2cbcf1,0x3cfd3b96,
 0xbc71bce2,0x3cff3b49,0xbca23cc6,0xbc15bcf5,0x3cf53c15,0xbcc63ca2,0xbb49bcff,0x3ce23c71,0x3ce2bc71,0xbb493cff,0xbcc6bca2,0x3cf5bc15,0xbc153cf5,0xbca2bcc6,0x3cffbb49,0xbc713ce2,
 0x3c713ce2,0xbcffbb49,0x3ca2bcc6,0x3c153cf5,0xbcf5bc15,0x3cc6bca2,0x3b493cff,0xbce2bc71,0xbce23c71,0x3b49bcff,0x3cc63ca2,0xbcf53c15,0x3c15bcf5,0x3ca23cc6,0xbcff3b49,0x3c71bce2,
 0xbd003ac9,0x3c98bcce,0x3bf93cf8,0xbce7bc5b,0x3cf13c2c,0xbcdc3c84,0x3b96bcfd,0x3cac3cbe,0xbcbebcac,0x3cfdbb96,0xbc843cdc,0xbc2cbcf1,0x3c5b3ce7,0xbcf8bbf9,0x3ccebc98,0xbac93d00,
 0xbac9bd00,0x3cce3c98,0xbcf83bf9,0x3c5bbce7,0xbc2c3cf1,0xbc84bcdc,0x3cfd3b96,0xbcbe3cac,0x3cacbcbe,0x3b963cfd,0xbcdcbc84,0x3cf1bc2c,0xbce73c5b,0x3bf9bcf8,0x3c983cce,0xbd00bac9,
 0xbced3c44,0x3c44bced,0x3c443ced,0xbcedbc44,0x3cedbc44,0xbc443ced,0xbc44bced,0x3ced3c44,0xbced3c44,0x3c44bced,0x3c443ced,0xbcedbc44,0x3cedbc44,0xbc443ced,0xbc44bced,0x3ced3c44,
 0xbced3c44,0x3c44bced,0x3c443ced,0xbcedbc44,0x3cedbc44,0xbc443ced,0xbc44bced,0x3ced3c44,0xbced3c44,0x3c44bced,0x3c443ced,0xbcedbc44,0x3cedbc44,0xbc443ced,0xbc44bced,0x3ced3c44,
 0x3d003ac9,0xbcce3c98,0x3bf9bcf8,0x3c5b3ce7,0xbcf13c2c,0x3c84bcdc,0x3b963cfd,0xbcbebcac,0x3cac3cbe,0xbcfdbb96,0x3cdcbc84,0xbc2c3cf1,0xbce7bc5b,0x3cf8bbf9,0xbc983cce,0xbac9bd00,
 0xbac93d00,0xbc98bcce,0x3cf83bf9,0xbce73c5b,0xbc2cbcf1,0x3cdc3c84,0xbcfd3b96,0x3cacbcbe,0xbcbe3cac,0x3b96bcfd,0x3c843cdc,0xbcf1bc2c,0x3c5bbce7,0x3bf93cf8,0xbccebc98,0x3d00bac9,
 0xbc15bcf5,0x3cc63ca2,0xbcffbb49,0x3ce2bc71,0xbc713ce2,0xbb49bcff,0x3ca23cc6,0xbcf5bc15,0xbcf53c15,0x3ca2bcc6,0xbb493cff,0xbc71bce2,0x3ce23c71,0xbcff3b49,0x3cc6bca2,0xbc153cf5,
 0x3c153cf5,0xbcc6bca2,0x3cff3b49,0xbce23c71,0x3c71bce2,0x3b493cff,0xbca2bcc6,0x3cf53c15,0x3cf5bc15,0xbca23cc6,0x3b49bcff,0x3c713ce2,0xbce2bc71,0x3cffbb49,0xbcc63ca2,0x3c15bcf5,
 0xbcfdbb96,0x3cf1bc2c,0xbcac3cbe,0x3bf9bcf8,0x3c84bcdc,0xbac93d00,0xbc5bbce7,0x3cce3c98,0x3c983cce,0xbce7bc5b,0x3d00bac9,0xbcdc3c84,0xbcf83bf9,0x3cbebcac,0xbc2c3cf1,0xbb96bcfd,
 0xbb963cfd,0xbc2cbcf1,0x3cbe3cac,0xbcf8bbf9,0xbcdcbc84,0x3d003ac9,0xbce73c5b,0x3c98bcce,0x3ccebc98,0xbc5b3ce7,0xbac9bd00,0x3c843cdc,0x3bf93cf8,0xbcacbcbe,0x3cf13c2c,0xbcfd3b96,
 0xbcfb3bc8,0x3cd5bc8e,0xbc8e3cd5,0x3bc8bcfb,0x3bc83cfb,0xbc8ebcd5,0x3cd53c8e,0xbcfbbbc8,0x3cfbbbc8,0xbcd53c8e,0x3c8ebcd5,0xbbc83cfb,0xbbc8bcfb,0x3c8e3cd5,0xbcd5bc8e,0x3cfb3bc8,
 0xbcfb3bc8,0x3cd5bc8e,0xbc8e3cd5,0x3bc8bcfb,0x3bc83cfb,0xbc8ebcd5,0x3cd53c8e,0xbcfbbbc8,0x3cfbbbc8,0xbcd53c8e,0x3c8ebcd5,0xbbc83cfb,0xbbc8bcfb,0x3c8e3cd5,0xbcd5bc8e,0x3cfb3bc8,
 0xbcf8bbf9,0x3d00bac9,0xbcf13c2c,0x3ccebc98,0xbb96bcfd,0x3c5b3ce7,0xbcacbcbe,0x3cdc3c84,0x3c843cdc,0xbcbebcac,0x3ce73c5b,0xbcfdbb96,0xbc983cce,0x3c2cbcf1,0xbac93d00,0xbbf9bcf8,
 0xbbf93cf8,0xbac9bd00,0x3c2c3cf1,0xbc98bcce,0xbcfd3b96,0x3ce7bc5b,0xbcbe3cac,0x3c84bcdc,0x3cdcbc84,0xbcac3cbe,0x3c5bbce7,0xbb963cfd,0x3cce3c98,0xbcf1bc2c,0x3d003ac9,0xbcf83bf9,
 0xbb49bcff,0x3c153cf5,0xbc71bce2,0x3ca23cc6,0xbcc6bca2,0x3ce23c71,0xbcf5bc15,0x3cff3b49,0x3cffbb49,0xbcf53c15,0x3ce2bc71,0xbcc63ca2,0x3ca2bcc6,0xbc713ce2,0x3c15bcf5,0xbb493cff,
 0x3b493cff,0xbc15bcf5,0x3c713ce2,0xbca2bcc6,0x3cc63ca2,0xbce2bc71,0x3cf53c15,0xbcffbb49,0xbcff3b49,0x3cf5bc15,0xbce23c71,0x3cc6bca2,0xbca23cc6,0x3c71bce2,0xbc153cf5,0x3b49bcff,
 0x3cf13c2c,0xbcf8bbf9,0x3cfd3b96,0xbd00bac9,0x3cbe3cac,0xbccebc98,0x3cdc3c84,0xbce7bc5b,0x3c5b3ce7,0xbc84bcdc,0x3c983cce,0xbcacbcbe,0x3ac93d00,0xbb96bcfd,0x3bf93cf8,0xbc2cbcf1,
 0xbc2c3cf1,0x3bf9bcf8,0xbb963cfd,0x3ac9bd00,0xbcac3cbe,0x3c98bcce,0xbc843cdc,0x3c5bbce7,0xbce73c5b,0x3cdcbc84,0xbcce3c98,0x3cbebcac,0xbd003ac9,0x3cfdbb96,0xbcf83bf9,0x3cf1bc2c,
 0xbd000000,0x3d000000,0xbd000000,0x3d000000,0xbd000000,0x3d000000,0xbd000000,0x3d000000,0xbd000000,0x3d000000,0xbd000000,0x3d000000,0xbd000000,0x3d000000,0xbd000000,0x3d000000,
 0xbd000000,0x3d000000,0xbd000000,0x3d000000,0xbd000000,0x3d000000,0xbd000000,0x3d000000,0xbd000000,0x3d000000,0xbd000000,0x3d000000,0xbd000000,0x3d000000,0xbd000000,0x3d000000,
 0xbce7bc5b,0x3cdc3c84,0xbccebc98,0x3cbe3cac,0xbd00bac9,0x3cfd3b96,0xbcf8bbf9,0x3cf13c2c,0xbc2cbcf1,0x3bf93cf8,0xbb96bcfd,0x3ac93d00,0xbcacbcbe,0x3c983cce,0xbc84bcdc,0x3c5b3ce7,
 0x3c5bbce7,0xbc843cdc,0x3c98bcce,0xbcac3cbe,0x3ac9bd00,0xbb963cfd,0x3bf9bcf8,0xbc2c3cf1,0x3cf1bc2c,0xbcf83bf9,0x3cfdbb96,0xbd003ac9,0x3cbebcac,0xbcce3c98,0x3cdcbc84,0xbce73c5b,
 0x3b49bcff,0xbc153cf5,0x3c71bce2,0xbca23cc6,0x3cc6bca2,0xbce23c71,0x3cf5bc15,0xbcff3b49,0xbcffbb49,0x3cf53c15,0xbce2bc71,0x3cc63ca2,0xbca2bcc6,0x3c713ce2,0xbc15bcf5,0x3b493cff,
 0xbb493cff,0x3c15bcf5,0xbc713ce2,0x3ca2bcc6,0xbcc63ca2,0x3ce2bc71,0xbcf53c15,0x3cffbb49,0x3cff3b49,0xbcf5bc15,0x3ce23c71,0xbcc6bca2,0x3ca23cc6,0xbc71bce2,0x3c153cf5,0xbb49bcff,
 0x3cdc3c84,0xbcacbcbe,0x3c5b3ce7,0xbb96bcfd,0x3ccebc98,0xbcf13c2c,0x3d00bac9,0xbcf8bbf9,0xbbf9bcf8,0xbac93d00,0x3c2cbcf1,0xbc983cce,0xbcfdbb96,0x3ce73c5b,0xbcbebcac,0x3c843cdc,
 0x3c84bcdc,0xbcbe3cac,0x3ce7bc5b,0xbcfd3b96,0xbc98bcce,0x3c2c3cf1,0xbac9bd00,0xbbf93cf8,0xbcf83bf9,0x3d003ac9,0xbcf1bc2c,0x3cce3c98,0xbb963cfd,0x3c5bbce7,0xbcac3cbe,0x3cdcbc84,
 0xbcfbbbc8,0x3cd53c8e,0xbc8ebcd5,0x3bc83cfb,0x3bc8bcfb,0xbc8e3cd5,0x3cd5bc8e,0xbcfb3bc8,0x3cfb3bc8,0xbcd5bc8e,0x3c8e3cd5,0xbbc8bcfb,0xbbc83cfb,0x3c8ebcd5,0xbcd53c8e,0x3cfbbbc8,
 0xbcfbbbc8,0x3cd53c8e,0xbc8ebcd5,0x3bc83cfb,0x3bc8bcfb,0xbc8e3cd5,0x3cd5bc8e,0xbcfb3bc8,0x3cfb3bc8,0xbcd5bc8e,0x3c8e3cd5,0xbbc8bcfb,0xbbc83cfb,0x3c8ebcd5,0xbcd53c8e,0x3cfbbbc8,
 0x3cce3c98,0xbc5bbce7,0xbac93d00,0x3c84bcdc,0x3bf9bcf8,0xbcac3cbe,0x3cf1bc2c,0xbcfdbb96,0xbb96bcfd,0xbc2c3cf1,0x3cbebcac,0xbcf83bf9,0xbcdc3c84,0x3d00bac9,0xbce7bc5b,0x3c983cce,
 0x3c98bcce,0xbce73c5b,0x3d003ac9,0xbcdcbc84,0xbcf8bbf9,0x3cbe3cac,0xbc2cbcf1,0xbb963cfd,0xbcfd3b96,0x3cf13c2c,0xbcacbcbe,0x3bf93cf8,0x3c843cdc,0xbac9bd00,0xbc5b3ce7,0x3ccebc98,
 0x3c15bcf5,0xbcc63ca2,0x3cffbb49,0xbce2bc71,0x3c713ce2,0x3b49bcff,0xbca23cc6,0x3cf5bc15,0x3cf53c15,0xbca2bcc6,0x3b493cff,0x3c71bce2,0xbce23c71,0x3cff3b49,0xbcc6bca2,0x3c153cf5,
 0xbc153cf5,0x3cc6bca2,0xbcff3b49,0x3ce23c71,0xbc71bce2,0xbb493cff,0x3ca2bcc6,0xbcf53c15,0xbcf5bc15,0x3ca23cc6,0xbb49bcff,0xbc713ce2,0x3ce2bc71,0xbcffbb49,0x3cc63ca2,0xbc15bcf5,
 0xbcbebcac,0x3b963cfd,0x3c84bcdc,0xbcf13c2c,0x3c5b3ce7,0x3bf9bcf8,0xbcce3c98,0x3d003ac9,0xbac9bd00,0xbc983cce,0x3cf8bbf9,0xbce7bc5b,0xbc2c3cf1,0x3cdcbc84,0xbcfdbb96,0x3cac3cbe,
 0x3cacbcbe,0xbcfd3b96,0x3cdc3c84,0xbc2cbcf1,0xbce73c5b,0x3cf83bf9,0xbc98bcce,0xbac93d00,0x3d00bac9,0xbccebc98,0x3bf93cf8,0x3c5bbce7,0xbcf1bc2c,0x3c843cdc,0x3b96bcfd,0xbcbe3cac,
 0xbcedbc44,0x3c443ced,0x3c44bced,0xbced3c44,0x3ced3c44,0xbc44bced,0xbc443ced,0x3cedbc44,0xbcedbc44,0x3c443ced,0x3c44bced,0xbced3c44,0x3ced3c44,0xbc44bced,0xbc443ced,0x3cedbc44,
 0xbcedbc44,0x3c443ced,0x3c44bced,0xbced3c44,0x3ced3c44,0xbc44bced,0xbc443ced,0x3cedbc44,0xbcedbc44,0x3c443ced,0x3c44bced,0xbced3c44,0x3ced3c44,0xbc44bced,0xbc443ced,0x3cedbc44,
 0x3cac3cbe,0x3b96bcfd,0xbcdc3c84,0x3cf13c2c,0xbce7bc5b,0x3bf93cf8,0x3c98bcce,0xbd003ac9,0xbac93d00,0x3ccebc98,0xbcf8bbf9,0x3c5b3ce7,0xbc2cbcf1,0xbc843cdc,0x3cfdbb96,0xbcbebcac,
 0xbcbe3cac,0x3cfd3b96,0xbc84bcdc,0xbc2c3cf1,0x3c5bbce7,0xbcf83bf9,0x3cce3c98,0xbac9bd00,0xbd00bac9,0x3c983cce,0x3bf9bcf8,0xbce73c5b,0x3cf1bc2c,0xbcdcbc84,0x3b963cfd,0x3cacbcbe,
 0x3c71bce2,0xbcff3b49,0x3ca23cc6,0x3c15bcf5,0xbcf53c15,0x3cc63ca2,0x3b49bcff,0xbce23c71,0xbce2bc71,0x3b493cff,0x3cc6bca2,0xbcf5bc15,0x3c153cf5,0x3ca2bcc6,0xbcffbb49,0x3c713ce2,
 0xbc713ce2,0x3cffbb49,0xbca2bcc6,0xbc153cf5,0x3cf5bc15,0xbcc6bca2,0xbb493cff,0x3ce2bc71,0x3ce23c71,0xbb49bcff,0xbcc63ca2,0x3cf53c15,0xbc15bcf5,0xbca23cc6,0x3cff3b49,0xbc71bce2,
 0xbc98bcce,0xbc5b3ce7,0x3d00bac9,0xbc84bcdc,0x3cf8bbf9,0xbcacbcbe,0xbc2c3cf1,0x3cfdbb96,0xbb963cfd,0x3cf1bc2c,0xbcbebcac,0xbbf93cf8,0xbcdcbc84,0xbac93d00,0x3ce7bc5b,0xbccebc98,
 0xbcce3c98,0x3ce73c5b,0xbac9bd00,0xbcdc3c84,0xbbf9bcf8,0xbcbe3cac,0x3cf13c2c,0xbb96bcfd,0x3cfd3b96,0xbc2cbcf1,0xbcac3cbe,0x3cf83bf9,0xbc843cdc,0x3d003ac9,0xbc5bbce7,0xbc983cce,
 0xbcd5bc8e,0xbbc83cfb,0x3cfbbbc8,0xbc8ebcd5,0xbc8e3cd5,0x3cfb3bc8,0xbbc8bcfb,0xbcd53c8e,0x3cd53c8e,0x3bc8bcfb,0xbcfb3bc8,0x3c8e3cd5,0x3c8ebcd5,0xbcfbbbc8,0x3bc83cfb,0x3cd5bc8e,
 0xbcd5bc8e,0xbbc83cfb,0x3cfbbbc8,0xbc8ebcd5,0xbc8e3cd5,0x3cfb3bc8,0xbbc8bcfb,0xbcd53c8e,0x3cd53c8e,0x3bc8bcfb,0xbcfb3bc8,0x3c8e3cd5,0x3c8ebcd5,0xbcfbbbc8,0x3bc83cfb,0x3cd5bc8e,
 0xbc84bcdc,0xbcac3cbe,0x3ce73c5b,0x3b96bcfd,0x3c98bcce,0xbcf1bc2c,0xbac93d00,0x3cf8bbf9,0xbbf93cf8,0x3d00bac9,0xbc2cbcf1,0xbcce3c98,0xbcfd3b96,0x3c5b3ce7,0x3cbebcac,0xbcdcbc84,
 0xbcdc3c84,0x3cbe3cac,0x3c5bbce7,0xbcfdbb96,0xbccebc98,0xbc2c3cf1,0x3d003ac9,0xbbf9bcf8,0x3cf83bf9,0xbac9bd00,0xbcf13c2c,0x3c983cce,0x3b963cfd,0x3ce7bc5b,0xbcacbcbe,0xbc843cdc,
 0x3ca2bcc6,0xbce2bc71,0xbc153cf5,0x3cff3b49,0xbb49bcff,0xbcf53c15,0x3c713ce2,0x3cc6bca2,0x3cc63ca2,0x3c71bce2,0xbcf5bc15,0xbb493cff,0x3cffbb49,0xbc15bcf5,0xbce23c71,0x3ca23cc6,
 0xbca23cc6,0x3ce23c71,0x3c15bcf5,0xbcffbb49,0x3b493cff,0x3cf5bc15,0xbc71bce2,0xbcc63ca2,0xbcc6bca2,0xbc713ce2,0x3cf53c15,0x3b49bcff,0xbcff3b49,0x3c153cf5,0x3ce2bc71,0xbca2bcc6,
 0x3c5b3ce7,0x3cdcbc84,0xbc98bcce,0xbcbe3cac,0x3ac93d00,0x3cfdbb96,0xbbf9bcf8,0xbcf13c2c,0xbc2c3cf1,0x3cf83bf9,0x3b96bcfd,0xbd00bac9,0xbcac3cbe,0x3cce3c98,0x3c84bcdc,0xbce7bc5b,
 0xbce73c5b,0x3c843cdc,0x3ccebc98,0xbcacbcbe,0xbd003ac9,0x3b963cfd,0x3cf8bbf9,0xbc2cbcf1,0xbcf1bc2c,0xbbf93cf8,0x3cfd3b96,0x3ac9bd00,0xbcbebcac,0xbc983cce,0x3cdc3c84,0x3c5bbce7,
 0xbcb5bcb5,0xbcb53cb5,0x3cb53cb5,0x3cb5bcb5,0xbcb5bcb5,0xbcb53cb5,0x3cb53cb5,0x3cb5bcb5,0xbcb5bcb5,0xbcb53cb5,0x3cb53cb5,0x3cb5bcb5,0xbcb5bcb5,0xbcb53cb5,0x3cb53cb5,0x3cb5bcb5,
 0xbcb5bcb5,0xbcb53cb5,0x3cb53cb5,0x3cb5bcb5,0xbcb5bcb5,0xbcb53cb5,0x3cb53cb5,0x3cb5bcb5,0xbcb5bcb5,0xbcb53cb5,0x3cb53cb5,0x3cb5bcb5,0xbcb5bcb5,0xbcb53cb5,0x3cb53cb5,0x3cb5bcb5,
 0xbc2cbcf1,0xbcf83bf9,0x3b963cfd,0x3d00bac9,0xbcacbcbe,0xbcce3c98,0x3c843cdc,0x3ce7bc5b,0x3c5bbce7,0xbcdcbc84,0xbc983cce,0x3cbe3cac,0x3ac9bd00,0xbcfdbb96,0xbbf93cf8,0x3cf13c2c,
 0x3cf1bc2c,0xbbf9bcf8,0xbcfd3b96,0x3ac93d00,0x3cbebcac,0xbc98bcce,0xbcdc3c84,0x3c5b3ce7,0x3ce73c5b,0x3c84bcdc,0xbccebc98,0xbcac3cbe,0x3d003ac9,0x3b96bcfd,0xbcf8bbf9,0xbc2c3cf1,
 0x00000000,0x00000000,0x00000000,0x00000000,0x00000000,0x00000000,0x00000000,0x00000000,0x00000000,0x00000000,0x00000000,0x00000000,0x00000000,0x00000000,0x00000000,0x00000000,
 0x00000000,0x00000000,0x00000000,0x00000000,0x00000000,0x00000000,0x00000000,0x00000000,0x00000000,0x00000000,0x00000000,0x00000000,0x00000000,0x00000000,0x00000000,0x00000000,
 0x00000000,0x00000000,0x00000000,0x00000000,0x00000000,0x00000000,0x00000000,0x00000000,0x00000000,0x00000000,0x00000000,0x00000000,0x00000000,0x00000000,0x00000000,0x00000000,
 0x00000000,0x00000000,0x00000000,0x00000000,0x00000000,0x00000000,0x00000000,0x00000000,0x00000000,0x00000000,0x00000000,0x00000000,0x00000000,0x00000000,0x00000000,0x00000000,
 0x00000000,0x00000000,0x00000000,0x00000000,0x00000000,0x00000000,0x00000000,0x00000000,0x00000000,0x00000000,0x00000000,0x00000000,0x00000000,0x00000000,0x00000000,0x00000000,
 0x00000000,0x00000000,0x00000000,0x00000000,0x00000000,0x00000000,0x00000000,0x00000000,0x00000000,0x00000000,0x00000000,0x00000000,0x00000000,0x00000000,0x00000000,0x00000000,
 0x00000000,0x00000000,0x00000000,0x00000000,0x00000000,0x00000000,0x00000000,0x00000000,0x00000000,0x00000000,0x00000000,0x00000000,0x00000000,0x00000000,0x00000000,0x00000000,
 0x00000000,0x00000000,0x00000000,0x00000000,0x00000000,0x00000000,0x00000000,0x00000000,0x00000000,0x00000000,0x00000000,0x00000000,0x00000000,0x00000000,0x00000000,0x00000000,
 0x00000000,0x00000000,0x00000000,0x00000000,0x00000000,0x00000000,0x00000000,0x00000000,0x00000000,0x00000000,0x00000000,0x00000000,0x00000000,0x00000000,0x00000000,0x00000000,
 0x00000000,0x00000000,0x00000000,0x00000000,0x00000000,0x00000000,0x00000000,0x00000000,0x00000000,0x00000000,0x00000000,0x00000000,0x00000000,0x00000000,0x00000000,0x00000000,
 0x00000000,0x00000000,0x00000000,0x00000000,0x00000000,0x00000000,0x00000000,0x00000000,0x00000000,0x00000000,0x00000000,0x00000000,0x00000000,0x00000000,0x00000000,0x00000000,
 0x00000000,0x00000000,0x00000000,0x00000000,0x00000000,0x00000000,0x00000000,0x00000000,0x00000000,0x00000000,0x00000000,0x00000000,0x00000000,0x00000000,0x00000000,0x00000000,
};

template<int SA>
__device__ __forceinline__ void wgmma_main(float (&d)[80], uint64_t da, uint64_t db, int sd) {
  asm volatile("{\n.reg .pred p;\nsetp.ne.b32 p, %82, 0;\n"
    "wgmma.mma_async.sync.aligned.m64n160k16.f32.bf16.bf16 "
    "{%0, %1, %2, %3, %4, %5, %6, %7, %8, %9, %10, %11, %12, %13, %14, %15, %16, %17, %18, %19, %20, %21, %22, %23, %24, %25, %26, %27, %28, %29, %30, %31, %32, %33, %34, %35, %36, %37, %38, %39, %40, %41, %42, %43, %44, %45, %46, %47, %48, %49, %50, %51, %52, %53, %54, %55, %56, %57, %58, %59, %60, %61, %62, %63, %64, %65, %66, %67, %68, %69, %70, %71, %72, %73, %74, %75, %76, %77, %78, %79}, %80, %81, p, %83, 1, 1, 0;\n}\n"
    : "+f"(d[0]), "+f"(d[1]), "+f"(d[2]), "+f"(d[3]), "+f"(d[4]), "+f"(d[5]), "+f"(d[6]), "+f"(d[7]), "+f"(d[8]), "+f"(d[9]), "+f"(d[10]), "+f"(d[11]), "+f"(d[12]), "+f"(d[13]), "+f"(d[14]), "+f"(d[15]), "+f"(d[16]), "+f"(d[17]), "+f"(d[18]), "+f"(d[19]), "+f"(d[20]), "+f"(d[21]), "+f"(d[22]), "+f"(d[23]), "+f"(d[24]), "+f"(d[25]), "+f"(d[26]), "+f"(d[27]), "+f"(d[28]), "+f"(d[29]), "+f"(d[30]), "+f"(d[31]), "+f"(d[32]), "+f"(d[33]), "+f"(d[34]), "+f"(d[35]), "+f"(d[36]), "+f"(d[37]), "+f"(d[38]), "+f"(d[39]), "+f"(d[40]), "+f"(d[41]), "+f"(d[42]), "+f"(d[43]), "+f"(d[44]), "+f"(d[45]), "+f"(d[46]), "+f"(d[47]), "+f"(d[48]), "+f"(d[49]), "+f"(d[50]), "+f"(d[51]), "+f"(d[52]), "+f"(d[53]), "+f"(d[54]), "+f"(d[55]), "+f"(d[56]), "+f"(d[57]), "+f"(d[58]), "+f"(d[59]), "+f"(d[60]), "+f"(d[61]), "+f"(d[62]), "+f"(d[63]), "+f"(d[64]), "+f"(d[65]), "+f"(d[66]), "+f"(d[67]), "+f"(d[68]), "+f"(d[69]), "+f"(d[70]), "+f"(d[71]), "+f"(d[72]), "+f"(d[73]), "+f"(d[74]), "+f"(d[75]), "+f"(d[76]), "+f"(d[77]), "+f"(d[78]), "+f"(d[79])
    : "l"(da), "l"(db), "r"(sd), "n"(SA));
}
template<int SA>
__device__ __forceinline__ void wgmma_fwd(float (&d)[32], uint64_t da, uint64_t db, int sd) {
  asm volatile("{\n.reg .pred p;\nsetp.ne.b32 p, %34, 0;\n"
    "wgmma.mma_async.sync.aligned.m64n64k16.f32.bf16.bf16 "
    "{%0, %1, %2, %3, %4, %5, %6, %7, %8, %9, %10, %11, %12, %13, %14, %15, %16, %17, %18, %19, %20, %21, %22, %23, %24, %25, %26, %27, %28, %29, %30, %31}, %32, %33, p, %35, 1, 0, 1;\n}\n"
    : "+f"(d[0]), "+f"(d[1]), "+f"(d[2]), "+f"(d[3]), "+f"(d[4]), "+f"(d[5]), "+f"(d[6]), "+f"(d[7]), "+f"(d[8]), "+f"(d[9]), "+f"(d[10]), "+f"(d[11]), "+f"(d[12]), "+f"(d[13]), "+f"(d[14]), "+f"(d[15]), "+f"(d[16]), "+f"(d[17]), "+f"(d[18]), "+f"(d[19]), "+f"(d[20]), "+f"(d[21]), "+f"(d[22]), "+f"(d[23]), "+f"(d[24]), "+f"(d[25]), "+f"(d[26]), "+f"(d[27]), "+f"(d[28]), "+f"(d[29]), "+f"(d[30]), "+f"(d[31])
    : "l"(da), "l"(db), "r"(sd), "n"(SA));
}
template<int SA>
__device__ __forceinline__ void wgmma_inv(float (&d)[28], uint64_t da, uint64_t db, int sd) {
  asm volatile("{\n.reg .pred p;\nsetp.ne.b32 p, %30, 0;\n"
    "wgmma.mma_async.sync.aligned.m64n56k16.f32.bf16.bf16 "
    "{%0, %1, %2, %3, %4, %5, %6, %7, %8, %9, %10, %11, %12, %13, %14, %15, %16, %17, %18, %19, %20, %21, %22, %23, %24, %25, %26, %27}, %28, %29, p, %31, 1, 1, 0;\n}\n"
    : "+f"(d[0]), "+f"(d[1]), "+f"(d[2]), "+f"(d[3]), "+f"(d[4]), "+f"(d[5]), "+f"(d[6]), "+f"(d[7]), "+f"(d[8]), "+f"(d[9]), "+f"(d[10]), "+f"(d[11]), "+f"(d[12]), "+f"(d[13]), "+f"(d[14]), "+f"(d[15]), "+f"(d[16]), "+f"(d[17]), "+f"(d[18]), "+f"(d[19]), "+f"(d[20]), "+f"(d[21]), "+f"(d[22]), "+f"(d[23]), "+f"(d[24]), "+f"(d[25]), "+f"(d[26]), "+f"(d[27])
    : "l"(da), "l"(db), "r"(sd), "n"(SA));
}

__device__ __forceinline__ uint32_t s2u(const void* p) { return (uint32_t)__cvta_generic_to_shared(p); }
__device__ __forceinline__ void mbar_init(uint32_t a, int c) { asm volatile("mbarrier.init.shared::cta.b64 [%0], %1;" ::"r"(a), "r"(c)); }
__device__ __forceinline__ void mbar_expect(uint32_t a, int b) { asm volatile("mbarrier.arrive.expect_tx.shared::cta.b64 _, [%0], %1;" ::"r"(a), "r"(b) : "memory"); }
__device__ __forceinline__ void mbar_arrive(uint32_t a) { asm volatile("mbarrier.arrive.shared::cta.b64 _, [%0];" ::"r"(a) : "memory"); }
__device__ __forceinline__ void mbar_arrive_cluster(uint32_t a, uint32_t cta, uint32_t cnt) {
  asm volatile("{\n.reg .b32 r;\nmapa.shared::cluster.u32 r, %0, %1;\nmbarrier.arrive.shared::cluster.b64 _, [r], %2;\n}" ::"r"(a), "r"(cta), "r"(cnt) : "memory");
}
__device__ __forceinline__ void mbar_wait(uint32_t a, int ph) {
  asm volatile("{\n.reg .pred p;\n.reg .u32 c;\nmov.u32 c, 0;\nWAIT:\n"
               "mbarrier.try_wait.parity.shared::cta.b64 p, [%0], %1;\n@p bra DONE;\n"
               "add.u32 c, c, 1;\nsetp.lt.u32 p, c, 0x400000;\n@p bra WAIT;\ntrap;\nDONE:\n}" ::"r"(a), "r"(ph) : "memory");
}
__device__ __forceinline__ void flag_wait(const unsigned* p, unsigned target) {
  asm volatile("{\n.reg .pred p;\n.reg .u32 c, v;\nmov.u32 c, 0;\nWAIT:\n"
               "ld.acquire.gpu.global.u32 v, [%0];\nsetp.ge.u32 p, v, %1;\n@p bra DONE;\n"
               "add.u32 c, c, 1;\nsetp.lt.u32 p, c, 0x400000;\n@p bra WAIT;\ntrap;\nDONE:\n}" ::"l"(p), "r"(target) : "memory");
}
__device__ __forceinline__ bool elect_one() {
  uint32_t p;
  asm volatile("{\n.reg .pred P;\nelect.sync _|P, 0xffffffff;\nselp.u32 %0, 1, 0, P;\n}" : "=r"(p));
  return p != 0;
}
__device__ __forceinline__ void bulk_ld(uint32_t dst, const void* src, int bytes, uint32_t bar) {
  asm volatile("cp.async.bulk.shared::cluster.global.mbarrier::complete_tx::bytes [%0], [%1], %2, [%3];" ::"r"(dst), "l"(src), "r"(bytes), "r"(bar) : "memory");
}
__device__ __forceinline__ void bulk_ld_mc_h(uint32_t dst, const void* src, int bytes, uint32_t bar, uint16_t mask, uint64_t pol) {
  asm volatile("cp.async.bulk.shared::cluster.global.mbarrier::complete_tx::bytes.multicast::cluster.L2::cache_hint [%0], [%1], %2, [%3], %4, %5;" ::"r"(dst), "l"(src), "r"(bytes), "r"(bar), "h"(mask), "l"(pol) : "memory");
}
__device__ __forceinline__ void tma_ld2(uint32_t dst, const CUtensorMap* tm, int c0, int c1, uint32_t bar) {
  asm volatile("cp.async.bulk.tensor.2d.shared::cluster.global.mbarrier::complete_tx::bytes [%0], [%1, {%3,%4}], [%2];" ::"r"(dst), "l"(tm), "r"(bar), "r"(c0), "r"(c1) : "memory");
}
__device__ __forceinline__ void tma_ld3(uint32_t dst, const CUtensorMap* tm, int c0, int c1, int c2, uint32_t bar) {
  asm volatile("cp.async.bulk.tensor.3d.shared::cluster.global.mbarrier::complete_tx::bytes [%0], [%1, {%3,%4,%5}], [%2];" ::"r"(dst), "l"(tm), "r"(bar), "r"(c0), "r"(c1), "r"(c2) : "memory");
}
__device__ __forceinline__ void tma_ld3h(uint32_t dst, const CUtensorMap* tm, int c0, int c1, int c2, uint32_t bar, uint64_t pol) {
  asm volatile("cp.async.bulk.tensor.3d.shared::cluster.global.mbarrier::complete_tx::bytes.L2::cache_hint [%0], [%1, {%3,%4,%5}], [%2], %6;" ::"r"(dst), "l"(tm), "r"(bar), "r"(c0), "r"(c1), "r"(c2), "l"(pol) : "memory");
}
__device__ __forceinline__ uint64_t policy_evict_first() {
  uint64_t p;
  asm("createpolicy.fractional.L2::evict_first.b64 %0, 1.0;" : "=l"(p));
  return p;
}
__device__ __forceinline__ void tma_st3(const CUtensorMap* tm, uint32_t src, int c0, int c1, int c2) {
  asm volatile("cp.async.bulk.tensor.3d.global.shared::cta.bulk_group [%0, {%2,%3,%4}], [%1];" ::"l"(tm), "r"(src), "r"(c0), "r"(c1), "r"(c2) : "memory");
}
__device__ __forceinline__ void tma_st4(const CUtensorMap* tm, uint32_t src, int c0, int c1, int c2, int c3) {
  asm volatile("cp.async.bulk.tensor.4d.global.shared::cta.bulk_group [%0, {%2,%3,%4,%5}], [%1];" ::"l"(tm), "r"(src), "r"(c0), "r"(c1), "r"(c2), "r"(c3) : "memory");
}
__device__ __forceinline__ void tma_st5(const CUtensorMap* tm, uint32_t src, int c0) {
  asm volatile("cp.async.bulk.tensor.5d.global.shared::cta.bulk_group [%0, {%2,%3,%3,%3,%3}], [%1];" ::"l"(tm), "r"(src), "r"(c0), "r"(0) : "memory");
}
__device__ __forceinline__ void bulk_commit() { asm volatile("cp.async.bulk.commit_group;" ::: "memory"); }
template <int N> __device__ __forceinline__ void bulk_wait_read() { asm volatile("cp.async.bulk.wait_group.read %0;" ::"n"(N) : "memory"); }
template <int N> __device__ __forceinline__ void bulk_wait() { asm volatile("cp.async.bulk.wait_group %0;" ::"n"(N) : "memory"); }
__device__ __forceinline__ void fence_async_smem() { asm volatile("fence.proxy.async.shared::cta;" ::: "memory"); }
__device__ __forceinline__ void wg_fence() { asm volatile("wgmma.fence.sync.aligned;" ::: "memory"); }
__device__ __forceinline__ void wg_commit() { asm volatile("wgmma.commit_group.sync.aligned;" ::: "memory"); }
template <int N> __device__ __forceinline__ void wg_wait() { asm volatile("wgmma.wait_group.sync.aligned %0;" ::"n"(N) : "memory"); }
template <int R> __device__ __forceinline__ void fence_regs(float (&d)[R]) {
#pragma unroll
  for (int i = 0; i < R; i++) asm volatile("" : "+f"(d[i])::"memory");
}
__device__ __forceinline__ uint64_t mk_desc(uint32_t addr) {
  return (uint64_t)((addr & 0x3FFFF) >> 4) | (1ull << 16) | (64ull << 32) | (1ull << 62);
}
__device__ __forceinline__ uint32_t pack2(float lo, float hi) {
  uint32_t r;
  asm("cvt.rn.bf16x2.f32 %0, %1, %2;" : "=r"(r) : "f"(hi), "f"(lo));
  return r;
}
__device__ __forceinline__ void stsm4(uint32_t ad, uint32_t a, uint32_t b, uint32_t c, uint32_t d) {
  asm volatile("stmatrix.sync.aligned.m8n8.x4.shared.b16 [%0], {%1,%2,%3,%4};" ::"r"(ad), "r"(a), "r"(b), "r"(c), "r"(d) : "memory");
}
__device__ __forceinline__ void stsm4t(uint32_t ad, uint32_t a, uint32_t b, uint32_t c, uint32_t d) {
  asm volatile("stmatrix.sync.aligned.m8n8.x4.trans.shared.b16 [%0], {%1,%2,%3,%4};" ::"r"(ad), "r"(a), "r"(b), "r"(c), "r"(d) : "memory");
}

__device__ __forceinline__ void stsm2t(uint32_t ad, uint32_t a, uint32_t b) {
  asm volatile("stmatrix.sync.aligned.m8n8.x2.trans.shared.b16 [%0], {%1,%2};" ::"r"(ad), "r"(a), "r"(b) : "memory");
}
__device__ __forceinline__ void red_add(unsigned* p) { asm volatile("red.relaxed.gpu.global.add.u32 [%0], 1;" ::"l"(p) : "memory"); }
__device__ __forceinline__ void fence_release() { asm volatile("fence.release.gpu;" ::: "memory"); }
__device__ __forceinline__ void fence_async_global() { asm volatile("fence.proxy.async.global;" ::: "memory"); }
__device__ __forceinline__ void tma_pf2(const CUtensorMap* tm, int c0, int c1) {
  asm volatile("cp.async.bulk.prefetch.tensor.2d.L2.global [%0, {%1,%2}];" ::"l"(tm), "r"(c0), "r"(c1) : "memory");
}
__device__ __forceinline__ void tma_pf3(const CUtensorMap* tm, int c0, int c1, int c2) {
  asm volatile("cp.async.bulk.prefetch.tensor.3d.L2.global [%0, {%1,%2,%3}];" ::"l"(tm), "r"(c0), "r"(c1), "r"(c2) : "memory");
}
__device__ __forceinline__ uint64_t policy_evict_unchanged() {
  uint64_t p;
  asm("createpolicy.fractional.L2::evict_unchanged.b64 %0, 1.0;" : "=l"(p));
  return p;
}

__device__ __forceinline__ int lane_id() {
  int l;
  asm volatile("mov.u32 %0, %%laneid;" : "=r"(l));
  return l;
}
__device__ __forceinline__ void poll64x4(const unsigned long long* p, unsigned long long (&v)[4]) {
  asm volatile("{\n.reg .pred p;\n.reg .u32 c;\n.reg .b64 t, u;\nmov.u32 c, 0;\nWAIT:\n"
               "ld.relaxed.gpu.global.u64 %0, [%4];\nld.relaxed.gpu.global.u64 %1, [%4+512];\n"
               "ld.relaxed.gpu.global.u64 %2, [%4+1024];\nld.relaxed.gpu.global.u64 %3, [%4+1536];\n"
               "or.b64 t, %0, %1;\nor.b64 u, %2, %3;\nor.b64 t, t, u;\nsetp.ge.s64 p, t, 0;\n@p bra DONE;\n"
               "add.u32 c, c, 1;\nsetp.lt.u32 p, c, 0x400000;\n@p bra WAIT;\ntrap;\nDONE:\n}"
               : "=l"(v[0]), "=l"(v[1]), "=l"(v[2]), "=l"(v[3]) : "l"(p) : "memory");
}

constexpr int G_STAGE = WBLK + XBLK;
constexpr int OFF_XR = 4 * G_STAGE;
constexpr int OFF_WS = OFF_XR + 6 * 8192;
constexpr int OFF_F = OFF_WS + 2 * 8192;
constexpr int OFF_WRAW = OFF_F + 8192;
constexpr int OFF_BAR = OFF_WRAW + 8192;
constexpr int OFF_GB = OFF_BAR + 1024;
constexpr int SMEM_BYTES = OFF_GB + 512;
constexpr int OFF_H0B = 10 * 8192;
constexpr int OFF_E = OFF_WRAW + 3072;
constexpr int B_RAWX = 0, B_F = 48, B_ROLE = 56, B_H0 = 80, B_H1 = 96, B_YFREE = 120, B_H0C = 136,
              B_EMPTY = 144,
              B_STGX = 192, B_STGW = 240, B_Y = 256, B_OUT = 272, B_YP = 352,
              B_FULL = 432, B_RAWW = 464, B_DONE = 496, S_ROLE = 576, S_PROBE = 592;

struct Maps { CUtensorMap x, we, wo, xst[2], wst, yst[2], yld[2], out, xe[2], w30; };

__device__ __forceinline__ int chunk_of(int n) { return n < 16 ? n : 31 - n; }
__device__ __forceinline__ bool has_x2(int id, int n, int g) { return (((id >> 5) ^ n) & 1) == 0 && ((n >> 1) & 1) == g; }
__device__ __forceinline__ int w_row(int id) { return (id & 62) | (id >> 6); }
__device__ __forceinline__ uint32_t x_base(int s, int idx, uint32_t pgmask, int& par) {
  const int page = idx >> 3, o = idx & 7;
  par = (s ^ (pgmask >> page) ^ __popc(o)) & 1;
  return (page << 21) | ((o & 3) << 16) | ((o >> 2) << 19);
}
__device__ __forceinline__ uint32_t read_info(uint32_t bar, int i) {
  uint32_t v;
  mbar_wait(bar + B_ROLE + 8 * i, 0);
  asm volatile("ld.shared.b32 %0, [%1];" : "=r"(v) : "r"(bar + S_ROLE + 4 * i) : "memory");
  return v;
}
__device__ __forceinline__ void send_info(uint32_t bar, int i, uint32_t v) {
#pragma unroll
  for (int r = 0; r < 2; r++)
    asm volatile("{\n.reg .b32 a, m;\nmapa.shared::cluster.u32 a, %0, %2;\nmapa.shared::cluster.u32 m, %1, %2;\n"
                 "st.async.weak.shared::cluster.mbarrier::complete_tx::bytes.b32 [a], %3, [m];\n}"
                 ::"r"(bar + S_ROLE + 4 * i), "r"(bar + B_ROLE + 8 * i), "r"(r), "r"(v) : "memory");
}
__device__ __forceinline__ unsigned probe(uint8_t* p, int lane) {
  if (lane < 2) *(uint4*)(p + lane * 16) = make_uint4(0, 0, 0, 0);
  __syncwarp();
  unsigned v, t0 = 0, t1 = 0;
  if (lane == 0) {
    asm volatile("mov.u32 %0, %%clock;" : "=r"(t0)::"memory");
    asm volatile("atom.relaxed.gpu.global.exch.b32 %0, [%1], 0;" : "=r"(v) : "l"(p) : "memory");
    asm volatile("{\n.reg .pred p;\nsetp.ne.u32 p, %1, 0xffffffff;\nmov.u32 %0, 0;\n@p mov.u32 %0, %%clock;\n}" : "=r"(t1) : "r"(v) : "memory");
  }
  return t1 - t0;
}

template <bool ISX>
__device__ __forceinline__ void t_issue(float (&t)[32], uint32_t sb, uint32_t raw) {
  const uint64_t da = mk_desc(sb + OFF_F), db = mk_desc(raw);
  wg_fence();
#pragma unroll
  for (int kk = 0; kk < (ISX ? 4 : 1); kk++) wgmma_fwd<1>(t, da + 2 * kk, db + 128 * kk, kk);
  wg_commit();
}
template <bool ISX>
__device__ __forceinline__ void t_finish(float (&t)[32], uint32_t dst, uint32_t sbar, int sw, int wg, int w, int lane) {
  fence_regs(t);
  if (ISX) asm volatile("bar.sync %0, 128;" ::"r"(1 + wg) : "memory");
  const int m = lane >> 3, r = lane & 7;
  uint32_t ad = dst + (8 * w + r) * 128;
  if (ISX) ad += ((((m & 1) * 4 + (m >> 1)) ^ sw ^ r) << 4);
  else ad += (m & 1) * 4096 + (((m >> 1) ^ sw ^ r) << 4);
#pragma unroll
  for (int i = 0; i < 4; i++) {
    const uint32_t a = ISX ? ((ad ^ ((i & 1) * 32)) + (i >> 1) * 4096) : (ad ^ (i * 32));
    stsm4(a, pack2(t[8 * i], t[8 * i + 1]), pack2(t[8 * i + 2], t[8 * i + 3]), pack2(t[8 * i + 4], t[8 * i + 5]), pack2(t[8 * i + 6], t[8 * i + 7]));
  }
  __syncwarp();
  if (lane == 0) mbar_arrive(sbar);
}
template <int NT, int K0, int K1>
__device__ __forceinline__ void batch(float (&yr)[80], float (&yi)[80], float (&t)[32], uint32_t st, int wg, int sd, uint32_t fa, uint32_t raw) {
  const uint64_t w0 = mk_desc(st + wg * 8192), x0 = mk_desc(st + WBLK);
  const uint64_t da = mk_desc(fa), db = mk_desc(raw);
  wg_fence();
  if (NT) {
#pragma unroll
    for (int kk = 0; kk < NT; kk++) wgmma_fwd<1>(t, da + 2 * kk, db + 128 * kk, kk);
    wg_commit();
  }
#pragma unroll
  for (int kk = K0; kk < K1; kk++) {
    const uint64_t wr = w0 + kk * 128, wi = wr + 256, xr = x0 + kk * 2, xi = xr + 4;
    wgmma_main<1>(yr, wr, xr, kk ? 1 : sd);
    wgmma_main<1>(yi, wr, xi, kk ? 1 : sd);
    wgmma_main<1>(yr, wi, xi, 1);
    wgmma_main<-1>(yi, wi, xr, 1);
  }
  wg_commit();
}

#define X_WAIT() PROF_W(wraw, mbar_wait(bar + B_RAWX + 8 * (wg * 3 + xs), xph))
#define X_ISSUE() t_issue<true>(t, sb, sb + OFF_XR + (wg * 3 + xs) * 8192)
#define X_FINISH(sw) do { t_finish<true>(t, sb + OFF_XR + (wg * 3 + xs) * 8192, bar + B_STGX + 8 * (wg * 3 + xs), sw, wg, w, lane); \
                          if (++xs == 3) { xs = 0; xph ^= 1; } } while (0)
#define W_WAIT(n) PROF_W(wraw, mbar_wait(bar + B_RAWW + 8 * (wg * 2 + ((n) & 1)), ((n) >> 1) & 1))
#define WRAW(n) (sb + OFF_WRAW + (wg * 2 + ((n) & 1)) * 2048)
#define W_FINISH() t_finish<false>(t, sb + OFF_WS + wg * 8192, bar + B_STGW + 8 * wg, w_row(id) & 7, wg, w, lane)

__device__ __forceinline__ void gelu_store(float (&hz)[28], uint32_t ad) {
#pragma unroll
  for (int i = 0; i < 28; i++) {
    const float in = hz[i] * fmaf(hz[i] * hz[i], 8.f * 0.044715f * 0.7978845608028654f, 2.f * 0.7978845608028654f);
    float th;
    asm("tanh.approx.f32 %0, %1;" : "=f"(th) : "f"(in));
    hz[i] = fmaf(hz[i], th, hz[i]);
  }
#pragma unroll
  for (int jj = 0; jj < 3; jj++) {
    const float* c = hz + 8 * jj;
    stsm4t(ad + jj * 2048, pack2(c[0], c[1]), pack2(c[2], c[3]), pack2(c[4], c[5]), pack2(c[6], c[7]));
  }
  stsm2t(ad + 3 * 2048, pack2(hz[24], hz[25]), pack2(hz[26], hz[27]));
}

template <int g>
__device__ __forceinline__ void manager(const Maps& tm, unsigned* ctr, const uint32_t sb, const int id) {
  const uint32_t bar = sb + OFF_BAR, rank = id & 1;
  const uint64_t pol = policy_evict_first();
  const int cl = w_row(id);
  int li = 0;
  auto refill = [&](int sl) {
    if (li >= 32) return;
    const uint32_t fb = bar + B_RAWX + 8 * (g * 3 + sl);
    mbar_expect(fb, 8192);
    tma_ld3h(sb + OFF_XR + (g * 3 + sl) * 8192, &tm.x, (li >> 1) * 64, ((li & 1) ? 128 + (id & 31) : 2 * (id & 63) + g) * MT, id >> 6, fb, pol);
    li += (li & 1) || has_x2(id, li >> 1, g) ? 1 : 2;
  };
#pragma unroll 1
  for (int sl = 0; sl < 3; sl++) refill(sl);
  int xs = 0, xph = 0, yp = 0;
  int wrow = (rank * 2 + (cl >> 5)) * 128 + g * 64 + (cl & 31);
  mbar_wait(bar + B_STGW + 8 * g, 0);
  fence_async_smem();
  tma_st4(&tm.wst, sb + OFF_WS + g * 8192, 0, 0, 0, wrow);
  bulk_commit();
  const uint32_t pgmask = read_info(bar, 1);
#pragma unroll 1
  for (int n = 0; n < 32; n++) {
    unsigned freed = 128;
    if (n >= WR) asm volatile("ld.relaxed.gpu.global.u32 %0, [%1];" : "=r"(freed) : "l"(&ctr[(C_LOADED + n - WR) * 32]) : "memory");
    if (n < 16) {
#pragma unroll 1
      for (int j = 0; j < (has_x2(id, n, g) ? 2 : 1); j++) {
        const int t = j ? 128 + (id & 31) : 2 * (id & 63) + g;
        int par0, par1;
        const uint32_t off0 = x_base(id >> 6, n * 10 + (t >> 5), pgmask, par0), off1 = x_base(id >> 6, n * 10 + 5 + (t >> 5), pgmask, par1);
        const uint32_t buf = sb + OFF_XR + (g * 3 + xs) * 8192;
        mbar_wait(bar + B_STGX + 8 * (g * 3 + xs), xph);
        fence_async_smem();
        tma_st5(&tm.xst[par0], buf, (off0 + (par0 << 12) + (t & 31) * 128) >> 1);
        tma_st5(&tm.xst[par1], buf + 4096, (off1 + (par1 << 12) + (t & 31) * 128) >> 1);
        bulk_commit();
        bulk_wait_read<0>();
        refill(xs);
        if (++xs == 3) { xs = 0; xph ^= 1; }
      }
    }
    if (n > 16 + LW && n <= YFLUSH && (n - 17 - LW) % YSTEP == 0) {
      if (yp == 0 || yp == 3) mbar_wait(bar + B_Y + 8 * g, yp & 1);
#pragma unroll 1
      do {
        tma_st4(&tm.yst[0], sb + OFF_XR + (g * 3 + (yp < 3 ? yp : yp - 3)) * 8192, 0, yp * 32, id & 62, (id >> 6) * 4 + rank * 2 + g);
      } while (++yp < 2);
      bulk_commit();
      bulk_wait_read<0>();
      if (yp == 2) mbar_arrive(bar + B_YFREE + 8 * g);
    }
    if (freed < 128) flag_wait(&ctr[(C_LOADED + n - WR) * 32], 128);
    if (n) {
      mbar_wait(bar + B_STGW + 8 * g, n & 1);
      fence_async_smem();
      tma_st4(&tm.wst, sb + OFF_WS + g * 8192, 0, 0, 0, wrow);
      bulk_commit();
    }
    wrow += WCHUNK / 128;
    if (wrow >= WR * WCHUNK / 128) wrow -= WR * WCHUNK / 128;
    if (n < 30) {
      const int cp = chunk_of(n + 2) * 64 + cl, sl = g * 2 + (n & 1);
      mbar_expect(bar + B_RAWW + 8 * sl, 2048);
      tma_ld3h(sb + OFF_WRAW + sl * 2048, &tm.we + (cp >> 9), 0, 0, (cp & 511) * 8 + ((n + 2) >> 4) * 4 + rank * 2 + g, bar + B_RAWW + 8 * sl, pol);
    }
    if (n < 4) {
#pragma unroll 1
      for (int q = 4 + n; q < 16; q += 4) {
        const int cp = q * 64 + cl;
        tma_pf3(&tm.we + (cp >> 9), 0, 0, (cp & 511) * 8 + rank * 2 + g);
      }
    }
    bulk_wait<0>();
    mbar_arrive(bar + B_DONE + 8 * (n & 7));
    mbar_arrive(bar + B_RAWW + 8 * (g * 2 + ((n + 1) & 1)));
  }
  const int b = id >> 6, u = (id >> 1) & 31;
  flag_wait(&ctr[(C_LOADED + 31) * 32], 128);
#pragma unroll 1
  for (int p = 0; p < 5; p++) {
    mbar_wait(bar + B_YP + 8 * (g * 5 + p), 0);
    fence_async_smem();
    tma_st4(&tm.yst[1], sb + (p * 2 + g) * 8192, 0, p * 32, 2 * u, b * 4 + rank * 2 + g);
  }
  bulk_commit();
  bulk_wait<0>();
  mbar_arrive(bar + B_DONE);
#pragma unroll 1
  for (int i = 0; i < 10; i++) {
    const int hf = i >= 5, k = i - 5 * hf;
    mbar_wait(bar + B_OUT + 8 * (g * 5 + k), hf);
    fence_async_smem();
    tma_st3(&tm.out, sb + (hf ? 0 : k < 4 ? OFF_XR : OFF_H0B - 65536) + (2 * k + g) * 8192, (hf * 4 + rank * 2 + (u & 1)) * 64, ((u >> 1) * 10 + 2 * k + g) * MT, b);
    bulk_commit();
  }
  bulk_wait_read<0>();
  if (g == 0) PROF_T(12);
}

__global__ void __cluster_dims__(2, 1, 1) __launch_bounds__(512, 1)
k1_main(uint8_t* __restrict__ xbuf, const void* __restrict__ fimg, unsigned* ctr, const __nv_bfloat16* __restrict__ gamma,
        const __nv_bfloat16* __restrict__ beta, const __grid_constant__ Maps tm) {
  extern __shared__ __align__(1024) uint8_t smem_raw[];
  const uint32_t sb = s2u(smem_raw);
  const uint32_t bar = sb + OFF_BAR;
  const int warp = __shfl_sync(0xffffffffu, threadIdx.x >> 5, 0);
  const int bid = blockIdx.x;
  const uint32_t rank = bid & 1;
  if (bid == 0 && threadIdx.x < 4) asm volatile("st.relaxed.gpu.global.u64 [%0], %1;" ::"l"(&ctr[C_REG * 32 + 2 * threadIdx.x]), "l"(1ull << 63) : "memory");
  if (warp >= 12) {
    asm volatile("setmaxnreg.dec.sync.aligned.u32 24;");
    asm volatile("barrier.cluster.arrive.relaxed.aligned;" ::: "memory");
    {
      const int lane = lane_id(), k = bid >> 1;
      if (rank == 0 || k < XPAGES) {
        const uint32_t off = rank ? (k << 21) + 0xb0000 : (XPAGES << 21) + ((k >> 6) << 18) + (((k >> 4) & 3) << 14) + (k & 15) * 128;
        const unsigned lat = probe(xbuf + off + (warp & 1) * 4096 + (warp & 2) * 1024, lane);
        if (lane == 0) asm volatile("st.shared.b32 [%0], %1;" ::"r"(bar + S_PROBE + 4 * (warp & 3)), "r"(lat) : "memory");
      }
      asm volatile("bar.sync 4, 128;" ::: "memory");
      asm volatile("barrier.cluster.wait.aligned;" ::: "memory");
      if (warp == 14 && lane == 0) {
        uint32_t l0, l1, l2, l3;
        asm volatile("ld.shared.v4.b32 {%0, %1, %2, %3}, [%4];" : "=r"(l0), "=r"(l1), "=r"(l2), "=r"(l3) : "r"(bar + S_PROBE) : "memory");
        const int near = min(l1, l3) < min(l0, l2);
        if (rank) {
          send_info(bar, 2, near);
        } else {
          unsigned long long add = 1ull << (8 * near), v, *reg = (unsigned long long*)&ctr[C_REG * 32];
          if (k < XPAGES) add += (unsigned long long)(read_info(bar, 2) ^ near ^ 1) << (16 + k);
          PROF_T(14);
          asm volatile("{\n.reg .pred p;\n.reg .u32 c;\nmov.u32 c, 0;\nAGAIN:\n"
                       "atom.relaxed.gpu.global.add.u64 %0, [%1], %2;\nsetp.lt.s64 p, %0, 0;\n@p bra DONE;\n"
                       "add.u32 c, c, 1;\nsetp.lt.u32 p, c, 0x100000;\n@p bra AGAIN;\ntrap;\nDONE:\n}" : "=l"(v) : "l"(reg), "l"(add) : "memory");
          const int ticket = (v >> (8 * near)) & 255;
          if (ticket < 32) send_info(bar, 0, near * 32 + ticket);
          PROF_T(15); PROF_V(16, near);
          asm volatile("{\n.reg .pred p;\n.reg .u32 c, a, b;\nmov.u32 c, 0;\nWAIT:\n"
                       "ld.relaxed.gpu.global.u64 %0, [%1];\ncvt.u32.u64 a, %0;\nbfe.u32 b, a, 8, 8;\nand.b32 a, a, 255;\nadd.u32 a, a, b;\n"
                       "setp.ge.u32 p, a, 66;\n@p bra DONE;\n"
                       "add.u32 c, c, 1;\nsetp.lt.u32 p, c, 0x400000;\n@p bra WAIT;\ntrap;\nDONE:\n}" : "=l"(v) : "l"(reg) : "memory");
          if (ticket >= 32) {
            const int j = ticket - 32 + (int)((v >> (8 * (near ^ 1))) & 255);
            send_info(bar, 0, j < 32 ? (near ^ 1) * 32 + j : (near == 0 && ticket == 32 && j == 33) ? 64 : 32 + j);
          }
          send_info(bar, 1, (uint32_t)(v >> 16));
          PROF_T(13);
        }
      }
      __syncwarp();
      const int role = read_info(bar, 0);
      if (role < 64 && warp - 12 < NFL && elect_one()) {
#pragma unroll 1
        for (int n = warp - 12; n < 33; n += NFL) {
          int f = n;
          if (n == 32) f += (role >> 5) * 2 + rank;
          mbar_wait(bar + B_DONE + 8 * (n & 7), (n >> 3) & 1);
          fence_release();
          red_add(&ctr[(C_FLAG + f) * 32]);
          if (n < 32) { PROF_T(64 + n); PROF_V(192 + n, tm0); } else { PROF_V(4, tm0); }
        }
      }
      if (role < 64 && warp == 15 && elect_one()) {
#pragma unroll 1
        for (int v = 0; v < 64; v++) {
          mbar_wait(bar + B_FULL + 8 * (v & 3), (v >> 2) & 1);
          mbar_arrive(bar + B_EMPTY + 8 * (v & 3));
          if ((v & 1) && (v < 2 * (32 - WR) || v == 63)) red_add(&ctr[(C_LOADED + (v >> 1)) * 32]);
        }
      }
      __syncwarp();
    }
    asm volatile("barrier.cluster.arrive.relaxed.aligned;\nbarrier.cluster.wait.aligned;" ::: "memory");
    return;
  } else {
    if (elect_one()) {
      if (warp == 0) PROF_T(0);
      if (warp >= 6) asm volatile("prefetch.tensormap [%0];" ::"l"(&tm.x + (warp - 6)) : "memory");
      const int cnt = warp < 3 ? 1 : warp == 3 ? 5 : warp < 9 ? 4 : 2;
#pragma unroll
      for (int i = 0; i < 6; i++) mbar_init(bar + warp * 48 + 8 * i, cnt);
      if (warp == 1) {
        mbar_expect(bar + B_F, 8192);
        bulk_ld(sb + OFF_F, fimg, 8192, bar + B_F);
        mbar_expect(bar + B_ROLE, 4);
        mbar_expect(bar + B_ROLE + 8, 4);
        mbar_expect(bar + B_ROLE + 16, 4);
      }
      asm volatile("fence.mbarrier_init.release.cluster;" ::: "memory");
    }
    asm volatile("bar.sync 0, 384;" ::: "memory");
    asm volatile("barrier.cluster.arrive.relaxed.aligned;" ::: "memory");
    if (threadIdx.x == 64) PROF_T(20);
    if (bid < 128 && warp < 4 && elect_one()) {
      const int g = warp & 1;
      if (warp < 2) {
        tma_pf3(&tm.x, 0, (2 * (bid & 63) + g) * MT, bid >> 6);
        if (has_x2(bid, 0, g)) tma_pf3(&tm.x, 0, (128 + (bid & 31)) * MT, bid >> 6);
      } else {
        tma_pf3(&tm.we, 0, 0, (bid >> 1) * 8 + rank * 2 + g);
      }
    }
    __syncwarp();
  }
  if (warp >= 8) {
    asm volatile("setmaxnreg.dec.sync.aligned.u32 40;");
    asm volatile("barrier.cluster.wait.aligned;" ::: "memory");
    const int role = __shfl_sync(0xffffffffu, read_info(bar, 0), 0);
    if (role >= 64) {
    } else if (warp == 9 || warp == 10) {
      asm volatile("barrier.cluster.arrive.relaxed.aligned;" ::: "memory");
      if (elect_one()) {
        if (warp == 9) manager<0>(tm, ctr, sb, role * 2 + rank); else manager<1>(tm, ctr, sb, role * 2 + rank);
      }
      __syncwarp();
      asm volatile("barrier.cluster.wait.aligned;" ::: "memory");
      return;
    } else if (warp == 11) {
      if (elect_one()) {
        const uint8_t* ws = g_W + (size_t)((role & 31) * 2 + rank) * 2 * WBLK;
        int slot = 0;
#pragma unroll 1
        for (int n = 0; n < 32; n++) {
          const uint8_t* src = ws + (size_t)slot * WCHUNK;
          const uint32_t s8 = (n & 1) * 16, dst = sb + (n & 1) * 2 * G_STAGE;
          const int ph = ((n >> 1) & 1) ^ 1;
          if (++slot == WR) slot = 0;
          flag_wait(&ctr[(C_FLAG + n) * 32], 128);
          fence_async_global();
          PROF_T(32 + n);
#pragma unroll
          for (int h = 0; h < 2; h++) {
            mbar_wait(bar + B_EMPTY + s8 + 8 * h, ph);
            mbar_expect(bar + B_FULL + s8 + 8 * h, WBLK);
            bulk_ld(dst + h * G_STAGE, src + h * WBLK, WBLK, bar + B_FULL + s8 + 8 * h);
          }
        }
      }
      __syncwarp();
    } else {
      if (elect_one()) {
        const uint32_t pgmask = read_info(bar, 1);
        PROF_T(1);
        const int b = role >> 5, u = role & 31;
        const int dq = rank * 2 + (u & 1), t0 = (u >> 1) * 10;
        const uint64_t pef = policy_evict_first(), pen = policy_evict_unchanged();
        const uint8_t* xs = xbuf + ((((u >> 1) & 3) << 14) | (((u >> 3) & 1) << 18) | ((u >> 4) << 20) | ((u & 1) << 13));
#pragma unroll 1
        for (int n = 0; n < 32; n++) {
          const int c = chunk_of(n);
          const uint64_t polx = (n < XKEEP || n >= 16) ? pef : pen;
          const uint32_t s8 = (n & 1) * 16, dst = sb + (n & 1) * 2 * G_STAGE + WBLK + rank * 8192;
          const int ph = ((n >> 1) & 1) ^ 1;
          uint32_t xo[6];
#pragma unroll
          for (int g = 0; g < 6; g++) {
            int par;
            xo[g] = x_base(b, c * 10 + (g / 3) * 5 + rank * 2 + g % 3, pgmask, par);
            xo[g] += ((par ^ u) & 1) << 12;
            asm volatile("" : "+r"(xo[g]));
          }
          if (n < 16) {
            flag_wait(&ctr[(C_FLAG + n) * 32], 128);
            fence_async_global();
          }
#pragma unroll
          for (int h = 0; h < 2; h++) {
            const uint32_t fb = bar + B_FULL + s8 + 8 * h;
            mbar_wait(bar + B_EMPTY + s8 + 8 * h, ph);
            mbar_expect(fb, XBLK);
#pragma unroll
            for (int g = 0; g < 3; g++) {
              const int skip = (g == 0 && rank) ? 2048 : 0, len = (g == (rank ? 0 : 2)) ? 2048 : 4096;
              bulk_ld_mc_h(dst + h * G_STAGE + g * 4096 + skip, xs + xo[3 * h + g] + skip, len, fb, 3, polx);
            }
          }
        }
        flag_wait(&ctr[C_E * 32], 4);
        flag_wait(&ctr[(C_FLAG + YFLUSH) * 32], 128);
        fence_async_global();
        mbar_expect(bar + B_H0C, 6 * 8192);
        for (int i = 0; i < 3; i++) tma_ld2(sb + OFF_XR + i * 16384, &tm.yld[0], 0, ((b * 4 + dq) * NT + t0 + 2 * i) * 64, bar + B_H0C);
        static_assert(YFLUSH >= 23, "phase of the B_DONE ring");
        mbar_wait(bar + B_DONE + 8 * 7, 1);
        mbar_expect(bar + B_H0, 2 * 8192 + 7168 + 5120 + 512);
        bulk_ld(sb + OFF_F, g_Gimg, 7168, bar + B_H0);
        tma_ld2(sb + OFF_WS, &tm.yld[0], 0, ((b * 4 + dq) * NT + t0 + 6) * 64, bar + B_H0);
        tma_pf2(&tm.yld[0], 0, ((b * 4 + dq) * NT + t0 + 8) * 64);
        for (int hf = 0; hf < 2; hf++) {
          bulk_ld(sb + OFF_E + hf * 2560, g_E + ((b * 8 + hf * 4 + dq) * NT + t0) * 64, 2560, bar + B_H0);
          bulk_ld(sb + OFF_GB + hf * 256, gamma + (hf * 4 + dq) * 64, 128, bar + B_H0);
          bulk_ld(sb + OFF_GB + hf * 256 + 128, beta + (hf * 4 + dq) * 64, 128, bar + B_H0);
        }
        mbar_wait(bar + B_EMPTY + 8 * 2, 1);
        mbar_expect(bar + B_H0 + 8, 16384);
        tma_ld2(sb + OFF_H0B, &tm.yld[0], 0, ((b * 4 + dq) * NT + t0 + 8) * 64, bar + B_H0 + 8);
        flag_wait(&ctr[(C_FLAG + 32 + b * 2 + rank) * 32], 32);
        fence_async_global();
        PROF_T(5);
        for (int i = 0; i < 5; i++) {
          const uint32_t fb = bar + B_H1 + 8 * (i >> 1);
          if ((i & 1) == 0) mbar_expect(fb, i < 4 ? 32768 : 16384);
          tma_ld2(sb + i * 16384, &tm.yld[1], 0, ((b * 4 + dq) * NT + t0 + 2 * i) * 64, fb);
        }
      }
      __syncwarp();
      const int lane = lane_id();
      unsigned old = 0;
      if (lane == 0) old = atomicAdd(&ctr[C_EXIT * 32], 1);
      if (__shfl_sync(0xffffffffu, old, 0) == 127) {
        for (int i = lane; i < C_NUM; i += 32) *(uint4*)&ctr[i * 32] = make_uint4(0, 0, 0, 0);
      }
    }
    asm volatile("barrier.cluster.arrive.relaxed.aligned;\nbarrier.cluster.wait.aligned;" ::: "memory");
  } else {
    asm volatile("setmaxnreg.inc.sync.aligned.u32 224;");
    const int wg = warp >> 2, w = warp & 3;
    int lane = lane_id();
    asm volatile("barrier.cluster.wait.aligned;" ::: "memory");
    mbar_wait(bar + B_F, 0);
    const int id = __shfl_sync(0xffffffffu, read_info(bar, 0), 0) * 2 + rank;
    if (id >= 128) {
      float ea[80], eb[80];
      const int b = (id >> 1) & 1;
      constexpr int ES = 32768 + 2 * XBLK;
#pragma unroll 1
      for (int k = -3; k < 8; k++) {
        const int sl = (k + 3) % 3;
        if (k >= 0) {
          mbar_wait(bar + B_RAWX + 8 * sl, (k / 3) & 1);
          const uint64_t da = mk_desc(sb + sl * ES + wg * 16384), db = mk_desc(sb + sl * ES + 32768);
          wg_fence();
#pragma unroll
          for (int kk = 0; kk < 8; kk++) {
            const uint64_t a0 = da + (kk & 3) * 128, b0 = db + (kk & 3) * 2 + (kk >> 2) * (XBLK >> 4);
            wgmma_main<1>(ea, a0, b0, (k | kk) != 0);
            wgmma_main<1>(eb, a0 + 512, b0, (k | kk) != 0);
          }
          wg_commit();
          wg_wait<0>();
          asm volatile("bar.sync 3, 256;" ::: "memory");
        }
        if (k + 3 < 8 && warp == 0 && elect_one()) {
          if (k == -3) {
            for (int i = 0; i < 64; i++) {
              unsigned v;
              asm volatile("ld.relaxed.gpu.global.u32 %0, [%1];" : "=r"(v) : "l"(&ctr[(C_FLAG + 14) * 32]) : "memory");
              if (v >= 128) break;
              __nanosleep(500);
            }
          }
          const uint32_t dst = sb + sl * ES, fb = bar + B_RAWX + 8 * sl;
          mbar_expect(fb, ES);
          for (int q = 0; q < 4; q++) tma_ld2(dst + q * 8192, &tm.w30, rank * 256 + q * 64, (k + 3) * 64, fb);
          for (int q = 0; q < 2; q++) tma_ld3(dst + 32768 + q * XBLK, &tm.xe[q], (k + 3) * 64, 0, b, fb);
        }
        __syncwarp();
      }
      fence_regs(ea);
      fence_regs(eb);
      float* e0 = g_E + ((b * 8 + rank * 4 + wg * 2) * NT + 2 * (lane & 3)) * 64 + 16 * w + (lane >> 2);
#pragma unroll
      for (int i = 0; i < 80; i++) {
        const int o = (8 * (i >> 2) + (i & 1)) * 64 + ((i >> 1) & 1) * 8;
        e0[o] = ea[i];
        e0[o + NT * 64] = eb[i];
      }
      asm volatile("bar.sync 3, 256;" ::: "memory");
      if (threadIdx.x == 0) {
        fence_release();
        red_add(&ctr[C_E * 32]);
        PROF_T(28);
      }
      asm volatile("barrier.cluster.arrive.relaxed.aligned;\nbarrier.cluster.wait.aligned;" ::: "memory");
      return;
    }
    if (w < 2 && elect_one()) {
      const uint32_t fb = bar + B_RAWW + 8 * (wg * 2 + w);
      mbar_expect(fb, 2048);
      tma_ld3h(sb + OFF_WRAW + (wg * 2 + w) * 2048, &tm.we, 0, 0, (w * 64 + w_row(id)) * 8 + rank * 2 + wg, fb, policy_evict_first());
      if (!w) mbar_arrive(fb);
    }
    __syncwarp();
    {
      float yr[80], yi[80], t[32];

      int xs = 0, xph = 0;
      if (threadIdx.x == 0) PROF_T(24);
      W_WAIT(0);
      t_issue<false>(t, sb, WRAW(0));
      wg_wait<0>();
      W_FINISH();
      if (threadIdx.x == 0) PROF_T(25);
#pragma unroll 1
      for (int m = 0; m <= LW; m++) {
        X_WAIT();
        X_ISSUE();
        wg_wait<0>();
        X_FINISH((2 * id + wg) & 7);
        if (threadIdx.x == 0 && m == 0) PROF_T(26);
        if (has_x2(id, m, wg)) {
          X_WAIT();
          X_ISSUE();
          wg_wait<0>();
          X_FINISH(id & 7);
        }
        if (m < LW && m) {
          W_WAIT(m);
          t_issue<false>(t, sb, WRAW(m));
          wg_wait<0>();
          W_FINISH();
        }
      }
      if (threadIdx.x == 0) PROF_T(27);
      const int ym = lane >> 3, yr8 = lane & 7;
      const uint32_t yad = (ym >> 1) * 4096 + yr8 * 128 + (((2 * w + (ym & 1)) ^ yr8) << 4);
#define STAGE_PROF0()
#define STAGE_PROF1()
#define STAGE_BEGIN() PROF_W(wfull, mbar_wait(bar + B_FULL + 8 * (v & 3), (v >> 2) & 1)); STAGE_PROF0(); const uint32_t st = sb + (v & 3) * G_STAGE
#define RELEASE(vv) do { if (w == 0 && lane < 2) mbar_arrive_cluster(bar + B_EMPTY + 8 * ((vv) & 3), lane, 1); } while (0)
#define XRAW (sb + OFF_XR + (wg * 3 + xs) * 8192)
#define STAGE_W0(mw, sd) do { W_WAIT(mw); batch<1, 0, 2>(yr, yi, t, st, wg, sd, sb + OFF_F, WRAW(mw)); wg_wait<1>(); W_FINISH(); wg_wait<0>(); RELEASE(v); } while (0)
#define STAGE_PLAIN0(sd) do { batch<0, 0, 2>(yr, yi, t, st, wg, sd, 0, 0); wg_wait<0>(); RELEASE(v); } while (0)
#define STAGE_W1(mw, sd) do { W_WAIT(mw); batch<1, 0, 1>(yr, yi, t, st, wg, sd, sb + OFF_F, WRAW(mw)); wg_wait<1>(); if (sd) RELEASE(v - 1); \
                              W_FINISH(); batch<0, 1, 2>(yr, yi, t, st, wg, 1, 0, 0); } while (0)
#define STAGE_PLAIN1(sd) do { batch<0, 0, 1>(yr, yi, t, st, wg, sd, 0, 0); wg_wait<1>(); if (sd) RELEASE(v - 1); \
                              batch<0, 1, 2>(yr, yi, t, st, wg, 1, 0, 0); } while (0)
#pragma unroll 1
      for (int v = 0; v < 32; v++) {
        const int m = ((v + 1) >> 1) + LW;
        STAGE_BEGIN();
        if (!(v & 1) || v == 31) {
          STAGE_W1(m, v != 0);
        } else if (m >= 16) {
          STAGE_PLAIN1(1);
        } else {
          X_WAIT();
          batch<4, 0, 1>(yr, yi, t, st, wg, 1, sb + OFF_F, XRAW);
          wg_wait<1>();
          RELEASE(v - 1);
          X_FINISH((2 * id + wg) & 7);
          if (has_x2(id, m, wg)) {
            X_WAIT();
            batch<4, 1, 2>(yr, yi, t, st, wg, 1, sb + OFF_F, XRAW);
            wg_wait<1>();
            X_FINISH(id & 7);
          } else {
            batch<0, 1, 2>(yr, yi, t, st, wg, 1, 0, 0);
          }
        }
        STAGE_PROF1();
      }
      wg_wait<0>();
      fence_regs(yr);
      fence_regs(yi);
      RELEASE(31);
      {
        uint32_t hold[32];
#pragma unroll
        for (int j = 0; j < 20; j++) {
          const uint32_t p0 = pack2(yr[4 * j], yr[4 * j + 1]), p1 = pack2(yr[4 * j + 2], yr[4 * j + 3]);
          const uint32_t p2 = pack2(yi[4 * j], yi[4 * j + 1]), p3 = pack2(yi[4 * j + 2], yi[4 * j + 3]);
          if (j < 12) {
            stsm4t(sb + OFF_XR + wg * 3 * 8192 + yad + (j >> 2) * 8192 + (j & 3) * 1024, p0, p1, p2, p3);
          } else {
            hold[4 * j - 48] = p0; hold[4 * j - 47] = p1; hold[4 * j - 46] = p2; hold[4 * j - 45] = p3;
          }
        }
#pragma unroll
        for (int j = 0; j < 32; j++) asm volatile("" : "+r"(hold[j])::"memory");
        fence_async_smem();
        __syncwarp();
        if (lane == 0) mbar_arrive(bar + B_Y + 8 * wg);
        if (threadIdx.x == 0) PROF_T(2);
#pragma unroll
        for (int v = 32; v < 34; v++) {
          STAGE_BEGIN();
          STAGE_PLAIN0(v != 32);
          STAGE_PROF1();
        }
        mbar_wait(bar + B_YFREE + 8 * wg, 0);
#pragma unroll
        for (int j = 0; j < 8; j++)
          stsm4t(sb + OFF_XR + wg * 3 * 8192 + yad + (j >> 2) * 8192 + (j & 3) * 1024, hold[4 * j], hold[4 * j + 1], hold[4 * j + 2], hold[4 * j + 3]);
        fence_async_smem();
        __syncwarp();
        if (lane == 0) mbar_arrive(bar + B_Y + 8 * wg);
#pragma unroll
        for (int j = 0; j < 32; j++) t[j] = __uint_as_float(hold[j]);
      }
#pragma unroll 1
      for (int v = 34; v < 64; v++) {
        const int m = (v >> 1) + LW;
        STAGE_BEGIN();
        if (!(v & 1) && m < 32) {
          STAGE_W0(m, 1);
        } else {
          STAGE_PLAIN0(1);
          if (v == 49 && wg == 0) g_part[id * 128 + w * 32 + lane] = ~0ull;
        }
        STAGE_PROF1();
      }
      wg_wait<0>();
      fence_regs(yr);
      fence_regs(yi);
      asm volatile("bar.sync 3, 256;" ::: "memory");
#pragma unroll
      for (int j = 0; j < 20; j++) {
        stsm4t(sb + wg * 8192 + yad + (j >> 2) * 16384 + (j & 3) * 1024, pack2(yr[4 * j], yr[4 * j + 1]), pack2(yr[4 * j + 2], yr[4 * j + 3]),
               pack2(yi[4 * j], yi[4 * j + 1]), pack2(yi[4 * j + 2], yi[4 * j + 3]));
        if ((j & 3) == 3) {
          __syncwarp();
          if (lane == 0) mbar_arrive(bar + B_YP + 8 * (wg * 5 + (j >> 2)));
        }
      }
      if (threadIdx.x == 0) PROF_T(3);
    }
    asm volatile("barrier.cluster.arrive.relaxed.aligned;" ::: "memory");
    lane = lane_id();
    const int tid = warp * 32 + lane, b = id >> 6, u = (id >> 1) & 31;
    const int dq = rank * 2 + (u & 1), tr = u >> 1;
    const int a = lane & 3, d0 = 16 * w + (lane >> 2);
    float2* s_red = (float2*)(smem_raw + OFF_WRAW);
    const uint32_t oad = wg * 8192 + ((lane >> 4) * 8 + (lane & 7)) * 128 + (((2 * w + ((lane >> 3) & 1)) ^ (lane & 7)) << 4);
#pragma unroll 1
    for (int hf = 0; hf < 2; hf++) {
      const uint32_t base = sb + (hf ? 0 : OFF_XR), last = hf ? 0 : OFF_H0B - 65536 - OFF_XR;
      float acc[5][28];
      float q1[4] = {0.f, 0.f, 0.f, 0.f}, q2[4] = {0.f, 0.f, 0.f, 0.f};
      if (hf == 0) { mbar_wait(bar + B_H0, 0); mbar_wait(bar + B_H0C, 0); }
      const float* se = (const float*)(smem_raw + OFF_E + hf * 2560) + wg * 64 + d0;
#pragma unroll
      for (int k2 = 0; k2 < 4; k2++) {
        if (k2 < 3) {
          if (hf) mbar_wait(bar + B_H1 + 8 * k2, 0);
          else if (k2 == 2) mbar_wait(bar + B_H0 + 8, 0);
          const uint64_t da = mk_desc(base + (4 * k2 + wg) * 8192 + (k2 == 2 ? last : 0)), db = mk_desc(sb + OFF_F);
          wg_fence();
#pragma unroll
          for (int kk = 0; kk < 4; kk++) {
            wgmma_inv<1>(acc[2 * k2], da + 128 * kk, db + 2 * kk, kk);
            if (k2 < 2) wgmma_inv<1>(acc[2 * k2 + 1], da + 1024 + 128 * kk, db + 2 * kk, kk);
          }
          wg_commit();
        }
        if (k2 > 0) {
          if (k2 < 3) wg_wait<1>(); else wg_wait<0>();
#pragma unroll
          for (int k = 2 * k2 - 2; k < 2 * k2 && k < 5; k++) {
            fence_regs(acc[k]);
            if (a == 0) {
              acc[k][25] += se[k * 128];
              acc[k][27] += se[k * 128 + 8];
            }
            if (k == 4 && tr == 15 && wg == 1) {
#pragma unroll
              for (int i = 16; i < 28; i++)
                if (8 * (i >> 2) + (i & 1) + 2 * a >= LOUT - (NT - 1) * MT) acc[k][i] = 0.f;
            }
#pragma unroll
            for (int i = 0; i < 28; i++) {
              q1[i & 3] += acc[k][i];
              q2[i & 3] = fmaf(acc[k][i], acc[k][i], q2[i & 3]);
            }
            fence_regs(q1);
            fence_regs(q2);
          }
        }
      }
      float s1[2] = {q1[0] + q1[1], q1[2] + q1[3]}, s2[2] = {q2[0] + q2[1], q2[2] + q2[3]};
#pragma unroll
      for (int i = 0; i < 2; i++) {
#pragma unroll
        for (int o = 1; o < 4; o <<= 1) {
          s1[i] += __shfl_xor_sync(0xffffffffu, s1[i], o);
          s2[i] += __shfl_xor_sync(0xffffffffu, s2[i], o);
        }
      }
      if (a == 0) {
        s_red[wg * 64 + d0] = make_float2(s1[0], s2[0]);
        s_red[wg * 64 + d0 + 8] = make_float2(s1[1], s2[1]);
      }
      asm volatile("bar.sync 3, 256;" ::: "memory");
      if (tid == 0) PROF_T(6 + 3 * hf);
      unsigned long long* part = g_part + ((hf * 2 + b) * 4 + dq) * 1024;
      if (tid < 64) {
        const float2 p0 = s_red[tid], p1 = s_red[64 + tid];
        const float x1 = p0.x + p1.x, x2 = p0.y + p1.y;
        const unsigned long long v = ((unsigned long long)(__float_as_uint(x2) & 0x7fffffffu) << 32) | __float_as_uint(x1);
        asm volatile("st.relaxed.gpu.global.u64 [%0], %1;" ::"l"(part + tr * 64 + tid), "l"(v) : "memory");
      }
      {
        const unsigned long long* q = part + (tid >> 6) * 256 + (tid & 63);
        unsigned long long v[4];
        poll64x4(q, v);
        float x1 = 0.f, x2 = 0.f;
#pragma unroll
        for (int i = 0; i < 4; i++) {
          x1 += __uint_as_float((uint32_t)v[i]);
          x2 += __uint_as_float((uint32_t)(v[i] >> 32));
        }
        s_red[128 + tid] = make_float2(x1, x2);
      }
      asm volatile("bar.sync 3, 256;" ::: "memory");
      if (tid == 0) PROF_T(7 + 3 * hf);
#pragma unroll
      for (int i = 0; i < 2; i++) {
        const float2 q0 = s_red[128 + d0 + 8 * i], q1 = s_red[192 + d0 + 8 * i], q2 = s_red[256 + d0 + 8 * i], q3 = s_red[320 + d0 + 8 * i];
        const float mu = ((q0.x + q1.x) + (q2.x + q3.x)) * (1.f / LOUT);
        const float var = fmaxf(((q0.y + q1.y) + (q2.y + q3.y)) * (1.f / LOUT) - mu * mu, 0.f);
        const __nv_bfloat16* gb = (const __nv_bfloat16*)(smem_raw + OFF_GB + hf * 256) + d0 + 8 * i;
        s1[i] = 0.5f * __bfloat162float(gb[0]) * rsqrtf(var + 1e-5f);
        s2[i] = 0.5f * __bfloat162float(gb[64]) - mu * s1[i];
      }
#pragma unroll
      for (int k = 0; k < 5; k++) {
        float hz[28];
#pragma unroll
        for (int i = 0; i < 28; i++) hz[i] = fmaf(acc[k][i], s1[(i >> 1) & 1], s2[(i >> 1) & 1]);
        gelu_store(hz, base + oad + k * 16384 + (k == 4 ? last : 0));
        float z;
        asm volatile("ld.volatile.shared.f32 %0, [%1];" : "=f"(z) : "r"(sb + OFF_F + 55 * 128) : "memory");
        s2[0] += z;
        s2[1] += z;
        __syncwarp();
        if (lane == 0) mbar_arrive(bar + B_OUT + 8 * (wg * 5 + k));
      }
      if (tid == 0) PROF_T(8 + 3 * hf);
    }
    asm volatile("barrier.cluster.wait.aligned;" ::: "memory");
  }
}

typedef CUresult (*EncFn)(CUtensorMap*, CUtensorMapDataType, cuuint32_t, void*, const cuuint64_t*, const cuuint64_t*, const cuuint32_t*,
                          const cuuint32_t*, CUtensorMapInterleave, CUtensorMapSwizzle, CUtensorMapL2promotion, CUtensorMapFloatOOBfill);

void encode(EncFn fn, CUtensorMap* m, int rank, void* base, const cuuint64_t* dims, const cuuint64_t* strides, const cuuint32_t* box,
            CUtensorMapL2promotion promo) {
  cuuint32_t es[5] = {1, 1, 1, 1, 1};
  fn(m, CU_TENSOR_MAP_DATA_TYPE_BFLOAT16, rank, base, dims, strides, box, es, CU_TENSOR_MAP_INTERLEAVE_NONE, CU_TENSOR_MAP_SWIZZLE_128B, promo,
     CU_TENSOR_MAP_FLOAT_OOB_FILL_NONE);
}

}

extern "C" void kernel_launch(void* const* d_in, const int* in_sizes, int n_in, void* d_out, int out_size) {
  (void)in_sizes; (void)n_in; (void)out_size;
  const __nv_bfloat16* x = (const __nv_bfloat16*)d_in[0];
  const __nv_bfloat16* w = (const __nv_bfloat16*)d_in[1];
  const __nv_bfloat16* gamma = (const __nv_bfloat16*)d_in[2];
  const __nv_bfloat16* beta = (const __nv_bfloat16*)d_in[3];
  void* fnp = nullptr;
  cudaDriverEntryPointQueryResult qr;
  cudaGetDriverEntryPoint("cuTensorMapEncodeTiled", &fnp, cudaEnableDefault, &qr);
  EncFn fn = (EncFn)fnp;
  void *cptr = nullptr, *fptr = nullptr, *xptr = nullptr, *wptr = nullptr, *yptr = nullptr;
  cudaGetSymbolAddress(&cptr, g_ctr);
  cudaGetSymbolAddress(&fptr, g_Fimg);
  cudaGetSymbolAddress(&xptr, g_X);
  cudaGetSymbolAddress(&wptr, g_W);
  cudaGetSymbolAddress(&yptr, g_Y);
  xptr = (void*)(((uintptr_t)xptr + (1u << 21) - 1) & ~(uintptr_t)((1u << 21) - 1));
  const CUtensorMapL2promotion P0 = CU_TENSOR_MAP_L2_PROMOTION_NONE, P128 = CU_TENSOR_MAP_L2_PROMOTION_L2_128B;
  Maps m;
  {
    cuuint64_t d[3] = {1024, 8000, 2}, s[2] = {2048, 8000ull * 2048};
    cuuint32_t bx[3] = {64, 64, 1};
    encode(fn, &m.x, 3, (void*)x, d, s, bx, P128);
  }
  for (int ph = 0; ph < 2; ph++) {
    cuuint64_t d[3] = {64, (cuuint64_t)(16 - ph), 4096}, s[2] = {2ull * 262144 * 2, 128};
    cuuint32_t bx[3] = {64, 16, 1};
    encode(fn, ph ? &m.wo : &m.we, 3, (void*)(w + (size_t)ph * 262144), d, s, bx, P128);
  }
  for (int par = 0; par < 2; par++) {
    cuuint64_t d[5] = {(cuuint64_t)XPAGES << 20, 2, 4, 2, 2}, s[4] = {par ? 0x1000u : 0x3000u, 1u << 14, 1u << 18, 1u << 20};
    cuuint32_t bx[5] = {64, 2, 4, 2, 2};
    encode(fn, &m.xst[par], 5, xptr, d, s, bx, P0);
  }
  {
    cuuint64_t d[4] = {64, 32, 2, (cuuint64_t)WR * WCHUNK / 128}, s[3] = {4ull * WBLK, 4096, 128};
    cuuint32_t bx[4] = {64, 32, 2, 1};
    encode(fn, &m.wst, 4, wptr, d, s, bx, P0);
  }
  for (int p = 0; p < 2; p++) {
    void* base = p ? wptr : yptr;
    cuuint64_t d[4] = {64, NT, 64, 8}, s[3] = {8192, 128, (cuuint64_t)NT * 8192};
    cuuint32_t bx[4] = {64, 32, 2, 1};
    encode(fn, &m.yst[p], 4, base, d, s, bx, P0);
    cuuint64_t d2[2] = {64, 8ull * NT * 64}, s2[1] = {128};
    cuuint32_t bx2[2] = {64, 128};
    encode(fn, &m.yld[p], 2, base, d2, s2, bx2, P128);
  }
  {
    cuuint64_t d[3] = {512, LOUT, 2}, s[2] = {1024, (cuuint64_t)LOUT * 1024};
    cuuint32_t bx[3] = {64, MT, 1};
    encode(fn, &m.out, 3, d_out, d, s, bx, P0);
  }
  for (int q = 0; q < 2; q++) {
    cuuint64_t d[3] = {512, (cuuint64_t)(NT - q), 2}, s[2] = {MT * 2048, 8000ull * 2048};
    cuuint32_t bx[3] = {64, NT, 1};
    encode(fn, &m.xe[q], 3, (void*)(x + q * 64 * 1024), d, s, bx, P128);
  }
  {
    cuuint64_t d[2] = {512, 512}, s[1] = {1024};
    cuuint32_t bx[2] = {64, 64};
    encode(fn, &m.w30, 2, (void*)(w + 30 * 262144), d, s, bx, P128);
  }
  cudaFuncSetAttribute(k1_main, cudaFuncAttributeMaxDynamicSharedMemorySize, SMEM_BYTES);
  k1_main<<<132, 512, SMEM_BYTES>>>((uint8_t*)xptr, fptr, (unsigned*)cptr, gamma, beta, m);
}
```

```cpp
#include <cuda_runtime.h>
#include <cuda_bf16.h>
#include <cuda.h>
#include <stdint.h>

namespace {

constexpr int LOUT = 7985;
constexpr int MT = 50;
constexpr int NT = 160;
constexpr int XBLK = NT * 128;
constexpr int WBLK = 16384;
constexpr int LW = 4;
constexpr int WR = 5;
constexpr int WCHUNK = 32 * 4 * WBLK;
constexpr int XPAGES = 20;
constexpr int NFL = 2;
constexpr int XKEEP = 9;
constexpr int YSTEP = 1;
constexpr int YFLUSH = 17 + LW + 3 * YSTEP;

__device__ __align__(1024) uint8_t g_X[(XPAGES + 2) << 21];
__device__ __align__(1024) uint8_t g_W[(size_t)WR * WCHUNK];
__device__ __align__(1024) uint8_t g_Y[8ull * NT * 8192];
__device__ __align__(128) float g_E[16 * NT * 64];
constexpr int CTR_OFF = (XPAGES << 21) + 0x100000, PART_OFF = CTR_OFF + 0x40000;
constexpr int C_FLAG = 0, C_LOADED = 128, C_Y = 256, C_E = 258, C_REG = 259, C_EXIT = 260, C_SIDE = 32;
__device__ __forceinline__ unsigned long long* part_ptr(uint8_t* xbuf, int side, int hf, int dq, int tr) {
  return (unsigned long long*)(xbuf + PART_OFF + ((hf * 4 + dq) * 2 + (tr >> 3)) * 8192 + ((side ^ hf ^ (tr >> 3)) << 12) + (tr & 7) * 512);
}
#define PROF_T(i)
#define PROF_C(i)
#define PROF_V(i, v)
#define PROF_W(acc, stmt) stmt

__device__ __align__(128) const uint32_t g_Fimg[2048] = {
 0x3f803f80,0x3f7d3f7f,0x3f783f7b,0x3f713f75,0x3f673f6d,0x3f5c3f62,0x3f4e3f55,0x3f3e3f46,0x3f2c3f35,0x3f183f22,0x3f043f0e,0x3edb3ef1,0x3eac3ec4,0x3e793e95,0x3e163e48,0x3d493dc9,
 0xbd490000,0xbe16bdc9,0xbe79be48,0xbeacbe95,0xbedbbec4,0xbf04bef1,0xbf18bf0e,0xbf2cbf22,0xbf3ebf35,0xbf4ebf46,0xbf5cbf55,0xbf67bf62,0xbf71bf6d,0xbf78bf75,0xbf7dbf7b,0xbf80bf7f,
 0x3e793ec4,0xbd493dc9,0xbeacbe48,0xbf18bef1,0x3f7d3f80,0x3f673f75,0x3f3e3f55,0x3f043f22,0xbf5cbf6d,0xbf2cbf46,0xbedbbf0e,0xbe16be95,0xbf4ebf35,0xbf71bf62,0xbf80bf7b,0xbf78bf7f,
 0x3f783f6d,0x3f803f7f,0x3f713f7b,0x3f4e3f62,0x3e160000,0x3edb3e95,0x3f2c3f0e,0x3f5c3f46,0xbf04bec4,0xbf3ebf22,0xbf67bf55,0xbf7dbf75,0x3f183f35,0x3eac3ef1,0x3d493e48,0xbe79bdc9,
 0xbf04bf35,0xbd49be95,0x3edb3e48,0x3f4e3f22,0x3f7d3f6d,0x3f713f7f,0x3f2c3f55,0x3e793ef1,0x3f783f80,0x3f3e3f62,0x3eac3f0e,0xbe163dc9,0xbf18bec4,0xbf67bf46,0xbf80bf7b,0xbf5cbf75,
 0x3f5c3f35,0x3f803f75,0x3f673f7b,0x3f183f46,0x3e163ec4,0xbeacbdc9,0xbf3ebf0e,0xbf78bf62,0xbe790000,0xbf2cbef1,0xbf71bf55,0xbf7dbf7f,0xbf4ebf6d,0xbedbbf22,0x3d49be48,0x3f043e95,
 0xbf2cbec4,0xbf7dbf62,0xbf5cbf7b,0xbeacbf22,0x3f673f35,0x3f783f7f,0x3f183f55,0xbd493e95,0xbf80bf6d,0xbf4ebf75,0xbe79bf0e,0x3edb3dc9,0x3f713f80,0x3f043f46,0xbe163e48,0xbf3ebef1,
 0x3f3e3f6d,0x3e163ef1,0xbf04be48,0xbf71bf46,0xbedbbf35,0x3e79bdc9,0x3f4e3f0e,0x3f803f75,0x3d493ec4,0xbf18be95,0xbf78bf55,0xbf67bf7f,0x3eac0000,0x3f5c3f22,0x3f7d3f7b,0x3f2c3f62,
 0xbedb0000,0xbf78bf46,0xbf4ebf7b,0xbd49bef1,0x3f3e3ec4,0x3f7d3f75,0x3f043f55,0xbeac3dc9,0xbf71bf35,0xbf5cbf7f,0xbe16bf0e,0x3f2c3e95,0x3f803f6d,0x3f183f62,0xbe793e48,0xbf67bf22,
 0x3f673f80,0x3e793f22,0xbf18be48,0xbf80bf62,0xbf2cbf6d,0x3e16be95,0x3f5c3f0e,0x3f713f7f,0x3eac3f35,0xbf04bdc9,0xbf7dbf55,0xbf3ebf75,0x3d49bec4,0x3f4e3ef1,0x3f783f7b,0x3edb3f46,
 0xbf7dbf6d,0xbeacbf46,0x3f2c3e48,0x3f783f75,0x3f040000,0x3f803f62,0x3edb3f55,0xbf18bdc9,0x3f4e3ec4,0x3f673f7f,0x3d493f0e,0xbf5cbef1,0x3e793f35,0xbf3ebe95,0xbf71bf7b,0xbe16bf22,
 0x3e16bec4,0x3f713f22,0x3f3e3f7b,0xbe793e95,0x3f5c3f80,0xbd493ef1,0xbf67bf0e,0xbf4ebf7f,0x3f183f6d,0xbedb3dc9,0xbf80bf55,0xbf04bf62,0xbf78bf35,0xbf2cbf75,0x3eacbe48,0x3f7d3f46,
 0x3f7d3f35,0x3edb3f62,0xbf3ebe48,0xbf5cbf7f,0x3e79bec4,0x3f803f46,0x3eac3f55,0xbf4ebe95,0xbf180000,0xbf71bf75,0x3d49bf0e,0x3f783f22,0x3f043f6d,0xbf2cbdc9,0xbf67bf7b,0x3e16bef1,
 0xbe16bf35,0x3f673ef1,0x3f2c3f7b,0xbf043dc9,0xbf78bf6d,0xbd49bf22,0x3f713f0e,0x3f183f75,0x3f4e3f80,0xbeac3e95,0xbf80bf55,0xbe79bf46,0x3f5c3ec4,0x3f3e3f7f,0xbedb3e48,0xbf7dbf62,
 0xbedbbf6d,0x3f5c3e95,0x3f183f7b,0xbf3ebdc9,0xbd49bf35,0x3f7d3f22,0x3e793f55,0xbf71bef1,0x3eacbec4,0x3f783f62,0xbe163f0e,0xbf80bf46,0x3f2c0000,0x3f4e3f7f,0xbf043e48,0xbf67bf75,
 0x3f673ec4,0x3f043f75,0xbf4ebe48,0xbf2cbf7f,0x3f803f35,0x3e163f46,0xbf78bf0e,0xbeacbf62,0x3f713f6d,0xbe793ef1,0xbf7dbf55,0x3d49bf22,0x3f3e3f80,0xbf183dc9,0xbf5cbf7b,0x3edbbe95,
 0xbd490000,0xbe16bdc9,0xbe79be48,0xbeacbe95,0xbedbbec4,0xbf04bef1,0xbf18bf0e,0xbf2cbf22,0xbf3ebf35,0xbf4ebf46,0xbf5cbf55,0xbf67bf62,0xbf71bf6d,0xbf78bf75,0xbf7dbf7b,0xbf80bf7f,
 0xbf80bf80,0xbf7dbf7f,0xbf78bf7b,0xbf71bf75,0xbf67bf6d,0xbf5cbf62,0xbf4ebf55,0xbf3ebf46,0xbf2cbf35,0xbf18bf22,0xbf04bf0e,0xbedbbef1,0xbeacbec4,0xbe79be95,0xbe16be48,0xbd49bdc9,
 0xbf78bf6d,0xbf80bf7f,0xbf71bf7b,0xbf4ebf62,0xbe160000,0xbedbbe95,0xbf2cbf0e,0xbf5cbf46,0x3f043ec4,0x3f3e3f22,0x3f673f55,0x3f7d3f75,0xbf18bf35,0xbeacbef1,0xbd49be48,0x3e793dc9,
 0x3e793ec4,0xbd493dc9,0xbeacbe48,0xbf18bef1,0x3f7d3f80,0x3f673f75,0x3f3e3f55,0x3f043f22,0xbf5cbf6d,0xbf2cbf46,0xbedbbf0e,0xbe16be95,0xbf4ebf35,0xbf71bf62,0xbf80bf7b,0xbf78bf7f,
 0x3f5c3f35,0x3f803f75,0x3f673f7b,0x3f183f46,0x3e163ec4,0xbeacbdc9,0xbf3ebf0e,0xbf78bf62,0xbe790000,0xbf2cbef1,0xbf71bf55,0xbf7dbf7f,0xbf4ebf6d,0xbedbbf22,0x3d49be48,0x3f043e95,
 0x3f043f35,0x3d493e95,0xbedbbe48,0xbf4ebf22,0xbf7dbf6d,0xbf71bf7f,0xbf2cbf55,0xbe79bef1,0xbf78bf80,0xbf3ebf62,0xbeacbf0e,0x3e16bdc9,0x3f183ec4,0x3f673f46,0x3f803f7b,0x3f5c3f75,
 0xbf3ebf6d,0xbe16bef1,0x3f043e48,0x3f713f46,0x3edb3f35,0xbe793dc9,0xbf4ebf0e,0xbf80bf75,0xbd49bec4,0x3f183e95,0x3f783f55,0x3f673f7f,0xbeac0000,0xbf5cbf22,0xbf7dbf7b,0xbf2cbf62,
 0xbf2cbec4,0xbf7dbf62,0xbf5cbf7b,0xbeacbf22,0x3f673f35,0x3f783f7f,0x3f183f55,0xbd493e95,0xbf80bf6d,0xbf4ebf75,0xbe79bf0e,0x3edb3dc9,0x3f713f80,0x3f043f46,0xbe163e48,0xbf3ebef1,
 0xbf67bf80,0xbe79bf22,0x3f183e48,0x3f803f62,0x3f2c3f6d,0xbe163e95,0xbf5cbf0e,0xbf71bf7f,0xbeacbf35,0x3f043dc9,0x3f7d3f55,0x3f3e3f75,0xbd493ec4,0xbf4ebef1,0xbf78bf7b,0xbedbbf46,
 0xbedb0000,0xbf78bf46,0xbf4ebf7b,0xbd49bef1,0x3f3e3ec4,0x3f7d3f75,0x3f043f55,0xbeac3dc9,0xbf71bf35,0xbf5cbf7f,0xbe16bf0e,0x3f2c3e95,0x3f803f6d,0x3f183f62,0xbe793e48,0xbf67bf22,
 0x3e16bec4,0x3f713f22,0x3f3e3f7b,0xbe793e95,0x3f5c3f80,0xbd493ef1,0xbf67bf0e,0xbf4ebf7f,0x3f183f6d,0xbedb3dc9,0xbf80bf55,0xbf04bf62,0xbf78bf35,0xbf2cbf75,0x3eacbe48,0x3f7d3f46,
 0x3f7d3f6d,0x3eac3f46,0xbf2cbe48,0xbf78bf75,0xbf040000,0xbf80bf62,0xbedbbf55,0x3f183dc9,0xbf4ebec4,0xbf67bf7f,0xbd49bf0e,0x3f5c3ef1,0xbe79bf35,0x3f3e3e95,0x3f713f7b,0x3e163f22,
 0x3e163f35,0xbf67bef1,0xbf2cbf7b,0x3f04bdc9,0x3f783f6d,0x3d493f22,0xbf71bf0e,0xbf18bf75,0xbf4ebf80,0x3eacbe95,0x3f803f55,0x3e793f46,0xbf5cbec4,0xbf3ebf7f,0x3edbbe48,0x3f7d3f62,
 0x3f7d3f35,0x3edb3f62,0xbf3ebe48,0xbf5cbf7f,0x3e79bec4,0x3f803f46,0x3eac3f55,0xbf4ebe95,0xbf180000,0xbf71bf75,0x3d49bf0e,0x3f783f22,0x3f043f6d,0xbf2cbdc9,0xbf67bf7b,0x3e16bef1,
 0x3f673ec4,0x3f043f75,0xbf4ebe48,0xbf2cbf7f,0x3f803f35,0x3e163f46,0xbf78bf0e,0xbeacbf62,0x3f713f6d,0xbe793ef1,0xbf7dbf55,0x3d49bf22,0x3f3e3f80,0xbf183dc9,0xbf5cbf7b,0x3edbbe95,
 0x3edb3f6d,0xbf5cbe95,0xbf18bf7b,0x3f3e3dc9,0x3d493f35,0xbf7dbf22,0xbe79bf55,0x3f713ef1,0xbeac3ec4,0xbf78bf62,0x3e16bf0e,0x3f803f46,0xbf2c0000,0xbf4ebf7f,0x3f04be48,0x3f673f75,
 0x3f2c3f80,0xbf4ebdc9,0xbf04bf7b,0x3f673e95,0x3eac3f6d,0xbf78bef1,0xbe16bf55,0x3f803f22,0xbd493f35,0xbf7dbf46,0x3e79bf0e,0x3f713f62,0xbedb3ec4,0xbf5cbf75,0x3f18be48,0x3f3e3f7f,
 0xbf3e0000,0xbf18bf7f,0x3f5c3e48,0x3edb3f75,0xbf71bec4,0xbe79bf62,0x3f7d3f0e,0x3d493f46,0xbf80bf35,0x3e16bf22,0x3f783f55,0xbeac3ef1,0xbf67bf6d,0x3f04be95,0x3f4e3f7b,0xbf2c3dc9,
 0xbf043ec4,0xbf2cbf7f,0x3f673e48,0x3e163f62,0x3f183f80,0xbf71be95,0xbd49bf55,0x3f783f46,0xbe79bf6d,0x3f803f22,0xbeac3f0e,0xbf4ebf75,0xbf7dbf35,0x3edbbef1,0x3f3e3f7b,0xbf5cbdc9,
 0x3f5c3f6d,0xbf3e3dc9,0xbedbbf7b,0x3f7d3ef1,0x3f4e0000,0x3eac3f75,0xbf80bf0e,0x3e79bf22,0xbf78bec4,0x3d49bf46,0x3f713f55,0xbf183e95,0xbe163f35,0xbf67bf62,0x3f2cbe48,0x3f043f7f,
 0x3e79bf35,0x3f3e3f75,0xbf71be48,0x3e16bf46,0x3f4e3f6d,0xbf67bdc9,0x3d49bf55,0x3f5c3f62,0x3f043f80,0xbf80bef1,0x3edbbf0e,0x3f183f7f,0xbf7dbec4,0x3eacbf22,0x3f2c3f7b,0xbf78be95,
 0x3f783f35,0xbf2c3e95,0xbeacbf7b,0x3f7d3f22,0xbf183ec4,0xbedbbf7f,0x3f803f0e,0xbf043ef1,0xbf5c0000,0xbd49bf62,0x3f673f55,0xbf4e3dc9,0xbe16bf6d,0x3f713f46,0xbf3e3e48,0xbe79bf75,
 0xbf80bec4,0x3f18bef1,0x3e793f7b,0xbf67bf46,0x3f713f35,0xbf5c3dc9,0x3e16bf55,0x3f2c3f75,0xbf3ebf6d,0x3f7d3e95,0xbf043f0e,0xbeacbf7f,0x3edb3f80,0xbf78bf22,0x3f4ebe48,0xbd493f62,
 0x3d493f6d,0xbf4ebf62,0x3f783e48,0xbedb3f22,0x3eacbf35,0x3f043f7f,0xbf7dbf0e,0x3f3ebe95,0xbf2c3ec4,0xbe16bf75,0x3f5c3f55,0xbf71bdc9,0x3f670000,0xbe793f46,0xbf18bf7b,0x3f803ef1,
 0xbf710000,0x3f04bf22,0x3e163f7b,0xbf3ebf62,0x3f803ec4,0xbf4e3e95,0x3e79bf55,0x3edb3f7f,0xbf67bf35,0x3f783dc9,0xbf183f0e,0xbd49bf75,0x3f2c3f6d,0xbf7dbef1,0x3f5cbe48,0xbeac3f46,
 0x3eac3f80,0xbf5cbf46,0x3f7d3e48,0xbf2c3ef1,0x3d49bf6d,0x3f183f75,0xbf78bf0e,0x3f67bdc9,0xbedb3f35,0xbe79bf7f,0x3f4e3f55,0xbf80be95,0x3f3ebec4,0xbe163f62,0xbf04bf7b,0x3f713f22,
 0xbf18bf6d,0x3f673f22,0xbf80be48,0x3f5cbe95,0x3f780000,0xbf3e3ef1,0x3eacbf55,0x3e163f7f,0x3f7d3ec4,0xbf713dc9,0x3f2cbf0e,0xbe793f62,0xbf043f35,0x3d49bf75,0x3edb3f7b,0xbf4ebf46,
 0x3f4ebec4,0xbedb3f46,0xbd49bf7b,0x3f043f75,0x3e793f80,0xbf2cbf62,0x3f713f0e,0xbf7dbdc9,0xbe163f6d,0xbeacbf7f,0x3f3e3f55,0xbf78bef1,0xbf5cbf35,0x3f803e95,0xbf673e48,0x3f18bf22,
 0x3f4e3f35,0xbf71bef1,0x3f803e48,0xbf783dc9,0x3f5cbec4,0xbf2c3f22,0x3edbbf55,0xbe163f75,0xbf7d0000,0x3f67be95,0xbf3e3f0e,0x3f04bf46,0xbe793f6d,0xbd49bf7f,0x3eac3f7b,0xbf18bf62,
 0x3f18bf35,0xbeac3f62,0x3d49bf7b,0x3e793f7f,0xbf04bf6d,0x3f3e3f46,0xbf67bf0e,0x3f7d3e95,0x3e163f80,0xbedbbf75,0x3f2c3f55,0xbf5cbf22,0x3f783ec4,0xbf80bdc9,0x3f71be48,0xbf4e3ef1,
 0x3eacbf6d,0xbe793f75,0x3e16bf7b,0xbd493f7f,0x3f2cbf35,0xbf183f46,0x3f04bf55,0xbedb3f62,0x3f67bec4,0xbf5c3ef1,0x3f4ebf0e,0xbf3e3f22,0x3f800000,0xbf7d3dc9,0x3f78be48,0xbf713e95,
 0x3f713ec4,0xbf78be95,0x3f7d3e48,0xbf80bdc9,0x3f3e3f35,0xbf4ebf22,0x3f5c3f0e,0xbf67bef1,0x3edb3f6d,0xbf04bf62,0x3f183f55,0xbf2cbf46,0x3d493f80,0xbe16bf7f,0x3e793f7b,0xbeacbf75,
 0xbf3e0000,0xbf18bf7f,0x3f5c3e48,0x3edb3f75,0xbf71bec4,0xbe79bf62,0x3f7d3f0e,0x3d493f46,0xbf80bf35,0x3e16bf22,0x3f783f55,0xbeac3ef1,0xbf67bf6d,0x3f04be95,0x3f4e3f7b,0xbf2c3dc9,
 0xbf2cbf80,0x3f4e3dc9,0x3f043f7b,0xbf67be95,0xbeacbf6d,0x3f783ef1,0x3e163f55,0xbf80bf22,0x3d49bf35,0x3f7d3f46,0xbe793f0e,0xbf71bf62,0x3edbbec4,0x3f5c3f75,0xbf183e48,0xbf3ebf7f,
 0xbf5cbf6d,0x3f3ebdc9,0x3edb3f7b,0xbf7dbef1,0xbf4e0000,0xbeacbf75,0x3f803f0e,0xbe793f22,0x3f783ec4,0xbd493f46,0xbf71bf55,0x3f18be95,0x3e16bf35,0x3f673f62,0xbf2c3e48,0xbf04bf7f,
 0xbf043ec4,0xbf2cbf7f,0x3f673e48,0x3e163f62,0x3f183f80,0xbf71be95,0xbd49bf55,0x3f783f46,0xbe79bf6d,0x3f803f22,0xbeac3f0e,0xbf4ebf75,0xbf7dbf35,0x3edbbef1,0x3f3e3f7b,0xbf5cbdc9,
 0x3f783f35,0xbf2c3e95,0xbeacbf7b,0x3f7d3f22,0xbf183ec4,0xbedbbf7f,0x3f803f0e,0xbf043ef1,0xbf5c0000,0xbd49bf62,0x3f673f55,0xbf4e3dc9,0xbe16bf6d,0x3f713f46,0xbf3e3e48,0xbe79bf75,
 0xbe793f35,0xbf3ebf75,0x3f713e48,0xbe163f46,0xbf4ebf6d,0x3f673dc9,0xbd493f55,0xbf5cbf62,0xbf04bf80,0x3f803ef1,0xbedb3f0e,0xbf18bf7f,0x3f7d3ec4,0xbeac3f22,0xbf2cbf7b,0x3f783e95,
 0xbd49bf6d,0x3f4e3f62,0xbf78be48,0x3edbbf22,0xbeac3f35,0xbf04bf7f,0x3f7d3f0e,0xbf3e3e95,0x3f2cbec4,0x3e163f75,0xbf5cbf55,0x3f713dc9,0xbf670000,0x3e79bf46,0x3f183f7b,0xbf80bef1,
 0xbf80bec4,0x3f18bef1,0x3e793f7b,0xbf67bf46,0x3f713f35,0xbf5c3dc9,0x3e16bf55,0x3f2c3f75,0xbf3ebf6d,0x3f7d3e95,0xbf043f0e,0xbeacbf7f,0x3edb3f80,0xbf78bf22,0x3f4ebe48,0xbd493f62,
 0xbeacbf80,0x3f5c3f46,0xbf7dbe48,0x3f2cbef1,0xbd493f6d,0xbf18bf75,0x3f783f0e,0xbf673dc9,0x3edbbf35,0x3e793f7f,0xbf4ebf55,0x3f803e95,0xbf3e3ec4,0x3e16bf62,0x3f043f7b,0xbf71bf22,
 0xbf710000,0x3f04bf22,0x3e163f7b,0xbf3ebf62,0x3f803ec4,0xbf4e3e95,0x3e79bf55,0x3edb3f7f,0xbf67bf35,0x3f783dc9,0xbf183f0e,0xbd49bf75,0x3f2c3f6d,0xbf7dbef1,0x3f5cbe48,0xbeac3f46,
 0x3f4ebec4,0xbedb3f46,0xbd49bf7b,0x3f043f75,0x3e793f80,0xbf2cbf62,0x3f713f0e,0xbf7dbdc9,0xbe163f6d,0xbeacbf7f,0x3f3e3f55,0xbf78bef1,0xbf5cbf35,0x3f803e95,0xbf673e48,0x3f18bf22,
 0x3f183f6d,0xbf67bf22,0x3f803e48,0xbf5c3e95,0xbf780000,0x3f3ebef1,0xbeac3f55,0xbe16bf7f,0xbf7dbec4,0x3f71bdc9,0xbf2c3f0e,0x3e79bf62,0x3f04bf35,0xbd493f75,0xbedbbf7b,0x3f4e3f46,
 0xbf183f35,0x3eacbf62,0xbd493f7b,0xbe79bf7f,0x3f043f6d,0xbf3ebf46,0x3f673f0e,0xbf7dbe95,0xbe16bf80,0x3edb3f75,0xbf2cbf55,0x3f5c3f22,0xbf78bec4,0x3f803dc9,0xbf713e48,0x3f4ebef1,
 0x3f4e3f35,0xbf71bef1,0x3f803e48,0xbf783dc9,0x3f5cbec4,0xbf2c3f22,0x3edbbf55,0xbe163f75,0xbf7d0000,0x3f67be95,0xbf3e3f0e,0x3f04bf46,0xbe793f6d,0xbd49bf7f,0x3eac3f7b,0xbf18bf62,
 0x3f713ec4,0xbf78be95,0x3f7d3e48,0xbf80bdc9,0x3f3e3f35,0xbf4ebf22,0x3f5c3f0e,0xbf67bef1,0x3edb3f6d,0xbf04bf62,0x3f183f55,0xbf2cbf46,0x3d493f80,0xbe16bf7f,0x3e793f7b,0xbeacbf75,
 0xbeac3f6d,0x3e79bf75,0xbe163f7b,0x3d49bf7f,0xbf2c3f35,0x3f18bf46,0xbf043f55,0x3edbbf62,0xbf673ec4,0x3f5cbef1,0xbf4e3f0e,0x3f3ebf22,0xbf800000,0x3f7dbdc9,0xbf783e48,0x3f71be95,
 0xbd493f80,0x3e16bf7f,0xbe793f7b,0x3eacbf75,0xbedb3f6d,0x3f04bf62,0xbf183f55,0x3f2cbf46,0xbf3e3f35,0x3f4ebf22,0xbf5c3f0e,0x3f67bef1,0xbf713ec4,0x3f78be95,0xbf7d3e48,0x3f80bdc9,
 0xbf800000,0x3f7d3dc9,0xbf78be48,0x3f713e95,0xbf67bec4,0x3f5c3ef1,0xbf4ebf0e,0x3f3e3f22,0xbf2cbf35,0x3f183f46,0xbf04bf55,0x3edb3f62,0xbeacbf6d,0x3e793f75,0xbe16bf7b,0x3d493f7f,
 0xbf783ec4,0x3f80bdc9,0xbf71be48,0x3f4e3ef1,0xbe163f80,0x3edbbf75,0xbf2c3f55,0x3f5cbf22,0x3f04bf6d,0xbf3e3f46,0x3f67bf0e,0xbf7d3e95,0xbf18bf35,0x3eac3f62,0xbd49bf7b,0xbe793f7f,
 0x3e793f6d,0x3d49bf7f,0xbeac3f7b,0x3f18bf62,0x3f7d0000,0xbf67be95,0x3f3e3f0e,0xbf04bf46,0xbf5cbec4,0x3f2c3f22,0xbedbbf55,0x3e163f75,0xbf4e3f35,0x3f71bef1,0xbf803e48,0x3f783dc9,
 0x3f5cbf35,0xbf803e95,0x3f673e48,0xbf18bf22,0x3e163f6d,0x3eacbf7f,0xbf3e3f55,0x3f78bef1,0xbe793f80,0x3f2cbf62,0xbf713f0e,0x3f7dbdc9,0xbf4ebec4,0x3edb3f46,0x3d49bf7b,0xbf043f75,
 0x3f043f35,0xbd49bf75,0xbedb3f7b,0x3f4ebf46,0xbf7d3ec4,0x3f713dc9,0xbf2cbf0e,0x3e793f62,0xbf780000,0x3f3e3ef1,0xbeacbf55,0xbe163f7f,0x3f18bf6d,0xbf673f22,0x3f80be48,0xbf5cbe95,
 0xbf3ebec4,0x3e163f62,0x3f04bf7b,0xbf713f22,0x3edb3f35,0x3e79bf7f,0xbf4e3f55,0x3f80be95,0xbd49bf6d,0xbf183f75,0x3f78bf0e,0xbf67bdc9,0xbeac3f80,0x3f5cbf46,0xbf7d3e48,0x3f2c3ef1,
 0xbf2c3f6d,0x3f7dbef1,0xbf5cbe48,0x3eac3f46,0x3f67bf35,0xbf783dc9,0x3f183f0e,0x3d49bf75,0xbf803ec4,0x3f4e3e95,0xbe79bf55,0xbedb3f7f,0x3f710000,0xbf04bf22,0xbe163f7b,0x3f3ebf62,
 0xbf670000,0x3e793f46,0x3f18bf7b,0xbf803ef1,0x3f2c3ec4,0x3e16bf75,0xbf5c3f55,0x3f71bdc9,0xbeacbf35,0xbf043f7f,0x3f7dbf0e,0xbf3ebe95,0xbd493f6d,0x3f4ebf62,0xbf783e48,0x3edb3f22,
 0xbedb3f80,0x3f78bf22,0xbf4ebe48,0x3d493f62,0x3f3ebf6d,0xbf7d3e95,0x3f043f0e,0x3eacbf7f,0xbf713f35,0x3f5c3dc9,0xbe16bf55,0xbf2c3f75,0x3f80bec4,0xbf18bef1,0xbe793f7b,0x3f67bf46,
 0x3e16bf6d,0xbf713f46,0x3f3e3e48,0x3e79bf75,0x3f5c0000,0x3d49bf62,0xbf673f55,0x3f4e3dc9,0x3f183ec4,0x3edbbf7f,0xbf803f0e,0x3f043ef1,0xbf783f35,0x3f2c3e95,0x3eacbf7b,0xbf7d3f22,
 0x3f7dbec4,0xbeacbf22,0xbf2c3f7b,0x3f78be95,0xbf043f80,0x3f80bef1,0xbedbbf0e,0xbf183f7f,0xbf4e3f6d,0x3f67bdc9,0xbd49bf55,0xbf5c3f62,0xbe79bf35,0xbf3e3f75,0x3f71be48,0xbe16bf46,
 0x3e163f35,0x3f67bf62,0xbf2cbe48,0xbf043f7f,0x3f78bec4,0xbd49bf46,0xbf713f55,0x3f183e95,0xbf4e0000,0xbeac3f75,0x3f80bf0e,0xbe79bf22,0xbf5c3f6d,0x3f3e3dc9,0x3edbbf7b,0xbf7d3ef1,
 0x3f7dbf35,0xbedbbef1,0xbf3e3f7b,0x3f5cbdc9,0x3e79bf6d,0xbf803f22,0x3eac3f0e,0x3f4ebf75,0xbf183f80,0x3f71be95,0x3d49bf55,0xbf783f46,0x3f043ec4,0x3f2cbf7f,0xbf673e48,0xbe163f62,
 0x3f67bf6d,0xbf04be95,0xbf4e3f7b,0x3f2c3dc9,0x3f80bf35,0xbe16bf22,0xbf783f55,0x3eac3ef1,0x3f71bec4,0x3e79bf62,0xbf7d3f0e,0xbd493f46,0x3f3e0000,0x3f18bf7f,0xbf5c3e48,0xbedb3f75,
 0x3edb3ec4,0x3f5cbf75,0xbf18be48,0xbf3e3f7f,0x3d493f35,0x3f7dbf46,0xbe79bf0e,0xbf713f62,0xbeac3f6d,0x3f78bef1,0x3e16bf55,0xbf803f22,0xbf2c3f80,0x3f4ebdc9,0x3f04bf7b,0xbf673e95,
 0xbf800000,0x3f7d3dc9,0xbf78be48,0x3f713e95,0xbf67bec4,0x3f5c3ef1,0xbf4ebf0e,0x3f3e3f22,0xbf2cbf35,0x3f183f46,0xbf04bf55,0x3edb3f62,0xbeacbf6d,0x3e793f75,0xbe16bf7b,0x3d493f7f,
 0x3d49bf80,0xbe163f7f,0x3e79bf7b,0xbeac3f75,0x3edbbf6d,0xbf043f62,0x3f18bf55,0xbf2c3f46,0x3f3ebf35,0xbf4e3f22,0x3f5cbf0e,0xbf673ef1,0x3f71bec4,0xbf783e95,0x3f7dbe48,0xbf803dc9,
 0xbe79bf6d,0xbd493f7f,0x3eacbf7b,0xbf183f62,0xbf7d0000,0x3f673e95,0xbf3ebf0e,0x3f043f46,0x3f5c3ec4,0xbf2cbf22,0x3edb3f55,0xbe16bf75,0x3f4ebf35,0xbf713ef1,0x3f80be48,0xbf78bdc9,
 0xbf783ec4,0x3f80bdc9,0xbf71be48,0x3f4e3ef1,0xbe163f80,0x3edbbf75,0xbf2c3f55,0x3f5cbf22,0x3f04bf6d,0xbf3e3f46,0x3f67bf0e,0xbf7d3e95,0xbf18bf35,0x3eac3f62,0xbd49bf7b,0xbe793f7f,
 0x3f043f35,0xbd49bf75,0xbedb3f7b,0x3f4ebf46,0xbf7d3ec4,0x3f713dc9,0xbf2cbf0e,0x3e793f62,0xbf780000,0x3f3e3ef1,0xbeacbf55,0xbe163f7f,0x3f18bf6d,0xbf673f22,0x3f80be48,0xbf5cbe95,
 0xbf5c3f35,0x3f80be95,0xbf67be48,0x3f183f22,0xbe16bf6d,0xbeac3f7f,0x3f3ebf55,0xbf783ef1,0x3e79bf80,0xbf2c3f62,0x3f71bf0e,0xbf7d3dc9,0x3f4e3ec4,0xbedbbf46,0xbd493f7b,0x3f04bf75,
 0x3f2cbf6d,0xbf7d3ef1,0x3f5c3e48,0xbeacbf46,0xbf673f35,0x3f78bdc9,0xbf18bf0e,0xbd493f75,0x3f80bec4,0xbf4ebe95,0x3e793f55,0x3edbbf7f,0xbf710000,0x3f043f22,0x3e16bf7b,0xbf3e3f62,
 0xbf3ebec4,0x3e163f62,0x3f04bf7b,0xbf713f22,0x3edb3f35,0x3e79bf7f,0xbf4e3f55,0x3f80be95,0xbd49bf6d,0xbf183f75,0x3f78bf0e,0xbf67bdc9,0xbeac3f80,0x3f5cbf46,0xbf7d3e48,0x3f2c3ef1,
 0x3edbbf80,0xbf783f22,0x3f4e3e48,0xbd49bf62,0xbf3e3f6d,0x3f7dbe95,0xbf04bf0e,0xbeac3f7f,0x3f71bf35,0xbf5cbdc9,0x3e163f55,0x3f2cbf75,0xbf803ec4,0x3f183ef1,0x3e79bf7b,0xbf673f46,
 0xbf670000,0x3e793f46,0x3f18bf7b,0xbf803ef1,0x3f2c3ec4,0x3e16bf75,0xbf5c3f55,0x3f71bdc9,0xbeacbf35,0xbf043f7f,0x3f7dbf0e,0xbf3ebe95,0xbd493f6d,0x3f4ebf62,0xbf783e48,0x3edb3f22,
 0x3f7dbec4,0xbeacbf22,0xbf2c3f7b,0x3f78be95,0xbf043f80,0x3f80bef1,0xbedbbf0e,0xbf183f7f,0xbf4e3f6d,0x3f67bdc9,0xbd49bf55,0xbf5c3f62,0xbe79bf35,0xbf3e3f75,0x3f71be48,0xbe16bf46,
 0xbe163f6d,0x3f71bf46,0xbf3ebe48,0xbe793f75,0xbf5c0000,0xbd493f62,0x3f67bf55,0xbf4ebdc9,0xbf18bec4,0xbedb3f7f,0x3f80bf0e,0xbf04bef1,0x3f78bf35,0xbf2cbe95,0xbeac3f7b,0x3f7dbf22,
 0xbf7d3f35,0x3edb3ef1,0x3f3ebf7b,0xbf5c3dc9,0xbe793f6d,0x3f80bf22,0xbeacbf0e,0xbf4e3f75,0x3f18bf80,0xbf713e95,0xbd493f55,0x3f78bf46,0xbf04bec4,0xbf2c3f7f,0x3f67be48,0x3e16bf62,
 0x3e163f35,0x3f67bf62,0xbf2cbe48,0xbf043f7f,0x3f78bec4,0xbd49bf46,0xbf713f55,0x3f183e95,0xbf4e0000,0xbeac3f75,0x3f80bf0e,0xbe79bf22,0xbf5c3f6d,0x3f3e3dc9,0x3edbbf7b,0xbf7d3ef1,
 0x3edb3ec4,0x3f5cbf75,0xbf18be48,0xbf3e3f7f,0x3d493f35,0x3f7dbf46,0xbe79bf0e,0xbf713f62,0xbeac3f6d,0x3f78bef1,0x3e16bf55,0xbf803f22,0xbf2c3f80,0x3f4ebdc9,0x3f04bf7b,0xbf673e95,
 0xbf673f6d,0x3f043e95,0x3f4ebf7b,0xbf2cbdc9,0xbf803f35,0x3e163f22,0x3f78bf55,0xbeacbef1,0xbf713ec4,0xbe793f62,0x3f7dbf0e,0x3d49bf46,0xbf3e0000,0xbf183f7f,0x3f5cbe48,0x3edbbf75,
 0xbf3e3f80,0x3f183dc9,0x3f5cbf7b,0xbedbbe95,0xbf713f6d,0x3e793ef1,0x3f7dbf55,0xbd49bf22,0xbf803f35,0xbe163f46,0x3f78bf0e,0x3eacbf62,0xbf673ec4,0xbf043f75,0x3f4ebe48,0x3f2cbf7f,
 0xbf2c0000,0xbf4e3f7f,0x3f043e48,0x3f67bf75,0xbeacbec4,0xbf783f62,0x3e163f0e,0x3f80bf46,0x3d49bf35,0xbf7d3f22,0xbe793f55,0x3f71bef1,0x3edbbf6d,0xbf5c3e95,0xbf183f7b,0x3f3ebdc9,
 0xbf5c3ec4,0xbf3e3f7f,0x3edb3e48,0x3f7dbf62,0xbf4e3f80,0x3eac3e95,0x3f80bf55,0x3e79bf46,0x3f78bf6d,0x3d49bf22,0xbf713f0e,0xbf183f75,0x3e16bf35,0xbf673ef1,0xbf2c3f7b,0x3f043dc9,
 0xbf043f6d,0x3f2cbdc9,0x3f67bf7b,0xbe16bef1,0x3f180000,0x3f71bf75,0xbd49bf0e,0xbf783f22,0xbe79bec4,0xbf803f46,0xbeac3f55,0x3f4ebe95,0xbf7d3f35,0xbedb3f62,0x3f3ebe48,0x3f5cbf7f,
 0x3f78bf35,0x3f2cbf75,0xbeacbe48,0xbf7d3f46,0xbf183f6d,0x3edb3dc9,0x3f80bf55,0x3f04bf62,0xbf5c3f80,0x3d493ef1,0x3f67bf0e,0x3f4ebf7f,0xbe16bec4,0xbf713f22,0xbf3e3f7b,0x3e793e95,
 0xbe793f35,0x3f3ebe95,0x3f71bf7b,0x3e16bf22,0xbf4e3ec4,0xbf673f7f,0xbd493f0e,0x3f5cbef1,0xbf040000,0xbf803f62,0xbedb3f55,0x3f18bdc9,0x3f7dbf6d,0x3eacbf46,0xbf2c3e48,0xbf783f75,
 0xbd49bec4,0xbf4e3ef1,0xbf783f7b,0xbedb3f46,0xbeac3f35,0x3f04bdc9,0x3f7dbf55,0x3f3ebf75,0x3f2cbf6d,0xbe16be95,0xbf5c3f0e,0xbf713f7f,0xbf673f80,0xbe793f22,0x3f18be48,0x3f80bf62,
 0xbf803f6d,0xbf183f62,0x3e793e48,0x3f67bf22,0x3f71bf35,0x3f5cbf7f,0x3e16bf0e,0xbf2c3e95,0xbf3e3ec4,0xbf7d3f75,0xbf043f55,0x3eac3dc9,0x3edb0000,0x3f78bf46,0x3f4ebf7b,0x3d49bef1,
 0xbeac0000,0xbf5c3f22,0xbf7d3f7b,0xbf2c3f62,0xbd493ec4,0x3f18be95,0x3f78bf55,0x3f67bf7f,0x3edbbf35,0xbe79bdc9,0xbf4e3f0e,0xbf803f75,0xbf3e3f6d,0xbe163ef1,0x3f04be48,0x3f71bf46,
 0xbf713f80,0xbf043f46,0x3e163e48,0x3f3ebef1,0x3f80bf6d,0x3f4ebf75,0x3e79bf0e,0xbedb3dc9,0xbf673f35,0xbf783f7f,0xbf183f55,0x3d493e95,0x3f2cbec4,0x3f7dbf62,0x3f5cbf7b,0x3eacbf22,
 0x3f4ebf6d,0x3edbbf22,0xbd49be48,0xbf043e95,0x3e790000,0x3f2cbef1,0x3f71bf55,0x3f7dbf7f,0xbe163ec4,0x3eacbdc9,0x3f3ebf0e,0x3f78bf62,0xbf5c3f35,0xbf803f75,0xbf673f7b,0xbf183f46,
 0x3f18bec4,0x3f67bf46,0x3f80bf7b,0x3f5cbf75,0xbf783f80,0xbf3e3f62,0xbeac3f0e,0x3e163dc9,0xbf7d3f6d,0xbf713f7f,0xbf2c3f55,0xbe793ef1,0x3f04bf35,0x3d49be95,0xbedb3e48,0xbf4e3f22,
 0xbf183f35,0xbeac3ef1,0xbd493e48,0x3e79bdc9,0x3f04bec4,0x3f3ebf22,0x3f67bf55,0x3f7dbf75,0xbe160000,0xbedb3e95,0xbf2c3f0e,0xbf5c3f46,0xbf783f6d,0xbf803f7f,0xbf713f7b,0xbf4e3f62,
 0x3f4ebf35,0x3f71bf62,0x3f80bf7b,0x3f78bf7f,0x3f5cbf6d,0x3f2cbf46,0x3edbbf0e,0x3e16be95,0xbf7d3f80,0xbf673f75,0xbf3e3f55,0xbf043f22,0xbe793ec4,0x3d493dc9,0x3eacbe48,0x3f18bef1,
 0x3f71bf6d,0x3f78bf75,0x3f7dbf7b,0x3f80bf7f,0x3f3ebf35,0x3f4ebf46,0x3f5cbf55,0x3f67bf62,0x3edbbec4,0x3f04bef1,0x3f18bf0e,0x3f2cbf22,0x3d490000,0x3e16bdc9,0x3e79be48,0x3eacbe95,
 0xbeac3ec4,0xbe793e95,0xbe163e48,0xbd493dc9,0xbf2c3f35,0xbf183f22,0xbf043f0e,0xbedb3ef1,0xbf673f6d,0xbf5c3f62,0xbf4e3f55,0xbf3e3f46,0xbf803f80,0xbf7d3f7f,0xbf783f7b,0xbf713f75,
 0xbf2c0000,0xbf4e3f7f,0x3f043e48,0x3f67bf75,0xbeacbec4,0xbf783f62,0x3e163f0e,0x3f80bf46,0x3d49bf35,0xbf7d3f22,0xbe793f55,0x3f71bef1,0x3edbbf6d,0xbf5c3e95,0xbf183f7b,0x3f3ebdc9,
 0x3f3ebf80,0xbf18bdc9,0xbf5c3f7b,0x3edb3e95,0x3f71bf6d,0xbe79bef1,0xbf7d3f55,0x3d493f22,0x3f80bf35,0x3e16bf46,0xbf783f0e,0xbeac3f62,0x3f67bec4,0x3f04bf75,0xbf4e3e48,0xbf2c3f7f,
 0x3f04bf6d,0xbf2c3dc9,0xbf673f7b,0x3e163ef1,0xbf180000,0xbf713f75,0x3d493f0e,0x3f78bf22,0x3e793ec4,0x3f80bf46,0x3eacbf55,0xbf4e3e95,0x3f7dbf35,0x3edbbf62,0xbf3e3e48,0xbf5c3f7f,
 0xbf5c3ec4,0xbf3e3f7f,0x3edb3e48,0x3f7dbf62,0xbf4e3f80,0x3eac3e95,0x3f80bf55,0x3e79bf46,0x3f78bf6d,0x3d49bf22,0xbf713f0e,0xbf183f75,0x3e16bf35,0xbf673ef1,0xbf2c3f7b,0x3f043dc9,
 0xbe793f35,0x3f3ebe95,0x3f71bf7b,0x3e16bf22,0xbf4e3ec4,0xbf673f7f,0xbd493f0e,0x3f5cbef1,0xbf040000,0xbf803f62,0xbedb3f55,0x3f18bdc9,0x3f7dbf6d,0x3eacbf46,0xbf2c3e48,0xbf783f75,
 0xbf783f35,0xbf2c3f75,0x3eac3e48,0x3f7dbf46,0x3f18bf6d,0xbedbbdc9,0xbf803f55,0xbf043f62,0x3f5cbf80,0xbd49bef1,0xbf673f0e,0xbf4e3f7f,0x3e163ec4,0x3f71bf22,0x3f3ebf7b,0xbe79be95,
 0x3f80bf6d,0x3f18bf62,0xbe79be48,0xbf673f22,0xbf713f35,0xbf5c3f7f,0xbe163f0e,0x3f2cbe95,0x3f3ebec4,0x3f7dbf75,0x3f04bf55,0xbeacbdc9,0xbedb0000,0xbf783f46,0xbf4e3f7b,0xbd493ef1,
 0xbd49bec4,0xbf4e3ef1,0xbf783f7b,0xbedb3f46,0xbeac3f35,0x3f04bdc9,0x3f7dbf55,0x3f3ebf75,0x3f2cbf6d,0xbe16be95,0xbf5c3f0e,0xbf713f7f,0xbf673f80,0xbe793f22,0x3f18be48,0x3f80bf62,
 0x3f71bf80,0x3f04bf46,0xbe16be48,0xbf3e3ef1,0xbf803f6d,0xbf4e3f75,0xbe793f0e,0x3edbbdc9,0x3f67bf35,0x3f78bf7f,0x3f18bf55,0xbd49be95,0xbf2c3ec4,0xbf7d3f62,0xbf5c3f7b,0xbeac3f22,
 0xbeac0000,0xbf5c3f22,0xbf7d3f7b,0xbf2c3f62,0xbd493ec4,0x3f18be95,0x3f78bf55,0x3f67bf7f,0x3edbbf35,0xbe79bdc9,0xbf4e3f0e,0xbf803f75,0xbf3e3f6d,0xbe163ef1,0x3f04be48,0x3f71bf46,
 0x3f18bec4,0x3f67bf46,0x3f80bf7b,0x3f5cbf75,0xbf783f80,0xbf3e3f62,0xbeac3f0e,0x3e163dc9,0xbf7d3f6d,0xbf713f7f,0xbf2c3f55,0xbe793ef1,0x3f04bf35,0x3d49be95,0xbedb3e48,0xbf4e3f22,
 0xbf4e3f6d,0xbedb3f22,0x3d493e48,0x3f04be95,0xbe790000,0xbf2c3ef1,0xbf713f55,0xbf7d3f7f,0x3e16bec4,0xbeac3dc9,0xbf3e3f0e,0xbf783f62,0x3f5cbf35,0x3f80bf75,0x3f67bf7b,0x3f18bf46,
 0xbf4e3f35,0xbf713f62,0xbf803f7b,0xbf783f7f,0xbf5c3f6d,0xbf2c3f46,0xbedb3f0e,0xbe163e95,0x3f7dbf80,0x3f67bf75,0x3f3ebf55,0x3f04bf22,0x3e79bec4,0xbd49bdc9,0xbeac3e48,0xbf183ef1,
 0xbf183f35,0xbeac3ef1,0xbd493e48,0x3e79bdc9,0x3f04bec4,0x3f3ebf22,0x3f67bf55,0x3f7dbf75,0xbe160000,0xbedb3e95,0xbf2c3f0e,0xbf5c3f46,0xbf783f6d,0xbf803f7f,0xbf713f7b,0xbf4e3f62,
 0xbeac3ec4,0xbe793e95,0xbe163e48,0xbd493dc9,0xbf2c3f35,0xbf183f22,0xbf043f0e,0xbedb3ef1,0xbf673f6d,0xbf5c3f62,0xbf4e3f55,0xbf3e3f46,0xbf803f80,0xbf7d3f7f,0xbf783f7b,0xbf713f75,
 0xbf713f6d,0xbf783f75,0xbf7d3f7b,0xbf803f7f,0xbf3e3f35,0xbf4e3f46,0xbf5c3f55,0xbf673f62,0xbedb3ec4,0xbf043ef1,0xbf183f0e,0xbf2c3f22,0xbd490000,0xbe163dc9,0xbe793e48,0xbeac3e95,
};
__device__ __align__(128) const uint32_t g_Gimg[1792] = {
 0x00003d00,0x00003d00,0x00003d00,0x00003d00,0x00003d00,0x00003d00,0x00003d00,0x00003d00,0x00003d00,0x00003d00,0x00003d00,0x00003d00,0x00003d00,0x00003d00,0x00003d00,0x00003d00,
 0x00003d00,0x00003d00,0x00003d00,0x00003d00,0x00003d00,0x00003d00,0x00003d00,0x00003d00,0x00003d00,0x00003d00,0x00003d00,0x00003d00,0x00003d00,0x00003d00,0x00003d00,0x00003d00,
 0xbc5b3ce7,0xbc843cdc,0xbc983cce,0xbcac3cbe,0xbac93d00,0xbb963cfd,0xbbf93cf8,0xbc2c3cf1,0xbcf13c2c,0xbcf83bf9,0xbcfd3b96,0xbd003ac9,0xbcbe3cac,0xbcce3c98,0xbcdc3c84,0xbce73c5b,
 0xbce7bc5b,0xbcdcbc84,0xbccebc98,0xbcbebcac,0xbd00bac9,0xbcfdbb96,0xbcf8bbf9,0xbcf1bc2c,0xbc2cbcf1,0xbbf9bcf8,0xbb96bcfd,0xbac9bd00,0xbcacbcbe,0xbc98bcce,0xbc84bcdc,0xbc5bbce7,
 0xbcffbb49,0xbcf5bc15,0xbce2bc71,0xbcc6bca2,0xbca2bcc6,0xbc71bce2,0xbc15bcf5,0xbb49bcff,0xbb493cff,0xbc153cf5,0xbc713ce2,0xbca23cc6,0xbcc63ca2,0xbce23c71,0xbcf53c15,0xbcff3b49,
 0x3cff3b49,0x3cf53c15,0x3ce23c71,0x3cc63ca2,0x3ca23cc6,0x3c713ce2,0x3c153cf5,0x3b493cff,0x3b49bcff,0x3c15bcf5,0x3c71bce2,0x3ca2bcc6,0x3cc6bca2,0x3ce2bc71,0x3cf5bc15,0x3cffbb49,
 0x3c84bcdc,0x3cbebcac,0x3ce7bc5b,0x3cfdbb96,0xbc98bcce,0xbc2cbcf1,0xbac9bd00,0x3bf9bcf8,0xbcf83bf9,0xbd00bac9,0xbcf1bc2c,0xbccebc98,0xbb963cfd,0xbc5b3ce7,0xbcac3cbe,0xbcdc3c84,
 0xbcdcbc84,0xbcacbcbe,0xbc5bbce7,0xbb96bcfd,0xbcce3c98,0xbcf13c2c,0xbd003ac9,0xbcf8bbf9,0x3bf93cf8,0xbac93d00,0xbc2c3cf1,0xbc983cce,0x3cfd3b96,0x3ce73c5b,0x3cbe3cac,0x3c843cdc,
 0xbbc83cfb,0xbc8e3cd5,0xbcd53c8e,0xbcfb3bc8,0xbcfbbbc8,0xbcd5bc8e,0xbc8ebcd5,0xbbc8bcfb,0x3bc8bcfb,0x3c8ebcd5,0x3cd5bc8e,0x3cfbbbc8,0x3cfb3bc8,0x3cd53c8e,0x3c8e3cd5,0x3bc83cfb,
 0xbbc83cfb,0xbc8e3cd5,0xbcd53c8e,0xbcfb3bc8,0xbcfbbbc8,0xbcd5bc8e,0xbc8ebcd5,0xbbc8bcfb,0x3bc8bcfb,0x3c8ebcd5,0x3cd5bc8e,0x3cfbbbc8,0x3cfb3bc8,0x3cd53c8e,0x3c8e3cd5,0x3bc83cfb,
 0x3c98bcce,0x3ce7bc5b,0x3d003ac9,0x3cdc3c84,0xbcf8bbf9,0xbcbebcac,0xbc2cbcf1,0x3b96bcfd,0xbcfd3b96,0xbcf1bc2c,0xbcacbcbe,0xbbf9bcf8,0x3c843cdc,0x3ac93d00,0xbc5b3ce7,0xbcce3c98,
 0xbccebc98,0xbc5bbce7,0x3ac9bd00,0x3c84bcdc,0xbbf93cf8,0xbcac3cbe,0xbcf13c2c,0xbcfdbb96,0x3b963cfd,0xbc2c3cf1,0xbcbe3cac,0xbcf83bf9,0x3cdcbc84,0x3d00bac9,0x3ce73c5b,0x3c983cce,
 0xbcf5bc15,0xbca2bcc6,0xbb49bcff,0x3c71bce2,0x3ce2bc71,0x3cff3b49,0x3cc63ca2,0x3c153cf5,0x3c15bcf5,0x3cc6bca2,0x3cffbb49,0x3ce23c71,0x3c713ce2,0xbb493cff,0xbca23cc6,0xbcf53c15,
 0x3cf53c15,0x3ca23cc6,0x3b493cff,0xbc713ce2,0xbce23c71,0xbcffbb49,0xbcc6bca2,0xbc15bcf5,0xbc153cf5,0xbcc63ca2,0xbcff3b49,0xbce2bc71,0xbc71bce2,0x3b49bcff,0x3ca2bcc6,0x3cf5bc15,
 0xbcac3cbe,0xbcfd3b96,0xbcdcbc84,0xbc2cbcf1,0x3ce7bc5b,0x3cf83bf9,0x3c983cce,0xbac93d00,0xbd003ac9,0xbccebc98,0xbbf9bcf8,0x3c5bbce7,0x3cf13c2c,0x3c843cdc,0xbb963cfd,0xbcbe3cac,
 0xbcbebcac,0xbb96bcfd,0x3c84bcdc,0x3cf1bc2c,0x3c5b3ce7,0xbbf93cf8,0xbcce3c98,0xbd00bac9,0xbac9bd00,0x3c98bcce,0x3cf8bbf9,0x3ce73c5b,0xbc2c3cf1,0xbcdc3c84,0xbcfdbb96,0xbcacbcbe,
 0xbc443ced,0xbced3c44,0xbcedbc44,0xbc44bced,0x3c44bced,0x3cedbc44,0x3ced3c44,0x3c443ced,0xbc443ced,0xbced3c44,0xbcedbc44,0xbc44bced,0x3c44bced,0x3cedbc44,0x3ced3c44,0x3c443ced,
 0xbc443ced,0xbced3c44,0xbcedbc44,0xbc44bced,0x3c44bced,0x3cedbc44,0x3ced3c44,0x3c443ced,0xbc443ced,0xbced3c44,0xbcedbc44,0xbc44bced,0x3c44bced,0x3cedbc44,0x3ced3c44,0x3c443ced,
 0x3cbebcac,0x3cfd3b96,0x3c843cdc,0xbc2c3cf1,0xbc5b3ce7,0xbcf83bf9,0xbccebc98,0xbac9bd00,0x3d003ac9,0x3c983cce,0xbbf93cf8,0xbce73c5b,0xbcf13c2c,0xbcdcbc84,0xbb96bcfd,0x3cacbcbe,
 0x3cac3cbe,0xbb963cfd,0xbcdc3c84,0xbcf1bc2c,0xbce7bc5b,0xbbf9bcf8,0x3c98bcce,0x3d00bac9,0xbac93d00,0xbcce3c98,0xbcf8bbf9,0xbc5bbce7,0xbc2cbcf1,0x3c84bcdc,0x3cfdbb96,0x3cbe3cac,
 0xbce2bc71,0xbb49bcff,0x3cc6bca2,0x3cf53c15,0x3c153cf5,0xbca23cc6,0xbcffbb49,0xbc71bce2,0xbc713ce2,0xbcff3b49,0xbca2bcc6,0x3c15bcf5,0x3cf5bc15,0x3cc63ca2,0xbb493cff,0xbce23c71,
 0x3ce23c71,0x3b493cff,0xbcc63ca2,0xbcf5bc15,0xbc15bcf5,0x3ca2bcc6,0x3cff3b49,0x3c713ce2,0x3c71bce2,0x3cffbb49,0x3ca23cc6,0xbc153cf5,0xbcf53c15,0xbcc6bca2,0x3b49bcff,0x3ce2bc71,
 0xbcce3c98,0xbce7bc5b,0xbac9bd00,0x3cdcbc84,0xbbf9bcf8,0x3cbebcac,0x3cf13c2c,0x3b963cfd,0x3cfd3b96,0x3c2c3cf1,0xbcac3cbe,0xbcf8bbf9,0xbc843cdc,0xbd00bac9,0xbc5bbce7,0x3c98bcce,
 0x3c983cce,0xbc5b3ce7,0xbd003ac9,0xbc84bcdc,0xbcf83bf9,0xbcacbcbe,0x3c2cbcf1,0x3cfdbb96,0x3b96bcfd,0x3cf1bc2c,0x3cbe3cac,0xbbf93cf8,0x3cdc3c84,0xbac93d00,0xbce73c5b,0xbccebc98,
 0xbc8e3cd5,0xbcfbbbc8,0xbbc8bcfb,0x3cd5bc8e,0x3cd53c8e,0xbbc83cfb,0xbcfb3bc8,0xbc8ebcd5,0x3c8ebcd5,0x3cfb3bc8,0x3bc83cfb,0xbcd53c8e,0xbcd5bc8e,0x3bc8bcfb,0x3cfbbbc8,0x3c8e3cd5,
 0xbc8e3cd5,0xbcfbbbc8,0xbbc8bcfb,0x3cd5bc8e,0x3cd53c8e,0xbbc83cfb,0xbcfb3bc8,0xbc8ebcd5,0x3c8ebcd5,0x3cfb3bc8,0x3bc83cfb,0xbcd53c8e,0xbcd5bc8e,0x3bc8bcfb,0x3cfbbbc8,0x3c8e3cd5,
 0xbcdc3c84,0xbcbebcac,0x3c5bbce7,0x3cfd3b96,0xbccebc98,0x3c2cbcf1,0x3d003ac9,0x3bf93cf8,0x3cf83bf9,0x3ac93d00,0xbcf13c2c,0xbc98bcce,0x3b963cfd,0xbce73c5b,0xbcacbcbe,0x3c84bcdc,
 0x3c843cdc,0xbcac3cbe,0xbce7bc5b,0x3b96bcfd,0xbc983cce,0xbcf1bc2c,0x3ac9bd00,0x3cf8bbf9,0x3bf9bcf8,0x3d00bac9,0x3c2c3cf1,0xbcce3c98,0x3cfdbb96,0x3c5b3ce7,0xbcbe3cac,0xbcdcbc84,
 0xbcc6bca2,0x3c71bce2,0x3cf53c15,0xbb493cff,0xbcff3b49,0xbc15bcf5,0x3ce2bc71,0x3ca23cc6,0x3ca2bcc6,0x3ce23c71,0xbc153cf5,0xbcffbb49,0xbb49bcff,0x3cf5bc15,0x3c713ce2,0xbcc63ca2,
 0x3cc63ca2,0xbc713ce2,0xbcf5bc15,0x3b49bcff,0x3cffbb49,0x3c153cf5,0xbce23c71,0xbca2bcc6,0xbca23cc6,0xbce2bc71,0x3c15bcf5,0x3cff3b49,0x3b493cff,0xbcf53c15,0xbc71bce2,0x3cc6bca2,
 0x3ce7bc5b,0x3c843cdc,0xbcce3c98,0xbcacbcbe,0x3d00bac9,0x3b963cfd,0xbcf83bf9,0xbc2cbcf1,0x3cf13c2c,0xbbf93cf8,0xbcfdbb96,0x3ac9bd00,0x3cbe3cac,0xbc983cce,0xbcdcbc84,0x3c5bbce7,
 0x3c5b3ce7,0xbcdc3c84,0xbc98bcce,0x3cbebcac,0x3ac93d00,0xbcfd3b96,0xbbf9bcf8,0x3cf1bc2c,0xbc2c3cf1,0xbcf8bbf9,0x3b96bcfd,0x3d003ac9,0xbcac3cbe,0xbccebc98,0x3c84bcdc,0x3ce73c5b,
 0xbcb53cb5,0xbcb5bcb5,0x3cb5bcb5,0x3cb53cb5,0xbcb53cb5,0xbcb5bcb5,0x3cb5bcb5,0x3cb53cb5,0xbcb53cb5,0xbcb5bcb5,0x3cb5bcb5,0x3cb53cb5,0xbcb53cb5,0xbcb5bcb5,0x3cb5bcb5,0x3cb53cb5,
 0xbcb53cb5,0xbcb5bcb5,0x3cb5bcb5,0x3cb53cb5,0xbcb53cb5,0xbcb5bcb5,0x3cb5bcb5,0x3cb53cb5,0xbcb53cb5,0xbcb5bcb5,0x3cb5bcb5,0x3cb53cb5,0xbcb53cb5,0xbcb5bcb5,0x3cb5bcb5,0x3cb53cb5,
 0xbcf13c2c,0xbbf9bcf8,0x3cfdbb96,0x3ac93d00,0xbcbe3cac,0xbc98bcce,0x3cdcbc84,0x3c5b3ce7,0xbce7bc5b,0x3c84bcdc,0x3cce3c98,0xbcac3cbe,0xbd00bac9,0x3b96bcfd,0x3cf83bf9,0xbc2c3cf1,
 0xbc2cbcf1,0x3cf8bbf9,0x3b963cfd,0xbd003ac9,0xbcacbcbe,0x3ccebc98,0x3c843cdc,0xbce73c5b,0x3c5bbce7,0x3cdc3c84,0xbc983cce,0xbcbebcac,0x3ac9bd00,0x3cfd3b96,0xbbf93cf8,0xbcf1bc2c,
 0xbca2bcc6,0x3ce2bc71,0x3c153cf5,0xbcff3b49,0x3b49bcff,0x3cf53c15,0xbc713ce2,0xbcc6bca2,0xbcc63ca2,0xbc71bce2,0x3cf5bc15,0x3b493cff,0xbcffbb49,0x3c15bcf5,0x3ce23c71,0xbca23cc6,
 0x3ca23cc6,0xbce23c71,0xbc15bcf5,0x3cffbb49,0xbb493cff,0xbcf5bc15,0x3c71bce2,0x3cc63ca2,0x3cc6bca2,0x3c713ce2,0xbcf53c15,0xbb49bcff,0x3cff3b49,0xbc153cf5,0xbce2bc71,0x3ca2bcc6,
 0x3cf8bbf9,0xbac93d00,0xbcf1bc2c,0x3c98bcce,0x3b96bcfd,0x3ce73c5b,0xbcac3cbe,0xbc84bcdc,0xbcdcbc84,0x3cbebcac,0x3c5b3ce7,0xbcfd3b96,0xbcce3c98,0xbc2cbcf1,0x3d00bac9,0xbbf93cf8,
 0xbbf9bcf8,0x3d003ac9,0xbc2c3cf1,0xbccebc98,0xbcfdbb96,0x3c5bbce7,0x3cbe3cac,0xbcdc3c84,0xbc843cdc,0xbcacbcbe,0x3ce7bc5b,0x3b963cfd,0x3c983cce,0xbcf13c2c,0xbac9bd00,0x3cf83bf9,
 0xbcd53c8e,0xbbc8bcfb,0x3cfb3bc8,0xbc8e3cd5,0xbc8ebcd5,0x3cfbbbc8,0xbbc83cfb,0xbcd5bc8e,0x3cd5bc8e,0x3bc83cfb,0xbcfbbbc8,0x3c8ebcd5,0x3c8e3cd5,0xbcfb3bc8,0x3bc8bcfb,0x3cd53c8e,
 0xbcd53c8e,0xbbc8bcfb,0x3cfb3bc8,0xbc8e3cd5,0xbc8ebcd5,0x3cfbbbc8,0xbbc83cfb,0xbcd5bc8e,0x3cd5bc8e,0x3bc83cfb,0xbcfbbbc8,0x3c8ebcd5,0x3c8e3cd5,0xbcfb3bc8,0x3bc8bcfb,0x3cd53c8e,
 0x3cfdbb96,0xbc2c3cf1,0xbcacbcbe,0x3cf8bbf9,0xbc84bcdc,0x3d00bac9,0xbc5b3ce7,0xbc98bcce,0xbccebc98,0x3ce7bc5b,0xbac93d00,0xbcdcbc84,0xbbf93cf8,0xbcbebcac,0x3cf1bc2c,0xbb963cfd,
 0xbb96bcfd,0x3cf13c2c,0xbcbe3cac,0xbbf9bcf8,0xbcdc3c84,0xbac9bd00,0x3ce73c5b,0xbcce3c98,0xbc983cce,0xbc5bbce7,0x3d003ac9,0xbc843cdc,0x3cf83bf9,0xbcac3cbe,0xbc2cbcf1,0x3cfd3b96,
 0xbc71bce2,0x3cff3b49,0xbca23cc6,0xbc15bcf5,0x3cf53c15,0xbcc63ca2,0xbb49bcff,0x3ce23c71,0x3ce2bc71,0xbb493cff,0xbcc6bca2,0x3cf5bc15,0xbc153cf5,0xbca2bcc6,0x3cffbb49,0xbc713ce2,
 0x3c713ce2,0xbcffbb49,0x3ca2bcc6,0x3c153cf5,0xbcf5bc15,0x3cc6bca2,0x3b493cff,0xbce2bc71,0xbce23c71,0x3b49bcff,0x3cc63ca2,0xbcf53c15,0x3c15bcf5,0x3ca23cc6,0xbcff3b49,0x3c71bce2,
 0xbd003ac9,0x3c98bcce,0x3bf93cf8,0xbce7bc5b,0x3cf13c2c,0xbcdc3c84,0x3b96bcfd,0x3cac3cbe,0xbcbebcac,0x3cfdbb96,0xbc843cdc,0xbc2cbcf1,0x3c5b3ce7,0xbcf8bbf9,0x3ccebc98,0xbac93d00,
 0xbac9bd00,0x3cce3c98,0xbcf83bf9,0x3c5bbce7,0xbc2c3cf1,0xbc84bcdc,0x3cfd3b96,0xbcbe3cac,0x3cacbcbe,0x3b963cfd,0xbcdcbc84,0x3cf1bc2c,0xbce73c5b,0x3bf9bcf8,0x3c983cce,0xbd00bac9,
 0xbced3c44,0x3c44bced,0x3c443ced,0xbcedbc44,0x3cedbc44,0xbc443ced,0xbc44bced,0x3ced3c44,0xbced3c44,0x3c44bced,0x3c443ced,0xbcedbc44,0x3cedbc44,0xbc443ced,0xbc44bced,0x3ced3c44,
 0xbced3c44,0x3c44bced,0x3c443ced,0xbcedbc44,0x3cedbc44,0xbc443ced,0xbc44bced,0x3ced3c44,0xbced3c44,0x3c44bced,0x3c443ced,0xbcedbc44,0x3cedbc44,0xbc443ced,0xbc44bced,0x3ced3c44,
 0x3d003ac9,0xbcce3c98,0x3bf9bcf8,0x3c5b3ce7,0xbcf13c2c,0x3c84bcdc,0x3b963cfd,0xbcbebcac,0x3cac3cbe,0xbcfdbb96,0x3cdcbc84,0xbc2c3cf1,0xbce7bc5b,0x3cf8bbf9,0xbc983cce,0xbac9bd00,
 0xbac93d00,0xbc98bcce,0x3cf83bf9,0xbce73c5b,0xbc2cbcf1,0x3cdc3c84,0xbcfd3b96,0x3cacbcbe,0xbcbe3cac,0x3b96bcfd,0x3c843cdc,0xbcf1bc2c,0x3c5bbce7,0x3bf93cf8,0xbccebc98,0x3d00bac9,
 0xbc15bcf5,0x3cc63ca2,0xbcffbb49,0x3ce2bc71,0xbc713ce2,0xbb49bcff,0x3ca23cc6,0xbcf5bc15,0xbcf53c15,0x3ca2bcc6,0xbb493cff,0xbc71bce2,0x3ce23c71,0xbcff3b49,0x3cc6bca2,0xbc153cf5,
 0x3c153cf5,0xbcc6bca2,0x3cff3b49,0xbce23c71,0x3c71bce2,0x3b493cff,0xbca2bcc6,0x3cf53c15,0x3cf5bc15,0xbca23cc6,0x3b49bcff,0x3c713ce2,0xbce2bc71,0x3cffbb49,0xbcc63ca2,0x3c15bcf5,
 0xbcfdbb96,0x3cf1bc2c,0xbcac3cbe,0x3bf9bcf8,0x3c84bcdc,0xbac93d00,0xbc5bbce7,0x3cce3c98,0x3c983cce,0xbce7bc5b,0x3d00bac9,0xbcdc3c84,0xbcf83bf9,0x3cbebcac,0xbc2c3cf1,0xbb96bcfd,
 0xbb963cfd,0xbc2cbcf1,0x3cbe3cac,0xbcf8bbf9,0xbcdcbc84,0x3d003ac9,0xbce73c5b,0x3c98bcce,0x3ccebc98,0xbc5b3ce7,0xbac9bd00,0x3c843cdc,0x3bf93cf8,0xbcacbcbe,0x3cf13c2c,0xbcfd3b96,
 0xbcfb3bc8,0x3cd5bc8e,0xbc8e3cd5,0x3bc8bcfb,0x3bc83cfb,0xbc8ebcd5,0x3cd53c8e,0xbcfbbbc8,0x3cfbbbc8,0xbcd53c8e,0x3c8ebcd5,0xbbc83cfb,0xbbc8bcfb,0x3c8e3cd5,0xbcd5bc8e,0x3cfb3bc8,
 0xbcfb3bc8,0x3cd5bc8e,0xbc8e3cd5,0x3bc8bcfb,0x3bc83cfb,0xbc8ebcd5,0x3cd53c8e,0xbcfbbbc8,0x3cfbbbc8,0xbcd53c8e,0x3c8ebcd5,0xbbc83cfb,0xbbc8bcfb,0x3c8e3cd5,0xbcd5bc8e,0x3cfb3bc8,
 0xbcf8bbf9,0x3d00bac9,0xbcf13c2c,0x3ccebc98,0xbb96bcfd,0x3c5b3ce7,0xbcacbcbe,0x3cdc3c84,0x3c843cdc,0xbcbebcac,0x3ce73c5b,0xbcfdbb96,0xbc983cce,0x3c2cbcf1,0xbac93d00,0xbbf9bcf8,
 0xbbf93cf8,0xbac9bd00,0x3c2c3cf1,0xbc98bcce,0xbcfd3b96,0x3ce7bc5b,0xbcbe3cac,0x3c84bcdc,0x3cdcbc84,0xbcac3cbe,0x3c5bbce7,0xbb963cfd,0x3cce3c98,0xbcf1bc2c,0x3d003ac9,0xbcf83bf9,
 0xbb49bcff,0x3c153cf5,0xbc71bce2,0x3ca23cc6,0xbcc6bca2,0x3ce23c71,0xbcf5bc15,0x3cff3b49,0x3cffbb49,0xbcf53c15,0x3ce2bc71,0xbcc63ca2,0x3ca2bcc6,0xbc713ce2,0x3c15bcf5,0xbb493cff,
 0x3b493cff,0xbc15bcf5,0x3c713ce2,0xbca2bcc6,0x3cc63ca2,0xbce2bc71,0x3cf53c15,0xbcffbb49,0xbcff3b49,0x3cf5bc15,0xbce23c71,0x3cc6bca2,0xbca23cc6,0x3c71bce2,0xbc153cf5,0x3b49bcff,
 0x3cf13c2c,0xbcf8bbf9,0x3cfd3b96,0xbd00bac9,0x3cbe3cac,0xbccebc98,0x3cdc3c84,0xbce7bc5b,0x3c5b3ce7,0xbc84bcdc,0x3c983cce,0xbcacbcbe,0x3ac93d00,0xbb96bcfd,0x3bf93cf8,0xbc2cbcf1,
 0xbc2c3cf1,0x3bf9bcf8,0xbb963cfd,0x3ac9bd00,0xbcac3cbe,0x3c98bcce,0xbc843cdc,0x3c5bbce7,0xbce73c5b,0x3cdcbc84,0xbcce3c98,0x3cbebcac,0xbd003ac9,0x3cfdbb96,0xbcf83bf9,0x3cf1bc2c,
 0xbd000000,0x3d000000,0xbd000000,0x3d000000,0xbd000000,0x3d000000,0xbd000000,0x3d000000,0xbd000000,0x3d000000,0xbd000000,0x3d000000,0xbd000000,0x3d000000,0xbd000000,0x3d000000,
 0xbd000000,0x3d000000,0xbd000000,0x3d000000,0xbd000000,0x3d000000,0xbd000000,0x3d000000,0xbd000000,0x3d000000,0xbd000000,0x3d000000,0xbd000000,0x3d000000,0xbd000000,0x3d000000,
 0xbce7bc5b,0x3cdc3c84,0xbccebc98,0x3cbe3cac,0xbd00bac9,0x3cfd3b96,0xbcf8bbf9,0x3cf13c2c,0xbc2cbcf1,0x3bf93cf8,0xbb96bcfd,0x3ac93d00,0xbcacbcbe,0x3c983cce,0xbc84bcdc,0x3c5b3ce7,
 0x3c5bbce7,0xbc843cdc,0x3c98bcce,0xbcac3cbe,0x3ac9bd00,0xbb963cfd,0x3bf9bcf8,0xbc2c3cf1,0x3cf1bc2c,0xbcf83bf9,0x3cfdbb96,0xbd003ac9,0x3cbebcac,0xbcce3c98,0x3cdcbc84,0xbce73c5b,
 0x3b49bcff,0xbc153cf5,0x3c71bce2,0xbca23cc6,0x3cc6bca2,0xbce23c71,0x3cf5bc15,0xbcff3b49,0xbcffbb49,0x3cf53c15,0xbce2bc71,0x3cc63ca2,0xbca2bcc6,0x3c713ce2,0xbc15bcf5,0x3b493cff,
 0xbb493cff,0x3c15bcf5,0xbc713ce2,0x3ca2bcc6,0xbcc63ca2,0x3ce2bc71,0xbcf53c15,0x3cffbb49,0x3cff3b49,0xbcf5bc15,0x3ce23c71,0xbcc6bca2,0x3ca23cc6,0xbc71bce2,0x3c153cf5,0xbb49bcff,
 0x3cdc3c84,0xbcacbcbe,0x3c5b3ce7,0xbb96bcfd,0x3ccebc98,0xbcf13c2c,0x3d00bac9,0xbcf8bbf9,0xbbf9bcf8,0xbac93d00,0x3c2cbcf1,0xbc983cce,0xbcfdbb96,0x3ce73c5b,0xbcbebcac,0x3c843cdc,
 0x3c84bcdc,0xbcbe3cac,0x3ce7bc5b,0xbcfd3b96,0xbc98bcce,0x3c2c3cf1,0xbac9bd00,0xbbf93cf8,0xbcf83bf9,0x3d003ac9,0xbcf1bc2c,0x3cce3c98,0xbb963cfd,0x3c5bbce7,0xbcac3cbe,0x3cdcbc84,
 0xbcfbbbc8,0x3cd53c8e,0xbc8ebcd5,0x3bc83cfb,0x3bc8bcfb,0xbc8e3cd5,0x3cd5bc8e,0xbcfb3bc8,0x3cfb3bc8,0xbcd5bc8e,0x3c8e3cd5,0xbbc8bcfb,0xbbc83cfb,0x3c8ebcd5,0xbcd53c8e,0x3cfbbbc8,
 0xbcfbbbc8,0x3cd53c8e,0xbc8ebcd5,0x3bc83cfb,0x3bc8bcfb,0xbc8e3cd5,0x3cd5bc8e,0xbcfb3bc8,0x3cfb3bc8,0xbcd5bc8e,0x3c8e3cd5,0xbbc8bcfb,0xbbc83cfb,0x3c8ebcd5,0xbcd53c8e,0x3cfbbbc8,
 0x3cce3c98,0xbc5bbce7,0xbac93d00,0x3c84bcdc,0x3bf9bcf8,0xbcac3cbe,0x3cf1bc2c,0xbcfdbb96,0xbb96bcfd,0xbc2c3cf1,0x3cbebcac,0xbcf83bf9,0xbcdc3c84,0x3d00bac9,0xbce7bc5b,0x3c983cce,
 0x3c98bcce,0xbce73c5b,0x3d003ac9,0xbcdcbc84,0xbcf8bbf9,0x3cbe3cac,0xbc2cbcf1,0xbb963cfd,0xbcfd3b96,0x3cf13c2c,0xbcacbcbe,0x3bf93cf8,0x3c843cdc,0xbac9bd00,0xbc5b3ce7,0x3ccebc98,
 0x3c15bcf5,0xbcc63ca2,0x3cffbb49,0xbce2bc71,0x3c713ce2,0x3b49bcff,0xbca23cc6,0x3cf5bc15,0x3cf53c15,0xbca2bcc6,0x3b493cff,0x3c71bce2,0xbce23c71,0x3cff3b49,0xbcc6bca2,0x3c153cf5,
 0xbc153cf5,0x3cc6bca2,0xbcff3b49,0x3ce23c71,0xbc71bce2,0xbb493cff,0x3ca2bcc6,0xbcf53c15,0xbcf5bc15,0x3ca23cc6,0xbb49bcff,0xbc713ce2,0x3ce2bc71,0xbcffbb49,0x3cc63ca2,0xbc15bcf5,
 0xbcbebcac,0x3b963cfd,0x3c84bcdc,0xbcf13c2c,0x3c5b3ce7,0x3bf9bcf8,0xbcce3c98,0x3d003ac9,0xbac9bd00,0xbc983cce,0x3cf8bbf9,0xbce7bc5b,0xbc2c3cf1,0x3cdcbc84,0xbcfdbb96,0x3cac3cbe,
 0x3cacbcbe,0xbcfd3b96,0x3cdc3c84,0xbc2cbcf1,0xbce73c5b,0x3cf83bf9,0xbc98bcce,0xbac93d00,0x3d00bac9,0xbccebc98,0x3bf93cf8,0x3c5bbce7,0xbcf1bc2c,0x3c843cdc,0x3b96bcfd,0xbcbe3cac,
 0xbcedbc44,0x3c443ced,0x3c44bced,0xbced3c44,0x3ced3c44,0xbc44bced,0xbc443ced,0x3cedbc44,0xbcedbc44,0x3c443ced,0x3c44bced,0xbced3c44,0x3ced3c44,0xbc44bced,0xbc443ced,0x3cedbc44,
 0xbcedbc44,0x3c443ced,0x3c44bced,0xbced3c44,0x3ced3c44,0xbc44bced,0xbc443ced,0x3cedbc44,0xbcedbc44,0x3c443ced,0x3c44bced,0xbced3c44,0x3ced3c44,0xbc44bced,0xbc443ced,0x3cedbc44,
 0x3cac3cbe,0x3b96bcfd,0xbcdc3c84,0x3cf13c2c,0xbce7bc5b,0x3bf93cf8,0x3c98bcce,0xbd003ac9,0xbac93d00,0x3ccebc98,0xbcf8bbf9,0x3c5b3ce7,0xbc2cbcf1,0xbc843cdc,0x3cfdbb96,0xbcbebcac,
 0xbcbe3cac,0x3cfd3b96,0xbc84bcdc,0xbc2c3cf1,0x3c5bbce7,0xbcf83bf9,0x3cce3c98,0xbac9bd00,0xbd00bac9,0x3c983cce,0x3bf9bcf8,0xbce73c5b,0x3cf1bc2c,0xbcdcbc84,0x3b963cfd,0x3cacbcbe,
 0x3c71bce2,0xbcff3b49,0x3ca23cc6,0x3c15bcf5,0xbcf53c15,0x3cc63ca2,0x3b49bcff,0xbce23c71,0xbce2bc71,0x3b493cff,0x3cc6bca2,0xbcf5bc15,0x3c153cf5,0x3ca2bcc6,0xbcffbb49,0x3c713ce2,
 0xbc713ce2,0x3cffbb49,0xbca2bcc6,0xbc153cf5,0x3cf5bc15,0xbcc6bca2,0xbb493cff,0x3ce2bc71,0x3ce23c71,0xbb49bcff,0xbcc63ca2,0x3cf53c15,0xbc15bcf5,0xbca23cc6,0x3cff3b49,0xbc71bce2,
 0xbc98bcce,0xbc5b3ce7,0x3d00bac9,0xbc84bcdc,0x3cf8bbf9,0xbcacbcbe,0xbc2c3cf1,0x3cfdbb96,0xbb963cfd,0x3cf1bc2c,0xbcbebcac,0xbbf93cf8,0xbcdcbc84,0xbac93d00,0x3ce7bc5b,0xbccebc98,
 0xbcce3c98,0x3ce73c5b,0xbac9bd00,0xbcdc3c84,0xbbf9bcf8,0xbcbe3cac,0x3cf13c2c,0xbb96bcfd,0x3cfd3b96,0xbc2cbcf1,0xbcac3cbe,0x3cf83bf9,0xbc843cdc,0x3d003ac9,0xbc5bbce7,0xbc983cce,
 0xbcd5bc8e,0xbbc83cfb,0x3cfbbbc8,0xbc8ebcd5,0xbc8e3cd5,0x3cfb3bc8,0xbbc8bcfb,0xbcd53c8e,0x3cd53c8e,0x3bc8bcfb,0xbcfb3bc8,0x3c8e3cd5,0x3c8ebcd5,0xbcfbbbc8,0x3bc83cfb,0x3cd5bc8e,
 0xbcd5bc8e,0xbbc83cfb,0x3cfbbbc8,0xbc8ebcd5,0xbc8e3cd5,0x3cfb3bc8,0xbbc8bcfb,0xbcd53c8e,0x3cd53c8e,0x3bc8bcfb,0xbcfb3bc8,0x3c8e3cd5,0x3c8ebcd5,0xbcfbbbc8,0x3bc83cfb,0x3cd5bc8e,
 0xbc84bcdc,0xbcac3cbe,0x3ce73c5b,0x3b96bcfd,0x3c98bcce,0xbcf1bc2c,0xbac93d00,0x3cf8bbf9,0xbbf93cf8,0x3d00bac9,0xbc2cbcf1,0xbcce3c98,0xbcfd3b96,0x3c5b3ce7,0x3cbebcac,0xbcdcbc84,
 0xbcdc3c84,0x3cbe3cac,0x3c5bbce7,0xbcfdbb96,0xbccebc98,0xbc2c3cf1,0x3d003ac9,0xbbf9bcf8,0x3cf83bf9,0xbac9bd00,0xbcf13c2c,0x3c983cce,0x3b963cfd,0x3ce7bc5b,0xbcacbcbe,0xbc843cdc,
 0x3ca2bcc6,0xbce2bc71,0xbc153cf5,0x3cff3b49,0xbb49bcff,0xbcf53c15,0x3c713ce2,0x3cc6bca2,0x3cc63ca2,0x3c71bce2,0xbcf5bc15,0xbb493cff,0x3cffbb49,0xbc15bcf5,0xbce23c71,0x3ca23cc6,
 0xbca23cc6,0x3ce23c71,0x3c15bcf5,0xbcffbb49,0x3b493cff,0x3cf5bc15,0xbc71bce2,0xbcc63ca2,0xbcc6bca2,0xbc713ce2,0x3cf53c15,0x3b49bcff,0xbcff3b49,0x3c153cf5,0x3ce2bc71,0xbca2bcc6,
 0x3c5b3ce7,0x3cdcbc84,0xbc98bcce,0xbcbe3cac,0x3ac93d00,0x3cfdbb96,0xbbf9bcf8,0xbcf13c2c,0xbc2c3cf1,0x3cf83bf9,0x3b96bcfd,0xbd00bac9,0xbcac3cbe,0x3cce3c98,0x3c84bcdc,0xbce7bc5b,
 0xbce73c5b,0x3c843cdc,0x3ccebc98,0xbcacbcbe,0xbd003ac9,0x3b963cfd,0x3cf8bbf9,0xbc2cbcf1,0xbcf1bc2c,0xbbf93cf8,0x3cfd3b96,0x3ac9bd00,0xbcbebcac,0xbc983cce,0x3cdc3c84,0x3c5bbce7,
 0xbcb5bcb5,0xbcb53cb5,0x3cb53cb5,0x3cb5bcb5,0xbcb5bcb5,0xbcb53cb5,0x3cb53cb5,0x3cb5bcb5,0xbcb5bcb5,0xbcb53cb5,0x3cb53cb5,0x3cb5bcb5,0xbcb5bcb5,0xbcb53cb5,0x3cb53cb5,0x3cb5bcb5,
 0xbcb5bcb5,0xbcb53cb5,0x3cb53cb5,0x3cb5bcb5,0xbcb5bcb5,0xbcb53cb5,0x3cb53cb5,0x3cb5bcb5,0xbcb5bcb5,0xbcb53cb5,0x3cb53cb5,0x3cb5bcb5,0xbcb5bcb5,0xbcb53cb5,0x3cb53cb5,0x3cb5bcb5,
 0xbc2cbcf1,0xbcf83bf9,0x3b963cfd,0x3d00bac9,0xbcacbcbe,0xbcce3c98,0x3c843cdc,0x3ce7bc5b,0x3c5bbce7,0xbcdcbc84,0xbc983cce,0x3cbe3cac,0x3ac9bd00,0xbcfdbb96,0xbbf93cf8,0x3cf13c2c,
 0x3cf1bc2c,0xbbf9bcf8,0xbcfd3b96,0x3ac93d00,0x3cbebcac,0xbc98bcce,0xbcdc3c84,0x3c5b3ce7,0x3ce73c5b,0x3c84bcdc,0xbccebc98,0xbcac3cbe,0x3d003ac9,0x3b96bcfd,0xbcf8bbf9,0xbc2c3cf1,
 0x00000000,0x00000000,0x00000000,0x00000000,0x00000000,0x00000000,0x00000000,0x00000000,0x00000000,0x00000000,0x00000000,0x00000000,0x00000000,0x00000000,0x00000000,0x00000000,
 0x00000000,0x00000000,0x00000000,0x00000000,0x00000000,0x00000000,0x00000000,0x00000000,0x00000000,0x00000000,0x00000000,0x00000000,0x00000000,0x00000000,0x00000000,0x00000000,
 0x00000000,0x00000000,0x00000000,0x00000000,0x00000000,0x00000000,0x00000000,0x00000000,0x00000000,0x00000000,0x00000000,0x00000000,0x00000000,0x00000000,0x00000000,0x00000000,
 0x00000000,0x00000000,0x00000000,0x00000000,0x00000000,0x00000000,0x00000000,0x00000000,0x00000000,0x00000000,0x00000000,0x00000000,0x00000000,0x00000000,0x00000000,0x00000000,
 0x00000000,0x00000000,0x00000000,0x00000000,0x00000000,0x00000000,0x00000000,0x00000000,0x00000000,0x00000000,0x00000000,0x00000000,0x00000000,0x00000000,0x00000000,0x00000000,
 0x00000000,0x00000000,0x00000000,0x00000000,0x00000000,0x00000000,0x00000000,0x00000000,0x00000000,0x00000000,0x00000000,0x00000000,0x00000000,0x00000000,0x00000000,0x00000000,
 0x00000000,0x00000000,0x00000000,0x00000000,0x00000000,0x00000000,0x00000000,0x00000000,0x00000000,0x00000000,0x00000000,0x00000000,0x00000000,0x00000000,0x00000000,0x00000000,
 0x00000000,0x00000000,0x00000000,0x00000000,0x00000000,0x00000000,0x00000000,0x00000000,0x00000000,0x00000000,0x00000000,0x00000000,0x00000000,0x00000000,0x00000000,0x00000000,
 0x00000000,0x00000000,0x00000000,0x00000000,0x00000000,0x00000000,0x00000000,0x00000000,0x00000000,0x00000000,0x00000000,0x00000000,0x00000000,0x00000000,0x00000000,0x00000000,
 0x00000000,0x00000000,0x00000000,0x00000000,0x00000000,0x00000000,0x00000000,0x00000000,0x00000000,0x00000000,0x00000000,0x00000000,0x00000000,0x00000000,0x00000000,0x00000000,
 0x00000000,0x00000000,0x00000000,0x00000000,0x00000000,0x00000000,0x00000000,0x00000000,0x00000000,0x00000000,0x00000000,0x00000000,0x00000000,0x00000000,0x00000000,0x00000000,
 0x00000000,0x00000000,0x00000000,0x00000000,0x00000000,0x00000000,0x00000000,0x00000000,0x00000000,0x00000000,0x00000000,0x00000000,0x00000000,0x00000000,0x00000000,0x00000000,
};

template<int SA>
__device__ __forceinline__ void wgmma_main(float (&d)[80], uint64_t da, uint64_t db, int sd) {
  asm volatile("{\n.reg .pred p;\nsetp.ne.b32 p, %82, 0;\n"
    "wgmma.mma_async.sync.aligned.m64n160k16.f32.bf16.bf16 "
    "{%0, %1, %2, %3, %4, %5, %6, %7, %8, %9, %10, %11, %12, %13, %14, %15, %16, %17, %18, %19, %20, %21, %22, %23, %24, %25, %26, %27, %28, %29, %30, %31, %32, %33, %34, %35, %36, %37, %38, %39, %40, %41, %42, %43, %44, %45, %46, %47, %48, %49, %50, %51, %52, %53, %54, %55, %56, %57, %58, %59, %60, %61, %62, %63, %64, %65, %66, %67, %68, %69, %70, %71, %72, %73, %74, %75, %76, %77, %78, %79}, %80, %81, p, %83, 1, 1, 0;\n}\n"
    : "+f"(d[0]), "+f"(d[1]), "+f"(d[2]), "+f"(d[3]), "+f"(d[4]), "+f"(d[5]), "+f"(d[6]), "+f"(d[7]), "+f"(d[8]), "+f"(d[9]), "+f"(d[10]), "+f"(d[11]), "+f"(d[12]), "+f"(d[13]), "+f"(d[14]), "+f"(d[15]), "+f"(d[16]), "+f"(d[17]), "+f"(d[18]), "+f"(d[19]), "+f"(d[20]), "+f"(d[21]), "+f"(d[22]), "+f"(d[23]), "+f"(d[24]), "+f"(d[25]), "+f"(d[26]), "+f"(d[27]), "+f"(d[28]), "+f"(d[29]), "+f"(d[30]), "+f"(d[31]), "+f"(d[32]), "+f"(d[33]), "+f"(d[34]), "+f"(d[35]), "+f"(d[36]), "+f"(d[37]), "+f"(d[38]), "+f"(d[39]), "+f"(d[40]), "+f"(d[41]), "+f"(d[42]), "+f"(d[43]), "+f"(d[44]), "+f"(d[45]), "+f"(d[46]), "+f"(d[47]), "+f"(d[48]), "+f"(d[49]), "+f"(d[50]), "+f"(d[51]), "+f"(d[52]), "+f"(d[53]), "+f"(d[54]), "+f"(d[55]), "+f"(d[56]), "+f"(d[57]), "+f"(d[58]), "+f"(d[59]), "+f"(d[60]), "+f"(d[61]), "+f"(d[62]), "+f"(d[63]), "+f"(d[64]), "+f"(d[65]), "+f"(d[66]), "+f"(d[67]), "+f"(d[68]), "+f"(d[69]), "+f"(d[70]), "+f"(d[71]), "+f"(d[72]), "+f"(d[73]), "+f"(d[74]), "+f"(d[75]), "+f"(d[76]), "+f"(d[77]), "+f"(d[78]), "+f"(d[79])
    : "l"(da), "l"(db), "r"(sd), "n"(SA));
}
template<int SA>
__device__ __forceinline__ void wgmma_fwd(float (&d)[32], uint64_t da, uint64_t db, int sd) {
  asm volatile("{\n.reg .pred p;\nsetp.ne.b32 p, %34, 0;\n"
    "wgmma.mma_async.sync.aligned.m64n64k16.f32.bf16.bf16 "
    "{%0, %1, %2, %3, %4, %5, %6, %7, %8, %9, %10, %11, %12, %13, %14, %15, %16, %17, %18, %19, %20, %21, %22, %23, %24, %25, %26, %27, %28, %29, %30, %31}, %32, %33, p, %35, 1, 0, 1;\n}\n"
    : "+f"(d[0]), "+f"(d[1]), "+f"(d[2]), "+f"(d[3]), "+f"(d[4]), "+f"(d[5]), "+f"(d[6]), "+f"(d[7]), "+f"(d[8]), "+f"(d[9]), "+f"(d[10]), "+f"(d[11]), "+f"(d[12]), "+f"(d[13]), "+f"(d[14]), "+f"(d[15]), "+f"(d[16]), "+f"(d[17]), "+f"(d[18]), "+f"(d[19]), "+f"(d[20]), "+f"(d[21]), "+f"(d[22]), "+f"(d[23]), "+f"(d[24]), "+f"(d[25]), "+f"(d[26]), "+f"(d[27]), "+f"(d[28]), "+f"(d[29]), "+f"(d[30]), "+f"(d[31])
    : "l"(da), "l"(db), "r"(sd), "n"(SA));
}
template<int SA>
__device__ __forceinline__ void wgmma_inv(float (&d)[28], uint64_t da, uint64_t db, int sd) {
  asm volatile("{\n.reg .pred p;\nsetp.ne.b32 p, %30, 0;\n"
    "wgmma.mma_async.sync.aligned.m64n56k16.f32.bf16.bf16 "
    "{%0, %1, %2, %3, %4, %5, %6, %7, %8, %9, %10, %11, %12, %13, %14, %15, %16, %17, %18, %19, %20, %21, %22, %23, %24, %25, %26, %27}, %28, %29, p, %31, 1, 1, 0;\n}\n"
    : "+f"(d[0]), "+f"(d[1]), "+f"(d[2]), "+f"(d[3]), "+f"(d[4]), "+f"(d[5]), "+f"(d[6]), "+f"(d[7]), "+f"(d[8]), "+f"(d[9]), "+f"(d[10]), "+f"(d[11]), "+f"(d[12]), "+f"(d[13]), "+f"(d[14]), "+f"(d[15]), "+f"(d[16]), "+f"(d[17]), "+f"(d[18]), "+f"(d[19]), "+f"(d[20]), "+f"(d[21]), "+f"(d[22]), "+f"(d[23]), "+f"(d[24]), "+f"(d[25]), "+f"(d[26]), "+f"(d[27])
    : "l"(da), "l"(db), "r"(sd), "n"(SA));
}

__device__ __forceinline__ uint32_t s2u(const void* p) { return (uint32_t)__cvta_generic_to_shared(p); }
__device__ __forceinline__ void mbar_init(uint32_t a, int c) { asm volatile("mbarrier.init.shared::cta.b64 [%0], %1;" ::"r"(a), "r"(c)); }
__device__ __forceinline__ void mbar_expect(uint32_t a, int b) { asm volatile("mbarrier.arrive.expect_tx.shared::cta.b64 _, [%0], %1;" ::"r"(a), "r"(b) : "memory"); }
__device__ __forceinline__ void mbar_arrive(uint32_t a) { asm volatile("mbarrier.arrive.shared::cta.b64 _, [%0];" ::"r"(a) : "memory"); }
__device__ __forceinline__ void mbar_arrive_cluster(uint32_t a, uint32_t cta, uint32_t cnt) {
  asm volatile("{\n.reg .b32 r;\nmapa.shared::cluster.u32 r, %0, %1;\nmbarrier.arrive.shared::cluster.b64 _, [r], %2;\n}" ::"r"(a), "r"(cta), "r"(cnt) : "memory");
}
__device__ __forceinline__ void mbar_wait(uint32_t a, int ph) {
  asm volatile("{\n.reg .pred p;\n.reg .u32 c;\nmov.u32 c, 0;\nWAIT:\n"
               "mbarrier.try_wait.parity.shared::cta.b64 p, [%0], %1;\n@p bra DONE;\n"
               "add.u32 c, c, 1;\nsetp.lt.u32 p, c, 0x400000;\n@p bra WAIT;\ntrap;\nDONE:\n}" ::"r"(a), "r"(ph) : "memory");
}
__device__ __forceinline__ void flag_wait(const unsigned* p, unsigned target) {
  asm volatile("{\n.reg .pred p;\n.reg .u32 c, v;\nmov.u32 c, 0;\nWAIT:\n"
               "ld.acquire.gpu.global.u32 v, [%0];\nsetp.ge.u32 p, v, %1;\n@p bra DONE;\n"
               "add.u32 c, c, 1;\nsetp.lt.u32 p, c, 0x400000;\n@p bra WAIT;\ntrap;\nDONE:\n}" ::"l"(p), "r"(target) : "memory");
}
__device__ __forceinline__ bool elect_one() {
  uint32_t p;
  asm volatile("{\n.reg .pred P;\nelect.sync _|P, 0xffffffff;\nselp.u32 %0, 1, 0, P;\n}" : "=r"(p));
  return p != 0;
}
__device__ __forceinline__ void bulk_ld(uint32_t dst, const void* src, int bytes, uint32_t bar) {
  asm volatile("cp.async.bulk.shared::cluster.global.mbarrier::complete_tx::bytes [%0], [%1], %2, [%3];" ::"r"(dst), "l"(src), "r"(bytes), "r"(bar) : "memory");
}
__device__ __forceinline__ void bulk_ld_mc_h(uint32_t dst, const void* src, int bytes, uint32_t bar, uint16_t mask, uint64_t pol) {
  asm volatile("cp.async.bulk.shared::cluster.global.mbarrier::complete_tx::bytes.multicast::cluster.L2::cache_hint [%0], [%1], %2, [%3], %4, %5;" ::"r"(dst), "l"(src), "r"(bytes), "r"(bar), "h"(mask), "l"(pol) : "memory");
}
__device__ __forceinline__ void tma_ld2(uint32_t dst, const CUtensorMap* tm, int c0, int c1, uint32_t bar) {
  asm volatile("cp.async.bulk.tensor.2d.shared::cluster.global.mbarrier::complete_tx::bytes [%0], [%1, {%3,%4}], [%2];" ::"r"(dst), "l"(tm), "r"(bar), "r"(c0), "r"(c1) : "memory");
}
__device__ __forceinline__ void tma_ld3(uint32_t dst, const CUtensorMap* tm, int c0, int c1, int c2, uint32_t bar) {
  asm volatile("cp.async.bulk.tensor.3d.shared::cluster.global.mbarrier::complete_tx::bytes [%0], [%1, {%3,%4,%5}], [%2];" ::"r"(dst), "l"(tm), "r"(bar), "r"(c0), "r"(c1), "r"(c2) : "memory");
}
__device__ __forceinline__ void tma_ld3h(uint32_t dst, const CUtensorMap* tm, int c0, int c1, int c2, uint32_t bar, uint64_t pol) {
  asm volatile("cp.async.bulk.tensor.3d.shared::cluster.global.mbarrier::complete_tx::bytes.L2::cache_hint [%0], [%1, {%3,%4,%5}], [%2], %6;" ::"r"(dst), "l"(tm), "r"(bar), "r"(c0), "r"(c1), "r"(c2), "l"(pol) : "memory");
}
__device__ __forceinline__ uint64_t policy_evict_first() {
  uint64_t p;
  asm("createpolicy.fractional.L2::evict_first.b64 %0, 1.0;" : "=l"(p));
  return p;
}
__device__ __forceinline__ void tma_st3(const CUtensorMap* tm, uint32_t src, int c0, int c1, int c2) {
  asm volatile("cp.async.bulk.tensor.3d.global.shared::cta.bulk_group [%0, {%2,%3,%4}], [%1];" ::"l"(tm), "r"(src), "r"(c0), "r"(c1), "r"(c2) : "memory");
}
__device__ __forceinline__ void tma_st4(const CUtensorMap* tm, uint32_t src, int c0, int c1, int c2, int c3) {
  asm volatile("cp.async.bulk.tensor.4d.global.shared::cta.bulk_group [%0, {%2,%3,%4,%5}], [%1];" ::"l"(tm), "r"(src), "r"(c0), "r"(c1), "r"(c2), "r"(c3) : "memory");
}
__device__ __forceinline__ void tma_st5(const CUtensorMap* tm, uint32_t src, int c0) {
  asm volatile("cp.async.bulk.tensor.5d.global.shared::cta.bulk_group [%0, {%2,%3,%3,%3,%3}], [%1];" ::"l"(tm), "r"(src), "r"(c0), "r"(0) : "memory");
}
__device__ __forceinline__ void bulk_commit() { asm volatile("cp.async.bulk.commit_group;" ::: "memory"); }
template <int N> __device__ __forceinline__ void bulk_wait_read() { asm volatile("cp.async.bulk.wait_group.read %0;" ::"n"(N) : "memory"); }
template <int N> __device__ __forceinline__ void bulk_wait() { asm volatile("cp.async.bulk.wait_group %0;" ::"n"(N) : "memory"); }
__device__ __forceinline__ void fence_async_smem() { asm volatile("fence.proxy.async.shared::cta;" ::: "memory"); }
__device__ __forceinline__ void wg_fence() { asm volatile("wgmma.fence.sync.aligned;" ::: "memory"); }
__device__ __forceinline__ void wg_commit() { asm volatile("wgmma.commit_group.sync.aligned;" ::: "memory"); }
template <int N> __device__ __forceinline__ void wg_wait() { asm volatile("wgmma.wait_group.sync.aligned %0;" ::"n"(N) : "memory"); }
template <int R> __device__ __forceinline__ void fence_regs(float (&d)[R]) {
#pragma unroll
  for (int i = 0; i < R; i++) asm volatile("" : "+f"(d[i])::"memory");
}
__device__ __forceinline__ uint64_t mk_desc(uint32_t addr) {
  return (uint64_t)((addr & 0x3FFFF) >> 4) | (1ull << 16) | (64ull << 32) | (1ull << 62);
}
__device__ __forceinline__ uint32_t pack2(float lo, float hi) {
  uint32_t r;
  asm("cvt.rn.bf16x2.f32 %0, %1, %2;" : "=r"(r) : "f"(hi), "f"(lo));
  return r;
}
__device__ __forceinline__ void stsm4(uint32_t ad, uint32_t a, uint32_t b, uint32_t c, uint32_t d) {
  asm volatile("stmatrix.sync.aligned.m8n8.x4.shared.b16 [%0], {%1,%2,%3,%4};" ::"r"(ad), "r"(a), "r"(b), "r"(c), "r"(d) : "memory");
}
__device__ __forceinline__ void stsm4t(uint32_t ad, uint32_t a, uint32_t b, uint32_t c, uint32_t d) {
  asm volatile("stmatrix.sync.aligned.m8n8.x4.trans.shared.b16 [%0], {%1,%2,%3,%4};" ::"r"(ad), "r"(a), "r"(b), "r"(c), "r"(d) : "memory");
}

__device__ __forceinline__ void stsm2t(uint32_t ad, uint32_t a, uint32_t b) {
  asm volatile("stmatrix.sync.aligned.m8n8.x2.trans.shared.b16 [%0], {%1,%2};" ::"r"(ad), "r"(a), "r"(b) : "memory");
}
__device__ __forceinline__ void red_add(unsigned* p) { asm volatile("red.relaxed.gpu.global.add.u32 [%0], 1;" ::"l"(p) : "memory"); }
__device__ __forceinline__ void fence_release() { asm volatile("fence.release.gpu;" ::: "memory"); }
__device__ __forceinline__ void fence_async_global() { asm volatile("fence.proxy.async.global;" ::: "memory"); }
__device__ __forceinline__ void tma_pf2(const CUtensorMap* tm, int c0, int c1) {
  asm volatile("cp.async.bulk.prefetch.tensor.2d.L2.global [%0, {%1,%2}];" ::"l"(tm), "r"(c0), "r"(c1) : "memory");
}
__device__ __forceinline__ void tma_pf3(const CUtensorMap* tm, int c0, int c1, int c2) {
  asm volatile("cp.async.bulk.prefetch.tensor.3d.L2.global [%0, {%1,%2,%3}];" ::"l"(tm), "r"(c0), "r"(c1), "r"(c2) : "memory");
}
__device__ __forceinline__ uint64_t policy_evict_unchanged() {
  uint64_t p;
  asm("createpolicy.fractional.L2::evict_unchanged.b64 %0, 1.0;" : "=l"(p));
  return p;
}

__device__ __forceinline__ int lane_id() {
  int l;
  asm volatile("mov.u32 %0, %%laneid;" : "=r"(l));
  return l;
}
__device__ __forceinline__ void poll64x4(const unsigned long long* p, unsigned long long (&v)[4]) {
  asm volatile("{\n.reg .pred p;\n.reg .u32 c;\n.reg .b64 t, u;\nmov.u32 c, 0;\nWAIT:\n"
               "ld.relaxed.gpu.global.u64 %0, [%4];\nld.relaxed.gpu.global.u64 %1, [%4+512];\n"
               "ld.relaxed.gpu.global.u64 %2, [%4+1024];\nld.relaxed.gpu.global.u64 %3, [%4+1536];\n"
               "or.b64 t, %0, %1;\nor.b64 u, %2, %3;\nor.b64 t, t, u;\nsetp.ge.s64 p, t, 0;\n@p bra DONE;\n"
               "add.u32 c, c, 1;\nsetp.lt.u32 p, c, 0x400000;\n@p bra WAIT;\ntrap;\nDONE:\n}"
               : "=l"(v[0]), "=l"(v[1]), "=l"(v[2]), "=l"(v[3]) : "l"(p) : "memory");
}

constexpr int G_STAGE = WBLK + XBLK;
constexpr int OFF_XR = 4 * G_STAGE;
constexpr int OFF_WS = OFF_XR + 6 * 8192;
constexpr int OFF_F = OFF_WS + 2 * 8192;
constexpr int OFF_WRAW = OFF_F + 8192;
constexpr int OFF_BAR = OFF_WRAW + 8192;
constexpr int OFF_GB = OFF_BAR + 1024;
constexpr int SMEM_BYTES = OFF_GB + 512;
constexpr int OFF_H0B = 10 * 8192;
constexpr int OFF_E = OFF_WRAW + 3072;
constexpr int B_RAWX = 0, B_F = 48, B_ROLE = 56, B_H0 = 80, B_H1 = 96, B_YFREE = 120, B_H0C = 136,
              B_EMPTY = 144,
              B_STGX = 192, B_STGW = 240, B_Y = 256, B_OUT = 272, B_YP = 352,
              B_FULL = 432, B_RAWW = 464, B_DONE = 496, S_ROLE = 576, S_PROBE = 592;

struct Maps { CUtensorMap x, we, wo, xst[2], wst, yst[2], yld[2], out, xe[2], w30; };

__device__ __forceinline__ int chunk_of(int n) { return n < 16 ? n : 31 - n; }
__device__ __forceinline__ bool has_x2(int id, int n, int g) { return (((id >> 5) ^ n) & 1) == 0 && ((n >> 1) & 1) == g; }
__device__ __forceinline__ int w_row(int id) { return (id & 62) | (id >> 6); }
__device__ __forceinline__ uint32_t x_base(int s, int idx, uint32_t pgmask, int& par) {
  const int page = idx >> 3, o = idx & 7;
  par = (s ^ (pgmask >> page) ^ __popc(o)) & 1;
  return (page << 21) | ((o & 3) << 16) | ((o >> 2) << 19);
}
__device__ __forceinline__ uint32_t read_info(uint32_t bar, int i) {
  uint32_t v;
  mbar_wait(bar + B_ROLE + 8 * i, 0);
  asm volatile("ld.shared.b32 %0, [%1];" : "=r"(v) : "r"(bar + S_ROLE + 4 * i) : "memory");
  return v;
}
__device__ __forceinline__ void send_info(uint32_t bar, int i, uint32_t v) {
#pragma unroll
  for (int r = 0; r < 2; r++)
    asm volatile("{\n.reg .b32 a, m;\nmapa.shared::cluster.u32 a, %0, %2;\nmapa.shared::cluster.u32 m, %1, %2;\n"
                 "st.async.weak.shared::cluster.mbarrier::complete_tx::bytes.b32 [a], %3, [m];\n}"
                 ::"r"(bar + S_ROLE + 4 * i), "r"(bar + B_ROLE + 8 * i), "r"(r), "r"(v) : "memory");
}
__device__ __forceinline__ unsigned probe(uint8_t* p, int lane) {
  if (lane < 2) *(uint4*)(p + lane * 16) = make_uint4(0, 0, 0, 0);
  __syncwarp();
  unsigned v, t0 = 0, t1 = 0;
  if (lane == 0) {
    asm volatile("mov.u32 %0, %%clock;" : "=r"(t0)::"memory");
    asm volatile("atom.relaxed.gpu.global.exch.b32 %0, [%1], 0;" : "=r"(v) : "l"(p) : "memory");
    asm volatile("{\n.reg .pred p;\nsetp.ne.u32 p, %1, 0xffffffff;\nmov.u32 %0, 0;\n@p mov.u32 %0, %%clock;\n}" : "=r"(t1) : "r"(v) : "memory");
  }
  return t1 - t0;
}

template <bool ISX>
__device__ __forceinline__ void t_issue(float (&t)[32], uint32_t sb, uint32_t raw) {
  const uint64_t da = mk_desc(sb + OFF_F), db = mk_desc(raw);
  wg_fence();
#pragma unroll
  for (int kk = 0; kk < (ISX ? 4 : 1); kk++) wgmma_fwd<1>(t, da + 2 * kk, db + 128 * kk, kk);
  wg_commit();
}
template <bool ISX>
__device__ __forceinline__ void t_finish(float (&t)[32], uint32_t dst, uint32_t sbar, int sw, int wg, int w, int lane) {
  fence_regs(t);
  if (ISX) asm volatile("bar.sync %0, 128;" ::"r"(1 + wg) : "memory");
  const int m = lane >> 3, r = lane & 7;
  uint32_t ad = dst + (8 * w + r) * 128;
  if (ISX) ad += ((((m & 1) * 4 + (m >> 1)) ^ sw ^ r) << 4);
  else ad += (m & 1) * 4096 + (((m >> 1) ^ sw ^ r) << 4);
#pragma unroll
  for (int i = 0; i < 4; i++) {
    const uint32_t a = ISX ? ((ad ^ ((i & 1) * 32)) + (i >> 1) * 4096) : (ad ^ (i * 32));
    stsm4(a, pack2(t[8 * i], t[8 * i + 1]), pack2(t[8 * i + 2], t[8 * i + 3]), pack2(t[8 * i + 4], t[8 * i + 5]), pack2(t[8 * i + 6], t[8 * i + 7]));
  }
  __syncwarp();
  if (lane == 0) mbar_arrive(sbar);
}
template <int NT, int K0, int K1>
__device__ __forceinline__ void batch(float (&yr)[80], float (&yi)[80], float (&t)[32], uint32_t st, int wg, int sd, uint32_t fa, uint32_t raw) {
  const uint64_t w0 = mk_desc(st + wg * 8192), x0 = mk_desc(st + WBLK);
  const uint64_t da = mk_desc(fa), db = mk_desc(raw);
  wg_fence();
  if (NT) {
#pragma unroll
    for (int kk = 0; kk < NT; kk++) wgmma_fwd<1>(t, da + 2 * kk, db + 128 * kk, kk);
    wg_commit();
  }
#pragma unroll
  for (int kk = K0; kk < K1; kk++) {
    const uint64_t wr = w0 + kk * 128, wi = wr + 256, xr = x0 + kk * 2, xi = xr + 4;
    wgmma_main<1>(yr, wr, xr, kk ? 1 : sd);
    wgmma_main<1>(yi, wr, xi, kk ? 1 : sd);
    wgmma_main<1>(yr, wi, xi, 1);
    wgmma_main<-1>(yi, wi, xr, 1);
  }
  wg_commit();
}

#define X_WAIT() PROF_W(wraw, mbar_wait(bar + B_RAWX + 8 * (wg * 3 + xs), xph))
#define X_ISSUE() t_issue<true>(t, sb, sb + OFF_XR + (wg * 3 + xs) * 8192)
#define X_FINISH(sw) do { t_finish<true>(t, sb + OFF_XR + (wg * 3 + xs) * 8192, bar + B_STGX + 8 * (wg * 3 + xs), sw, wg, w, lane); \
                          if (++xs == 3) { xs = 0; xph ^= 1; } } while (0)
#define W_WAIT(n) PROF_W(wraw, mbar_wait(bar + B_RAWW + 8 * (wg * 2 + ((n) & 1)), ((n) >> 1) & 1))
#define WRAW(n) (sb + OFF_WRAW + (wg * 2 + ((n) & 1)) * 2048)
#define W_FINISH() t_finish<false>(t, sb + OFF_WS + wg * 8192, bar + B_STGW + 8 * wg, w_row(id) & 7, wg, w, lane)

__device__ __forceinline__ void gelu_store(float (&hz)[28], uint32_t ad) {
#pragma unroll
  for (int i = 0; i < 28; i++) {
    const float in = hz[i] * fmaf(hz[i] * hz[i], 8.f * 0.044715f * 0.7978845608028654f, 2.f * 0.7978845608028654f);
    float th;
    asm("tanh.approx.f32 %0, %1;" : "=f"(th) : "f"(in));
    hz[i] = fmaf(hz[i], th, hz[i]);
  }
#pragma unroll
  for (int jj = 0; jj < 3; jj++) {
    const float* c = hz + 8 * jj;
    stsm4t(ad + jj * 2048, pack2(c[0], c[1]), pack2(c[2], c[3]), pack2(c[4], c[5]), pack2(c[6], c[7]));
  }
  stsm2t(ad + 3 * 2048, pack2(hz[24], hz[25]), pack2(hz[26], hz[27]));
}

template <int g>
__device__ __forceinline__ void manager(const Maps& tm, const unsigned* ctr, const uint32_t sb, const int id) {
  const uint32_t bar = sb + OFF_BAR, rank = id & 1;
  const uint64_t pol = policy_evict_first();
  const int cl = w_row(id);
  int li = 0;
  auto refill = [&](int sl) {
    if (li >= 32) return;
    const uint32_t fb = bar + B_RAWX + 8 * (g * 3 + sl);
    mbar_expect(fb, 8192);
    tma_ld3h(sb + OFF_XR + (g * 3 + sl) * 8192, &tm.x, (li >> 1) * 64, ((li & 1) ? 128 + (id & 31) : 2 * (id & 63) + g) * MT, id >> 6, fb, pol);
    li += (li & 1) || has_x2(id, li >> 1, g) ? 1 : 2;
  };
#pragma unroll 1
  for (int sl = 0; sl < 3; sl++) refill(sl);
  int xs = 0, xph = 0, yp = 0;
  int wrow = (rank * 2 + (cl >> 5)) * 128 + g * 64 + (cl & 31);
  mbar_wait(bar + B_STGW + 8 * g, 0);
  fence_async_smem();
  tma_st4(&tm.wst, sb + OFF_WS + g * 8192, 0, 0, 0, wrow);
  bulk_commit();
  const uint32_t pgmask = read_info(bar, 1);
#pragma unroll 1
  for (int n = 0; n < 32; n++) {
    unsigned freed = 128;
    if (n >= WR) asm volatile("ld.relaxed.gpu.global.u32 %0, [%1];" : "=r"(freed) : "l"(&ctr[(C_LOADED + n - WR) * 32]) : "memory");
    if (n < 16) {
#pragma unroll 1
      for (int j = 0; j < (has_x2(id, n, g) ? 2 : 1); j++) {
        const int t = j ? 128 + (id & 31) : 2 * (id & 63) + g;
        int par0, par1;
        const uint32_t off0 = x_base(id >> 6, n * 10 + (t >> 5), pgmask, par0), off1 = x_base(id >> 6, n * 10 + 5 + (t >> 5), pgmask, par1);
        const uint32_t buf = sb + OFF_XR + (g * 3 + xs) * 8192;
        mbar_wait(bar + B_STGX + 8 * (g * 3 + xs), xph);
        fence_async_smem();
        tma_st5(&tm.xst[par0], buf, (off0 + (par0 << 12) + (t & 31) * 128) >> 1);
        tma_st5(&tm.xst[par1], buf + 4096, (off1 + (par1 << 12) + (t & 31) * 128) >> 1);
        bulk_commit();
        bulk_wait_read<0>();
        refill(xs);
        if (++xs == 3) { xs = 0; xph ^= 1; }
      }
    }
    if (n > 16 + LW && n <= YFLUSH && (n - 17 - LW) % YSTEP == 0) {
      if (yp == 0 || yp == 3) mbar_wait(bar + B_Y + 8 * g, yp & 1);
#pragma unroll 1
      do {
        tma_st4(&tm.yst[0], sb + OFF_XR + (g * 3 + (yp < 3 ? yp : yp - 3)) * 8192, 0, yp * 32, id & 62, (id >> 6) * 4 + rank * 2 + g);
      } while (++yp < 2);
      bulk_commit();
      bulk_wait_read<0>();
      if (yp == 2) mbar_arrive(bar + B_YFREE + 8 * g);
    }
    if (freed < 128) flag_wait(&ctr[(C_LOADED + n - WR) * 32], 128);
    if (n) {
      mbar_wait(bar + B_STGW + 8 * g, n & 1);
      fence_async_smem();
      tma_st4(&tm.wst, sb + OFF_WS + g * 8192, 0, 0, 0, wrow);
      bulk_commit();
    }
    wrow += WCHUNK / 128;
    if (wrow >= WR * WCHUNK / 128) wrow -= WR * WCHUNK / 128;
    if (n < 30) {
      const int cp = chunk_of(n + 2) * 64 + cl, sl = g * 2 + (n & 1);
      mbar_expect(bar + B_RAWW + 8 * sl, 2048);
      tma_ld3h(sb + OFF_WRAW + sl * 2048, &tm.we + (cp >> 9), 0, 0, (cp & 511) * 8 + ((n + 2) >> 4) * 4 + rank * 2 + g, bar + B_RAWW + 8 * sl, pol);
    }
    if (n < 4) {
#pragma unroll 1
      for (int q = 4 + n; q < 16; q += 4) {
        const int cp = q * 64 + cl;
        tma_pf3(&tm.we + (cp >> 9), 0, 0, (cp & 511) * 8 + rank * 2 + g);
      }
    }
    bulk_wait<0>();
    mbar_arrive(bar + B_DONE + 8 * (n & 7));
    mbar_arrive(bar + B_RAWW + 8 * (g * 2 + ((n + 1) & 1)));
  }
  const int b = id >> 6, u = (id >> 1) & 31;
  flag_wait(&ctr[(C_LOADED + 31) * 32], 128);
#pragma unroll 1
  for (int p = 0; p < 5; p++) {
    mbar_wait(bar + B_YP + 8 * (g * 5 + p), 0);
    fence_async_smem();
    tma_st4(&tm.yst[1], sb + (p * 2 + g) * 8192, 0, p * 32, 2 * u, b * 4 + rank * 2 + g);
  }
  bulk_commit();
  bulk_wait<0>();
  mbar_arrive(bar + B_DONE);
#pragma unroll 1
  for (int i = 0; i < 10; i++) {
    const int hf = i >= 5, k = i - 5 * hf;
    mbar_wait(bar + B_OUT + 8 * (g * 5 + k), hf);
    fence_async_smem();
    tma_st3(&tm.out, sb + (hf ? 0 : k < 4 ? OFF_XR : OFF_H0B - 65536) + (2 * k + g) * 8192, (hf * 4 + rank * 2 + (u & 1)) * 64, ((u >> 1) * 10 + 2 * k + g) * MT, b);
    bulk_commit();
  }
  bulk_wait_read<0>();
  if (g == 0) PROF_T(12);
}

__global__ void __cluster_dims__(2, 1, 1) __launch_bounds__(512, 1)
k1_main(uint8_t* xbuf, const void* __restrict__ fimg, const __nv_bfloat16* __restrict__ gamma,
        const __nv_bfloat16* __restrict__ beta, const __grid_constant__ Maps tm) {
  extern __shared__ __align__(1024) uint8_t smem_raw[];
  const uint32_t sb = s2u(smem_raw);
  const uint32_t bar = sb + OFF_BAR;
  const int warp = __shfl_sync(0xffffffffu, threadIdx.x >> 5, 0);
  const int bid = blockIdx.x;
  unsigned* ctr = (unsigned*)(xbuf + CTR_OFF);
  const uint32_t rank = bid & 1;
  if (bid == 0 && threadIdx.x < 4) asm volatile("st.relaxed.gpu.global.u64 [%0], %1;" ::"l"(&ctr[C_REG * 32 + 2 * threadIdx.x]), "l"(1ull << 63) : "memory");
  if (warp >= 12) {
    asm volatile("setmaxnreg.dec.sync.aligned.u32 24;");
    asm volatile("barrier.cluster.arrive.relaxed.aligned;" ::: "memory");
    {
      const int lane = lane_id(), k = bid >> 1;
      if (rank == 0 || k < XPAGES) {
        const uint32_t off = rank ? (k << 21) + 0xb0000 : (XPAGES << 21) + ((k >> 6) << 18) + (((k >> 4) & 3) << 14) + (k & 15) * 128;
        const unsigned lat = probe(xbuf + off + (warp & 1) * 4096 + (warp & 2) * 1024, lane);
        if (lane == 0) asm volatile("st.shared.b32 [%0], %1;" ::"r"(bar + S_PROBE + 4 * (warp & 3)), "r"(lat) : "memory");
      }
      asm volatile("bar.sync 4, 128;" ::: "memory");
      asm volatile("barrier.cluster.wait.aligned;" ::: "memory");
      if (warp == 14 && lane == 0) {
        uint32_t l0, l1, l2, l3;
        asm volatile("ld.shared.v4.b32 {%0, %1, %2, %3}, [%4];" : "=r"(l0), "=r"(l1), "=r"(l2), "=r"(l3) : "r"(bar + S_PROBE) : "memory");
        const int near = min(l1, l3) < min(l0, l2);
        if (rank) {
          send_info(bar, 2, near);
        } else {
          unsigned long long add = 1ull << (8 * near), v, *reg = (unsigned long long*)&ctr[C_REG * 32];
          if (k < XPAGES) add += (unsigned long long)(read_info(bar, 2) ^ near ^ 1) << (16 + k);
          PROF_T(14);
          asm volatile("{\n.reg .pred p;\n.reg .u32 c;\nmov.u32 c, 0;\nAGAIN:\n"
                       "atom.relaxed.gpu.global.add.u64 %0, [%1], %2;\nsetp.lt.s64 p, %0, 0;\n@p bra DONE;\n"
                       "add.u32 c, c, 1;\nsetp.lt.u32 p, c, 0x100000;\n@p bra AGAIN;\ntrap;\nDONE:\n}" : "=l"(v) : "l"(reg), "l"(add) : "memory");
          const int ticket = (v >> (8 * near)) & 255;
          if (ticket < 32) send_info(bar, 0, near * 32 + ticket);
          PROF_T(15); PROF_V(16, near);
          asm volatile("{\n.reg .pred p;\n.reg .u32 c, a, b;\nmov.u32 c, 0;\nWAIT:\n"
                       "ld.relaxed.gpu.global.u64 %0, [%1];\ncvt.u32.u64 a, %0;\nbfe.u32 b, a, 8, 8;\nand.b32 a, a, 255;\nadd.u32 a, a, b;\n"
                       "setp.ge.u32 p, a, 66;\n@p bra DONE;\n"
                       "add.u32 c, c, 1;\nsetp.lt.u32 p, c, 0x400000;\n@p bra WAIT;\ntrap;\nDONE:\n}" : "=l"(v) : "l"(reg) : "memory");
          if (ticket >= 32) {
            const int j = ticket - 32 + (int)((v >> (8 * (near ^ 1))) & 255);
            send_info(bar, 0, j < 32 ? (near ^ 1) * 32 + j : (near == 0 && ticket == 32 && j == 33) ? 64 : 32 + j);
          }
          send_info(bar, 1, (uint32_t)(v >> 16));
          PROF_T(13);
        }
      }
      __syncwarp();
      const int role = read_info(bar, 0);
      if (role < 64 && warp - 12 < NFL && elect_one()) {
#pragma unroll 1
        for (int n = warp - 12; n < 33; n += NFL) {
          mbar_wait(bar + B_DONE + 8 * (n & 7), (n >> 3) & 1);
          fence_release();
          if (n < 32) {
            red_add(&ctr[(C_FLAG + n + C_SIDE * ((role >> 5) ^ 1)) * 32]);
            red_add(&ctr[(C_FLAG + n + C_SIDE * (role >> 5)) * 32]);
          } else {
            red_add(&ctr[(C_Y + rank + C_SIDE * (role >> 5)) * 32]);
          }
          if (n < 32) { PROF_T(64 + n); PROF_V(192 + n, tm0); } else { PROF_V(4, tm0); }
        }
      }
      if (role < 64 && warp == 15 && elect_one()) {
#pragma unroll 1
        for (int v = 0; v < 64; v++) {
          mbar_wait(bar + B_FULL + 8 * (v & 3), (v >> 2) & 1);
          mbar_arrive(bar + B_EMPTY + 8 * (v & 3));
          if ((v & 1) && (v < 2 * (32 - WR) || v == 63)) {
            red_add(&ctr[(C_LOADED + (v >> 1)) * 32]);
            red_add(&ctr[(C_LOADED + (v >> 1) + C_SIDE) * 32]);
          }
        }
      }
      __syncwarp();
    }
    asm volatile("barrier.cluster.arrive.relaxed.aligned;\nbarrier.cluster.wait.aligned;" ::: "memory");
    return;
  } else {
    if (elect_one()) {
      if (warp == 0) PROF_T(0);
      if (warp >= 6) asm volatile("prefetch.tensormap [%0];" ::"l"(&tm.x + (warp - 6)) : "memory");
      const int cnt = warp < 3 ? 1 : warp == 3 ? 5 : warp < 9 ? 4 : 2;
#pragma unroll
      for (int i = 0; i < 6; i++) mbar_init(bar + warp * 48 + 8 * i, cnt);
      if (warp == 1) {
        mbar_expect(bar + B_F, 8192);
        bulk_ld(sb + OFF_F, fimg, 8192, bar + B_F);
        mbar_expect(bar + B_ROLE, 4);
        mbar_expect(bar + B_ROLE + 8, 4);
        mbar_expect(bar + B_ROLE + 16, 4);
      }
      asm volatile("fence.mbarrier_init.release.cluster;" ::: "memory");
    }
    asm volatile("bar.sync 0, 384;" ::: "memory");
    asm volatile("barrier.cluster.arrive.relaxed.aligned;" ::: "memory");
    if (threadIdx.x == 64) PROF_T(20);
    if (bid < 128 && warp < 4 && elect_one()) {
      const int g = warp & 1;
      if (warp < 2) {
        tma_pf3(&tm.x, 0, (2 * (bid & 63) + g) * MT, bid >> 6);
        if (has_x2(bid, 0, g)) tma_pf3(&tm.x, 0, (128 + (bid & 31)) * MT, bid >> 6);
      } else {
        tma_pf3(&tm.we, 0, 0, (bid >> 1) * 8 + rank * 2 + g);
      }
    }
    __syncwarp();
  }
  if (warp >= 8) {
    asm volatile("setmaxnreg.dec.sync.aligned.u32 40;");
    asm volatile("barrier.cluster.wait.aligned;" ::: "memory");
    const int role = __shfl_sync(0xffffffffu, read_info(bar, 0), 0);
    const unsigned* lctr = ctr + (role >> 5) * C_SIDE * 32;
    if (role >= 64) {
    } else if (warp == 9 || warp == 10) {
      asm volatile("barrier.cluster.arrive.relaxed.aligned;" ::: "memory");
      if (elect_one()) {
        if (warp == 9) manager<0>(tm, lctr, sb, role * 2 + rank); else manager<1>(tm, lctr, sb, role * 2 + rank);
      }
      __syncwarp();
      asm volatile("barrier.cluster.wait.aligned;" ::: "memory");
      return;
    } else if (warp == 11) {
      if (elect_one()) {
        const uint8_t* ws = g_W + (size_t)((role & 31) * 2 + rank) * 2 * WBLK;
        int slot = 0;
#pragma unroll 1
        for (int n = 0; n < 32; n++) {
          const uint8_t* src = ws + (size_t)slot * WCHUNK;
          const uint32_t s8 = (n & 1) * 16, dst = sb + (n & 1) * 2 * G_STAGE;
          const int ph = ((n >> 1) & 1) ^ 1;
          if (++slot == WR) slot = 0;
          flag_wait(&lctr[(C_FLAG + n) * 32], 128);
          fence_async_global();
          PROF_T(32 + n);
#pragma unroll
          for (int h = 0; h < 2; h++) {
            mbar_wait(bar + B_EMPTY + s8 + 8 * h, ph);
            mbar_expect(bar + B_FULL + s8 + 8 * h, WBLK);
            bulk_ld(dst + h * G_STAGE, src + h * WBLK, WBLK, bar + B_FULL + s8 + 8 * h);
          }
        }
      }
      __syncwarp();
    } else {
      if (elect_one()) {
        const uint32_t pgmask = read_info(bar, 1);
        PROF_T(1);
        const int b = role >> 5, u = role & 31;
        const int dq = rank * 2 + (u & 1), t0 = (u >> 1) * 10;
        const uint64_t pef = policy_evict_first(), pen = policy_evict_unchanged();
        const uint8_t* xs = xbuf + ((((u >> 1) & 3) << 14) | (((u >> 3) & 1) << 18) | ((u >> 4) << 20) | ((u & 1) << 13));
#pragma unroll 1
        for (int n = 0; n < 32; n++) {
          const int c = chunk_of(n);
          const uint64_t polx = (n < XKEEP || n >= 16) ? pef : pen;
          const uint32_t s8 = (n & 1) * 16, dst = sb + (n & 1) * 2 * G_STAGE + WBLK + rank * 8192;
          const int ph = ((n >> 1) & 1) ^ 1;
          uint32_t xo[6];
#pragma unroll
          for (int g = 0; g < 6; g++) {
            int par;
            xo[g] = x_base(b, c * 10 + (g / 3) * 5 + rank * 2 + g % 3, pgmask, par);
            xo[g] += ((par ^ u) & 1) << 12;
            asm volatile("" : "+r"(xo[g]));
          }
          if (n < 16) {
            flag_wait(&lctr[(C_FLAG + n) * 32], 128);
            fence_async_global();
          }
#pragma unroll
          for (int h = 0; h < 2; h++) {
            const uint32_t fb = bar + B_FULL + s8 + 8 * h;
            mbar_wait(bar + B_EMPTY + s8 + 8 * h, ph);
            mbar_expect(fb, XBLK);
#pragma unroll
            for (int g = 0; g < 3; g++) {
              const int skip = (g == 0 && rank) ? 2048 : 0, len = (g == (rank ? 0 : 2)) ? 2048 : 4096;
              bulk_ld_mc_h(dst + h * G_STAGE + g * 4096 + skip, xs + xo[3 * h + g] + skip, len, fb, 3, polx);
            }
          }
        }
        flag_wait(&ctr[C_E * 32], 4);
        flag_wait(&lctr[(C_FLAG + YFLUSH) * 32], 128);
        fence_async_global();
        mbar_expect(bar + B_H0C, 6 * 8192);
        for (int i = 0; i < 3; i++) tma_ld2(sb + OFF_XR + i * 16384, &tm.yld[0], 0, ((b * 4 + dq) * NT + t0 + 2 * i) * 64, bar + B_H0C);
        static_assert(YFLUSH >= 23, "phase of the B_DONE ring");
        mbar_wait(bar + B_DONE + 8 * 7, 1);
        mbar_expect(bar + B_H0, 2 * 8192 + 7168 + 5120 + 512);
        bulk_ld(sb + OFF_F, g_Gimg, 7168, bar + B_H0);
        tma_ld2(sb + OFF_WS, &tm.yld[0], 0, ((b * 4 + dq) * NT + t0 + 6) * 64, bar + B_H0);
        tma_pf2(&tm.yld[0], 0, ((b * 4 + dq) * NT + t0 + 8) * 64);
        for (int hf = 0; hf < 2; hf++) {
          bulk_ld(sb + OFF_E + hf * 2560, g_E + ((b * 8 + hf * 4 + dq) * NT + t0) * 64, 2560, bar + B_H0);
          bulk_ld(sb + OFF_GB + hf * 256, gamma + (hf * 4 + dq) * 64, 128, bar + B_H0);
          bulk_ld(sb + OFF_GB + hf * 256 + 128, beta + (hf * 4 + dq) * 64, 128, bar + B_H0);
        }
        mbar_wait(bar + B_EMPTY + 8 * 2, 1);
        mbar_expect(bar + B_H0 + 8, 16384);
        tma_ld2(sb + OFF_H0B, &tm.yld[0], 0, ((b * 4 + dq) * NT + t0 + 8) * 64, bar + B_H0 + 8);
        flag_wait(&lctr[(C_Y + rank) * 32], 32);
        fence_async_global();
        PROF_T(5);
        for (int i = 0; i < 5; i++) {
          const uint32_t fb = bar + B_H1 + 8 * (i >> 1);
          if ((i & 1) == 0) mbar_expect(fb, i < 4 ? 32768 : 16384);
          tma_ld2(sb + i * 16384, &tm.yld[1], 0, ((b * 4 + dq) * NT + t0 + 2 * i) * 64, fb);
        }
      }
      __syncwarp();
      const int lane = lane_id();
      unsigned old = 0;
      if (lane == 0) old = atomicAdd(&ctr[C_EXIT * 32], 1);
      if (__shfl_sync(0xffffffffu, old, 0) == 127) {
#pragma unroll
        for (int i = 0; i < 6; i++) *(uint4*)&ctr[((i >> 1) * 128 + (i & 1) * C_SIDE + lane) * 32] = make_uint4(0, 0, 0, 0);
      }
    }
    asm volatile("barrier.cluster.arrive.relaxed.aligned;\nbarrier.cluster.wait.aligned;" ::: "memory");
  } else {
    asm volatile("setmaxnreg.inc.sync.aligned.u32 224;");
    const int wg = warp >> 2, w = warp & 3;
    int lane = lane_id();
    asm volatile("barrier.cluster.wait.aligned;" ::: "memory");
    mbar_wait(bar + B_F, 0);
    const int id = __shfl_sync(0xffffffffu, read_info(bar, 0), 0) * 2 + rank;
    if (id >= 128) {
      float ea[80], eb[80];
      const int b = (id >> 1) & 1;
      constexpr int ES = 32768 + 2 * XBLK;
#pragma unroll 1
      for (int k = -3; k < 8; k++) {
        const int sl = (k + 3) % 3;
        if (k >= 0) {
          mbar_wait(bar + B_RAWX + 8 * sl, (k / 3) & 1);
          const uint64_t da = mk_desc(sb + sl * ES + wg * 16384), db = mk_desc(sb + sl * ES + 32768);
          wg_fence();
#pragma unroll
          for (int kk = 0; kk < 8; kk++) {
            const uint64_t a0 = da + (kk & 3) * 128, b0 = db + (kk & 3) * 2 + (kk >> 2) * (XBLK >> 4);
            wgmma_main<1>(ea, a0, b0, (k | kk) != 0);
            wgmma_main<1>(eb, a0 + 512, b0, (k | kk) != 0);
          }
          wg_commit();
          wg_wait<0>();
          asm volatile("bar.sync 3, 256;" ::: "memory");
        }
        if (k + 3 < 8 && warp == 0 && elect_one()) {
          if (k == -3) {
            for (int i = 0; i < 64; i++) {
              unsigned v;
              asm volatile("ld.relaxed.gpu.global.u32 %0, [%1];" : "=r"(v) : "l"(&ctr[(C_FLAG + 14) * 32]) : "memory");
              if (v >= 128) break;
              __nanosleep(500);
            }
          }
          const uint32_t dst = sb + sl * ES, fb = bar + B_RAWX + 8 * sl;
          mbar_expect(fb, ES);
          for (int q = 0; q < 4; q++) tma_ld2(dst + q * 8192, &tm.w30, rank * 256 + q * 64, (k + 3) * 64, fb);
          for (int q = 0; q < 2; q++) tma_ld3(dst + 32768 + q * XBLK, &tm.xe[q], (k + 3) * 64, 0, b, fb);
        }
        __syncwarp();
      }
      fence_regs(ea);
      fence_regs(eb);
      float* e0 = g_E + ((b * 8 + rank * 4 + wg * 2) * NT + 2 * (lane & 3)) * 64 + 16 * w + (lane >> 2);
#pragma unroll
      for (int i = 0; i < 80; i++) {
        const int o = (8 * (i >> 2) + (i & 1)) * 64 + ((i >> 1) & 1) * 8;
        e0[o] = ea[i];
        e0[o + NT * 64] = eb[i];
      }
      asm volatile("bar.sync 3, 256;" ::: "memory");
      if (threadIdx.x == 0) {
        fence_release();
        red_add(&ctr[C_E * 32]);
        PROF_T(28);
      }
      asm volatile("barrier.cluster.arrive.relaxed.aligned;\nbarrier.cluster.wait.aligned;" ::: "memory");
      return;
    }
    if (w < 2 && elect_one()) {
      const uint32_t fb = bar + B_RAWW + 8 * (wg * 2 + w);
      mbar_expect(fb, 2048);
      tma_ld3h(sb + OFF_WRAW + (wg * 2 + w) * 2048, &tm.we, 0, 0, (w * 64 + w_row(id)) * 8 + rank * 2 + wg, fb, policy_evict_first());
      if (!w) mbar_arrive(fb);
    }
    __syncwarp();
    {
      float yr[80], yi[80], t[32];

      int xs = 0, xph = 0;
      if (threadIdx.x == 0) PROF_T(24);
      W_WAIT(0);
      t_issue<false>(t, sb, WRAW(0));
      wg_wait<0>();
      W_FINISH();
      if (threadIdx.x == 0) PROF_T(25);
#pragma unroll 1
      for (int m = 0; m <= LW; m++) {
        X_WAIT();
        X_ISSUE();
        wg_wait<0>();
        X_FINISH((2 * id + wg) & 7);
        if (threadIdx.x == 0 && m == 0) PROF_T(26);
        if (has_x2(id, m, wg)) {
          X_WAIT();
          X_ISSUE();
          wg_wait<0>();
          X_FINISH(id & 7);
        }
        if (m < LW && m) {
          W_WAIT(m);
          t_issue<false>(t, sb, WRAW(m));
          wg_wait<0>();
          W_FINISH();
        }
      }
      if (threadIdx.x == 0) PROF_T(27);
      const int ym = lane >> 3, yr8 = lane & 7;
      const uint32_t yad = (ym >> 1) * 4096 + yr8 * 128 + (((2 * w + (ym & 1)) ^ yr8) << 4);
#define STAGE_PROF0()
#define STAGE_PROF1()
#define STAGE_BEGIN() PROF_W(wfull, mbar_wait(bar + B_FULL + 8 * (v & 3), (v >> 2) & 1)); STAGE_PROF0(); const uint32_t st = sb + (v & 3) * G_STAGE
#define RELEASE(vv) do { if (w == 0 && lane < 2) mbar_arrive_cluster(bar + B_EMPTY + 8 * ((vv) & 3), lane, 1); } while (0)
#define XRAW (sb + OFF_XR + (wg * 3 + xs) * 8192)
#define STAGE_W0(mw, sd) do { W_WAIT(mw); batch<1, 0, 2>(yr, yi, t, st, wg, sd, sb + OFF_F, WRAW(mw)); wg_wait<1>(); W_FINISH(); wg_wait<0>(); RELEASE(v); } while (0)
#define STAGE_PLAIN0(sd) do { batch<0, 0, 2>(yr, yi, t, st, wg, sd, 0, 0); wg_wait<0>(); RELEASE(v); } while (0)
#define STAGE_W1(mw, sd) do { W_WAIT(mw); batch<1, 0, 1>(yr, yi, t, st, wg, sd, sb + OFF_F, WRAW(mw)); wg_wait<1>(); if (sd) RELEASE(v - 1); \
                              W_FINISH(); batch<0, 1, 2>(yr, yi, t, st, wg, 1, 0, 0); } while (0)
#define STAGE_PLAIN1(sd) do { batch<0, 0, 1>(yr, yi, t, st, wg, sd, 0, 0); wg_wait<1>(); if (sd) RELEASE(v - 1); \
                              batch<0, 1, 2>(yr, yi, t, st, wg, 1, 0, 0); } while (0)
#pragma unroll 1
      for (int v = 0; v < 32; v++) {
        const int m = ((v + 1) >> 1) + LW;
        STAGE_BEGIN();
        if (!(v & 1) || v == 31) {
          STAGE_W1(m, v != 0);
        } else if (m >= 16) {
          STAGE_PLAIN1(1);
        } else {
          X_WAIT();
          batch<4, 0, 1>(yr, yi, t, st, wg, 1, sb + OFF_F, XRAW);
          wg_wait<1>();
          RELEASE(v - 1);
          X_FINISH((2 * id + wg) & 7);
          if (has_x2(id, m, wg)) {
            X_WAIT();
            batch<4, 1, 2>(yr, yi, t, st, wg, 1, sb + OFF_F, XRAW);
            wg_wait<1>();
            X_FINISH(id & 7);
          } else {
            batch<0, 1, 2>(yr, yi, t, st, wg, 1, 0, 0);
          }
        }
        STAGE_PROF1();
      }
      wg_wait<0>();
      fence_regs(yr);
      fence_regs(yi);
      RELEASE(31);
      {
        uint32_t hold[32];
#pragma unroll
        for (int j = 0; j < 20; j++) {
          const uint32_t p0 = pack2(yr[4 * j], yr[4 * j + 1]), p1 = pack2(yr[4 * j + 2], yr[4 * j + 3]);
          const uint32_t p2 = pack2(yi[4 * j], yi[4 * j + 1]), p3 = pack2(yi[4 * j + 2], yi[4 * j + 3]);
          if (j < 12) {
            stsm4t(sb + OFF_XR + wg * 3 * 8192 + yad + (j >> 2) * 8192 + (j & 3) * 1024, p0, p1, p2, p3);
          } else {
            hold[4 * j - 48] = p0; hold[4 * j - 47] = p1; hold[4 * j - 46] = p2; hold[4 * j - 45] = p3;
          }
        }
#pragma unroll
        for (int j = 0; j < 32; j++) asm volatile("" : "+r"(hold[j])::"memory");
        fence_async_smem();
        __syncwarp();
        if (lane == 0) mbar_arrive(bar + B_Y + 8 * wg);
        if (threadIdx.x == 0) PROF_T(2);
#pragma unroll
        for (int v = 32; v < 34; v++) {
          STAGE_BEGIN();
          STAGE_PLAIN0(v != 32);
          STAGE_PROF1();
        }
        mbar_wait(bar + B_YFREE + 8 * wg, 0);
#pragma unroll
        for (int j = 0; j < 8; j++)
          stsm4t(sb + OFF_XR + wg * 3 * 8192 + yad + (j >> 2) * 8192 + (j & 3) * 1024, hold[4 * j], hold[4 * j + 1], hold[4 * j + 2], hold[4 * j + 3]);
        fence_async_smem();
        __syncwarp();
        if (lane == 0) mbar_arrive(bar + B_Y + 8 * wg);
#pragma unroll
        for (int j = 0; j < 32; j++) t[j] = __uint_as_float(hold[j]);
      }
#pragma unroll 1
      for (int v = 34; v < 64; v++) {
        const int m = (v >> 1) + LW;
        STAGE_BEGIN();
        if (!(v & 1) && m < 32) {
          STAGE_W0(m, 1);
        } else {
          STAGE_PLAIN0(1);
          if (v == 49 && wg == 0) part_ptr(xbuf, id >> 6, w >> 1, rank * 2 + ((id >> 1) & 1), (id >> 2) & 15)[(w & 1) * 32 + lane] = ~0ull;
        }
        STAGE_PROF1();
      }
      wg_wait<0>();
      fence_regs(yr);
      fence_regs(yi);
      asm volatile("bar.sync 3, 256;" ::: "memory");
#pragma unroll
      for (int j = 0; j < 20; j++) {
        stsm4t(sb + wg * 8192 + yad + (j >> 2) * 16384 + (j & 3) * 1024, pack2(yr[4 * j], yr[4 * j + 1]), pack2(yr[4 * j + 2], yr[4 * j + 3]),
               pack2(yi[4 * j], yi[4 * j + 1]), pack2(yi[4 * j + 2], yi[4 * j + 3]));
        if ((j & 3) == 3) {
          __syncwarp();
          if (lane == 0) mbar_arrive(bar + B_YP + 8 * (wg * 5 + (j >> 2)));
        }
      }
      if (threadIdx.x == 0) PROF_T(3);
    }
    asm volatile("barrier.cluster.arrive.relaxed.aligned;" ::: "memory");
    lane = lane_id();
    const int tid = warp * 32 + lane, b = id >> 6, u = (id >> 1) & 31;
    const int dq = rank * 2 + (u & 1), tr = u >> 1;
    const int a = lane & 3, d0 = 16 * w + (lane >> 2);
    float2* s_red = (float2*)(smem_raw + OFF_WRAW);
    const uint32_t oad = wg * 8192 + ((lane >> 4) * 8 + (lane & 7)) * 128 + (((2 * w + ((lane >> 3) & 1)) ^ (lane & 7)) << 4);
#pragma unroll 1
    for (int hf = 0; hf < 2; hf++) {
      const uint32_t base = sb + (hf ? 0 : OFF_XR), last = hf ? 0 : OFF_H0B - 65536 - OFF_XR;
      float acc[5][28];
      float q1[4] = {0.f, 0.f, 0.f, 0.f}, q2[4] = {0.f, 0.f, 0.f, 0.f};
      if (hf == 0) { mbar_wait(bar + B_H0, 0); mbar_wait(bar + B_H0C, 0); }
      const float* se = (const float*)(smem_raw + OFF_E + hf * 2560) + wg * 64 + d0;
#pragma unroll
      for (int k2 = 0; k2 < 4; k2++) {
        if (k2 < 3) {
          if (hf) mbar_wait(bar + B_H1 + 8 * k2, 0);
          else if (k2 == 2) mbar_wait(bar + B_H0 + 8, 0);
          const uint64_t da = mk_desc(base + (4 * k2 + wg) * 8192 + (k2 == 2 ? last : 0)), db = mk_desc(sb + OFF_F);
          wg_fence();
#pragma unroll
          for (int kk = 0; kk < 4; kk++) {
            wgmma_inv<1>(acc[2 * k2], da + 128 * kk, db + 2 * kk, kk);
            if (k2 < 2) wgmma_inv<1>(acc[2 * k2 + 1], da + 1024 + 128 * kk, db + 2 * kk, kk);
          }
          wg_commit();
        }
        if (k2 > 0) {
          if (k2 < 3) wg_wait<1>(); else wg_wait<0>();
#pragma unroll
          for (int k = 2 * k2 - 2; k < 2 * k2 && k < 5; k++) {
            fence_regs(acc[k]);
            if (a == 0) {
              acc[k][25] += se[k * 128];
              acc[k][27] += se[k * 128 + 8];
            }
            if (k == 4 && tr == 15 && wg == 1) {
#pragma unroll
              for (int i = 16; i < 28; i++)
                if (8 * (i >> 2) + (i & 1) + 2 * a >= LOUT - (NT - 1) * MT) acc[k][i] = 0.f;
            }
#pragma unroll
            for (int i = 0; i < 28; i++) {
              q1[i & 3] += acc[k][i];
              q2[i & 3] = fmaf(acc[k][i], acc[k][i], q2[i & 3]);
            }
            fence_regs(q1);
            fence_regs(q2);
          }
        }
      }
      float s1[2] = {q1[0] + q1[1], q1[2] + q1[3]}, s2[2] = {q2[0] + q2[1], q2[2] + q2[3]};
#pragma unroll
      for (int i = 0; i < 2; i++) {
#pragma unroll
        for (int o = 1; o < 4; o <<= 1) {
          s1[i] += __shfl_xor_sync(0xffffffffu, s1[i], o);
          s2[i] += __shfl_xor_sync(0xffffffffu, s2[i], o);
        }
      }
      if (a == 0) {
        s_red[wg * 64 + d0] = make_float2(s1[0], s2[0]);
        s_red[wg * 64 + d0 + 8] = make_float2(s1[1], s2[1]);
      }
      asm volatile("bar.sync 3, 256;" ::: "memory");
      if (tid == 0) PROF_T(6 + 3 * hf);
      if (tid < 64) {
        const float2 p0 = s_red[tid], p1 = s_red[64 + tid];
        const float x1 = p0.x + p1.x, x2 = p0.y + p1.y;
        const unsigned long long v = ((unsigned long long)(__float_as_uint(x2) & 0x7fffffffu) << 32) | __float_as_uint(x1);
        asm volatile("st.relaxed.gpu.global.u64 [%0], %1;" ::"l"(part_ptr(xbuf, b, hf, dq, tr) + tid), "l"(v) : "memory");
      }
      {
        const unsigned long long* q = part_ptr(xbuf, b, hf, dq, (tid >> 6) * 4) + (tid & 63);
        unsigned long long v[4];
        poll64x4(q, v);
        float x1 = 0.f, x2 = 0.f;
#pragma unroll
        for (int i = 0; i < 4; i++) {
          x1 += __uint_as_float((uint32_t)v[i]);
          x2 += __uint_as_float((uint32_t)(v[i] >> 32));
        }
        s_red[128 + tid] = make_float2(x1, x2);
      }
      asm volatile("bar.sync 3, 256;" ::: "memory");
      if (tid == 0) PROF_T(7 + 3 * hf);
#pragma unroll
      for (int i = 0; i < 2; i++) {
        const float2 q0 = s_red[128 + d0 + 8 * i], q1 = s_red[192 + d0 + 8 * i], q2 = s_red[256 + d0 + 8 * i], q3 = s_red[320 + d0 + 8 * i];
        const float mu = ((q0.x + q1.x) + (q2.x + q3.x)) * (1.f / LOUT);
        const float var = fmaxf(((q0.y + q1.y) + (q2.y + q3.y)) * (1.f / LOUT) - mu * mu, 0.f);
        const __nv_bfloat16* gb = (const __nv_bfloat16*)(smem_raw + OFF_GB + hf * 256) + d0 + 8 * i;
        s1[i] = 0.5f * __bfloat162float(gb[0]) * rsqrtf(var + 1e-5f);
        s2[i] = 0.5f * __bfloat162float(gb[64]) - mu * s1[i];
      }
#pragma unroll
      for (int k = 0; k < 5; k++) {
        float hz[28];
#pragma unroll
        for (int i = 0; i < 28; i++) hz[i] = fmaf(acc[k][i], s1[(i >> 1) & 1], s2[(i >> 1) & 1]);
        gelu_store(hz, base + oad + k * 16384 + (k == 4 ? last : 0));
        float z;
        asm volatile("ld.volatile.shared.f32 %0, [%1];" : "=f"(z) : "r"(sb + OFF_F + 55 * 128) : "memory");
        s2[0] += z;
        s2[1] += z;
        __syncwarp();
        if (lane == 0) mbar_arrive(bar + B_OUT + 8 * (wg * 5 + k));
      }
      if (tid == 0) PROF_T(8 + 3 * hf);
    }
    asm volatile("barrier.cluster.wait.aligned;" ::: "memory");
  }
}

typedef CUresult (*EncFn)(CUtensorMap*, CUtensorMapDataType, cuuint32_t, void*, const cuuint64_t*, const cuuint64_t*, const cuuint32_t*,
                          const cuuint32_t*, CUtensorMapInterleave, CUtensorMapSwizzle, CUtensorMapL2promotion, CUtensorMapFloatOOBfill);

void encode(EncFn fn, CUtensorMap* m, int rank, void* base, const cuuint64_t* dims, const cuuint64_t* strides, const cuuint32_t* box,
            CUtensorMapL2promotion promo) {
  cuuint32_t es[5] = {1, 1, 1, 1, 1};
  fn(m, CU_TENSOR_MAP_DATA_TYPE_BFLOAT16, rank, base, dims, strides, box, es, CU_TENSOR_MAP_INTERLEAVE_NONE, CU_TENSOR_MAP_SWIZZLE_128B, promo,
     CU_TENSOR_MAP_FLOAT_OOB_FILL_NONE);
}

}

extern "C" void kernel_launch(void* const* d_in, const int* in_sizes, int n_in, void* d_out, int out_size) {
  (void)in_sizes; (void)n_in; (void)out_size;
  const __nv_bfloat16* x = (const __nv_bfloat16*)d_in[0];
  const __nv_bfloat16* w = (const __nv_bfloat16*)d_in[1];
  const __nv_bfloat16* gamma = (const __nv_bfloat16*)d_in[2];
  const __nv_bfloat16* beta = (const __nv_bfloat16*)d_in[3];
  void* fnp = nullptr;
  cudaDriverEntryPointQueryResult qr;
  cudaGetDriverEntryPoint("cuTensorMapEncodeTiled", &fnp, cudaEnableDefault, &qr);
  EncFn fn = (EncFn)fnp;
  void *fptr = nullptr, *xptr = nullptr, *wptr = nullptr, *yptr = nullptr;
  cudaGetSymbolAddress(&fptr, g_Fimg);
  cudaGetSymbolAddress(&xptr, g_X);
  cudaGetSymbolAddress(&wptr, g_W);
  cudaGetSymbolAddress(&yptr, g_Y);
  xptr = (void*)(((uintptr_t)xptr + (1u << 21) - 1) & ~(uintptr_t)((1u << 21) - 1));
  const CUtensorMapL2promotion P0 = CU_TENSOR_MAP_L2_PROMOTION_NONE, P128 = CU_TENSOR_MAP_L2_PROMOTION_L2_128B;
  Maps m;
  {
    cuuint64_t d[3] = {1024, 8000, 2}, s[2] = {2048, 8000ull * 2048};
    cuuint32_t bx[3] = {64, 64, 1};
    encode(fn, &m.x, 3, (void*)x, d, s, bx, P128);
  }
  for (int ph = 0; ph < 2; ph++) {
    cuuint64_t d[3] = {64, (cuuint64_t)(16 - ph), 4096}, s[2] = {2ull * 262144 * 2, 128};
    cuuint32_t bx[3] = {64, 16, 1};
    encode(fn, ph ? &m.wo : &m.we, 3, (void*)(w + (size_t)ph * 262144), d, s, bx, P128);
  }
  for (int par = 0; par < 2; par++) {
    cuuint64_t d[5] = {(cuuint64_t)XPAGES << 20, 2, 4, 2, 2}, s[4] = {par ? 0x1000u : 0x3000u, 1u << 14, 1u << 18, 1u << 20};
    cuuint32_t bx[5] = {64, 2, 4, 2, 2};
    encode(fn, &m.xst[par], 5, xptr, d, s, bx, P0);
  }
  {
    cuuint64_t d[4] = {64, 32, 2, (cuuint64_t)WR * WCHUNK / 128}, s[3] = {4ull * WBLK, 4096, 128};
    cuuint32_t bx[4] = {64, 32, 2, 1};
    encode(fn, &m.wst, 4, wptr, d, s, bx, P0);
  }
  for (int p = 0; p < 2; p++) {
    void* base = p ? wptr : yptr;
    cuuint64_t d[4] = {64, NT, 64, 8}, s[3] = {8192, 128, (cuuint64_t)NT * 8192};
    cuuint32_t bx[4] = {64, 32, 2, 1};
    encode(fn, &m.yst[p], 4, base, d, s, bx, P0);
    cuuint64_t d2[2] = {64, 8ull * NT * 64}, s2[1] = {128};
    cuuint32_t bx2[2] = {64, 128};
    encode(fn, &m.yld[p], 2, base, d2, s2, bx2, P128);
  }
  {
    cuuint64_t d[3] = {512, LOUT, 2}, s[2] = {1024, (cuuint64_t)LOUT * 1024};
    cuuint32_t bx[3] = {64, MT, 1};
    encode(fn, &m.out, 3, d_out, d, s, bx, P0);
  }
  for (int q = 0; q < 2; q++) {
    cuuint64_t d[3] = {512, (cuuint64_t)(NT - q), 2}, s[2] = {MT * 2048, 8000ull * 2048};
    cuuint32_t bx[3] = {64, NT, 1};
    encode(fn, &m.xe[q], 3, (void*)(x + q * 64 * 1024), d, s, bx, P128);
  }
  {
    cuuint64_t d[2] = {512, 512}, s[1] = {1024};
    cuuint32_t bx[2] = {64, 64};
    encode(fn, &m.w30, 2, (void*)(w + 30 * 262144), d, s, bx, P128);
  }
  cudaFuncSetAttribute(k1_main, cudaFuncAttributeMaxDynamicSharedMemorySize, SMEM_BYTES);
  k1_main<<<132, 512, SMEM_BYTES>>>((uint8_t*)xptr, fptr, gamma, beta, m);
}
```

```cpp
#include <cuda_runtime.h>
#include <cuda_bf16.h>
#include <cuda.h>
#include <stdint.h>

namespace {

constexpr int LOUT = 7985;
constexpr int MT = 50;
constexpr int NT = 160;
constexpr int XBLK = NT * 128;
constexpr int WBLK = 16384;
#define XF 0
#define NS_ 10
#define LW_ 4
constexpr int LW = LW_;
constexpr int WR = NS_;
constexpr int WSLOT = 64 * WBLK;
constexpr int XPAGES = 20;
constexpr int NFL = 2;
constexpr int XKEEP = 9;
constexpr int YFLUSH = 20 + LW;

__device__ __align__(1024) uint8_t g_X[(XPAGES + 2) << 21];
__device__ __align__(1024) uint8_t g_W[(size_t)(WR > 10 ? WR : 10) * WSLOT];
__device__ __align__(1024) uint8_t g_Y[8ull * NT * 8192];
__device__ __align__(128) float g_E[16 * NT * 64];
constexpr int CTR_OFF = (XPAGES << 21) + 0x100000, PART_OFF = CTR_OFF + 0x40000;
constexpr int C_FLAG = 0, C_LOADED = 128  , C_Y = 256, C_E = 258, C_REG = 259, C_EXIT = 260, C_SIDE = 32;
__device__ __forceinline__ unsigned long long* part_ptr(uint8_t* xbuf, int side, int hf, int dq, int tr) {
  return (unsigned long long*)(xbuf + PART_OFF + ((hf * 4 + dq) * 2 + (tr >> 3)) * 8192 + ((side ^ hf ^ (tr >> 3)) << 12) + (tr & 7) * 512);
}
#define PROF_T(i)
#define PROF_C(i)
#define PROF_V(i, v)
#define PROF_W(acc, stmt) stmt

__device__ __align__(128) const uint32_t g_Fimg[2048] = {
 0x3f803f80,0x3f7d3f7f,0x3f783f7b,0x3f713f75,0x3f673f6d,0x3f5c3f62,0x3f4e3f55,0x3f3e3f46,0x3f2c3f35,0x3f183f22,0x3f043f0e,0x3edb3ef1,0x3eac3ec4,0x3e793e95,0x3e163e48,0x3d493dc9,
 0xbd490000,0xbe16bdc9,0xbe79be48,0xbeacbe95,0xbedbbec4,0xbf04bef1,0xbf18bf0e,0xbf2cbf22,0xbf3ebf35,0xbf4ebf46,0xbf5cbf55,0xbf67bf62,0xbf71bf6d,0xbf78bf75,0xbf7dbf7b,0xbf80bf7f,
 0x3e793ec4,0xbd493dc9,0xbeacbe48,0xbf18bef1,0x3f7d3f80,0x3f673f75,0x3f3e3f55,0x3f043f22,0xbf5cbf6d,0xbf2cbf46,0xbedbbf0e,0xbe16be95,0xbf4ebf35,0xbf71bf62,0xbf80bf7b,0xbf78bf7f,
 0x3f783f6d,0x3f803f7f,0x3f713f7b,0x3f4e3f62,0x3e160000,0x3edb3e95,0x3f2c3f0e,0x3f5c3f46,0xbf04bec4,0xbf3ebf22,0xbf67bf55,0xbf7dbf75,0x3f183f35,0x3eac3ef1,0x3d493e48,0xbe79bdc9,
 0xbf04bf35,0xbd49be95,0x3edb3e48,0x3f4e3f22,0x3f7d3f6d,0x3f713f7f,0x3f2c3f55,0x3e793ef1,0x3f783f80,0x3f3e3f62,0x3eac3f0e,0xbe163dc9,0xbf18bec4,0xbf67bf46,0xbf80bf7b,0xbf5cbf75,
 0x3f5c3f35,0x3f803f75,0x3f673f7b,0x3f183f46,0x3e163ec4,0xbeacbdc9,0xbf3ebf0e,0xbf78bf62,0xbe790000,0xbf2cbef1,0xbf71bf55,0xbf7dbf7f,0xbf4ebf6d,0xbedbbf22,0x3d49be48,0x3f043e95,
 0xbf2cbec4,0xbf7dbf62,0xbf5cbf7b,0xbeacbf22,0x3f673f35,0x3f783f7f,0x3f183f55,0xbd493e95,0xbf80bf6d,0xbf4ebf75,0xbe79bf0e,0x3edb3dc9,0x3f713f80,0x3f043f46,0xbe163e48,0xbf3ebef1,
 0x3f3e3f6d,0x3e163ef1,0xbf04be48,0xbf71bf46,0xbedbbf35,0x3e79bdc9,0x3f4e3f0e,0x3f803f75,0x3d493ec4,0xbf18be95,0xbf78bf55,0xbf67bf7f,0x3eac0000,0x3f5c3f22,0x3f7d3f7b,0x3f2c3f62,
 0xbedb0000,0xbf78bf46,0xbf4ebf7b,0xbd49bef1,0x3f3e3ec4,0x3f7d3f75,0x3f043f55,0xbeac3dc9,0xbf71bf35,0xbf5cbf7f,0xbe16bf0e,0x3f2c3e95,0x3f803f6d,0x3f183f62,0xbe793e48,0xbf67bf22,
 0x3f673f80,0x3e793f22,0xbf18be48,0xbf80bf62,0xbf2cbf6d,0x3e16be95,0x3f5c3f0e,0x3f713f7f,0x3eac3f35,0xbf04bdc9,0xbf7dbf55,0xbf3ebf75,0x3d49bec4,0x3f4e3ef1,0x3f783f7b,0x3edb3f46,
 0xbf7dbf6d,0xbeacbf46,0x3f2c3e48,0x3f783f75,0x3f040000,0x3f803f62,0x3edb3f55,0xbf18bdc9,0x3f4e3ec4,0x3f673f7f,0x3d493f0e,0xbf5cbef1,0x3e793f35,0xbf3ebe95,0xbf71bf7b,0xbe16bf22,
 0x3e16bec4,0x3f713f22,0x3f3e3f7b,0xbe793e95,0x3f5c3f80,0xbd493ef1,0xbf67bf0e,0xbf4ebf7f,0x3f183f6d,0xbedb3dc9,0xbf80bf55,0xbf04bf62,0xbf78bf35,0xbf2cbf75,0x3eacbe48,0x3f7d3f46,
 0x3f7d3f35,0x3edb3f62,0xbf3ebe48,0xbf5cbf7f,0x3e79bec4,0x3f803f46,0x3eac3f55,0xbf4ebe95,0xbf180000,0xbf71bf75,0x3d49bf0e,0x3f783f22,0x3f043f6d,0xbf2cbdc9,0xbf67bf7b,0x3e16bef1,
 0xbe16bf35,0x3f673ef1,0x3f2c3f7b,0xbf043dc9,0xbf78bf6d,0xbd49bf22,0x3f713f0e,0x3f183f75,0x3f4e3f80,0xbeac3e95,0xbf80bf55,0xbe79bf46,0x3f5c3ec4,0x3f3e3f7f,0xbedb3e48,0xbf7dbf62,
 0xbedbbf6d,0x3f5c3e95,0x3f183f7b,0xbf3ebdc9,0xbd49bf35,0x3f7d3f22,0x3e793f55,0xbf71bef1,0x3eacbec4,0x3f783f62,0xbe163f0e,0xbf80bf46,0x3f2c0000,0x3f4e3f7f,0xbf043e48,0xbf67bf75,
 0x3f673ec4,0x3f043f75,0xbf4ebe48,0xbf2cbf7f,0x3f803f35,0x3e163f46,0xbf78bf0e,0xbeacbf62,0x3f713f6d,0xbe793ef1,0xbf7dbf55,0x3d49bf22,0x3f3e3f80,0xbf183dc9,0xbf5cbf7b,0x3edbbe95,
 0xbd490000,0xbe16bdc9,0xbe79be48,0xbeacbe95,0xbedbbec4,0xbf04bef1,0xbf18bf0e,0xbf2cbf22,0xbf3ebf35,0xbf4ebf46,0xbf5cbf55,0xbf67bf62,0xbf71bf6d,0xbf78bf75,0xbf7dbf7b,0xbf80bf7f,
 0xbf80bf80,0xbf7dbf7f,0xbf78bf7b,0xbf71bf75,0xbf67bf6d,0xbf5cbf62,0xbf4ebf55,0xbf3ebf46,0xbf2cbf35,0xbf18bf22,0xbf04bf0e,0xbedbbef1,0xbeacbec4,0xbe79be95,0xbe16be48,0xbd49bdc9,
 0xbf78bf6d,0xbf80bf7f,0xbf71bf7b,0xbf4ebf62,0xbe160000,0xbedbbe95,0xbf2cbf0e,0xbf5cbf46,0x3f043ec4,0x3f3e3f22,0x3f673f55,0x3f7d3f75,0xbf18bf35,0xbeacbef1,0xbd49be48,0x3e793dc9,
 0x3e793ec4,0xbd493dc9,0xbeacbe48,0xbf18bef1,0x3f7d3f80,0x3f673f75,0x3f3e3f55,0x3f043f22,0xbf5cbf6d,0xbf2cbf46,0xbedbbf0e,0xbe16be95,0xbf4ebf35,0xbf71bf62,0xbf80bf7b,0xbf78bf7f,
 0x3f5c3f35,0x3f803f75,0x3f673f7b,0x3f183f46,0x3e163ec4,0xbeacbdc9,0xbf3ebf0e,0xbf78bf62,0xbe790000,0xbf2cbef1,0xbf71bf55,0xbf7dbf7f,0xbf4ebf6d,0xbedbbf22,0x3d49be48,0x3f043e95,
 0x3f043f35,0x3d493e95,0xbedbbe48,0xbf4ebf22,0xbf7dbf6d,0xbf71bf7f,0xbf2cbf55,0xbe79bef1,0xbf78bf80,0xbf3ebf62,0xbeacbf0e,0x3e16bdc9,0x3f183ec4,0x3f673f46,0x3f803f7b,0x3f5c3f75,
 0xbf3ebf6d,0xbe16bef1,0x3f043e48,0x3f713f46,0x3edb3f35,0xbe793dc9,0xbf4ebf0e,0xbf80bf75,0xbd49bec4,0x3f183e95,0x3f783f55,0x3f673f7f,0xbeac0000,0xbf5cbf22,0xbf7dbf7b,0xbf2cbf62,
 0xbf2cbec4,0xbf7dbf62,0xbf5cbf7b,0xbeacbf22,0x3f673f35,0x3f783f7f,0x3f183f55,0xbd493e95,0xbf80bf6d,0xbf4ebf75,0xbe79bf0e,0x3edb3dc9,0x3f713f80,0x3f043f46,0xbe163e48,0xbf3ebef1,
 0xbf67bf80,0xbe79bf22,0x3f183e48,0x3f803f62,0x3f2c3f6d,0xbe163e95,0xbf5cbf0e,0xbf71bf7f,0xbeacbf35,0x3f043dc9,0x3f7d3f55,0x3f3e3f75,0xbd493ec4,0xbf4ebef1,0xbf78bf7b,0xbedbbf46,
 0xbedb0000,0xbf78bf46,0xbf4ebf7b,0xbd49bef1,0x3f3e3ec4,0x3f7d3f75,0x3f043f55,0xbeac3dc9,0xbf71bf35,0xbf5cbf7f,0xbe16bf0e,0x3f2c3e95,0x3f803f6d,0x3f183f62,0xbe793e48,0xbf67bf22,
 0x3e16bec4,0x3f713f22,0x3f3e3f7b,0xbe793e95,0x3f5c3f80,0xbd493ef1,0xbf67bf0e,0xbf4ebf7f,0x3f183f6d,0xbedb3dc9,0xbf80bf55,0xbf04bf62,0xbf78bf35,0xbf2cbf75,0x3eacbe48,0x3f7d3f46,
 0x3f7d3f6d,0x3eac3f46,0xbf2cbe48,0xbf78bf75,0xbf040000,0xbf80bf62,0xbedbbf55,0x3f183dc9,0xbf4ebec4,0xbf67bf7f,0xbd49bf0e,0x3f5c3ef1,0xbe79bf35,0x3f3e3e95,0x3f713f7b,0x3e163f22,
 0x3e163f35,0xbf67bef1,0xbf2cbf7b,0x3f04bdc9,0x3f783f6d,0x3d493f22,0xbf71bf0e,0xbf18bf75,0xbf4ebf80,0x3eacbe95,0x3f803f55,0x3e793f46,0xbf5cbec4,0xbf3ebf7f,0x3edbbe48,0x3f7d3f62,
 0x3f7d3f35,0x3edb3f62,0xbf3ebe48,0xbf5cbf7f,0x3e79bec4,0x3f803f46,0x3eac3f55,0xbf4ebe95,0xbf180000,0xbf71bf75,0x3d49bf0e,0x3f783f22,0x3f043f6d,0xbf2cbdc9,0xbf67bf7b,0x3e16bef1,
 0x3f673ec4,0x3f043f75,0xbf4ebe48,0xbf2cbf7f,0x3f803f35,0x3e163f46,0xbf78bf0e,0xbeacbf62,0x3f713f6d,0xbe793ef1,0xbf7dbf55,0x3d49bf22,0x3f3e3f80,0xbf183dc9,0xbf5cbf7b,0x3edbbe95,
 0x3edb3f6d,0xbf5cbe95,0xbf18bf7b,0x3f3e3dc9,0x3d493f35,0xbf7dbf22,0xbe79bf55,0x3f713ef1,0xbeac3ec4,0xbf78bf62,0x3e16bf0e,0x3f803f46,0xbf2c0000,0xbf4ebf7f,0x3f04be48,0x3f673f75,
 0x3f2c3f80,0xbf4ebdc9,0xbf04bf7b,0x3f673e95,0x3eac3f6d,0xbf78bef1,0xbe16bf55,0x3f803f22,0xbd493f35,0xbf7dbf46,0x3e79bf0e,0x3f713f62,0xbedb3ec4,0xbf5cbf75,0x3f18be48,0x3f3e3f7f,
 0xbf3e0000,0xbf18bf7f,0x3f5c3e48,0x3edb3f75,0xbf71bec4,0xbe79bf62,0x3f7d3f0e,0x3d493f46,0xbf80bf35,0x3e16bf22,0x3f783f55,0xbeac3ef1,0xbf67bf6d,0x3f04be95,0x3f4e3f7b,0xbf2c3dc9,
 0xbf043ec4,0xbf2cbf7f,0x3f673e48,0x3e163f62,0x3f183f80,0xbf71be95,0xbd49bf55,0x3f783f46,0xbe79bf6d,0x3f803f22,0xbeac3f0e,0xbf4ebf75,0xbf7dbf35,0x3edbbef1,0x3f3e3f7b,0xbf5cbdc9,
 0x3f5c3f6d,0xbf3e3dc9,0xbedbbf7b,0x3f7d3ef1,0x3f4e0000,0x3eac3f75,0xbf80bf0e,0x3e79bf22,0xbf78bec4,0x3d49bf46,0x3f713f55,0xbf183e95,0xbe163f35,0xbf67bf62,0x3f2cbe48,0x3f043f7f,
 0x3e79bf35,0x3f3e3f75,0xbf71be48,0x3e16bf46,0x3f4e3f6d,0xbf67bdc9,0x3d49bf55,0x3f5c3f62,0x3f043f80,0xbf80bef1,0x3edbbf0e,0x3f183f7f,0xbf7dbec4,0x3eacbf22,0x3f2c3f7b,0xbf78be95,
 0x3f783f35,0xbf2c3e95,0xbeacbf7b,0x3f7d3f22,0xbf183ec4,0xbedbbf7f,0x3f803f0e,0xbf043ef1,0xbf5c0000,0xbd49bf62,0x3f673f55,0xbf4e3dc9,0xbe16bf6d,0x3f713f46,0xbf3e3e48,0xbe79bf75,
 0xbf80bec4,0x3f18bef1,0x3e793f7b,0xbf67bf46,0x3f713f35,0xbf5c3dc9,0x3e16bf55,0x3f2c3f75,0xbf3ebf6d,0x3f7d3e95,0xbf043f0e,0xbeacbf7f,0x3edb3f80,0xbf78bf22,0x3f4ebe48,0xbd493f62,
 0x3d493f6d,0xbf4ebf62,0x3f783e48,0xbedb3f22,0x3eacbf35,0x3f043f7f,0xbf7dbf0e,0x3f3ebe95,0xbf2c3ec4,0xbe16bf75,0x3f5c3f55,0xbf71bdc9,0x3f670000,0xbe793f46,0xbf18bf7b,0x3f803ef1,
 0xbf710000,0x3f04bf22,0x3e163f7b,0xbf3ebf62,0x3f803ec4,0xbf4e3e95,0x3e79bf55,0x3edb3f7f,0xbf67bf35,0x3f783dc9,0xbf183f0e,0xbd49bf75,0x3f2c3f6d,0xbf7dbef1,0x3f5cbe48,0xbeac3f46,
 0x3eac3f80,0xbf5cbf46,0x3f7d3e48,0xbf2c3ef1,0x3d49bf6d,0x3f183f75,0xbf78bf0e,0x3f67bdc9,0xbedb3f35,0xbe79bf7f,0x3f4e3f55,0xbf80be95,0x3f3ebec4,0xbe163f62,0xbf04bf7b,0x3f713f22,
 0xbf18bf6d,0x3f673f22,0xbf80be48,0x3f5cbe95,0x3f780000,0xbf3e3ef1,0x3eacbf55,0x3e163f7f,0x3f7d3ec4,0xbf713dc9,0x3f2cbf0e,0xbe793f62,0xbf043f35,0x3d49bf75,0x3edb3f7b,0xbf4ebf46,
 0x3f4ebec4,0xbedb3f46,0xbd49bf7b,0x3f043f75,0x3e793f80,0xbf2cbf62,0x3f713f0e,0xbf7dbdc9,0xbe163f6d,0xbeacbf7f,0x3f3e3f55,0xbf78bef1,0xbf5cbf35,0x3f803e95,0xbf673e48,0x3f18bf22,
 0x3f4e3f35,0xbf71bef1,0x3f803e48,0xbf783dc9,0x3f5cbec4,0xbf2c3f22,0x3edbbf55,0xbe163f75,0xbf7d0000,0x3f67be95,0xbf3e3f0e,0x3f04bf46,0xbe793f6d,0xbd49bf7f,0x3eac3f7b,0xbf18bf62,
 0x3f18bf35,0xbeac3f62,0x3d49bf7b,0x3e793f7f,0xbf04bf6d,0x3f3e3f46,0xbf67bf0e,0x3f7d3e95,0x3e163f80,0xbedbbf75,0x3f2c3f55,0xbf5cbf22,0x3f783ec4,0xbf80bdc9,0x3f71be48,0xbf4e3ef1,
 0x3eacbf6d,0xbe793f75,0x3e16bf7b,0xbd493f7f,0x3f2cbf35,0xbf183f46,0x3f04bf55,0xbedb3f62,0x3f67bec4,0xbf5c3ef1,0x3f4ebf0e,0xbf3e3f22,0x3f800000,0xbf7d3dc9,0x3f78be48,0xbf713e95,
 0x3f713ec4,0xbf78be95,0x3f7d3e48,0xbf80bdc9,0x3f3e3f35,0xbf4ebf22,0x3f5c3f0e,0xbf67bef1,0x3edb3f6d,0xbf04bf62,0x3f183f55,0xbf2cbf46,0x3d493f80,0xbe16bf7f,0x3e793f7b,0xbeacbf75,
 0xbf3e0000,0xbf18bf7f,0x3f5c3e48,0x3edb3f75,0xbf71bec4,0xbe79bf62,0x3f7d3f0e,0x3d493f46,0xbf80bf35,0x3e16bf22,0x3f783f55,0xbeac3ef1,0xbf67bf6d,0x3f04be95,0x3f4e3f7b,0xbf2c3dc9,
 0xbf2cbf80,0x3f4e3dc9,0x3f043f7b,0xbf67be95,0xbeacbf6d,0x3f783ef1,0x3e163f55,0xbf80bf22,0x3d49bf35,0x3f7d3f46,0xbe793f0e,0xbf71bf62,0x3edbbec4,0x3f5c3f75,0xbf183e48,0xbf3ebf7f,
 0xbf5cbf6d,0x3f3ebdc9,0x3edb3f7b,0xbf7dbef1,0xbf4e0000,0xbeacbf75,0x3f803f0e,0xbe793f22,0x3f783ec4,0xbd493f46,0xbf71bf55,0x3f18be95,0x3e16bf35,0x3f673f62,0xbf2c3e48,0xbf04bf7f,
 0xbf043ec4,0xbf2cbf7f,0x3f673e48,0x3e163f62,0x3f183f80,0xbf71be95,0xbd49bf55,0x3f783f46,0xbe79bf6d,0x3f803f22,0xbeac3f0e,0xbf4ebf75,0xbf7dbf35,0x3edbbef1,0x3f3e3f7b,0xbf5cbdc9,
 0x3f783f35,0xbf2c3e95,0xbeacbf7b,0x3f7d3f22,0xbf183ec4,0xbedbbf7f,0x3f803f0e,0xbf043ef1,0xbf5c0000,0xbd49bf62,0x3f673f55,0xbf4e3dc9,0xbe16bf6d,0x3f713f46,0xbf3e3e48,0xbe79bf75,
 0xbe793f35,0xbf3ebf75,0x3f713e48,0xbe163f46,0xbf4ebf6d,0x3f673dc9,0xbd493f55,0xbf5cbf62,0xbf04bf80,0x3f803ef1,0xbedb3f0e,0xbf18bf7f,0x3f7d3ec4,0xbeac3f22,0xbf2cbf7b,0x3f783e95,
 0xbd49bf6d,0x3f4e3f62,0xbf78be48,0x3edbbf22,0xbeac3f35,0xbf04bf7f,0x3f7d3f0e,0xbf3e3e95,0x3f2cbec4,0x3e163f75,0xbf5cbf55,0x3f713dc9,0xbf670000,0x3e79bf46,0x3f183f7b,0xbf80bef1,
 0xbf80bec4,0x3f18bef1,0x3e793f7b,0xbf67bf46,0x3f713f35,0xbf5c3dc9,0x3e16bf55,0x3f2c3f75,0xbf3ebf6d,0x3f7d3e95,0xbf043f0e,0xbeacbf7f,0x3edb3f80,0xbf78bf22,0x3f4ebe48,0xbd493f62,
 0xbeacbf80,0x3f5c3f46,0xbf7dbe48,0x3f2cbef1,0xbd493f6d,0xbf18bf75,0x3f783f0e,0xbf673dc9,0x3edbbf35,0x3e793f7f,0xbf4ebf55,0x3f803e95,0xbf3e3ec4,0x3e16bf62,0x3f043f7b,0xbf71bf22,
 0xbf710000,0x3f04bf22,0x3e163f7b,0xbf3ebf62,0x3f803ec4,0xbf4e3e95,0x3e79bf55,0x3edb3f7f,0xbf67bf35,0x3f783dc9,0xbf183f0e,0xbd49bf75,0x3f2c3f6d,0xbf7dbef1,0x3f5cbe48,0xbeac3f46,
 0x3f4ebec4,0xbedb3f46,0xbd49bf7b,0x3f043f75,0x3e793f80,0xbf2cbf62,0x3f713f0e,0xbf7dbdc9,0xbe163f6d,0xbeacbf7f,0x3f3e3f55,0xbf78bef1,0xbf5cbf35,0x3f803e95,0xbf673e48,0x3f18bf22,
 0x3f183f6d,0xbf67bf22,0x3f803e48,0xbf5c3e95,0xbf780000,0x3f3ebef1,0xbeac3f55,0xbe16bf7f,0xbf7dbec4,0x3f71bdc9,0xbf2c3f0e,0x3e79bf62,0x3f04bf35,0xbd493f75,0xbedbbf7b,0x3f4e3f46,
 0xbf183f35,0x3eacbf62,0xbd493f7b,0xbe79bf7f,0x3f043f6d,0xbf3ebf46,0x3f673f0e,0xbf7dbe95,0xbe16bf80,0x3edb3f75,0xbf2cbf55,0x3f5c3f22,0xbf78bec4,0x3f803dc9,0xbf713e48,0x3f4ebef1,
 0x3f4e3f35,0xbf71bef1,0x3f803e48,0xbf783dc9,0x3f5cbec4,0xbf2c3f22,0x3edbbf55,0xbe163f75,0xbf7d0000,0x3f67be95,0xbf3e3f0e,0x3f04bf46,0xbe793f6d,0xbd49bf7f,0x3eac3f7b,0xbf18bf62,
 0x3f713ec4,0xbf78be95,0x3f7d3e48,0xbf80bdc9,0x3f3e3f35,0xbf4ebf22,0x3f5c3f0e,0xbf67bef1,0x3edb3f6d,0xbf04bf62,0x3f183f55,0xbf2cbf46,0x3d493f80,0xbe16bf7f,0x3e793f7b,0xbeacbf75,
 0xbeac3f6d,0x3e79bf75,0xbe163f7b,0x3d49bf7f,0xbf2c3f35,0x3f18bf46,0xbf043f55,0x3edbbf62,0xbf673ec4,0x3f5cbef1,0xbf4e3f0e,0x3f3ebf22,0xbf800000,0x3f7dbdc9,0xbf783e48,0x3f71be95,
 0xbd493f80,0x3e16bf7f,0xbe793f7b,0x3eacbf75,0xbedb3f6d,0x3f04bf62,0xbf183f55,0x3f2cbf46,0xbf3e3f35,0x3f4ebf22,0xbf5c3f0e,0x3f67bef1,0xbf713ec4,0x3f78be95,0xbf7d3e48,0x3f80bdc9,
 0xbf800000,0x3f7d3dc9,0xbf78be48,0x3f713e95,0xbf67bec4,0x3f5c3ef1,0xbf4ebf0e,0x3f3e3f22,0xbf2cbf35,0x3f183f46,0xbf04bf55,0x3edb3f62,0xbeacbf6d,0x3e793f75,0xbe16bf7b,0x3d493f7f,
 0xbf783ec4,0x3f80bdc9,0xbf71be48,0x3f4e3ef1,0xbe163f80,0x3edbbf75,0xbf2c3f55,0x3f5cbf22,0x3f04bf6d,0xbf3e3f46,0x3f67bf0e,0xbf7d3e95,0xbf18bf35,0x3eac3f62,0xbd49bf7b,0xbe793f7f,
 0x3e793f6d,0x3d49bf7f,0xbeac3f7b,0x3f18bf62,0x3f7d0000,0xbf67be95,0x3f3e3f0e,0xbf04bf46,0xbf5cbec4,0x3f2c3f22,0xbedbbf55,0x3e163f75,0xbf4e3f35,0x3f71bef1,0xbf803e48,0x3f783dc9,
 0x3f5cbf35,0xbf803e95,0x3f673e48,0xbf18bf22,0x3e163f6d,0x3eacbf7f,0xbf3e3f55,0x3f78bef1,0xbe793f80,0x3f2cbf62,0xbf713f0e,0x3f7dbdc9,0xbf4ebec4,0x3edb3f46,0x3d49bf7b,0xbf043f75,
 0x3f043f35,0xbd49bf75,0xbedb3f7b,0x3f4ebf46,0xbf7d3ec4,0x3f713dc9,0xbf2cbf0e,0x3e793f62,0xbf780000,0x3f3e3ef1,0xbeacbf55,0xbe163f7f,0x3f18bf6d,0xbf673f22,0x3f80be48,0xbf5cbe95,
 0xbf3ebec4,0x3e163f62,0x3f04bf7b,0xbf713f22,0x3edb3f35,0x3e79bf7f,0xbf4e3f55,0x3f80be95,0xbd49bf6d,0xbf183f75,0x3f78bf0e,0xbf67bdc9,0xbeac3f80,0x3f5cbf46,0xbf7d3e48,0x3f2c3ef1,
 0xbf2c3f6d,0x3f7dbef1,0xbf5cbe48,0x3eac3f46,0x3f67bf35,0xbf783dc9,0x3f183f0e,0x3d49bf75,0xbf803ec4,0x3f4e3e95,0xbe79bf55,0xbedb3f7f,0x3f710000,0xbf04bf22,0xbe163f7b,0x3f3ebf62,
 0xbf670000,0x3e793f46,0x3f18bf7b,0xbf803ef1,0x3f2c3ec4,0x3e16bf75,0xbf5c3f55,0x3f71bdc9,0xbeacbf35,0xbf043f7f,0x3f7dbf0e,0xbf3ebe95,0xbd493f6d,0x3f4ebf62,0xbf783e48,0x3edb3f22,
 0xbedb3f80,0x3f78bf22,0xbf4ebe48,0x3d493f62,0x3f3ebf6d,0xbf7d3e95,0x3f043f0e,0x3eacbf7f,0xbf713f35,0x3f5c3dc9,0xbe16bf55,0xbf2c3f75,0x3f80bec4,0xbf18bef1,0xbe793f7b,0x3f67bf46,
 0x3e16bf6d,0xbf713f46,0x3f3e3e48,0x3e79bf75,0x3f5c0000,0x3d49bf62,0xbf673f55,0x3f4e3dc9,0x3f183ec4,0x3edbbf7f,0xbf803f0e,0x3f043ef1,0xbf783f35,0x3f2c3e95,0x3eacbf7b,0xbf7d3f22,
 0x3f7dbec4,0xbeacbf22,0xbf2c3f7b,0x3f78be95,0xbf043f80,0x3f80bef1,0xbedbbf0e,0xbf183f7f,0xbf4e3f6d,0x3f67bdc9,0xbd49bf55,0xbf5c3f62,0xbe79bf35,0xbf3e3f75,0x3f71be48,0xbe16bf46,
 0x3e163f35,0x3f67bf62,0xbf2cbe48,0xbf043f7f,0x3f78bec4,0xbd49bf46,0xbf713f55,0x3f183e95,0xbf4e0000,0xbeac3f75,0x3f80bf0e,0xbe79bf22,0xbf5c3f6d,0x3f3e3dc9,0x3edbbf7b,0xbf7d3ef1,
 0x3f7dbf35,0xbedbbef1,0xbf3e3f7b,0x3f5cbdc9,0x3e79bf6d,0xbf803f22,0x3eac3f0e,0x3f4ebf75,0xbf183f80,0x3f71be95,0x3d49bf55,0xbf783f46,0x3f043ec4,0x3f2cbf7f,0xbf673e48,0xbe163f62,
 0x3f67bf6d,0xbf04be95,0xbf4e3f7b,0x3f2c3dc9,0x3f80bf35,0xbe16bf22,0xbf783f55,0x3eac3ef1,0x3f71bec4,0x3e79bf62,0xbf7d3f0e,0xbd493f46,0x3f3e0000,0x3f18bf7f,0xbf5c3e48,0xbedb3f75,
 0x3edb3ec4,0x3f5cbf75,0xbf18be48,0xbf3e3f7f,0x3d493f35,0x3f7dbf46,0xbe79bf0e,0xbf713f62,0xbeac3f6d,0x3f78bef1,0x3e16bf55,0xbf803f22,0xbf2c3f80,0x3f4ebdc9,0x3f04bf7b,0xbf673e95,
 0xbf800000,0x3f7d3dc9,0xbf78be48,0x3f713e95,0xbf67bec4,0x3f5c3ef1,0xbf4ebf0e,0x3f3e3f22,0xbf2cbf35,0x3f183f46,0xbf04bf55,0x3edb3f62,0xbeacbf6d,0x3e793f75,0xbe16bf7b,0x3d493f7f,
 0x3d49bf80,0xbe163f7f,0x3e79bf7b,0xbeac3f75,0x3edbbf6d,0xbf043f62,0x3f18bf55,0xbf2c3f46,0x3f3ebf35,0xbf4e3f22,0x3f5cbf0e,0xbf673ef1,0x3f71bec4,0xbf783e95,0x3f7dbe48,0xbf803dc9,
 0xbe79bf6d,0xbd493f7f,0x3eacbf7b,0xbf183f62,0xbf7d0000,0x3f673e95,0xbf3ebf0e,0x3f043f46,0x3f5c3ec4,0xbf2cbf22,0x3edb3f55,0xbe16bf75,0x3f4ebf35,0xbf713ef1,0x3f80be48,0xbf78bdc9,
 0xbf783ec4,0x3f80bdc9,0xbf71be48,0x3f4e3ef1,0xbe163f80,0x3edbbf75,0xbf2c3f55,0x3f5cbf22,0x3f04bf6d,0xbf3e3f46,0x3f67bf0e,0xbf7d3e95,0xbf18bf35,0x3eac3f62,0xbd49bf7b,0xbe793f7f,
 0x3f043f35,0xbd49bf75,0xbedb3f7b,0x3f4ebf46,0xbf7d3ec4,0x3f713dc9,0xbf2cbf0e,0x3e793f62,0xbf780000,0x3f3e3ef1,0xbeacbf55,0xbe163f7f,0x3f18bf6d,0xbf673f22,0x3f80be48,0xbf5cbe95,
 0xbf5c3f35,0x3f80be95,0xbf67be48,0x3f183f22,0xbe16bf6d,0xbeac3f7f,0x3f3ebf55,0xbf783ef1,0x3e79bf80,0xbf2c3f62,0x3f71bf0e,0xbf7d3dc9,0x3f4e3ec4,0xbedbbf46,0xbd493f7b,0x3f04bf75,
 0x3f2cbf6d,0xbf7d3ef1,0x3f5c3e48,0xbeacbf46,0xbf673f35,0x3f78bdc9,0xbf18bf0e,0xbd493f75,0x3f80bec4,0xbf4ebe95,0x3e793f55,0x3edbbf7f,0xbf710000,0x3f043f22,0x3e16bf7b,0xbf3e3f62,
 0xbf3ebec4,0x3e163f62,0x3f04bf7b,0xbf713f22,0x3edb3f35,0x3e79bf7f,0xbf4e3f55,0x3f80be95,0xbd49bf6d,0xbf183f75,0x3f78bf0e,0xbf67bdc9,0xbeac3f80,0x3f5cbf46,0xbf7d3e48,0x3f2c3ef1,
 0x3edbbf80,0xbf783f22,0x3f4e3e48,0xbd49bf62,0xbf3e3f6d,0x3f7dbe95,0xbf04bf0e,0xbeac3f7f,0x3f71bf35,0xbf5cbdc9,0x3e163f55,0x3f2cbf75,0xbf803ec4,0x3f183ef1,0x3e79bf7b,0xbf673f46,
 0xbf670000,0x3e793f46,0x3f18bf7b,0xbf803ef1,0x3f2c3ec4,0x3e16bf75,0xbf5c3f55,0x3f71bdc9,0xbeacbf35,0xbf043f7f,0x3f7dbf0e,0xbf3ebe95,0xbd493f6d,0x3f4ebf62,0xbf783e48,0x3edb3f22,
 0x3f7dbec4,0xbeacbf22,0xbf2c3f7b,0x3f78be95,0xbf043f80,0x3f80bef1,0xbedbbf0e,0xbf183f7f,0xbf4e3f6d,0x3f67bdc9,0xbd49bf55,0xbf5c3f62,0xbe79bf35,0xbf3e3f75,0x3f71be48,0xbe16bf46,
 0xbe163f6d,0x3f71bf46,0xbf3ebe48,0xbe793f75,0xbf5c0000,0xbd493f62,0x3f67bf55,0xbf4ebdc9,0xbf18bec4,0xbedb3f7f,0x3f80bf0e,0xbf04bef1,0x3f78bf35,0xbf2cbe95,0xbeac3f7b,0x3f7dbf22,
 0xbf7d3f35,0x3edb3ef1,0x3f3ebf7b,0xbf5c3dc9,0xbe793f6d,0x3f80bf22,0xbeacbf0e,0xbf4e3f75,0x3f18bf80,0xbf713e95,0xbd493f55,0x3f78bf46,0xbf04bec4,0xbf2c3f7f,0x3f67be48,0x3e16bf62,
 0x3e163f35,0x3f67bf62,0xbf2cbe48,0xbf043f7f,0x3f78bec4,0xbd49bf46,0xbf713f55,0x3f183e95,0xbf4e0000,0xbeac3f75,0x3f80bf0e,0xbe79bf22,0xbf5c3f6d,0x3f3e3dc9,0x3edbbf7b,0xbf7d3ef1,
 0x3edb3ec4,0x3f5cbf75,0xbf18be48,0xbf3e3f7f,0x3d493f35,0x3f7dbf46,0xbe79bf0e,0xbf713f62,0xbeac3f6d,0x3f78bef1,0x3e16bf55,0xbf803f22,0xbf2c3f80,0x3f4ebdc9,0x3f04bf7b,0xbf673e95,
 0xbf673f6d,0x3f043e95,0x3f4ebf7b,0xbf2cbdc9,0xbf803f35,0x3e163f22,0x3f78bf55,0xbeacbef1,0xbf713ec4,0xbe793f62,0x3f7dbf0e,0x3d49bf46,0xbf3e0000,0xbf183f7f,0x3f5cbe48,0x3edbbf75,
 0xbf3e3f80,0x3f183dc9,0x3f5cbf7b,0xbedbbe95,0xbf713f6d,0x3e793ef1,0x3f7dbf55,0xbd49bf22,0xbf803f35,0xbe163f46,0x3f78bf0e,0x3eacbf62,0xbf673ec4,0xbf043f75,0x3f4ebe48,0x3f2cbf7f,
 0xbf2c0000,0xbf4e3f7f,0x3f043e48,0x3f67bf75,0xbeacbec4,0xbf783f62,0x3e163f0e,0x3f80bf46,0x3d49bf35,0xbf7d3f22,0xbe793f55,0x3f71bef1,0x3edbbf6d,0xbf5c3e95,0xbf183f7b,0x3f3ebdc9,
 0xbf5c3ec4,0xbf3e3f7f,0x3edb3e48,0x3f7dbf62,0xbf4e3f80,0x3eac3e95,0x3f80bf55,0x3e79bf46,0x3f78bf6d,0x3d49bf22,0xbf713f0e,0xbf183f75,0x3e16bf35,0xbf673ef1,0xbf2c3f7b,0x3f043dc9,
 0xbf043f6d,0x3f2cbdc9,0x3f67bf7b,0xbe16bef1,0x3f180000,0x3f71bf75,0xbd49bf0e,0xbf783f22,0xbe79bec4,0xbf803f46,0xbeac3f55,0x3f4ebe95,0xbf7d3f35,0xbedb3f62,0x3f3ebe48,0x3f5cbf7f,
 0x3f78bf35,0x3f2cbf75,0xbeacbe48,0xbf7d3f46,0xbf183f6d,0x3edb3dc9,0x3f80bf55,0x3f04bf62,0xbf5c3f80,0x3d493ef1,0x3f67bf0e,0x3f4ebf7f,0xbe16bec4,0xbf713f22,0xbf3e3f7b,0x3e793e95,
 0xbe793f35,0x3f3ebe95,0x3f71bf7b,0x3e16bf22,0xbf4e3ec4,0xbf673f7f,0xbd493f0e,0x3f5cbef1,0xbf040000,0xbf803f62,0xbedb3f55,0x3f18bdc9,0x3f7dbf6d,0x3eacbf46,0xbf2c3e48,0xbf783f75,
 0xbd49bec4,0xbf4e3ef1,0xbf783f7b,0xbedb3f46,0xbeac3f35,0x3f04bdc9,0x3f7dbf55,0x3f3ebf75,0x3f2cbf6d,0xbe16be95,0xbf5c3f0e,0xbf713f7f,0xbf673f80,0xbe793f22,0x3f18be48,0x3f80bf62,
 0xbf803f6d,0xbf183f62,0x3e793e48,0x3f67bf22,0x3f71bf35,0x3f5cbf7f,0x3e16bf0e,0xbf2c3e95,0xbf3e3ec4,0xbf7d3f75,0xbf043f55,0x3eac3dc9,0x3edb0000,0x3f78bf46,0x3f4ebf7b,0x3d49bef1,
 0xbeac0000,0xbf5c3f22,0xbf7d3f7b,0xbf2c3f62,0xbd493ec4,0x3f18be95,0x3f78bf55,0x3f67bf7f,0x3edbbf35,0xbe79bdc9,0xbf4e3f0e,0xbf803f75,0xbf3e3f6d,0xbe163ef1,0x3f04be48,0x3f71bf46,
 0xbf713f80,0xbf043f46,0x3e163e48,0x3f3ebef1,0x3f80bf6d,0x3f4ebf75,0x3e79bf0e,0xbedb3dc9,0xbf673f35,0xbf783f7f,0xbf183f55,0x3d493e95,0x3f2cbec4,0x3f7dbf62,0x3f5cbf7b,0x3eacbf22,
 0x3f4ebf6d,0x3edbbf22,0xbd49be48,0xbf043e95,0x3e790000,0x3f2cbef1,0x3f71bf55,0x3f7dbf7f,0xbe163ec4,0x3eacbdc9,0x3f3ebf0e,0x3f78bf62,0xbf5c3f35,0xbf803f75,0xbf673f7b,0xbf183f46,
 0x3f18bec4,0x3f67bf46,0x3f80bf7b,0x3f5cbf75,0xbf783f80,0xbf3e3f62,0xbeac3f0e,0x3e163dc9,0xbf7d3f6d,0xbf713f7f,0xbf2c3f55,0xbe793ef1,0x3f04bf35,0x3d49be95,0xbedb3e48,0xbf4e3f22,
 0xbf183f35,0xbeac3ef1,0xbd493e48,0x3e79bdc9,0x3f04bec4,0x3f3ebf22,0x3f67bf55,0x3f7dbf75,0xbe160000,0xbedb3e95,0xbf2c3f0e,0xbf5c3f46,0xbf783f6d,0xbf803f7f,0xbf713f7b,0xbf4e3f62,
 0x3f4ebf35,0x3f71bf62,0x3f80bf7b,0x3f78bf7f,0x3f5cbf6d,0x3f2cbf46,0x3edbbf0e,0x3e16be95,0xbf7d3f80,0xbf673f75,0xbf3e3f55,0xbf043f22,0xbe793ec4,0x3d493dc9,0x3eacbe48,0x3f18bef1,
 0x3f71bf6d,0x3f78bf75,0x3f7dbf7b,0x3f80bf7f,0x3f3ebf35,0x3f4ebf46,0x3f5cbf55,0x3f67bf62,0x3edbbec4,0x3f04bef1,0x3f18bf0e,0x3f2cbf22,0x3d490000,0x3e16bdc9,0x3e79be48,0x3eacbe95,
 0xbeac3ec4,0xbe793e95,0xbe163e48,0xbd493dc9,0xbf2c3f35,0xbf183f22,0xbf043f0e,0xbedb3ef1,0xbf673f6d,0xbf5c3f62,0xbf4e3f55,0xbf3e3f46,0xbf803f80,0xbf7d3f7f,0xbf783f7b,0xbf713f75,
 0xbf2c0000,0xbf4e3f7f,0x3f043e48,0x3f67bf75,0xbeacbec4,0xbf783f62,0x3e163f0e,0x3f80bf46,0x3d49bf35,0xbf7d3f22,0xbe793f55,0x3f71bef1,0x3edbbf6d,0xbf5c3e95,0xbf183f7b,0x3f3ebdc9,
 0x3f3ebf80,0xbf18bdc9,0xbf5c3f7b,0x3edb3e95,0x3f71bf6d,0xbe79bef1,0xbf7d3f55,0x3d493f22,0x3f80bf35,0x3e16bf46,0xbf783f0e,0xbeac3f62,0x3f67bec4,0x3f04bf75,0xbf4e3e48,0xbf2c3f7f,
 0x3f04bf6d,0xbf2c3dc9,0xbf673f7b,0x3e163ef1,0xbf180000,0xbf713f75,0x3d493f0e,0x3f78bf22,0x3e793ec4,0x3f80bf46,0x3eacbf55,0xbf4e3e95,0x3f7dbf35,0x3edbbf62,0xbf3e3e48,0xbf5c3f7f,
 0xbf5c3ec4,0xbf3e3f7f,0x3edb3e48,0x3f7dbf62,0xbf4e3f80,0x3eac3e95,0x3f80bf55,0x3e79bf46,0x3f78bf6d,0x3d49bf22,0xbf713f0e,0xbf183f75,0x3e16bf35,0xbf673ef1,0xbf2c3f7b,0x3f043dc9,
 0xbe793f35,0x3f3ebe95,0x3f71bf7b,0x3e16bf22,0xbf4e3ec4,0xbf673f7f,0xbd493f0e,0x3f5cbef1,0xbf040000,0xbf803f62,0xbedb3f55,0x3f18bdc9,0x3f7dbf6d,0x3eacbf46,0xbf2c3e48,0xbf783f75,
 0xbf783f35,0xbf2c3f75,0x3eac3e48,0x3f7dbf46,0x3f18bf6d,0xbedbbdc9,0xbf803f55,0xbf043f62,0x3f5cbf80,0xbd49bef1,0xbf673f0e,0xbf4e3f7f,0x3e163ec4,0x3f71bf22,0x3f3ebf7b,0xbe79be95,
 0x3f80bf6d,0x3f18bf62,0xbe79be48,0xbf673f22,0xbf713f35,0xbf5c3f7f,0xbe163f0e,0x3f2cbe95,0x3f3ebec4,0x3f7dbf75,0x3f04bf55,0xbeacbdc9,0xbedb0000,0xbf783f46,0xbf4e3f7b,0xbd493ef1,
 0xbd49bec4,0xbf4e3ef1,0xbf783f7b,0xbedb3f46,0xbeac3f35,0x3f04bdc9,0x3f7dbf55,0x3f3ebf75,0x3f2cbf6d,0xbe16be95,0xbf5c3f0e,0xbf713f7f,0xbf673f80,0xbe793f22,0x3f18be48,0x3f80bf62,
 0x3f71bf80,0x3f04bf46,0xbe16be48,0xbf3e3ef1,0xbf803f6d,0xbf4e3f75,0xbe793f0e,0x3edbbdc9,0x3f67bf35,0x3f78bf7f,0x3f18bf55,0xbd49be95,0xbf2c3ec4,0xbf7d3f62,0xbf5c3f7b,0xbeac3f22,
 0xbeac0000,0xbf5c3f22,0xbf7d3f7b,0xbf2c3f62,0xbd493ec4,0x3f18be95,0x3f78bf55,0x3f67bf7f,0x3edbbf35,0xbe79bdc9,0xbf4e3f0e,0xbf803f75,0xbf3e3f6d,0xbe163ef1,0x3f04be48,0x3f71bf46,
 0x3f18bec4,0x3f67bf46,0x3f80bf7b,0x3f5cbf75,0xbf783f80,0xbf3e3f62,0xbeac3f0e,0x3e163dc9,0xbf7d3f6d,0xbf713f7f,0xbf2c3f55,0xbe793ef1,0x3f04bf35,0x3d49be95,0xbedb3e48,0xbf4e3f22,
 0xbf4e3f6d,0xbedb3f22,0x3d493e48,0x3f04be95,0xbe790000,0xbf2c3ef1,0xbf713f55,0xbf7d3f7f,0x3e16bec4,0xbeac3dc9,0xbf3e3f0e,0xbf783f62,0x3f5cbf35,0x3f80bf75,0x3f67bf7b,0x3f18bf46,
 0xbf4e3f35,0xbf713f62,0xbf803f7b,0xbf783f7f,0xbf5c3f6d,0xbf2c3f46,0xbedb3f0e,0xbe163e95,0x3f7dbf80,0x3f67bf75,0x3f3ebf55,0x3f04bf22,0x3e79bec4,0xbd49bdc9,0xbeac3e48,0xbf183ef1,
 0xbf183f35,0xbeac3ef1,0xbd493e48,0x3e79bdc9,0x3f04bec4,0x3f3ebf22,0x3f67bf55,0x3f7dbf75,0xbe160000,0xbedb3e95,0xbf2c3f0e,0xbf5c3f46,0xbf783f6d,0xbf803f7f,0xbf713f7b,0xbf4e3f62,
 0xbeac3ec4,0xbe793e95,0xbe163e48,0xbd493dc9,0xbf2c3f35,0xbf183f22,0xbf043f0e,0xbedb3ef1,0xbf673f6d,0xbf5c3f62,0xbf4e3f55,0xbf3e3f46,0xbf803f80,0xbf7d3f7f,0xbf783f7b,0xbf713f75,
 0xbf713f6d,0xbf783f75,0xbf7d3f7b,0xbf803f7f,0xbf3e3f35,0xbf4e3f46,0xbf5c3f55,0xbf673f62,0xbedb3ec4,0xbf043ef1,0xbf183f0e,0xbf2c3f22,0xbd490000,0xbe163dc9,0xbe793e48,0xbeac3e95,
};
__device__ __align__(128) const uint32_t g_Gimg[1792] = {
 0x00003d00,0x00003d00,0x00003d00,0x00003d00,0x00003d00,0x00003d00,0x00003d00,0x00003d00,0x00003d00,0x00003d00,0x00003d00,0x00003d00,0x00003d00,0x00003d00,0x00003d00,0x00003d00,
 0x00003d00,0x00003d00,0x00003d00,0x00003d00,0x00003d00,0x00003d00,0x00003d00,0x00003d00,0x00003d00,0x00003d00,0x00003d00,0x00003d00,0x00003d00,0x00003d00,0x00003d00,0x00003d00,
 0xbc5b3ce7,0xbc843cdc,0xbc983cce,0xbcac3cbe,0xbac93d00,0xbb963cfd,0xbbf93cf8,0xbc2c3cf1,0xbcf13c2c,0xbcf83bf9,0xbcfd3b96,0xbd003ac9,0xbcbe3cac,0xbcce3c98,0xbcdc3c84,0xbce73c5b,
 0xbce7bc5b,0xbcdcbc84,0xbccebc98,0xbcbebcac,0xbd00bac9,0xbcfdbb96,0xbcf8bbf9,0xbcf1bc2c,0xbc2cbcf1,0xbbf9bcf8,0xbb96bcfd,0xbac9bd00,0xbcacbcbe,0xbc98bcce,0xbc84bcdc,0xbc5bbce7,
 0xbcffbb49,0xbcf5bc15,0xbce2bc71,0xbcc6bca2,0xbca2bcc6,0xbc71bce2,0xbc15bcf5,0xbb49bcff,0xbb493cff,0xbc153cf5,0xbc713ce2,0xbca23cc6,0xbcc63ca2,0xbce23c71,0xbcf53c15,0xbcff3b49,
 0x3cff3b49,0x3cf53c15,0x3ce23c71,0x3cc63ca2,0x3ca23cc6,0x3c713ce2,0x3c153cf5,0x3b493cff,0x3b49bcff,0x3c15bcf5,0x3c71bce2,0x3ca2bcc6,0x3cc6bca2,0x3ce2bc71,0x3cf5bc15,0x3cffbb49,
 0x3c84bcdc,0x3cbebcac,0x3ce7bc5b,0x3cfdbb96,0xbc98bcce,0xbc2cbcf1,0xbac9bd00,0x3bf9bcf8,0xbcf83bf9,0xbd00bac9,0xbcf1bc2c,0xbccebc98,0xbb963cfd,0xbc5b3ce7,0xbcac3cbe,0xbcdc3c84,
 0xbcdcbc84,0xbcacbcbe,0xbc5bbce7,0xbb96bcfd,0xbcce3c98,0xbcf13c2c,0xbd003ac9,0xbcf8bbf9,0x3bf93cf8,0xbac93d00,0xbc2c3cf1,0xbc983cce,0x3cfd3b96,0x3ce73c5b,0x3cbe3cac,0x3c843cdc,
 0xbbc83cfb,0xbc8e3cd5,0xbcd53c8e,0xbcfb3bc8,0xbcfbbbc8,0xbcd5bc8e,0xbc8ebcd5,0xbbc8bcfb,0x3bc8bcfb,0x3c8ebcd5,0x3cd5bc8e,0x3cfbbbc8,0x3cfb3bc8,0x3cd53c8e,0x3c8e3cd5,0x3bc83cfb,
 0xbbc83cfb,0xbc8e3cd5,0xbcd53c8e,0xbcfb3bc8,0xbcfbbbc8,0xbcd5bc8e,0xbc8ebcd5,0xbbc8bcfb,0x3bc8bcfb,0x3c8ebcd5,0x3cd5bc8e,0x3cfbbbc8,0x3cfb3bc8,0x3cd53c8e,0x3c8e3cd5,0x3bc83cfb,
 0x3c98bcce,0x3ce7bc5b,0x3d003ac9,0x3cdc3c84,0xbcf8bbf9,0xbcbebcac,0xbc2cbcf1,0x3b96bcfd,0xbcfd3b96,0xbcf1bc2c,0xbcacbcbe,0xbbf9bcf8,0x3c843cdc,0x3ac93d00,0xbc5b3ce7,0xbcce3c98,
 0xbccebc98,0xbc5bbce7,0x3ac9bd00,0x3c84bcdc,0xbbf93cf8,0xbcac3cbe,0xbcf13c2c,0xbcfdbb96,0x3b963cfd,0xbc2c3cf1,0xbcbe3cac,0xbcf83bf9,0x3cdcbc84,0x3d00bac9,0x3ce73c5b,0x3c983cce,
 0xbcf5bc15,0xbca2bcc6,0xbb49bcff,0x3c71bce2,0x3ce2bc71,0x3cff3b49,0x3cc63ca2,0x3c153cf5,0x3c15bcf5,0x3cc6bca2,0x3cffbb49,0x3ce23c71,0x3c713ce2,0xbb493cff,0xbca23cc6,0xbcf53c15,
 0x3cf53c15,0x3ca23cc6,0x3b493cff,0xbc713ce2,0xbce23c71,0xbcffbb49,0xbcc6bca2,0xbc15bcf5,0xbc153cf5,0xbcc63ca2,0xbcff3b49,0xbce2bc71,0xbc71bce2,0x3b49bcff,0x3ca2bcc6,0x3cf5bc15,
 0xbcac3cbe,0xbcfd3b96,0xbcdcbc84,0xbc2cbcf1,0x3ce7bc5b,0x3cf83bf9,0x3c983cce,0xbac93d00,0xbd003ac9,0xbccebc98,0xbbf9bcf8,0x3c5bbce7,0x3cf13c2c,0x3c843cdc,0xbb963cfd,0xbcbe3cac,
 0xbcbebcac,0xbb96bcfd,0x3c84bcdc,0x3cf1bc2c,0x3c5b3ce7,0xbbf93cf8,0xbcce3c98,0xbd00bac9,0xbac9bd00,0x3c98bcce,0x3cf8bbf9,0x3ce73c5b,0xbc2c3cf1,0xbcdc3c84,0xbcfdbb96,0xbcacbcbe,
 0xbc443ced,0xbced3c44,0xbcedbc44,0xbc44bced,0x3c44bced,0x3cedbc44,0x3ced3c44,0x3c443ced,0xbc443ced,0xbced3c44,0xbcedbc44,0xbc44bced,0x3c44bced,0x3cedbc44,0x3ced3c44,0x3c443ced,
 0xbc443ced,0xbced3c44,0xbcedbc44,0xbc44bced,0x3c44bced,0x3cedbc44,0x3ced3c44,0x3c443ced,0xbc443ced,0xbced3c44,0xbcedbc44,0xbc44bced,0x3c44bced,0x3cedbc44,0x3ced3c44,0x3c443ced,
 0x3cbebcac,0x3cfd3b96,0x3c843cdc,0xbc2c3cf1,0xbc5b3ce7,0xbcf83bf9,0xbccebc98,0xbac9bd00,0x3d003ac9,0x3c983cce,0xbbf93cf8,0xbce73c5b,0xbcf13c2c,0xbcdcbc84,0xbb96bcfd,0x3cacbcbe,
 0x3cac3cbe,0xbb963cfd,0xbcdc3c84,0xbcf1bc2c,0xbce7bc5b,0xbbf9bcf8,0x3c98bcce,0x3d00bac9,0xbac93d00,0xbcce3c98,0xbcf8bbf9,0xbc5bbce7,0xbc2cbcf1,0x3c84bcdc,0x3cfdbb96,0x3cbe3cac,
 0xbce2bc71,0xbb49bcff,0x3cc6bca2,0x3cf53c15,0x3c153cf5,0xbca23cc6,0xbcffbb49,0xbc71bce2,0xbc713ce2,0xbcff3b49,0xbca2bcc6,0x3c15bcf5,0x3cf5bc15,0x3cc63ca2,0xbb493cff,0xbce23c71,
 0x3ce23c71,0x3b493cff,0xbcc63ca2,0xbcf5bc15,0xbc15bcf5,0x3ca2bcc6,0x3cff3b49,0x3c713ce2,0x3c71bce2,0x3cffbb49,0x3ca23cc6,0xbc153cf5,0xbcf53c15,0xbcc6bca2,0x3b49bcff,0x3ce2bc71,
 0xbcce3c98,0xbce7bc5b,0xbac9bd00,0x3cdcbc84,0xbbf9bcf8,0x3cbebcac,0x3cf13c2c,0x3b963cfd,0x3cfd3b96,0x3c2c3cf1,0xbcac3cbe,0xbcf8bbf9,0xbc843cdc,0xbd00bac9,0xbc5bbce7,0x3c98bcce,
 0x3c983cce,0xbc5b3ce7,0xbd003ac9,0xbc84bcdc,0xbcf83bf9,0xbcacbcbe,0x3c2cbcf1,0x3cfdbb96,0x3b96bcfd,0x3cf1bc2c,0x3cbe3cac,0xbbf93cf8,0x3cdc3c84,0xbac93d00,0xbce73c5b,0xbccebc98,
 0xbc8e3cd5,0xbcfbbbc8,0xbbc8bcfb,0x3cd5bc8e,0x3cd53c8e,0xbbc83cfb,0xbcfb3bc8,0xbc8ebcd5,0x3c8ebcd5,0x3cfb3bc8,0x3bc83cfb,0xbcd53c8e,0xbcd5bc8e,0x3bc8bcfb,0x3cfbbbc8,0x3c8e3cd5,
 0xbc8e3cd5,0xbcfbbbc8,0xbbc8bcfb,0x3cd5bc8e,0x3cd53c8e,0xbbc83cfb,0xbcfb3bc8,0xbc8ebcd5,0x3c8ebcd5,0x3cfb3bc8,0x3bc83cfb,0xbcd53c8e,0xbcd5bc8e,0x3bc8bcfb,0x3cfbbbc8,0x3c8e3cd5,
 0xbcdc3c84,0xbcbebcac,0x3c5bbce7,0x3cfd3b96,0xbccebc98,0x3c2cbcf1,0x3d003ac9,0x3bf93cf8,0x3cf83bf9,0x3ac93d00,0xbcf13c2c,0xbc98bcce,0x3b963cfd,0xbce73c5b,0xbcacbcbe,0x3c84bcdc,
 0x3c843cdc,0xbcac3cbe,0xbce7bc5b,0x3b96bcfd,0xbc983cce,0xbcf1bc2c,0x3ac9bd00,0x3cf8bbf9,0x3bf9bcf8,0x3d00bac9,0x3c2c3cf1,0xbcce3c98,0x3cfdbb96,0x3c5b3ce7,0xbcbe3cac,0xbcdcbc84,
 0xbcc6bca2,0x3c71bce2,0x3cf53c15,0xbb493cff,0xbcff3b49,0xbc15bcf5,0x3ce2bc71,0x3ca23cc6,0x3ca2bcc6,0x3ce23c71,0xbc153cf5,0xbcffbb49,0xbb49bcff,0x3cf5bc15,0x3c713ce2,0xbcc63ca2,
 0x3cc63ca2,0xbc713ce2,0xbcf5bc15,0x3b49bcff,0x3cffbb49,0x3c153cf5,0xbce23c71,0xbca2bcc6,0xbca23cc6,0xbce2bc71,0x3c15bcf5,0x3cff3b49,0x3b493cff,0xbcf53c15,0xbc71bce2,0x3cc6bca2,
 0x3ce7bc5b,0x3c843cdc,0xbcce3c98,0xbcacbcbe,0x3d00bac9,0x3b963cfd,0xbcf83bf9,0xbc2cbcf1,0x3cf13c2c,0xbbf93cf8,0xbcfdbb96,0x3ac9bd00,0x3cbe3cac,0xbc983cce,0xbcdcbc84,0x3c5bbce7,
 0x3c5b3ce7,0xbcdc3c84,0xbc98bcce,0x3cbebcac,0x3ac93d00,0xbcfd3b96,0xbbf9bcf8,0x3cf1bc2c,0xbc2c3cf1,0xbcf8bbf9,0x3b96bcfd,0x3d003ac9,0xbcac3cbe,0xbccebc98,0x3c84bcdc,0x3ce73c5b,
 0xbcb53cb5,0xbcb5bcb5,0x3cb5bcb5,0x3cb53cb5,0xbcb53cb5,0xbcb5bcb5,0x3cb5bcb5,0x3cb53cb5,0xbcb53cb5,0xbcb5bcb5,0x3cb5bcb5,0x3cb53cb5,0xbcb53cb5,0xbcb5bcb5,0x3cb5bcb5,0x3cb53cb5,
 0xbcb53cb5,0xbcb5bcb5,0x3cb5bcb5,0x3cb53cb5,0xbcb53cb5,0xbcb5bcb5,0x3cb5bcb5,0x3cb53cb5,0xbcb53cb5,0xbcb5bcb5,0x3cb5bcb5,0x3cb53cb5,0xbcb53cb5,0xbcb5bcb5,0x3cb5bcb5,0x3cb53cb5,
 0xbcf13c2c,0xbbf9bcf8,0x3cfdbb96,0x3ac93d00,0xbcbe3cac,0xbc98bcce,0x3cdcbc84,0x3c5b3ce7,0xbce7bc5b,0x3c84bcdc,0x3cce3c98,0xbcac3cbe,0xbd00bac9,0x3b96bcfd,0x3cf83bf9,0xbc2c3cf1,
 0xbc2cbcf1,0x3cf8bbf9,0x3b963cfd,0xbd003ac9,0xbcacbcbe,0x3ccebc98,0x3c843cdc,0xbce73c5b,0x3c5bbce7,0x3cdc3c84,0xbc983cce,0xbcbebcac,0x3ac9bd00,0x3cfd3b96,0xbbf93cf8,0xbcf1bc2c,
 0xbca2bcc6,0x3ce2bc71,0x3c153cf5,0xbcff3b49,0x3b49bcff,0x3cf53c15,0xbc713ce2,0xbcc6bca2,0xbcc63ca2,0xbc71bce2,0x3cf5bc15,0x3b493cff,0xbcffbb49,0x3c15bcf5,0x3ce23c71,0xbca23cc6,
 0x3ca23cc6,0xbce23c71,0xbc15bcf5,0x3cffbb49,0xbb493cff,0xbcf5bc15,0x3c71bce2,0x3cc63ca2,0x3cc6bca2,0x3c713ce2,0xbcf53c15,0xbb49bcff,0x3cff3b49,0xbc153cf5,0xbce2bc71,0x3ca2bcc6,
 0x3cf8bbf9,0xbac93d00,0xbcf1bc2c,0x3c98bcce,0x3b96bcfd,0x3ce73c5b,0xbcac3cbe,0xbc84bcdc,0xbcdcbc84,0x3cbebcac,0x3c5b3ce7,0xbcfd3b96,0xbcce3c98,0xbc2cbcf1,0x3d00bac9,0xbbf93cf8,
 0xbbf9bcf8,0x3d003ac9,0xbc2c3cf1,0xbccebc98,0xbcfdbb96,0x3c5bbce7,0x3cbe3cac,0xbcdc3c84,0xbc843cdc,0xbcacbcbe,0x3ce7bc5b,0x3b963cfd,0x3c983cce,0xbcf13c2c,0xbac9bd00,0x3cf83bf9,
 0xbcd53c8e,0xbbc8bcfb,0x3cfb3bc8,0xbc8e3cd5,0xbc8ebcd5,0x3cfbbbc8,0xbbc83cfb,0xbcd5bc8e,0x3cd5bc8e,0x3bc83cfb,0xbcfbbbc8,0x3c8ebcd5,0x3c8e3cd5,0xbcfb3bc8,0x3bc8bcfb,0x3cd53c8e,
 0xbcd53c8e,0xbbc8bcfb,0x3cfb3bc8,0xbc8e3cd5,0xbc8ebcd5,0x3cfbbbc8,0xbbc83cfb,0xbcd5bc8e,0x3cd5bc8e,0x3bc83cfb,0xbcfbbbc8,0x3c8ebcd5,0x3c8e3cd5,0xbcfb3bc8,0x3bc8bcfb,0x3cd53c8e,
 0x3cfdbb96,0xbc2c3cf1,0xbcacbcbe,0x3cf8bbf9,0xbc84bcdc,0x3d00bac9,0xbc5b3ce7,0xbc98bcce,0xbccebc98,0x3ce7bc5b,0xbac93d00,0xbcdcbc84,0xbbf93cf8,0xbcbebcac,0x3cf1bc2c,0xbb963cfd,
 0xbb96bcfd,0x3cf13c2c,0xbcbe3cac,0xbbf9bcf8,0xbcdc3c84,0xbac9bd00,0x3ce73c5b,0xbcce3c98,0xbc983cce,0xbc5bbce7,0x3d003ac9,0xbc843cdc,0x3cf83bf9,0xbcac3cbe,0xbc2cbcf1,0x3cfd3b96,
 0xbc71bce2,0x3cff3b49,0xbca23cc6,0xbc15bcf5,0x3cf53c15,0xbcc63ca2,0xbb49bcff,0x3ce23c71,0x3ce2bc71,0xbb493cff,0xbcc6bca2,0x3cf5bc15,0xbc153cf5,0xbca2bcc6,0x3cffbb49,0xbc713ce2,
 0x3c713ce2,0xbcffbb49,0x3ca2bcc6,0x3c153cf5,0xbcf5bc15,0x3cc6bca2,0x3b493cff,0xbce2bc71,0xbce23c71,0x3b49bcff,0x3cc63ca2,0xbcf53c15,0x3c15bcf5,0x3ca23cc6,0xbcff3b49,0x3c71bce2,
 0xbd003ac9,0x3c98bcce,0x3bf93cf8,0xbce7bc5b,0x3cf13c2c,0xbcdc3c84,0x3b96bcfd,0x3cac3cbe,0xbcbebcac,0x3cfdbb96,0xbc843cdc,0xbc2cbcf1,0x3c5b3ce7,0xbcf8bbf9,0x3ccebc98,0xbac93d00,
 0xbac9bd00,0x3cce3c98,0xbcf83bf9,0x3c5bbce7,0xbc2c3cf1,0xbc84bcdc,0x3cfd3b96,0xbcbe3cac,0x3cacbcbe,0x3b963cfd,0xbcdcbc84,0x3cf1bc2c,0xbce73c5b,0x3bf9bcf8,0x3c983cce,0xbd00bac9,
 0xbced3c44,0x3c44bced,0x3c443ced,0xbcedbc44,0x3cedbc44,0xbc443ced,0xbc44bced,0x3ced3c44,0xbced3c44,0x3c44bced,0x3c443ced,0xbcedbc44,0x3cedbc44,0xbc443ced,0xbc44bced,0x3ced3c44,
 0xbced3c44,0x3c44bced,0x3c443ced,0xbcedbc44,0x3cedbc44,0xbc443ced,0xbc44bced,0x3ced3c44,0xbced3c44,0x3c44bced,0x3c443ced,0xbcedbc44,0x3cedbc44,0xbc443ced,0xbc44bced,0x3ced3c44,
 0x3d003ac9,0xbcce3c98,0x3bf9bcf8,0x3c5b3ce7,0xbcf13c2c,0x3c84bcdc,0x3b963cfd,0xbcbebcac,0x3cac3cbe,0xbcfdbb96,0x3cdcbc84,0xbc2c3cf1,0xbce7bc5b,0x3cf8bbf9,0xbc983cce,0xbac9bd00,
 0xbac93d00,0xbc98bcce,0x3cf83bf9,0xbce73c5b,0xbc2cbcf1,0x3cdc3c84,0xbcfd3b96,0x3cacbcbe,0xbcbe3cac,0x3b96bcfd,0x3c843cdc,0xbcf1bc2c,0x3c5bbce7,0x3bf93cf8,0xbccebc98,0x3d00bac9,
 0xbc15bcf5,0x3cc63ca2,0xbcffbb49,0x3ce2bc71,0xbc713ce2,0xbb49bcff,0x3ca23cc6,0xbcf5bc15,0xbcf53c15,0x3ca2bcc6,0xbb493cff,0xbc71bce2,0x3ce23c71,0xbcff3b49,0x3cc6bca2,0xbc153cf5,
 0x3c153cf5,0xbcc6bca2,0x3cff3b49,0xbce23c71,0x3c71bce2,0x3b493cff,0xbca2bcc6,0x3cf53c15,0x3cf5bc15,0xbca23cc6,0x3b49bcff,0x3c713ce2,0xbce2bc71,0x3cffbb49,0xbcc63ca2,0x3c15bcf5,
 0xbcfdbb96,0x3cf1bc2c,0xbcac3cbe,0x3bf9bcf8,0x3c84bcdc,0xbac93d00,0xbc5bbce7,0x3cce3c98,0x3c983cce,0xbce7bc5b,0x3d00bac9,0xbcdc3c84,0xbcf83bf9,0x3cbebcac,0xbc2c3cf1,0xbb96bcfd,
 0xbb963cfd,0xbc2cbcf1,0x3cbe3cac,0xbcf8bbf9,0xbcdcbc84,0x3d003ac9,0xbce73c5b,0x3c98bcce,0x3ccebc98,0xbc5b3ce7,0xbac9bd00,0x3c843cdc,0x3bf93cf8,0xbcacbcbe,0x3cf13c2c,0xbcfd3b96,
 0xbcfb3bc8,0x3cd5bc8e,0xbc8e3cd5,0x3bc8bcfb,0x3bc83cfb,0xbc8ebcd5,0x3cd53c8e,0xbcfbbbc8,0x3cfbbbc8,0xbcd53c8e,0x3c8ebcd5,0xbbc83cfb,0xbbc8bcfb,0x3c8e3cd5,0xbcd5bc8e,0x3cfb3bc8,
 0xbcfb3bc8,0x3cd5bc8e,0xbc8e3cd5,0x3bc8bcfb,0x3bc83cfb,0xbc8ebcd5,0x3cd53c8e,0xbcfbbbc8,0x3cfbbbc8,0xbcd53c8e,0x3c8ebcd5,0xbbc83cfb,0xbbc8bcfb,0x3c8e3cd5,0xbcd5bc8e,0x3cfb3bc8,
 0xbcf8bbf9,0x3d00bac9,0xbcf13c2c,0x3ccebc98,0xbb96bcfd,0x3c5b3ce7,0xbcacbcbe,0x3cdc3c84,0x3c843cdc,0xbcbebcac,0x3ce73c5b,0xbcfdbb96,0xbc983cce,0x3c2cbcf1,0xbac93d00,0xbbf9bcf8,
 0xbbf93cf8,0xbac9bd00,0x3c2c3cf1,0xbc98bcce,0xbcfd3b96,0x3ce7bc5b,0xbcbe3cac,0x3c84bcdc,0x3cdcbc84,0xbcac3cbe,0x3c5bbce7,0xbb963cfd,0x3cce3c98,0xbcf1bc2c,0x3d003ac9,0xbcf83bf9,
 0xbb49bcff,0x3c153cf5,0xbc71bce2,0x3ca23cc6,0xbcc6bca2,0x3ce23c71,0xbcf5bc15,0x3cff3b49,0x3cffbb49,0xbcf53c15,0x3ce2bc71,0xbcc63ca2,0x3ca2bcc6,0xbc713ce2,0x3c15bcf5,0xbb493cff,
 0x3b493cff,0xbc15bcf5,0x3c713ce2,0xbca2bcc6,0x3cc63ca2,0xbce2bc71,0x3cf53c15,0xbcffbb49,0xbcff3b49,0x3cf5bc15,0xbce23c71,0x3cc6bca2,0xbca23cc6,0x3c71bce2,0xbc153cf5,0x3b49bcff,
 0x3cf13c2c,0xbcf8bbf9,0x3cfd3b96,0xbd00bac9,0x3cbe3cac,0xbccebc98,0x3cdc3c84,0xbce7bc5b,0x3c5b3ce7,0xbc84bcdc,0x3c983cce,0xbcacbcbe,0x3ac93d00,0xbb96bcfd,0x3bf93cf8,0xbc2cbcf1,
 0xbc2c3cf1,0x3bf9bcf8,0xbb963cfd,0x3ac9bd00,0xbcac3cbe,0x3c98bcce,0xbc843cdc,0x3c5bbce7,0xbce73c5b,0x3cdcbc84,0xbcce3c98,0x3cbebcac,0xbd003ac9,0x3cfdbb96,0xbcf83bf9,0x3cf1bc2c,
 0xbd000000,0x3d000000,0xbd000000,0x3d000000,0xbd000000,0x3d000000,0xbd000000,0x3d000000,0xbd000000,0x3d000000,0xbd000000,0x3d000000,0xbd000000,0x3d000000,0xbd000000,0x3d000000,
 0xbd000000,0x3d000000,0xbd000000,0x3d000000,0xbd000000,0x3d000000,0xbd000000,0x3d000000,0xbd000000,0x3d000000,0xbd000000,0x3d000000,0xbd000000,0x3d000000,0xbd000000,0x3d000000,
 0xbce7bc5b,0x3cdc3c84,0xbccebc98,0x3cbe3cac,0xbd00bac9,0x3cfd3b96,0xbcf8bbf9,0x3cf13c2c,0xbc2cbcf1,0x3bf93cf8,0xbb96bcfd,0x3ac93d00,0xbcacbcbe,0x3c983cce,0xbc84bcdc,0x3c5b3ce7,
 0x3c5bbce7,0xbc843cdc,0x3c98bcce,0xbcac3cbe,0x3ac9bd00,0xbb963cfd,0x3bf9bcf8,0xbc2c3cf1,0x3cf1bc2c,0xbcf83bf9,0x3cfdbb96,0xbd003ac9,0x3cbebcac,0xbcce3c98,0x3cdcbc84,0xbce73c5b,
 0x3b49bcff,0xbc153cf5,0x3c71bce2,0xbca23cc6,0x3cc6bca2,0xbce23c71,0x3cf5bc15,0xbcff3b49,0xbcffbb49,0x3cf53c15,0xbce2bc71,0x3cc63ca2,0xbca2bcc6,0x3c713ce2,0xbc15bcf5,0x3b493cff,
 0xbb493cff,0x3c15bcf5,0xbc713ce2,0x3ca2bcc6,0xbcc63ca2,0x3ce2bc71,0xbcf53c15,0x3cffbb49,0x3cff3b49,0xbcf5bc15,0x3ce23c71,0xbcc6bca2,0x3ca23cc6,0xbc71bce2,0x3c153cf5,0xbb49bcff,
 0x3cdc3c84,0xbcacbcbe,0x3c5b3ce7,0xbb96bcfd,0x3ccebc98,0xbcf13c2c,0x3d00bac9,0xbcf8bbf9,0xbbf9bcf8,0xbac93d00,0x3c2cbcf1,0xbc983cce,0xbcfdbb96,0x3ce73c5b,0xbcbebcac,0x3c843cdc,
 0x3c84bcdc,0xbcbe3cac,0x3ce7bc5b,0xbcfd3b96,0xbc98bcce,0x3c2c3cf1,0xbac9bd00,0xbbf93cf8,0xbcf83bf9,0x3d003ac9,0xbcf1bc2c,0x3cce3c98,0xbb963cfd,0x3c5bbce7,0xbcac3cbe,0x3cdcbc84,
 0xbcfbbbc8,0x3cd53c8e,0xbc8ebcd5,0x3bc83cfb,0x3bc8bcfb,0xbc8e3cd5,0x3cd5bc8e,0xbcfb3bc8,0x3cfb3bc8,0xbcd5bc8e,0x3c8e3cd5,0xbbc8bcfb,0xbbc83cfb,0x3c8ebcd5,0xbcd53c8e,0x3cfbbbc8,
 0xbcfbbbc8,0x3cd53c8e,0xbc8ebcd5,0x3bc83cfb,0x3bc8bcfb,0xbc8e3cd5,0x3cd5bc8e,0xbcfb3bc8,0x3cfb3bc8,0xbcd5bc8e,0x3c8e3cd5,0xbbc8bcfb,0xbbc83cfb,0x3c8ebcd5,0xbcd53c8e,0x3cfbbbc8,
 0x3cce3c98,0xbc5bbce7,0xbac93d00,0x3c84bcdc,0x3bf9bcf8,0xbcac3cbe,0x3cf1bc2c,0xbcfdbb96,0xbb96bcfd,0xbc2c3cf1,0x3cbebcac,0xbcf83bf9,0xbcdc3c84,0x3d00bac9,0xbce7bc5b,0x3c983cce,
 0x3c98bcce,0xbce73c5b,0x3d003ac9,0xbcdcbc84,0xbcf8bbf9,0x3cbe3cac,0xbc2cbcf1,0xbb963cfd,0xbcfd3b96,0x3cf13c2c,0xbcacbcbe,0x3bf93cf8,0x3c843cdc,0xbac9bd00,0xbc5b3ce7,0x3ccebc98,
 0x3c15bcf5,0xbcc63ca2,0x3cffbb49,0xbce2bc71,0x3c713ce2,0x3b49bcff,0xbca23cc6,0x3cf5bc15,0x3cf53c15,0xbca2bcc6,0x3b493cff,0x3c71bce2,0xbce23c71,0x3cff3b49,0xbcc6bca2,0x3c153cf5,
 0xbc153cf5,0x3cc6bca2,0xbcff3b49,0x3ce23c71,0xbc71bce2,0xbb493cff,0x3ca2bcc6,0xbcf53c15,0xbcf5bc15,0x3ca23cc6,0xbb49bcff,0xbc713ce2,0x3ce2bc71,0xbcffbb49,0x3cc63ca2,0xbc15bcf5,
 0xbcbebcac,0x3b963cfd,0x3c84bcdc,0xbcf13c2c,0x3c5b3ce7,0x3bf9bcf8,0xbcce3c98,0x3d003ac9,0xbac9bd00,0xbc983cce,0x3cf8bbf9,0xbce7bc5b,0xbc2c3cf1,0x3cdcbc84,0xbcfdbb96,0x3cac3cbe,
 0x3cacbcbe,0xbcfd3b96,0x3cdc3c84,0xbc2cbcf1,0xbce73c5b,0x3cf83bf9,0xbc98bcce,0xbac93d00,0x3d00bac9,0xbccebc98,0x3bf93cf8,0x3c5bbce7,0xbcf1bc2c,0x3c843cdc,0x3b96bcfd,0xbcbe3cac,
 0xbcedbc44,0x3c443ced,0x3c44bced,0xbced3c44,0x3ced3c44,0xbc44bced,0xbc443ced,0x3cedbc44,0xbcedbc44,0x3c443ced,0x3c44bced,0xbced3c44,0x3ced3c44,0xbc44bced,0xbc443ced,0x3cedbc44,
 0xbcedbc44,0x3c443ced,0x3c44bced,0xbced3c44,0x3ced3c44,0xbc44bced,0xbc443ced,0x3cedbc44,0xbcedbc44,0x3c443ced,0x3c44bced,0xbced3c44,0x3ced3c44,0xbc44bced,0xbc443ced,0x3cedbc44,
 0x3cac3cbe,0x3b96bcfd,0xbcdc3c84,0x3cf13c2c,0xbce7bc5b,0x3bf93cf8,0x3c98bcce,0xbd003ac9,0xbac93d00,0x3ccebc98,0xbcf8bbf9,0x3c5b3ce7,0xbc2cbcf1,0xbc843cdc,0x3cfdbb96,0xbcbebcac,
 0xbcbe3cac,0x3cfd3b96,0xbc84bcdc,0xbc2c3cf1,0x3c5bbce7,0xbcf83bf9,0x3cce3c98,0xbac9bd00,0xbd00bac9,0x3c983cce,0x3bf9bcf8,0xbce73c5b,0x3cf1bc2c,0xbcdcbc84,0x3b963cfd,0x3cacbcbe,
 0x3c71bce2,0xbcff3b49,0x3ca23cc6,0x3c15bcf5,0xbcf53c15,0x3cc63ca2,0x3b49bcff,0xbce23c71,0xbce2bc71,0x3b493cff,0x3cc6bca2,0xbcf5bc15,0x3c153cf5,0x3ca2bcc6,0xbcffbb49,0x3c713ce2,
 0xbc713ce2,0x3cffbb49,0xbca2bcc6,0xbc153cf5,0x3cf5bc15,0xbcc6bca2,0xbb493cff,0x3ce2bc71,0x3ce23c71,0xbb49bcff,0xbcc63ca2,0x3cf53c15,0xbc15bcf5,0xbca23cc6,0x3cff3b49,0xbc71bce2,
 0xbc98bcce,0xbc5b3ce7,0x3d00bac9,0xbc84bcdc,0x3cf8bbf9,0xbcacbcbe,0xbc2c3cf1,0x3cfdbb96,0xbb963cfd,0x3cf1bc2c,0xbcbebcac,0xbbf93cf8,0xbcdcbc84,0xbac93d00,0x3ce7bc5b,0xbccebc98,
 0xbcce3c98,0x3ce73c5b,0xbac9bd00,0xbcdc3c84,0xbbf9bcf8,0xbcbe3cac,0x3cf13c2c,0xbb96bcfd,0x3cfd3b96,0xbc2cbcf1,0xbcac3cbe,0x3cf83bf9,0xbc843cdc,0x3d003ac9,0xbc5bbce7,0xbc983cce,
 0xbcd5bc8e,0xbbc83cfb,0x3cfbbbc8,0xbc8ebcd5,0xbc8e3cd5,0x3cfb3bc8,0xbbc8bcfb,0xbcd53c8e,0x3cd53c8e,0x3bc8bcfb,0xbcfb3bc8,0x3c8e3cd5,0x3c8ebcd5,0xbcfbbbc8,0x3bc83cfb,0x3cd5bc8e,
 0xbcd5bc8e,0xbbc83cfb,0x3cfbbbc8,0xbc8ebcd5,0xbc8e3cd5,0x3cfb3bc8,0xbbc8bcfb,0xbcd53c8e,0x3cd53c8e,0x3bc8bcfb,0xbcfb3bc8,0x3c8e3cd5,0x3c8ebcd5,0xbcfbbbc8,0x3bc83cfb,0x3cd5bc8e,
 0xbc84bcdc,0xbcac3cbe,0x3ce73c5b,0x3b96bcfd,0x3c98bcce,0xbcf1bc2c,0xbac93d00,0x3cf8bbf9,0xbbf93cf8,0x3d00bac9,0xbc2cbcf1,0xbcce3c98,0xbcfd3b96,0x3c5b3ce7,0x3cbebcac,0xbcdcbc84,
 0xbcdc3c84,0x3cbe3cac,0x3c5bbce7,0xbcfdbb96,0xbccebc98,0xbc2c3cf1,0x3d003ac9,0xbbf9bcf8,0x3cf83bf9,0xbac9bd00,0xbcf13c2c,0x3c983cce,0x3b963cfd,0x3ce7bc5b,0xbcacbcbe,0xbc843cdc,
 0x3ca2bcc6,0xbce2bc71,0xbc153cf5,0x3cff3b49,0xbb49bcff,0xbcf53c15,0x3c713ce2,0x3cc6bca2,0x3cc63ca2,0x3c71bce2,0xbcf5bc15,0xbb493cff,0x3cffbb49,0xbc15bcf5,0xbce23c71,0x3ca23cc6,
 0xbca23cc6,0x3ce23c71,0x3c15bcf5,0xbcffbb49,0x3b493cff,0x3cf5bc15,0xbc71bce2,0xbcc63ca2,0xbcc6bca2,0xbc713ce2,0x3cf53c15,0x3b49bcff,0xbcff3b49,0x3c153cf5,0x3ce2bc71,0xbca2bcc6,
 0x3c5b3ce7,0x3cdcbc84,0xbc98bcce,0xbcbe3cac,0x3ac93d00,0x3cfdbb96,0xbbf9bcf8,0xbcf13c2c,0xbc2c3cf1,0x3cf83bf9,0x3b96bcfd,0xbd00bac9,0xbcac3cbe,0x3cce3c98,0x3c84bcdc,0xbce7bc5b,
 0xbce73c5b,0x3c843cdc,0x3ccebc98,0xbcacbcbe,0xbd003ac9,0x3b963cfd,0x3cf8bbf9,0xbc2cbcf1,0xbcf1bc2c,0xbbf93cf8,0x3cfd3b96,0x3ac9bd00,0xbcbebcac,0xbc983cce,0x3cdc3c84,0x3c5bbce7,
 0xbcb5bcb5,0xbcb53cb5,0x3cb53cb5,0x3cb5bcb5,0xbcb5bcb5,0xbcb53cb5,0x3cb53cb5,0x3cb5bcb5,0xbcb5bcb5,0xbcb53cb5,0x3cb53cb5,0x3cb5bcb5,0xbcb5bcb5,0xbcb53cb5,0x3cb53cb5,0x3cb5bcb5,
 0xbcb5bcb5,0xbcb53cb5,0x3cb53cb5,0x3cb5bcb5,0xbcb5bcb5,0xbcb53cb5,0x3cb53cb5,0x3cb5bcb5,0xbcb5bcb5,0xbcb53cb5,0x3cb53cb5,0x3cb5bcb5,0xbcb5bcb5,0xbcb53cb5,0x3cb53cb5,0x3cb5bcb5,
 0xbc2cbcf1,0xbcf83bf9,0x3b963cfd,0x3d00bac9,0xbcacbcbe,0xbcce3c98,0x3c843cdc,0x3ce7bc5b,0x3c5bbce7,0xbcdcbc84,0xbc983cce,0x3cbe3cac,0x3ac9bd00,0xbcfdbb96,0xbbf93cf8,0x3cf13c2c,
 0x3cf1bc2c,0xbbf9bcf8,0xbcfd3b96,0x3ac93d00,0x3cbebcac,0xbc98bcce,0xbcdc3c84,0x3c5b3ce7,0x3ce73c5b,0x3c84bcdc,0xbccebc98,0xbcac3cbe,0x3d003ac9,0x3b96bcfd,0xbcf8bbf9,0xbc2c3cf1,
 0x00000000,0x00000000,0x00000000,0x00000000,0x00000000,0x00000000,0x00000000,0x00000000,0x00000000,0x00000000,0x00000000,0x00000000,0x00000000,0x00000000,0x00000000,0x00000000,
 0x00000000,0x00000000,0x00000000,0x00000000,0x00000000,0x00000000,0x00000000,0x00000000,0x00000000,0x00000000,0x00000000,0x00000000,0x00000000,0x00000000,0x00000000,0x00000000,
 0x00000000,0x00000000,0x00000000,0x00000000,0x00000000,0x00000000,0x00000000,0x00000000,0x00000000,0x00000000,0x00000000,0x00000000,0x00000000,0x00000000,0x00000000,0x00000000,
 0x00000000,0x00000000,0x00000000,0x00000000,0x00000000,0x00000000,0x00000000,0x00000000,0x00000000,0x00000000,0x00000000,0x00000000,0x00000000,0x00000000,0x00000000,0x00000000,
 0x00000000,0x00000000,0x00000000,0x00000000,0x00000000,0x00000000,0x00000000,0x00000000,0x00000000,0x00000000,0x00000000,0x00000000,0x00000000,0x00000000,0x00000000,0x00000000,
 0x00000000,0x00000000,0x00000000,0x00000000,0x00000000,0x00000000,0x00000000,0x00000000,0x00000000,0x00000000,0x00000000,0x00000000,0x00000000,0x00000000,0x00000000,0x00000000,
 0x00000000,0x00000000,0x00000000,0x00000000,0x00000000,0x00000000,0x00000000,0x00000000,0x00000000,0x00000000,0x00000000,0x00000000,0x00000000,0x00000000,0x00000000,0x00000000,
 0x00000000,0x00000000,0x00000000,0x00000000,0x00000000,0x00000000,0x00000000,0x00000000,0x00000000,0x00000000,0x00000000,0x00000000,0x00000000,0x00000000,0x00000000,0x00000000,
 0x00000000,0x00000000,0x00000000,0x00000000,0x00000000,0x00000000,0x00000000,0x00000000,0x00000000,0x00000000,0x00000000,0x00000000,0x00000000,0x00000000,0x00000000,0x00000000,
 0x00000000,0x00000000,0x00000000,0x00000000,0x00000000,0x00000000,0x00000000,0x00000000,0x00000000,0x00000000,0x00000000,0x00000000,0x00000000,0x00000000,0x00000000,0x00000000,
 0x00000000,0x00000000,0x00000000,0x00000000,0x00000000,0x00000000,0x00000000,0x00000000,0x00000000,0x00000000,0x00000000,0x00000000,0x00000000,0x00000000,0x00000000,0x00000000,
 0x00000000,0x00000000,0x00000000,0x00000000,0x00000000,0x00000000,0x00000000,0x00000000,0x00000000,0x00000000,0x00000000,0x00000000,0x00000000,0x00000000,0x00000000,0x00000000,
};

template<int SA>
__device__ __forceinline__ void wgmma_main(float (&d)[80], uint64_t da, uint64_t db, int sd) {
  asm volatile("{\n.reg .pred p;\nsetp.ne.b32 p, %82, 0;\n"
    "wgmma.mma_async.sync.aligned.m64n160k16.f32.bf16.bf16 "
    "{%0, %1, %2, %3, %4, %5, %6, %7, %8, %9, %10, %11, %12, %13, %14, %15, %16, %17, %18, %19, %20, %21, %22, %23, %24, %25, %26, %27, %28, %29, %30, %31, %32, %33, %34, %35, %36, %37, %38, %39, %40, %41, %42, %43, %44, %45, %46, %47, %48, %49, %50, %51, %52, %53, %54, %55, %56, %57, %58, %59, %60, %61, %62, %63, %64, %65, %66, %67, %68, %69, %70, %71, %72, %73, %74, %75, %76, %77, %78, %79}, %80, %81, p, %83, 1, 1, 0;\n}\n"
    : "+f"(d[0]), "+f"(d[1]), "+f"(d[2]), "+f"(d[3]), "+f"(d[4]), "+f"(d[5]), "+f"(d[6]), "+f"(d[7]), "+f"(d[8]), "+f"(d[9]), "+f"(d[10]), "+f"(d[11]), "+f"(d[12]), "+f"(d[13]), "+f"(d[14]), "+f"(d[15]), "+f"(d[16]), "+f"(d[17]), "+f"(d[18]), "+f"(d[19]), "+f"(d[20]), "+f"(d[21]), "+f"(d[22]), "+f"(d[23]), "+f"(d[24]), "+f"(d[25]), "+f"(d[26]), "+f"(d[27]), "+f"(d[28]), "+f"(d[29]), "+f"(d[30]), "+f"(d[31]), "+f"(d[32]), "+f"(d[33]), "+f"(d[34]), "+f"(d[35]), "+f"(d[36]), "+f"(d[37]), "+f"(d[38]), "+f"(d[39]), "+f"(d[40]), "+f"(d[41]), "+f"(d[42]), "+f"(d[43]), "+f"(d[44]), "+f"(d[45]), "+f"(d[46]), "+f"(d[47]), "+f"(d[48]), "+f"(d[49]), "+f"(d[50]), "+f"(d[51]), "+f"(d[52]), "+f"(d[53]), "+f"(d[54]), "+f"(d[55]), "+f"(d[56]), "+f"(d[57]), "+f"(d[58]), "+f"(d[59]), "+f"(d[60]), "+f"(d[61]), "+f"(d[62]), "+f"(d[63]), "+f"(d[64]), "+f"(d[65]), "+f"(d[66]), "+f"(d[67]), "+f"(d[68]), "+f"(d[69]), "+f"(d[70]), "+f"(d[71]), "+f"(d[72]), "+f"(d[73]), "+f"(d[74]), "+f"(d[75]), "+f"(d[76]), "+f"(d[77]), "+f"(d[78]), "+f"(d[79])
    : "l"(da), "l"(db), "r"(sd), "n"(SA));
}
template<int SA>
__device__ __forceinline__ void wgmma_fwd(float (&d)[32], uint64_t da, uint64_t db, int sd) {
  asm volatile("{\n.reg .pred p;\nsetp.ne.b32 p, %34, 0;\n"
    "wgmma.mma_async.sync.aligned.m64n64k16.f32.bf16.bf16 "
    "{%0, %1, %2, %3, %4, %5, %6, %7, %8, %9, %10, %11, %12, %13, %14, %15, %16, %17, %18, %19, %20, %21, %22, %23, %24, %25, %26, %27, %28, %29, %30, %31}, %32, %33, p, %35, 1, 0, 1;\n}\n"
    : "+f"(d[0]), "+f"(d[1]), "+f"(d[2]), "+f"(d[3]), "+f"(d[4]), "+f"(d[5]), "+f"(d[6]), "+f"(d[7]), "+f"(d[8]), "+f"(d[9]), "+f"(d[10]), "+f"(d[11]), "+f"(d[12]), "+f"(d[13]), "+f"(d[14]), "+f"(d[15]), "+f"(d[16]), "+f"(d[17]), "+f"(d[18]), "+f"(d[19]), "+f"(d[20]), "+f"(d[21]), "+f"(d[22]), "+f"(d[23]), "+f"(d[24]), "+f"(d[25]), "+f"(d[26]), "+f"(d[27]), "+f"(d[28]), "+f"(d[29]), "+f"(d[30]), "+f"(d[31])
    : "l"(da), "l"(db), "r"(sd), "n"(SA));
}
template<int SA>
__device__ __forceinline__ void wgmma_inv(float (&d)[28], uint64_t da, uint64_t db, int sd) {
  asm volatile("{\n.reg .pred p;\nsetp.ne.b32 p, %30, 0;\n"
    "wgmma.mma_async.sync.aligned.m64n56k16.f32.bf16.bf16 "
    "{%0, %1, %2, %3, %4, %5, %6, %7, %8, %9, %10, %11, %12, %13, %14, %15, %16, %17, %18, %19, %20, %21, %22, %23, %24, %25, %26, %27}, %28, %29, p, %31, 1, 1, 0;\n}\n"
    : "+f"(d[0]), "+f"(d[1]), "+f"(d[2]), "+f"(d[3]), "+f"(d[4]), "+f"(d[5]), "+f"(d[6]), "+f"(d[7]), "+f"(d[8]), "+f"(d[9]), "+f"(d[10]), "+f"(d[11]), "+f"(d[12]), "+f"(d[13]), "+f"(d[14]), "+f"(d[15]), "+f"(d[16]), "+f"(d[17]), "+f"(d[18]), "+f"(d[19]), "+f"(d[20]), "+f"(d[21]), "+f"(d[22]), "+f"(d[23]), "+f"(d[24]), "+f"(d[25]), "+f"(d[26]), "+f"(d[27])
    : "l"(da), "l"(db), "r"(sd), "n"(SA));
}

__device__ __forceinline__ uint32_t s2u(const void* p) { return (uint32_t)__cvta_generic_to_shared(p); }
__device__ __forceinline__ void mbar_init(uint32_t a, int c) { asm volatile("mbarrier.init.shared::cta.b64 [%0], %1;" ::"r"(a), "r"(c)); }
__device__ __forceinline__ void mbar_expect(uint32_t a, int b) { asm volatile("mbarrier.arrive.expect_tx.shared::cta.b64 _, [%0], %1;" ::"r"(a), "r"(b) : "memory"); }
__device__ __forceinline__ void mbar_arrive(uint32_t a) { asm volatile("mbarrier.arrive.shared::cta.b64 _, [%0];" ::"r"(a) : "memory"); }
__device__ __forceinline__ void mbar_arrive_cluster(uint32_t a, uint32_t cta, uint32_t cnt) {
  asm volatile("{\n.reg .b32 r;\nmapa.shared::cluster.u32 r, %0, %1;\nmbarrier.arrive.shared::cluster.b64 _, [r], %2;\n}" ::"r"(a), "r"(cta), "r"(cnt) : "memory");
}
__device__ __forceinline__ void mbar_wait(uint32_t a, int ph) {
  asm volatile("{\n.reg .pred p;\n.reg .u32 c;\nmov.u32 c, 0;\nWAIT:\n"
               "mbarrier.try_wait.parity.shared::cta.b64 p, [%0], %1;\n@p bra DONE;\n"
               "add.u32 c, c, 1;\nsetp.lt.u32 p, c, 0x400000;\n@p bra WAIT;\ntrap;\nDONE:\n}" ::"r"(a), "r"(ph) : "memory");
}
__device__ __forceinline__ void flag_wait(const unsigned* p, unsigned target) {
  asm volatile("{\n.reg .pred p;\n.reg .u32 c, v;\nmov.u32 c, 0;\nWAIT:\n"
               "ld.acquire.gpu.global.u32 v, [%0];\nsetp.ge.u32 p, v, %1;\n@p bra DONE;\n"
               "add.u32 c, c, 1;\nsetp.lt.u32 p, c, 0x400000;\n@p bra WAIT;\ntrap;\nDONE:\n}" ::"l"(p), "r"(target) : "memory");
}
__device__ __forceinline__ bool elect_one() {
  uint32_t p;
  asm volatile("{\n.reg .pred P;\nelect.sync _|P, 0xffffffff;\nselp.u32 %0, 1, 0, P;\n}" : "=r"(p));
  return p != 0;
}
__device__ __forceinline__ void bulk_ld(uint32_t dst, const void* src, int bytes, uint32_t bar) {
  asm volatile("cp.async.bulk.shared::cluster.global.mbarrier::complete_tx::bytes [%0], [%1], %2, [%3];" ::"r"(dst), "l"(src), "r"(bytes), "r"(bar) : "memory");
}
__device__ __forceinline__ void bulk_ld_mc_h(uint32_t dst, const void* src, int bytes, uint32_t bar, uint16_t mask, uint64_t pol) {
  asm volatile("cp.async.bulk.shared::cluster.global.mbarrier::complete_tx::bytes.multicast::cluster.L2::cache_hint [%0], [%1], %2, [%3], %4, %5;" ::"r"(dst), "l"(src), "r"(bytes), "r"(bar), "h"(mask), "l"(pol) : "memory");
}
__device__ __forceinline__ void tma_ld2(uint32_t dst, const CUtensorMap* tm, int c0, int c1, uint32_t bar) {
  asm volatile("cp.async.bulk.tensor.2d.shared::cluster.global.mbarrier::complete_tx::bytes [%0], [%1, {%3,%4}], [%2];" ::"r"(dst), "l"(tm), "r"(bar), "r"(c0), "r"(c1) : "memory");
}
__device__ __forceinline__ void tma_ld3(uint32_t dst, const CUtensorMap* tm, int c0, int c1, int c2, uint32_t bar) {
  asm volatile("cp.async.bulk.tensor.3d.shared::cluster.global.mbarrier::complete_tx::bytes [%0], [%1, {%3,%4,%5}], [%2];" ::"r"(dst), "l"(tm), "r"(bar), "r"(c0), "r"(c1), "r"(c2) : "memory");
}
__device__ __forceinline__ void tma_ld3h(uint32_t dst, const CUtensorMap* tm, int c0, int c1, int c2, uint32_t bar, uint64_t pol) {
  asm volatile("cp.async.bulk.tensor.3d.shared::cluster.global.mbarrier::complete_tx::bytes.L2::cache_hint [%0], [%1, {%3,%4,%5}], [%2], %6;" ::"r"(dst), "l"(tm), "r"(bar), "r"(c0), "r"(c1), "r"(c2), "l"(pol) : "memory");
}
__device__ __forceinline__ uint64_t policy_evict_first() {
  uint64_t p;
  asm("createpolicy.fractional.L2::evict_first.b64 %0, 1.0;" : "=l"(p));
  return p;
}
__device__ __forceinline__ void tma_st3(const CUtensorMap* tm, uint32_t src, int c0, int c1, int c2) {
  asm volatile("cp.async.bulk.tensor.3d.global.shared::cta.bulk_group [%0, {%2,%3,%4}], [%1];" ::"l"(tm), "r"(src), "r"(c0), "r"(c1), "r"(c2) : "memory");
}
__device__ __forceinline__ void tma_st4(const CUtensorMap* tm, uint32_t src, int c0, int c1, int c2, int c3) {
  asm volatile("cp.async.bulk.tensor.4d.global.shared::cta.bulk_group [%0, {%2,%3,%4,%5}], [%1];" ::"l"(tm), "r"(src), "r"(c0), "r"(c1), "r"(c2), "r"(c3) : "memory");
}
__device__ __forceinline__ void tma_st5(const CUtensorMap* tm, uint32_t src, int c0) {
  asm volatile("cp.async.bulk.tensor.5d.global.shared::cta.bulk_group [%0, {%2,%3,%3,%3,%3}], [%1];" ::"l"(tm), "r"(src), "r"(c0), "r"(0) : "memory");
}
__device__ __forceinline__ void bulk_commit() { asm volatile("cp.async.bulk.commit_group;" ::: "memory"); }
template <int N> __device__ __forceinline__ void bulk_wait_read() { asm volatile("cp.async.bulk.wait_group.read %0;" ::"n"(N) : "memory"); }
template <int N> __device__ __forceinline__ void bulk_wait() { asm volatile("cp.async.bulk.wait_group %0;" ::"n"(N) : "memory"); }
__device__ __forceinline__ void fence_async_smem() { asm volatile("fence.proxy.async.shared::cta;" ::: "memory"); }
__device__ __forceinline__ void wg_fence() { asm volatile("wgmma.fence.sync.aligned;" ::: "memory"); }
__device__ __forceinline__ void wg_commit() { asm volatile("wgmma.commit_group.sync.aligned;" ::: "memory"); }
template <int N> __device__ __forceinline__ void wg_wait() { asm volatile("wgmma.wait_group.sync.aligned %0;" ::"n"(N) : "memory"); }
template <int R> __device__ __forceinline__ void fence_regs(float (&d)[R]) {
#pragma unroll
  for (int i = 0; i < R; i++) asm volatile("" : "+f"(d[i])::"memory");
}
__device__ __forceinline__ uint64_t mk_desc(uint32_t addr) {
  return (uint64_t)((addr & 0x3FFFF) >> 4) | (1ull << 16) | (64ull << 32) | (1ull << 62);
}
__device__ __forceinline__ uint32_t pack2(float lo, float hi) {
  uint32_t r;
  asm("cvt.rn.bf16x2.f32 %0, %1, %2;" : "=r"(r) : "f"(hi), "f"(lo));
  return r;
}
__device__ __forceinline__ void stsm4(uint32_t ad, uint32_t a, uint32_t b, uint32_t c, uint32_t d) {
  asm volatile("stmatrix.sync.aligned.m8n8.x4.shared.b16 [%0], {%1,%2,%3,%4};" ::"r"(ad), "r"(a), "r"(b), "r"(c), "r"(d) : "memory");
}
__device__ __forceinline__ void stsm4t(uint32_t ad, uint32_t a, uint32_t b, uint32_t c, uint32_t d) {
  asm volatile("stmatrix.sync.aligned.m8n8.x4.trans.shared.b16 [%0], {%1,%2,%3,%4};" ::"r"(ad), "r"(a), "r"(b), "r"(c), "r"(d) : "memory");
}

__device__ __forceinline__ void stsm2t(uint32_t ad, uint32_t a, uint32_t b) {
  asm volatile("stmatrix.sync.aligned.m8n8.x2.trans.shared.b16 [%0], {%1,%2};" ::"r"(ad), "r"(a), "r"(b) : "memory");
}
__device__ __forceinline__ void red_add(unsigned* p) { asm volatile("red.relaxed.gpu.global.add.u32 [%0], 1;" ::"l"(p) : "memory"); }
__device__ __forceinline__ void fence_release() { asm volatile("fence.release.gpu;" ::: "memory"); }
__device__ __forceinline__ void fence_async_global() { asm volatile("fence.proxy.async.global;" ::: "memory"); }
__device__ __forceinline__ void tma_pf2(const CUtensorMap* tm, int c0, int c1) {
  asm volatile("cp.async.bulk.prefetch.tensor.2d.L2.global [%0, {%1,%2}];" ::"l"(tm), "r"(c0), "r"(c1) : "memory");
}
__device__ __forceinline__ void tma_pf3(const CUtensorMap* tm, int c0, int c1, int c2) {
  asm volatile("cp.async.bulk.prefetch.tensor.3d.L2.global [%0, {%1,%2,%3}];" ::"l"(tm), "r"(c0), "r"(c1), "r"(c2) : "memory");
}
__device__ __forceinline__ uint64_t policy_evict_unchanged() {
  uint64_t p;
  asm("createpolicy.fractional.L2::evict_unchanged.b64 %0, 1.0;" : "=l"(p));
  return p;
}

__device__ __forceinline__ unsigned flag_peek(const unsigned* p) {
  unsigned v;
  asm volatile("ld.acquire.gpu.global.u32 %0, [%1];" : "=r"(v) : "l"(p) : "memory");
  return v;
}
__device__ __forceinline__ int lane_id() {
  int l;
  asm volatile("mov.u32 %0, %%laneid;" : "=r"(l));
  return l;
}
__device__ __forceinline__ void poll64x4(const unsigned long long* p, unsigned long long (&v)[4]) {
  asm volatile("{\n.reg .pred p;\n.reg .u32 c;\n.reg .b64 t, u;\nmov.u32 c, 0;\nWAIT:\n"
               "ld.relaxed.gpu.global.u64 %0, [%4];\nld.relaxed.gpu.global.u64 %1, [%4+512];\n"
               "ld.relaxed.gpu.global.u64 %2, [%4+1024];\nld.relaxed.gpu.global.u64 %3, [%4+1536];\n"
               "or.b64 t, %0, %1;\nor.b64 u, %2, %3;\nor.b64 t, t, u;\nsetp.ge.s64 p, t, 0;\n@p bra DONE;\n"
               "add.u32 c, c, 1;\nsetp.lt.u32 p, c, 0x400000;\n@p bra WAIT;\ntrap;\nDONE:\n}"
               : "=l"(v[0]), "=l"(v[1]), "=l"(v[2]), "=l"(v[3]) : "l"(p) : "memory");
}

constexpr int G_STAGE = WBLK + XBLK;
constexpr int OFF_XR = 4 * G_STAGE;
constexpr int OFF_WS = OFF_XR + 6 * 8192;
constexpr int OFF_F = OFF_WS + 2 * 8192;
constexpr int OFF_WRAW = OFF_F + 8192;
constexpr int OFF_BAR = OFF_WRAW + 8192;
constexpr int OFF_GB = OFF_BAR + 1024;
constexpr int SMEM_BYTES = OFF_GB + 512;
constexpr int OFF_H0B = 10 * 8192;
constexpr int OFF_E = OFF_WRAW + 3072;
constexpr int B_RAWX = 0, B_F = 48, B_ROLE = 56, B_H0 = 80, B_H1 = 96, B_YFREE = 120, B_H0C = 136,
              B_EMPTY = 144,
              B_STGX = 192, B_STGW = 240, B_Y = 256, B_OUT = 272, B_YP = 352,
              B_FULL = 432, B_RAWW = 464, B_DONE = 496, S_ROLE = 576, S_PROBE = 592;

struct Maps { CUtensorMap x, we, wo, xst[2], wst, yst[2], yld[2], out, xe[2], w30; };

__device__ __forceinline__ int chunk_of(int n) { return n < 16 ? n : 31 - n; }
__device__ __forceinline__ bool has_x2(int id, int n, int g) { return (((id >> 5) ^ n) & 1) == 0 && ((n >> 1) & 1) == g; }
__device__ __forceinline__ int w_row(int id) { return (id & 62) | (id >> 6); }
__device__ __forceinline__ uint32_t x_base(int s, int idx, uint32_t pgmask, int& par) {
  const int page = idx >> 3, o = idx & 7;
  par = (s ^ (pgmask >> page) ^ __popc(o)) & 1;
  return (page << 21) | ((o & 3) << 16) | ((o >> 2) << 19);
}
__device__ __forceinline__ uint32_t read_info(uint32_t bar, int i) {
  uint32_t v;
  mbar_wait(bar + B_ROLE + 8 * i, 0);
  asm volatile("ld.shared.b32 %0, [%1];" : "=r"(v) : "r"(bar + S_ROLE + 4 * i) : "memory");
  return v;
}
__device__ __forceinline__ void send_info(uint32_t bar, int i, uint32_t v) {
#pragma unroll
  for (int r = 0; r < 2; r++)
    asm volatile("{\n.reg .b32 a, m;\nmapa.shared::cluster.u32 a, %0, %2;\nmapa.shared::cluster.u32 m, %1, %2;\n"
                 "st.async.weak.shared::cluster.mbarrier::complete_tx::bytes.b32 [a], %3, [m];\n}"
                 ::"r"(bar + S_ROLE + 4 * i), "r"(bar + B_ROLE + 8 * i), "r"(r), "r"(v) : "memory");
}
__device__ __forceinline__ unsigned probe(uint8_t* p, int lane) {
  if (lane < 2) *(uint4*)(p + lane * 16) = make_uint4(0, 0, 0, 0);
  __syncwarp();
  unsigned v, t0 = 0, t1 = 0;
  if (lane == 0) {
    asm volatile("mov.u32 %0, %%clock;" : "=r"(t0)::"memory");
    asm volatile("atom.relaxed.gpu.global.exch.b32 %0, [%1], 0;" : "=r"(v) : "l"(p) : "memory");
    asm volatile("{\n.reg .pred p;\nsetp.ne.u32 p, %1, 0xffffffff;\nmov.u32 %0, 0;\n@p mov.u32 %0, %%clock;\n}" : "=r"(t1) : "r"(v) : "memory");
  }
  return t1 - t0;
}

template <bool ISX>
__device__ __forceinline__ void t_issue(float (&t)[32], uint32_t sb, uint32_t raw) {
  const uint64_t da = mk_desc(sb + OFF_F), db = mk_desc(raw);
  wg_fence();
#pragma unroll
  for (int kk = 0; kk < (ISX ? 4 : 1); kk++) wgmma_fwd<1>(t, da + 2 * kk, db + 128 * kk, kk);
  wg_commit();
}
template <bool ISX>
__device__ __forceinline__ void t_finish(float (&t)[32], uint32_t dst, uint32_t sbar, int sw, int wg, int w, int lane) {
  fence_regs(t);
  if (ISX) asm volatile("bar.sync %0, 128;" ::"r"(1 + wg) : "memory");
  const int m = lane >> 3, r = lane & 7;
  uint32_t ad = dst + (8 * w + r) * 128;
  if (ISX) ad += ((((m & 1) * 4 + (m >> 1)) ^ sw ^ r) << 4);
  else ad += (m & 1) * 4096 + (((m >> 1) ^ sw ^ r) << 4);
#pragma unroll
  for (int i = 0; i < 4; i++) {
    const uint32_t a = ISX ? ((ad ^ ((i & 1) * 32)) + (i >> 1) * 4096) : (ad ^ (i * 32));
    stsm4(a, pack2(t[8 * i], t[8 * i + 1]), pack2(t[8 * i + 2], t[8 * i + 3]), pack2(t[8 * i + 4], t[8 * i + 5]), pack2(t[8 * i + 6], t[8 * i + 7]));
  }
  __syncwarp();
  if (lane == 0) mbar_arrive(sbar);
}
template <int NT, int K0, int K1>
__device__ __forceinline__ void batch(float (&yr)[80], float (&yi)[80], float (&t)[32], uint32_t st, int wg, int sd, uint32_t fa, uint32_t raw) {
  const uint64_t w0 = mk_desc(st + wg * 8192), x0 = mk_desc(st + WBLK);
  const uint64_t da = mk_desc(fa), db = mk_desc(raw);
  wg_fence();
  if (NT) {
#pragma unroll
    for (int kk = 0; kk < NT; kk++) wgmma_fwd<1>(t, da + 2 * kk, db + 128 * kk, kk);
    wg_commit();
  }
#pragma unroll
  for (int kk = K0; kk < K1; kk++) {
    const uint64_t wr = w0 + kk * 128, wi = wr + 256, xr = x0 + kk * 2, xi = xr + 4;
    wgmma_main<1>(yr, wr, xr, kk ? 1 : sd);
    wgmma_main<1>(yi, wr, xi, kk ? 1 : sd);
    wgmma_main<1>(yr, wi, xi, 1);
    wgmma_main<-1>(yi, wi, xr, 1);
  }
  wg_commit();
}

#define X_WAIT() PROF_W(wraw, mbar_wait(bar + B_RAWX + 8 * (wg * 3 + xs), xph))
#define X_ISSUE() t_issue<true>(t, sb, sb + OFF_XR + (wg * 3 + xs) * 8192)
#define X_FINISH(sw) do { t_finish<true>(t, sb + OFF_XR + (wg * 3 + xs) * 8192, bar + B_STGX + 8 * (wg * 3 + xs), sw, wg, w, lane); \
                          if (++xs == 3) { xs = 0; xph ^= 1; } } while (0)
#define W_WAIT(n) PROF_W(wraw, mbar_wait(bar + B_RAWW + 8 * (wg * 2 + ((n) & 1)), ((n) >> 1) & 1))
#define WRAW(n) (sb + OFF_WRAW + (wg * 2 + ((n) & 1)) * 2048)
#define W_FINISH() t_finish<false>(t, sb + OFF_WS + wg * 8192, bar + B_STGW + 8 * wg, w_row(id) & 7, wg, w, lane)

__device__ __forceinline__ void gelu_store(float (&hz)[28], uint32_t ad) {
#pragma unroll
  for (int i = 0; i < 28; i++) {
    const float in = hz[i] * fmaf(hz[i] * hz[i], 8.f * 0.044715f * 0.7978845608028654f, 2.f * 0.7978845608028654f);
    float th;
    asm("tanh.approx.f32 %0, %1;" : "=f"(th) : "f"(in));
    hz[i] = fmaf(hz[i], th, hz[i]);
  }
#pragma unroll
  for (int jj = 0; jj < 3; jj++) {
    const float* c = hz + 8 * jj;
    stsm4t(ad + jj * 2048, pack2(c[0], c[1]), pack2(c[2], c[3]), pack2(c[4], c[5]), pack2(c[6], c[7]));
  }
  stsm2t(ad + 3 * 2048, pack2(hz[24], hz[25]), pack2(hz[26], hz[27]));
}

#define ONE(...) do { if (elect_one()) { __VA_ARGS__; } } while (0)
template <int g>
__device__ __forceinline__ void manager(const Maps& tm, const unsigned* ctr, const uint32_t sb, const int id) {
  const uint32_t bar = sb + OFF_BAR, rank = id & 1;
  const uint64_t pol = policy_evict_first();
  const int cl = w_row(id), b = id >> 6, u = (id >> 1) & 31;
  const unsigned* pf = ctr + (C_LOADED + (((cl >> 5) - WR) >> 1)) * 32 + (((cl >> 5) - WR) & 1);
  int li = 0;
  auto refill = [&](int sl, bool wait) {
    const uint32_t fb = bar + B_RAWX + 8 * (g * 3 + sl);
    int row = ((li & 1) ? 128 + (id & 31) : 2 * (id & 63) + g) * MT, col = (li >> 1) * 64;
    asm volatile("" : "+r"(row), "+r"(col));
    ONE(if (li < 32) mbar_expect(fb, 8192);
        if (wait) bulk_wait_read<0>();
        if (li < 32) tma_ld3h(sb + OFF_XR + (g * 3 + sl) * 8192, &tm.x, col, row, b, fb, pol));
    li += (li & 1) || has_x2(id, li >> 1, g) ? 1 : 2;
  };
#pragma unroll 1
  for (int sl = 0; sl < 3; sl++) refill(sl, false);
  int xs = 0, xph = 0, yp = 0;
  int wrow = (cl >> 5) * (WSLOT / 128) + rank * 128 + g * 64 + (cl & 31);
  mbar_wait(bar + B_STGW + 8 * g, 0);
  ONE(fence_async_smem(); tma_st4(&tm.wst, sb + OFF_WS + g * 8192, 0, 0, 0, wrow); bulk_commit());
  const uint32_t pgmask = __shfl_sync(0xffffffffu, read_info(bar, 1), 0);
#pragma unroll 1
  for (int n = 0; n < 32; n++) {
    unsigned freed = 128;
    if (2 * n + (cl >> 5) >= WR) asm volatile("ld.relaxed.gpu.global.u32 %0, [%1];" : "=r"(freed) : "l"(pf + n * 32) : "memory");
    if (n < 16) {
#pragma unroll 1
      for (int j = 0; j < (has_x2(id, n, g) ? 2 : 1); j++) {
        const int t = j ? 128 + (id & 31) : 2 * (id & 63) + g;
        int par0, par1;
        const uint32_t off0 = x_base(b, n * 10 + (t >> 5), pgmask, par0), off1 = x_base(b, n * 10 + 5 + (t >> 5), pgmask, par1);
        uint32_t buf = sb + OFF_XR + (g * 3 + xs) * 8192;
        int c0 = (off0 + (par0 << 12) + (t & 31) * 128) >> 1, c1 = (off1 + (par1 << 12) + (t & 31) * 128) >> 1;
        const CUtensorMap *m0 = &tm.xst[par0], *m1 = &tm.xst[par1];
        asm volatile("" : "+r"(buf), "+r"(c0), "+r"(c1), "+l"(m0), "+l"(m1));
        mbar_wait(bar + B_STGX + 8 * (g * 3 + xs), xph);
        ONE(fence_async_smem(); tma_st5(m0, buf, c0); tma_st5(m1, buf + 4096, c1); bulk_commit());
        refill(xs, true);
        if (++xs == 3) { xs = 0; xph ^= 1; }
      }
    }
    if (n > 16 + LW && n <= YFLUSH) {
      if (yp == 0 || yp == 3) mbar_wait(bar + B_Y + 8 * g, yp & 1);
      const uint32_t buf = sb + OFF_XR + (g * 3 + (yp < 3 ? yp : yp - 3)) * 8192;
      ONE(tma_st4(&tm.yst[0], buf, 0, yp * 32, 2 * u, b * 4 + rank * 2 + g);
          if (yp == 0) tma_st4(&tm.yst[0], buf + 8192, 0, 32, 2 * u, b * 4 + rank * 2 + g);
          bulk_commit();
          bulk_wait_read<0>();
          if (yp == 0) mbar_arrive(bar + B_YFREE + 8 * g));
      yp += yp ? 1 : 2;
    }
    if (__shfl_sync(0xffffffffu, freed, 0) < 128) flag_wait(pf + n * 32, 128);
    const int cp = chunk_of(n + 2) * 64 + cl, sl = g * 2 + (n & 1);
    if (n) mbar_wait(bar + B_STGW + 8 * g, n & 1);
    ONE(if (n) {
          fence_async_smem();
          tma_st4(&tm.wst, sb + OFF_WS + g * 8192, 0, 0, 0, wrow);
          bulk_commit();
        }
        if (n < 30) {
          mbar_expect(bar + B_RAWW + 8 * sl, 2048);
          tma_ld3h(sb + OFF_WRAW + sl * 2048, &tm.we + (cp >> 9), 0, 0, (cp & 511) * 8 + ((n + 2) >> 4) * 4 + rank * 2 + g, bar + B_RAWW + 8 * sl, pol);
        }
        if (n < 4) {
          tma_pf3(&tm.we, 0, 0, ((n + 4) * 64 + cl) * 8 + rank * 2 + g);
          tma_pf3(&tm.wo, 0, 0, (n * 64 + cl) * 8 + rank * 2 + g);
          tma_pf3(&tm.wo, 0, 0, ((n + 4) * 64 + cl) * 8 + rank * 2 + g);
        }
        bulk_wait<0>();
        mbar_arrive(bar + B_DONE + 8 * (n & 7));
        mbar_arrive(bar + B_RAWW + 8 * (sl ^ 1)));
    wrow += 2 * WSLOT / 128;
    if (wrow >= WR * WSLOT / 128) wrow -= WR * WSLOT / 128;
  }
  ONE(asm volatile("prefetch.tensormap [%0];" ::"l"(g ? &tm.out : &tm.yst[1]) : "memory"));
  flag_wait(&ctr[(C_LOADED + 31) * 32 + 1], 128);
#pragma unroll 1
  for (int p = 0; p < 5; p++) {
    mbar_wait(bar + B_YP + 8 * (g * 5 + p), 0);
    ONE(fence_async_smem(); tma_st4(&tm.yst[1], sb + (p * 2 + g) * 8192, 0, p * 32, 2 * u, b * 4 + rank * 2 + g));
  }
  ONE(bulk_commit(); bulk_wait<0>(); mbar_arrive(bar + B_DONE));
#pragma unroll 1
  for (int i = 0; i < 10; i++) {
    const int hf = i >= 5, k = i - 5 * hf;
    const uint32_t buf = sb + (hf ? 0 : k < 4 ? OFF_XR : OFF_H0B - 65536) + (2 * k + g) * 8192;
    mbar_wait(bar + B_OUT + 8 * (g * 5 + k), hf);
    ONE(fence_async_smem();
        tma_st3(&tm.out, buf, (hf * 4 + rank * 2 + (u & 1)) * 64, ((u >> 1) * 10 + 2 * k + g) * MT, b);
        bulk_commit());
  }
  ONE(bulk_wait_read<0>(); if (g == 0) PROF_T(12));
}

__global__ void __cluster_dims__(2, 1, 1) __launch_bounds__(512, 1)
k1_main(uint8_t* xbuf, const void* __restrict__ fimg, const __nv_bfloat16* __restrict__ gamma,
        const __nv_bfloat16* __restrict__ beta, const __grid_constant__ Maps tm) {
  extern __shared__ __align__(1024) uint8_t smem_raw[];
  const uint32_t sb = s2u(smem_raw);
  const uint32_t bar = sb + OFF_BAR;
  const int warp = __shfl_sync(0xffffffffu, threadIdx.x >> 5, 0);
  const int bid = blockIdx.x;
  unsigned* ctr = (unsigned*)(xbuf + CTR_OFF);
  const uint32_t rank = bid & 1;
  if (bid == 0 && threadIdx.x < 4) asm volatile("st.relaxed.gpu.global.u64 [%0], %1;" ::"l"(&ctr[C_REG * 32 + 2 * threadIdx.x]), "l"(1ull << 63) : "memory");
  if (warp >= 12) {
    asm volatile("setmaxnreg.dec.sync.aligned.u32 24;");
    asm volatile("barrier.cluster.arrive.relaxed.aligned;" ::: "memory");
    {
      const int lane = lane_id(), k = bid >> 1;
      if (rank == 0 || k < XPAGES) {
        const uint32_t off = rank ? (k << 21) + 0xb0000 : (XPAGES << 21) + ((k >> 6) << 18) + (((k >> 4) & 3) << 14) + (k & 15) * 128;
        const unsigned lat = probe(xbuf + off + (warp & 1) * 4096 + (warp & 2) * 1024, lane);
        if (lane == 0) asm volatile("st.shared.b32 [%0], %1;" ::"r"(bar + S_PROBE + 4 * (warp & 3)), "r"(lat) : "memory");
      }
      asm volatile("bar.sync 4, 128;" ::: "memory");
      asm volatile("barrier.cluster.wait.aligned;" ::: "memory");
      if (warp == 14 && lane == 0) {
        uint32_t l0, l1, l2, l3;
        asm volatile("ld.shared.v4.b32 {%0, %1, %2, %3}, [%4];" : "=r"(l0), "=r"(l1), "=r"(l2), "=r"(l3) : "r"(bar + S_PROBE) : "memory");
        const int near = min(l1, l3) < min(l0, l2);
        if (rank) {
          send_info(bar, 2, near);
        } else {
          unsigned long long add = 1ull << (8 * near), v, *reg = (unsigned long long*)&ctr[C_REG * 32];
          if (k < XPAGES) add += (unsigned long long)(read_info(bar, 2) ^ near ^ 1) << (16 + k);
          PROF_T(14);
          asm volatile("{\n.reg .pred p;\n.reg .u32 c;\nmov.u32 c, 0;\nAGAIN:\n"
                       "atom.relaxed.gpu.global.add.u64 %0, [%1], %2;\nsetp.lt.s64 p, %0, 0;\n@p bra DONE;\n"
                       "add.u32 c, c, 1;\nsetp.lt.u32 p, c, 0x100000;\n@p bra AGAIN;\ntrap;\nDONE:\n}" : "=l"(v) : "l"(reg), "l"(add) : "memory");
          const int ticket = (v >> (8 * near)) & 255;
          if (ticket < 32) send_info(bar, 0, near * 32 + ticket);
          PROF_T(15); PROF_V(16, near);
          asm volatile("{\n.reg .pred p;\n.reg .u32 c, a, b;\nmov.u32 c, 0;\nWAIT:\n"
                       "ld.relaxed.gpu.global.u64 %0, [%1];\ncvt.u32.u64 a, %0;\nbfe.u32 b, a, 8, 8;\nand.b32 a, a, 255;\nadd.u32 a, a, b;\n"
                       "setp.ge.u32 p, a, 66;\n@p bra DONE;\n"
                       "add.u32 c, c, 1;\nsetp.lt.u32 p, c, 0x400000;\n@p bra WAIT;\ntrap;\nDONE:\n}" : "=l"(v) : "l"(reg) : "memory");
          if (ticket >= 32) {
            const int j = ticket - 32 + (int)((v >> (8 * (near ^ 1))) & 255);
            send_info(bar, 0, j < 32 ? (near ^ 1) * 32 + j : (near == 0 && ticket == 32 && j == 33) ? 64 : 32 + j);
          }
          send_info(bar, 1, (uint32_t)(v >> 16));
          PROF_T(13);
        }
      }
      __syncwarp();
      const int role = read_info(bar, 0);
      if (role < 64 && warp - 12 < NFL && elect_one()) {
#pragma unroll 1
        for (int n = warp - 12; n < 33; n += NFL) {
          mbar_wait(bar + B_DONE + 8 * (n & 7), (n >> 3) & 1);
          fence_release();
          if (n < 32) {
            red_add(&ctr[(C_FLAG + n + C_SIDE * ((role >> 5) ^ 1)) * 32]);
            red_add(&ctr[(C_FLAG + n + C_SIDE * (role >> 5)) * 32]);
          } else {
            red_add(&ctr[(C_Y + rank + C_SIDE * (role >> 5)) * 32]);
          }
          if (n < 32) { PROF_T(64 + n); PROF_V(192 + n, tm0); } else { PROF_V(4, tm0); }
        }
      }
      if (role < 64 && warp == 15 && elect_one()) {
#pragma unroll 1
        for (int v = 0; v < 64; v++) {
          mbar_wait(bar + B_FULL + 8 * (v & 3), (v >> 2) & 1);
          mbar_arrive(bar + B_EMPTY + 8 * (v & 3));
          if (v < 64 - WR || v == 63) {
            red_add(&ctr[(C_LOADED + (v >> 1)) * 32 + (v & 1)]);
            red_add(&ctr[(C_LOADED + (v >> 1) + C_SIDE) * 32 + (v & 1)]);
          }
        }
      }
      __syncwarp();
    }
    asm volatile("barrier.cluster.arrive.relaxed.aligned;\nbarrier.cluster.wait.aligned;" ::: "memory");
    return;
  } else {
    if (elect_one()) {
      if (warp == 0) PROF_T(0);
      if (warp >= 6) asm volatile("prefetch.tensormap [%0];" ::"l"(&tm.x + (warp - 6)) : "memory");
      const int cnt = warp < 3 ? 1 : warp == 3 ? 5 : warp < 9 ? 4 : 2;
#pragma unroll
      for (int i = 0; i < 6; i++) mbar_init(bar + warp * 48 + 8 * i, cnt);
      if (warp == 1) {
        mbar_expect(bar + B_F, 8192);
        bulk_ld(sb + OFF_F, fimg, 8192, bar + B_F);
        mbar_expect(bar + B_ROLE, 4);
        mbar_expect(bar + B_ROLE + 8, 4);
        mbar_expect(bar + B_ROLE + 16, 4);
      }
      asm volatile("fence.mbarrier_init.release.cluster;" ::: "memory");
    }
    asm volatile("bar.sync 0, 384;" ::: "memory");
    asm volatile("barrier.cluster.arrive.relaxed.aligned;" ::: "memory");
    if (threadIdx.x == 64) PROF_T(20);
    if (bid < 128 && warp < 4 && elect_one()) {
      const int g = warp & 1;
      if (warp < 2) {
        tma_pf3(&tm.x, 0, (2 * (bid & 63) + g) * MT, bid >> 6);
        if (has_x2(bid, 0, g)) tma_pf3(&tm.x, 0, (128 + (bid & 31)) * MT, bid >> 6);
      } else {
        tma_pf3(&tm.we, 0, 0, (bid >> 1) * 8 + rank * 2 + g);
      }
    }
    __syncwarp();
  }
  if (warp >= 8) {
    asm volatile("setmaxnreg.dec.sync.aligned.u32 40;");
    asm volatile("barrier.cluster.wait.aligned;" ::: "memory");
    const int role = __shfl_sync(0xffffffffu, read_info(bar, 0), 0);
    const unsigned* lctr = ctr + (role >> 5) * C_SIDE * 32;
    if (role >= 64) {
    } else if (warp == 9 || warp == 10) {
      asm volatile("barrier.cluster.arrive.relaxed.aligned;" ::: "memory");
      if (warp == 9) manager<0>(tm, lctr, sb, role * 2 + rank); else manager<1>(tm, lctr, sb, role * 2 + rank);
      __syncwarp();
      asm volatile("barrier.cluster.wait.aligned;" ::: "memory");
      return;
    } else if (warp == 11) {
      const uint8_t* ws = g_W + (size_t)((role & 31) * 2 + rank) * WBLK;
      int slot = 0;
#pragma unroll 1
      for (int v = 0; v < 64; v++) {
        const uint8_t* src = ws + (size_t)slot * WSLOT;
        uint32_t dst = sb + (v & 3) * G_STAGE, fb = bar + B_FULL + 8 * (v & 3);
        asm volatile("" : "+l"(src), "+r"(dst), "+r"(fb));
        if (++slot == WR) slot = 0;
        const unsigned* fp = &lctr[(C_FLAG + (v >> 1)) * 32];
        const bool ready = (v & 1) || __shfl_sync(0xffffffffu, flag_peek(fp), 0) >= 128;
        mbar_wait(bar + B_EMPTY + 8 * (v & 3), ((v >> 2) & 1) ^ 1);
        ONE(mbar_expect(fb, WBLK));
        if (!ready) flag_wait(fp, 128);
        ONE(fence_async_global(); bulk_ld(dst, src, WBLK, fb));
      }
    } else {
      const uint32_t pgmask = __shfl_sync(0xffffffffu, read_info(bar, 1), 0);
      const int b = role >> 5, u = role & 31;
      const uint64_t pef = policy_evict_first(), pen = policy_evict_unchanged();
      const uint8_t* xs = xbuf + ((((u >> 1) & 3) << 14) | (((u >> 3) & 1) << 18) | ((u >> 4) << 20) | ((u & 1) << 13));
      const int skip = rank * 2048;
#pragma unroll 1
      for (int v = 0; v < 64; v++) {
        const int n = v >> 1;
        uint64_t polx = (n < XKEEP || n >= 16) ? pef : pen;
        uint32_t dst = sb + (v & 3) * G_STAGE + WBLK + rank * 8192, fb = bar + B_FULL + 8 * (v & 3);
        const uint8_t* src[3];
#pragma unroll
        for (int g = 0; g < 3; g++) {
          int par;
          const uint32_t o = x_base(b ^ u, chunk_of(n) * 10 + (v & 1) * 5 + rank * 2 + g, pgmask, par);
          src[g] = xs + o + (par << 12) + (g ? 0 : skip);
        }
        asm volatile("" : "+l"(src[0]), "+l"(src[1]), "+l"(src[2]), "+l"(polx), "+r"(dst), "+r"(fb));
        const unsigned* fp = &lctr[(C_FLAG + n) * 32];
        const bool ready = (v & 1) || v >= 32 || __shfl_sync(0xffffffffu, flag_peek(fp), 0) >= 128;
        mbar_wait(bar + B_EMPTY + 8 * (v & 3), ((v >> 2) & 1) ^ 1);
        ONE(mbar_expect(fb, XBLK));
        if (!ready) flag_wait(fp, 128);
        ONE(fence_async_global();
            bulk_ld_mc_h(dst + skip, src[0], 4096 - skip, fb, 3, polx);
            bulk_ld_mc_h(dst + 4096, src[1], 4096, fb, 3, polx);
            bulk_ld_mc_h(dst + 8192, src[2], 2048 + skip, fb, 3, polx));
      }
      const int dq = rank * 2 + (u & 1), t0 = (u >> 1) * 10, row = ((b * 4 + dq) * NT + t0) * 64;
      flag_wait(&ctr[C_E * 32], 4);
      flag_wait(&lctr[(C_FLAG + YFLUSH) * 32], 128);
      ONE(fence_async_global();
          mbar_expect(bar + B_H0C, 6 * 8192);
          for (int i = 0; i < 3; i++) tma_ld2(sb + OFF_XR + i * 16384, &tm.yld[0], 0, row + i * 128, bar + B_H0C));
      static_assert(YFLUSH >= 23, "phase of the B_DONE ring");
      mbar_wait(bar + B_DONE + 8 * 7, 1);
      ONE(mbar_expect(bar + B_H0, 2 * 8192 + 7168 + 5120 + 512);
          bulk_ld(sb + OFF_F, g_Gimg, 7168, bar + B_H0);
          tma_ld2(sb + OFF_WS, &tm.yld[0], 0, row + 6 * 64, bar + B_H0);
          tma_pf2(&tm.yld[0], 0, row + 8 * 64);
          for (int hf = 0; hf < 2; hf++) {
            bulk_ld(sb + OFF_E + hf * 2560, g_E + ((b * 8 + hf * 4 + dq) * NT + t0) * 64, 2560, bar + B_H0);
            bulk_ld(sb + OFF_GB + hf * 256, gamma + (hf * 4 + dq) * 64, 128, bar + B_H0);
            bulk_ld(sb + OFF_GB + hf * 256 + 128, beta + (hf * 4 + dq) * 64, 128, bar + B_H0);
          });
      mbar_wait(bar + B_EMPTY + 8 * 2, 1);
      ONE(mbar_expect(bar + B_H0 + 8, 16384);
          tma_ld2(sb + OFF_H0B, &tm.yld[0], 0, row + 8 * 64, bar + B_H0 + 8);
          for (int i = 0; i < 3; i++) mbar_expect(bar + B_H1 + 8 * i, i < 2 ? 32768 : 16384);
          asm volatile("prefetch.tensormap [%0];" ::"l"(&tm.yld[1]) : "memory"));
      flag_wait(&lctr[(C_Y + rank) * 32], 32);
      ONE(fence_async_global();
          for (int i = 0; i < 5; i++) tma_ld2(sb + i * 16384, &tm.yld[1], 0, row + i * 128, bar + B_H1 + 8 * (i >> 1));
          PROF_T(5));
      const int lane = lane_id();
      unsigned old = 0;
      if (lane == 0) old = atomicAdd(&ctr[C_EXIT * 32], 1);
      if (__shfl_sync(0xffffffffu, old, 0) == 127) {
#pragma unroll
        for (int i = 0; i < 6; i++) *(uint4*)&ctr[((i >> 1) * 128 + (i & 1) * C_SIDE + lane) * 32] = make_uint4(0, 0, 0, 0);
      }
    }
    asm volatile("barrier.cluster.arrive.relaxed.aligned;\nbarrier.cluster.wait.aligned;" ::: "memory");
  } else {
    asm volatile("setmaxnreg.inc.sync.aligned.u32 224;");
    const int wg = warp >> 2, w = warp & 3;
    int lane = lane_id();
    asm volatile("barrier.cluster.wait.aligned;" ::: "memory");
    mbar_wait(bar + B_F, 0);
    const int id = __shfl_sync(0xffffffffu, read_info(bar, 0), 0) * 2 + rank;
    if (id >= 128) {
      float ea[80], eb[80];
      const int b = (id >> 1) & 1;
      constexpr int ES = 32768 + 2 * XBLK;
#pragma unroll 1
      for (int k = -3; k < 8; k++) {
        const int sl = (k + 3) % 3;
        if (k >= 0) {
          mbar_wait(bar + B_RAWX + 8 * sl, (k / 3) & 1);
          const uint64_t da = mk_desc(sb + sl * ES + wg * 16384), db = mk_desc(sb + sl * ES + 32768);
          wg_fence();
#pragma unroll
          for (int kk = 0; kk < 8; kk++) {
            const uint64_t a0 = da + (kk & 3) * 128, b0 = db + (kk & 3) * 2 + (kk >> 2) * (XBLK >> 4);
            wgmma_main<1>(ea, a0, b0, (k | kk) != 0);
            wgmma_main<1>(eb, a0 + 512, b0, (k | kk) != 0);
          }
          wg_commit();
          wg_wait<0>();
          asm volatile("bar.sync 3, 256;" ::: "memory");
        }
        if (k + 3 < 8 && warp == 0 && elect_one()) {
          if (k == -3) {
            for (int i = 0; i < 64; i++) {
              unsigned v;
              asm volatile("ld.relaxed.gpu.global.u32 %0, [%1];" : "=r"(v) : "l"(&ctr[(C_FLAG + 14) * 32]) : "memory");
              if (v >= 128) break;
              __nanosleep(500);
            }
          }
          const uint32_t dst = sb + sl * ES, fb = bar + B_RAWX + 8 * sl;
          mbar_expect(fb, ES);
          for (int q = 0; q < 4; q++) tma_ld2(dst + q * 8192, &tm.w30, rank * 256 + q * 64, (k + 3) * 64, fb);
          for (int q = 0; q < 2; q++) tma_ld3(dst + 32768 + q * XBLK, &tm.xe[q], (k + 3) * 64, 0, b, fb);
        }
        __syncwarp();
      }
      fence_regs(ea);
      fence_regs(eb);
      float* e0 = g_E + ((b * 8 + rank * 4 + wg * 2) * NT + 2 * (lane & 3)) * 64 + 16 * w + (lane >> 2);
#pragma unroll
      for (int i = 0; i < 80; i++) {
        const int o = (8 * (i >> 2) + (i & 1)) * 64 + ((i >> 1) & 1) * 8;
        e0[o] = ea[i];
        e0[o + NT * 64] = eb[i];
      }
      asm volatile("bar.sync 3, 256;" ::: "memory");
      if (threadIdx.x == 0) {
        fence_release();
        red_add(&ctr[C_E * 32]);
        PROF_T(28);
      }
      asm volatile("barrier.cluster.arrive.relaxed.aligned;\nbarrier.cluster.wait.aligned;" ::: "memory");
      return;
    }
    if (w < 2 && elect_one()) {
      const uint32_t fb = bar + B_RAWW + 8 * (wg * 2 + w);
      mbar_expect(fb, 2048);
      tma_ld3h(sb + OFF_WRAW + (wg * 2 + w) * 2048, &tm.we, 0, 0, (w * 64 + w_row(id)) * 8 + rank * 2 + wg, fb, policy_evict_first());
      if (!w) mbar_arrive(fb);
    }
    __syncwarp();
    {
      float yr[80], yi[80], t[32];

      int xs = 0, xph = 0;
      if (threadIdx.x == 0) PROF_T(24);
      W_WAIT(0);
      t_issue<false>(t, sb, WRAW(0));
      wg_wait<0>();
      W_FINISH();
      if (threadIdx.x == 0) PROF_T(25);
#pragma unroll 1
      for (int m = 0; m <= LW; m++) {
        X_WAIT();
        X_ISSUE();
        wg_wait<0>();
        X_FINISH((2 * id + wg) & 7);
        if (threadIdx.x == 0 && m == 0) PROF_T(26);
        if (has_x2(id, m, wg)) {
          X_WAIT();
          X_ISSUE();
          wg_wait<0>();
          X_FINISH(id & 7);
        }
        if (m < LW + XF && m) {
          W_WAIT(m);
          t_issue<false>(t, sb, WRAW(m));
          wg_wait<0>();
          W_FINISH();
        }
      }
      if (threadIdx.x == 0) PROF_T(27);
      const int ym = lane >> 3, yr8 = lane & 7;
      const uint32_t yad = (ym >> 1) * 4096 + yr8 * 128 + (((2 * w + (ym & 1)) ^ yr8) << 4);
#define STAGE_PROF0()
#define STAGE_PROF1()
#define STAGE_BEGIN() PROF_W(wfull, mbar_wait(bar + B_FULL + 8 * (v & 3), (v >> 2) & 1)); STAGE_PROF0(); const uint32_t st = sb + (v & 3) * G_STAGE
#define RELEASE(vv) do { if (w == 0 && lane < 2) mbar_arrive_cluster(bar + B_EMPTY + 8 * ((vv) & 3), lane, 1); } while (0)
#define XRAW (sb + OFF_XR + (wg * 3 + xs) * 8192)
#define STAGE_W0(mw, sd) do { W_WAIT(mw); batch<1, 0, 2>(yr, yi, t, st, wg, sd, sb + OFF_F, WRAW(mw)); wg_wait<1>(); W_FINISH(); wg_wait<0>(); RELEASE(v); } while (0)
#define STAGE_PLAIN0(sd) do { batch<0, 0, 2>(yr, yi, t, st, wg, sd, 0, 0); wg_wait<0>(); RELEASE(v); } while (0)
#define STAGE_W1(mw, sd) do { W_WAIT(mw); batch<1, 0, 1>(yr, yi, t, st, wg, sd, sb + OFF_F, WRAW(mw)); wg_wait<1>(); if (sd) RELEASE(v - 1); \
                              W_FINISH(); batch<0, 1, 2>(yr, yi, t, st, wg, 1, 0, 0); } while (0)
#define STAGE_PLAIN1(sd) do { batch<0, 0, 1>(yr, yi, t, st, wg, sd, 0, 0); wg_wait<1>(); if (sd) RELEASE(v - 1); \
                              batch<0, 1, 2>(yr, yi, t, st, wg, 1, 0, 0); } while (0)
#pragma unroll 1
      for (int v = 0; v < 32; v++) {
        const int m = XF ? (v >> 1) + LW + 1 : ((v + 1) >> 1) + LW;
        STAGE_BEGIN();
        if (XF ? (v & 1) : (!(v & 1) || v == 31)) {
          STAGE_W1(m, v != 0);
        } else if (m >= 16) {
          STAGE_PLAIN1(1);
        } else {
          X_WAIT();
          batch<4, 0, 1>(yr, yi, t, st, wg, v != 0, sb + OFF_F, XRAW);
          wg_wait<1>();
          if (v) RELEASE(v - 1);
          X_FINISH((2 * id + wg) & 7);
          if (has_x2(id, m, wg)) {
            X_WAIT();
            batch<4, 1, 2>(yr, yi, t, st, wg, 1, sb + OFF_F, XRAW);
            wg_wait<1>();
            X_FINISH(id & 7);
          } else {
            batch<0, 1, 2>(yr, yi, t, st, wg, 1, 0, 0);
          }
        }
        STAGE_PROF1();
      }
      wg_wait<0>();
      fence_regs(yr);
      fence_regs(yi);
      RELEASE(31);
      {
        uint32_t hold[32];
#pragma unroll
        for (int j = 0; j < 20; j++) {
          const uint32_t p0 = pack2(yr[4 * j], yr[4 * j + 1]), p1 = pack2(yr[4 * j + 2], yr[4 * j + 3]);
          const uint32_t p2 = pack2(yi[4 * j], yi[4 * j + 1]), p3 = pack2(yi[4 * j + 2], yi[4 * j + 3]);
          if (j < 12) {
            stsm4t(sb + OFF_XR + wg * 3 * 8192 + yad + (j >> 2) * 8192 + (j & 3) * 1024, p0, p1, p2, p3);
          } else {
            hold[4 * j - 48] = p0; hold[4 * j - 47] = p1; hold[4 * j - 46] = p2; hold[4 * j - 45] = p3;
          }
        }
#pragma unroll
        for (int j = 0; j < 32; j++) asm volatile("" : "+r"(hold[j])::"memory");
        fence_async_smem();
        __syncwarp();
        if (lane == 0) mbar_arrive(bar + B_Y + 8 * wg);
        if (threadIdx.x == 0) PROF_T(2);
#pragma unroll
        for (int v = 32; v < 34; v++) {
          STAGE_BEGIN();
          STAGE_PLAIN0(v != 32);
          STAGE_PROF1();
        }
        mbar_wait(bar + B_YFREE + 8 * wg, 0);
#pragma unroll
        for (int j = 0; j < 8; j++)
          stsm4t(sb + OFF_XR + wg * 3 * 8192 + yad + (j >> 2) * 8192 + (j & 3) * 1024, hold[4 * j], hold[4 * j + 1], hold[4 * j + 2], hold[4 * j + 3]);
        fence_async_smem();
        __syncwarp();
        if (lane == 0) mbar_arrive(bar + B_Y + 8 * wg);
#pragma unroll
        for (int j = 0; j < 32; j++) t[j] = __uint_as_float(hold[j]);
      }
#pragma unroll 1
      for (int v = 34; v < 64; v++) {
        const int m = (v >> 1) + LW;
        STAGE_BEGIN();
        if (!(v & 1) && m < 32) {
          STAGE_W0(m, 1);
        } else {
          STAGE_PLAIN0(1);
          if (v == 49 && wg == 0) part_ptr(xbuf, id >> 6, w >> 1, rank * 2 + ((id >> 1) & 1), (id >> 2) & 15)[(w & 1) * 32 + lane] = ~0ull;
        }
        STAGE_PROF1();
      }
      wg_wait<0>();
      fence_regs(yr);
      fence_regs(yi);
      asm volatile("bar.sync 3, 256;" ::: "memory");
#pragma unroll
      for (int j = 0; j < 20; j++) {
        stsm4t(sb + wg * 8192 + yad + (j >> 2) * 16384 + (j & 3) * 1024, pack2(yr[4 * j], yr[4 * j + 1]), pack2(yr[4 * j + 2], yr[4 * j + 3]),
               pack2(yi[4 * j], yi[4 * j + 1]), pack2(yi[4 * j + 2], yi[4 * j + 3]));
        if ((j & 3) == 3) {
          __syncwarp();
          if (lane == 0) mbar_arrive(bar + B_YP + 8 * (wg * 5 + (j >> 2)));
        }
      }
      if (threadIdx.x == 0) PROF_T(3);
    }
    asm volatile("barrier.cluster.arrive.relaxed.aligned;" ::: "memory");
    lane = lane_id();
    const int tid = warp * 32 + lane, b = id >> 6, u = (id >> 1) & 31;
    const int dq = rank * 2 + (u & 1), tr = u >> 1;
    const int a = lane & 3, d0 = 16 * w + (lane >> 2);
    float2* s_red = (float2*)(smem_raw + OFF_WRAW);
    const uint32_t oad = wg * 8192 + ((lane >> 4) * 8 + (lane & 7)) * 128 + (((2 * w + ((lane >> 3) & 1)) ^ (lane & 7)) << 4);
#pragma unroll 1
    for (int hf = 0; hf < 2; hf++) {
      const uint32_t base = sb + (hf ? 0 : OFF_XR), last = hf ? 0 : OFF_H0B - 65536 - OFF_XR;
      float acc[5][28];
      float q1[4] = {0.f, 0.f, 0.f, 0.f}, q2[4] = {0.f, 0.f, 0.f, 0.f};
      if (hf == 0) { mbar_wait(bar + B_H0, 0); mbar_wait(bar + B_H0C, 0); }
      const float* se = (const float*)(smem_raw + OFF_E + hf * 2560) + wg * 64 + d0;
#pragma unroll
      for (int k2 = 0; k2 < 4; k2++) {
        if (k2 < 3) {
          if (hf) mbar_wait(bar + B_H1 + 8 * k2, 0);
          else if (k2 == 2) mbar_wait(bar + B_H0 + 8, 0);
          const uint64_t da = mk_desc(base + (4 * k2 + wg) * 8192 + (k2 == 2 ? last : 0)), db = mk_desc(sb + OFF_F);
          wg_fence();
#pragma unroll
          for (int kk = 0; kk < 4; kk++) {
            wgmma_inv<1>(acc[2 * k2], da + 128 * kk, db + 2 * kk, kk);
            if (k2 < 2) wgmma_inv<1>(acc[2 * k2 + 1], da + 1024 + 128 * kk, db + 2 * kk, kk);
          }
          wg_commit();
        }
        if (k2 > 0) {
          if (k2 < 3) wg_wait<1>(); else wg_wait<0>();
#pragma unroll
          for (int k = 2 * k2 - 2; k < 2 * k2 && k < 5; k++) {
            fence_regs(acc[k]);
            if (a == 0) {
              acc[k][25] += se[k * 128];
              acc[k][27] += se[k * 128 + 8];
            }
            if (k == 4 && tr == 15 && wg == 1) {
#pragma unroll
              for (int i = 16; i < 28; i++)
                if (8 * (i >> 2) + (i & 1) + 2 * a >= LOUT - (NT - 1) * MT) acc[k][i] = 0.f;
            }
#pragma unroll
            for (int i = 0; i < 28; i++) {
              q1[i & 3] += acc[k][i];
              q2[i & 3] = fmaf(acc[k][i], acc[k][i], q2[i & 3]);
            }
            fence_regs(q1);
            fence_regs(q2);
          }
        }
      }
      float s1[2] = {q1[0] + q1[1], q1[2] + q1[3]}, s2[2] = {q2[0] + q2[1], q2[2] + q2[3]};
#pragma unroll
      for (int i = 0; i < 2; i++) {
#pragma unroll
        for (int o = 1; o < 4; o <<= 1) {
          s1[i] += __shfl_xor_sync(0xffffffffu, s1[i], o);
          s2[i] += __shfl_xor_sync(0xffffffffu, s2[i], o);
        }
      }
      if (a == 0) {
        s_red[wg * 64 + d0] = make_float2(s1[0], s2[0]);
        s_red[wg * 64 + d0 + 8] = make_float2(s1[1], s2[1]);
      }
      asm volatile("bar.sync 3, 256;" ::: "memory");
      if (tid == 0) PROF_T(6 + 3 * hf);
      if (tid < 64) {
        const float2 p0 = s_red[tid], p1 = s_red[64 + tid];
        const float x1 = p0.x + p1.x, x2 = p0.y + p1.y;
        const unsigned long long v = ((unsigned long long)(__float_as_uint(x2) & 0x7fffffffu) << 32) | __float_as_uint(x1);
        asm volatile("st.relaxed.gpu.global.u64 [%0], %1;" ::"l"(part_ptr(xbuf, b, hf, dq, tr) + tid), "l"(v) : "memory");
      }
      {
        const unsigned long long* q = part_ptr(xbuf, b, hf, dq, (tid >> 6) * 4) + (tid & 63);
        unsigned long long v[4];
        poll64x4(q, v);
        float x1 = 0.f, x2 = 0.f;
#pragma unroll
        for (int i = 0; i < 4; i++) {
          x1 += __uint_as_float((uint32_t)v[i]);
          x2 += __uint_as_float((uint32_t)(v[i] >> 32));
        }
        s_red[128 + tid] = make_float2(x1, x2);
      }
      asm volatile("bar.sync 3, 256;" ::: "memory");
      if (tid == 0) PROF_T(7 + 3 * hf);
#pragma unroll
      for (int i = 0; i < 2; i++) {
        const float2 q0 = s_red[128 + d0 + 8 * i], q1 = s_red[192 + d0 + 8 * i], q2 = s_red[256 + d0 + 8 * i], q3 = s_red[320 + d0 + 8 * i];
        const float mu = ((q0.x + q1.x) + (q2.x + q3.x)) * (1.f / LOUT);
        const float var = fmaxf(((q0.y + q1.y) + (q2.y + q3.y)) * (1.f / LOUT) - mu * mu, 0.f);
        const __nv_bfloat16* gb = (const __nv_bfloat16*)(smem_raw + OFF_GB + hf * 256) + d0 + 8 * i;
        s1[i] = 0.5f * __bfloat162float(gb[0]) * rsqrtf(var + 1e-5f);
        s2[i] = 0.5f * __bfloat162float(gb[64]) - mu * s1[i];
      }
#pragma unroll
      for (int k = 0; k < 5; k++) {
        float hz[28];
#pragma unroll
        for (int i = 0; i < 28; i++) hz[i] = fmaf(acc[k][i], s1[(i >> 1) & 1], s2[(i >> 1) & 1]);
        gelu_store(hz, base + oad + k * 16384 + (k == 4 ? last : 0));
        float z;
        asm volatile("ld.volatile.shared.f32 %0, [%1];" : "=f"(z) : "r"(sb + OFF_F + 55 * 128) : "memory");
        s2[0] += z;
        s2[1] += z;
        __syncwarp();
        if (lane == 0) mbar_arrive(bar + B_OUT + 8 * (wg * 5 + k));
      }
      if (tid == 0) PROF_T(8 + 3 * hf);
    }
    asm volatile("barrier.cluster.wait.aligned;" ::: "memory");
  }
}

typedef CUresult (*EncFn)(CUtensorMap*, CUtensorMapDataType, cuuint32_t, void*, const cuuint64_t*, const cuuint64_t*, const cuuint32_t*,
                          const cuuint32_t*, CUtensorMapInterleave, CUtensorMapSwizzle, CUtensorMapL2promotion, CUtensorMapFloatOOBfill);

void encode(EncFn fn, CUtensorMap* m, int rank, void* base, const cuuint64_t* dims, const cuuint64_t* strides, const cuuint32_t* box,
            CUtensorMapL2promotion promo) {
  cuuint32_t es[5] = {1, 1, 1, 1, 1};
  fn(m, CU_TENSOR_MAP_DATA_TYPE_BFLOAT16, rank, base, dims, strides, box, es, CU_TENSOR_MAP_INTERLEAVE_NONE, CU_TENSOR_MAP_SWIZZLE_128B, promo,
     CU_TENSOR_MAP_FLOAT_OOB_FILL_NONE);
}

}

extern "C" void kernel_launch(void* const* d_in, const int* in_sizes, int n_in, void* d_out, int out_size) {
  (void)in_sizes; (void)n_in; (void)out_size;
  const __nv_bfloat16* x = (const __nv_bfloat16*)d_in[0];
  const __nv_bfloat16* w = (const __nv_bfloat16*)d_in[1];
  const __nv_bfloat16* gamma = (const __nv_bfloat16*)d_in[2];
  const __nv_bfloat16* beta = (const __nv_bfloat16*)d_in[3];
  void* fnp = nullptr;
  cudaDriverEntryPointQueryResult qr;
  cudaGetDriverEntryPoint("cuTensorMapEncodeTiled", &fnp, cudaEnableDefault, &qr);
  EncFn fn = (EncFn)fnp;
  void *fptr = nullptr, *xptr = nullptr, *wptr = nullptr, *yptr = nullptr;
  cudaGetSymbolAddress(&fptr, g_Fimg);
  cudaGetSymbolAddress(&xptr, g_X);
  cudaGetSymbolAddress(&wptr, g_W);
  cudaGetSymbolAddress(&yptr, g_Y);
  xptr = (void*)(((uintptr_t)xptr + (1u << 21) - 1) & ~(uintptr_t)((1u << 21) - 1));
  const CUtensorMapL2promotion P0 = CU_TENSOR_MAP_L2_PROMOTION_NONE, P128 = CU_TENSOR_MAP_L2_PROMOTION_L2_128B;
  Maps m;
  {
    cuuint64_t d[3] = {1024, 8000, 2}, s[2] = {2048, 8000ull * 2048};
    cuuint32_t bx[3] = {64, 64, 1};
    encode(fn, &m.x, 3, (void*)x, d, s, bx, P128);
  }
  for (int ph = 0; ph < 2; ph++) {
    cuuint64_t d[3] = {64, (cuuint64_t)(16 - ph), 4096}, s[2] = {2ull * 262144 * 2, 128};
    cuuint32_t bx[3] = {64, 16, 1};
    encode(fn, ph ? &m.wo : &m.we, 3, (void*)(w + (size_t)ph * 262144), d, s, bx, P128);
  }
  for (int par = 0; par < 2; par++) {
    cuuint64_t d[5] = {(cuuint64_t)XPAGES << 20, 2, 4, 2, 2}, s[4] = {par ? 0x1000u : 0x3000u, 1u << 14, 1u << 18, 1u << 20};
    cuuint32_t bx[5] = {64, 2, 4, 2, 2};
    encode(fn, &m.xst[par], 5, xptr, d, s, bx, P0);
  }
  {
    cuuint64_t d[4] = {64, 32, 2, (cuuint64_t)WR * WSLOT / 128}, s[3] = {2ull * WBLK, 4096, 128};
    cuuint32_t bx[4] = {64, 32, 2, 1};
    encode(fn, &m.wst, 4, wptr, d, s, bx, P0);
  }
  for (int p = 0; p < 2; p++) {
    void* base = p ? wptr : yptr;
    cuuint64_t d[4] = {64, NT, 64, 8}, s[3] = {8192, 128, (cuuint64_t)NT * 8192};
    cuuint32_t bx[4] = {64, 32, 2, 1};
    encode(fn, &m.yst[p], 4, base, d, s, bx, P0);
    cuuint64_t d2[2] = {64, 8ull * NT * 64}, s2[1] = {128};
    cuuint32_t bx2[2] = {64, 128};
    encode(fn, &m.yld[p], 2, base, d2, s2, bx2, P128);
  }
  {
    cuuint64_t d[3] = {512, LOUT, 2}, s[2] = {1024, (cuuint64_t)LOUT * 1024};
    cuuint32_t bx[3] = {64, MT, 1};
    encode(fn, &m.out, 3, d_out, d, s, bx, P0);
  }
  for (int q = 0; q < 2; q++) {
    cuuint64_t d[3] = {512, (cuuint64_t)(NT - q), 2}, s[2] = {MT * 2048, 8000ull * 2048};
    cuuint32_t bx[3] = {64, NT, 1};
    encode(fn, &m.xe[q], 3, (void*)(x + q * 64 * 1024), d, s, bx, P128);
  }
  {
    cuuint64_t d[2] = {512, 512}, s[1] = {1024};
    cuuint32_t bx[2] = {64, 64};
    encode(fn, &m.w30, 2, (void*)(w + 30 * 262144), d, s, bx, P128);
  }
  cudaFuncSetAttribute(k1_main, cudaFuncAttributeMaxDynamicSharedMemorySize, SMEM_BYTES);
  k1_main<<<132, 512, SMEM_BYTES>>>((uint8_t*)xptr, fptr, gamma, beta, m);
}
```

```cpp
#include <cuda_runtime.h>
#include <cuda_bf16.h>
#include <cuda.h>
#include <stdint.h>

namespace {

#define YA 2
#define HOLD 1
constexpr int LOUT = 7985;
constexpr int MT = 50;
constexpr int NT = 160;
constexpr int XBLK = NT * 128;
constexpr int WBLK = 16384;
constexpr int LW = 4;
constexpr int WR = 10;
constexpr int WSLOT = 64 * WBLK;
constexpr int PG_Y = 20, PG_W = 25, XPAGES = 30;
constexpr int NFL = 2;
constexpr int XKEEP = 9;
constexpr int YFLUSH = 20 + LW;

__device__ __align__(1024) uint8_t g_X[(XPAGES + 2) << 21];
__device__ __align__(128) float g_E[16 * NT * 64];
constexpr int CTR_OFF = (XPAGES << 21) + 0x100000, PART_OFF = CTR_OFF + 0x40000;
constexpr int C_FLAG = 0, C_LOADED = 128  , C_Y = 256, C_E = 260, C_REG = 261, C_EXIT = 262, C_SIDE = 32;
__device__ __forceinline__ unsigned long long* part_ptr(uint8_t* xbuf, int side, int hf, int dq, int tr) {
  return (unsigned long long*)(xbuf + PART_OFF + ((hf * 4 + dq) * 2 + (tr >> 3)) * 8192 + ((side ^ hf ^ (tr >> 3)) << 12) + (tr & 7) * 512);
}
#define PROF_T(i)
#define PROF_C(i)
#define PROF_V(i, v)
#define PROF_W(acc, stmt) stmt

__device__ __align__(128) const uint32_t g_Fimg[2048] = {
 0x3f803f80,0x3f7d3f7f,0x3f783f7b,0x3f713f75,0x3f673f6d,0x3f5c3f62,0x3f4e3f55,0x3f3e3f46,0x3f2c3f35,0x3f183f22,0x3f043f0e,0x3edb3ef1,0x3eac3ec4,0x3e793e95,0x3e163e48,0x3d493dc9,
 0xbd490000,0xbe16bdc9,0xbe79be48,0xbeacbe95,0xbedbbec4,0xbf04bef1,0xbf18bf0e,0xbf2cbf22,0xbf3ebf35,0xbf4ebf46,0xbf5cbf55,0xbf67bf62,0xbf71bf6d,0xbf78bf75,0xbf7dbf7b,0xbf80bf7f,
 0x3e793ec4,0xbd493dc9,0xbeacbe48,0xbf18bef1,0x3f7d3f80,0x3f673f75,0x3f3e3f55,0x3f043f22,0xbf5cbf6d,0xbf2cbf46,0xbedbbf0e,0xbe16be95,0xbf4ebf35,0xbf71bf62,0xbf80bf7b,0xbf78bf7f,
 0x3f783f6d,0x3f803f7f,0x3f713f7b,0x3f4e3f62,0x3e160000,0x3edb3e95,0x3f2c3f0e,0x3f5c3f46,0xbf04bec4,0xbf3ebf22,0xbf67bf55,0xbf7dbf75,0x3f183f35,0x3eac3ef1,0x3d493e48,0xbe79bdc9,
 0xbf04bf35,0xbd49be95,0x3edb3e48,0x3f4e3f22,0x3f7d3f6d,0x3f713f7f,0x3f2c3f55,0x3e793ef1,0x3f783f80,0x3f3e3f62,0x3eac3f0e,0xbe163dc9,0xbf18bec4,0xbf67bf46,0xbf80bf7b,0xbf5cbf75,
 0x3f5c3f35,0x3f803f75,0x3f673f7b,0x3f183f46,0x3e163ec4,0xbeacbdc9,0xbf3ebf0e,0xbf78bf62,0xbe790000,0xbf2cbef1,0xbf71bf55,0xbf7dbf7f,0xbf4ebf6d,0xbedbbf22,0x3d49be48,0x3f043e95,
 0xbf2cbec4,0xbf7dbf62,0xbf5cbf7b,0xbeacbf22,0x3f673f35,0x3f783f7f,0x3f183f55,0xbd493e95,0xbf80bf6d,0xbf4ebf75,0xbe79bf0e,0x3edb3dc9,0x3f713f80,0x3f043f46,0xbe163e48,0xbf3ebef1,
 0x3f3e3f6d,0x3e163ef1,0xbf04be48,0xbf71bf46,0xbedbbf35,0x3e79bdc9,0x3f4e3f0e,0x3f803f75,0x3d493ec4,0xbf18be95,0xbf78bf55,0xbf67bf7f,0x3eac0000,0x3f5c3f22,0x3f7d3f7b,0x3f2c3f62,
 0xbedb0000,0xbf78bf46,0xbf4ebf7b,0xbd49bef1,0x3f3e3ec4,0x3f7d3f75,0x3f043f55,0xbeac3dc9,0xbf71bf35,0xbf5cbf7f,0xbe16bf0e,0x3f2c3e95,0x3f803f6d,0x3f183f62,0xbe793e48,0xbf67bf22,
 0x3f673f80,0x3e793f22,0xbf18be48,0xbf80bf62,0xbf2cbf6d,0x3e16be95,0x3f5c3f0e,0x3f713f7f,0x3eac3f35,0xbf04bdc9,0xbf7dbf55,0xbf3ebf75,0x3d49bec4,0x3f4e3ef1,0x3f783f7b,0x3edb3f46,
 0xbf7dbf6d,0xbeacbf46,0x3f2c3e48,0x3f783f75,0x3f040000,0x3f803f62,0x3edb3f55,0xbf18bdc9,0x3f4e3ec4,0x3f673f7f,0x3d493f0e,0xbf5cbef1,0x3e793f35,0xbf3ebe95,0xbf71bf7b,0xbe16bf22,
 0x3e16bec4,0x3f713f22,0x3f3e3f7b,0xbe793e95,0x3f5c3f80,0xbd493ef1,0xbf67bf0e,0xbf4ebf7f,0x3f183f6d,0xbedb3dc9,0xbf80bf55,0xbf04bf62,0xbf78bf35,0xbf2cbf75,0x3eacbe48,0x3f7d3f46,
 0x3f7d3f35,0x3edb3f62,0xbf3ebe48,0xbf5cbf7f,0x3e79bec4,0x3f803f46,0x3eac3f55,0xbf4ebe95,0xbf180000,0xbf71bf75,0x3d49bf0e,0x3f783f22,0x3f043f6d,0xbf2cbdc9,0xbf67bf7b,0x3e16bef1,
 0xbe16bf35,0x3f673ef1,0x3f2c3f7b,0xbf043dc9,0xbf78bf6d,0xbd49bf22,0x3f713f0e,0x3f183f75,0x3f4e3f80,0xbeac3e95,0xbf80bf55,0xbe79bf46,0x3f5c3ec4,0x3f3e3f7f,0xbedb3e48,0xbf7dbf62,
 0xbedbbf6d,0x3f5c3e95,0x3f183f7b,0xbf3ebdc9,0xbd49bf35,0x3f7d3f22,0x3e793f55,0xbf71bef1,0x3eacbec4,0x3f783f62,0xbe163f0e,0xbf80bf46,0x3f2c0000,0x3f4e3f7f,0xbf043e48,0xbf67bf75,
 0x3f673ec4,0x3f043f75,0xbf4ebe48,0xbf2cbf7f,0x3f803f35,0x3e163f46,0xbf78bf0e,0xbeacbf62,0x3f713f6d,0xbe793ef1,0xbf7dbf55,0x3d49bf22,0x3f3e3f80,0xbf183dc9,0xbf5cbf7b,0x3edbbe95,
 0xbd490000,0xbe16bdc9,0xbe79be48,0xbeacbe95,0xbedbbec4,0xbf04bef1,0xbf18bf0e,0xbf2cbf22,0xbf3ebf35,0xbf4ebf46,0xbf5cbf55,0xbf67bf62,0xbf71bf6d,0xbf78bf75,0xbf7dbf7b,0xbf80bf7f,
 0xbf80bf80,0xbf7dbf7f,0xbf78bf7b,0xbf71bf75,0xbf67bf6d,0xbf5cbf62,0xbf4ebf55,0xbf3ebf46,0xbf2cbf35,0xbf18bf22,0xbf04bf0e,0xbedbbef1,0xbeacbec4,0xbe79be95,0xbe16be48,0xbd49bdc9,
 0xbf78bf6d,0xbf80bf7f,0xbf71bf7b,0xbf4ebf62,0xbe160000,0xbedbbe95,0xbf2cbf0e,0xbf5cbf46,0x3f043ec4,0x3f3e3f22,0x3f673f55,0x3f7d3f75,0xbf18bf35,0xbeacbef1,0xbd49be48,0x3e793dc9,
 0x3e793ec4,0xbd493dc9,0xbeacbe48,0xbf18bef1,0x3f7d3f80,0x3f673f75,0x3f3e3f55,0x3f043f22,0xbf5cbf6d,0xbf2cbf46,0xbedbbf0e,0xbe16be95,0xbf4ebf35,0xbf71bf62,0xbf80bf7b,0xbf78bf7f,
 0x3f5c3f35,0x3f803f75,0x3f673f7b,0x3f183f46,0x3e163ec4,0xbeacbdc9,0xbf3ebf0e,0xbf78bf62,0xbe790000,0xbf2cbef1,0xbf71bf55,0xbf7dbf7f,0xbf4ebf6d,0xbedbbf22,0x3d49be48,0x3f043e95,
 0x3f043f35,0x3d493e95,0xbedbbe48,0xbf4ebf22,0xbf7dbf6d,0xbf71bf7f,0xbf2cbf55,0xbe79bef1,0xbf78bf80,0xbf3ebf62,0xbeacbf0e,0x3e16bdc9,0x3f183ec4,0x3f673f46,0x3f803f7b,0x3f5c3f75,
 0xbf3ebf6d,0xbe16bef1,0x3f043e48,0x3f713f46,0x3edb3f35,0xbe793dc9,0xbf4ebf0e,0xbf80bf75,0xbd49bec4,0x3f183e95,0x3f783f55,0x3f673f7f,0xbeac0000,0xbf5cbf22,0xbf7dbf7b,0xbf2cbf62,
 0xbf2cbec4,0xbf7dbf62,0xbf5cbf7b,0xbeacbf22,0x3f673f35,0x3f783f7f,0x3f183f55,0xbd493e95,0xbf80bf6d,0xbf4ebf75,0xbe79bf0e,0x3edb3dc9,0x3f713f80,0x3f043f46,0xbe163e48,0xbf3ebef1,
 0xbf67bf80,0xbe79bf22,0x3f183e48,0x3f803f62,0x3f2c3f6d,0xbe163e95,0xbf5cbf0e,0xbf71bf7f,0xbeacbf35,0x3f043dc9,0x3f7d3f55,0x3f3e3f75,0xbd493ec4,0xbf4ebef1,0xbf78bf7b,0xbedbbf46,
 0xbedb0000,0xbf78bf46,0xbf4ebf7b,0xbd49bef1,0x3f3e3ec4,0x3f7d3f75,0x3f043f55,0xbeac3dc9,0xbf71bf35,0xbf5cbf7f,0xbe16bf0e,0x3f2c3e95,0x3f803f6d,0x3f183f62,0xbe793e48,0xbf67bf22,
 0x3e16bec4,0x3f713f22,0x3f3e3f7b,0xbe793e95,0x3f5c3f80,0xbd493ef1,0xbf67bf0e,0xbf4ebf7f,0x3f183f6d,0xbedb3dc9,0xbf80bf55,0xbf04bf62,0xbf78bf35,0xbf2cbf75,0x3eacbe48,0x3f7d3f46,
 0x3f7d3f6d,0x3eac3f46,0xbf2cbe48,0xbf78bf75,0xbf040000,0xbf80bf62,0xbedbbf55,0x3f183dc9,0xbf4ebec4,0xbf67bf7f,0xbd49bf0e,0x3f5c3ef1,0xbe79bf35,0x3f3e3e95,0x3f713f7b,0x3e163f22,
 0x3e163f35,0xbf67bef1,0xbf2cbf7b,0x3f04bdc9,0x3f783f6d,0x3d493f22,0xbf71bf0e,0xbf18bf75,0xbf4ebf80,0x3eacbe95,0x3f803f55,0x3e793f46,0xbf5cbec4,0xbf3ebf7f,0x3edbbe48,0x3f7d3f62,
 0x3f7d3f35,0x3edb3f62,0xbf3ebe48,0xbf5cbf7f,0x3e79bec4,0x3f803f46,0x3eac3f55,0xbf4ebe95,0xbf180000,0xbf71bf75,0x3d49bf0e,0x3f783f22,0x3f043f6d,0xbf2cbdc9,0xbf67bf7b,0x3e16bef1,
 0x3f673ec4,0x3f043f75,0xbf4ebe48,0xbf2cbf7f,0x3f803f35,0x3e163f46,0xbf78bf0e,0xbeacbf62,0x3f713f6d,0xbe793ef1,0xbf7dbf55,0x3d49bf22,0x3f3e3f80,0xbf183dc9,0xbf5cbf7b,0x3edbbe95,
 0x3edb3f6d,0xbf5cbe95,0xbf18bf7b,0x3f3e3dc9,0x3d493f35,0xbf7dbf22,0xbe79bf55,0x3f713ef1,0xbeac3ec4,0xbf78bf62,0x3e16bf0e,0x3f803f46,0xbf2c0000,0xbf4ebf7f,0x3f04be48,0x3f673f75,
 0x3f2c3f80,0xbf4ebdc9,0xbf04bf7b,0x3f673e95,0x3eac3f6d,0xbf78bef1,0xbe16bf55,0x3f803f22,0xbd493f35,0xbf7dbf46,0x3e79bf0e,0x3f713f62,0xbedb3ec4,0xbf5cbf75,0x3f18be48,0x3f3e3f7f,
 0xbf3e0000,0xbf18bf7f,0x3f5c3e48,0x3edb3f75,0xbf71bec4,0xbe79bf62,0x3f7d3f0e,0x3d493f46,0xbf80bf35,0x3e16bf22,0x3f783f55,0xbeac3ef1,0xbf67bf6d,0x3f04be95,0x3f4e3f7b,0xbf2c3dc9,
 0xbf043ec4,0xbf2cbf7f,0x3f673e48,0x3e163f62,0x3f183f80,0xbf71be95,0xbd49bf55,0x3f783f46,0xbe79bf6d,0x3f803f22,0xbeac3f0e,0xbf4ebf75,0xbf7dbf35,0x3edbbef1,0x3f3e3f7b,0xbf5cbdc9,
 0x3f5c3f6d,0xbf3e3dc9,0xbedbbf7b,0x3f7d3ef1,0x3f4e0000,0x3eac3f75,0xbf80bf0e,0x3e79bf22,0xbf78bec4,0x3d49bf46,0x3f713f55,0xbf183e95,0xbe163f35,0xbf67bf62,0x3f2cbe48,0x3f043f7f,
 0x3e79bf35,0x3f3e3f75,0xbf71be48,0x3e16bf46,0x3f4e3f6d,0xbf67bdc9,0x3d49bf55,0x3f5c3f62,0x3f043f80,0xbf80bef1,0x3edbbf0e,0x3f183f7f,0xbf7dbec4,0x3eacbf22,0x3f2c3f7b,0xbf78be95,
 0x3f783f35,0xbf2c3e95,0xbeacbf7b,0x3f7d3f22,0xbf183ec4,0xbedbbf7f,0x3f803f0e,0xbf043ef1,0xbf5c0000,0xbd49bf62,0x3f673f55,0xbf4e3dc9,0xbe16bf6d,0x3f713f46,0xbf3e3e48,0xbe79bf75,
 0xbf80bec4,0x3f18bef1,0x3e793f7b,0xbf67bf46,0x3f713f35,0xbf5c3dc9,0x3e16bf55,0x3f2c3f75,0xbf3ebf6d,0x3f7d3e95,0xbf043f0e,0xbeacbf7f,0x3edb3f80,0xbf78bf22,0x3f4ebe48,0xbd493f62,
 0x3d493f6d,0xbf4ebf62,0x3f783e48,0xbedb3f22,0x3eacbf35,0x3f043f7f,0xbf7dbf0e,0x3f3ebe95,0xbf2c3ec4,0xbe16bf75,0x3f5c3f55,0xbf71bdc9,0x3f670000,0xbe793f46,0xbf18bf7b,0x3f803ef1,
 0xbf710000,0x3f04bf22,0x3e163f7b,0xbf3ebf62,0x3f803ec4,0xbf4e3e95,0x3e79bf55,0x3edb3f7f,0xbf67bf35,0x3f783dc9,0xbf183f0e,0xbd49bf75,0x3f2c3f6d,0xbf7dbef1,0x3f5cbe48,0xbeac3f46,
 0x3eac3f80,0xbf5cbf46,0x3f7d3e48,0xbf2c3ef1,0x3d49bf6d,0x3f183f75,0xbf78bf0e,0x3f67bdc9,0xbedb3f35,0xbe79bf7f,0x3f4e3f55,0xbf80be95,0x3f3ebec4,0xbe163f62,0xbf04bf7b,0x3f713f22,
 0xbf18bf6d,0x3f673f22,0xbf80be48,0x3f5cbe95,0x3f780000,0xbf3e3ef1,0x3eacbf55,0x3e163f7f,0x3f7d3ec4,0xbf713dc9,0x3f2cbf0e,0xbe793f62,0xbf043f35,0x3d49bf75,0x3edb3f7b,0xbf4ebf46,
 0x3f4ebec4,0xbedb3f46,0xbd49bf7b,0x3f043f75,0x3e793f80,0xbf2cbf62,0x3f713f0e,0xbf7dbdc9,0xbe163f6d,0xbeacbf7f,0x3f3e3f55,0xbf78bef1,0xbf5cbf35,0x3f803e95,0xbf673e48,0x3f18bf22,
 0x3f4e3f35,0xbf71bef1,0x3f803e48,0xbf783dc9,0x3f5cbec4,0xbf2c3f22,0x3edbbf55,0xbe163f75,0xbf7d0000,0x3f67be95,0xbf3e3f0e,0x3f04bf46,0xbe793f6d,0xbd49bf7f,0x3eac3f7b,0xbf18bf62,
 0x3f18bf35,0xbeac3f62,0x3d49bf7b,0x3e793f7f,0xbf04bf6d,0x3f3e3f46,0xbf67bf0e,0x3f7d3e95,0x3e163f80,0xbedbbf75,0x3f2c3f55,0xbf5cbf22,0x3f783ec4,0xbf80bdc9,0x3f71be48,0xbf4e3ef1,
 0x3eacbf6d,0xbe793f75,0x3e16bf7b,0xbd493f7f,0x3f2cbf35,0xbf183f46,0x3f04bf55,0xbedb3f62,0x3f67bec4,0xbf5c3ef1,0x3f4ebf0e,0xbf3e3f22,0x3f800000,0xbf7d3dc9,0x3f78be48,0xbf713e95,
 0x3f713ec4,0xbf78be95,0x3f7d3e48,0xbf80bdc9,0x3f3e3f35,0xbf4ebf22,0x3f5c3f0e,0xbf67bef1,0x3edb3f6d,0xbf04bf62,0x3f183f55,0xbf2cbf46,0x3d493f80,0xbe16bf7f,0x3e793f7b,0xbeacbf75,
 0xbf3e0000,0xbf18bf7f,0x3f5c3e48,0x3edb3f75,0xbf71bec4,0xbe79bf62,0x3f7d3f0e,0x3d493f46,0xbf80bf35,0x3e16bf22,0x3f783f55,0xbeac3ef1,0xbf67bf6d,0x3f04be95,0x3f4e3f7b,0xbf2c3dc9,
 0xbf2cbf80,0x3f4e3dc9,0x3f043f7b,0xbf67be95,0xbeacbf6d,0x3f783ef1,0x3e163f55,0xbf80bf22,0x3d49bf35,0x3f7d3f46,0xbe793f0e,0xbf71bf62,0x3edbbec4,0x3f5c3f75,0xbf183e48,0xbf3ebf7f,
 0xbf5cbf6d,0x3f3ebdc9,0x3edb3f7b,0xbf7dbef1,0xbf4e0000,0xbeacbf75,0x3f803f0e,0xbe793f22,0x3f783ec4,0xbd493f46,0xbf71bf55,0x3f18be95,0x3e16bf35,0x3f673f62,0xbf2c3e48,0xbf04bf7f,
 0xbf043ec4,0xbf2cbf7f,0x3f673e48,0x3e163f62,0x3f183f80,0xbf71be95,0xbd49bf55,0x3f783f46,0xbe79bf6d,0x3f803f22,0xbeac3f0e,0xbf4ebf75,0xbf7dbf35,0x3edbbef1,0x3f3e3f7b,0xbf5cbdc9,
 0x3f783f35,0xbf2c3e95,0xbeacbf7b,0x3f7d3f22,0xbf183ec4,0xbedbbf7f,0x3f803f0e,0xbf043ef1,0xbf5c0000,0xbd49bf62,0x3f673f55,0xbf4e3dc9,0xbe16bf6d,0x3f713f46,0xbf3e3e48,0xbe79bf75,
 0xbe793f35,0xbf3ebf75,0x3f713e48,0xbe163f46,0xbf4ebf6d,0x3f673dc9,0xbd493f55,0xbf5cbf62,0xbf04bf80,0x3f803ef1,0xbedb3f0e,0xbf18bf7f,0x3f7d3ec4,0xbeac3f22,0xbf2cbf7b,0x3f783e95,
 0xbd49bf6d,0x3f4e3f62,0xbf78be48,0x3edbbf22,0xbeac3f35,0xbf04bf7f,0x3f7d3f0e,0xbf3e3e95,0x3f2cbec4,0x3e163f75,0xbf5cbf55,0x3f713dc9,0xbf670000,0x3e79bf46,0x3f183f7b,0xbf80bef1,
 0xbf80bec4,0x3f18bef1,0x3e793f7b,0xbf67bf46,0x3f713f35,0xbf5c3dc9,0x3e16bf55,0x3f2c3f75,0xbf3ebf6d,0x3f7d3e95,0xbf043f0e,0xbeacbf7f,0x3edb3f80,0xbf78bf22,0x3f4ebe48,0xbd493f62,
 0xbeacbf80,0x3f5c3f46,0xbf7dbe48,0x3f2cbef1,0xbd493f6d,0xbf18bf75,0x3f783f0e,0xbf673dc9,0x3edbbf35,0x3e793f7f,0xbf4ebf55,0x3f803e95,0xbf3e3ec4,0x3e16bf62,0x3f043f7b,0xbf71bf22,
 0xbf710000,0x3f04bf22,0x3e163f7b,0xbf3ebf62,0x3f803ec4,0xbf4e3e95,0x3e79bf55,0x3edb3f7f,0xbf67bf35,0x3f783dc9,0xbf183f0e,0xbd49bf75,0x3f2c3f6d,0xbf7dbef1,0x3f5cbe48,0xbeac3f46,
 0x3f4ebec4,0xbedb3f46,0xbd49bf7b,0x3f043f75,0x3e793f80,0xbf2cbf62,0x3f713f0e,0xbf7dbdc9,0xbe163f6d,0xbeacbf7f,0x3f3e3f55,0xbf78bef1,0xbf5cbf35,0x3f803e95,0xbf673e48,0x3f18bf22,
 0x3f183f6d,0xbf67bf22,0x3f803e48,0xbf5c3e95,0xbf780000,0x3f3ebef1,0xbeac3f55,0xbe16bf7f,0xbf7dbec4,0x3f71bdc9,0xbf2c3f0e,0x3e79bf62,0x3f04bf35,0xbd493f75,0xbedbbf7b,0x3f4e3f46,
 0xbf183f35,0x3eacbf62,0xbd493f7b,0xbe79bf7f,0x3f043f6d,0xbf3ebf46,0x3f673f0e,0xbf7dbe95,0xbe16bf80,0x3edb3f75,0xbf2cbf55,0x3f5c3f22,0xbf78bec4,0x3f803dc9,0xbf713e48,0x3f4ebef1,
 0x3f4e3f35,0xbf71bef1,0x3f803e48,0xbf783dc9,0x3f5cbec4,0xbf2c3f22,0x3edbbf55,0xbe163f75,0xbf7d0000,0x3f67be95,0xbf3e3f0e,0x3f04bf46,0xbe793f6d,0xbd49bf7f,0x3eac3f7b,0xbf18bf62,
 0x3f713ec4,0xbf78be95,0x3f7d3e48,0xbf80bdc9,0x3f3e3f35,0xbf4ebf22,0x3f5c3f0e,0xbf67bef1,0x3edb3f6d,0xbf04bf62,0x3f183f55,0xbf2cbf46,0x3d493f80,0xbe16bf7f,0x3e793f7b,0xbeacbf75,
 0xbeac3f6d,0x3e79bf75,0xbe163f7b,0x3d49bf7f,0xbf2c3f35,0x3f18bf46,0xbf043f55,0x3edbbf62,0xbf673ec4,0x3f5cbef1,0xbf4e3f0e,0x3f3ebf22,0xbf800000,0x3f7dbdc9,0xbf783e48,0x3f71be95,
 0xbd493f80,0x3e16bf7f,0xbe793f7b,0x3eacbf75,0xbedb3f6d,0x3f04bf62,0xbf183f55,0x3f2cbf46,0xbf3e3f35,0x3f4ebf22,0xbf5c3f0e,0x3f67bef1,0xbf713ec4,0x3f78be95,0xbf7d3e48,0x3f80bdc9,
 0xbf800000,0x3f7d3dc9,0xbf78be48,0x3f713e95,0xbf67bec4,0x3f5c3ef1,0xbf4ebf0e,0x3f3e3f22,0xbf2cbf35,0x3f183f46,0xbf04bf55,0x3edb3f62,0xbeacbf6d,0x3e793f75,0xbe16bf7b,0x3d493f7f,
 0xbf783ec4,0x3f80bdc9,0xbf71be48,0x3f4e3ef1,0xbe163f80,0x3edbbf75,0xbf2c3f55,0x3f5cbf22,0x3f04bf6d,0xbf3e3f46,0x3f67bf0e,0xbf7d3e95,0xbf18bf35,0x3eac3f62,0xbd49bf7b,0xbe793f7f,
 0x3e793f6d,0x3d49bf7f,0xbeac3f7b,0x3f18bf62,0x3f7d0000,0xbf67be95,0x3f3e3f0e,0xbf04bf46,0xbf5cbec4,0x3f2c3f22,0xbedbbf55,0x3e163f75,0xbf4e3f35,0x3f71bef1,0xbf803e48,0x3f783dc9,
 0x3f5cbf35,0xbf803e95,0x3f673e48,0xbf18bf22,0x3e163f6d,0x3eacbf7f,0xbf3e3f55,0x3f78bef1,0xbe793f80,0x3f2cbf62,0xbf713f0e,0x3f7dbdc9,0xbf4ebec4,0x3edb3f46,0x3d49bf7b,0xbf043f75,
 0x3f043f35,0xbd49bf75,0xbedb3f7b,0x3f4ebf46,0xbf7d3ec4,0x3f713dc9,0xbf2cbf0e,0x3e793f62,0xbf780000,0x3f3e3ef1,0xbeacbf55,0xbe163f7f,0x3f18bf6d,0xbf673f22,0x3f80be48,0xbf5cbe95,
 0xbf3ebec4,0x3e163f62,0x3f04bf7b,0xbf713f22,0x3edb3f35,0x3e79bf7f,0xbf4e3f55,0x3f80be95,0xbd49bf6d,0xbf183f75,0x3f78bf0e,0xbf67bdc9,0xbeac3f80,0x3f5cbf46,0xbf7d3e48,0x3f2c3ef1,
 0xbf2c3f6d,0x3f7dbef1,0xbf5cbe48,0x3eac3f46,0x3f67bf35,0xbf783dc9,0x3f183f0e,0x3d49bf75,0xbf803ec4,0x3f4e3e95,0xbe79bf55,0xbedb3f7f,0x3f710000,0xbf04bf22,0xbe163f7b,0x3f3ebf62,
 0xbf670000,0x3e793f46,0x3f18bf7b,0xbf803ef1,0x3f2c3ec4,0x3e16bf75,0xbf5c3f55,0x3f71bdc9,0xbeacbf35,0xbf043f7f,0x3f7dbf0e,0xbf3ebe95,0xbd493f6d,0x3f4ebf62,0xbf783e48,0x3edb3f22,
 0xbedb3f80,0x3f78bf22,0xbf4ebe48,0x3d493f62,0x3f3ebf6d,0xbf7d3e95,0x3f043f0e,0x3eacbf7f,0xbf713f35,0x3f5c3dc9,0xbe16bf55,0xbf2c3f75,0x3f80bec4,0xbf18bef1,0xbe793f7b,0x3f67bf46,
 0x3e16bf6d,0xbf713f46,0x3f3e3e48,0x3e79bf75,0x3f5c0000,0x3d49bf62,0xbf673f55,0x3f4e3dc9,0x3f183ec4,0x3edbbf7f,0xbf803f0e,0x3f043ef1,0xbf783f35,0x3f2c3e95,0x3eacbf7b,0xbf7d3f22,
 0x3f7dbec4,0xbeacbf22,0xbf2c3f7b,0x3f78be95,0xbf043f80,0x3f80bef1,0xbedbbf0e,0xbf183f7f,0xbf4e3f6d,0x3f67bdc9,0xbd49bf55,0xbf5c3f62,0xbe79bf35,0xbf3e3f75,0x3f71be48,0xbe16bf46,
 0x3e163f35,0x3f67bf62,0xbf2cbe48,0xbf043f7f,0x3f78bec4,0xbd49bf46,0xbf713f55,0x3f183e95,0xbf4e0000,0xbeac3f75,0x3f80bf0e,0xbe79bf22,0xbf5c3f6d,0x3f3e3dc9,0x3edbbf7b,0xbf7d3ef1,
 0x3f7dbf35,0xbedbbef1,0xbf3e3f7b,0x3f5cbdc9,0x3e79bf6d,0xbf803f22,0x3eac3f0e,0x3f4ebf75,0xbf183f80,0x3f71be95,0x3d49bf55,0xbf783f46,0x3f043ec4,0x3f2cbf7f,0xbf673e48,0xbe163f62,
 0x3f67bf6d,0xbf04be95,0xbf4e3f7b,0x3f2c3dc9,0x3f80bf35,0xbe16bf22,0xbf783f55,0x3eac3ef1,0x3f71bec4,0x3e79bf62,0xbf7d3f0e,0xbd493f46,0x3f3e0000,0x3f18bf7f,0xbf5c3e48,0xbedb3f75,
 0x3edb3ec4,0x3f5cbf75,0xbf18be48,0xbf3e3f7f,0x3d493f35,0x3f7dbf46,0xbe79bf0e,0xbf713f62,0xbeac3f6d,0x3f78bef1,0x3e16bf55,0xbf803f22,0xbf2c3f80,0x3f4ebdc9,0x3f04bf7b,0xbf673e95,
 0xbf800000,0x3f7d3dc9,0xbf78be48,0x3f713e95,0xbf67bec4,0x3f5c3ef1,0xbf4ebf0e,0x3f3e3f22,0xbf2cbf35,0x3f183f46,0xbf04bf55,0x3edb3f62,0xbeacbf6d,0x3e793f75,0xbe16bf7b,0x3d493f7f,
 0x3d49bf80,0xbe163f7f,0x3e79bf7b,0xbeac3f75,0x3edbbf6d,0xbf043f62,0x3f18bf55,0xbf2c3f46,0x3f3ebf35,0xbf4e3f22,0x3f5cbf0e,0xbf673ef1,0x3f71bec4,0xbf783e95,0x3f7dbe48,0xbf803dc9,
 0xbe79bf6d,0xbd493f7f,0x3eacbf7b,0xbf183f62,0xbf7d0000,0x3f673e95,0xbf3ebf0e,0x3f043f46,0x3f5c3ec4,0xbf2cbf22,0x3edb3f55,0xbe16bf75,0x3f4ebf35,0xbf713ef1,0x3f80be48,0xbf78bdc9,
 0xbf783ec4,0x3f80bdc9,0xbf71be48,0x3f4e3ef1,0xbe163f80,0x3edbbf75,0xbf2c3f55,0x3f5cbf22,0x3f04bf6d,0xbf3e3f46,0x3f67bf0e,0xbf7d3e95,0xbf18bf35,0x3eac3f62,0xbd49bf7b,0xbe793f7f,
 0x3f043f35,0xbd49bf75,0xbedb3f7b,0x3f4ebf46,0xbf7d3ec4,0x3f713dc9,0xbf2cbf0e,0x3e793f62,0xbf780000,0x3f3e3ef1,0xbeacbf55,0xbe163f7f,0x3f18bf6d,0xbf673f22,0x3f80be48,0xbf5cbe95,
 0xbf5c3f35,0x3f80be95,0xbf67be48,0x3f183f22,0xbe16bf6d,0xbeac3f7f,0x3f3ebf55,0xbf783ef1,0x3e79bf80,0xbf2c3f62,0x3f71bf0e,0xbf7d3dc9,0x3f4e3ec4,0xbedbbf46,0xbd493f7b,0x3f04bf75,
 0x3f2cbf6d,0xbf7d3ef1,0x3f5c3e48,0xbeacbf46,0xbf673f35,0x3f78bdc9,0xbf18bf0e,0xbd493f75,0x3f80bec4,0xbf4ebe95,0x3e793f55,0x3edbbf7f,0xbf710000,0x3f043f22,0x3e16bf7b,0xbf3e3f62,
 0xbf3ebec4,0x3e163f62,0x3f04bf7b,0xbf713f22,0x3edb3f35,0x3e79bf7f,0xbf4e3f55,0x3f80be95,0xbd49bf6d,0xbf183f75,0x3f78bf0e,0xbf67bdc9,0xbeac3f80,0x3f5cbf46,0xbf7d3e48,0x3f2c3ef1,
 0x3edbbf80,0xbf783f22,0x3f4e3e48,0xbd49bf62,0xbf3e3f6d,0x3f7dbe95,0xbf04bf0e,0xbeac3f7f,0x3f71bf35,0xbf5cbdc9,0x3e163f55,0x3f2cbf75,0xbf803ec4,0x3f183ef1,0x3e79bf7b,0xbf673f46,
 0xbf670000,0x3e793f46,0x3f18bf7b,0xbf803ef1,0x3f2c3ec4,0x3e16bf75,0xbf5c3f55,0x3f71bdc9,0xbeacbf35,0xbf043f7f,0x3f7dbf0e,0xbf3ebe95,0xbd493f6d,0x3f4ebf62,0xbf783e48,0x3edb3f22,
 0x3f7dbec4,0xbeacbf22,0xbf2c3f7b,0x3f78be95,0xbf043f80,0x3f80bef1,0xbedbbf0e,0xbf183f7f,0xbf4e3f6d,0x3f67bdc9,0xbd49bf55,0xbf5c3f62,0xbe79bf35,0xbf3e3f75,0x3f71be48,0xbe16bf46,
 0xbe163f6d,0x3f71bf46,0xbf3ebe48,0xbe793f75,0xbf5c0000,0xbd493f62,0x3f67bf55,0xbf4ebdc9,0xbf18bec4,0xbedb3f7f,0x3f80bf0e,0xbf04bef1,0x3f78bf35,0xbf2cbe95,0xbeac3f7b,0x3f7dbf22,
 0xbf7d3f35,0x3edb3ef1,0x3f3ebf7b,0xbf5c3dc9,0xbe793f6d,0x3f80bf22,0xbeacbf0e,0xbf4e3f75,0x3f18bf80,0xbf713e95,0xbd493f55,0x3f78bf46,0xbf04bec4,0xbf2c3f7f,0x3f67be48,0x3e16bf62,
 0x3e163f35,0x3f67bf62,0xbf2cbe48,0xbf043f7f,0x3f78bec4,0xbd49bf46,0xbf713f55,0x3f183e95,0xbf4e0000,0xbeac3f75,0x3f80bf0e,0xbe79bf22,0xbf5c3f6d,0x3f3e3dc9,0x3edbbf7b,0xbf7d3ef1,
 0x3edb3ec4,0x3f5cbf75,0xbf18be48,0xbf3e3f7f,0x3d493f35,0x3f7dbf46,0xbe79bf0e,0xbf713f62,0xbeac3f6d,0x3f78bef1,0x3e16bf55,0xbf803f22,0xbf2c3f80,0x3f4ebdc9,0x3f04bf7b,0xbf673e95,
 0xbf673f6d,0x3f043e95,0x3f4ebf7b,0xbf2cbdc9,0xbf803f35,0x3e163f22,0x3f78bf55,0xbeacbef1,0xbf713ec4,0xbe793f62,0x3f7dbf0e,0x3d49bf46,0xbf3e0000,0xbf183f7f,0x3f5cbe48,0x3edbbf75,
 0xbf3e3f80,0x3f183dc9,0x3f5cbf7b,0xbedbbe95,0xbf713f6d,0x3e793ef1,0x3f7dbf55,0xbd49bf22,0xbf803f35,0xbe163f46,0x3f78bf0e,0x3eacbf62,0xbf673ec4,0xbf043f75,0x3f4ebe48,0x3f2cbf7f,
 0xbf2c0000,0xbf4e3f7f,0x3f043e48,0x3f67bf75,0xbeacbec4,0xbf783f62,0x3e163f0e,0x3f80bf46,0x3d49bf35,0xbf7d3f22,0xbe793f55,0x3f71bef1,0x3edbbf6d,0xbf5c3e95,0xbf183f7b,0x3f3ebdc9,
 0xbf5c3ec4,0xbf3e3f7f,0x3edb3e48,0x3f7dbf62,0xbf4e3f80,0x3eac3e95,0x3f80bf55,0x3e79bf46,0x3f78bf6d,0x3d49bf22,0xbf713f0e,0xbf183f75,0x3e16bf35,0xbf673ef1,0xbf2c3f7b,0x3f043dc9,
 0xbf043f6d,0x3f2cbdc9,0x3f67bf7b,0xbe16bef1,0x3f180000,0x3f71bf75,0xbd49bf0e,0xbf783f22,0xbe79bec4,0xbf803f46,0xbeac3f55,0x3f4ebe95,0xbf7d3f35,0xbedb3f62,0x3f3ebe48,0x3f5cbf7f,
 0x3f78bf35,0x3f2cbf75,0xbeacbe48,0xbf7d3f46,0xbf183f6d,0x3edb3dc9,0x3f80bf55,0x3f04bf62,0xbf5c3f80,0x3d493ef1,0x3f67bf0e,0x3f4ebf7f,0xbe16bec4,0xbf713f22,0xbf3e3f7b,0x3e793e95,
 0xbe793f35,0x3f3ebe95,0x3f71bf7b,0x3e16bf22,0xbf4e3ec4,0xbf673f7f,0xbd493f0e,0x3f5cbef1,0xbf040000,0xbf803f62,0xbedb3f55,0x3f18bdc9,0x3f7dbf6d,0x3eacbf46,0xbf2c3e48,0xbf783f75,
 0xbd49bec4,0xbf4e3ef1,0xbf783f7b,0xbedb3f46,0xbeac3f35,0x3f04bdc9,0x3f7dbf55,0x3f3ebf75,0x3f2cbf6d,0xbe16be95,0xbf5c3f0e,0xbf713f7f,0xbf673f80,0xbe793f22,0x3f18be48,0x3f80bf62,
 0xbf803f6d,0xbf183f62,0x3e793e48,0x3f67bf22,0x3f71bf35,0x3f5cbf7f,0x3e16bf0e,0xbf2c3e95,0xbf3e3ec4,0xbf7d3f75,0xbf043f55,0x3eac3dc9,0x3edb0000,0x3f78bf46,0x3f4ebf7b,0x3d49bef1,
 0xbeac0000,0xbf5c3f22,0xbf7d3f7b,0xbf2c3f62,0xbd493ec4,0x3f18be95,0x3f78bf55,0x3f67bf7f,0x3edbbf35,0xbe79bdc9,0xbf4e3f0e,0xbf803f75,0xbf3e3f6d,0xbe163ef1,0x3f04be48,0x3f71bf46,
 0xbf713f80,0xbf043f46,0x3e163e48,0x3f3ebef1,0x3f80bf6d,0x3f4ebf75,0x3e79bf0e,0xbedb3dc9,0xbf673f35,0xbf783f7f,0xbf183f55,0x3d493e95,0x3f2cbec4,0x3f7dbf62,0x3f5cbf7b,0x3eacbf22,
 0x3f4ebf6d,0x3edbbf22,0xbd49be48,0xbf043e95,0x3e790000,0x3f2cbef1,0x3f71bf55,0x3f7dbf7f,0xbe163ec4,0x3eacbdc9,0x3f3ebf0e,0x3f78bf62,0xbf5c3f35,0xbf803f75,0xbf673f7b,0xbf183f46,
 0x3f18bec4,0x3f67bf46,0x3f80bf7b,0x3f5cbf75,0xbf783f80,0xbf3e3f62,0xbeac3f0e,0x3e163dc9,0xbf7d3f6d,0xbf713f7f,0xbf2c3f55,0xbe793ef1,0x3f04bf35,0x3d49be95,0xbedb3e48,0xbf4e3f22,
 0xbf183f35,0xbeac3ef1,0xbd493e48,0x3e79bdc9,0x3f04bec4,0x3f3ebf22,0x3f67bf55,0x3f7dbf75,0xbe160000,0xbedb3e95,0xbf2c3f0e,0xbf5c3f46,0xbf783f6d,0xbf803f7f,0xbf713f7b,0xbf4e3f62,
 0x3f4ebf35,0x3f71bf62,0x3f80bf7b,0x3f78bf7f,0x3f5cbf6d,0x3f2cbf46,0x3edbbf0e,0x3e16be95,0xbf7d3f80,0xbf673f75,0xbf3e3f55,0xbf043f22,0xbe793ec4,0x3d493dc9,0x3eacbe48,0x3f18bef1,
 0x3f71bf6d,0x3f78bf75,0x3f7dbf7b,0x3f80bf7f,0x3f3ebf35,0x3f4ebf46,0x3f5cbf55,0x3f67bf62,0x3edbbec4,0x3f04bef1,0x3f18bf0e,0x3f2cbf22,0x3d490000,0x3e16bdc9,0x3e79be48,0x3eacbe95,
 0xbeac3ec4,0xbe793e95,0xbe163e48,0xbd493dc9,0xbf2c3f35,0xbf183f22,0xbf043f0e,0xbedb3ef1,0xbf673f6d,0xbf5c3f62,0xbf4e3f55,0xbf3e3f46,0xbf803f80,0xbf7d3f7f,0xbf783f7b,0xbf713f75,
 0xbf2c0000,0xbf4e3f7f,0x3f043e48,0x3f67bf75,0xbeacbec4,0xbf783f62,0x3e163f0e,0x3f80bf46,0x3d49bf35,0xbf7d3f22,0xbe793f55,0x3f71bef1,0x3edbbf6d,0xbf5c3e95,0xbf183f7b,0x3f3ebdc9,
 0x3f3ebf80,0xbf18bdc9,0xbf5c3f7b,0x3edb3e95,0x3f71bf6d,0xbe79bef1,0xbf7d3f55,0x3d493f22,0x3f80bf35,0x3e16bf46,0xbf783f0e,0xbeac3f62,0x3f67bec4,0x3f04bf75,0xbf4e3e48,0xbf2c3f7f,
 0x3f04bf6d,0xbf2c3dc9,0xbf673f7b,0x3e163ef1,0xbf180000,0xbf713f75,0x3d493f0e,0x3f78bf22,0x3e793ec4,0x3f80bf46,0x3eacbf55,0xbf4e3e95,0x3f7dbf35,0x3edbbf62,0xbf3e3e48,0xbf5c3f7f,
 0xbf5c3ec4,0xbf3e3f7f,0x3edb3e48,0x3f7dbf62,0xbf4e3f80,0x3eac3e95,0x3f80bf55,0x3e79bf46,0x3f78bf6d,0x3d49bf22,0xbf713f0e,0xbf183f75,0x3e16bf35,0xbf673ef1,0xbf2c3f7b,0x3f043dc9,
 0xbe793f35,0x3f3ebe95,0x3f71bf7b,0x3e16bf22,0xbf4e3ec4,0xbf673f7f,0xbd493f0e,0x3f5cbef1,0xbf040000,0xbf803f62,0xbedb3f55,0x3f18bdc9,0x3f7dbf6d,0x3eacbf46,0xbf2c3e48,0xbf783f75,
 0xbf783f35,0xbf2c3f75,0x3eac3e48,0x3f7dbf46,0x3f18bf6d,0xbedbbdc9,0xbf803f55,0xbf043f62,0x3f5cbf80,0xbd49bef1,0xbf673f0e,0xbf4e3f7f,0x3e163ec4,0x3f71bf22,0x3f3ebf7b,0xbe79be95,
 0x3f80bf6d,0x3f18bf62,0xbe79be48,0xbf673f22,0xbf713f35,0xbf5c3f7f,0xbe163f0e,0x3f2cbe95,0x3f3ebec4,0x3f7dbf75,0x3f04bf55,0xbeacbdc9,0xbedb0000,0xbf783f46,0xbf4e3f7b,0xbd493ef1,
 0xbd49bec4,0xbf4e3ef1,0xbf783f7b,0xbedb3f46,0xbeac3f35,0x3f04bdc9,0x3f7dbf55,0x3f3ebf75,0x3f2cbf6d,0xbe16be95,0xbf5c3f0e,0xbf713f7f,0xbf673f80,0xbe793f22,0x3f18be48,0x3f80bf62,
 0x3f71bf80,0x3f04bf46,0xbe16be48,0xbf3e3ef1,0xbf803f6d,0xbf4e3f75,0xbe793f0e,0x3edbbdc9,0x3f67bf35,0x3f78bf7f,0x3f18bf55,0xbd49be95,0xbf2c3ec4,0xbf7d3f62,0xbf5c3f7b,0xbeac3f22,
 0xbeac0000,0xbf5c3f22,0xbf7d3f7b,0xbf2c3f62,0xbd493ec4,0x3f18be95,0x3f78bf55,0x3f67bf7f,0x3edbbf35,0xbe79bdc9,0xbf4e3f0e,0xbf803f75,0xbf3e3f6d,0xbe163ef1,0x3f04be48,0x3f71bf46,
 0x3f18bec4,0x3f67bf46,0x3f80bf7b,0x3f5cbf75,0xbf783f80,0xbf3e3f62,0xbeac3f0e,0x3e163dc9,0xbf7d3f6d,0xbf713f7f,0xbf2c3f55,0xbe793ef1,0x3f04bf35,0x3d49be95,0xbedb3e48,0xbf4e3f22,
 0xbf4e3f6d,0xbedb3f22,0x3d493e48,0x3f04be95,0xbe790000,0xbf2c3ef1,0xbf713f55,0xbf7d3f7f,0x3e16bec4,0xbeac3dc9,0xbf3e3f0e,0xbf783f62,0x3f5cbf35,0x3f80bf75,0x3f67bf7b,0x3f18bf46,
 0xbf4e3f35,0xbf713f62,0xbf803f7b,0xbf783f7f,0xbf5c3f6d,0xbf2c3f46,0xbedb3f0e,0xbe163e95,0x3f7dbf80,0x3f67bf75,0x3f3ebf55,0x3f04bf22,0x3e79bec4,0xbd49bdc9,0xbeac3e48,0xbf183ef1,
 0xbf183f35,0xbeac3ef1,0xbd493e48,0x3e79bdc9,0x3f04bec4,0x3f3ebf22,0x3f67bf55,0x3f7dbf75,0xbe160000,0xbedb3e95,0xbf2c3f0e,0xbf5c3f46,0xbf783f6d,0xbf803f7f,0xbf713f7b,0xbf4e3f62,
 0xbeac3ec4,0xbe793e95,0xbe163e48,0xbd493dc9,0xbf2c3f35,0xbf183f22,0xbf043f0e,0xbedb3ef1,0xbf673f6d,0xbf5c3f62,0xbf4e3f55,0xbf3e3f46,0xbf803f80,0xbf7d3f7f,0xbf783f7b,0xbf713f75,
 0xbf713f6d,0xbf783f75,0xbf7d3f7b,0xbf803f7f,0xbf3e3f35,0xbf4e3f46,0xbf5c3f55,0xbf673f62,0xbedb3ec4,0xbf043ef1,0xbf183f0e,0xbf2c3f22,0xbd490000,0xbe163dc9,0xbe793e48,0xbeac3e95,
};
__device__ __align__(128) const uint32_t g_Gimg[1792] = {
 0x00003d00,0x00003d00,0x00003d00,0x00003d00,0x00003d00,0x00003d00,0x00003d00,0x00003d00,0x00003d00,0x00003d00,0x00003d00,0x00003d00,0x00003d00,0x00003d00,0x00003d00,0x00003d00,
 0x00003d00,0x00003d00,0x00003d00,0x00003d00,0x00003d00,0x00003d00,0x00003d00,0x00003d00,0x00003d00,0x00003d00,0x00003d00,0x00003d00,0x00003d00,0x00003d00,0x00003d00,0x00003d00,
 0xbc5b3ce7,0xbc843cdc,0xbc983cce,0xbcac3cbe,0xbac93d00,0xbb963cfd,0xbbf93cf8,0xbc2c3cf1,0xbcf13c2c,0xbcf83bf9,0xbcfd3b96,0xbd003ac9,0xbcbe3cac,0xbcce3c98,0xbcdc3c84,0xbce73c5b,
 0xbce7bc5b,0xbcdcbc84,0xbccebc98,0xbcbebcac,0xbd00bac9,0xbcfdbb96,0xbcf8bbf9,0xbcf1bc2c,0xbc2cbcf1,0xbbf9bcf8,0xbb96bcfd,0xbac9bd00,0xbcacbcbe,0xbc98bcce,0xbc84bcdc,0xbc5bbce7,
 0xbcffbb49,0xbcf5bc15,0xbce2bc71,0xbcc6bca2,0xbca2bcc6,0xbc71bce2,0xbc15bcf5,0xbb49bcff,0xbb493cff,0xbc153cf5,0xbc713ce2,0xbca23cc6,0xbcc63ca2,0xbce23c71,0xbcf53c15,0xbcff3b49,
 0x3cff3b49,0x3cf53c15,0x3ce23c71,0x3cc63ca2,0x3ca23cc6,0x3c713ce2,0x3c153cf5,0x3b493cff,0x3b49bcff,0x3c15bcf5,0x3c71bce2,0x3ca2bcc6,0x3cc6bca2,0x3ce2bc71,0x3cf5bc15,0x3cffbb49,
 0x3c84bcdc,0x3cbebcac,0x3ce7bc5b,0x3cfdbb96,0xbc98bcce,0xbc2cbcf1,0xbac9bd00,0x3bf9bcf8,0xbcf83bf9,0xbd00bac9,0xbcf1bc2c,0xbccebc98,0xbb963cfd,0xbc5b3ce7,0xbcac3cbe,0xbcdc3c84,
 0xbcdcbc84,0xbcacbcbe,0xbc5bbce7,0xbb96bcfd,0xbcce3c98,0xbcf13c2c,0xbd003ac9,0xbcf8bbf9,0x3bf93cf8,0xbac93d00,0xbc2c3cf1,0xbc983cce,0x3cfd3b96,0x3ce73c5b,0x3cbe3cac,0x3c843cdc,
 0xbbc83cfb,0xbc8e3cd5,0xbcd53c8e,0xbcfb3bc8,0xbcfbbbc8,0xbcd5bc8e,0xbc8ebcd5,0xbbc8bcfb,0x3bc8bcfb,0x3c8ebcd5,0x3cd5bc8e,0x3cfbbbc8,0x3cfb3bc8,0x3cd53c8e,0x3c8e3cd5,0x3bc83cfb,
 0xbbc83cfb,0xbc8e3cd5,0xbcd53c8e,0xbcfb3bc8,0xbcfbbbc8,0xbcd5bc8e,0xbc8ebcd5,0xbbc8bcfb,0x3bc8bcfb,0x3c8ebcd5,0x3cd5bc8e,0x3cfbbbc8,0x3cfb3bc8,0x3cd53c8e,0x3c8e3cd5,0x3bc83cfb,
 0x3c98bcce,0x3ce7bc5b,0x3d003ac9,0x3cdc3c84,0xbcf8bbf9,0xbcbebcac,0xbc2cbcf1,0x3b96bcfd,0xbcfd3b96,0xbcf1bc2c,0xbcacbcbe,0xbbf9bcf8,0x3c843cdc,0x3ac93d00,0xbc5b3ce7,0xbcce3c98,
 0xbccebc98,0xbc5bbce7,0x3ac9bd00,0x3c84bcdc,0xbbf93cf8,0xbcac3cbe,0xbcf13c2c,0xbcfdbb96,0x3b963cfd,0xbc2c3cf1,0xbcbe3cac,0xbcf83bf9,0x3cdcbc84,0x3d00bac9,0x3ce73c5b,0x3c983cce,
 0xbcf5bc15,0xbca2bcc6,0xbb49bcff,0x3c71bce2,0x3ce2bc71,0x3cff3b49,0x3cc63ca2,0x3c153cf5,0x3c15bcf5,0x3cc6bca2,0x3cffbb49,0x3ce23c71,0x3c713ce2,0xbb493cff,0xbca23cc6,0xbcf53c15,
 0x3cf53c15,0x3ca23cc6,0x3b493cff,0xbc713ce2,0xbce23c71,0xbcffbb49,0xbcc6bca2,0xbc15bcf5,0xbc153cf5,0xbcc63ca2,0xbcff3b49,0xbce2bc71,0xbc71bce2,0x3b49bcff,0x3ca2bcc6,0x3cf5bc15,
 0xbcac3cbe,0xbcfd3b96,0xbcdcbc84,0xbc2cbcf1,0x3ce7bc5b,0x3cf83bf9,0x3c983cce,0xbac93d00,0xbd003ac9,0xbccebc98,0xbbf9bcf8,0x3c5bbce7,0x3cf13c2c,0x3c843cdc,0xbb963cfd,0xbcbe3cac,
 0xbcbebcac,0xbb96bcfd,0x3c84bcdc,0x3cf1bc2c,0x3c5b3ce7,0xbbf93cf8,0xbcce3c98,0xbd00bac9,0xbac9bd00,0x3c98bcce,0x3cf8bbf9,0x3ce73c5b,0xbc2c3cf1,0xbcdc3c84,0xbcfdbb96,0xbcacbcbe,
 0xbc443ced,0xbced3c44,0xbcedbc44,0xbc44bced,0x3c44bced,0x3cedbc44,0x3ced3c44,0x3c443ced,0xbc443ced,0xbced3c44,0xbcedbc44,0xbc44bced,0x3c44bced,0x3cedbc44,0x3ced3c44,0x3c443ced,
 0xbc443ced,0xbced3c44,0xbcedbc44,0xbc44bced,0x3c44bced,0x3cedbc44,0x3ced3c44,0x3c443ced,0xbc443ced,0xbced3c44,0xbcedbc44,0xbc44bced,0x3c44bced,0x3cedbc44,0x3ced3c44,0x3c443ced,
 0x3cbebcac,0x3cfd3b96,0x3c843cdc,0xbc2c3cf1,0xbc5b3ce7,0xbcf83bf9,0xbccebc98,0xbac9bd00,0x3d003ac9,0x3c983cce,0xbbf93cf8,0xbce73c5b,0xbcf13c2c,0xbcdcbc84,0xbb96bcfd,0x3cacbcbe,
 0x3cac3cbe,0xbb963cfd,0xbcdc3c84,0xbcf1bc2c,0xbce7bc5b,0xbbf9bcf8,0x3c98bcce,0x3d00bac9,0xbac93d00,0xbcce3c98,0xbcf8bbf9,0xbc5bbce7,0xbc2cbcf1,0x3c84bcdc,0x3cfdbb96,0x3cbe3cac,
 0xbce2bc71,0xbb49bcff,0x3cc6bca2,0x3cf53c15,0x3c153cf5,0xbca23cc6,0xbcffbb49,0xbc71bce2,0xbc713ce2,0xbcff3b49,0xbca2bcc6,0x3c15bcf5,0x3cf5bc15,0x3cc63ca2,0xbb493cff,0xbce23c71,
 0x3ce23c71,0x3b493cff,0xbcc63ca2,0xbcf5bc15,0xbc15bcf5,0x3ca2bcc6,0x3cff3b49,0x3c713ce2,0x3c71bce2,0x3cffbb49,0x3ca23cc6,0xbc153cf5,0xbcf53c15,0xbcc6bca2,0x3b49bcff,0x3ce2bc71,
 0xbcce3c98,0xbce7bc5b,0xbac9bd00,0x3cdcbc84,0xbbf9bcf8,0x3cbebcac,0x3cf13c2c,0x3b963cfd,0x3cfd3b96,0x3c2c3cf1,0xbcac3cbe,0xbcf8bbf9,0xbc843cdc,0xbd00bac9,0xbc5bbce7,0x3c98bcce,
 0x3c983cce,0xbc5b3ce7,0xbd003ac9,0xbc84bcdc,0xbcf83bf9,0xbcacbcbe,0x3c2cbcf1,0x3cfdbb96,0x3b96bcfd,0x3cf1bc2c,0x3cbe3cac,0xbbf93cf8,0x3cdc3c84,0xbac93d00,0xbce73c5b,0xbccebc98,
 0xbc8e3cd5,0xbcfbbbc8,0xbbc8bcfb,0x3cd5bc8e,0x3cd53c8e,0xbbc83cfb,0xbcfb3bc8,0xbc8ebcd5,0x3c8ebcd5,0x3cfb3bc8,0x3bc83cfb,0xbcd53c8e,0xbcd5bc8e,0x3bc8bcfb,0x3cfbbbc8,0x3c8e3cd5,
 0xbc8e3cd5,0xbcfbbbc8,0xbbc8bcfb,0x3cd5bc8e,0x3cd53c8e,0xbbc83cfb,0xbcfb3bc8,0xbc8ebcd5,0x3c8ebcd5,0x3cfb3bc8,0x3bc83cfb,0xbcd53c8e,0xbcd5bc8e,0x3bc8bcfb,0x3cfbbbc8,0x3c8e3cd5,
 0xbcdc3c84,0xbcbebcac,0x3c5bbce7,0x3cfd3b96,0xbccebc98,0x3c2cbcf1,0x3d003ac9,0x3bf93cf8,0x3cf83bf9,0x3ac93d00,0xbcf13c2c,0xbc98bcce,0x3b963cfd,0xbce73c5b,0xbcacbcbe,0x3c84bcdc,
 0x3c843cdc,0xbcac3cbe,0xbce7bc5b,0x3b96bcfd,0xbc983cce,0xbcf1bc2c,0x3ac9bd00,0x3cf8bbf9,0x3bf9bcf8,0x3d00bac9,0x3c2c3cf1,0xbcce3c98,0x3cfdbb96,0x3c5b3ce7,0xbcbe3cac,0xbcdcbc84,
 0xbcc6bca2,0x3c71bce2,0x3cf53c15,0xbb493cff,0xbcff3b49,0xbc15bcf5,0x3ce2bc71,0x3ca23cc6,0x3ca2bcc6,0x3ce23c71,0xbc153cf5,0xbcffbb49,0xbb49bcff,0x3cf5bc15,0x3c713ce2,0xbcc63ca2,
 0x3cc63ca2,0xbc713ce2,0xbcf5bc15,0x3b49bcff,0x3cffbb49,0x3c153cf5,0xbce23c71,0xbca2bcc6,0xbca23cc6,0xbce2bc71,0x3c15bcf5,0x3cff3b49,0x3b493cff,0xbcf53c15,0xbc71bce2,0x3cc6bca2,
 0x3ce7bc5b,0x3c843cdc,0xbcce3c98,0xbcacbcbe,0x3d00bac9,0x3b963cfd,0xbcf83bf9,0xbc2cbcf1,0x3cf13c2c,0xbbf93cf8,0xbcfdbb96,0x3ac9bd00,0x3cbe3cac,0xbc983cce,0xbcdcbc84,0x3c5bbce7,
 0x3c5b3ce7,0xbcdc3c84,0xbc98bcce,0x3cbebcac,0x3ac93d00,0xbcfd3b96,0xbbf9bcf8,0x3cf1bc2c,0xbc2c3cf1,0xbcf8bbf9,0x3b96bcfd,0x3d003ac9,0xbcac3cbe,0xbccebc98,0x3c84bcdc,0x3ce73c5b,
 0xbcb53cb5,0xbcb5bcb5,0x3cb5bcb5,0x3cb53cb5,0xbcb53cb5,0xbcb5bcb5,0x3cb5bcb5,0x3cb53cb5,0xbcb53cb5,0xbcb5bcb5,0x3cb5bcb5,0x3cb53cb5,0xbcb53cb5,0xbcb5bcb5,0x3cb5bcb5,0x3cb53cb5,
 0xbcb53cb5,0xbcb5bcb5,0x3cb5bcb5,0x3cb53cb5,0xbcb53cb5,0xbcb5bcb5,0x3cb5bcb5,0x3cb53cb5,0xbcb53cb5,0xbcb5bcb5,0x3cb5bcb5,0x3cb53cb5,0xbcb53cb5,0xbcb5bcb5,0x3cb5bcb5,0x3cb53cb5,
 0xbcf13c2c,0xbbf9bcf8,0x3cfdbb96,0x3ac93d00,0xbcbe3cac,0xbc98bcce,0x3cdcbc84,0x3c5b3ce7,0xbce7bc5b,0x3c84bcdc,0x3cce3c98,0xbcac3cbe,0xbd00bac9,0x3b96bcfd,0x3cf83bf9,0xbc2c3cf1,
 0xbc2cbcf1,0x3cf8bbf9,0x3b963cfd,0xbd003ac9,0xbcacbcbe,0x3ccebc98,0x3c843cdc,0xbce73c5b,0x3c5bbce7,0x3cdc3c84,0xbc983cce,0xbcbebcac,0x3ac9bd00,0x3cfd3b96,0xbbf93cf8,0xbcf1bc2c,
 0xbca2bcc6,0x3ce2bc71,0x3c153cf5,0xbcff3b49,0x3b49bcff,0x3cf53c15,0xbc713ce2,0xbcc6bca2,0xbcc63ca2,0xbc71bce2,0x3cf5bc15,0x3b493cff,0xbcffbb49,0x3c15bcf5,0x3ce23c71,0xbca23cc6,
 0x3ca23cc6,0xbce23c71,0xbc15bcf5,0x3cffbb49,0xbb493cff,0xbcf5bc15,0x3c71bce2,0x3cc63ca2,0x3cc6bca2,0x3c713ce2,0xbcf53c15,0xbb49bcff,0x3cff3b49,0xbc153cf5,0xbce2bc71,0x3ca2bcc6,
 0x3cf8bbf9,0xbac93d00,0xbcf1bc2c,0x3c98bcce,0x3b96bcfd,0x3ce73c5b,0xbcac3cbe,0xbc84bcdc,0xbcdcbc84,0x3cbebcac,0x3c5b3ce7,0xbcfd3b96,0xbcce3c98,0xbc2cbcf1,0x3d00bac9,0xbbf93cf8,
 0xbbf9bcf8,0x3d003ac9,0xbc2c3cf1,0xbccebc98,0xbcfdbb96,0x3c5bbce7,0x3cbe3cac,0xbcdc3c84,0xbc843cdc,0xbcacbcbe,0x3ce7bc5b,0x3b963cfd,0x3c983cce,0xbcf13c2c,0xbac9bd00,0x3cf83bf9,
 0xbcd53c8e,0xbbc8bcfb,0x3cfb3bc8,0xbc8e3cd5,0xbc8ebcd5,0x3cfbbbc8,0xbbc83cfb,0xbcd5bc8e,0x3cd5bc8e,0x3bc83cfb,0xbcfbbbc8,0x3c8ebcd5,0x3c8e3cd5,0xbcfb3bc8,0x3bc8bcfb,0x3cd53c8e,
 0xbcd53c8e,0xbbc8bcfb,0x3cfb3bc8,0xbc8e3cd5,0xbc8ebcd5,0x3cfbbbc8,0xbbc83cfb,0xbcd5bc8e,0x3cd5bc8e,0x3bc83cfb,0xbcfbbbc8,0x3c8ebcd5,0x3c8e3cd5,0xbcfb3bc8,0x3bc8bcfb,0x3cd53c8e,
 0x3cfdbb96,0xbc2c3cf1,0xbcacbcbe,0x3cf8bbf9,0xbc84bcdc,0x3d00bac9,0xbc5b3ce7,0xbc98bcce,0xbccebc98,0x3ce7bc5b,0xbac93d00,0xbcdcbc84,0xbbf93cf8,0xbcbebcac,0x3cf1bc2c,0xbb963cfd,
 0xbb96bcfd,0x3cf13c2c,0xbcbe3cac,0xbbf9bcf8,0xbcdc3c84,0xbac9bd00,0x3ce73c5b,0xbcce3c98,0xbc983cce,0xbc5bbce7,0x3d003ac9,0xbc843cdc,0x3cf83bf9,0xbcac3cbe,0xbc2cbcf1,0x3cfd3b96,
 0xbc71bce2,0x3cff3b49,0xbca23cc6,0xbc15bcf5,0x3cf53c15,0xbcc63ca2,0xbb49bcff,0x3ce23c71,0x3ce2bc71,0xbb493cff,0xbcc6bca2,0x3cf5bc15,0xbc153cf5,0xbca2bcc6,0x3cffbb49,0xbc713ce2,
 0x3c713ce2,0xbcffbb49,0x3ca2bcc6,0x3c153cf5,0xbcf5bc15,0x3cc6bca2,0x3b493cff,0xbce2bc71,0xbce23c71,0x3b49bcff,0x3cc63ca2,0xbcf53c15,0x3c15bcf5,0x3ca23cc6,0xbcff3b49,0x3c71bce2,
 0xbd003ac9,0x3c98bcce,0x3bf93cf8,0xbce7bc5b,0x3cf13c2c,0xbcdc3c84,0x3b96bcfd,0x3cac3cbe,0xbcbebcac,0x3cfdbb96,0xbc843cdc,0xbc2cbcf1,0x3c5b3ce7,0xbcf8bbf9,0x3ccebc98,0xbac93d00,
 0xbac9bd00,0x3cce3c98,0xbcf83bf9,0x3c5bbce7,0xbc2c3cf1,0xbc84bcdc,0x3cfd3b96,0xbcbe3cac,0x3cacbcbe,0x3b963cfd,0xbcdcbc84,0x3cf1bc2c,0xbce73c5b,0x3bf9bcf8,0x3c983cce,0xbd00bac9,
 0xbced3c44,0x3c44bced,0x3c443ced,0xbcedbc44,0x3cedbc44,0xbc443ced,0xbc44bced,0x3ced3c44,0xbced3c44,0x3c44bced,0x3c443ced,0xbcedbc44,0x3cedbc44,0xbc443ced,0xbc44bced,0x3ced3c44,
 0xbced3c44,0x3c44bced,0x3c443ced,0xbcedbc44,0x3cedbc44,0xbc443ced,0xbc44bced,0x3ced3c44,0xbced3c44,0x3c44bced,0x3c443ced,0xbcedbc44,0x3cedbc44,0xbc443ced,0xbc44bced,0x3ced3c44,
 0x3d003ac9,0xbcce3c98,0x3bf9bcf8,0x3c5b3ce7,0xbcf13c2c,0x3c84bcdc,0x3b963cfd,0xbcbebcac,0x3cac3cbe,0xbcfdbb96,0x3cdcbc84,0xbc2c3cf1,0xbce7bc5b,0x3cf8bbf9,0xbc983cce,0xbac9bd00,
 0xbac93d00,0xbc98bcce,0x3cf83bf9,0xbce73c5b,0xbc2cbcf1,0x3cdc3c84,0xbcfd3b96,0x3cacbcbe,0xbcbe3cac,0x3b96bcfd,0x3c843cdc,0xbcf1bc2c,0x3c5bbce7,0x3bf93cf8,0xbccebc98,0x3d00bac9,
 0xbc15bcf5,0x3cc63ca2,0xbcffbb49,0x3ce2bc71,0xbc713ce2,0xbb49bcff,0x3ca23cc6,0xbcf5bc15,0xbcf53c15,0x3ca2bcc6,0xbb493cff,0xbc71bce2,0x3ce23c71,0xbcff3b49,0x3cc6bca2,0xbc153cf5,
 0x3c153cf5,0xbcc6bca2,0x3cff3b49,0xbce23c71,0x3c71bce2,0x3b493cff,0xbca2bcc6,0x3cf53c15,0x3cf5bc15,0xbca23cc6,0x3b49bcff,0x3c713ce2,0xbce2bc71,0x3cffbb49,0xbcc63ca2,0x3c15bcf5,
 0xbcfdbb96,0x3cf1bc2c,0xbcac3cbe,0x3bf9bcf8,0x3c84bcdc,0xbac93d00,0xbc5bbce7,0x3cce3c98,0x3c983cce,0xbce7bc5b,0x3d00bac9,0xbcdc3c84,0xbcf83bf9,0x3cbebcac,0xbc2c3cf1,0xbb96bcfd,
 0xbb963cfd,0xbc2cbcf1,0x3cbe3cac,0xbcf8bbf9,0xbcdcbc84,0x3d003ac9,0xbce73c5b,0x3c98bcce,0x3ccebc98,0xbc5b3ce7,0xbac9bd00,0x3c843cdc,0x3bf93cf8,0xbcacbcbe,0x3cf13c2c,0xbcfd3b96,
 0xbcfb3bc8,0x3cd5bc8e,0xbc8e3cd5,0x3bc8bcfb,0x3bc83cfb,0xbc8ebcd5,0x3cd53c8e,0xbcfbbbc8,0x3cfbbbc8,0xbcd53c8e,0x3c8ebcd5,0xbbc83cfb,0xbbc8bcfb,0x3c8e3cd5,0xbcd5bc8e,0x3cfb3bc8,
 0xbcfb3bc8,0x3cd5bc8e,0xbc8e3cd5,0x3bc8bcfb,0x3bc83cfb,0xbc8ebcd5,0x3cd53c8e,0xbcfbbbc8,0x3cfbbbc8,0xbcd53c8e,0x3c8ebcd5,0xbbc83cfb,0xbbc8bcfb,0x3c8e3cd5,0xbcd5bc8e,0x3cfb3bc8,
 0xbcf8bbf9,0x3d00bac9,0xbcf13c2c,0x3ccebc98,0xbb96bcfd,0x3c5b3ce7,0xbcacbcbe,0x3cdc3c84,0x3c843cdc,0xbcbebcac,0x3ce73c5b,0xbcfdbb96,0xbc983cce,0x3c2cbcf1,0xbac93d00,0xbbf9bcf8,
 0xbbf93cf8,0xbac9bd00,0x3c2c3cf1,0xbc98bcce,0xbcfd3b96,0x3ce7bc5b,0xbcbe3cac,0x3c84bcdc,0x3cdcbc84,0xbcac3cbe,0x3c5bbce7,0xbb963cfd,0x3cce3c98,0xbcf1bc2c,0x3d003ac9,0xbcf83bf9,
 0xbb49bcff,0x3c153cf5,0xbc71bce2,0x3ca23cc6,0xbcc6bca2,0x3ce23c71,0xbcf5bc15,0x3cff3b49,0x3cffbb49,0xbcf53c15,0x3ce2bc71,0xbcc63ca2,0x3ca2bcc6,0xbc713ce2,0x3c15bcf5,0xbb493cff,
 0x3b493cff,0xbc15bcf5,0x3c713ce2,0xbca2bcc6,0x3cc63ca2,0xbce2bc71,0x3cf53c15,0xbcffbb49,0xbcff3b49,0x3cf5bc15,0xbce23c71,0x3cc6bca2,0xbca23cc6,0x3c71bce2,0xbc153cf5,0x3b49bcff,
 0x3cf13c2c,0xbcf8bbf9,0x3cfd3b96,0xbd00bac9,0x3cbe3cac,0xbccebc98,0x3cdc3c84,0xbce7bc5b,0x3c5b3ce7,0xbc84bcdc,0x3c983cce,0xbcacbcbe,0x3ac93d00,0xbb96bcfd,0x3bf93cf8,0xbc2cbcf1,
 0xbc2c3cf1,0x3bf9bcf8,0xbb963cfd,0x3ac9bd00,0xbcac3cbe,0x3c98bcce,0xbc843cdc,0x3c5bbce7,0xbce73c5b,0x3cdcbc84,0xbcce3c98,0x3cbebcac,0xbd003ac9,0x3cfdbb96,0xbcf83bf9,0x3cf1bc2c,
 0xbd000000,0x3d000000,0xbd000000,0x3d000000,0xbd000000,0x3d000000,0xbd000000,0x3d000000,0xbd000000,0x3d000000,0xbd000000,0x3d000000,0xbd000000,0x3d000000,0xbd000000,0x3d000000,
 0xbd000000,0x3d000000,0xbd000000,0x3d000000,0xbd000000,0x3d000000,0xbd000000,0x3d000000,0xbd000000,0x3d000000,0xbd000000,0x3d000000,0xbd000000,0x3d000000,0xbd000000,0x3d000000,
 0xbce7bc5b,0x3cdc3c84,0xbccebc98,0x3cbe3cac,0xbd00bac9,0x3cfd3b96,0xbcf8bbf9,0x3cf13c2c,0xbc2cbcf1,0x3bf93cf8,0xbb96bcfd,0x3ac93d00,0xbcacbcbe,0x3c983cce,0xbc84bcdc,0x3c5b3ce7,
 0x3c5bbce7,0xbc843cdc,0x3c98bcce,0xbcac3cbe,0x3ac9bd00,0xbb963cfd,0x3bf9bcf8,0xbc2c3cf1,0x3cf1bc2c,0xbcf83bf9,0x3cfdbb96,0xbd003ac9,0x3cbebcac,0xbcce3c98,0x3cdcbc84,0xbce73c5b,
 0x3b49bcff,0xbc153cf5,0x3c71bce2,0xbca23cc6,0x3cc6bca2,0xbce23c71,0x3cf5bc15,0xbcff3b49,0xbcffbb49,0x3cf53c15,0xbce2bc71,0x3cc63ca2,0xbca2bcc6,0x3c713ce2,0xbc15bcf5,0x3b493cff,
 0xbb493cff,0x3c15bcf5,0xbc713ce2,0x3ca2bcc6,0xbcc63ca2,0x3ce2bc71,0xbcf53c15,0x3cffbb49,0x3cff3b49,0xbcf5bc15,0x3ce23c71,0xbcc6bca2,0x3ca23cc6,0xbc71bce2,0x3c153cf5,0xbb49bcff,
 0x3cdc3c84,0xbcacbcbe,0x3c5b3ce7,0xbb96bcfd,0x3ccebc98,0xbcf13c2c,0x3d00bac9,0xbcf8bbf9,0xbbf9bcf8,0xbac93d00,0x3c2cbcf1,0xbc983cce,0xbcfdbb96,0x3ce73c5b,0xbcbebcac,0x3c843cdc,
 0x3c84bcdc,0xbcbe3cac,0x3ce7bc5b,0xbcfd3b96,0xbc98bcce,0x3c2c3cf1,0xbac9bd00,0xbbf93cf8,0xbcf83bf9,0x3d003ac9,0xbcf1bc2c,0x3cce3c98,0xbb963cfd,0x3c5bbce7,0xbcac3cbe,0x3cdcbc84,
 0xbcfbbbc8,0x3cd53c8e,0xbc8ebcd5,0x3bc83cfb,0x3bc8bcfb,0xbc8e3cd5,0x3cd5bc8e,0xbcfb3bc8,0x3cfb3bc8,0xbcd5bc8e,0x3c8e3cd5,0xbbc8bcfb,0xbbc83cfb,0x3c8ebcd5,0xbcd53c8e,0x3cfbbbc8,
 0xbcfbbbc8,0x3cd53c8e,0xbc8ebcd5,0x3bc83cfb,0x3bc8bcfb,0xbc8e3cd5,0x3cd5bc8e,0xbcfb3bc8,0x3cfb3bc8,0xbcd5bc8e,0x3c8e3cd5,0xbbc8bcfb,0xbbc83cfb,0x3c8ebcd5,0xbcd53c8e,0x3cfbbbc8,
 0x3cce3c98,0xbc5bbce7,0xbac93d00,0x3c84bcdc,0x3bf9bcf8,0xbcac3cbe,0x3cf1bc2c,0xbcfdbb96,0xbb96bcfd,0xbc2c3cf1,0x3cbebcac,0xbcf83bf9,0xbcdc3c84,0x3d00bac9,0xbce7bc5b,0x3c983cce,
 0x3c98bcce,0xbce73c5b,0x3d003ac9,0xbcdcbc84,0xbcf8bbf9,0x3cbe3cac,0xbc2cbcf1,0xbb963cfd,0xbcfd3b96,0x3cf13c2c,0xbcacbcbe,0x3bf93cf8,0x3c843cdc,0xbac9bd00,0xbc5b3ce7,0x3ccebc98,
 0x3c15bcf5,0xbcc63ca2,0x3cffbb49,0xbce2bc71,0x3c713ce2,0x3b49bcff,0xbca23cc6,0x3cf5bc15,0x3cf53c15,0xbca2bcc6,0x3b493cff,0x3c71bce2,0xbce23c71,0x3cff3b49,0xbcc6bca2,0x3c153cf5,
 0xbc153cf5,0x3cc6bca2,0xbcff3b49,0x3ce23c71,0xbc71bce2,0xbb493cff,0x3ca2bcc6,0xbcf53c15,0xbcf5bc15,0x3ca23cc6,0xbb49bcff,0xbc713ce2,0x3ce2bc71,0xbcffbb49,0x3cc63ca2,0xbc15bcf5,
 0xbcbebcac,0x3b963cfd,0x3c84bcdc,0xbcf13c2c,0x3c5b3ce7,0x3bf9bcf8,0xbcce3c98,0x3d003ac9,0xbac9bd00,0xbc983cce,0x3cf8bbf9,0xbce7bc5b,0xbc2c3cf1,0x3cdcbc84,0xbcfdbb96,0x3cac3cbe,
 0x3cacbcbe,0xbcfd3b96,0x3cdc3c84,0xbc2cbcf1,0xbce73c5b,0x3cf83bf9,0xbc98bcce,0xbac93d00,0x3d00bac9,0xbccebc98,0x3bf93cf8,0x3c5bbce7,0xbcf1bc2c,0x3c843cdc,0x3b96bcfd,0xbcbe3cac,
 0xbcedbc44,0x3c443ced,0x3c44bced,0xbced3c44,0x3ced3c44,0xbc44bced,0xbc443ced,0x3cedbc44,0xbcedbc44,0x3c443ced,0x3c44bced,0xbced3c44,0x3ced3c44,0xbc44bced,0xbc443ced,0x3cedbc44,
 0xbcedbc44,0x3c443ced,0x3c44bced,0xbced3c44,0x3ced3c44,0xbc44bced,0xbc443ced,0x3cedbc44,0xbcedbc44,0x3c443ced,0x3c44bced,0xbced3c44,0x3ced3c44,0xbc44bced,0xbc443ced,0x3cedbc44,
 0x3cac3cbe,0x3b96bcfd,0xbcdc3c84,0x3cf13c2c,0xbce7bc5b,0x3bf93cf8,0x3c98bcce,0xbd003ac9,0xbac93d00,0x3ccebc98,0xbcf8bbf9,0x3c5b3ce7,0xbc2cbcf1,0xbc843cdc,0x3cfdbb96,0xbcbebcac,
 0xbcbe3cac,0x3cfd3b96,0xbc84bcdc,0xbc2c3cf1,0x3c5bbce7,0xbcf83bf9,0x3cce3c98,0xbac9bd00,0xbd00bac9,0x3c983cce,0x3bf9bcf8,0xbce73c5b,0x3cf1bc2c,0xbcdcbc84,0x3b963cfd,0x3cacbcbe,
 0x3c71bce2,0xbcff3b49,0x3ca23cc6,0x3c15bcf5,0xbcf53c15,0x3cc63ca2,0x3b49bcff,0xbce23c71,0xbce2bc71,0x3b493cff,0x3cc6bca2,0xbcf5bc15,0x3c153cf5,0x3ca2bcc6,0xbcffbb49,0x3c713ce2,
 0xbc713ce2,0x3cffbb49,0xbca2bcc6,0xbc153cf5,0x3cf5bc15,0xbcc6bca2,0xbb493cff,0x3ce2bc71,0x3ce23c71,0xbb49bcff,0xbcc63ca2,0x3cf53c15,0xbc15bcf5,0xbca23cc6,0x3cff3b49,0xbc71bce2,
 0xbc98bcce,0xbc5b3ce7,0x3d00bac9,0xbc84bcdc,0x3cf8bbf9,0xbcacbcbe,0xbc2c3cf1,0x3cfdbb96,0xbb963cfd,0x3cf1bc2c,0xbcbebcac,0xbbf93cf8,0xbcdcbc84,0xbac93d00,0x3ce7bc5b,0xbccebc98,
 0xbcce3c98,0x3ce73c5b,0xbac9bd00,0xbcdc3c84,0xbbf9bcf8,0xbcbe3cac,0x3cf13c2c,0xbb96bcfd,0x3cfd3b96,0xbc2cbcf1,0xbcac3cbe,0x3cf83bf9,0xbc843cdc,0x3d003ac9,0xbc5bbce7,0xbc983cce,
 0xbcd5bc8e,0xbbc83cfb,0x3cfbbbc8,0xbc8ebcd5,0xbc8e3cd5,0x3cfb3bc8,0xbbc8bcfb,0xbcd53c8e,0x3cd53c8e,0x3bc8bcfb,0xbcfb3bc8,0x3c8e3cd5,0x3c8ebcd5,0xbcfbbbc8,0x3bc83cfb,0x3cd5bc8e,
 0xbcd5bc8e,0xbbc83cfb,0x3cfbbbc8,0xbc8ebcd5,0xbc8e3cd5,0x3cfb3bc8,0xbbc8bcfb,0xbcd53c8e,0x3cd53c8e,0x3bc8bcfb,0xbcfb3bc8,0x3c8e3cd5,0x3c8ebcd5,0xbcfbbbc8,0x3bc83cfb,0x3cd5bc8e,
 0xbc84bcdc,0xbcac3cbe,0x3ce73c5b,0x3b96bcfd,0x3c98bcce,0xbcf1bc2c,0xbac93d00,0x3cf8bbf9,0xbbf93cf8,0x3d00bac9,0xbc2cbcf1,0xbcce3c98,0xbcfd3b96,0x3c5b3ce7,0x3cbebcac,0xbcdcbc84,
 0xbcdc3c84,0x3cbe3cac,0x3c5bbce7,0xbcfdbb96,0xbccebc98,0xbc2c3cf1,0x3d003ac9,0xbbf9bcf8,0x3cf83bf9,0xbac9bd00,0xbcf13c2c,0x3c983cce,0x3b963cfd,0x3ce7bc5b,0xbcacbcbe,0xbc843cdc,
 0x3ca2bcc6,0xbce2bc71,0xbc153cf5,0x3cff3b49,0xbb49bcff,0xbcf53c15,0x3c713ce2,0x3cc6bca2,0x3cc63ca2,0x3c71bce2,0xbcf5bc15,0xbb493cff,0x3cffbb49,0xbc15bcf5,0xbce23c71,0x3ca23cc6,
 0xbca23cc6,0x3ce23c71,0x3c15bcf5,0xbcffbb49,0x3b493cff,0x3cf5bc15,0xbc71bce2,0xbcc63ca2,0xbcc6bca2,0xbc713ce2,0x3cf53c15,0x3b49bcff,0xbcff3b49,0x3c153cf5,0x3ce2bc71,0xbca2bcc6,
 0x3c5b3ce7,0x3cdcbc84,0xbc98bcce,0xbcbe3cac,0x3ac93d00,0x3cfdbb96,0xbbf9bcf8,0xbcf13c2c,0xbc2c3cf1,0x3cf83bf9,0x3b96bcfd,0xbd00bac9,0xbcac3cbe,0x3cce3c98,0x3c84bcdc,0xbce7bc5b,
 0xbce73c5b,0x3c843cdc,0x3ccebc98,0xbcacbcbe,0xbd003ac9,0x3b963cfd,0x3cf8bbf9,0xbc2cbcf1,0xbcf1bc2c,0xbbf93cf8,0x3cfd3b96,0x3ac9bd00,0xbcbebcac,0xbc983cce,0x3cdc3c84,0x3c5bbce7,
 0xbcb5bcb5,0xbcb53cb5,0x3cb53cb5,0x3cb5bcb5,0xbcb5bcb5,0xbcb53cb5,0x3cb53cb5,0x3cb5bcb5,0xbcb5bcb5,0xbcb53cb5,0x3cb53cb5,0x3cb5bcb5,0xbcb5bcb5,0xbcb53cb5,0x3cb53cb5,0x3cb5bcb5,
 0xbcb5bcb5,0xbcb53cb5,0x3cb53cb5,0x3cb5bcb5,0xbcb5bcb5,0xbcb53cb5,0x3cb53cb5,0x3cb5bcb5,0xbcb5bcb5,0xbcb53cb5,0x3cb53cb5,0x3cb5bcb5,0xbcb5bcb5,0xbcb53cb5,0x3cb53cb5,0x3cb5bcb5,
 0xbc2cbcf1,0xbcf83bf9,0x3b963cfd,0x3d00bac9,0xbcacbcbe,0xbcce3c98,0x3c843cdc,0x3ce7bc5b,0x3c5bbce7,0xbcdcbc84,0xbc983cce,0x3cbe3cac,0x3ac9bd00,0xbcfdbb96,0xbbf93cf8,0x3cf13c2c,
 0x3cf1bc2c,0xbbf9bcf8,0xbcfd3b96,0x3ac93d00,0x3cbebcac,0xbc98bcce,0xbcdc3c84,0x3c5b3ce7,0x3ce73c5b,0x3c84bcdc,0xbccebc98,0xbcac3cbe,0x3d003ac9,0x3b96bcfd,0xbcf8bbf9,0xbc2c3cf1,
 0x00000000,0x00000000,0x00000000,0x00000000,0x00000000,0x00000000,0x00000000,0x00000000,0x00000000,0x00000000,0x00000000,0x00000000,0x00000000,0x00000000,0x00000000,0x00000000,
 0x00000000,0x00000000,0x00000000,0x00000000,0x00000000,0x00000000,0x00000000,0x00000000,0x00000000,0x00000000,0x00000000,0x00000000,0x00000000,0x00000000,0x00000000,0x00000000,
 0x00000000,0x00000000,0x00000000,0x00000000,0x00000000,0x00000000,0x00000000,0x00000000,0x00000000,0x00000000,0x00000000,0x00000000,0x00000000,0x00000000,0x00000000,0x00000000,
 0x00000000,0x00000000,0x00000000,0x00000000,0x00000000,0x00000000,0x00000000,0x00000000,0x00000000,0x00000000,0x00000000,0x00000000,0x00000000,0x00000000,0x00000000,0x00000000,
 0x00000000,0x00000000,0x00000000,0x00000000,0x00000000,0x00000000,0x00000000,0x00000000,0x00000000,0x00000000,0x00000000,0x00000000,0x00000000,0x00000000,0x00000000,0x00000000,
 0x00000000,0x00000000,0x00000000,0x00000000,0x00000000,0x00000000,0x00000000,0x00000000,0x00000000,0x00000000,0x00000000,0x00000000,0x00000000,0x00000000,0x00000000,0x00000000,
 0x00000000,0x00000000,0x00000000,0x00000000,0x00000000,0x00000000,0x00000000,0x00000000,0x00000000,0x00000000,0x00000000,0x00000000,0x00000000,0x00000000,0x00000000,0x00000000,
 0x00000000,0x00000000,0x00000000,0x00000000,0x00000000,0x00000000,0x00000000,0x00000000,0x00000000,0x00000000,0x00000000,0x00000000,0x00000000,0x00000000,0x00000000,0x00000000,
 0x00000000,0x00000000,0x00000000,0x00000000,0x00000000,0x00000000,0x00000000,0x00000000,0x00000000,0x00000000,0x00000000,0x00000000,0x00000000,0x00000000,0x00000000,0x00000000,
 0x00000000,0x00000000,0x00000000,0x00000000,0x00000000,0x00000000,0x00000000,0x00000000,0x00000000,0x00000000,0x00000000,0x00000000,0x00000000,0x00000000,0x00000000,0x00000000,
 0x00000000,0x00000000,0x00000000,0x00000000,0x00000000,0x00000000,0x00000000,0x00000000,0x00000000,0x00000000,0x00000000,0x00000000,0x00000000,0x00000000,0x00000000,0x00000000,
 0x00000000,0x00000000,0x00000000,0x00000000,0x00000000,0x00000000,0x00000000,0x00000000,0x00000000,0x00000000,0x00000000,0x00000000,0x00000000,0x00000000,0x00000000,0x00000000,
};

template<int SA>
__device__ __forceinline__ void wgmma_main(float (&d)[80], uint64_t da, uint64_t db, int sd) {
  asm volatile("{\n.reg .pred p;\nsetp.ne.b32 p, %82, 0;\n"
    "wgmma.mma_async.sync.aligned.m64n160k16.f32.bf16.bf16 "
    "{%0, %1, %2, %3, %4, %5, %6, %7, %8, %9, %10, %11, %12, %13, %14, %15, %16, %17, %18, %19, %20, %21, %22, %23, %24, %25, %26, %27, %28, %29, %30, %31, %32, %33, %34, %35, %36, %37, %38, %39, %40, %41, %42, %43, %44, %45, %46, %47, %48, %49, %50, %51, %52, %53, %54, %55, %56, %57, %58, %59, %60, %61, %62, %63, %64, %65, %66, %67, %68, %69, %70, %71, %72, %73, %74, %75, %76, %77, %78, %79}, %80, %81, p, %83, 1, 1, 0;\n}\n"
    : "+f"(d[0]), "+f"(d[1]), "+f"(d[2]), "+f"(d[3]), "+f"(d[4]), "+f"(d[5]), "+f"(d[6]), "+f"(d[7]), "+f"(d[8]), "+f"(d[9]), "+f"(d[10]), "+f"(d[11]), "+f"(d[12]), "+f"(d[13]), "+f"(d[14]), "+f"(d[15]), "+f"(d[16]), "+f"(d[17]), "+f"(d[18]), "+f"(d[19]), "+f"(d[20]), "+f"(d[21]), "+f"(d[22]), "+f"(d[23]), "+f"(d[24]), "+f"(d[25]), "+f"(d[26]), "+f"(d[27]), "+f"(d[28]), "+f"(d[29]), "+f"(d[30]), "+f"(d[31]), "+f"(d[32]), "+f"(d[33]), "+f"(d[34]), "+f"(d[35]), "+f"(d[36]), "+f"(d[37]), "+f"(d[38]), "+f"(d[39]), "+f"(d[40]), "+f"(d[41]), "+f"(d[42]), "+f"(d[43]), "+f"(d[44]), "+f"(d[45]), "+f"(d[46]), "+f"(d[47]), "+f"(d[48]), "+f"(d[49]), "+f"(d[50]), "+f"(d[51]), "+f"(d[52]), "+f"(d[53]), "+f"(d[54]), "+f"(d[55]), "+f"(d[56]), "+f"(d[57]), "+f"(d[58]), "+f"(d[59]), "+f"(d[60]), "+f"(d[61]), "+f"(d[62]), "+f"(d[63]), "+f"(d[64]), "+f"(d[65]), "+f"(d[66]), "+f"(d[67]), "+f"(d[68]), "+f"(d[69]), "+f"(d[70]), "+f"(d[71]), "+f"(d[72]), "+f"(d[73]), "+f"(d[74]), "+f"(d[75]), "+f"(d[76]), "+f"(d[77]), "+f"(d[78]), "+f"(d[79])
    : "l"(da), "l"(db), "r"(sd), "n"(SA));
}
template<int SA>
__device__ __forceinline__ void wgmma_fwd(float (&d)[32], uint64_t da, uint64_t db, int sd) {
  asm volatile("{\n.reg .pred p;\nsetp.ne.b32 p, %34, 0;\n"
    "wgmma.mma_async.sync.aligned.m64n64k16.f32.bf16.bf16 "
    "{%0, %1, %2, %3, %4, %5, %6, %7, %8, %9, %10, %11, %12, %13, %14, %15, %16, %17, %18, %19, %20, %21, %22, %23, %24, %25, %26, %27, %28, %29, %30, %31}, %32, %33, p, %35, 1, 0, 1;\n}\n"
    : "+f"(d[0]), "+f"(d[1]), "+f"(d[2]), "+f"(d[3]), "+f"(d[4]), "+f"(d[5]), "+f"(d[6]), "+f"(d[7]), "+f"(d[8]), "+f"(d[9]), "+f"(d[10]), "+f"(d[11]), "+f"(d[12]), "+f"(d[13]), "+f"(d[14]), "+f"(d[15]), "+f"(d[16]), "+f"(d[17]), "+f"(d[18]), "+f"(d[19]), "+f"(d[20]), "+f"(d[21]), "+f"(d[22]), "+f"(d[23]), "+f"(d[24]), "+f"(d[25]), "+f"(d[26]), "+f"(d[27]), "+f"(d[28]), "+f"(d[29]), "+f"(d[30]), "+f"(d[31])
    : "l"(da), "l"(db), "r"(sd), "n"(SA));
}
template<int SA>
__device__ __forceinline__ void wgmma_inv(float (&d)[28], uint64_t da, uint64_t db, int sd) {
  asm volatile("{\n.reg .pred p;\nsetp.ne.b32 p, %30, 0;\n"
    "wgmma.mma_async.sync.aligned.m64n56k16.f32.bf16.bf16 "
    "{%0, %1, %2, %3, %4, %5, %6, %7, %8, %9, %10, %11, %12, %13, %14, %15, %16, %17, %18, %19, %20, %21, %22, %23, %24, %25, %26, %27}, %28, %29, p, %31, 1, 1, 0;\n}\n"
    : "+f"(d[0]), "+f"(d[1]), "+f"(d[2]), "+f"(d[3]), "+f"(d[4]), "+f"(d[5]), "+f"(d[6]), "+f"(d[7]), "+f"(d[8]), "+f"(d[9]), "+f"(d[10]), "+f"(d[11]), "+f"(d[12]), "+f"(d[13]), "+f"(d[14]), "+f"(d[15]), "+f"(d[16]), "+f"(d[17]), "+f"(d[18]), "+f"(d[19]), "+f"(d[20]), "+f"(d[21]), "+f"(d[22]), "+f"(d[23]), "+f"(d[24]), "+f"(d[25]), "+f"(d[26]), "+f"(d[27])
    : "l"(da), "l"(db), "r"(sd), "n"(SA));
}

__device__ __forceinline__ uint32_t s2u(const void* p) { return (uint32_t)__cvta_generic_to_shared(p); }
__device__ __forceinline__ void mbar_init(uint32_t a, int c) { asm volatile("mbarrier.init.shared::cta.b64 [%0], %1;" ::"r"(a), "r"(c)); }
__device__ __forceinline__ void mbar_expect(uint32_t a, int b) { asm volatile("mbarrier.arrive.expect_tx.shared::cta.b64 _, [%0], %1;" ::"r"(a), "r"(b) : "memory"); }
__device__ __forceinline__ void mbar_arrive(uint32_t a) { asm volatile("mbarrier.arrive.shared::cta.b64 _, [%0];" ::"r"(a) : "memory"); }
__device__ __forceinline__ void mbar_arrive_cluster(uint32_t a, uint32_t cta, uint32_t cnt) {
  asm volatile("{\n.reg .b32 r;\nmapa.shared::cluster.u32 r, %0, %1;\nmbarrier.arrive.shared::cluster.b64 _, [r], %2;\n}" ::"r"(a), "r"(cta), "r"(cnt) : "memory");
}
__device__ __forceinline__ void mbar_wait(uint32_t a, int ph) {
  asm volatile("{\n.reg .pred p;\n.reg .u32 c;\nmov.u32 c, 0;\nWAIT:\n"
               "mbarrier.try_wait.parity.shared::cta.b64 p, [%0], %1;\n@p bra DONE;\n"
               "add.u32 c, c, 1;\nsetp.lt.u32 p, c, 0x400000;\n@p bra WAIT;\ntrap;\nDONE:\n}" ::"r"(a), "r"(ph) : "memory");
}
__device__ __forceinline__ void flag_wait(const unsigned* p, unsigned target) {
  asm volatile("{\n.reg .pred p;\n.reg .u32 c, v;\nmov.u32 c, 0;\nWAIT:\n"
               "ld.acquire.gpu.global.u32 v, [%0];\nsetp.ge.u32 p, v, %1;\n@p bra DONE;\n"
               "add.u32 c, c, 1;\nsetp.lt.u32 p, c, 0x400000;\n@p bra WAIT;\ntrap;\nDONE:\n}" ::"l"(p), "r"(target) : "memory");
}
__device__ __forceinline__ bool elect_one() {
  uint32_t p;
  asm volatile("{\n.reg .pred P;\nelect.sync _|P, 0xffffffff;\nselp.u32 %0, 1, 0, P;\n}" : "=r"(p));
  return p != 0;
}
__device__ __forceinline__ void bulk_ld(uint32_t dst, const void* src, int bytes, uint32_t bar) {
  asm volatile("cp.async.bulk.shared::cluster.global.mbarrier::complete_tx::bytes [%0], [%1], %2, [%3];" ::"r"(dst), "l"(src), "r"(bytes), "r"(bar) : "memory");
}
__device__ __forceinline__ void bulk_ld_mc_h(uint32_t dst, const void* src, int bytes, uint32_t bar, uint16_t mask, uint64_t pol) {
  asm volatile("cp.async.bulk.shared::cluster.global.mbarrier::complete_tx::bytes.multicast::cluster.L2::cache_hint [%0], [%1], %2, [%3], %4, %5;" ::"r"(dst), "l"(src), "r"(bytes), "r"(bar), "h"(mask), "l"(pol) : "memory");
}
__device__ __forceinline__ void tma_ld2(uint32_t dst, const CUtensorMap* tm, int c0, int c1, uint32_t bar) {
  asm volatile("cp.async.bulk.tensor.2d.shared::cluster.global.mbarrier::complete_tx::bytes [%0], [%1, {%3,%4}], [%2];" ::"r"(dst), "l"(tm), "r"(bar), "r"(c0), "r"(c1) : "memory");
}
__device__ __forceinline__ void tma_ld3(uint32_t dst, const CUtensorMap* tm, int c0, int c1, int c2, uint32_t bar) {
  asm volatile("cp.async.bulk.tensor.3d.shared::cluster.global.mbarrier::complete_tx::bytes [%0], [%1, {%3,%4,%5}], [%2];" ::"r"(dst), "l"(tm), "r"(bar), "r"(c0), "r"(c1), "r"(c2) : "memory");
}
__device__ __forceinline__ void tma_ld3h(uint32_t dst, const CUtensorMap* tm, int c0, int c1, int c2, uint32_t bar, uint64_t pol) {
  asm volatile("cp.async.bulk.tensor.3d.shared::cluster.global.mbarrier::complete_tx::bytes.L2::cache_hint [%0], [%1, {%3,%4,%5}], [%2], %6;" ::"r"(dst), "l"(tm), "r"(bar), "r"(c0), "r"(c1), "r"(c2), "l"(pol) : "memory");
}
__device__ __forceinline__ uint64_t policy_evict_first() {
  uint64_t p;
  asm("createpolicy.fractional.L2::evict_first.b64 %0, 1.0;" : "=l"(p));
  return p;
}
__device__ __forceinline__ void tma_st3(const CUtensorMap* tm, uint32_t src, int c0, int c1, int c2) {
  asm volatile("cp.async.bulk.tensor.3d.global.shared::cta.bulk_group [%0, {%2,%3,%4}], [%1];" ::"l"(tm), "r"(src), "r"(c0), "r"(c1), "r"(c2) : "memory");
}
__device__ __forceinline__ void tma_st4(const CUtensorMap* tm, uint32_t src, int c0, int c1, int c2, int c3) {
  asm volatile("cp.async.bulk.tensor.4d.global.shared::cta.bulk_group [%0, {%2,%3,%4,%5}], [%1];" ::"l"(tm), "r"(src), "r"(c0), "r"(c1), "r"(c2), "r"(c3) : "memory");
}
__device__ __forceinline__ void tma_st5(const CUtensorMap* tm, uint32_t src, int c0) {
  asm volatile("cp.async.bulk.tensor.5d.global.shared::cta.bulk_group [%0, {%2,%3,%3,%3,%3}], [%1];" ::"l"(tm), "r"(src), "r"(c0), "r"(0) : "memory");
}
__device__ __forceinline__ void bulk_commit() { asm volatile("cp.async.bulk.commit_group;" ::: "memory"); }
template <int N> __device__ __forceinline__ void bulk_wait_read() { asm volatile("cp.async.bulk.wait_group.read %0;" ::"n"(N) : "memory"); }
template <int N> __device__ __forceinline__ void bulk_wait() { asm volatile("cp.async.bulk.wait_group %0;" ::"n"(N) : "memory"); }
__device__ __forceinline__ void fence_async_smem() { asm volatile("fence.proxy.async.shared::cta;" ::: "memory"); }
__device__ __forceinline__ void wg_fence() { asm volatile("wgmma.fence.sync.aligned;" ::: "memory"); }
__device__ __forceinline__ void wg_commit() { asm volatile("wgmma.commit_group.sync.aligned;" ::: "memory"); }
template <int N> __device__ __forceinline__ void wg_wait() { asm volatile("wgmma.wait_group.sync.aligned %0;" ::"n"(N) : "memory"); }
template <int R> __device__ __forceinline__ void fence_regs(float (&d)[R]) {
#pragma unroll
  for (int i = 0; i < R; i++) asm volatile("" : "+f"(d[i])::"memory");
}
__device__ __forceinline__ uint64_t mk_desc(uint32_t addr) {
  return (uint64_t)((addr & 0x3FFFF) >> 4) | (1ull << 16) | (64ull << 32) | (1ull << 62);
}
__device__ __forceinline__ uint32_t pack2(float lo, float hi) {
  uint32_t r;
  asm("cvt.rn.bf16x2.f32 %0, %1, %2;" : "=r"(r) : "f"(hi), "f"(lo));
  return r;
}
__device__ __forceinline__ void stsm4(uint32_t ad, uint32_t a, uint32_t b, uint32_t c, uint32_t d) {
  asm volatile("stmatrix.sync.aligned.m8n8.x4.shared.b16 [%0], {%1,%2,%3,%4};" ::"r"(ad), "r"(a), "r"(b), "r"(c), "r"(d) : "memory");
}
__device__ __forceinline__ void stsm4t(uint32_t ad, uint32_t a, uint32_t b, uint32_t c, uint32_t d) {
  asm volatile("stmatrix.sync.aligned.m8n8.x4.trans.shared.b16 [%0], {%1,%2,%3,%4};" ::"r"(ad), "r"(a), "r"(b), "r"(c), "r"(d) : "memory");
}

__device__ __forceinline__ void stsm2t(uint32_t ad, uint32_t a, uint32_t b) {
  asm volatile("stmatrix.sync.aligned.m8n8.x2.trans.shared.b16 [%0], {%1,%2};" ::"r"(ad), "r"(a), "r"(b) : "memory");
}
__device__ __forceinline__ void red_add(unsigned* p) { asm volatile("red.relaxed.gpu.global.add.u32 [%0], 1;" ::"l"(p) : "memory"); }
__device__ __forceinline__ void fence_release() { asm volatile("fence.release.gpu;" ::: "memory"); }
__device__ __forceinline__ void fence_async_global() { asm volatile("fence.proxy.async.global;" ::: "memory"); }
__device__ __forceinline__ void tma_pf3(const CUtensorMap* tm, int c0, int c1, int c2) {
  asm volatile("cp.async.bulk.prefetch.tensor.3d.L2.global [%0, {%1,%2,%3}];" ::"l"(tm), "r"(c0), "r"(c1), "r"(c2) : "memory");
}
__device__ __forceinline__ uint64_t policy_evict_unchanged() {
  uint64_t p;
  asm("createpolicy.fractional.L2::evict_unchanged.b64 %0, 1.0;" : "=l"(p));
  return p;
}
__device__ __forceinline__ void tma_ld4(uint32_t dst, const CUtensorMap* tm, int c1, uint32_t bar) {
  asm volatile("cp.async.bulk.tensor.4d.shared::cluster.global.mbarrier::complete_tx::bytes [%0], [%1, {%4,%3,%4,%4}], [%2];" ::"r"(dst), "l"(tm), "r"(bar), "r"(c1), "r"(0) : "memory");
}

__device__ __forceinline__ unsigned flag_peek(const unsigned* p) {
  unsigned v;
  asm volatile("ld.acquire.gpu.global.u32 %0, [%1];" : "=r"(v) : "l"(p) : "memory");
  return v;
}
__device__ __forceinline__ int lane_id() {
  int l;
  asm volatile("mov.u32 %0, %%laneid;" : "=r"(l));
  return l;
}
__device__ __forceinline__ void poll64x4(const unsigned long long* p, unsigned long long (&v)[4]) {
  asm volatile("{\n.reg .pred p;\n.reg .u32 c;\n.reg .b64 t, u;\nmov.u32 c, 0;\nWAIT:\n"
               "ld.relaxed.gpu.global.u64 %0, [%4];\nld.relaxed.gpu.global.u64 %1, [%4+512];\n"
               "ld.relaxed.gpu.global.u64 %2, [%4+1024];\nld.relaxed.gpu.global.u64 %3, [%4+1536];\n"
               "or.b64 t, %0, %1;\nor.b64 u, %2, %3;\nor.b64 t, t, u;\nsetp.ge.s64 p, t, 0;\n@p bra DONE;\n"
               "add.u32 c, c, 1;\nsetp.lt.u32 p, c, 0x400000;\n@p bra WAIT;\ntrap;\nDONE:\n}"
               : "=l"(v[0]), "=l"(v[1]), "=l"(v[2]), "=l"(v[3]) : "l"(p) : "memory");
}

constexpr int G_STAGE = WBLK + XBLK;
constexpr int OFF_XR = 4 * G_STAGE;
constexpr int OFF_WS = OFF_XR + 6 * 8192;
constexpr int OFF_F = OFF_WS + 2 * 8192;
constexpr int OFF_WRAW = OFF_F + 8192;
constexpr int OFF_BAR = OFF_WRAW + 8192;
constexpr int OFF_GB = OFF_BAR + 1024;
constexpr int SMEM_BYTES = OFF_GB + 512;
constexpr int OFF_H0B = 10 * 8192;
constexpr int OFF_E = OFF_WRAW + 3072;
constexpr int B_RAWX = 0, B_F = 48, B_ROLE = 56, B_H0 = 80, B_H1 = 96, B_YFREE = 120, B_H0C = 136,
              B_EMPTY = 144,
              B_STGX = 192, B_STGW = 240, B_Y = 256, B_OUT = 272, B_YP = 352,
              B_FULL = 432, B_RAWW = 464, B_DONE = 496, S_ROLE = 576, S_PROBE = 592;

struct Maps { CUtensorMap x, we, wo, xst[2], wst, yld[2], out, xe[2], w30; };

__device__ __forceinline__ int chunk_of(int n) { return n < 16 ? n : 31 - n; }
__device__ __forceinline__ bool has_x2(int id, int n, int g) { return (((id >> 5) ^ n) & 1) == 0 && ((n >> 1) & 1) == g; }
__device__ __forceinline__ int w_row(int id) { return (id & 62) | (id >> 6); }
__device__ __forceinline__ uint32_t x_base(int s, int idx, uint32_t pgmask, int& par) {
  const int page = idx >> 3, o = idx & 7;
  par = (s ^ (pgmask >> page) ^ __popc(o)) & 1;
  return (page << 21) | ((o & 3) << 16) | ((o >> 2) << 19);
}
__device__ __forceinline__ uint32_t spread5(int i) { return (((i >> 1) & 3) << 14) | (((i >> 3) & 1) << 18) | ((i >> 4) << 20) | ((i & 1) << 13); }
__device__ __forceinline__ int y_idx(int half, int dq, int piece) { return (PG_Y + 5 * half) * 8 + (dq * 5 + piece) * 2; }
__device__ __forceinline__ int tail_win(int tr) { return (tr & 1) + 4 * (tr >> 1); }
__device__ __forceinline__ uint32_t read_info(uint32_t bar, int i) {
  uint32_t v;
  mbar_wait(bar + B_ROLE + 8 * i, 0);
  asm volatile("ld.shared.b32 %0, [%1];" : "=r"(v) : "r"(bar + S_ROLE + 4 * i) : "memory");
  return v;
}
__device__ __forceinline__ void send_info(uint32_t bar, int i, uint32_t v) {
#pragma unroll
  for (int r = 0; r < 2; r++)
    asm volatile("{\n.reg .b32 a, m;\nmapa.shared::cluster.u32 a, %0, %2;\nmapa.shared::cluster.u32 m, %1, %2;\n"
                 "st.async.weak.shared::cluster.mbarrier::complete_tx::bytes.b32 [a], %3, [m];\n}"
                 ::"r"(bar + S_ROLE + 4 * i), "r"(bar + B_ROLE + 8 * i), "r"(r), "r"(v) : "memory");
}
__device__ __forceinline__ unsigned probe(uint8_t* p, int lane) {
  if (lane < 2) *(uint4*)(p + lane * 16) = make_uint4(0, 0, 0, 0);
  __syncwarp();
  unsigned v, t0 = 0, t1 = 0;
  if (lane == 0) {
    asm volatile("mov.u32 %0, %%clock;" : "=r"(t0)::"memory");
    asm volatile("atom.relaxed.gpu.global.exch.b32 %0, [%1], 0;" : "=r"(v) : "l"(p) : "memory");
    asm volatile("{\n.reg .pred p;\nsetp.ne.u32 p, %1, 0xffffffff;\nmov.u32 %0, 0;\n@p mov.u32 %0, %%clock;\n}" : "=r"(t1) : "r"(v) : "memory");
  }
  return t1 - t0;
}

template <bool ISX>
__device__ __forceinline__ void t_issue(float (&t)[32], uint32_t sb, uint32_t raw) {
  const uint64_t da = mk_desc(sb + OFF_F), db = mk_desc(raw);
  wg_fence();
#pragma unroll
  for (int kk = 0; kk < (ISX ? 4 : 1); kk++) wgmma_fwd<1>(t, da + 2 * kk, db + 128 * kk, kk);
  wg_commit();
}
template <bool ISX>
__device__ __forceinline__ void t_finish(float (&t)[32], uint32_t dst, uint32_t sbar, int sw, int wg, int w, int lane) {
  fence_regs(t);
  if (ISX) asm volatile("bar.sync %0, 128;" ::"r"(1 + wg) : "memory");
  const int m = lane >> 3, r = lane & 7;
  uint32_t ad = dst + (8 * w + r) * 128;
  if (ISX) ad += ((((m & 1) * 4 + (m >> 1)) ^ sw ^ r) << 4);
  else ad += (m & 1) * 4096 + (((m >> 1) ^ sw ^ r) << 4);
#pragma unroll
  for (int i = 0; i < 4; i++) {
    const uint32_t a = ISX ? ((ad ^ ((i & 1) * 32)) + (i >> 1) * 4096) : (ad ^ (i * 32));
    stsm4(a, pack2(t[8 * i], t[8 * i + 1]), pack2(t[8 * i + 2], t[8 * i + 3]), pack2(t[8 * i + 4], t[8 * i + 5]), pack2(t[8 * i + 6], t[8 * i + 7]));
  }
  __syncwarp();
  if (lane == 0) mbar_arrive(sbar);
}
template <int NT, int K0, int K1>
__device__ __forceinline__ void batch(float (&yr)[80], float (&yi)[80], float (&t)[32], uint32_t st, int wg, int sd, uint32_t fa, uint32_t raw) {
  const uint64_t w0 = mk_desc(st + wg * 8192), x0 = mk_desc(st + WBLK);
  const uint64_t da = mk_desc(fa), db = mk_desc(raw);
  wg_fence();
  if (NT) {
#pragma unroll
    for (int kk = 0; kk < NT; kk++) wgmma_fwd<1>(t, da + 2 * kk, db + 128 * kk, kk);
    wg_commit();
  }
#pragma unroll
  for (int kk = K0; kk < K1; kk++) {
    const uint64_t wr = w0 + kk * 128, wi = wr + 256, xr = x0 + kk * 2, xi = xr + 4;
    wgmma_main<1>(yr, wr, xr, kk ? 1 : sd);
    wgmma_main<1>(yi, wr, xi, kk ? 1 : sd);
    wgmma_main<1>(yr, wi, xi, 1);
    wgmma_main<-1>(yi, wi, xr, 1);
  }
  wg_commit();
}

#define X_WAIT() PROF_W(wraw, mbar_wait(bar + B_RAWX + 8 * (wg * 3 + xs), xph))
#define X_ISSUE() t_issue<true>(t, sb, sb + OFF_XR + (wg * 3 + xs) * 8192)
#define X_FINISH(sw) do { t_finish<true>(t, sb + OFF_XR + (wg * 3 + xs) * 8192, bar + B_STGX + 8 * (wg * 3 + xs), sw, wg, w, lane); \
                          if (++xs == 3) { xs = 0; xph ^= 1; } } while (0)
#define W_WAIT(n) PROF_W(wraw, mbar_wait(bar + B_RAWW + 8 * (wg * 2 + ((n) & 1)), ((n) >> 1) & 1))
#define WRAW(n) (sb + OFF_WRAW + (wg * 2 + ((n) & 1)) * 2048)
#define W_FINISH() t_finish<false>(t, sb + OFF_WS + wg * 8192, bar + B_STGW + 8 * wg, w_row(id) & 7, wg, w, lane)

__device__ __forceinline__ void gelu_store(float (&hz)[28], uint32_t ad) {
#pragma unroll
  for (int i = 0; i < 28; i++) {
    const float in = hz[i] * fmaf(hz[i] * hz[i], 8.f * 0.044715f * 0.7978845608028654f, 2.f * 0.7978845608028654f);
    float th;
    asm("tanh.approx.f32 %0, %1;" : "=f"(th) : "f"(in));
    hz[i] = fmaf(hz[i], th, hz[i]);
  }
#pragma unroll
  for (int jj = 0; jj < 3; jj++) {
    const float* c = hz + 8 * jj;
    stsm4t(ad + jj * 2048, pack2(c[0], c[1]), pack2(c[2], c[3]), pack2(c[4], c[5]), pack2(c[6], c[7]));
  }
  stsm2t(ad + 3 * 2048, pack2(hz[24], hz[25]), pack2(hz[26], hz[27]));
}

#define ONE(...) do { if (elect_one()) { __VA_ARGS__; } } while (0)
template <int g>
__device__ __forceinline__ void manager(const Maps& tm, const unsigned* ctr, const uint32_t sb, const int id) {
  const uint32_t bar = sb + OFF_BAR, rank = id & 1;
  const uint64_t pol = policy_evict_first();
  const int cl = w_row(id), b = id >> 6, u = (id >> 1) & 31;
  const unsigned* pf = ctr + (C_LOADED + (((cl >> 5) - WR) >> 1)) * 32 + (((cl >> 5) - WR) & 1);
  int li = 0;
  auto refill = [&](int sl, bool wait) {
    const uint32_t fb = bar + B_RAWX + 8 * (g * 3 + sl);
    int row = ((li & 1) ? 128 + (id & 31) : 2 * (id & 63) + g) * MT, col = (li >> 1) * 64;
    asm volatile("" : "+r"(row), "+r"(col));
    ONE(if (li < 32) mbar_expect(fb, 8192);
        if (wait) bulk_wait_read<0>();
        if (li < 32) tma_ld3h(sb + OFF_XR + (g * 3 + sl) * 8192, &tm.x, col, row, b, fb, pol));
    li += (li & 1) || has_x2(id, li >> 1, g) ? 1 : 2;
  };
#pragma unroll 1
  for (int sl = 0; sl < 3; sl++) refill(sl, false);
  int xs = 0, xph = 0, yp = 0;
  int wrow = (cl >> 5) * (WSLOT / 128) + rank * 128 + g * 64 + (cl & 31);
  const uint32_t pgmask = __shfl_sync(0xffffffffu, read_info(bar, 1), 0);
  auto store_y = [&](int half, int piece, uint32_t buf, uint32_t wait_bar, int ph) {
    int par;
    int c = x_base(b, y_idx(half, rank * 2 + g, piece) + (u >> 4), pgmask, par);
    c = (c + (par << 12) + (u & 15) * 256) >> 1;
    const CUtensorMap* m = &tm.xst[par];
    asm volatile("" : "+r"(c), "+l"(m));
    if (wait_bar) mbar_wait(wait_bar, ph);
    ONE(fence_async_smem(); tma_st5(m, buf, c); tma_st5(m, buf + 4096, c + 64));
  };
  mbar_wait(bar + B_STGW + 8 * g, 0);
  ONE(fence_async_smem(); tma_st4(&tm.wst, sb + OFF_WS + g * 8192, 0, 0, 0, wrow); bulk_commit());
#pragma unroll 1
  for (int n = 0; n < 32; n++) {
    unsigned freed = 128;
    if (2 * n + (cl >> 5) >= WR) asm volatile("ld.relaxed.gpu.global.u32 %0, [%1];" : "=r"(freed) : "l"(pf + n * 32) : "memory");
    if (n < 16) {
#pragma unroll 1
      for (int j = 0; j < (has_x2(id, n, g) ? 2 : 1); j++) {
        const int t = j ? 128 + (id & 31) : 2 * (id & 63) + g;
        int par0, par1;
        const uint32_t off0 = x_base(b, n * 10 + (t >> 5), pgmask, par0), off1 = x_base(b, n * 10 + 5 + (t >> 5), pgmask, par1);
        uint32_t buf = sb + OFF_XR + (g * 3 + xs) * 8192;
        int c0 = (off0 + (par0 << 12) + (t & 31) * 128) >> 1, c1 = (off1 + (par1 << 12) + (t & 31) * 128) >> 1;
        const CUtensorMap *m0 = &tm.xst[par0], *m1 = &tm.xst[par1];
        asm volatile("" : "+r"(buf), "+r"(c0), "+r"(c1), "+l"(m0), "+l"(m1));
        mbar_wait(bar + B_STGX + 8 * (g * 3 + xs), xph);
        ONE(fence_async_smem(); tma_st5(m0, buf, c0); tma_st5(m1, buf + 4096, c1); bulk_commit());
        refill(xs, true);
        if (++xs == 3) { xs = 0; xph ^= 1; }
      }
    }
    if (n > 16 + LW && n <= YFLUSH) {
#pragma unroll 1
      do {
        store_y(0, yp, sb + OFF_XR + (g * 3 + (yp < 3 ? yp : yp - 3)) * 8192, (yp == 0 || yp == 3) ? bar + B_Y + 8 * g : 0, yp & 1);
      } while (++yp < 2);
      ONE(bulk_commit(); bulk_wait_read<0>(); if (yp == 2) mbar_arrive(bar + B_YFREE + 8 * g));
    }
    if (__shfl_sync(0xffffffffu, freed, 0) < 128) flag_wait(pf + n * 32, 128);
    const int cp = chunk_of(n + 2) * 64 + cl, sl = g * 2 + (n & 1);
    if (n) mbar_wait(bar + B_STGW + 8 * g, n & 1);
    ONE(if (n) {
          fence_async_smem();
          tma_st4(&tm.wst, sb + OFF_WS + g * 8192, 0, 0, 0, wrow);
          bulk_commit();
        }
        if (n < 30) {
          mbar_expect(bar + B_RAWW + 8 * sl, 2048);
          tma_ld3h(sb + OFF_WRAW + sl * 2048, &tm.we + (cp >> 9), 0, 0, (cp & 511) * 8 + ((n + 2) >> 4) * 4 + rank * 2 + g, bar + B_RAWW + 8 * sl, pol);
        }
        if (n < 4) {
          tma_pf3(&tm.we, 0, 0, ((n + 4) * 64 + cl) * 8 + rank * 2 + g);
          tma_pf3(&tm.wo, 0, 0, (n * 64 + cl) * 8 + rank * 2 + g);
          tma_pf3(&tm.wo, 0, 0, ((n + 4) * 64 + cl) * 8 + rank * 2 + g);
        }
        bulk_wait<0>();
        mbar_arrive(bar + B_DONE + 8 * (n & 7));
        mbar_arrive(bar + B_RAWW + 8 * (sl ^ 1)));
    wrow += 2 * WSLOT / 128;
    if (wrow >= WR * WSLOT / 128) wrow -= WR * WSLOT / 128;
  }
  ONE(asm volatile("prefetch.tensormap [%0];" ::"l"(g ? &tm.out : &tm.xst[b]) : "memory"));
  flag_wait(&ctr[(C_LOADED + 31) * 32 + 1], 128);
#pragma unroll 1
  for (int p = 0; p < 5; p++) {
    store_y(1, p, sb + (p * 2 + g) * 8192, bar + B_YP + 8 * (g * 5 + p), 0);
    if (p == YA - 1) ONE(bulk_commit());
  }
  if (YA < 5) ONE(bulk_commit(); bulk_wait<1>(); mbar_arrive(bar + B_DONE); bulk_wait<0>(); mbar_arrive(bar + B_DONE + 8));
  else ONE(bulk_wait<0>(); mbar_arrive(bar + B_DONE));
#pragma unroll 1
  for (int i = 0; i < 10; i++) {
    const int hf = i >= 5, k = i - 5 * hf;
    const uint32_t buf = sb + (hf ? 0 : k < 4 ? OFF_XR : OFF_H0B - 65536) + (2 * k + g) * 8192;
    mbar_wait(bar + B_OUT + 8 * (g * 5 + k), hf);
    ONE(fence_async_smem();
        tma_st3(&tm.out, buf, (hf * 4 + rank * 2 + (u & 1)) * 64, (32 * k + tail_win(u >> 1) + 2 * g) * MT, b);
        bulk_commit());
  }
  ONE(bulk_wait_read<0>(); if (g == 0) PROF_T(12));
}

__global__ void __cluster_dims__(2, 1, 1) __launch_bounds__(512, 1)
k1_main(uint8_t* xbuf, const void* __restrict__ fimg, const __nv_bfloat16* __restrict__ gamma,
        const __nv_bfloat16* __restrict__ beta, const __grid_constant__ Maps tm) {
  extern __shared__ __align__(1024) uint8_t smem_raw[];
  const uint32_t sb = s2u(smem_raw);
  const uint32_t bar = sb + OFF_BAR;
  const int warp = __shfl_sync(0xffffffffu, threadIdx.x >> 5, 0);
  const int bid = blockIdx.x;
  unsigned* ctr = (unsigned*)(xbuf + CTR_OFF);
  const uint32_t rank = bid & 1;
  if (bid == 0 && threadIdx.x < 4) asm volatile("st.relaxed.gpu.global.u64 [%0], %1;" ::"l"(&ctr[C_REG * 32 + 2 * threadIdx.x]), "l"(1ull << 63) : "memory");
  if (warp >= 12) {
    asm volatile("setmaxnreg.dec.sync.aligned.u32 24;");
    asm volatile("barrier.cluster.arrive.relaxed.aligned;" ::: "memory");
    {
      const int lane = lane_id(), k = bid >> 1;
      if (rank == 0 || k < XPAGES) {
        const uint32_t off = rank ? (k << 21) + 0xb0000 : (XPAGES << 21) + ((k >> 6) << 18) + (((k >> 4) & 3) << 14) + (k & 15) * 128;
        const unsigned lat = probe(xbuf + off + (warp & 1) * 4096 + (warp & 2) * 1024, lane);
        if (lane == 0) asm volatile("st.shared.b32 [%0], %1;" ::"r"(bar + S_PROBE + 4 * (warp & 3)), "r"(lat) : "memory");
      }
      asm volatile("bar.sync 4, 128;" ::: "memory");
      asm volatile("barrier.cluster.wait.aligned;" ::: "memory");
      if (warp == 14 && lane == 0) {
        uint32_t l0, l1, l2, l3;
        asm volatile("ld.shared.v4.b32 {%0, %1, %2, %3}, [%4];" : "=r"(l0), "=r"(l1), "=r"(l2), "=r"(l3) : "r"(bar + S_PROBE) : "memory");
        const int near = min(l1, l3) < min(l0, l2);
        if (rank) {
          send_info(bar, 2, near);
        } else {
          unsigned long long add = 1ull << (8 * near), v, *reg = (unsigned long long*)&ctr[C_REG * 32];
          if (k < XPAGES) add += (unsigned long long)(read_info(bar, 2) ^ near ^ 1) << (16 + k);
          PROF_T(14);
          asm volatile("{\n.reg .pred p;\n.reg .u32 c;\nmov.u32 c, 0;\nAGAIN:\n"
                       "atom.relaxed.gpu.global.add.u64 %0, [%1], %2;\nsetp.lt.s64 p, %0, 0;\n@p bra DONE;\n"
                       "add.u32 c, c, 1;\nsetp.lt.u32 p, c, 0x100000;\n@p bra AGAIN;\ntrap;\nDONE:\n}" : "=l"(v) : "l"(reg), "l"(add) : "memory");
          const int ticket = (v >> (8 * near)) & 255;
          if (ticket < 32) send_info(bar, 0, near * 32 + ticket);
          PROF_T(15); PROF_V(16, near);
          asm volatile("{\n.reg .pred p;\n.reg .u32 c, a, b;\nmov.u32 c, 0;\nWAIT:\n"
                       "ld.relaxed.gpu.global.u64 %0, [%1];\ncvt.u32.u64 a, %0;\nbfe.u32 b, a, 8, 8;\nand.b32 a, a, 255;\nadd.u32 a, a, b;\n"
                       "setp.ge.u32 p, a, 66;\n@p bra DONE;\n"
                       "add.u32 c, c, 1;\nsetp.lt.u32 p, c, 0x400000;\n@p bra WAIT;\ntrap;\nDONE:\n}" : "=l"(v) : "l"(reg) : "memory");
          if (ticket >= 32) {
            const int j = ticket - 32 + (int)((v >> (8 * (near ^ 1))) & 255);
            send_info(bar, 0, j < 32 ? (near ^ 1) * 32 + j : (near == 0 && ticket == 32 && j == 33) ? 64 : 32 + j);
          }
          send_info(bar, 1, (uint32_t)(v >> 16));
          PROF_T(13);
        }
      }
      __syncwarp();
      const int role = read_info(bar, 0);
      if (role < 64 && warp - 12 < NFL && elect_one()) {
#pragma unroll 1
        for (int n = warp - 12; n < 33 + (YA < 5); n += NFL) {
          mbar_wait(bar + B_DONE + 8 * (n & 7), (n >> 3) & 1);
          fence_release();
          if (n < 32) {
            red_add(&ctr[(C_FLAG + n + C_SIDE * ((role >> 5) ^ 1)) * 32]);
            red_add(&ctr[(C_FLAG + n + C_SIDE * (role >> 5)) * 32]);
          } else {
            red_add(&ctr[(C_Y + 2 * (n - 32) + rank + C_SIDE * (role >> 5)) * 32]);
          }
          if (n < 32) { PROF_T(64 + n); PROF_V(192 + n, tm0); } else { PROF_V(4, tm0); }
        }
      }
      if (role < 64 && warp == 15 && elect_one()) {
#pragma unroll 1
        for (int v = 0; v < 64; v++) {
          mbar_wait(bar + B_FULL + 8 * (v & 3), (v >> 2) & 1);
          mbar_arrive(bar + B_EMPTY + 8 * (v & 3));
          if (v < 64 - WR || v == 63) {
            red_add(&ctr[(C_LOADED + (v >> 1)) * 32 + (v & 1)]);
            red_add(&ctr[(C_LOADED + (v >> 1) + C_SIDE) * 32 + (v & 1)]);
          }
        }
      }
      __syncwarp();
    }
    asm volatile("barrier.cluster.arrive.relaxed.aligned;\nbarrier.cluster.wait.aligned;" ::: "memory");
    return;
  } else {
    if (elect_one()) {
      if (warp == 0) PROF_T(0);
      if (warp >= 6) asm volatile("prefetch.tensormap [%0];" ::"l"(&tm.x + (warp - 6)) : "memory");
      const int cnt = warp < 3 ? 1 : warp == 3 ? 5 : warp < 9 ? 4 : 2;
#pragma unroll
      for (int i = 0; i < 6; i++) mbar_init(bar + warp * 48 + 8 * i, cnt);
      if (warp == 1) {
        mbar_expect(bar + B_F, 8192);
        bulk_ld(sb + OFF_F, fimg, 8192, bar + B_F);
        mbar_expect(bar + B_ROLE, 4);
        mbar_expect(bar + B_ROLE + 8, 4);
        mbar_expect(bar + B_ROLE + 16, 4);
      }
      asm volatile("fence.mbarrier_init.release.cluster;" ::: "memory");
    }
    asm volatile("bar.sync 0, 384;" ::: "memory");
    asm volatile("barrier.cluster.arrive.relaxed.aligned;" ::: "memory");
    if (threadIdx.x == 64) PROF_T(20);
    if (bid < 128 && warp < 4 && elect_one()) {
      const int g = warp & 1;
      if (warp < 2) {
        tma_pf3(&tm.x, 0, (2 * (bid & 63) + g) * MT, bid >> 6);
        if (has_x2(bid, 0, g)) tma_pf3(&tm.x, 0, (128 + (bid & 31)) * MT, bid >> 6);
      } else {
        tma_pf3(&tm.we, 0, 0, (bid >> 1) * 8 + rank * 2 + g);
      }
    }
    __syncwarp();
  }
  if (warp >= 8) {
    asm volatile("setmaxnreg.dec.sync.aligned.u32 40;");
    asm volatile("barrier.cluster.wait.aligned;" ::: "memory");
    const int role = __shfl_sync(0xffffffffu, read_info(bar, 0), 0);
    const unsigned* lctr = ctr + (role >> 5) * C_SIDE * 32;
    if (role >= 64) {
    } else if (warp == 9 || warp == 10) {
      asm volatile("barrier.cluster.arrive.relaxed.aligned;" ::: "memory");
      if (warp == 9) manager<0>(tm, lctr, sb, role * 2 + rank); else manager<1>(tm, lctr, sb, role * 2 + rank);
      __syncwarp();
      asm volatile("barrier.cluster.wait.aligned;" ::: "memory");
      return;
    } else if (warp == 11) {
      const uint8_t* ws = xbuf + (PG_W << 21) + ((role & 31) * 2 + rank) * WBLK;
      int slot = 0;
#pragma unroll 1
      for (int v = 0; v < 64; v++) {
        const uint8_t* src = ws + (size_t)slot * WSLOT;
        uint32_t dst = sb + (v & 3) * G_STAGE, fb = bar + B_FULL + 8 * (v & 3);
        asm volatile("" : "+l"(src), "+r"(dst), "+r"(fb));
        if (++slot == WR) slot = 0;
        const unsigned* fp = &lctr[(C_FLAG + (v >> 1)) * 32];
        const bool ready = (v & 1) || __shfl_sync(0xffffffffu, flag_peek(fp), 0) >= 128;
        mbar_wait(bar + B_EMPTY + 8 * (v & 3), ((v >> 2) & 1) ^ 1);
        ONE(mbar_expect(fb, WBLK));
        if (!ready) flag_wait(fp, 128);
        ONE(fence_async_global(); bulk_ld(dst, src, WBLK, fb));
      }
    } else {
      const uint32_t pgmask = __shfl_sync(0xffffffffu, read_info(bar, 1), 0);
      const int b = role >> 5, u = role & 31;
      const uint64_t pef = policy_evict_first(), pen = policy_evict_unchanged();
      const uint8_t* xs = xbuf + spread5(u);
      const int skip = rank * 2048;
#pragma unroll 1
      for (int v = 0; v < 64; v++) {
        const int n = v >> 1;
        uint64_t polx = (n < XKEEP || n >= 16) ? pef : pen;
        uint32_t dst = sb + (v & 3) * G_STAGE + WBLK + rank * 8192, fb = bar + B_FULL + 8 * (v & 3);
        const uint8_t* src[3];
#pragma unroll
        for (int g = 0; g < 3; g++) {
          int par;
          const uint32_t o = x_base(b ^ u, chunk_of(n) * 10 + (v & 1) * 5 + rank * 2 + g, pgmask, par);
          src[g] = xs + o + (par << 12) + (g ? 0 : skip);
        }
        asm volatile("" : "+l"(src[0]), "+l"(src[1]), "+l"(src[2]), "+l"(polx), "+r"(dst), "+r"(fb));
        const unsigned* fp = &lctr[(C_FLAG + n) * 32];
        const bool ready = (v & 1) || v >= 32 || __shfl_sync(0xffffffffu, flag_peek(fp), 0) >= 128;
        mbar_wait(bar + B_EMPTY + 8 * (v & 3), ((v >> 2) & 1) ^ 1);
        ONE(mbar_expect(fb, XBLK));
        if (!ready) flag_wait(fp, 128);
        ONE(fence_async_global();
            bulk_ld_mc_h(dst + skip, src[0], 4096 - skip, fb, 3, polx);
            bulk_ld_mc_h(dst + 4096, src[1], 4096, fb, 3, polx);
            bulk_ld_mc_h(dst + 8192, src[2], 2048 + skip, fb, 3, polx));
      }
      const int dq = rank * 2 + (u & 1), t0 = (u >> 1) * 10, tw = tail_win(u >> 1);
      int row[5];
      const CUtensorMap* mp[5];
      auto locate = [&](int half) {
#pragma unroll
        for (int k = 0; k < 5; k++) {
          int par;
          row[k] = x_base(b ^ tw, y_idx(half, dq, k), pgmask, par);
          row[k] = (row[k] + spread5(tw) + (par << 12)) >> 7;
          mp[k] = &tm.yld[par];
          asm volatile("" : "+r"(row[k]), "+l"(mp[k]));
        }
      };
      locate(0);
      flag_wait(&ctr[C_E * 32], 4);
      flag_wait(&lctr[(C_FLAG + YFLUSH) * 32], 128);
      ONE(fence_async_global();
          mbar_expect(bar + B_H0C, 6 * 8192);
          for (int i = 0; i < 3; i++) tma_ld4(sb + OFF_XR + i * 16384, mp[i], row[i], bar + B_H0C));
      static_assert(YFLUSH >= 23, "phase of the B_DONE ring");
      mbar_wait(bar + B_DONE + 8 * 7, 1);
      ONE(mbar_expect(bar + B_H0, 2 * 8192 + 7168 + 5120 + 512);
          bulk_ld(sb + OFF_F, g_Gimg, 7168, bar + B_H0);
          tma_ld4(sb + OFF_WS, mp[3], row[3], bar + B_H0);
          for (int hf = 0; hf < 2; hf++) {
            bulk_ld(sb + OFF_E + hf * 2560, g_E + ((b * 8 + hf * 4 + dq) * NT + t0) * 64, 2560, bar + B_H0);
            bulk_ld(sb + OFF_GB + hf * 256, gamma + (hf * 4 + dq) * 64, 128, bar + B_H0);
            bulk_ld(sb + OFF_GB + hf * 256 + 128, beta + (hf * 4 + dq) * 64, 128, bar + B_H0);
          });
      mbar_wait(bar + B_EMPTY + 8 * 2, 1);
      ONE(mbar_expect(bar + B_H0 + 8, 16384);
          tma_ld4(sb + OFF_H0B, mp[4], row[4], bar + B_H0 + 8);
          for (int i = 0; i < 3; i++) mbar_expect(bar + B_H1 + 8 * i, i < 2 ? 32768 : 16384));
      locate(1);
      flag_wait(&lctr[(C_Y + rank) * 32], 32);
      ONE(fence_async_global();
          for (int i = 0; i < YA; i++) tma_ld4(sb + i * 16384, mp[i], row[i], bar + B_H1 + 8 * (i >> 1));
          PROF_T(5));
      if (YA < 5) {
        flag_wait(&lctr[(C_Y + 2 + rank) * 32], 32);
        ONE(fence_async_global();
            for (int i = YA; i < 5; i++) tma_ld4(sb + i * 16384, mp[i], row[i], bar + B_H1 + 8 * (i >> 1));
            PROF_T(1));
      }
      const int lane = lane_id();
      unsigned old = 0;
      if (lane == 0) old = atomicAdd(&ctr[C_EXIT * 32], 1);
      if (__shfl_sync(0xffffffffu, old, 0) == 127) {
#pragma unroll
        for (int i = 0; i < 6; i++) *(uint4*)&ctr[((i >> 1) * 128 + (i & 1) * C_SIDE + lane) * 32] = make_uint4(0, 0, 0, 0);
      }
    }
    asm volatile("barrier.cluster.arrive.relaxed.aligned;\nbarrier.cluster.wait.aligned;" ::: "memory");
  } else {
    asm volatile("setmaxnreg.inc.sync.aligned.u32 224;");
    const int wg = warp >> 2, w = warp & 3;
    int lane = lane_id();
    asm volatile("barrier.cluster.wait.aligned;" ::: "memory");
    mbar_wait(bar + B_F, 0);
    const int id = __shfl_sync(0xffffffffu, read_info(bar, 0), 0) * 2 + rank;
    if (id >= 128) {
      float ea[80], eb[80];
      const int b = (id >> 1) & 1;
      constexpr int ES = 32768 + 2 * XBLK;
#pragma unroll 1
      for (int k = -3; k < 8; k++) {
        const int sl = (k + 3) % 3;
        if (k >= 0) {
          mbar_wait(bar + B_RAWX + 8 * sl, (k / 3) & 1);
          const uint64_t da = mk_desc(sb + sl * ES + wg * 16384), db = mk_desc(sb + sl * ES + 32768);
          wg_fence();
#pragma unroll
          for (int kk = 0; kk < 8; kk++) {
            const uint64_t a0 = da + (kk & 3) * 128, b0 = db + (kk & 3) * 2 + (kk >> 2) * (XBLK >> 4);
            wgmma_main<1>(ea, a0, b0, (k | kk) != 0);
            wgmma_main<1>(eb, a0 + 512, b0, (k | kk) != 0);
          }
          wg_commit();
          wg_wait<0>();
          asm volatile("bar.sync 3, 256;" ::: "memory");
        }
        if (k + 3 < 8 && warp == 0 && elect_one()) {
          if (k == -3) {
            for (int i = 0; i < 64; i++) {
              unsigned v;
              asm volatile("ld.relaxed.gpu.global.u32 %0, [%1];" : "=r"(v) : "l"(&ctr[(C_FLAG + 14) * 32]) : "memory");
              if (v >= 128) break;
              __nanosleep(500);
            }
          }
          const uint32_t dst = sb + sl * ES, fb = bar + B_RAWX + 8 * sl;
          mbar_expect(fb, ES);
          for (int q = 0; q < 4; q++) tma_ld2(dst + q * 8192, &tm.w30, rank * 256 + q * 64, (k + 3) * 64, fb);
          for (int q = 0; q < 2; q++) tma_ld3(dst + 32768 + q * XBLK, &tm.xe[q], (k + 3) * 64, 0, b, fb);
        }
        __syncwarp();
      }
      fence_regs(ea);
      fence_regs(eb);
      float* e0 = g_E + ((b * 8 + rank * 4 + wg * 2) * NT + 10 * (lane & 2) + (lane & 1)) * 64 + 16 * w + (lane >> 2);
#pragma unroll
      for (int i = 0; i < 80; i++) {
        const int o = (40 * ((i >> 2) & 3) + 2 * (i >> 4) + 10 * (i & 1)) * 64 + ((i >> 1) & 1) * 8;
        e0[o] = ea[i];
        e0[o + NT * 64] = eb[i];
      }
      asm volatile("bar.sync 3, 256;" ::: "memory");
      if (threadIdx.x == 0) {
        fence_release();
        red_add(&ctr[C_E * 32]);
        PROF_T(28);
      }
      asm volatile("barrier.cluster.arrive.relaxed.aligned;\nbarrier.cluster.wait.aligned;" ::: "memory");
      return;
    }
    if (w < 2 && elect_one()) {
      const uint32_t fb = bar + B_RAWW + 8 * (wg * 2 + w);
      mbar_expect(fb, 2048);
      tma_ld3h(sb + OFF_WRAW + (wg * 2 + w) * 2048, &tm.we, 0, 0, (w * 64 + w_row(id)) * 8 + rank * 2 + wg, fb, policy_evict_first());
      if (!w) mbar_arrive(fb);
    }
    __syncwarp();
    {
      float yr[80], yi[80], t[32];

      int xs = 0, xph = 0;
      if (threadIdx.x == 0) PROF_T(24);
      W_WAIT(0);
      t_issue<false>(t, sb, WRAW(0));
      wg_wait<0>();
      W_FINISH();
      if (threadIdx.x == 0) PROF_T(25);
#pragma unroll 1
      for (int m = 0; m <= LW; m++) {
        X_WAIT();
        X_ISSUE();
        wg_wait<0>();
        X_FINISH((2 * id + wg) & 7);
        if (threadIdx.x == 0 && m == 0) PROF_T(26);
        if (has_x2(id, m, wg)) {
          X_WAIT();
          X_ISSUE();
          wg_wait<0>();
          X_FINISH(id & 7);
        }
        if (m < LW && m) {
          W_WAIT(m);
          t_issue<false>(t, sb, WRAW(m));
          wg_wait<0>();
          W_FINISH();
        }
      }
      if (threadIdx.x == 0) PROF_T(27);
      const int ym = lane >> 3, yr8 = lane & 7;
      const uint32_t yad = (ym >> 1) * 4096 + yr8 * 128 + (((2 * w + (ym & 1)) ^ yr8) << 4);
#define STAGE_PROF0()
#define STAGE_PROF1()
#define STAGE_BEGIN() PROF_W(wfull, mbar_wait(bar + B_FULL + 8 * (v & 3), (v >> 2) & 1)); STAGE_PROF0(); const uint32_t st = sb + (v & 3) * G_STAGE
#define RELEASE(vv) do { if (w == 0 && lane < 2) mbar_arrive_cluster(bar + B_EMPTY + 8 * ((vv) & 3), lane, 1); } while (0)
#define XRAW (sb + OFF_XR + (wg * 3 + xs) * 8192)
#define STAGE_W0(mw, sd) do { W_WAIT(mw); batch<1, 0, 2>(yr, yi, t, st, wg, sd, sb + OFF_F, WRAW(mw)); wg_wait<1>(); W_FINISH(); wg_wait<0>(); RELEASE(v); } while (0)
#define STAGE_PLAIN0(sd) do { batch<0, 0, 2>(yr, yi, t, st, wg, sd, 0, 0); wg_wait<0>(); RELEASE(v); } while (0)
#define STAGE_W1(mw, sd) do { W_WAIT(mw); batch<1, 0, 1>(yr, yi, t, st, wg, sd, sb + OFF_F, WRAW(mw)); wg_wait<1>(); if (sd) RELEASE(v - 1); \
                              W_FINISH(); batch<0, 1, 2>(yr, yi, t, st, wg, 1, 0, 0); } while (0)
#define STAGE_PLAIN1(sd) do { batch<0, 0, 1>(yr, yi, t, st, wg, sd, 0, 0); wg_wait<1>(); if (sd) RELEASE(v - 1); \
                              batch<0, 1, 2>(yr, yi, t, st, wg, 1, 0, 0); } while (0)
#pragma unroll 1
      for (int v = 0; v < 32; v++) {
        const int m = ((v + 1) >> 1) + LW;
        STAGE_BEGIN();
        if (!(v & 1) || v == 31) {
          STAGE_W1(m, v != 0);
        } else if (m >= 16) {
          STAGE_PLAIN1(1);
        } else {
          X_WAIT();
          batch<4, 0, 1>(yr, yi, t, st, wg, 1, sb + OFF_F, XRAW);
          wg_wait<1>();
          RELEASE(v - 1);
          X_FINISH((2 * id + wg) & 7);
          if (has_x2(id, m, wg)) {
            X_WAIT();
            batch<4, 1, 2>(yr, yi, t, st, wg, 1, sb + OFF_F, XRAW);
            wg_wait<1>();
            X_FINISH(id & 7);
          } else {
            batch<0, 1, 2>(yr, yi, t, st, wg, 1, 0, 0);
          }
        }
        STAGE_PROF1();
      }
      wg_wait<0>();
      fence_regs(yr);
      fence_regs(yi);
      RELEASE(31);
      {
        uint32_t hold[32];
#pragma unroll
        for (int j = 0; j < 20; j++) {
          const uint32_t p0 = pack2(yr[4 * j], yr[4 * j + 1]), p1 = pack2(yr[4 * j + 2], yr[4 * j + 3]);
          const uint32_t p2 = pack2(yi[4 * j], yi[4 * j + 1]), p3 = pack2(yi[4 * j + 2], yi[4 * j + 3]);
          if (j < 12) {
            stsm4t(sb + OFF_XR + wg * 3 * 8192 + yad + (j >> 2) * 8192 + (j & 3) * 1024, p0, p1, p2, p3);
          } else {
            hold[4 * j - 48] = p0; hold[4 * j - 47] = p1; hold[4 * j - 46] = p2; hold[4 * j - 45] = p3;
          }
        }
#pragma unroll
        for (int j = 0; j < 32; j++) asm volatile("" : "+r"(hold[j])::"memory");
        fence_async_smem();
        __syncwarp();
        if (lane == 0) mbar_arrive(bar + B_Y + 8 * wg);
        if (threadIdx.x == 0) PROF_T(2);
#pragma unroll
        for (int v = 32; v < 34; v++) {
          STAGE_BEGIN();
          STAGE_PLAIN0(v != 32);
          STAGE_PROF1();
        }
        mbar_wait(bar + B_YFREE + 8 * wg, 0);
#pragma unroll
        for (int j = 0; j < 8; j++)
          stsm4t(sb + OFF_XR + wg * 3 * 8192 + yad + (j >> 2) * 8192 + (j & 3) * 1024, hold[4 * j], hold[4 * j + 1], hold[4 * j + 2], hold[4 * j + 3]);
        fence_async_smem();
        __syncwarp();
        if (lane == 0) mbar_arrive(bar + B_Y + 8 * wg);
#pragma unroll
        for (int j = 0; j < 32; j++) t[j] = __uint_as_float(hold[j]);
      }
#pragma unroll 1
      for (int v = 34; v < 64; v++) {
        const int m = (v >> 1) + LW;
        STAGE_BEGIN();
        if (!(v & 1) && m < 32) {
          STAGE_W0(m, 1);
        } else {
          STAGE_PLAIN0(1);
          if (v == 49 && wg == 0) part_ptr(xbuf, id >> 6, w >> 1, rank * 2 + ((id >> 1) & 1), (id >> 2) & 15)[(w & 1) * 32 + lane] = ~0ull;
        }
        STAGE_PROF1();
      }
      wg_wait<0>();
      fence_regs(yr);
      fence_regs(yi);
      asm volatile("bar.sync 3, 256;" ::: "memory");
#pragma unroll
      for (int j = 0; j < 20; j++) {
        stsm4t(sb + wg * 8192 + yad + (j >> 2) * 16384 + (j & 3) * 1024, pack2(yr[4 * j], yr[4 * j + 1]), pack2(yr[4 * j + 2], yr[4 * j + 3]),
               pack2(yi[4 * j], yi[4 * j + 1]), pack2(yi[4 * j + 2], yi[4 * j + 3]));
        if ((j & 3) == 3) {
          __syncwarp();
          if (lane == 0) mbar_arrive(bar + B_YP + 8 * (wg * 5 + (j >> 2)));
        }
      }
      if (threadIdx.x == 0) { PROF_T(3); unsigned smid_; asm("mov.u32 %0, %%smid;" : "=r"(smid_)); PROF_V(19, smid_ + 1000 * id); }
    }
    asm volatile("barrier.cluster.arrive.relaxed.aligned;" ::: "memory");
    lane = lane_id();
    const int tid = warp * 32 + lane, b = id >> 6, u = (id >> 1) & 31;
    const int dq = rank * 2 + (u & 1), tr = u >> 1;
    const int a = lane & 3, d0 = 16 * w + (lane >> 2);
    float2* s_red = (float2*)(smem_raw + OFF_WRAW);
    const uint32_t oad = wg * 8192 + ((lane >> 4) * 8 + (lane & 7)) * 128 + (((2 * w + ((lane >> 3) & 1)) ^ (lane & 7)) << 4);
    float hz[28];
#pragma unroll
    for (int i = 0; i < 28; i++) hz[i] = 0.f;
#pragma unroll 1
    for (int hf = 0; hf < 2; hf++) {
      const uint32_t base = sb + (hf ? 0 : OFF_XR), last = hf ? 0 : OFF_H0B - 65536 - OFF_XR;
      float acc[5][28];
      float q1[4] = {0.f, 0.f, 0.f, 0.f}, q2[4] = {0.f, 0.f, 0.f, 0.f};
      if (hf == 0) { mbar_wait(bar + B_H0, 0); mbar_wait(bar + B_H0C, 0); }
      const float* se = (const float*)(smem_raw + OFF_E + hf * 2560) + wg * 64 + d0;
#pragma unroll
      for (int k2 = 0; k2 < 4; k2++) {
        if (k2 < 3) {
          if (hf) mbar_wait(bar + B_H1 + 8 * k2, 0);
          else if (k2 == 2) mbar_wait(bar + B_H0 + 8, 0);
          const uint64_t da = mk_desc(base + (4 * k2 + wg) * 8192 + (k2 == 2 ? last : 0)), db = mk_desc(sb + OFF_F);
          wg_fence();
#pragma unroll
          for (int kk = 0; kk < 4; kk++) {
            wgmma_inv<1>(acc[2 * k2], da + 128 * kk, db + 2 * kk, kk);
            if (k2 < 2) wgmma_inv<1>(acc[2 * k2 + 1], da + 1024 + 128 * kk, db + 2 * kk, kk);
          }
          wg_commit();
        }
        if (k2 > 0) {
          if (k2 < 3) wg_wait<1>(); else wg_wait<0>();
#pragma unroll
          for (int k = 2 * k2 - 2; k < 2 * k2 && k < 5; k++) {
            fence_regs(acc[k]);
            if (a == 0) {
              acc[k][25] += se[k * 128];
              acc[k][27] += se[k * 128 + 8];
            }
            if (k == 4 && tr == 15 && wg == 1) {
#pragma unroll
              for (int i = 16; i < 28; i++)
                if (8 * (i >> 2) + (i & 1) + 2 * a >= LOUT - (NT - 1) * MT) acc[k][i] = 0.f;
            }
#pragma unroll
            for (int i = 0; i < 28; i++) {
              q1[i & 3] += acc[k][i];
              q2[i & 3] = fmaf(acc[k][i], acc[k][i], q2[i & 3]);
            }
            fence_regs(q1);
            fence_regs(q2);
          }
        }
      }
      float s1[2] = {q1[0] + q1[1], q1[2] + q1[3]}, s2[2] = {q2[0] + q2[1], q2[2] + q2[3]};
#pragma unroll
      for (int i = 0; i < 2; i++) {
#pragma unroll
        for (int o = 1; o < 4; o <<= 1) {
          s1[i] += __shfl_xor_sync(0xffffffffu, s1[i], o);
          s2[i] += __shfl_xor_sync(0xffffffffu, s2[i], o);
        }
      }
      if (a == 0) {
        s_red[wg * 64 + d0] = make_float2(s1[0], s2[0]);
        s_red[wg * 64 + d0 + 8] = make_float2(s1[1], s2[1]);
      }
      asm volatile("bar.sync 3, 256;" ::: "memory");
      if (tid == 0) PROF_T(6 + 3 * hf);
      if (tid < 64) {
        const float2 p0 = s_red[tid], p1 = s_red[64 + tid];
        const float x1 = p0.x + p1.x, x2 = p0.y + p1.y;
        const unsigned long long v = ((unsigned long long)(__float_as_uint(x2) & 0x7fffffffu) << 32) | __float_as_uint(x1);
        asm volatile("st.relaxed.gpu.global.u64 [%0], %1;" ::"l"(part_ptr(xbuf, b, hf, dq, tr) + tid), "l"(v) : "memory");
      }
      if (HOLD && hf) {
        gelu_store(hz, sb + OFF_H0B + oad);
        __syncwarp();
        if (lane == 0) mbar_arrive(bar + B_OUT + 8 * (wg * 5 + 4));
      }
      {
        const unsigned long long* q = part_ptr(xbuf, b, hf, dq, (tid >> 6) * 4) + (tid & 63);
        unsigned long long v[4];
        poll64x4(q, v);
        float x1 = 0.f, x2 = 0.f;
#pragma unroll
        for (int i = 0; i < 4; i++) {
          x1 += __uint_as_float((uint32_t)v[i]);
          x2 += __uint_as_float((uint32_t)(v[i] >> 32));
        }
        s_red[128 + tid] = make_float2(x1, x2);
      }
      asm volatile("bar.sync 3, 256;" ::: "memory");
      if (tid == 0) PROF_T(7 + 3 * hf);
#pragma unroll
      for (int i = 0; i < 2; i++) {
        const float2 q0 = s_red[128 + d0 + 8 * i], q1 = s_red[192 + d0 + 8 * i], q2 = s_red[256 + d0 + 8 * i], q3 = s_red[320 + d0 + 8 * i];
        const float mu = ((q0.x + q1.x) + (q2.x + q3.x)) * (1.f / LOUT);
        const float var = fmaxf(((q0.y + q1.y) + (q2.y + q3.y)) * (1.f / LOUT) - mu * mu, 0.f);
        const __nv_bfloat16* gb = (const __nv_bfloat16*)(smem_raw + OFF_GB + hf * 256) + d0 + 8 * i;
        s1[i] = 0.5f * __bfloat162float(gb[0]) * rsqrtf(var + 1e-5f);
        s2[i] = 0.5f * __bfloat162float(gb[64]) - mu * s1[i];
      }
#pragma unroll
      for (int k = 0; k < 5; k++) {
#pragma unroll
        for (int i = 0; i < 28; i++) hz[i] = fmaf(acc[k][i], s1[(i >> 1) & 1], s2[(i >> 1) & 1]);
        if (HOLD && k == 4) break;
        gelu_store(hz, base + oad + k * 16384 + (k == 4 ? last : 0));
        float z;
        asm volatile("ld.volatile.shared.f32 %0, [%1];" : "=f"(z) : "r"(sb + OFF_F + 55 * 128) : "memory");
        s2[0] += z;
        s2[1] += z;
        __syncwarp();
        if (lane == 0) mbar_arrive(bar + B_OUT + 8 * (wg * 5 + k));
      }
      if (tid == 0) PROF_T(8 + 3 * hf);
    }
    if (HOLD) {
      gelu_store(hz, sb + 4 * 16384 + oad);
      __syncwarp();
      if (lane == 0) mbar_arrive(bar + B_OUT + 8 * (wg * 5 + 4));
    }
    asm volatile("barrier.cluster.wait.aligned;" ::: "memory");
  }
}

typedef CUresult (*EncFn)(CUtensorMap*, CUtensorMapDataType, cuuint32_t, void*, const cuuint64_t*, const cuuint64_t*, const cuuint32_t*,
                          const cuuint32_t*, CUtensorMapInterleave, CUtensorMapSwizzle, CUtensorMapL2promotion, CUtensorMapFloatOOBfill);

void encode(EncFn fn, CUtensorMap* m, int rank, void* base, const cuuint64_t* dims, const cuuint64_t* strides, const cuuint32_t* box,
            CUtensorMapL2promotion promo) {
  cuuint32_t es[5] = {1, 1, 1, 1, 1};
  fn(m, CU_TENSOR_MAP_DATA_TYPE_BFLOAT16, rank, base, dims, strides, box, es, CU_TENSOR_MAP_INTERLEAVE_NONE, CU_TENSOR_MAP_SWIZZLE_128B, promo,
     CU_TENSOR_MAP_FLOAT_OOB_FILL_NONE);
}

}

extern "C" void kernel_launch(void* const* d_in, const int* in_sizes, int n_in, void* d_out, int out_size) {
  (void)in_sizes; (void)n_in; (void)out_size;
  const __nv_bfloat16* x = (const __nv_bfloat16*)d_in[0];
  const __nv_bfloat16* w = (const __nv_bfloat16*)d_in[1];
  const __nv_bfloat16* gamma = (const __nv_bfloat16*)d_in[2];
  const __nv_bfloat16* beta = (const __nv_bfloat16*)d_in[3];
  void* fnp = nullptr;
  cudaDriverEntryPointQueryResult qr;
  cudaGetDriverEntryPoint("cuTensorMapEncodeTiled", &fnp, cudaEnableDefault, &qr);
  EncFn fn = (EncFn)fnp;
  void *fptr = nullptr, *xptr = nullptr;
  cudaGetSymbolAddress(&fptr, g_Fimg);
  cudaGetSymbolAddress(&xptr, g_X);
  xptr = (void*)(((uintptr_t)xptr + (1u << 21) - 1) & ~(uintptr_t)((1u << 21) - 1));
  const CUtensorMapL2promotion P0 = CU_TENSOR_MAP_L2_PROMOTION_NONE, P128 = CU_TENSOR_MAP_L2_PROMOTION_L2_128B;
  Maps m;
  {
    cuuint64_t d[3] = {1024, 8000, 2}, s[2] = {2048, 8000ull * 2048};
    cuuint32_t bx[3] = {64, 64, 1};
    encode(fn, &m.x, 3, (void*)x, d, s, bx, P128);
  }
  for (int ph = 0; ph < 2; ph++) {
    cuuint64_t d[3] = {64, (cuuint64_t)(16 - ph), 4096}, s[2] = {2ull * 262144 * 2, 128};
    cuuint32_t bx[3] = {64, 16, 1};
    encode(fn, ph ? &m.wo : &m.we, 3, (void*)(w + (size_t)ph * 262144), d, s, bx, P128);
  }
  for (int par = 0; par < 2; par++) {
    cuuint64_t d[5] = {(cuuint64_t)XPAGES << 20, 2, 4, 2, 2}, s[4] = {par ? 0x1000u : 0x3000u, 1u << 14, 1u << 18, 1u << 20};
    cuuint32_t bx[5] = {64, 2, 4, 2, 2};
    encode(fn, &m.xst[par], 5, xptr, d, s, bx, P0);
  }
  {
    cuuint64_t d[4] = {64, 32, 2, (cuuint64_t)WR * WSLOT / 128}, s[3] = {2ull * WBLK, 4096, 128};
    cuuint32_t bx[4] = {64, 32, 2, 1};
    encode(fn, &m.wst, 4, (char*)xptr + ((size_t)PG_W << 21), d, s, bx, P0);
  }
  for (int par = 0; par < 2; par++) {
    cuuint64_t d[4] = {64, (cuuint64_t)XPAGES << 14, 2, 2}, s[3] = {128, par ? 0xf000u : 0x11000u, 1u << 14};
    cuuint32_t bx[4] = {64, 32, 2, 2};
    encode(fn, &m.yld[par], 4, xptr, d, s, bx, P128);
  }
  {
    cuuint64_t d[3] = {512, LOUT, 2}, s[2] = {1024, (cuuint64_t)LOUT * 1024};
    cuuint32_t bx[3] = {64, MT, 1};
    encode(fn, &m.out, 3, d_out, d, s, bx, P0);
  }
  for (int q = 0; q < 2; q++) {
    cuuint64_t d[3] = {512, (cuuint64_t)(NT - q), 2}, s[2] = {MT * 2048, 8000ull * 2048};
    cuuint32_t bx[3] = {64, NT, 1};
    encode(fn, &m.xe[q], 3, (void*)(x + q * 64 * 1024), d, s, bx, P128);
  }
  {
    cuuint64_t d[2] = {512, 512}, s[1] = {1024};
    cuuint32_t bx[2] = {64, 64};
    encode(fn, &m.w30, 2, (void*)(w + 30 * 262144), d, s, bx, P128);
  }
  cudaFuncSetAttribute(k1_main, cudaFuncAttributeMaxDynamicSharedMemorySize, SMEM_BYTES);
  k1_main<<<132, 512, SMEM_BYTES>>>((uint8_t*)xptr, fptr, gamma, beta, m);
}
```

```cpp
#include <cuda_runtime.h>
#include <cuda_bf16.h>
#include <cuda.h>
#include <stdint.h>

namespace {

#define FINB 0
constexpr int LOUT = 7985;
constexpr int MT = 50;
constexpr int NT = 160;
constexpr int XBLK = NT * 128;
constexpr int WBLK = 16384;
constexpr int LW = 4;
constexpr int WR = 10;
constexpr int WSLOT = 64 * WBLK;
constexpr int PG_Y = 20, PG_W = 25, XPAGES = 30;
constexpr int YA = 2;
constexpr int NFL = 2;
constexpr int XKEEP = 9;
constexpr int YFLUSH = 20 + LW;

__device__ __align__(1024) uint8_t g_X[(XPAGES + 2) << 21];
__device__ __align__(128) float g_E[16 * NT * 64];
constexpr int CTR_OFF = (XPAGES << 21) + 0x100000, PART_OFF = CTR_OFF + 0x40000;
constexpr int C_FLAG = 0, C_LOADED = 128  , C_Y = 256, C_E = 260, C_REG = 261, C_EXIT = 262, C_SIDE = 32;
__device__ __forceinline__ unsigned long long* part_ptr(uint8_t* xbuf, int side, int hf, int dq, int tr) {
  return (unsigned long long*)(xbuf + PART_OFF + ((hf * 4 + dq) * 2 + (tr >> 3)) * 8192 + ((side ^ hf ^ (tr >> 3)) << 12) + (tr & 7) * 512);
}
#define PROF_T(i)
#define PROF_C(i)
#define PROF_V(i, v)
#define PROF_W(acc, stmt) stmt

__device__ __align__(128) const uint32_t g_Fimg[2048] = {
 0x3f803f80,0x3f7d3f7f,0x3f783f7b,0x3f713f75,0x3f673f6d,0x3f5c3f62,0x3f4e3f55,0x3f3e3f46,0x3f2c3f35,0x3f183f22,0x3f043f0e,0x3edb3ef1,0x3eac3ec4,0x3e793e95,0x3e163e48,0x3d493dc9,
 0xbd490000,0xbe16bdc9,0xbe79be48,0xbeacbe95,0xbedbbec4,0xbf04bef1,0xbf18bf0e,0xbf2cbf22,0xbf3ebf35,0xbf4ebf46,0xbf5cbf55,0xbf67bf62,0xbf71bf6d,0xbf78bf75,0xbf7dbf7b,0xbf80bf7f,
 0x3e793ec4,0xbd493dc9,0xbeacbe48,0xbf18bef1,0x3f7d3f80,0x3f673f75,0x3f3e3f55,0x3f043f22,0xbf5cbf6d,0xbf2cbf46,0xbedbbf0e,0xbe16be95,0xbf4ebf35,0xbf71bf62,0xbf80bf7b,0xbf78bf7f,
 0x3f783f6d,0x3f803f7f,0x3f713f7b,0x3f4e3f62,0x3e160000,0x3edb3e95,0x3f2c3f0e,0x3f5c3f46,0xbf04bec4,0xbf3ebf22,0xbf67bf55,0xbf7dbf75,0x3f183f35,0x3eac3ef1,0x3d493e48,0xbe79bdc9,
 0xbf04bf35,0xbd49be95,0x3edb3e48,0x3f4e3f22,0x3f7d3f6d,0x3f713f7f,0x3f2c3f55,0x3e793ef1,0x3f783f80,0x3f3e3f62,0x3eac3f0e,0xbe163dc9,0xbf18bec4,0xbf67bf46,0xbf80bf7b,0xbf5cbf75,
 0x3f5c3f35,0x3f803f75,0x3f673f7b,0x3f183f46,0x3e163ec4,0xbeacbdc9,0xbf3ebf0e,0xbf78bf62,0xbe790000,0xbf2cbef1,0xbf71bf55,0xbf7dbf7f,0xbf4ebf6d,0xbedbbf22,0x3d49be48,0x3f043e95,
 0xbf2cbec4,0xbf7dbf62,0xbf5cbf7b,0xbeacbf22,0x3f673f35,0x3f783f7f,0x3f183f55,0xbd493e95,0xbf80bf6d,0xbf4ebf75,0xbe79bf0e,0x3edb3dc9,0x3f713f80,0x3f043f46,0xbe163e48,0xbf3ebef1,
 0x3f3e3f6d,0x3e163ef1,0xbf04be48,0xbf71bf46,0xbedbbf35,0x3e79bdc9,0x3f4e3f0e,0x3f803f75,0x3d493ec4,0xbf18be95,0xbf78bf55,0xbf67bf7f,0x3eac0000,0x3f5c3f22,0x3f7d3f7b,0x3f2c3f62,
 0xbedb0000,0xbf78bf46,0xbf4ebf7b,0xbd49bef1,0x3f3e3ec4,0x3f7d3f75,0x3f043f55,0xbeac3dc9,0xbf71bf35,0xbf5cbf7f,0xbe16bf0e,0x3f2c3e95,0x3f803f6d,0x3f183f62,0xbe793e48,0xbf67bf22,
 0x3f673f80,0x3e793f22,0xbf18be48,0xbf80bf62,0xbf2cbf6d,0x3e16be95,0x3f5c3f0e,0x3f713f7f,0x3eac3f35,0xbf04bdc9,0xbf7dbf55,0xbf3ebf75,0x3d49bec4,0x3f4e3ef1,0x3f783f7b,0x3edb3f46,
 0xbf7dbf6d,0xbeacbf46,0x3f2c3e48,0x3f783f75,0x3f040000,0x3f803f62,0x3edb3f55,0xbf18bdc9,0x3f4e3ec4,0x3f673f7f,0x3d493f0e,0xbf5cbef1,0x3e793f35,0xbf3ebe95,0xbf71bf7b,0xbe16bf22,
 0x3e16bec4,0x3f713f22,0x3f3e3f7b,0xbe793e95,0x3f5c3f80,0xbd493ef1,0xbf67bf0e,0xbf4ebf7f,0x3f183f6d,0xbedb3dc9,0xbf80bf55,0xbf04bf62,0xbf78bf35,0xbf2cbf75,0x3eacbe48,0x3f7d3f46,
 0x3f7d3f35,0x3edb3f62,0xbf3ebe48,0xbf5cbf7f,0x3e79bec4,0x3f803f46,0x3eac3f55,0xbf4ebe95,0xbf180000,0xbf71bf75,0x3d49bf0e,0x3f783f22,0x3f043f6d,0xbf2cbdc9,0xbf67bf7b,0x3e16bef1,
 0xbe16bf35,0x3f673ef1,0x3f2c3f7b,0xbf043dc9,0xbf78bf6d,0xbd49bf22,0x3f713f0e,0x3f183f75,0x3f4e3f80,0xbeac3e95,0xbf80bf55,0xbe79bf46,0x3f5c3ec4,0x3f3e3f7f,0xbedb3e48,0xbf7dbf62,
 0xbedbbf6d,0x3f5c3e95,0x3f183f7b,0xbf3ebdc9,0xbd49bf35,0x3f7d3f22,0x3e793f55,0xbf71bef1,0x3eacbec4,0x3f783f62,0xbe163f0e,0xbf80bf46,0x3f2c0000,0x3f4e3f7f,0xbf043e48,0xbf67bf75,
 0x3f673ec4,0x3f043f75,0xbf4ebe48,0xbf2cbf7f,0x3f803f35,0x3e163f46,0xbf78bf0e,0xbeacbf62,0x3f713f6d,0xbe793ef1,0xbf7dbf55,0x3d49bf22,0x3f3e3f80,0xbf183dc9,0xbf5cbf7b,0x3edbbe95,
 0xbd490000,0xbe16bdc9,0xbe79be48,0xbeacbe95,0xbedbbec4,0xbf04bef1,0xbf18bf0e,0xbf2cbf22,0xbf3ebf35,0xbf4ebf46,0xbf5cbf55,0xbf67bf62,0xbf71bf6d,0xbf78bf75,0xbf7dbf7b,0xbf80bf7f,
 0xbf80bf80,0xbf7dbf7f,0xbf78bf7b,0xbf71bf75,0xbf67bf6d,0xbf5cbf62,0xbf4ebf55,0xbf3ebf46,0xbf2cbf35,0xbf18bf22,0xbf04bf0e,0xbedbbef1,0xbeacbec4,0xbe79be95,0xbe16be48,0xbd49bdc9,
 0xbf78bf6d,0xbf80bf7f,0xbf71bf7b,0xbf4ebf62,0xbe160000,0xbedbbe95,0xbf2cbf0e,0xbf5cbf46,0x3f043ec4,0x3f3e3f22,0x3f673f55,0x3f7d3f75,0xbf18bf35,0xbeacbef1,0xbd49be48,0x3e793dc9,
 0x3e793ec4,0xbd493dc9,0xbeacbe48,0xbf18bef1,0x3f7d3f80,0x3f673f75,0x3f3e3f55,0x3f043f22,0xbf5cbf6d,0xbf2cbf46,0xbedbbf0e,0xbe16be95,0xbf4ebf35,0xbf71bf62,0xbf80bf7b,0xbf78bf7f,
 0x3f5c3f35,0x3f803f75,0x3f673f7b,0x3f183f46,0x3e163ec4,0xbeacbdc9,0xbf3ebf0e,0xbf78bf62,0xbe790000,0xbf2cbef1,0xbf71bf55,0xbf7dbf7f,0xbf4ebf6d,0xbedbbf22,0x3d49be48,0x3f043e95,
 0x3f043f35,0x3d493e95,0xbedbbe48,0xbf4ebf22,0xbf7dbf6d,0xbf71bf7f,0xbf2cbf55,0xbe79bef1,0xbf78bf80,0xbf3ebf62,0xbeacbf0e,0x3e16bdc9,0x3f183ec4,0x3f673f46,0x3f803f7b,0x3f5c3f75,
 0xbf3ebf6d,0xbe16bef1,0x3f043e48,0x3f713f46,0x3edb3f35,0xbe793dc9,0xbf4ebf0e,0xbf80bf75,0xbd49bec4,0x3f183e95,0x3f783f55,0x3f673f7f,0xbeac0000,0xbf5cbf22,0xbf7dbf7b,0xbf2cbf62,
 0xbf2cbec4,0xbf7dbf62,0xbf5cbf7b,0xbeacbf22,0x3f673f35,0x3f783f7f,0x3f183f55,0xbd493e95,0xbf80bf6d,0xbf4ebf75,0xbe79bf0e,0x3edb3dc9,0x3f713f80,0x3f043f46,0xbe163e48,0xbf3ebef1,
 0xbf67bf80,0xbe79bf22,0x3f183e48,0x3f803f62,0x3f2c3f6d,0xbe163e95,0xbf5cbf0e,0xbf71bf7f,0xbeacbf35,0x3f043dc9,0x3f7d3f55,0x3f3e3f75,0xbd493ec4,0xbf4ebef1,0xbf78bf7b,0xbedbbf46,
 0xbedb0000,0xbf78bf46,0xbf4ebf7b,0xbd49bef1,0x3f3e3ec4,0x3f7d3f75,0x3f043f55,0xbeac3dc9,0xbf71bf35,0xbf5cbf7f,0xbe16bf0e,0x3f2c3e95,0x3f803f6d,0x3f183f62,0xbe793e48,0xbf67bf22,
 0x3e16bec4,0x3f713f22,0x3f3e3f7b,0xbe793e95,0x3f5c3f80,0xbd493ef1,0xbf67bf0e,0xbf4ebf7f,0x3f183f6d,0xbedb3dc9,0xbf80bf55,0xbf04bf62,0xbf78bf35,0xbf2cbf75,0x3eacbe48,0x3f7d3f46,
 0x3f7d3f6d,0x3eac3f46,0xbf2cbe48,0xbf78bf75,0xbf040000,0xbf80bf62,0xbedbbf55,0x3f183dc9,0xbf4ebec4,0xbf67bf7f,0xbd49bf0e,0x3f5c3ef1,0xbe79bf35,0x3f3e3e95,0x3f713f7b,0x3e163f22,
 0x3e163f35,0xbf67bef1,0xbf2cbf7b,0x3f04bdc9,0x3f783f6d,0x3d493f22,0xbf71bf0e,0xbf18bf75,0xbf4ebf80,0x3eacbe95,0x3f803f55,0x3e793f46,0xbf5cbec4,0xbf3ebf7f,0x3edbbe48,0x3f7d3f62,
 0x3f7d3f35,0x3edb3f62,0xbf3ebe48,0xbf5cbf7f,0x3e79bec4,0x3f803f46,0x3eac3f55,0xbf4ebe95,0xbf180000,0xbf71bf75,0x3d49bf0e,0x3f783f22,0x3f043f6d,0xbf2cbdc9,0xbf67bf7b,0x3e16bef1,
 0x3f673ec4,0x3f043f75,0xbf4ebe48,0xbf2cbf7f,0x3f803f35,0x3e163f46,0xbf78bf0e,0xbeacbf62,0x3f713f6d,0xbe793ef1,0xbf7dbf55,0x3d49bf22,0x3f3e3f80,0xbf183dc9,0xbf5cbf7b,0x3edbbe95,
 0x3edb3f6d,0xbf5cbe95,0xbf18bf7b,0x3f3e3dc9,0x3d493f35,0xbf7dbf22,0xbe79bf55,0x3f713ef1,0xbeac3ec4,0xbf78bf62,0x3e16bf0e,0x3f803f46,0xbf2c0000,0xbf4ebf7f,0x3f04be48,0x3f673f75,
 0x3f2c3f80,0xbf4ebdc9,0xbf04bf7b,0x3f673e95,0x3eac3f6d,0xbf78bef1,0xbe16bf55,0x3f803f22,0xbd493f35,0xbf7dbf46,0x3e79bf0e,0x3f713f62,0xbedb3ec4,0xbf5cbf75,0x3f18be48,0x3f3e3f7f,
 0xbf3e0000,0xbf18bf7f,0x3f5c3e48,0x3edb3f75,0xbf71bec4,0xbe79bf62,0x3f7d3f0e,0x3d493f46,0xbf80bf35,0x3e16bf22,0x3f783f55,0xbeac3ef1,0xbf67bf6d,0x3f04be95,0x3f4e3f7b,0xbf2c3dc9,
 0xbf043ec4,0xbf2cbf7f,0x3f673e48,0x3e163f62,0x3f183f80,0xbf71be95,0xbd49bf55,0x3f783f46,0xbe79bf6d,0x3f803f22,0xbeac3f0e,0xbf4ebf75,0xbf7dbf35,0x3edbbef1,0x3f3e3f7b,0xbf5cbdc9,
 0x3f5c3f6d,0xbf3e3dc9,0xbedbbf7b,0x3f7d3ef1,0x3f4e0000,0x3eac3f75,0xbf80bf0e,0x3e79bf22,0xbf78bec4,0x3d49bf46,0x3f713f55,0xbf183e95,0xbe163f35,0xbf67bf62,0x3f2cbe48,0x3f043f7f,
 0x3e79bf35,0x3f3e3f75,0xbf71be48,0x3e16bf46,0x3f4e3f6d,0xbf67bdc9,0x3d49bf55,0x3f5c3f62,0x3f043f80,0xbf80bef1,0x3edbbf0e,0x3f183f7f,0xbf7dbec4,0x3eacbf22,0x3f2c3f7b,0xbf78be95,
 0x3f783f35,0xbf2c3e95,0xbeacbf7b,0x3f7d3f22,0xbf183ec4,0xbedbbf7f,0x3f803f0e,0xbf043ef1,0xbf5c0000,0xbd49bf62,0x3f673f55,0xbf4e3dc9,0xbe16bf6d,0x3f713f46,0xbf3e3e48,0xbe79bf75,
 0xbf80bec4,0x3f18bef1,0x3e793f7b,0xbf67bf46,0x3f713f35,0xbf5c3dc9,0x3e16bf55,0x3f2c3f75,0xbf3ebf6d,0x3f7d3e95,0xbf043f0e,0xbeacbf7f,0x3edb3f80,0xbf78bf22,0x3f4ebe48,0xbd493f62,
 0x3d493f6d,0xbf4ebf62,0x3f783e48,0xbedb3f22,0x3eacbf35,0x3f043f7f,0xbf7dbf0e,0x3f3ebe95,0xbf2c3ec4,0xbe16bf75,0x3f5c3f55,0xbf71bdc9,0x3f670000,0xbe793f46,0xbf18bf7b,0x3f803ef1,
 0xbf710000,0x3f04bf22,0x3e163f7b,0xbf3ebf62,0x3f803ec4,0xbf4e3e95,0x3e79bf55,0x3edb3f7f,0xbf67bf35,0x3f783dc9,0xbf183f0e,0xbd49bf75,0x3f2c3f6d,0xbf7dbef1,0x3f5cbe48,0xbeac3f46,
 0x3eac3f80,0xbf5cbf46,0x3f7d3e48,0xbf2c3ef1,0x3d49bf6d,0x3f183f75,0xbf78bf0e,0x3f67bdc9,0xbedb3f35,0xbe79bf7f,0x3f4e3f55,0xbf80be95,0x3f3ebec4,0xbe163f62,0xbf04bf7b,0x3f713f22,
 0xbf18bf6d,0x3f673f22,0xbf80be48,0x3f5cbe95,0x3f780000,0xbf3e3ef1,0x3eacbf55,0x3e163f7f,0x3f7d3ec4,0xbf713dc9,0x3f2cbf0e,0xbe793f62,0xbf043f35,0x3d49bf75,0x3edb3f7b,0xbf4ebf46,
 0x3f4ebec4,0xbedb3f46,0xbd49bf7b,0x3f043f75,0x3e793f80,0xbf2cbf62,0x3f713f0e,0xbf7dbdc9,0xbe163f6d,0xbeacbf7f,0x3f3e3f55,0xbf78bef1,0xbf5cbf35,0x3f803e95,0xbf673e48,0x3f18bf22,
 0x3f4e3f35,0xbf71bef1,0x3f803e48,0xbf783dc9,0x3f5cbec4,0xbf2c3f22,0x3edbbf55,0xbe163f75,0xbf7d0000,0x3f67be95,0xbf3e3f0e,0x3f04bf46,0xbe793f6d,0xbd49bf7f,0x3eac3f7b,0xbf18bf62,
 0x3f18bf35,0xbeac3f62,0x3d49bf7b,0x3e793f7f,0xbf04bf6d,0x3f3e3f46,0xbf67bf0e,0x3f7d3e95,0x3e163f80,0xbedbbf75,0x3f2c3f55,0xbf5cbf22,0x3f783ec4,0xbf80bdc9,0x3f71be48,0xbf4e3ef1,
 0x3eacbf6d,0xbe793f75,0x3e16bf7b,0xbd493f7f,0x3f2cbf35,0xbf183f46,0x3f04bf55,0xbedb3f62,0x3f67bec4,0xbf5c3ef1,0x3f4ebf0e,0xbf3e3f22,0x3f800000,0xbf7d3dc9,0x3f78be48,0xbf713e95,
 0x3f713ec4,0xbf78be95,0x3f7d3e48,0xbf80bdc9,0x3f3e3f35,0xbf4ebf22,0x3f5c3f0e,0xbf67bef1,0x3edb3f6d,0xbf04bf62,0x3f183f55,0xbf2cbf46,0x3d493f80,0xbe16bf7f,0x3e793f7b,0xbeacbf75,
 0xbf3e0000,0xbf18bf7f,0x3f5c3e48,0x3edb3f75,0xbf71bec4,0xbe79bf62,0x3f7d3f0e,0x3d493f46,0xbf80bf35,0x3e16bf22,0x3f783f55,0xbeac3ef1,0xbf67bf6d,0x3f04be95,0x3f4e3f7b,0xbf2c3dc9,
 0xbf2cbf80,0x3f4e3dc9,0x3f043f7b,0xbf67be95,0xbeacbf6d,0x3f783ef1,0x3e163f55,0xbf80bf22,0x3d49bf35,0x3f7d3f46,0xbe793f0e,0xbf71bf62,0x3edbbec4,0x3f5c3f75,0xbf183e48,0xbf3ebf7f,
 0xbf5cbf6d,0x3f3ebdc9,0x3edb3f7b,0xbf7dbef1,0xbf4e0000,0xbeacbf75,0x3f803f0e,0xbe793f22,0x3f783ec4,0xbd493f46,0xbf71bf55,0x3f18be95,0x3e16bf35,0x3f673f62,0xbf2c3e48,0xbf04bf7f,
 0xbf043ec4,0xbf2cbf7f,0x3f673e48,0x3e163f62,0x3f183f80,0xbf71be95,0xbd49bf55,0x3f783f46,0xbe79bf6d,0x3f803f22,0xbeac3f0e,0xbf4ebf75,0xbf7dbf35,0x3edbbef1,0x3f3e3f7b,0xbf5cbdc9,
 0x3f783f35,0xbf2c3e95,0xbeacbf7b,0x3f7d3f22,0xbf183ec4,0xbedbbf7f,0x3f803f0e,0xbf043ef1,0xbf5c0000,0xbd49bf62,0x3f673f55,0xbf4e3dc9,0xbe16bf6d,0x3f713f46,0xbf3e3e48,0xbe79bf75,
 0xbe793f35,0xbf3ebf75,0x3f713e48,0xbe163f46,0xbf4ebf6d,0x3f673dc9,0xbd493f55,0xbf5cbf62,0xbf04bf80,0x3f803ef1,0xbedb3f0e,0xbf18bf7f,0x3f7d3ec4,0xbeac3f22,0xbf2cbf7b,0x3f783e95,
 0xbd49bf6d,0x3f4e3f62,0xbf78be48,0x3edbbf22,0xbeac3f35,0xbf04bf7f,0x3f7d3f0e,0xbf3e3e95,0x3f2cbec4,0x3e163f75,0xbf5cbf55,0x3f713dc9,0xbf670000,0x3e79bf46,0x3f183f7b,0xbf80bef1,
 0xbf80bec4,0x3f18bef1,0x3e793f7b,0xbf67bf46,0x3f713f35,0xbf5c3dc9,0x3e16bf55,0x3f2c3f75,0xbf3ebf6d,0x3f7d3e95,0xbf043f0e,0xbeacbf7f,0x3edb3f80,0xbf78bf22,0x3f4ebe48,0xbd493f62,
 0xbeacbf80,0x3f5c3f46,0xbf7dbe48,0x3f2cbef1,0xbd493f6d,0xbf18bf75,0x3f783f0e,0xbf673dc9,0x3edbbf35,0x3e793f7f,0xbf4ebf55,0x3f803e95,0xbf3e3ec4,0x3e16bf62,0x3f043f7b,0xbf71bf22,
 0xbf710000,0x3f04bf22,0x3e163f7b,0xbf3ebf62,0x3f803ec4,0xbf4e3e95,0x3e79bf55,0x3edb3f7f,0xbf67bf35,0x3f783dc9,0xbf183f0e,0xbd49bf75,0x3f2c3f6d,0xbf7dbef1,0x3f5cbe48,0xbeac3f46,
 0x3f4ebec4,0xbedb3f46,0xbd49bf7b,0x3f043f75,0x3e793f80,0xbf2cbf62,0x3f713f0e,0xbf7dbdc9,0xbe163f6d,0xbeacbf7f,0x3f3e3f55,0xbf78bef1,0xbf5cbf35,0x3f803e95,0xbf673e48,0x3f18bf22,
 0x3f183f6d,0xbf67bf22,0x3f803e48,0xbf5c3e95,0xbf780000,0x3f3ebef1,0xbeac3f55,0xbe16bf7f,0xbf7dbec4,0x3f71bdc9,0xbf2c3f0e,0x3e79bf62,0x3f04bf35,0xbd493f75,0xbedbbf7b,0x3f4e3f46,
 0xbf183f35,0x3eacbf62,0xbd493f7b,0xbe79bf7f,0x3f043f6d,0xbf3ebf46,0x3f673f0e,0xbf7dbe95,0xbe16bf80,0x3edb3f75,0xbf2cbf55,0x3f5c3f22,0xbf78bec4,0x3f803dc9,0xbf713e48,0x3f4ebef1,
 0x3f4e3f35,0xbf71bef1,0x3f803e48,0xbf783dc9,0x3f5cbec4,0xbf2c3f22,0x3edbbf55,0xbe163f75,0xbf7d0000,0x3f67be95,0xbf3e3f0e,0x3f04bf46,0xbe793f6d,0xbd49bf7f,0x3eac3f7b,0xbf18bf62,
 0x3f713ec4,0xbf78be95,0x3f7d3e48,0xbf80bdc9,0x3f3e3f35,0xbf4ebf22,0x3f5c3f0e,0xbf67bef1,0x3edb3f6d,0xbf04bf62,0x3f183f55,0xbf2cbf46,0x3d493f80,0xbe16bf7f,0x3e793f7b,0xbeacbf75,
 0xbeac3f6d,0x3e79bf75,0xbe163f7b,0x3d49bf7f,0xbf2c3f35,0x3f18bf46,0xbf043f55,0x3edbbf62,0xbf673ec4,0x3f5cbef1,0xbf4e3f0e,0x3f3ebf22,0xbf800000,0x3f7dbdc9,0xbf783e48,0x3f71be95,
 0xbd493f80,0x3e16bf7f,0xbe793f7b,0x3eacbf75,0xbedb3f6d,0x3f04bf62,0xbf183f55,0x3f2cbf46,0xbf3e3f35,0x3f4ebf22,0xbf5c3f0e,0x3f67bef1,0xbf713ec4,0x3f78be95,0xbf7d3e48,0x3f80bdc9,
 0xbf800000,0x3f7d3dc9,0xbf78be48,0x3f713e95,0xbf67bec4,0x3f5c3ef1,0xbf4ebf0e,0x3f3e3f22,0xbf2cbf35,0x3f183f46,0xbf04bf55,0x3edb3f62,0xbeacbf6d,0x3e793f75,0xbe16bf7b,0x3d493f7f,
 0xbf783ec4,0x3f80bdc9,0xbf71be48,0x3f4e3ef1,0xbe163f80,0x3edbbf75,0xbf2c3f55,0x3f5cbf22,0x3f04bf6d,0xbf3e3f46,0x3f67bf0e,0xbf7d3e95,0xbf18bf35,0x3eac3f62,0xbd49bf7b,0xbe793f7f,
 0x3e793f6d,0x3d49bf7f,0xbeac3f7b,0x3f18bf62,0x3f7d0000,0xbf67be95,0x3f3e3f0e,0xbf04bf46,0xbf5cbec4,0x3f2c3f22,0xbedbbf55,0x3e163f75,0xbf4e3f35,0x3f71bef1,0xbf803e48,0x3f783dc9,
 0x3f5cbf35,0xbf803e95,0x3f673e48,0xbf18bf22,0x3e163f6d,0x3eacbf7f,0xbf3e3f55,0x3f78bef1,0xbe793f80,0x3f2cbf62,0xbf713f0e,0x3f7dbdc9,0xbf4ebec4,0x3edb3f46,0x3d49bf7b,0xbf043f75,
 0x3f043f35,0xbd49bf75,0xbedb3f7b,0x3f4ebf46,0xbf7d3ec4,0x3f713dc9,0xbf2cbf0e,0x3e793f62,0xbf780000,0x3f3e3ef1,0xbeacbf55,0xbe163f7f,0x3f18bf6d,0xbf673f22,0x3f80be48,0xbf5cbe95,
 0xbf3ebec4,0x3e163f62,0x3f04bf7b,0xbf713f22,0x3edb3f35,0x3e79bf7f,0xbf4e3f55,0x3f80be95,0xbd49bf6d,0xbf183f75,0x3f78bf0e,0xbf67bdc9,0xbeac3f80,0x3f5cbf46,0xbf7d3e48,0x3f2c3ef1,
 0xbf2c3f6d,0x3f7dbef1,0xbf5cbe48,0x3eac3f46,0x3f67bf35,0xbf783dc9,0x3f183f0e,0x3d49bf75,0xbf803ec4,0x3f4e3e95,0xbe79bf55,0xbedb3f7f,0x3f710000,0xbf04bf22,0xbe163f7b,0x3f3ebf62,
 0xbf670000,0x3e793f46,0x3f18bf7b,0xbf803ef1,0x3f2c3ec4,0x3e16bf75,0xbf5c3f55,0x3f71bdc9,0xbeacbf35,0xbf043f7f,0x3f7dbf0e,0xbf3ebe95,0xbd493f6d,0x3f4ebf62,0xbf783e48,0x3edb3f22,
 0xbedb3f80,0x3f78bf22,0xbf4ebe48,0x3d493f62,0x3f3ebf6d,0xbf7d3e95,0x3f043f0e,0x3eacbf7f,0xbf713f35,0x3f5c3dc9,0xbe16bf55,0xbf2c3f75,0x3f80bec4,0xbf18bef1,0xbe793f7b,0x3f67bf46,
 0x3e16bf6d,0xbf713f46,0x3f3e3e48,0x3e79bf75,0x3f5c0000,0x3d49bf62,0xbf673f55,0x3f4e3dc9,0x3f183ec4,0x3edbbf7f,0xbf803f0e,0x3f043ef1,0xbf783f35,0x3f2c3e95,0x3eacbf7b,0xbf7d3f22,
 0x3f7dbec4,0xbeacbf22,0xbf2c3f7b,0x3f78be95,0xbf043f80,0x3f80bef1,0xbedbbf0e,0xbf183f7f,0xbf4e3f6d,0x3f67bdc9,0xbd49bf55,0xbf5c3f62,0xbe79bf35,0xbf3e3f75,0x3f71be48,0xbe16bf46,
 0x3e163f35,0x3f67bf62,0xbf2cbe48,0xbf043f7f,0x3f78bec4,0xbd49bf46,0xbf713f55,0x3f183e95,0xbf4e0000,0xbeac3f75,0x3f80bf0e,0xbe79bf22,0xbf5c3f6d,0x3f3e3dc9,0x3edbbf7b,0xbf7d3ef1,
 0x3f7dbf35,0xbedbbef1,0xbf3e3f7b,0x3f5cbdc9,0x3e79bf6d,0xbf803f22,0x3eac3f0e,0x3f4ebf75,0xbf183f80,0x3f71be95,0x3d49bf55,0xbf783f46,0x3f043ec4,0x3f2cbf7f,0xbf673e48,0xbe163f62,
 0x3f67bf6d,0xbf04be95,0xbf4e3f7b,0x3f2c3dc9,0x3f80bf35,0xbe16bf22,0xbf783f55,0x3eac3ef1,0x3f71bec4,0x3e79bf62,0xbf7d3f0e,0xbd493f46,0x3f3e0000,0x3f18bf7f,0xbf5c3e48,0xbedb3f75,
 0x3edb3ec4,0x3f5cbf75,0xbf18be48,0xbf3e3f7f,0x3d493f35,0x3f7dbf46,0xbe79bf0e,0xbf713f62,0xbeac3f6d,0x3f78bef1,0x3e16bf55,0xbf803f22,0xbf2c3f80,0x3f4ebdc9,0x3f04bf7b,0xbf673e95,
 0xbf800000,0x3f7d3dc9,0xbf78be48,0x3f713e95,0xbf67bec4,0x3f5c3ef1,0xbf4ebf0e,0x3f3e3f22,0xbf2cbf35,0x3f183f46,0xbf04bf55,0x3edb3f62,0xbeacbf6d,0x3e793f75,0xbe16bf7b,0x3d493f7f,
 0x3d49bf80,0xbe163f7f,0x3e79bf7b,0xbeac3f75,0x3edbbf6d,0xbf043f62,0x3f18bf55,0xbf2c3f46,0x3f3ebf35,0xbf4e3f22,0x3f5cbf0e,0xbf673ef1,0x3f71bec4,0xbf783e95,0x3f7dbe48,0xbf803dc9,
 0xbe79bf6d,0xbd493f7f,0x3eacbf7b,0xbf183f62,0xbf7d0000,0x3f673e95,0xbf3ebf0e,0x3f043f46,0x3f5c3ec4,0xbf2cbf22,0x3edb3f55,0xbe16bf75,0x3f4ebf35,0xbf713ef1,0x3f80be48,0xbf78bdc9,
 0xbf783ec4,0x3f80bdc9,0xbf71be48,0x3f4e3ef1,0xbe163f80,0x3edbbf75,0xbf2c3f55,0x3f5cbf22,0x3f04bf6d,0xbf3e3f46,0x3f67bf0e,0xbf7d3e95,0xbf18bf35,0x3eac3f62,0xbd49bf7b,0xbe793f7f,
 0x3f043f35,0xbd49bf75,0xbedb3f7b,0x3f4ebf46,0xbf7d3ec4,0x3f713dc9,0xbf2cbf0e,0x3e793f62,0xbf780000,0x3f3e3ef1,0xbeacbf55,0xbe163f7f,0x3f18bf6d,0xbf673f22,0x3f80be48,0xbf5cbe95,
 0xbf5c3f35,0x3f80be95,0xbf67be48,0x3f183f22,0xbe16bf6d,0xbeac3f7f,0x3f3ebf55,0xbf783ef1,0x3e79bf80,0xbf2c3f62,0x3f71bf0e,0xbf7d3dc9,0x3f4e3ec4,0xbedbbf46,0xbd493f7b,0x3f04bf75,
 0x3f2cbf6d,0xbf7d3ef1,0x3f5c3e48,0xbeacbf46,0xbf673f35,0x3f78bdc9,0xbf18bf0e,0xbd493f75,0x3f80bec4,0xbf4ebe95,0x3e793f55,0x3edbbf7f,0xbf710000,0x3f043f22,0x3e16bf7b,0xbf3e3f62,
 0xbf3ebec4,0x3e163f62,0x3f04bf7b,0xbf713f22,0x3edb3f35,0x3e79bf7f,0xbf4e3f55,0x3f80be95,0xbd49bf6d,0xbf183f75,0x3f78bf0e,0xbf67bdc9,0xbeac3f80,0x3f5cbf46,0xbf7d3e48,0x3f2c3ef1,
 0x3edbbf80,0xbf783f22,0x3f4e3e48,0xbd49bf62,0xbf3e3f6d,0x3f7dbe95,0xbf04bf0e,0xbeac3f7f,0x3f71bf35,0xbf5cbdc9,0x3e163f55,0x3f2cbf75,0xbf803ec4,0x3f183ef1,0x3e79bf7b,0xbf673f46,
 0xbf670000,0x3e793f46,0x3f18bf7b,0xbf803ef1,0x3f2c3ec4,0x3e16bf75,0xbf5c3f55,0x3f71bdc9,0xbeacbf35,0xbf043f7f,0x3f7dbf0e,0xbf3ebe95,0xbd493f6d,0x3f4ebf62,0xbf783e48,0x3edb3f22,
 0x3f7dbec4,0xbeacbf22,0xbf2c3f7b,0x3f78be95,0xbf043f80,0x3f80bef1,0xbedbbf0e,0xbf183f7f,0xbf4e3f6d,0x3f67bdc9,0xbd49bf55,0xbf5c3f62,0xbe79bf35,0xbf3e3f75,0x3f71be48,0xbe16bf46,
 0xbe163f6d,0x3f71bf46,0xbf3ebe48,0xbe793f75,0xbf5c0000,0xbd493f62,0x3f67bf55,0xbf4ebdc9,0xbf18bec4,0xbedb3f7f,0x3f80bf0e,0xbf04bef1,0x3f78bf35,0xbf2cbe95,0xbeac3f7b,0x3f7dbf22,
 0xbf7d3f35,0x3edb3ef1,0x3f3ebf7b,0xbf5c3dc9,0xbe793f6d,0x3f80bf22,0xbeacbf0e,0xbf4e3f75,0x3f18bf80,0xbf713e95,0xbd493f55,0x3f78bf46,0xbf04bec4,0xbf2c3f7f,0x3f67be48,0x3e16bf62,
 0x3e163f35,0x3f67bf62,0xbf2cbe48,0xbf043f7f,0x3f78bec4,0xbd49bf46,0xbf713f55,0x3f183e95,0xbf4e0000,0xbeac3f75,0x3f80bf0e,0xbe79bf22,0xbf5c3f6d,0x3f3e3dc9,0x3edbbf7b,0xbf7d3ef1,
 0x3edb3ec4,0x3f5cbf75,0xbf18be48,0xbf3e3f7f,0x3d493f35,0x3f7dbf46,0xbe79bf0e,0xbf713f62,0xbeac3f6d,0x3f78bef1,0x3e16bf55,0xbf803f22,0xbf2c3f80,0x3f4ebdc9,0x3f04bf7b,0xbf673e95,
 0xbf673f6d,0x3f043e95,0x3f4ebf7b,0xbf2cbdc9,0xbf803f35,0x3e163f22,0x3f78bf55,0xbeacbef1,0xbf713ec4,0xbe793f62,0x3f7dbf0e,0x3d49bf46,0xbf3e0000,0xbf183f7f,0x3f5cbe48,0x3edbbf75,
 0xbf3e3f80,0x3f183dc9,0x3f5cbf7b,0xbedbbe95,0xbf713f6d,0x3e793ef1,0x3f7dbf55,0xbd49bf22,0xbf803f35,0xbe163f46,0x3f78bf0e,0x3eacbf62,0xbf673ec4,0xbf043f75,0x3f4ebe48,0x3f2cbf7f,
 0xbf2c0000,0xbf4e3f7f,0x3f043e48,0x3f67bf75,0xbeacbec4,0xbf783f62,0x3e163f0e,0x3f80bf46,0x3d49bf35,0xbf7d3f22,0xbe793f55,0x3f71bef1,0x3edbbf6d,0xbf5c3e95,0xbf183f7b,0x3f3ebdc9,
 0xbf5c3ec4,0xbf3e3f7f,0x3edb3e48,0x3f7dbf62,0xbf4e3f80,0x3eac3e95,0x3f80bf55,0x3e79bf46,0x3f78bf6d,0x3d49bf22,0xbf713f0e,0xbf183f75,0x3e16bf35,0xbf673ef1,0xbf2c3f7b,0x3f043dc9,
 0xbf043f6d,0x3f2cbdc9,0x3f67bf7b,0xbe16bef1,0x3f180000,0x3f71bf75,0xbd49bf0e,0xbf783f22,0xbe79bec4,0xbf803f46,0xbeac3f55,0x3f4ebe95,0xbf7d3f35,0xbedb3f62,0x3f3ebe48,0x3f5cbf7f,
 0x3f78bf35,0x3f2cbf75,0xbeacbe48,0xbf7d3f46,0xbf183f6d,0x3edb3dc9,0x3f80bf55,0x3f04bf62,0xbf5c3f80,0x3d493ef1,0x3f67bf0e,0x3f4ebf7f,0xbe16bec4,0xbf713f22,0xbf3e3f7b,0x3e793e95,
 0xbe793f35,0x3f3ebe95,0x3f71bf7b,0x3e16bf22,0xbf4e3ec4,0xbf673f7f,0xbd493f0e,0x3f5cbef1,0xbf040000,0xbf803f62,0xbedb3f55,0x3f18bdc9,0x3f7dbf6d,0x3eacbf46,0xbf2c3e48,0xbf783f75,
 0xbd49bec4,0xbf4e3ef1,0xbf783f7b,0xbedb3f46,0xbeac3f35,0x3f04bdc9,0x3f7dbf55,0x3f3ebf75,0x3f2cbf6d,0xbe16be95,0xbf5c3f0e,0xbf713f7f,0xbf673f80,0xbe793f22,0x3f18be48,0x3f80bf62,
 0xbf803f6d,0xbf183f62,0x3e793e48,0x3f67bf22,0x3f71bf35,0x3f5cbf7f,0x3e16bf0e,0xbf2c3e95,0xbf3e3ec4,0xbf7d3f75,0xbf043f55,0x3eac3dc9,0x3edb0000,0x3f78bf46,0x3f4ebf7b,0x3d49bef1,
 0xbeac0000,0xbf5c3f22,0xbf7d3f7b,0xbf2c3f62,0xbd493ec4,0x3f18be95,0x3f78bf55,0x3f67bf7f,0x3edbbf35,0xbe79bdc9,0xbf4e3f0e,0xbf803f75,0xbf3e3f6d,0xbe163ef1,0x3f04be48,0x3f71bf46,
 0xbf713f80,0xbf043f46,0x3e163e48,0x3f3ebef1,0x3f80bf6d,0x3f4ebf75,0x3e79bf0e,0xbedb3dc9,0xbf673f35,0xbf783f7f,0xbf183f55,0x3d493e95,0x3f2cbec4,0x3f7dbf62,0x3f5cbf7b,0x3eacbf22,
 0x3f4ebf6d,0x3edbbf22,0xbd49be48,0xbf043e95,0x3e790000,0x3f2cbef1,0x3f71bf55,0x3f7dbf7f,0xbe163ec4,0x3eacbdc9,0x3f3ebf0e,0x3f78bf62,0xbf5c3f35,0xbf803f75,0xbf673f7b,0xbf183f46,
 0x3f18bec4,0x3f67bf46,0x3f80bf7b,0x3f5cbf75,0xbf783f80,0xbf3e3f62,0xbeac3f0e,0x3e163dc9,0xbf7d3f6d,0xbf713f7f,0xbf2c3f55,0xbe793ef1,0x3f04bf35,0x3d49be95,0xbedb3e48,0xbf4e3f22,
 0xbf183f35,0xbeac3ef1,0xbd493e48,0x3e79bdc9,0x3f04bec4,0x3f3ebf22,0x3f67bf55,0x3f7dbf75,0xbe160000,0xbedb3e95,0xbf2c3f0e,0xbf5c3f46,0xbf783f6d,0xbf803f7f,0xbf713f7b,0xbf4e3f62,
 0x3f4ebf35,0x3f71bf62,0x3f80bf7b,0x3f78bf7f,0x3f5cbf6d,0x3f2cbf46,0x3edbbf0e,0x3e16be95,0xbf7d3f80,0xbf673f75,0xbf3e3f55,0xbf043f22,0xbe793ec4,0x3d493dc9,0x3eacbe48,0x3f18bef1,
 0x3f71bf6d,0x3f78bf75,0x3f7dbf7b,0x3f80bf7f,0x3f3ebf35,0x3f4ebf46,0x3f5cbf55,0x3f67bf62,0x3edbbec4,0x3f04bef1,0x3f18bf0e,0x3f2cbf22,0x3d490000,0x3e16bdc9,0x3e79be48,0x3eacbe95,
 0xbeac3ec4,0xbe793e95,0xbe163e48,0xbd493dc9,0xbf2c3f35,0xbf183f22,0xbf043f0e,0xbedb3ef1,0xbf673f6d,0xbf5c3f62,0xbf4e3f55,0xbf3e3f46,0xbf803f80,0xbf7d3f7f,0xbf783f7b,0xbf713f75,
 0xbf2c0000,0xbf4e3f7f,0x3f043e48,0x3f67bf75,0xbeacbec4,0xbf783f62,0x3e163f0e,0x3f80bf46,0x3d49bf35,0xbf7d3f22,0xbe793f55,0x3f71bef1,0x3edbbf6d,0xbf5c3e95,0xbf183f7b,0x3f3ebdc9,
 0x3f3ebf80,0xbf18bdc9,0xbf5c3f7b,0x3edb3e95,0x3f71bf6d,0xbe79bef1,0xbf7d3f55,0x3d493f22,0x3f80bf35,0x3e16bf46,0xbf783f0e,0xbeac3f62,0x3f67bec4,0x3f04bf75,0xbf4e3e48,0xbf2c3f7f,
 0x3f04bf6d,0xbf2c3dc9,0xbf673f7b,0x3e163ef1,0xbf180000,0xbf713f75,0x3d493f0e,0x3f78bf22,0x3e793ec4,0x3f80bf46,0x3eacbf55,0xbf4e3e95,0x3f7dbf35,0x3edbbf62,0xbf3e3e48,0xbf5c3f7f,
 0xbf5c3ec4,0xbf3e3f7f,0x3edb3e48,0x3f7dbf62,0xbf4e3f80,0x3eac3e95,0x3f80bf55,0x3e79bf46,0x3f78bf6d,0x3d49bf22,0xbf713f0e,0xbf183f75,0x3e16bf35,0xbf673ef1,0xbf2c3f7b,0x3f043dc9,
 0xbe793f35,0x3f3ebe95,0x3f71bf7b,0x3e16bf22,0xbf4e3ec4,0xbf673f7f,0xbd493f0e,0x3f5cbef1,0xbf040000,0xbf803f62,0xbedb3f55,0x3f18bdc9,0x3f7dbf6d,0x3eacbf46,0xbf2c3e48,0xbf783f75,
 0xbf783f35,0xbf2c3f75,0x3eac3e48,0x3f7dbf46,0x3f18bf6d,0xbedbbdc9,0xbf803f55,0xbf043f62,0x3f5cbf80,0xbd49bef1,0xbf673f0e,0xbf4e3f7f,0x3e163ec4,0x3f71bf22,0x3f3ebf7b,0xbe79be95,
 0x3f80bf6d,0x3f18bf62,0xbe79be48,0xbf673f22,0xbf713f35,0xbf5c3f7f,0xbe163f0e,0x3f2cbe95,0x3f3ebec4,0x3f7dbf75,0x3f04bf55,0xbeacbdc9,0xbedb0000,0xbf783f46,0xbf4e3f7b,0xbd493ef1,
 0xbd49bec4,0xbf4e3ef1,0xbf783f7b,0xbedb3f46,0xbeac3f35,0x3f04bdc9,0x3f7dbf55,0x3f3ebf75,0x3f2cbf6d,0xbe16be95,0xbf5c3f0e,0xbf713f7f,0xbf673f80,0xbe793f22,0x3f18be48,0x3f80bf62,
 0x3f71bf80,0x3f04bf46,0xbe16be48,0xbf3e3ef1,0xbf803f6d,0xbf4e3f75,0xbe793f0e,0x3edbbdc9,0x3f67bf35,0x3f78bf7f,0x3f18bf55,0xbd49be95,0xbf2c3ec4,0xbf7d3f62,0xbf5c3f7b,0xbeac3f22,
 0xbeac0000,0xbf5c3f22,0xbf7d3f7b,0xbf2c3f62,0xbd493ec4,0x3f18be95,0x3f78bf55,0x3f67bf7f,0x3edbbf35,0xbe79bdc9,0xbf4e3f0e,0xbf803f75,0xbf3e3f6d,0xbe163ef1,0x3f04be48,0x3f71bf46,
 0x3f18bec4,0x3f67bf46,0x3f80bf7b,0x3f5cbf75,0xbf783f80,0xbf3e3f62,0xbeac3f0e,0x3e163dc9,0xbf7d3f6d,0xbf713f7f,0xbf2c3f55,0xbe793ef1,0x3f04bf35,0x3d49be95,0xbedb3e48,0xbf4e3f22,
 0xbf4e3f6d,0xbedb3f22,0x3d493e48,0x3f04be95,0xbe790000,0xbf2c3ef1,0xbf713f55,0xbf7d3f7f,0x3e16bec4,0xbeac3dc9,0xbf3e3f0e,0xbf783f62,0x3f5cbf35,0x3f80bf75,0x3f67bf7b,0x3f18bf46,
 0xbf4e3f35,0xbf713f62,0xbf803f7b,0xbf783f7f,0xbf5c3f6d,0xbf2c3f46,0xbedb3f0e,0xbe163e95,0x3f7dbf80,0x3f67bf75,0x3f3ebf55,0x3f04bf22,0x3e79bec4,0xbd49bdc9,0xbeac3e48,0xbf183ef1,
 0xbf183f35,0xbeac3ef1,0xbd493e48,0x3e79bdc9,0x3f04bec4,0x3f3ebf22,0x3f67bf55,0x3f7dbf75,0xbe160000,0xbedb3e95,0xbf2c3f0e,0xbf5c3f46,0xbf783f6d,0xbf803f7f,0xbf713f7b,0xbf4e3f62,
 0xbeac3ec4,0xbe793e95,0xbe163e48,0xbd493dc9,0xbf2c3f35,0xbf183f22,0xbf043f0e,0xbedb3ef1,0xbf673f6d,0xbf5c3f62,0xbf4e3f55,0xbf3e3f46,0xbf803f80,0xbf7d3f7f,0xbf783f7b,0xbf713f75,
 0xbf713f6d,0xbf783f75,0xbf7d3f7b,0xbf803f7f,0xbf3e3f35,0xbf4e3f46,0xbf5c3f55,0xbf673f62,0xbedb3ec4,0xbf043ef1,0xbf183f0e,0xbf2c3f22,0xbd490000,0xbe163dc9,0xbe793e48,0xbeac3e95,
};
__device__ __align__(128) const uint32_t g_Gimg[1792] = {
 0x00003d00,0x00003d00,0x00003d00,0x00003d00,0x00003d00,0x00003d00,0x00003d00,0x00003d00,0x00003d00,0x00003d00,0x00003d00,0x00003d00,0x00003d00,0x00003d00,0x00003d00,0x00003d00,
 0x00003d00,0x00003d00,0x00003d00,0x00003d00,0x00003d00,0x00003d00,0x00003d00,0x00003d00,0x00003d00,0x00003d00,0x00003d00,0x00003d00,0x00003d00,0x00003d00,0x00003d00,0x00003d00,
 0xbc5b3ce7,0xbc843cdc,0xbc983cce,0xbcac3cbe,0xbac93d00,0xbb963cfd,0xbbf93cf8,0xbc2c3cf1,0xbcf13c2c,0xbcf83bf9,0xbcfd3b96,0xbd003ac9,0xbcbe3cac,0xbcce3c98,0xbcdc3c84,0xbce73c5b,
 0xbce7bc5b,0xbcdcbc84,0xbccebc98,0xbcbebcac,0xbd00bac9,0xbcfdbb96,0xbcf8bbf9,0xbcf1bc2c,0xbc2cbcf1,0xbbf9bcf8,0xbb96bcfd,0xbac9bd00,0xbcacbcbe,0xbc98bcce,0xbc84bcdc,0xbc5bbce7,
 0xbcffbb49,0xbcf5bc15,0xbce2bc71,0xbcc6bca2,0xbca2bcc6,0xbc71bce2,0xbc15bcf5,0xbb49bcff,0xbb493cff,0xbc153cf5,0xbc713ce2,0xbca23cc6,0xbcc63ca2,0xbce23c71,0xbcf53c15,0xbcff3b49,
 0x3cff3b49,0x3cf53c15,0x3ce23c71,0x3cc63ca2,0x3ca23cc6,0x3c713ce2,0x3c153cf5,0x3b493cff,0x3b49bcff,0x3c15bcf5,0x3c71bce2,0x3ca2bcc6,0x3cc6bca2,0x3ce2bc71,0x3cf5bc15,0x3cffbb49,
 0x3c84bcdc,0x3cbebcac,0x3ce7bc5b,0x3cfdbb96,0xbc98bcce,0xbc2cbcf1,0xbac9bd00,0x3bf9bcf8,0xbcf83bf9,0xbd00bac9,0xbcf1bc2c,0xbccebc98,0xbb963cfd,0xbc5b3ce7,0xbcac3cbe,0xbcdc3c84,
 0xbcdcbc84,0xbcacbcbe,0xbc5bbce7,0xbb96bcfd,0xbcce3c98,0xbcf13c2c,0xbd003ac9,0xbcf8bbf9,0x3bf93cf8,0xbac93d00,0xbc2c3cf1,0xbc983cce,0x3cfd3b96,0x3ce73c5b,0x3cbe3cac,0x3c843cdc,
 0xbbc83cfb,0xbc8e3cd5,0xbcd53c8e,0xbcfb3bc8,0xbcfbbbc8,0xbcd5bc8e,0xbc8ebcd5,0xbbc8bcfb,0x3bc8bcfb,0x3c8ebcd5,0x3cd5bc8e,0x3cfbbbc8,0x3cfb3bc8,0x3cd53c8e,0x3c8e3cd5,0x3bc83cfb,
 0xbbc83cfb,0xbc8e3cd5,0xbcd53c8e,0xbcfb3bc8,0xbcfbbbc8,0xbcd5bc8e,0xbc8ebcd5,0xbbc8bcfb,0x3bc8bcfb,0x3c8ebcd5,0x3cd5bc8e,0x3cfbbbc8,0x3cfb3bc8,0x3cd53c8e,0x3c8e3cd5,0x3bc83cfb,
 0x3c98bcce,0x3ce7bc5b,0x3d003ac9,0x3cdc3c84,0xbcf8bbf9,0xbcbebcac,0xbc2cbcf1,0x3b96bcfd,0xbcfd3b96,0xbcf1bc2c,0xbcacbcbe,0xbbf9bcf8,0x3c843cdc,0x3ac93d00,0xbc5b3ce7,0xbcce3c98,
 0xbccebc98,0xbc5bbce7,0x3ac9bd00,0x3c84bcdc,0xbbf93cf8,0xbcac3cbe,0xbcf13c2c,0xbcfdbb96,0x3b963cfd,0xbc2c3cf1,0xbcbe3cac,0xbcf83bf9,0x3cdcbc84,0x3d00bac9,0x3ce73c5b,0x3c983cce,
 0xbcf5bc15,0xbca2bcc6,0xbb49bcff,0x3c71bce2,0x3ce2bc71,0x3cff3b49,0x3cc63ca2,0x3c153cf5,0x3c15bcf5,0x3cc6bca2,0x3cffbb49,0x3ce23c71,0x3c713ce2,0xbb493cff,0xbca23cc6,0xbcf53c15,
 0x3cf53c15,0x3ca23cc6,0x3b493cff,0xbc713ce2,0xbce23c71,0xbcffbb49,0xbcc6bca2,0xbc15bcf5,0xbc153cf5,0xbcc63ca2,0xbcff3b49,0xbce2bc71,0xbc71bce2,0x3b49bcff,0x3ca2bcc6,0x3cf5bc15,
 0xbcac3cbe,0xbcfd3b96,0xbcdcbc84,0xbc2cbcf1,0x3ce7bc5b,0x3cf83bf9,0x3c983cce,0xbac93d00,0xbd003ac9,0xbccebc98,0xbbf9bcf8,0x3c5bbce7,0x3cf13c2c,0x3c843cdc,0xbb963cfd,0xbcbe3cac,
 0xbcbebcac,0xbb96bcfd,0x3c84bcdc,0x3cf1bc2c,0x3c5b3ce7,0xbbf93cf8,0xbcce3c98,0xbd00bac9,0xbac9bd00,0x3c98bcce,0x3cf8bbf9,0x3ce73c5b,0xbc2c3cf1,0xbcdc3c84,0xbcfdbb96,0xbcacbcbe,
 0xbc443ced,0xbced3c44,0xbcedbc44,0xbc44bced,0x3c44bced,0x3cedbc44,0x3ced3c44,0x3c443ced,0xbc443ced,0xbced3c44,0xbcedbc44,0xbc44bced,0x3c44bced,0x3cedbc44,0x3ced3c44,0x3c443ced,
 0xbc443ced,0xbced3c44,0xbcedbc44,0xbc44bced,0x3c44bced,0x3cedbc44,0x3ced3c44,0x3c443ced,0xbc443ced,0xbced3c44,0xbcedbc44,0xbc44bced,0x3c44bced,0x3cedbc44,0x3ced3c44,0x3c443ced,
 0x3cbebcac,0x3cfd3b96,0x3c843cdc,0xbc2c3cf1,0xbc5b3ce7,0xbcf83bf9,0xbccebc98,0xbac9bd00,0x3d003ac9,0x3c983cce,0xbbf93cf8,0xbce73c5b,0xbcf13c2c,0xbcdcbc84,0xbb96bcfd,0x3cacbcbe,
 0x3cac3cbe,0xbb963cfd,0xbcdc3c84,0xbcf1bc2c,0xbce7bc5b,0xbbf9bcf8,0x3c98bcce,0x3d00bac9,0xbac93d00,0xbcce3c98,0xbcf8bbf9,0xbc5bbce7,0xbc2cbcf1,0x3c84bcdc,0x3cfdbb96,0x3cbe3cac,
 0xbce2bc71,0xbb49bcff,0x3cc6bca2,0x3cf53c15,0x3c153cf5,0xbca23cc6,0xbcffbb49,0xbc71bce2,0xbc713ce2,0xbcff3b49,0xbca2bcc6,0x3c15bcf5,0x3cf5bc15,0x3cc63ca2,0xbb493cff,0xbce23c71,
 0x3ce23c71,0x3b493cff,0xbcc63ca2,0xbcf5bc15,0xbc15bcf5,0x3ca2bcc6,0x3cff3b49,0x3c713ce2,0x3c71bce2,0x3cffbb49,0x3ca23cc6,0xbc153cf5,0xbcf53c15,0xbcc6bca2,0x3b49bcff,0x3ce2bc71,
 0xbcce3c98,0xbce7bc5b,0xbac9bd00,0x3cdcbc84,0xbbf9bcf8,0x3cbebcac,0x3cf13c2c,0x3b963cfd,0x3cfd3b96,0x3c2c3cf1,0xbcac3cbe,0xbcf8bbf9,0xbc843cdc,0xbd00bac9,0xbc5bbce7,0x3c98bcce,
 0x3c983cce,0xbc5b3ce7,0xbd003ac9,0xbc84bcdc,0xbcf83bf9,0xbcacbcbe,0x3c2cbcf1,0x3cfdbb96,0x3b96bcfd,0x3cf1bc2c,0x3cbe3cac,0xbbf93cf8,0x3cdc3c84,0xbac93d00,0xbce73c5b,0xbccebc98,
 0xbc8e3cd5,0xbcfbbbc8,0xbbc8bcfb,0x3cd5bc8e,0x3cd53c8e,0xbbc83cfb,0xbcfb3bc8,0xbc8ebcd5,0x3c8ebcd5,0x3cfb3bc8,0x3bc83cfb,0xbcd53c8e,0xbcd5bc8e,0x3bc8bcfb,0x3cfbbbc8,0x3c8e3cd5,
 0xbc8e3cd5,0xbcfbbbc8,0xbbc8bcfb,0x3cd5bc8e,0x3cd53c8e,0xbbc83cfb,0xbcfb3bc8,0xbc8ebcd5,0x3c8ebcd5,0x3cfb3bc8,0x3bc83cfb,0xbcd53c8e,0xbcd5bc8e,0x3bc8bcfb,0x3cfbbbc8,0x3c8e3cd5,
 0xbcdc3c84,0xbcbebcac,0x3c5bbce7,0x3cfd3b96,0xbccebc98,0x3c2cbcf1,0x3d003ac9,0x3bf93cf8,0x3cf83bf9,0x3ac93d00,0xbcf13c2c,0xbc98bcce,0x3b963cfd,0xbce73c5b,0xbcacbcbe,0x3c84bcdc,
 0x3c843cdc,0xbcac3cbe,0xbce7bc5b,0x3b96bcfd,0xbc983cce,0xbcf1bc2c,0x3ac9bd00,0x3cf8bbf9,0x3bf9bcf8,0x3d00bac9,0x3c2c3cf1,0xbcce3c98,0x3cfdbb96,0x3c5b3ce7,0xbcbe3cac,0xbcdcbc84,
 0xbcc6bca2,0x3c71bce2,0x3cf53c15,0xbb493cff,0xbcff3b49,0xbc15bcf5,0x3ce2bc71,0x3ca23cc6,0x3ca2bcc6,0x3ce23c71,0xbc153cf5,0xbcffbb49,0xbb49bcff,0x3cf5bc15,0x3c713ce2,0xbcc63ca2,
 0x3cc63ca2,0xbc713ce2,0xbcf5bc15,0x3b49bcff,0x3cffbb49,0x3c153cf5,0xbce23c71,0xbca2bcc6,0xbca23cc6,0xbce2bc71,0x3c15bcf5,0x3cff3b49,0x3b493cff,0xbcf53c15,0xbc71bce2,0x3cc6bca2,
 0x3ce7bc5b,0x3c843cdc,0xbcce3c98,0xbcacbcbe,0x3d00bac9,0x3b963cfd,0xbcf83bf9,0xbc2cbcf1,0x3cf13c2c,0xbbf93cf8,0xbcfdbb96,0x3ac9bd00,0x3cbe3cac,0xbc983cce,0xbcdcbc84,0x3c5bbce7,
 0x3c5b3ce7,0xbcdc3c84,0xbc98bcce,0x3cbebcac,0x3ac93d00,0xbcfd3b96,0xbbf9bcf8,0x3cf1bc2c,0xbc2c3cf1,0xbcf8bbf9,0x3b96bcfd,0x3d003ac9,0xbcac3cbe,0xbccebc98,0x3c84bcdc,0x3ce73c5b,
 0xbcb53cb5,0xbcb5bcb5,0x3cb5bcb5,0x3cb53cb5,0xbcb53cb5,0xbcb5bcb5,0x3cb5bcb5,0x3cb53cb5,0xbcb53cb5,0xbcb5bcb5,0x3cb5bcb5,0x3cb53cb5,0xbcb53cb5,0xbcb5bcb5,0x3cb5bcb5,0x3cb53cb5,
 0xbcb53cb5,0xbcb5bcb5,0x3cb5bcb5,0x3cb53cb5,0xbcb53cb5,0xbcb5bcb5,0x3cb5bcb5,0x3cb53cb5,0xbcb53cb5,0xbcb5bcb5,0x3cb5bcb5,0x3cb53cb5,0xbcb53cb5,0xbcb5bcb5,0x3cb5bcb5,0x3cb53cb5,
 0xbcf13c2c,0xbbf9bcf8,0x3cfdbb96,0x3ac93d00,0xbcbe3cac,0xbc98bcce,0x3cdcbc84,0x3c5b3ce7,0xbce7bc5b,0x3c84bcdc,0x3cce3c98,0xbcac3cbe,0xbd00bac9,0x3b96bcfd,0x3cf83bf9,0xbc2c3cf1,
 0xbc2cbcf1,0x3cf8bbf9,0x3b963cfd,0xbd003ac9,0xbcacbcbe,0x3ccebc98,0x3c843cdc,0xbce73c5b,0x3c5bbce7,0x3cdc3c84,0xbc983cce,0xbcbebcac,0x3ac9bd00,0x3cfd3b96,0xbbf93cf8,0xbcf1bc2c,
 0xbca2bcc6,0x3ce2bc71,0x3c153cf5,0xbcff3b49,0x3b49bcff,0x3cf53c15,0xbc713ce2,0xbcc6bca2,0xbcc63ca2,0xbc71bce2,0x3cf5bc15,0x3b493cff,0xbcffbb49,0x3c15bcf5,0x3ce23c71,0xbca23cc6,
 0x3ca23cc6,0xbce23c71,0xbc15bcf5,0x3cffbb49,0xbb493cff,0xbcf5bc15,0x3c71bce2,0x3cc63ca2,0x3cc6bca2,0x3c713ce2,0xbcf53c15,0xbb49bcff,0x3cff3b49,0xbc153cf5,0xbce2bc71,0x3ca2bcc6,
 0x3cf8bbf9,0xbac93d00,0xbcf1bc2c,0x3c98bcce,0x3b96bcfd,0x3ce73c5b,0xbcac3cbe,0xbc84bcdc,0xbcdcbc84,0x3cbebcac,0x3c5b3ce7,0xbcfd3b96,0xbcce3c98,0xbc2cbcf1,0x3d00bac9,0xbbf93cf8,
 0xbbf9bcf8,0x3d003ac9,0xbc2c3cf1,0xbccebc98,0xbcfdbb96,0x3c5bbce7,0x3cbe3cac,0xbcdc3c84,0xbc843cdc,0xbcacbcbe,0x3ce7bc5b,0x3b963cfd,0x3c983cce,0xbcf13c2c,0xbac9bd00,0x3cf83bf9,
 0xbcd53c8e,0xbbc8bcfb,0x3cfb3bc8,0xbc8e3cd5,0xbc8ebcd5,0x3cfbbbc8,0xbbc83cfb,0xbcd5bc8e,0x3cd5bc8e,0x3bc83cfb,0xbcfbbbc8,0x3c8ebcd5,0x3c8e3cd5,0xbcfb3bc8,0x3bc8bcfb,0x3cd53c8e,
 0xbcd53c8e,0xbbc8bcfb,0x3cfb3bc8,0xbc8e3cd5,0xbc8ebcd5,0x3cfbbbc8,0xbbc83cfb,0xbcd5bc8e,0x3cd5bc8e,0x3bc83cfb,0xbcfbbbc8,0x3c8ebcd5,0x3c8e3cd5,0xbcfb3bc8,0x3bc8bcfb,0x3cd53c8e,
 0x3cfdbb96,0xbc2c3cf1,0xbcacbcbe,0x3cf8bbf9,0xbc84bcdc,0x3d00bac9,0xbc5b3ce7,0xbc98bcce,0xbccebc98,0x3ce7bc5b,0xbac93d00,0xbcdcbc84,0xbbf93cf8,0xbcbebcac,0x3cf1bc2c,0xbb963cfd,
 0xbb96bcfd,0x3cf13c2c,0xbcbe3cac,0xbbf9bcf8,0xbcdc3c84,0xbac9bd00,0x3ce73c5b,0xbcce3c98,0xbc983cce,0xbc5bbce7,0x3d003ac9,0xbc843cdc,0x3cf83bf9,0xbcac3cbe,0xbc2cbcf1,0x3cfd3b96,
 0xbc71bce2,0x3cff3b49,0xbca23cc6,0xbc15bcf5,0x3cf53c15,0xbcc63ca2,0xbb49bcff,0x3ce23c71,0x3ce2bc71,0xbb493cff,0xbcc6bca2,0x3cf5bc15,0xbc153cf5,0xbca2bcc6,0x3cffbb49,0xbc713ce2,
 0x3c713ce2,0xbcffbb49,0x3ca2bcc6,0x3c153cf5,0xbcf5bc15,0x3cc6bca2,0x3b493cff,0xbce2bc71,0xbce23c71,0x3b49bcff,0x3cc63ca2,0xbcf53c15,0x3c15bcf5,0x3ca23cc6,0xbcff3b49,0x3c71bce2,
 0xbd003ac9,0x3c98bcce,0x3bf93cf8,0xbce7bc5b,0x3cf13c2c,0xbcdc3c84,0x3b96bcfd,0x3cac3cbe,0xbcbebcac,0x3cfdbb96,0xbc843cdc,0xbc2cbcf1,0x3c5b3ce7,0xbcf8bbf9,0x3ccebc98,0xbac93d00,
 0xbac9bd00,0x3cce3c98,0xbcf83bf9,0x3c5bbce7,0xbc2c3cf1,0xbc84bcdc,0x3cfd3b96,0xbcbe3cac,0x3cacbcbe,0x3b963cfd,0xbcdcbc84,0x3cf1bc2c,0xbce73c5b,0x3bf9bcf8,0x3c983cce,0xbd00bac9,
 0xbced3c44,0x3c44bced,0x3c443ced,0xbcedbc44,0x3cedbc44,0xbc443ced,0xbc44bced,0x3ced3c44,0xbced3c44,0x3c44bced,0x3c443ced,0xbcedbc44,0x3cedbc44,0xbc443ced,0xbc44bced,0x3ced3c44,
 0xbced3c44,0x3c44bced,0x3c443ced,0xbcedbc44,0x3cedbc44,0xbc443ced,0xbc44bced,0x3ced3c44,0xbced3c44,0x3c44bced,0x3c443ced,0xbcedbc44,0x3cedbc44,0xbc443ced,0xbc44bced,0x3ced3c44,
 0x3d003ac9,0xbcce3c98,0x3bf9bcf8,0x3c5b3ce7,0xbcf13c2c,0x3c84bcdc,0x3b963cfd,0xbcbebcac,0x3cac3cbe,0xbcfdbb96,0x3cdcbc84,0xbc2c3cf1,0xbce7bc5b,0x3cf8bbf9,0xbc983cce,0xbac9bd00,
 0xbac93d00,0xbc98bcce,0x3cf83bf9,0xbce73c5b,0xbc2cbcf1,0x3cdc3c84,0xbcfd3b96,0x3cacbcbe,0xbcbe3cac,0x3b96bcfd,0x3c843cdc,0xbcf1bc2c,0x3c5bbce7,0x3bf93cf8,0xbccebc98,0x3d00bac9,
 0xbc15bcf5,0x3cc63ca2,0xbcffbb49,0x3ce2bc71,0xbc713ce2,0xbb49bcff,0x3ca23cc6,0xbcf5bc15,0xbcf53c15,0x3ca2bcc6,0xbb493cff,0xbc71bce2,0x3ce23c71,0xbcff3b49,0x3cc6bca2,0xbc153cf5,
 0x3c153cf5,0xbcc6bca2,0x3cff3b49,0xbce23c71,0x3c71bce2,0x3b493cff,0xbca2bcc6,0x3cf53c15,0x3cf5bc15,0xbca23cc6,0x3b49bcff,0x3c713ce2,0xbce2bc71,0x3cffbb49,0xbcc63ca2,0x3c15bcf5,
 0xbcfdbb96,0x3cf1bc2c,0xbcac3cbe,0x3bf9bcf8,0x3c84bcdc,0xbac93d00,0xbc5bbce7,0x3cce3c98,0x3c983cce,0xbce7bc5b,0x3d00bac9,0xbcdc3c84,0xbcf83bf9,0x3cbebcac,0xbc2c3cf1,0xbb96bcfd,
 0xbb963cfd,0xbc2cbcf1,0x3cbe3cac,0xbcf8bbf9,0xbcdcbc84,0x3d003ac9,0xbce73c5b,0x3c98bcce,0x3ccebc98,0xbc5b3ce7,0xbac9bd00,0x3c843cdc,0x3bf93cf8,0xbcacbcbe,0x3cf13c2c,0xbcfd3b96,
 0xbcfb3bc8,0x3cd5bc8e,0xbc8e3cd5,0x3bc8bcfb,0x3bc83cfb,0xbc8ebcd5,0x3cd53c8e,0xbcfbbbc8,0x3cfbbbc8,0xbcd53c8e,0x3c8ebcd5,0xbbc83cfb,0xbbc8bcfb,0x3c8e3cd5,0xbcd5bc8e,0x3cfb3bc8,
 0xbcfb3bc8,0x3cd5bc8e,0xbc8e3cd5,0x3bc8bcfb,0x3bc83cfb,0xbc8ebcd5,0x3cd53c8e,0xbcfbbbc8,0x3cfbbbc8,0xbcd53c8e,0x3c8ebcd5,0xbbc83cfb,0xbbc8bcfb,0x3c8e3cd5,0xbcd5bc8e,0x3cfb3bc8,
 0xbcf8bbf9,0x3d00bac9,0xbcf13c2c,0x3ccebc98,0xbb96bcfd,0x3c5b3ce7,0xbcacbcbe,0x3cdc3c84,0x3c843cdc,0xbcbebcac,0x3ce73c5b,0xbcfdbb96,0xbc983cce,0x3c2cbcf1,0xbac93d00,0xbbf9bcf8,
 0xbbf93cf8,0xbac9bd00,0x3c2c3cf1,0xbc98bcce,0xbcfd3b96,0x3ce7bc5b,0xbcbe3cac,0x3c84bcdc,0x3cdcbc84,0xbcac3cbe,0x3c5bbce7,0xbb963cfd,0x3cce3c98,0xbcf1bc2c,0x3d003ac9,0xbcf83bf9,
 0xbb49bcff,0x3c153cf5,0xbc71bce2,0x3ca23cc6,0xbcc6bca2,0x3ce23c71,0xbcf5bc15,0x3cff3b49,0x3cffbb49,0xbcf53c15,0x3ce2bc71,0xbcc63ca2,0x3ca2bcc6,0xbc713ce2,0x3c15bcf5,0xbb493cff,
 0x3b493cff,0xbc15bcf5,0x3c713ce2,0xbca2bcc6,0x3cc63ca2,0xbce2bc71,0x3cf53c15,0xbcffbb49,0xbcff3b49,0x3cf5bc15,0xbce23c71,0x3cc6bca2,0xbca23cc6,0x3c71bce2,0xbc153cf5,0x3b49bcff,
 0x3cf13c2c,0xbcf8bbf9,0x3cfd3b96,0xbd00bac9,0x3cbe3cac,0xbccebc98,0x3cdc3c84,0xbce7bc5b,0x3c5b3ce7,0xbc84bcdc,0x3c983cce,0xbcacbcbe,0x3ac93d00,0xbb96bcfd,0x3bf93cf8,0xbc2cbcf1,
 0xbc2c3cf1,0x3bf9bcf8,0xbb963cfd,0x3ac9bd00,0xbcac3cbe,0x3c98bcce,0xbc843cdc,0x3c5bbce7,0xbce73c5b,0x3cdcbc84,0xbcce3c98,0x3cbebcac,0xbd003ac9,0x3cfdbb96,0xbcf83bf9,0x3cf1bc2c,
 0xbd000000,0x3d000000,0xbd000000,0x3d000000,0xbd000000,0x3d000000,0xbd000000,0x3d000000,0xbd000000,0x3d000000,0xbd000000,0x3d000000,0xbd000000,0x3d000000,0xbd000000,0x3d000000,
 0xbd000000,0x3d000000,0xbd000000,0x3d000000,0xbd000000,0x3d000000,0xbd000000,0x3d000000,0xbd000000,0x3d000000,0xbd000000,0x3d000000,0xbd000000,0x3d000000,0xbd000000,0x3d000000,
 0xbce7bc5b,0x3cdc3c84,0xbccebc98,0x3cbe3cac,0xbd00bac9,0x3cfd3b96,0xbcf8bbf9,0x3cf13c2c,0xbc2cbcf1,0x3bf93cf8,0xbb96bcfd,0x3ac93d00,0xbcacbcbe,0x3c983cce,0xbc84bcdc,0x3c5b3ce7,
 0x3c5bbce7,0xbc843cdc,0x3c98bcce,0xbcac3cbe,0x3ac9bd00,0xbb963cfd,0x3bf9bcf8,0xbc2c3cf1,0x3cf1bc2c,0xbcf83bf9,0x3cfdbb96,0xbd003ac9,0x3cbebcac,0xbcce3c98,0x3cdcbc84,0xbce73c5b,
 0x3b49bcff,0xbc153cf5,0x3c71bce2,0xbca23cc6,0x3cc6bca2,0xbce23c71,0x3cf5bc15,0xbcff3b49,0xbcffbb49,0x3cf53c15,0xbce2bc71,0x3cc63ca2,0xbca2bcc6,0x3c713ce2,0xbc15bcf5,0x3b493cff,
 0xbb493cff,0x3c15bcf5,0xbc713ce2,0x3ca2bcc6,0xbcc63ca2,0x3ce2bc71,0xbcf53c15,0x3cffbb49,0x3cff3b49,0xbcf5bc15,0x3ce23c71,0xbcc6bca2,0x3ca23cc6,0xbc71bce2,0x3c153cf5,0xbb49bcff,
 0x3cdc3c84,0xbcacbcbe,0x3c5b3ce7,0xbb96bcfd,0x3ccebc98,0xbcf13c2c,0x3d00bac9,0xbcf8bbf9,0xbbf9bcf8,0xbac93d00,0x3c2cbcf1,0xbc983cce,0xbcfdbb96,0x3ce73c5b,0xbcbebcac,0x3c843cdc,
 0x3c84bcdc,0xbcbe3cac,0x3ce7bc5b,0xbcfd3b96,0xbc98bcce,0x3c2c3cf1,0xbac9bd00,0xbbf93cf8,0xbcf83bf9,0x3d003ac9,0xbcf1bc2c,0x3cce3c98,0xbb963cfd,0x3c5bbce7,0xbcac3cbe,0x3cdcbc84,
 0xbcfbbbc8,0x3cd53c8e,0xbc8ebcd5,0x3bc83cfb,0x3bc8bcfb,0xbc8e3cd5,0x3cd5bc8e,0xbcfb3bc8,0x3cfb3bc8,0xbcd5bc8e,0x3c8e3cd5,0xbbc8bcfb,0xbbc83cfb,0x3c8ebcd5,0xbcd53c8e,0x3cfbbbc8,
 0xbcfbbbc8,0x3cd53c8e,0xbc8ebcd5,0x3bc83cfb,0x3bc8bcfb,0xbc8e3cd5,0x3cd5bc8e,0xbcfb3bc8,0x3cfb3bc8,0xbcd5bc8e,0x3c8e3cd5,0xbbc8bcfb,0xbbc83cfb,0x3c8ebcd5,0xbcd53c8e,0x3cfbbbc8,
 0x3cce3c98,0xbc5bbce7,0xbac93d00,0x3c84bcdc,0x3bf9bcf8,0xbcac3cbe,0x3cf1bc2c,0xbcfdbb96,0xbb96bcfd,0xbc2c3cf1,0x3cbebcac,0xbcf83bf9,0xbcdc3c84,0x3d00bac9,0xbce7bc5b,0x3c983cce,
 0x3c98bcce,0xbce73c5b,0x3d003ac9,0xbcdcbc84,0xbcf8bbf9,0x3cbe3cac,0xbc2cbcf1,0xbb963cfd,0xbcfd3b96,0x3cf13c2c,0xbcacbcbe,0x3bf93cf8,0x3c843cdc,0xbac9bd00,0xbc5b3ce7,0x3ccebc98,
 0x3c15bcf5,0xbcc63ca2,0x3cffbb49,0xbce2bc71,0x3c713ce2,0x3b49bcff,0xbca23cc6,0x3cf5bc15,0x3cf53c15,0xbca2bcc6,0x3b493cff,0x3c71bce2,0xbce23c71,0x3cff3b49,0xbcc6bca2,0x3c153cf5,
 0xbc153cf5,0x3cc6bca2,0xbcff3b49,0x3ce23c71,0xbc71bce2,0xbb493cff,0x3ca2bcc6,0xbcf53c15,0xbcf5bc15,0x3ca23cc6,0xbb49bcff,0xbc713ce2,0x3ce2bc71,0xbcffbb49,0x3cc63ca2,0xbc15bcf5,
 0xbcbebcac,0x3b963cfd,0x3c84bcdc,0xbcf13c2c,0x3c5b3ce7,0x3bf9bcf8,0xbcce3c98,0x3d003ac9,0xbac9bd00,0xbc983cce,0x3cf8bbf9,0xbce7bc5b,0xbc2c3cf1,0x3cdcbc84,0xbcfdbb96,0x3cac3cbe,
 0x3cacbcbe,0xbcfd3b96,0x3cdc3c84,0xbc2cbcf1,0xbce73c5b,0x3cf83bf9,0xbc98bcce,0xbac93d00,0x3d00bac9,0xbccebc98,0x3bf93cf8,0x3c5bbce7,0xbcf1bc2c,0x3c843cdc,0x3b96bcfd,0xbcbe3cac,
 0xbcedbc44,0x3c443ced,0x3c44bced,0xbced3c44,0x3ced3c44,0xbc44bced,0xbc443ced,0x3cedbc44,0xbcedbc44,0x3c443ced,0x3c44bced,0xbced3c44,0x3ced3c44,0xbc44bced,0xbc443ced,0x3cedbc44,
 0xbcedbc44,0x3c443ced,0x3c44bced,0xbced3c44,0x3ced3c44,0xbc44bced,0xbc443ced,0x3cedbc44,0xbcedbc44,0x3c443ced,0x3c44bced,0xbced3c44,0x3ced3c44,0xbc44bced,0xbc443ced,0x3cedbc44,
 0x3cac3cbe,0x3b96bcfd,0xbcdc3c84,0x3cf13c2c,0xbce7bc5b,0x3bf93cf8,0x3c98bcce,0xbd003ac9,0xbac93d00,0x3ccebc98,0xbcf8bbf9,0x3c5b3ce7,0xbc2cbcf1,0xbc843cdc,0x3cfdbb96,0xbcbebcac,
 0xbcbe3cac,0x3cfd3b96,0xbc84bcdc,0xbc2c3cf1,0x3c5bbce7,0xbcf83bf9,0x3cce3c98,0xbac9bd00,0xbd00bac9,0x3c983cce,0x3bf9bcf8,0xbce73c5b,0x3cf1bc2c,0xbcdcbc84,0x3b963cfd,0x3cacbcbe,
 0x3c71bce2,0xbcff3b49,0x3ca23cc6,0x3c15bcf5,0xbcf53c15,0x3cc63ca2,0x3b49bcff,0xbce23c71,0xbce2bc71,0x3b493cff,0x3cc6bca2,0xbcf5bc15,0x3c153cf5,0x3ca2bcc6,0xbcffbb49,0x3c713ce2,
 0xbc713ce2,0x3cffbb49,0xbca2bcc6,0xbc153cf5,0x3cf5bc15,0xbcc6bca2,0xbb493cff,0x3ce2bc71,0x3ce23c71,0xbb49bcff,0xbcc63ca2,0x3cf53c15,0xbc15bcf5,0xbca23cc6,0x3cff3b49,0xbc71bce2,
 0xbc98bcce,0xbc5b3ce7,0x3d00bac9,0xbc84bcdc,0x3cf8bbf9,0xbcacbcbe,0xbc2c3cf1,0x3cfdbb96,0xbb963cfd,0x3cf1bc2c,0xbcbebcac,0xbbf93cf8,0xbcdcbc84,0xbac93d00,0x3ce7bc5b,0xbccebc98,
 0xbcce3c98,0x3ce73c5b,0xbac9bd00,0xbcdc3c84,0xbbf9bcf8,0xbcbe3cac,0x3cf13c2c,0xbb96bcfd,0x3cfd3b96,0xbc2cbcf1,0xbcac3cbe,0x3cf83bf9,0xbc843cdc,0x3d003ac9,0xbc5bbce7,0xbc983cce,
 0xbcd5bc8e,0xbbc83cfb,0x3cfbbbc8,0xbc8ebcd5,0xbc8e3cd5,0x3cfb3bc8,0xbbc8bcfb,0xbcd53c8e,0x3cd53c8e,0x3bc8bcfb,0xbcfb3bc8,0x3c8e3cd5,0x3c8ebcd5,0xbcfbbbc8,0x3bc83cfb,0x3cd5bc8e,
 0xbcd5bc8e,0xbbc83cfb,0x3cfbbbc8,0xbc8ebcd5,0xbc8e3cd5,0x3cfb3bc8,0xbbc8bcfb,0xbcd53c8e,0x3cd53c8e,0x3bc8bcfb,0xbcfb3bc8,0x3c8e3cd5,0x3c8ebcd5,0xbcfbbbc8,0x3bc83cfb,0x3cd5bc8e,
 0xbc84bcdc,0xbcac3cbe,0x3ce73c5b,0x3b96bcfd,0x3c98bcce,0xbcf1bc2c,0xbac93d00,0x3cf8bbf9,0xbbf93cf8,0x3d00bac9,0xbc2cbcf1,0xbcce3c98,0xbcfd3b96,0x3c5b3ce7,0x3cbebcac,0xbcdcbc84,
 0xbcdc3c84,0x3cbe3cac,0x3c5bbce7,0xbcfdbb96,0xbccebc98,0xbc2c3cf1,0x3d003ac9,0xbbf9bcf8,0x3cf83bf9,0xbac9bd00,0xbcf13c2c,0x3c983cce,0x3b963cfd,0x3ce7bc5b,0xbcacbcbe,0xbc843cdc,
 0x3ca2bcc6,0xbce2bc71,0xbc153cf5,0x3cff3b49,0xbb49bcff,0xbcf53c15,0x3c713ce2,0x3cc6bca2,0x3cc63ca2,0x3c71bce2,0xbcf5bc15,0xbb493cff,0x3cffbb49,0xbc15bcf5,0xbce23c71,0x3ca23cc6,
 0xbca23cc6,0x3ce23c71,0x3c15bcf5,0xbcffbb49,0x3b493cff,0x3cf5bc15,0xbc71bce2,0xbcc63ca2,0xbcc6bca2,0xbc713ce2,0x3cf53c15,0x3b49bcff,0xbcff3b49,0x3c153cf5,0x3ce2bc71,0xbca2bcc6,
 0x3c5b3ce7,0x3cdcbc84,0xbc98bcce,0xbcbe3cac,0x3ac93d00,0x3cfdbb96,0xbbf9bcf8,0xbcf13c2c,0xbc2c3cf1,0x3cf83bf9,0x3b96bcfd,0xbd00bac9,0xbcac3cbe,0x3cce3c98,0x3c84bcdc,0xbce7bc5b,
 0xbce73c5b,0x3c843cdc,0x3ccebc98,0xbcacbcbe,0xbd003ac9,0x3b963cfd,0x3cf8bbf9,0xbc2cbcf1,0xbcf1bc2c,0xbbf93cf8,0x3cfd3b96,0x3ac9bd00,0xbcbebcac,0xbc983cce,0x3cdc3c84,0x3c5bbce7,
 0xbcb5bcb5,0xbcb53cb5,0x3cb53cb5,0x3cb5bcb5,0xbcb5bcb5,0xbcb53cb5,0x3cb53cb5,0x3cb5bcb5,0xbcb5bcb5,0xbcb53cb5,0x3cb53cb5,0x3cb5bcb5,0xbcb5bcb5,0xbcb53cb5,0x3cb53cb5,0x3cb5bcb5,
 0xbcb5bcb5,0xbcb53cb5,0x3cb53cb5,0x3cb5bcb5,0xbcb5bcb5,0xbcb53cb5,0x3cb53cb5,0x3cb5bcb5,0xbcb5bcb5,0xbcb53cb5,0x3cb53cb5,0x3cb5bcb5,0xbcb5bcb5,0xbcb53cb5,0x3cb53cb5,0x3cb5bcb5,
 0xbc2cbcf1,0xbcf83bf9,0x3b963cfd,0x3d00bac9,0xbcacbcbe,0xbcce3c98,0x3c843cdc,0x3ce7bc5b,0x3c5bbce7,0xbcdcbc84,0xbc983cce,0x3cbe3cac,0x3ac9bd00,0xbcfdbb96,0xbbf93cf8,0x3cf13c2c,
 0x3cf1bc2c,0xbbf9bcf8,0xbcfd3b96,0x3ac93d00,0x3cbebcac,0xbc98bcce,0xbcdc3c84,0x3c5b3ce7,0x3ce73c5b,0x3c84bcdc,0xbccebc98,0xbcac3cbe,0x3d003ac9,0x3b96bcfd,0xbcf8bbf9,0xbc2c3cf1,
 0x00000000,0x00000000,0x00000000,0x00000000,0x00000000,0x00000000,0x00000000,0x00000000,0x00000000,0x00000000,0x00000000,0x00000000,0x00000000,0x00000000,0x00000000,0x00000000,
 0x00000000,0x00000000,0x00000000,0x00000000,0x00000000,0x00000000,0x00000000,0x00000000,0x00000000,0x00000000,0x00000000,0x00000000,0x00000000,0x00000000,0x00000000,0x00000000,
 0x00000000,0x00000000,0x00000000,0x00000000,0x00000000,0x00000000,0x00000000,0x00000000,0x00000000,0x00000000,0x00000000,0x00000000,0x00000000,0x00000000,0x00000000,0x00000000,
 0x00000000,0x00000000,0x00000000,0x00000000,0x00000000,0x00000000,0x00000000,0x00000000,0x00000000,0x00000000,0x00000000,0x00000000,0x00000000,0x00000000,0x00000000,0x00000000,
 0x00000000,0x00000000,0x00000000,0x00000000,0x00000000,0x00000000,0x00000000,0x00000000,0x00000000,0x00000000,0x00000000,0x00000000,0x00000000,0x00000000,0x00000000,0x00000000,
 0x00000000,0x00000000,0x00000000,0x00000000,0x00000000,0x00000000,0x00000000,0x00000000,0x00000000,0x00000000,0x00000000,0x00000000,0x00000000,0x00000000,0x00000000,0x00000000,
 0x00000000,0x00000000,0x00000000,0x00000000,0x00000000,0x00000000,0x00000000,0x00000000,0x00000000,0x00000000,0x00000000,0x00000000,0x00000000,0x00000000,0x00000000,0x00000000,
 0x00000000,0x00000000,0x00000000,0x00000000,0x00000000,0x00000000,0x00000000,0x00000000,0x00000000,0x00000000,0x00000000,0x00000000,0x00000000,0x00000000,0x00000000,0x00000000,
 0x00000000,0x00000000,0x00000000,0x00000000,0x00000000,0x00000000,0x00000000,0x00000000,0x00000000,0x00000000,0x00000000,0x00000000,0x00000000,0x00000000,0x00000000,0x00000000,
 0x00000000,0x00000000,0x00000000,0x00000000,0x00000000,0x00000000,0x00000000,0x00000000,0x00000000,0x00000000,0x00000000,0x00000000,0x00000000,0x00000000,0x00000000,0x00000000,
 0x00000000,0x00000000,0x00000000,0x00000000,0x00000000,0x00000000,0x00000000,0x00000000,0x00000000,0x00000000,0x00000000,0x00000000,0x00000000,0x00000000,0x00000000,0x00000000,
 0x00000000,0x00000000,0x00000000,0x00000000,0x00000000,0x00000000,0x00000000,0x00000000,0x00000000,0x00000000,0x00000000,0x00000000,0x00000000,0x00000000,0x00000000,0x00000000,
};

template<int SA>
__device__ __forceinline__ void wgmma_main(float (&d)[80], uint64_t da, uint64_t db, int sd) {
  asm volatile("{\n.reg .pred p;\nsetp.ne.b32 p, %82, 0;\n"
    "wgmma.mma_async.sync.aligned.m64n160k16.f32.bf16.bf16 "
    "{%0, %1, %2, %3, %4, %5, %6, %7, %8, %9, %10, %11, %12, %13, %14, %15, %16, %17, %18, %19, %20, %21, %22, %23, %24, %25, %26, %27, %28, %29, %30, %31, %32, %33, %34, %35, %36, %37, %38, %39, %40, %41, %42, %43, %44, %45, %46, %47, %48, %49, %50, %51, %52, %53, %54, %55, %56, %57, %58, %59, %60, %61, %62, %63, %64, %65, %66, %67, %68, %69, %70, %71, %72, %73, %74, %75, %76, %77, %78, %79}, %80, %81, p, %83, 1, 1, 0;\n}\n"
    : "+f"(d[0]), "+f"(d[1]), "+f"(d[2]), "+f"(d[3]), "+f"(d[4]), "+f"(d[5]), "+f"(d[6]), "+f"(d[7]), "+f"(d[8]), "+f"(d[9]), "+f"(d[10]), "+f"(d[11]), "+f"(d[12]), "+f"(d[13]), "+f"(d[14]), "+f"(d[15]), "+f"(d[16]), "+f"(d[17]), "+f"(d[18]), "+f"(d[19]), "+f"(d[20]), "+f"(d[21]), "+f"(d[22]), "+f"(d[23]), "+f"(d[24]), "+f"(d[25]), "+f"(d[26]), "+f"(d[27]), "+f"(d[28]), "+f"(d[29]), "+f"(d[30]), "+f"(d[31]), "+f"(d[32]), "+f"(d[33]), "+f"(d[34]), "+f"(d[35]), "+f"(d[36]), "+f"(d[37]), "+f"(d[38]), "+f"(d[39]), "+f"(d[40]), "+f"(d[41]), "+f"(d[42]), "+f"(d[43]), "+f"(d[44]), "+f"(d[45]), "+f"(d[46]), "+f"(d[47]), "+f"(d[48]), "+f"(d[49]), "+f"(d[50]), "+f"(d[51]), "+f"(d[52]), "+f"(d[53]), "+f"(d[54]), "+f"(d[55]), "+f"(d[56]), "+f"(d[57]), "+f"(d[58]), "+f"(d[59]), "+f"(d[60]), "+f"(d[61]), "+f"(d[62]), "+f"(d[63]), "+f"(d[64]), "+f"(d[65]), "+f"(d[66]), "+f"(d[67]), "+f"(d[68]), "+f"(d[69]), "+f"(d[70]), "+f"(d[71]), "+f"(d[72]), "+f"(d[73]), "+f"(d[74]), "+f"(d[75]), "+f"(d[76]), "+f"(d[77]), "+f"(d[78]), "+f"(d[79])
    : "l"(da), "l"(db), "r"(sd), "n"(SA));
}
template<int SA>
__device__ __forceinline__ void wgmma_fwd(float (&d)[32], uint64_t da, uint64_t db, int sd) {
  asm volatile("{\n.reg .pred p;\nsetp.ne.b32 p, %34, 0;\n"
    "wgmma.mma_async.sync.aligned.m64n64k16.f32.bf16.bf16 "
    "{%0, %1, %2, %3, %4, %5, %6, %7, %8, %9, %10, %11, %12, %13, %14, %15, %16, %17, %18, %19, %20, %21, %22, %23, %24, %25, %26, %27, %28, %29, %30, %31}, %32, %33, p, %35, 1, 0, 1;\n}\n"
    : "+f"(d[0]), "+f"(d[1]), "+f"(d[2]), "+f"(d[3]), "+f"(d[4]), "+f"(d[5]), "+f"(d[6]), "+f"(d[7]), "+f"(d[8]), "+f"(d[9]), "+f"(d[10]), "+f"(d[11]), "+f"(d[12]), "+f"(d[13]), "+f"(d[14]), "+f"(d[15]), "+f"(d[16]), "+f"(d[17]), "+f"(d[18]), "+f"(d[19]), "+f"(d[20]), "+f"(d[21]), "+f"(d[22]), "+f"(d[23]), "+f"(d[24]), "+f"(d[25]), "+f"(d[26]), "+f"(d[27]), "+f"(d[28]), "+f"(d[29]), "+f"(d[30]), "+f"(d[31])
    : "l"(da), "l"(db), "r"(sd), "n"(SA));
}
template<int SA>
__device__ __forceinline__ void wgmma_inv(float (&d)[28], uint64_t da, uint64_t db, int sd) {
  asm volatile("{\n.reg .pred p;\nsetp.ne.b32 p, %30, 0;\n"
    "wgmma.mma_async.sync.aligned.m64n56k16.f32.bf16.bf16 "
    "{%0, %1, %2, %3, %4, %5, %6, %7, %8, %9, %10, %11, %12, %13, %14, %15, %16, %17, %18, %19, %20, %21, %22, %23, %24, %25, %26, %27}, %28, %29, p, %31, 1, 1, 0;\n}\n"
    : "+f"(d[0]), "+f"(d[1]), "+f"(d[2]), "+f"(d[3]), "+f"(d[4]), "+f"(d[5]), "+f"(d[6]), "+f"(d[7]), "+f"(d[8]), "+f"(d[9]), "+f"(d[10]), "+f"(d[11]), "+f"(d[12]), "+f"(d[13]), "+f"(d[14]), "+f"(d[15]), "+f"(d[16]), "+f"(d[17]), "+f"(d[18]), "+f"(d[19]), "+f"(d[20]), "+f"(d[21]), "+f"(d[22]), "+f"(d[23]), "+f"(d[24]), "+f"(d[25]), "+f"(d[26]), "+f"(d[27])
    : "l"(da), "l"(db), "r"(sd), "n"(SA));
}

__device__ __forceinline__ uint32_t s2u(const void* p) { return (uint32_t)__cvta_generic_to_shared(p); }
__device__ __forceinline__ void mbar_init(uint32_t a, int c) { asm volatile("mbarrier.init.shared::cta.b64 [%0], %1;" ::"r"(a), "r"(c)); }
__device__ __forceinline__ void mbar_expect(uint32_t a, int b) { asm volatile("mbarrier.arrive.expect_tx.shared::cta.b64 _, [%0], %1;" ::"r"(a), "r"(b) : "memory"); }
__device__ __forceinline__ void mbar_arrive(uint32_t a) { asm volatile("mbarrier.arrive.shared::cta.b64 _, [%0];" ::"r"(a) : "memory"); }
__device__ __forceinline__ void mbar_arrive_cluster(uint32_t a, uint32_t cta, uint32_t cnt) {
  asm volatile("{\n.reg .b32 r;\nmapa.shared::cluster.u32 r, %0, %1;\nmbarrier.arrive.shared::cluster.b64 _, [r], %2;\n}" ::"r"(a), "r"(cta), "r"(cnt) : "memory");
}
__device__ __forceinline__ void mbar_wait(uint32_t a, int ph) {
  asm volatile("{\n.reg .pred p;\n.reg .u32 c;\nmov.u32 c, 0;\nWAIT:\n"
               "mbarrier.try_wait.parity.shared::cta.b64 p, [%0], %1;\n@p bra DONE;\n"
               "add.u32 c, c, 1;\nsetp.lt.u32 p, c, 0x400000;\n@p bra WAIT;\ntrap;\nDONE:\n}" ::"r"(a), "r"(ph) : "memory");
}
__device__ __forceinline__ void flag_wait(const unsigned* p, unsigned target) {
  asm volatile("{\n.reg .pred p;\n.reg .u32 c, v;\nmov.u32 c, 0;\nWAIT:\n"
               "ld.acquire.gpu.global.u32 v, [%0];\nsetp.ge.u32 p, v, %1;\n@p bra DONE;\n"
               "add.u32 c, c, 1;\nsetp.lt.u32 p, c, 0x400000;\n@p bra WAIT;\ntrap;\nDONE:\n}" ::"l"(p), "r"(target) : "memory");
}
__device__ __forceinline__ bool elect_one() {
  uint32_t p;
  asm volatile("{\n.reg .pred P;\nelect.sync _|P, 0xffffffff;\nselp.u32 %0, 1, 0, P;\n}" : "=r"(p));
  return p != 0;
}
__device__ __forceinline__ void bulk_ld(uint32_t dst, const void* src, int bytes, uint32_t bar) {
  asm volatile("cp.async.bulk.shared::cluster.global.mbarrier::complete_tx::bytes [%0], [%1], %2, [%3];" ::"r"(dst), "l"(src), "r"(bytes), "r"(bar) : "memory");
}
__device__ __forceinline__ void bulk_ld_mc_h(uint32_t dst, const void* src, int bytes, uint32_t bar, uint16_t mask, uint64_t pol) {
  asm volatile("cp.async.bulk.shared::cluster.global.mbarrier::complete_tx::bytes.multicast::cluster.L2::cache_hint [%0], [%1], %2, [%3], %4, %5;" ::"r"(dst), "l"(src), "r"(bytes), "r"(bar), "h"(mask), "l"(pol) : "memory");
}
__device__ __forceinline__ void tma_ld2(uint32_t dst, const CUtensorMap* tm, int c0, int c1, uint32_t bar) {
  asm volatile("cp.async.bulk.tensor.2d.shared::cluster.global.mbarrier::complete_tx::bytes [%0], [%1, {%3,%4}], [%2];" ::"r"(dst), "l"(tm), "r"(bar), "r"(c0), "r"(c1) : "memory");
}
__device__ __forceinline__ void tma_ld3(uint32_t dst, const CUtensorMap* tm, int c0, int c1, int c2, uint32_t bar) {
  asm volatile("cp.async.bulk.tensor.3d.shared::cluster.global.mbarrier::complete_tx::bytes [%0], [%1, {%3,%4,%5}], [%2];" ::"r"(dst), "l"(tm), "r"(bar), "r"(c0), "r"(c1), "r"(c2) : "memory");
}
__device__ __forceinline__ void tma_ld3h(uint32_t dst, const CUtensorMap* tm, int c0, int c1, int c2, uint32_t bar, uint64_t pol) {
  asm volatile("cp.async.bulk.tensor.3d.shared::cluster.global.mbarrier::complete_tx::bytes.L2::cache_hint [%0], [%1, {%3,%4,%5}], [%2], %6;" ::"r"(dst), "l"(tm), "r"(bar), "r"(c0), "r"(c1), "r"(c2), "l"(pol) : "memory");
}
__device__ __forceinline__ uint64_t policy_evict_first() {
  uint64_t p;
  asm("createpolicy.fractional.L2::evict_first.b64 %0, 1.0;" : "=l"(p));
  return p;
}
__device__ __forceinline__ void tma_st3(const CUtensorMap* tm, uint32_t src, int c0, int c1, int c2) {
  asm volatile("cp.async.bulk.tensor.3d.global.shared::cta.bulk_group [%0, {%2,%3,%4}], [%1];" ::"l"(tm), "r"(src), "r"(c0), "r"(c1), "r"(c2) : "memory");
}
__device__ __forceinline__ void tma_st4(const CUtensorMap* tm, uint32_t src, int c0, int c1, int c2, int c3) {
  asm volatile("cp.async.bulk.tensor.4d.global.shared::cta.bulk_group [%0, {%2,%3,%4,%5}], [%1];" ::"l"(tm), "r"(src), "r"(c0), "r"(c1), "r"(c2), "r"(c3) : "memory");
}
__device__ __forceinline__ void tma_st5(const CUtensorMap* tm, uint32_t src, int c0) {
  asm volatile("cp.async.bulk.tensor.5d.global.shared::cta.bulk_group [%0, {%2,%3,%3,%3,%3}], [%1];" ::"l"(tm), "r"(src), "r"(c0), "r"(0) : "memory");
}
__device__ __forceinline__ void bulk_commit() { asm volatile("cp.async.bulk.commit_group;" ::: "memory"); }
template <int N> __device__ __forceinline__ void bulk_wait_read() { asm volatile("cp.async.bulk.wait_group.read %0;" ::"n"(N) : "memory"); }
template <int N> __device__ __forceinline__ void bulk_wait() { asm volatile("cp.async.bulk.wait_group %0;" ::"n"(N) : "memory"); }
__device__ __forceinline__ void fence_async_smem() { asm volatile("fence.proxy.async.shared::cta;" ::: "memory"); }
__device__ __forceinline__ void wg_fence() { asm volatile("wgmma.fence.sync.aligned;" ::: "memory"); }
__device__ __forceinline__ void wg_commit() { asm volatile("wgmma.commit_group.sync.aligned;" ::: "memory"); }
template <int N> __device__ __forceinline__ void wg_wait() { asm volatile("wgmma.wait_group.sync.aligned %0;" ::"n"(N) : "memory"); }
template <int R> __device__ __forceinline__ void fence_regs(float (&d)[R]) {
#pragma unroll
  for (int i = 0; i < R; i++) asm volatile("" : "+f"(d[i])::"memory");
}
__device__ __forceinline__ uint64_t mk_desc(uint32_t addr) {
  return (uint64_t)((addr & 0x3FFFF) >> 4) | (1ull << 16) | (64ull << 32) | (1ull << 62);
}
__device__ __forceinline__ uint32_t pack2(float lo, float hi) {
  uint32_t r;
  asm("cvt.rn.bf16x2.f32 %0, %1, %2;" : "=r"(r) : "f"(hi), "f"(lo));
  return r;
}
__device__ __forceinline__ void stsm4(uint32_t ad, uint32_t a, uint32_t b, uint32_t c, uint32_t d) {
  asm volatile("stmatrix.sync.aligned.m8n8.x4.shared.b16 [%0], {%1,%2,%3,%4};" ::"r"(ad), "r"(a), "r"(b), "r"(c), "r"(d) : "memory");
}
__device__ __forceinline__ void stsm4t(uint32_t ad, uint32_t a, uint32_t b, uint32_t c, uint32_t d) {
  asm volatile("stmatrix.sync.aligned.m8n8.x4.trans.shared.b16 [%0], {%1,%2,%3,%4};" ::"r"(ad), "r"(a), "r"(b), "r"(c), "r"(d) : "memory");
}

__device__ __forceinline__ void stsm2t(uint32_t ad, uint32_t a, uint32_t b) {
  asm volatile("stmatrix.sync.aligned.m8n8.x2.trans.shared.b16 [%0], {%1,%2};" ::"r"(ad), "r"(a), "r"(b) : "memory");
}
__device__ __forceinline__ void red_add(unsigned* p) { asm volatile("red.relaxed.gpu.global.add.u32 [%0], 1;" ::"l"(p) : "memory"); }
__device__ __forceinline__ void fence_release() { asm volatile("fence.release.gpu;" ::: "memory"); }
__device__ __forceinline__ void fence_async_global() { asm volatile("fence.proxy.async.global;" ::: "memory"); }
__device__ __forceinline__ void tma_pf3(const CUtensorMap* tm, int c0, int c1, int c2) {
  asm volatile("cp.async.bulk.prefetch.tensor.3d.L2.global [%0, {%1,%2,%3}];" ::"l"(tm), "r"(c0), "r"(c1), "r"(c2) : "memory");
}
__device__ __forceinline__ uint64_t policy_evict_unchanged() {
  uint64_t p;
  asm("createpolicy.fractional.L2::evict_unchanged.b64 %0, 1.0;" : "=l"(p));
  return p;
}
__device__ __forceinline__ void tma_ld4(uint32_t dst, const CUtensorMap* tm, int c1, uint32_t bar) {
  asm volatile("cp.async.bulk.tensor.4d.shared::cluster.global.mbarrier::complete_tx::bytes [%0], [%1, {%4,%3,%4,%4}], [%2];" ::"r"(dst), "l"(tm), "r"(bar), "r"(c1), "r"(0) : "memory");
}

__device__ __forceinline__ unsigned flag_peek(const unsigned* p) {
  unsigned v;
  asm volatile("ld.acquire.gpu.global.u32 %0, [%1];" : "=r"(v) : "l"(p) : "memory");
  return v;
}
__device__ __forceinline__ int lane_id() {
  int l;
  asm volatile("mov.u32 %0, %%laneid;" : "=r"(l));
  return l;
}
__device__ __forceinline__ void poll64x4(const unsigned long long* p, unsigned long long (&v)[4]) {
  asm volatile("{\n.reg .pred p;\n.reg .u32 c;\n.reg .b64 t, u;\nmov.u32 c, 0;\nWAIT:\n"
               "ld.relaxed.gpu.global.u64 %0, [%4];\nld.relaxed.gpu.global.u64 %1, [%4+512];\n"
               "ld.relaxed.gpu.global.u64 %2, [%4+1024];\nld.relaxed.gpu.global.u64 %3, [%4+1536];\n"
               "or.b64 t, %0, %1;\nor.b64 u, %2, %3;\nor.b64 t, t, u;\nsetp.ge.s64 p, t, 0;\n@p bra DONE;\n"
               "add.u32 c, c, 1;\nsetp.lt.u32 p, c, 0x400000;\n@p bra WAIT;\ntrap;\nDONE:\n}"
               : "=l"(v[0]), "=l"(v[1]), "=l"(v[2]), "=l"(v[3]) : "l"(p) : "memory");
}

constexpr int G_STAGE = WBLK + XBLK;
constexpr int OFF_XR = 4 * G_STAGE;
constexpr int OFF_WS = OFF_XR + 6 * 8192;
constexpr int OFF_F = OFF_WS + 2 * 8192;
constexpr int OFF_WRAW = OFF_F + 8192;
constexpr int OFF_BAR = OFF_WRAW + 8192;
constexpr int OFF_GB = OFF_BAR + 1024;
constexpr int SMEM_BYTES = OFF_GB + 512;
constexpr int OFF_H0B = 10 * 8192;
constexpr int OFF_E = OFF_WRAW + 3072;
constexpr int B_RAWX = 0, B_F = 48, B_ROLE = 56, B_H0 = 80, B_H1 = 96, B_YFREE = 120, B_H0C = 136,
              B_EMPTY = 144,
              B_STGX = 192, B_STGW = 240, B_Y = 256, B_OUT = 272, B_YP = 352,
              B_FULL = 432, B_RAWW = 464, B_DONE = 496, S_ROLE = 576, S_PROBE = 592;

struct Maps { CUtensorMap x, we, wo, xst[2], wst, yld[2], out, xe[2], w30; };

__device__ __forceinline__ int chunk_of(int n) { return n < 16 ? n : 31 - n; }
__device__ __forceinline__ bool has_x2(int id, int n, int g) { return (((id >> 5) ^ n) & 1) == 0 && ((n >> 1) & 1) == g; }
__device__ __forceinline__ int w_row(int id) { return (id & 62) | (id >> 6); }
__device__ __forceinline__ uint32_t x_base(int s, int idx, uint32_t pgmask, int& par) {
  const int page = idx >> 3, o = idx & 7;
  par = (s ^ (pgmask >> page) ^ __popc(o)) & 1;
  return (page << 21) | ((o & 3) << 16) | ((o >> 2) << 19);
}
__device__ __forceinline__ uint32_t spread5(int i) { return (((i >> 1) & 3) << 14) | (((i >> 3) & 1) << 18) | ((i >> 4) << 20) | ((i & 1) << 13); }
__device__ __forceinline__ int y_idx(int half, int dq, int piece) { return (PG_Y + 5 * half) * 8 + (dq * 5 + piece) * 2; }
__device__ __forceinline__ int tail_win(int tr) { return (tr & 1) + 4 * (tr >> 1); }
__device__ __forceinline__ uint32_t read_info(uint32_t bar, int i) {
  uint32_t v;
  mbar_wait(bar + B_ROLE + 8 * i, 0);
  asm volatile("ld.shared.b32 %0, [%1];" : "=r"(v) : "r"(bar + S_ROLE + 4 * i) : "memory");
  return v;
}
__device__ __forceinline__ void send_info(uint32_t bar, int i, uint32_t v) {
#pragma unroll
  for (int r = 0; r < 2; r++)
    asm volatile("{\n.reg .b32 a, m;\nmapa.shared::cluster.u32 a, %0, %2;\nmapa.shared::cluster.u32 m, %1, %2;\n"
                 "st.async.weak.shared::cluster.mbarrier::complete_tx::bytes.b32 [a], %3, [m];\n}"
                 ::"r"(bar + S_ROLE + 4 * i), "r"(bar + B_ROLE + 8 * i), "r"(r), "r"(v) : "memory");
}
__device__ __forceinline__ unsigned probe(uint8_t* p, int lane) {
  if (lane < 2) *(uint4*)(p + lane * 16) = make_uint4(0, 0, 0, 0);
  __syncwarp();
  unsigned v, t0 = 0, t1 = 0;
  if (lane == 0) {
    asm volatile("mov.u32 %0, %%clock;" : "=r"(t0)::"memory");
    asm volatile("atom.relaxed.gpu.global.exch.b32 %0, [%1], 0;" : "=r"(v) : "l"(p) : "memory");
    asm volatile("{\n.reg .pred p;\nsetp.ne.u32 p, %1, 0xffffffff;\nmov.u32 %0, 0;\n@p mov.u32 %0, %%clock;\n}" : "=r"(t1) : "r"(v) : "memory");
  }
  return t1 - t0;
}

template <bool ISX>
__device__ __forceinline__ void t_issue(float (&t)[32], uint32_t sb, uint32_t raw) {
  const uint64_t da = mk_desc(sb + OFF_F), db = mk_desc(raw);
  wg_fence();
#pragma unroll
  for (int kk = 0; kk < (ISX ? 4 : 1); kk++) wgmma_fwd<1>(t, da + 2 * kk, db + 128 * kk, kk);
  wg_commit();
}
template <bool ISX>
__device__ __forceinline__ void t_finish(float (&t)[32], uint32_t dst, uint32_t sbar, int sw, int wg, int w, int lane) {
  fence_regs(t);
  if (ISX) asm volatile("bar.sync %0, 128;" ::"r"(1 + wg) : "memory");
  const int m = lane >> 3, r = lane & 7;
  uint32_t ad = dst + (8 * w + r) * 128;
  if (ISX) ad += ((((m & 1) * 4 + (m >> 1)) ^ sw ^ r) << 4);
  else ad += (m & 1) * 4096 + (((m >> 1) ^ sw ^ r) << 4);
#pragma unroll
  for (int i = 0; i < 4; i++) {
    const uint32_t a = ISX ? ((ad ^ ((i & 1) * 32)) + (i >> 1) * 4096) : (ad ^ (i * 32));
    stsm4(a, pack2(t[8 * i], t[8 * i + 1]), pack2(t[8 * i + 2], t[8 * i + 3]), pack2(t[8 * i + 4], t[8 * i + 5]), pack2(t[8 * i + 6], t[8 * i + 7]));
  }
  __syncwarp();
  if (lane == 0) mbar_arrive(sbar);
}
template <int NT, int K0, int K1>
__device__ __forceinline__ void batch(float (&yr)[80], float (&yi)[80], float (&t)[32], uint32_t st, int wg, int sd, uint32_t fa, uint32_t raw) {
  const uint64_t w0 = mk_desc(st + wg * 8192), x0 = mk_desc(st + WBLK);
  const uint64_t da = mk_desc(fa), db = mk_desc(raw);
  wg_fence();
  if (NT) {
#pragma unroll
    for (int kk = 0; kk < NT; kk++) wgmma_fwd<1>(t, da + 2 * kk, db + 128 * kk, kk);
    wg_commit();
  }
#pragma unroll
  for (int kk = K0; kk < K1; kk++) {
    const uint64_t wr = w0 + kk * 128, wi = wr + 256, xr = x0 + kk * 2, xi = xr + 4;
    wgmma_main<1>(yr, wr, xr, kk ? 1 : sd);
    wgmma_main<1>(yi, wr, xi, kk ? 1 : sd);
    wgmma_main<1>(yr, wi, xi, 1);
    wgmma_main<-1>(yi, wi, xr, 1);
  }
  wg_commit();
}

#define X_WAIT() PROF_W(wraw, mbar_wait(bar + B_RAWX + 8 * (wg * 3 + xs), xph))
#define X_ISSUE() t_issue<true>(t, sb, sb + OFF_XR + (wg * 3 + xs) * 8192)
#define X_FINISH(sw) do { t_finish<true>(t, sb + OFF_XR + (wg * 3 + xs) * 8192, bar + B_STGX + 8 * (wg * 3 + xs), sw, wg, w, lane); \
                          if (++xs == 3) { xs = 0; xph ^= 1; } } while (0)
#define W_WAIT(n) PROF_W(wraw, mbar_wait(bar + B_RAWW + 8 * (wg * 2 + ((n) & 1)), ((n) >> 1) & 1))
#define WRAW(n) (sb + OFF_WRAW + (wg * 2 + ((n) & 1)) * 2048)
#define W_FINISH() t_finish<false>(t, sb + OFF_WS + wg * 8192, bar + B_STGW + 8 * wg, w_row(id) & 7, wg, w, lane)

__device__ __forceinline__ void gelu_store(float (&hz)[28], uint32_t ad) {
#pragma unroll
  for (int i = 0; i < 28; i++) {
    const float in = hz[i] * fmaf(hz[i] * hz[i], 8.f * 0.044715f * 0.7978845608028654f, 2.f * 0.7978845608028654f);
    float th;
    asm("tanh.approx.f32 %0, %1;" : "=f"(th) : "f"(in));
    hz[i] = fmaf(hz[i], th, hz[i]);
  }
#pragma unroll
  for (int jj = 0; jj < 3; jj++) {
    const float* c = hz + 8 * jj;
    stsm4t(ad + jj * 2048, pack2(c[0], c[1]), pack2(c[2], c[3]), pack2(c[4], c[5]), pack2(c[6], c[7]));
  }
  stsm2t(ad + 3 * 2048, pack2(hz[24], hz[25]), pack2(hz[26], hz[27]));
}

#define ONE(...) do { if (elect_one()) { __VA_ARGS__; } } while (0)
template <int g>
__device__ __forceinline__ void manager(const Maps& tm, const unsigned* ctr, const uint32_t sb, const int id) {
  const uint32_t bar = sb + OFF_BAR, rank = id & 1;
  const uint64_t pol = policy_evict_first();
  const int cl = w_row(id), b = id >> 6, u = (id >> 1) & 31;
  const unsigned* pf = ctr + (C_LOADED + (((cl >> 5) - WR) >> 1)) * 32 + (((cl >> 5) - WR) & 1);
  int li = 0;
  auto refill = [&](int sl, bool wait) {
    const uint32_t fb = bar + B_RAWX + 8 * (g * 3 + sl);
    int row = ((li & 1) ? 128 + (id & 31) : 2 * (id & 63) + g) * MT, col = (li >> 1) * 64;
    asm volatile("" : "+r"(row), "+r"(col));
    ONE(if (li < 32) mbar_expect(fb, 8192);
        if (wait) bulk_wait_read<0>();
        if (li < 32) tma_ld3h(sb + OFF_XR + (g * 3 + sl) * 8192, &tm.x, col, row, b, fb, pol));
    li += (li & 1) || has_x2(id, li >> 1, g) ? 1 : 2;
  };
#pragma unroll 1
  for (int sl = 0; sl < 3; sl++) refill(sl, false);
  int xs = 0, xph = 0, yp = 0;
  int wrow = (cl >> 5) * (WSLOT / 128) + rank * 128 + g * 64 + (cl & 31);
  const uint32_t pgmask = __shfl_sync(0xffffffffu, read_info(bar, 1), 0);
  auto store_y = [&](int half, int piece, uint32_t buf, uint32_t wait_bar, int ph) {
    int par;
    int c = x_base(b, y_idx(half, rank * 2 + g, piece) + (u >> 4), pgmask, par);
    c = (c + (par << 12) + (u & 15) * 256) >> 1;
    const CUtensorMap* m = &tm.xst[par];
    asm volatile("" : "+r"(c), "+l"(m));
    if (wait_bar) mbar_wait(wait_bar, ph);
    ONE(fence_async_smem(); tma_st5(m, buf, c); tma_st5(m, buf + 4096, c + 64));
  };
  mbar_wait(bar + B_STGW + 8 * g, 0);
  ONE(fence_async_smem(); tma_st4(&tm.wst, sb + OFF_WS + g * 8192, 0, 0, 0, wrow); bulk_commit());
#pragma unroll 1
  for (int n = 0; n < 32; n++) {
    unsigned freed = 128;
    if (2 * n + (cl >> 5) >= WR) asm volatile("ld.relaxed.gpu.global.u32 %0, [%1];" : "=r"(freed) : "l"(pf + n * 32) : "memory");
    if (n < 16) {
#pragma unroll 1
      for (int j = 0; j < (has_x2(id, n, g) ? 2 : 1); j++) {
        const int t = j ? 128 + (id & 31) : 2 * (id & 63) + g;
        int par0, par1;
        const uint32_t off0 = x_base(b, n * 10 + (t >> 5), pgmask, par0), off1 = x_base(b, n * 10 + 5 + (t >> 5), pgmask, par1);
        uint32_t buf = sb + OFF_XR + (g * 3 + xs) * 8192;
        int c0 = (off0 + (par0 << 12) + (t & 31) * 128) >> 1, c1 = (off1 + (par1 << 12) + (t & 31) * 128) >> 1;
        const CUtensorMap *m0 = &tm.xst[par0], *m1 = &tm.xst[par1];
        asm volatile("" : "+r"(buf), "+r"(c0), "+r"(c1), "+l"(m0), "+l"(m1));
        mbar_wait(bar + B_STGX + 8 * (g * 3 + xs), xph);
        ONE(fence_async_smem(); tma_st5(m0, buf, c0); tma_st5(m1, buf + 4096, c1); bulk_commit());
        refill(xs, true);
        if (++xs == 3) { xs = 0; xph ^= 1; }
      }
    }
    if (n > 16 + LW && n <= YFLUSH) {
#pragma unroll 1
      do {
        store_y(0, yp, sb + OFF_XR + (g * 3 + (yp < 3 ? yp : yp - 3)) * 8192, (yp == 0 || yp == 3) ? bar + B_Y + 8 * g : 0, yp & 1);
      } while (++yp < 2);
      ONE(bulk_commit(); bulk_wait_read<0>(); if (yp == 2) mbar_arrive(bar + B_YFREE + 8 * g));
    }
    if (__shfl_sync(0xffffffffu, freed, 0) < 128) flag_wait(pf + n * 32, 128);
    const int cp = chunk_of(n + 2) * 64 + cl, sl = g * 2 + (n & 1);
    if (n) mbar_wait(bar + B_STGW + 8 * g, n & 1);
    ONE(if (n) {
          fence_async_smem();
          tma_st4(&tm.wst, sb + OFF_WS + g * 8192, 0, 0, 0, wrow);
          bulk_commit();
        }
        if (n < 30) {
          mbar_expect(bar + B_RAWW + 8 * sl, 2048);
          tma_ld3h(sb + OFF_WRAW + sl * 2048, &tm.we + (cp >> 9), 0, 0, (cp & 511) * 8 + ((n + 2) >> 4) * 4 + rank * 2 + g, bar + B_RAWW + 8 * sl, pol);
        }
        if (n < 4) {
          tma_pf3(&tm.we, 0, 0, ((n + 4) * 64 + cl) * 8 + rank * 2 + g);
          tma_pf3(&tm.wo, 0, 0, (n * 64 + cl) * 8 + rank * 2 + g);
          tma_pf3(&tm.wo, 0, 0, ((n + 4) * 64 + cl) * 8 + rank * 2 + g);
        }
        bulk_wait<0>();
        mbar_arrive(bar + B_DONE + 8 * (n & 7));
        mbar_arrive(bar + B_RAWW + 8 * (sl ^ 1)));
    wrow += 2 * WSLOT / 128;
    if (wrow >= WR * WSLOT / 128) wrow -= WR * WSLOT / 128;
  }
  ONE(asm volatile("prefetch.tensormap [%0];" ::"l"(g ? &tm.out : &tm.xst[b]) : "memory"));
  flag_wait(&ctr[(C_LOADED + 31) * 32 + 1], 128);
#pragma unroll 1
  for (int p = 0; p < 5; p++) {
    store_y(1, p, sb + (p * 2 + g) * 8192, bar + B_YP + 8 * (g * 5 + p), 0);
    if (p == YA - 1) ONE(bulk_commit());
  }
  ONE(bulk_commit(); bulk_wait<1>(); mbar_arrive(bar + B_DONE); bulk_wait<0>(); mbar_arrive(bar + B_DONE + 8));
#pragma unroll 1
  for (int i = 0; i < 10; i++) {
    const int hf = i >= 5, k = i - 5 * hf;
    const uint32_t buf = sb + (hf ? 0 : k < 4 ? OFF_XR : OFF_H0B - 65536) + (2 * k + g) * 8192;
    mbar_wait(bar + B_OUT + 8 * (g * 5 + k), hf);
    ONE(fence_async_smem();
        tma_st3(&tm.out, buf, (hf * 4 + rank * 2 + (u & 1)) * 64, (32 * k + tail_win(u >> 1) + 2 * g) * MT, b);
        bulk_commit());
  }
  ONE(bulk_wait_read<0>(); if (g == 0) PROF_T(12));
}

__global__ void __cluster_dims__(2, 1, 1) __launch_bounds__(512, 1)
k1_main(uint8_t* xbuf, const void* __restrict__ fimg, const __nv_bfloat16* __restrict__ gamma,
        const __nv_bfloat16* __restrict__ beta, const __grid_constant__ Maps tm) {
  extern __shared__ __align__(1024) uint8_t smem_raw[];
  const uint32_t sb = s2u(smem_raw);
  const uint32_t bar = sb + OFF_BAR;
  const int warp = __shfl_sync(0xffffffffu, threadIdx.x >> 5, 0);
  const int bid = blockIdx.x;
  unsigned* ctr = (unsigned*)(xbuf + CTR_OFF);
  const uint32_t rank = bid & 1;
  if (bid == 0 && threadIdx.x < 4) asm volatile("st.relaxed.gpu.global.u64 [%0], %1;" ::"l"(&ctr[C_REG * 32 + 2 * threadIdx.x]), "l"(1ull << 63) : "memory");
  if (warp >= 12) {
    asm volatile("setmaxnreg.dec.sync.aligned.u32 24;");
    asm volatile("barrier.cluster.arrive.relaxed.aligned;" ::: "memory");
    {
      const int lane = lane_id(), k = bid >> 1;
      if (rank == 0 || k < XPAGES) {
        const uint32_t off = rank ? (k << 21) + 0xb0000 : (XPAGES << 21) + ((k >> 6) << 18) + (((k >> 4) & 3) << 14) + (k & 15) * 128;
        const unsigned lat = probe(xbuf + off + (warp & 1) * 4096 + (warp & 2) * 1024, lane);
        if (lane == 0) asm volatile("st.shared.b32 [%0], %1;" ::"r"(bar + S_PROBE + 4 * (warp & 3)), "r"(lat) : "memory");
      }
      asm volatile("bar.sync 4, 128;" ::: "memory");
      asm volatile("barrier.cluster.wait.aligned;" ::: "memory");
      if (warp == 14 && lane == 0) {
        uint32_t l0, l1, l2, l3;
        asm volatile("ld.shared.v4.b32 {%0, %1, %2, %3}, [%4];" : "=r"(l0), "=r"(l1), "=r"(l2), "=r"(l3) : "r"(bar + S_PROBE) : "memory");
        const int near = min(l1, l3) < min(l0, l2);
        if (rank) {
          send_info(bar, 2, near);
        } else {
          unsigned long long add = 1ull << (8 * near), v, *reg = (unsigned long long*)&ctr[C_REG * 32];
          if (k < XPAGES) add += (unsigned long long)(read_info(bar, 2) ^ near ^ 1) << (16 + k);
          PROF_T(14);
          asm volatile("{\n.reg .pred p;\n.reg .u32 c;\nmov.u32 c, 0;\nAGAIN:\n"
                       "atom.relaxed.gpu.global.add.u64 %0, [%1], %2;\nsetp.lt.s64 p, %0, 0;\n@p bra DONE;\n"
                       "add.u32 c, c, 1;\nsetp.lt.u32 p, c, 0x100000;\n@p bra AGAIN;\ntrap;\nDONE:\n}" : "=l"(v) : "l"(reg), "l"(add) : "memory");
          const int ticket = (v >> (8 * near)) & 255;
          if (ticket < 32) send_info(bar, 0, near * 32 + ticket);
          PROF_T(15); PROF_V(16, near);
          asm volatile("{\n.reg .pred p;\n.reg .u32 c, a, b;\nmov.u32 c, 0;\nWAIT:\n"
                       "ld.relaxed.gpu.global.u64 %0, [%1];\ncvt.u32.u64 a, %0;\nbfe.u32 b, a, 8, 8;\nand.b32 a, a, 255;\nadd.u32 a, a, b;\n"
                       "setp.ge.u32 p, a, 66;\n@p bra DONE;\n"
                       "add.u32 c, c, 1;\nsetp.lt.u32 p, c, 0x400000;\n@p bra WAIT;\ntrap;\nDONE:\n}" : "=l"(v) : "l"(reg) : "memory");
          if (ticket >= 32) {
            const int j = ticket - 32 + (int)((v >> (8 * (near ^ 1))) & 255);
            send_info(bar, 0, j < 32 ? (near ^ 1) * 32 + j : (near == 0 && ticket == 32 && j == 33) ? 64 : 32 + j);
          }
          send_info(bar, 1, (uint32_t)(v >> 16));
          PROF_T(13);
        }
      }
      __syncwarp();
      const int role = read_info(bar, 0);
      if (role < 64 && warp - 12 < NFL && elect_one()) {
#pragma unroll 1
        for (int n = warp - 12; n < 34; n += NFL) {
          mbar_wait(bar + B_DONE + 8 * (n & 7), (n >> 3) & 1);
          fence_release();
          if (n < 32) {
            red_add(&ctr[(C_FLAG + n + C_SIDE * ((role >> 5) ^ 1)) * 32]);
            red_add(&ctr[(C_FLAG + n + C_SIDE * (role >> 5)) * 32]);
          } else {
            red_add(&ctr[(C_Y + 2 * (n - 32) + rank + C_SIDE * (role >> 5)) * 32]);
          }
          if (n < 32) { PROF_T(64 + n); PROF_V(192 + n, tm0); } else { PROF_V(4, tm0); }
        }
      }
      if (role < 64 && warp == 15 && elect_one()) {
#pragma unroll 1
        for (int v = 0; v < 64; v++) {
          mbar_wait(bar + B_FULL + 8 * (v & 3), (v >> 2) & 1);
          mbar_arrive(bar + B_EMPTY + 8 * (v & 3));
          if (v < 64 - WR || v == 63) {
            red_add(&ctr[(C_LOADED + (v >> 1)) * 32 + (v & 1)]);
            red_add(&ctr[(C_LOADED + (v >> 1) + C_SIDE) * 32 + (v & 1)]);
          }
        }
      }
      __syncwarp();
    }
    asm volatile("barrier.cluster.arrive.relaxed.aligned;\nbarrier.cluster.wait.aligned;" ::: "memory");
    return;
  } else {
    if (elect_one()) {
      if (warp == 0) PROF_T(0);
      if (warp >= 6) asm volatile("prefetch.tensormap [%0];" ::"l"(&tm.x + (warp - 6)) : "memory");
      const int cnt = warp < 3 ? 1 : warp == 3 ? 5 : warp < 9 ? 4 : 2;
#pragma unroll
      for (int i = 0; i < 6; i++) mbar_init(bar + warp * 48 + 8 * i, cnt);
      if (warp == 1) {
        mbar_expect(bar + B_F, 8192);
        bulk_ld(sb + OFF_F, fimg, 8192, bar + B_F);
        mbar_expect(bar + B_ROLE, 4);
        mbar_expect(bar + B_ROLE + 8, 4);
        mbar_expect(bar + B_ROLE + 16, 4);
      }
      asm volatile("fence.mbarrier_init.release.cluster;" ::: "memory");
    }
    asm volatile("bar.sync 0, 384;" ::: "memory");
    asm volatile("barrier.cluster.arrive.relaxed.aligned;" ::: "memory");
    if (threadIdx.x == 64) PROF_T(20);
    if (bid < 128 && warp < 4 && elect_one()) {
      const int g = warp & 1;
      if (warp < 2) {
        tma_pf3(&tm.x, 0, (2 * (bid & 63) + g) * MT, bid >> 6);
        if (has_x2(bid, 0, g)) tma_pf3(&tm.x, 0, (128 + (bid & 31)) * MT, bid >> 6);
      } else {
        tma_pf3(&tm.we, 0, 0, (bid >> 1) * 8 + rank * 2 + g);
      }
    }
    __syncwarp();
  }
  if (warp >= 8) {
    asm volatile("setmaxnreg.dec.sync.aligned.u32 40;");
    asm volatile("barrier.cluster.wait.aligned;" ::: "memory");
    const int role = __shfl_sync(0xffffffffu, read_info(bar, 0), 0);
    const unsigned* lctr = ctr + (role >> 5) * C_SIDE * 32;
    if (role >= 64) {
    } else if (warp == 9 || warp == 10) {
      asm volatile("barrier.cluster.arrive.relaxed.aligned;" ::: "memory");
      if (warp == 9) manager<0>(tm, lctr, sb, role * 2 + rank); else manager<1>(tm, lctr, sb, role * 2 + rank);
      __syncwarp();
      asm volatile("barrier.cluster.wait.aligned;" ::: "memory");
      return;
    } else if (warp == 11) {
      const uint8_t* ws = xbuf + (PG_W << 21) + ((role & 31) * 2 + rank) * WBLK;
      int slot = 0;
#pragma unroll 1
      for (int v = 0; v < 64; v++) {
        const uint8_t* src = ws + (size_t)slot * WSLOT;
        uint32_t dst = sb + (v & 3) * G_STAGE, fb = bar + B_FULL + 8 * (v & 3);
        asm volatile("" : "+l"(src), "+r"(dst), "+r"(fb));
        if (++slot == WR) slot = 0;
        const unsigned* fp = &lctr[(C_FLAG + (v >> 1)) * 32];
        const bool ready = (v & 1) || __shfl_sync(0xffffffffu, flag_peek(fp), 0) >= 128;
        mbar_wait(bar + B_EMPTY + 8 * (v & 3), ((v >> 2) & 1) ^ 1);
        ONE(mbar_expect(fb, WBLK));
        if (!ready) flag_wait(fp, 128);
        ONE(fence_async_global(); bulk_ld(dst, src, WBLK, fb));
      }
    } else {
      const uint32_t pgmask = __shfl_sync(0xffffffffu, read_info(bar, 1), 0);
      const int b = role >> 5, u = role & 31;
      const uint64_t pef = policy_evict_first(), pen = policy_evict_unchanged();
      const uint8_t* xs = xbuf + spread5(u);
      const int skip = rank * 2048;
#pragma unroll 1
      for (int v = 0; v < 64; v++) {
        const int n = v >> 1;
        uint64_t polx = (n < XKEEP || n >= 16) ? pef : pen;
        uint32_t dst = sb + (v & 3) * G_STAGE + WBLK + rank * 8192, fb = bar + B_FULL + 8 * (v & 3);
        const uint8_t* src[3];
#pragma unroll
        for (int g = 0; g < 3; g++) {
          int par;
          const uint32_t o = x_base(b ^ u, chunk_of(n) * 10 + (v & 1) * 5 + rank * 2 + g, pgmask, par);
          src[g] = xs + o + (par << 12) + (g ? 0 : skip);
        }
        asm volatile("" : "+l"(src[0]), "+l"(src[1]), "+l"(src[2]), "+l"(polx), "+r"(dst), "+r"(fb));
        const unsigned* fp = &lctr[(C_FLAG + n) * 32];
        const bool ready = (v & 1) || v >= 32 || __shfl_sync(0xffffffffu, flag_peek(fp), 0) >= 128;
        mbar_wait(bar + B_EMPTY + 8 * (v & 3), ((v >> 2) & 1) ^ 1);
        ONE(mbar_expect(fb, XBLK));
        if (!ready) flag_wait(fp, 128);
        ONE(fence_async_global();
            bulk_ld_mc_h(dst + skip, src[0], 4096 - skip, fb, 3, polx);
            bulk_ld_mc_h(dst + 4096, src[1], 4096, fb, 3, polx);
            bulk_ld_mc_h(dst + 8192, src[2], 2048 + skip, fb, 3, polx));
      }
      const int dq = rank * 2 + (u & 1), t0 = (u >> 1) * 10, tw = tail_win(u >> 1);
      int row[5];
      const CUtensorMap* mp[5];
      auto locate = [&](int half) {
#pragma unroll
        for (int k = 0; k < 5; k++) {
          int par;
          row[k] = x_base(b ^ tw, y_idx(half, dq, k), pgmask, par);
          row[k] = (row[k] + spread5(tw) + (par << 12)) >> 7;
          mp[k] = &tm.yld[par];
          asm volatile("" : "+r"(row[k]), "+l"(mp[k]));
        }
      };
      locate(0);
      flag_wait(&ctr[C_E * 32], 4);
      flag_wait(&lctr[(C_FLAG + YFLUSH) * 32], 128);
      ONE(fence_async_global();
          mbar_expect(bar + B_H0C, 6 * 8192);
          for (int i = 0; i < 3; i++) tma_ld4(sb + OFF_XR + i * 16384, mp[i], row[i], bar + B_H0C));
      static_assert(YFLUSH >= 23, "phase of the B_DONE ring");
      mbar_wait(bar + B_DONE + 8 * 7, 1);
      ONE(mbar_expect(bar + B_H0, 2 * 8192 + 7168 + 5120 + 512);
          bulk_ld(sb + OFF_F, g_Gimg, 7168, bar + B_H0);
          tma_ld4(sb + OFF_WS, mp[3], row[3], bar + B_H0);
          for (int hf = 0; hf < 2; hf++) {
            bulk_ld(sb + OFF_E + hf * 2560, g_E + ((b * 8 + hf * 4 + dq) * NT + t0) * 64, 2560, bar + B_H0);
            bulk_ld(sb + OFF_GB + hf * 256, gamma + (hf * 4 + dq) * 64, 128, bar + B_H0);
            bulk_ld(sb + OFF_GB + hf * 256 + 128, beta + (hf * 4 + dq) * 64, 128, bar + B_H0);
          });
      mbar_wait(bar + B_EMPTY + 8 * 2, 1);
      ONE(mbar_expect(bar + B_H0 + 8, 16384);
          tma_ld4(sb + OFF_H0B, mp[4], row[4], bar + B_H0 + 8);
          for (int i = 0; i < 3; i++) mbar_expect(bar + B_H1 + 8 * i, i < 2 ? 32768 : 16384));
      locate(1);
      flag_wait(&lctr[(C_Y + rank) * 32], 32);
      ONE(fence_async_global();
          for (int i = 0; i < YA; i++) tma_ld4(sb + i * 16384, mp[i], row[i], bar + B_H1 + 8 * (i >> 1));
          PROF_T(5));
      flag_wait(&lctr[(C_Y + 2 + rank) * 32], 32);
      ONE(fence_async_global();
          for (int i = YA; i < 5; i++) tma_ld4(sb + i * 16384, mp[i], row[i], bar + B_H1 + 8 * (i >> 1));
          PROF_T(1));
      const int lane = lane_id();
      unsigned old = 0;
      if (lane == 0) old = atomicAdd(&ctr[C_EXIT * 32], 1);
      if (__shfl_sync(0xffffffffu, old, 0) == 127) {
#pragma unroll
        for (int i = 0; i < 6; i++) *(uint4*)&ctr[((i >> 1) * 128 + (i & 1) * C_SIDE + lane) * 32] = make_uint4(0, 0, 0, 0);
      }
    }
    asm volatile("barrier.cluster.arrive.relaxed.aligned;\nbarrier.cluster.wait.aligned;" ::: "memory");
  } else {
    asm volatile("setmaxnreg.inc.sync.aligned.u32 224;");
    const int wg = warp >> 2, w = warp & 3;
    int lane = lane_id();
    asm volatile("barrier.cluster.wait.aligned;" ::: "memory");
    mbar_wait(bar + B_F, 0);
    const int id = __shfl_sync(0xffffffffu, read_info(bar, 0), 0) * 2 + rank;
    if (id >= 128) {
      float ea[80], eb[80];
      const int b = (id >> 1) & 1;
      constexpr int ES = 32768 + 2 * XBLK;
#pragma unroll 1
      for (int k = -3; k < 8; k++) {
        const int sl = (k + 3) % 3;
        if (k >= 0) {
          mbar_wait(bar + B_RAWX + 8 * sl, (k / 3) & 1);
          const uint64_t da = mk_desc(sb + sl * ES + wg * 16384), db = mk_desc(sb + sl * ES + 32768);
          wg_fence();
#pragma unroll
          for (int kk = 0; kk < 8; kk++) {
            const uint64_t a0 = da + (kk & 3) * 128, b0 = db + (kk & 3) * 2 + (kk >> 2) * (XBLK >> 4);
            wgmma_main<1>(ea, a0, b0, (k | kk) != 0);
            wgmma_main<1>(eb, a0 + 512, b0, (k | kk) != 0);
          }
          wg_commit();
          wg_wait<0>();
          asm volatile("bar.sync 3, 256;" ::: "memory");
        }
        if (k + 3 < 8 && warp == 0 && elect_one()) {
          if (k == -3) {
            for (int i = 0; i < 64; i++) {
              unsigned v;
              asm volatile("ld.relaxed.gpu.global.u32 %0, [%1];" : "=r"(v) : "l"(&ctr[(C_FLAG + 14) * 32]) : "memory");
              if (v >= 128) break;
              __nanosleep(500);
            }
          }
          const uint32_t dst = sb + sl * ES, fb = bar + B_RAWX + 8 * sl;
          mbar_expect(fb, ES);
          for (int q = 0; q < 4; q++) tma_ld2(dst + q * 8192, &tm.w30, rank * 256 + q * 64, (k + 3) * 64, fb);
          for (int q = 0; q < 2; q++) tma_ld3(dst + 32768 + q * XBLK, &tm.xe[q], (k + 3) * 64, 0, b, fb);
        }
        __syncwarp();
      }
      fence_regs(ea);
      fence_regs(eb);
      float* e0 = g_E + ((b * 8 + rank * 4 + wg * 2) * NT + 10 * (lane & 2) + (lane & 1)) * 64 + 16 * w + (lane >> 2);
#pragma unroll
      for (int i = 0; i < 80; i++) {
        const int o = (40 * ((i >> 2) & 3) + 2 * (i >> 4) + 10 * (i & 1)) * 64 + ((i >> 1) & 1) * 8;
        e0[o] = ea[i];
        e0[o + NT * 64] = eb[i];
      }
      asm volatile("bar.sync 3, 256;" ::: "memory");
      if (threadIdx.x == 0) {
        fence_release();
        red_add(&ctr[C_E * 32]);
        PROF_T(28);
      }
      asm volatile("barrier.cluster.arrive.relaxed.aligned;\nbarrier.cluster.wait.aligned;" ::: "memory");
      return;
    }
    if (w < 2 && elect_one()) {
      const uint32_t fb = bar + B_RAWW + 8 * (wg * 2 + w);
      mbar_expect(fb, 2048);
      tma_ld3h(sb + OFF_WRAW + (wg * 2 + w) * 2048, &tm.we, 0, 0, (w * 64 + w_row(id)) * 8 + rank * 2 + wg, fb, policy_evict_first());
      if (!w) mbar_arrive(fb);
    }
    __syncwarp();
    {
      float yr[80], yi[80], t[32];

      int xs = 0, xph = 0;
      if (threadIdx.x == 0) PROF_T(24);
      W_WAIT(0);
      t_issue<false>(t, sb, WRAW(0));
      wg_wait<0>();
      W_FINISH();
      if (threadIdx.x == 0) PROF_T(25);
#pragma unroll 1
      for (int m = 0; m <= LW; m++) {
        X_WAIT();
        X_ISSUE();
        wg_wait<0>();
        X_FINISH((2 * id + wg) & 7);
        if (threadIdx.x == 0 && m == 0) PROF_T(26);
        if (has_x2(id, m, wg)) {
          X_WAIT();
          X_ISSUE();
          wg_wait<0>();
          X_FINISH(id & 7);
        }
        if (m < LW && m) {
          W_WAIT(m);
          t_issue<false>(t, sb, WRAW(m));
          wg_wait<0>();
          W_FINISH();
        }
      }
      if (threadIdx.x == 0) PROF_T(27);
      const int ym = lane >> 3, yr8 = lane & 7;
      const uint32_t yad = (ym >> 1) * 4096 + yr8 * 128 + (((2 * w + (ym & 1)) ^ yr8) << 4);
#define STAGE_PROF0()
#define STAGE_PROF1()
#define STAGE_BEGIN() PROF_W(wfull, mbar_wait(bar + B_FULL + 8 * (v & 3), (v >> 2) & 1)); STAGE_PROF0(); const uint32_t st = sb + (v & 3) * G_STAGE
#define RELEASE(vv) do { if (w == 0 && lane < 2) mbar_arrive_cluster(bar + B_EMPTY + 8 * ((vv) & 3), lane, 1); } while (0)
#define XRAW (sb + OFF_XR + (wg * 3 + xs) * 8192)
#define STAGE_W0(mw, sd) do { W_WAIT(mw); batch<1, 0, 2>(yr, yi, t, st, wg, sd, sb + OFF_F, WRAW(mw)); wg_wait<1>(); W_FINISH(); wg_wait<0>(); RELEASE(v); } while (0)
#define STAGE_PLAIN0(sd) do { batch<0, 0, 2>(yr, yi, t, st, wg, sd, 0, 0); wg_wait<0>(); RELEASE(v); } while (0)
#define STAGE_W1(mw, sd) do { W_WAIT(mw); batch<1, 0, 1>(yr, yi, t, st, wg, sd, sb + OFF_F, WRAW(mw)); wg_wait<1>(); if (sd) RELEASE(v - 1); \
                              W_FINISH(); batch<0, 1, 2>(yr, yi, t, st, wg, 1, 0, 0); } while (0)
      constexpr int VX = 31 - 2 * LW;
#pragma unroll 1
      for (int v = 0; v < VX; v++) {
        const int m = ((v + 1) >> 1) + LW;
        STAGE_BEGIN();
        if (!(v & 1)) {
          STAGE_W1(m, v != 0);
        } else {
          X_WAIT();
          batch<4, 0, 1>(yr, yi, t, st, wg, 1, sb + OFF_F, XRAW);
          wg_wait<1>();
          RELEASE(v - 1);
          X_FINISH((2 * id + wg) & 7);
          if (has_x2(id, m, wg)) {
            X_WAIT();
            batch<4, 1, 2>(yr, yi, t, st, wg, 1, sb + OFF_F, XRAW);
            wg_wait<1>();
            X_FINISH(id & 7);
          } else {
            batch<0, 1, 2>(yr, yi, t, st, wg, 1, 0, 0);
          }
        }
        STAGE_PROF1();
      }
      wg_wait<0>();
      RELEASE(VX - 1);
#pragma unroll 1
      for (int v = VX; v < 32; v++) {
        const int m = ((v + 1) >> 1) + LW;
        STAGE_BEGIN();
        if (!(v & 1) || v == 31) STAGE_W0(m, 1); else STAGE_PLAIN0(1);
        STAGE_PROF1();
      }
      fence_regs(yr);
      fence_regs(yi);
      {
        uint32_t hold[32];
#pragma unroll
        for (int j = 0; j < 20; j++) {
          const uint32_t p0 = pack2(yr[4 * j], yr[4 * j + 1]), p1 = pack2(yr[4 * j + 2], yr[4 * j + 3]);
          const uint32_t p2 = pack2(yi[4 * j], yi[4 * j + 1]), p3 = pack2(yi[4 * j + 2], yi[4 * j + 3]);
          if (j < 12) {
            stsm4t(sb + OFF_XR + wg * 3 * 8192 + yad + (j >> 2) * 8192 + (j & 3) * 1024, p0, p1, p2, p3);
          } else {
            hold[4 * j - 48] = p0; hold[4 * j - 47] = p1; hold[4 * j - 46] = p2; hold[4 * j - 45] = p3;
          }
        }
#pragma unroll
        for (int j = 0; j < 32; j++) asm volatile("" : "+r"(hold[j])::"memory");
        __syncwarp();
        if (lane == 0) mbar_arrive(bar + B_Y + 8 * wg);
        if (threadIdx.x == 0) PROF_T(2);
#pragma unroll
        for (int v = 32; v < 34; v++) {
          STAGE_BEGIN();
          STAGE_PLAIN0(v != 32);
          STAGE_PROF1();
        }
        mbar_wait(bar + B_YFREE + 8 * wg, 0);
#pragma unroll
        for (int j = 0; j < 8; j++)
          stsm4t(sb + OFF_XR + wg * 3 * 8192 + yad + (j >> 2) * 8192 + (j & 3) * 1024, hold[4 * j], hold[4 * j + 1], hold[4 * j + 2], hold[4 * j + 3]);
        __syncwarp();
        if (lane == 0) mbar_arrive(bar + B_Y + 8 * wg);
#pragma unroll
        for (int j = 0; j < 32; j++) t[j] = __uint_as_float(hold[j]);
      }
#pragma unroll 1
      for (int v = 34; v < 64; v++) {
        const int m = (v >> 1) + LW;
        STAGE_BEGIN();
        if (!(v & 1) && m < 32) {
          STAGE_W0(m, 1);
        } else {
          STAGE_PLAIN0(1);
          if (v == 49 && wg == 0) part_ptr(xbuf, id >> 6, w >> 1, rank * 2 + ((id >> 1) & 1), (id >> 2) & 15)[(w & 1) * 32 + lane] = ~0ull;
        }
        STAGE_PROF1();
      }
      wg_wait<0>();
      fence_regs(yr);
      fence_regs(yi);
      if (FINB) asm volatile("bar.sync 3, 256;" ::: "memory");
      else mbar_wait(bar + B_EMPTY + 8 * 2, 1);
#pragma unroll
      for (int j = 0; j < 20; j++) {
        stsm4t(sb + wg * 8192 + yad + (j >> 2) * 16384 + (j & 3) * 1024, pack2(yr[4 * j], yr[4 * j + 1]), pack2(yr[4 * j + 2], yr[4 * j + 3]),
               pack2(yi[4 * j], yi[4 * j + 1]), pack2(yi[4 * j + 2], yi[4 * j + 3]));
        if ((j & 3) == 3) {
          __syncwarp();
          if (lane == 0) mbar_arrive(bar + B_YP + 8 * (wg * 5 + (j >> 2)));
        }
      }
      if (threadIdx.x == 0) PROF_T(3);
    }
    asm volatile("barrier.cluster.arrive.relaxed.aligned;" ::: "memory");
    lane = lane_id();
    const int tid = warp * 32 + lane, b = id >> 6, u = (id >> 1) & 31;
    const int dq = rank * 2 + (u & 1), tr = u >> 1;
    const int a = lane & 3, d0 = 16 * w + (lane >> 2);
    float2* s_red = (float2*)(smem_raw + OFF_WRAW);
    const uint32_t oad = wg * 8192 + ((lane >> 4) * 8 + (lane & 7)) * 128 + (((2 * w + ((lane >> 3) & 1)) ^ (lane & 7)) << 4);
    float hz[28];
#pragma unroll
    for (int i = 0; i < 28; i++) hz[i] = 0.f;
#pragma unroll 1
    for (int hf = 0; hf < 2; hf++) {
      const uint32_t base = sb + (hf ? 0 : OFF_XR), last = hf ? 0 : OFF_H0B - 65536 - OFF_XR;
      float acc[5][28];
      float q1[4] = {0.f, 0.f, 0.f, 0.f}, q2[4] = {0.f, 0.f, 0.f, 0.f};
      if (hf == 0) { mbar_wait(bar + B_H0, 0); mbar_wait(bar + B_H0C, 0); }
      const float* se = (const float*)(smem_raw + OFF_E + hf * 2560) + wg * 64 + d0;
#pragma unroll
      for (int k2 = 0; k2 < 4; k2++) {
        if (k2 < 3) {
          if (hf) mbar_wait(bar + B_H1 + 8 * k2, 0);
          else if (k2 == 2) mbar_wait(bar + B_H0 + 8, 0);
          const uint64_t da = mk_desc(base + (4 * k2 + wg) * 8192 + (k2 == 2 ? last : 0)), db = mk_desc(sb + OFF_F);
          wg_fence();
#pragma unroll
          for (int kk = 0; kk < 4; kk++) {
            wgmma_inv<1>(acc[2 * k2], da + 128 * kk, db + 2 * kk, kk);
            if (k2 < 2) wgmma_inv<1>(acc[2 * k2 + 1], da + 1024 + 128 * kk, db + 2 * kk, kk);
          }
          wg_commit();
        }
        if (k2 > 0) {
          if (k2 < 3) wg_wait<1>(); else wg_wait<0>();
#pragma unroll
          for (int k = 2 * k2 - 2; k < 2 * k2 && k < 5; k++) {
            fence_regs(acc[k]);
            if (a == 0) {
              acc[k][25] += se[k * 128];
              acc[k][27] += se[k * 128 + 8];
            }
            if (k == 4 && tr == 15 && wg == 1) {
#pragma unroll
              for (int i = 16; i < 28; i++)
                if (8 * (i >> 2) + (i & 1) + 2 * a >= LOUT - (NT - 1) * MT) acc[k][i] = 0.f;
            }
#pragma unroll
            for (int i = 0; i < 28; i++) {
              q1[i & 3] += acc[k][i];
              q2[i & 3] = fmaf(acc[k][i], acc[k][i], q2[i & 3]);
            }
            fence_regs(q1);
            fence_regs(q2);
          }
        }
      }
      float s1[2] = {q1[0] + q1[1], q1[2] + q1[3]}, s2[2] = {q2[0] + q2[1], q2[2] + q2[3]};
#pragma unroll
      for (int i = 0; i < 2; i++) {
#pragma unroll
        for (int o = 1; o < 4; o <<= 1) {
          s1[i] += __shfl_xor_sync(0xffffffffu, s1[i], o);
          s2[i] += __shfl_xor_sync(0xffffffffu, s2[i], o);
        }
      }
      if (a == 0) {
        s_red[wg * 64 + d0] = make_float2(s1[0], s2[0]);
        s_red[wg * 64 + d0 + 8] = make_float2(s1[1], s2[1]);
      }
      asm volatile("bar.sync 3, 256;" ::: "memory");
      if (tid == 0) PROF_T(6 + 3 * hf);
      if (tid < 64) {
        const float2 p0 = s_red[tid], p1 = s_red[64 + tid];
        const float x1 = p0.x + p1.x, x2 = p0.y + p1.y;
        const unsigned long long v = ((unsigned long long)(__float_as_uint(x2) & 0x7fffffffu) << 32) | __float_as_uint(x1);
        asm volatile("st.relaxed.gpu.global.u64 [%0], %1;" ::"l"(part_ptr(xbuf, b, hf, dq, tr) + tid), "l"(v) : "memory");
      }
      if (hf) {
        gelu_store(hz, sb + OFF_H0B + oad);
        __syncwarp();
        if (lane == 0) mbar_arrive(bar + B_OUT + 8 * (wg * 5 + 4));
      }
      {
        const unsigned long long* q = part_ptr(xbuf, b, hf, dq, (tid >> 6) * 4) + (tid & 63);
        unsigned long long v[4];
        poll64x4(q, v);
        float x1 = 0.f, x2 = 0.f;
#pragma unroll
        for (int i = 0; i < 4; i++) {
          x1 += __uint_as_float((uint32_t)v[i]);
          x2 += __uint_as_float((uint32_t)(v[i] >> 32));
        }
        s_red[128 + tid] = make_float2(x1, x2);
      }
      asm volatile("bar.sync 3, 256;" ::: "memory");
      if (tid == 0) PROF_T(7 + 3 * hf);
#pragma unroll
      for (int i = 0; i < 2; i++) {
        const float2 q0 = s_red[128 + d0 + 8 * i], q1 = s_red[192 + d0 + 8 * i], q2 = s_red[256 + d0 + 8 * i], q3 = s_red[320 + d0 + 8 * i];
        const float mu = ((q0.x + q1.x) + (q2.x + q3.x)) * (1.f / LOUT);
        const float var = fmaxf(((q0.y + q1.y) + (q2.y + q3.y)) * (1.f / LOUT) - mu * mu, 0.f);
        const __nv_bfloat16* gb = (const __nv_bfloat16*)(smem_raw + OFF_GB + hf * 256) + d0 + 8 * i;
        s1[i] = 0.5f * __bfloat162float(gb[0]) * rsqrtf(var + 1e-5f);
        s2[i] = 0.5f * __bfloat162float(gb[64]) - mu * s1[i];
      }
#pragma unroll
      for (int k = 0; k < 5; k++) {
#pragma unroll
        for (int i = 0; i < 28; i++) hz[i] = fmaf(acc[k][i], s1[(i >> 1) & 1], s2[(i >> 1) & 1]);
        if (k == 4) break;
        gelu_store(hz, base + oad + k * 16384);
        float z;
        asm volatile("ld.volatile.shared.f32 %0, [%1];" : "=f"(z) : "r"(sb + OFF_F + 55 * 128) : "memory");
        s2[0] += z;
        s2[1] += z;
        __syncwarp();
        if (lane == 0) mbar_arrive(bar + B_OUT + 8 * (wg * 5 + k));
      }
      if (tid == 0) PROF_T(8 + 3 * hf);
    }
    gelu_store(hz, sb + 4 * 16384 + oad);
    __syncwarp();
    if (lane == 0) mbar_arrive(bar + B_OUT + 8 * (wg * 5 + 4));
    asm volatile("barrier.cluster.wait.aligned;" ::: "memory");
  }
}

typedef CUresult (*EncFn)(CUtensorMap*, CUtensorMapDataType, cuuint32_t, void*, const cuuint64_t*, const cuuint64_t*, const cuuint32_t*,
                          const cuuint32_t*, CUtensorMapInterleave, CUtensorMapSwizzle, CUtensorMapL2promotion, CUtensorMapFloatOOBfill);

void encode(EncFn fn, CUtensorMap* m, int rank, void* base, const cuuint64_t* dims, const cuuint64_t* strides, const cuuint32_t* box,
            CUtensorMapL2promotion promo) {
  cuuint32_t es[5] = {1, 1, 1, 1, 1};
  fn(m, CU_TENSOR_MAP_DATA_TYPE_BFLOAT16, rank, base, dims, strides, box, es, CU_TENSOR_MAP_INTERLEAVE_NONE, CU_TENSOR_MAP_SWIZZLE_128B, promo,
     CU_TENSOR_MAP_FLOAT_OOB_FILL_NONE);
}

}

extern "C" void kernel_launch(void* const* d_in, const int* in_sizes, int n_in, void* d_out, int out_size) {
  (void)in_sizes; (void)n_in; (void)out_size;
  const __nv_bfloat16* x = (const __nv_bfloat16*)d_in[0];
  const __nv_bfloat16* w = (const __nv_bfloat16*)d_in[1];
  const __nv_bfloat16* gamma = (const __nv_bfloat16*)d_in[2];
  const __nv_bfloat16* beta = (const __nv_bfloat16*)d_in[3];
  void* fnp = nullptr;
  cudaDriverEntryPointQueryResult qr;
  cudaGetDriverEntryPoint("cuTensorMapEncodeTiled", &fnp, cudaEnableDefault, &qr);
  EncFn fn = (EncFn)fnp;
  void *fptr = nullptr, *xptr = nullptr;
  cudaGetSymbolAddress(&fptr, g_Fimg);
  cudaGetSymbolAddress(&xptr, g_X);
  xptr = (void*)(((uintptr_t)xptr + (1u << 21) - 1) & ~(uintptr_t)((1u << 21) - 1));
  const CUtensorMapL2promotion P0 = CU_TENSOR_MAP_L2_PROMOTION_NONE, P128 = CU_TENSOR_MAP_L2_PROMOTION_L2_128B;
  Maps m;
  {
    cuuint64_t d[3] = {1024, 8000, 2}, s[2] = {2048, 8000ull * 2048};
    cuuint32_t bx[3] = {64, 64, 1};
    encode(fn, &m.x, 3, (void*)x, d, s, bx, P128);
  }
  for (int ph = 0; ph < 2; ph++) {
    cuuint64_t d[3] = {64, (cuuint64_t)(16 - ph), 4096}, s[2] = {2ull * 262144 * 2, 128};
    cuuint32_t bx[3] = {64, 16, 1};
    encode(fn, ph ? &m.wo : &m.we, 3, (void*)(w + (size_t)ph * 262144), d, s, bx, P128);
  }
  for (int par = 0; par < 2; par++) {
    cuuint64_t d[5] = {(cuuint64_t)XPAGES << 20, 2, 4, 2, 2}, s[4] = {par ? 0x1000u : 0x3000u, 1u << 14, 1u << 18, 1u << 20};
    cuuint32_t bx[5] = {64, 2, 4, 2, 2};
    encode(fn, &m.xst[par], 5, xptr, d, s, bx, P0);
  }
  {
    cuuint64_t d[4] = {64, 32, 2, (cuuint64_t)WR * WSLOT / 128}, s[3] = {2ull * WBLK, 4096, 128};
    cuuint32_t bx[4] = {64, 32, 2, 1};
    encode(fn, &m.wst, 4, (char*)xptr + ((size_t)PG_W << 21), d, s, bx, P0);
  }
  for (int par = 0; par < 2; par++) {
    cuuint64_t d[4] = {64, (cuuint64_t)XPAGES << 14, 2, 2}, s[3] = {128, par ? 0xf000u : 0x11000u, 1u << 14};
    cuuint32_t bx[4] = {64, 32, 2, 2};
    encode(fn, &m.yld[par], 4, xptr, d, s, bx, P128);
  }
  {
    cuuint64_t d[3] = {512, LOUT, 2}, s[2] = {1024, (cuuint64_t)LOUT * 1024};
    cuuint32_t bx[3] = {64, MT, 1};
    encode(fn, &m.out, 3, d_out, d, s, bx, P0);
  }
  for (int q = 0; q < 2; q++) {
    cuuint64_t d[3] = {512, (cuuint64_t)(NT - q), 2}, s[2] = {MT * 2048, 8000ull * 2048};
    cuuint32_t bx[3] = {64, NT, 1};
    encode(fn, &m.xe[q], 3, (void*)(x + q * 64 * 1024), d, s, bx, P128);
  }
  {
    cuuint64_t d[2] = {512, 512}, s[1] = {1024};
    cuuint32_t bx[2] = {64, 64};
    encode(fn, &m.w30, 2, (void*)(w + 30 * 262144), d, s, bx, P128);
  }
  cudaFuncSetAttribute(k1_main, cudaFuncAttributeMaxDynamicSharedMemorySize, SMEM_BYTES);
  k1_main<<<132, 512, SMEM_BYTES>>>((uint8_t*)xptr, fptr, gamma, beta, m);
}
```

```cpp
#include <cuda_runtime.h>
#include <cuda_bf16.h>
#include <cuda.h>
#include <stdint.h>

namespace {

constexpr int LOUT = 7985;
constexpr int MT = 50;
constexpr int NT = 160;
constexpr int XBLK = NT * 128;
constexpr int WBLK = 16384;
constexpr int LW = 4;
constexpr int WR = 10;
constexpr int WSLOT = 64 * WBLK;
constexpr int PG_Y = 20, PG_W = 25, XPAGES = 30;
constexpr int YA = 2;
constexpr int NFL = 2;
constexpr int XKEEP = 9;
constexpr int YFLUSH = 20 + LW;

__device__ __align__(1024) uint8_t g_X[(XPAGES + 2) << 21];
__device__ __align__(128) float g_E[16 * NT * 64];
constexpr int CTR_OFF = (XPAGES << 21) + 0x100000, PART_OFF = CTR_OFF + 0x40000;
constexpr int C_FLAG = 0, C_LOADED = 128  , C_Y = 256, C_E = 260, C_REG = 261, C_EXIT = 262, C_SIDE = 32;
__device__ __forceinline__ unsigned long long* part_ptr(uint8_t* xbuf, int side, int hf, int dq, int tr) {
  return (unsigned long long*)(xbuf + PART_OFF + ((hf * 4 + dq) * 2 + (tr >> 3)) * 8192 + ((side ^ hf ^ (tr >> 3)) << 12) + (tr & 7) * 512);
}
#define PROF_T(i)
#define PROF_C(i)
#define PROF_V(i, v)
#define PROF_W(acc, stmt) stmt

__device__ __align__(128) const uint32_t g_Fimg[2048] = {
 0x3f803f80,0x3f7d3f7f,0x3f783f7b,0x3f713f75,0x3f673f6d,0x3f5c3f62,0x3f4e3f55,0x3f3e3f46,0x3f2c3f35,0x3f183f22,0x3f043f0e,0x3edb3ef1,0x3eac3ec4,0x3e793e95,0x3e163e48,0x3d493dc9,
 0xbd490000,0xbe16bdc9,0xbe79be48,0xbeacbe95,0xbedbbec4,0xbf04bef1,0xbf18bf0e,0xbf2cbf22,0xbf3ebf35,0xbf4ebf46,0xbf5cbf55,0xbf67bf62,0xbf71bf6d,0xbf78bf75,0xbf7dbf7b,0xbf80bf7f,
 0x3e793ec4,0xbd493dc9,0xbeacbe48,0xbf18bef1,0x3f7d3f80,0x3f673f75,0x3f3e3f55,0x3f043f22,0xbf5cbf6d,0xbf2cbf46,0xbedbbf0e,0xbe16be95,0xbf4ebf35,0xbf71bf62,0xbf80bf7b,0xbf78bf7f,
 0x3f783f6d,0x3f803f7f,0x3f713f7b,0x3f4e3f62,0x3e160000,0x3edb3e95,0x3f2c3f0e,0x3f5c3f46,0xbf04bec4,0xbf3ebf22,0xbf67bf55,0xbf7dbf75,0x3f183f35,0x3eac3ef1,0x3d493e48,0xbe79bdc9,
 0xbf04bf35,0xbd49be95,0x3edb3e48,0x3f4e3f22,0x3f7d3f6d,0x3f713f7f,0x3f2c3f55,0x3e793ef1,0x3f783f80,0x3f3e3f62,0x3eac3f0e,0xbe163dc9,0xbf18bec4,0xbf67bf46,0xbf80bf7b,0xbf5cbf75,
 0x3f5c3f35,0x3f803f75,0x3f673f7b,0x3f183f46,0x3e163ec4,0xbeacbdc9,0xbf3ebf0e,0xbf78bf62,0xbe790000,0xbf2cbef1,0xbf71bf55,0xbf7dbf7f,0xbf4ebf6d,0xbedbbf22,0x3d49be48,0x3f043e95,
 0xbf2cbec4,0xbf7dbf62,0xbf5cbf7b,0xbeacbf22,0x3f673f35,0x3f783f7f,0x3f183f55,0xbd493e95,0xbf80bf6d,0xbf4ebf75,0xbe79bf0e,0x3edb3dc9,0x3f713f80,0x3f043f46,0xbe163e48,0xbf3ebef1,
 0x3f3e3f6d,0x3e163ef1,0xbf04be48,0xbf71bf46,0xbedbbf35,0x3e79bdc9,0x3f4e3f0e,0x3f803f75,0x3d493ec4,0xbf18be95,0xbf78bf55,0xbf67bf7f,0x3eac0000,0x3f5c3f22,0x3f7d3f7b,0x3f2c3f62,
 0xbedb0000,0xbf78bf46,0xbf4ebf7b,0xbd49bef1,0x3f3e3ec4,0x3f7d3f75,0x3f043f55,0xbeac3dc9,0xbf71bf35,0xbf5cbf7f,0xbe16bf0e,0x3f2c3e95,0x3f803f6d,0x3f183f62,0xbe793e48,0xbf67bf22,
 0x3f673f80,0x3e793f22,0xbf18be48,0xbf80bf62,0xbf2cbf6d,0x3e16be95,0x3f5c3f0e,0x3f713f7f,0x3eac3f35,0xbf04bdc9,0xbf7dbf55,0xbf3ebf75,0x3d49bec4,0x3f4e3ef1,0x3f783f7b,0x3edb3f46,
 0xbf7dbf6d,0xbeacbf46,0x3f2c3e48,0x3f783f75,0x3f040000,0x3f803f62,0x3edb3f55,0xbf18bdc9,0x3f4e3ec4,0x3f673f7f,0x3d493f0e,0xbf5cbef1,0x3e793f35,0xbf3ebe95,0xbf71bf7b,0xbe16bf22,
 0x3e16bec4,0x3f713f22,0x3f3e3f7b,0xbe793e95,0x3f5c3f80,0xbd493ef1,0xbf67bf0e,0xbf4ebf7f,0x3f183f6d,0xbedb3dc9,0xbf80bf55,0xbf04bf62,0xbf78bf35,0xbf2cbf75,0x3eacbe48,0x3f7d3f46,
 0x3f7d3f35,0x3edb3f62,0xbf3ebe48,0xbf5cbf7f,0x3e79bec4,0x3f803f46,0x3eac3f55,0xbf4ebe95,0xbf180000,0xbf71bf75,0x3d49bf0e,0x3f783f22,0x3f043f6d,0xbf2cbdc9,0xbf67bf7b,0x3e16bef1,
 0xbe16bf35,0x3f673ef1,0x3f2c3f7b,0xbf043dc9,0xbf78bf6d,0xbd49bf22,0x3f713f0e,0x3f183f75,0x3f4e3f80,0xbeac3e95,0xbf80bf55,0xbe79bf46,0x3f5c3ec4,0x3f3e3f7f,0xbedb3e48,0xbf7dbf62,
 0xbedbbf6d,0x3f5c3e95,0x3f183f7b,0xbf3ebdc9,0xbd49bf35,0x3f7d3f22,0x3e793f55,0xbf71bef1,0x3eacbec4,0x3f783f62,0xbe163f0e,0xbf80bf46,0x3f2c0000,0x3f4e3f7f,0xbf043e48,0xbf67bf75,
 0x3f673ec4,0x3f043f75,0xbf4ebe48,0xbf2cbf7f,0x3f803f35,0x3e163f46,0xbf78bf0e,0xbeacbf62,0x3f713f6d,0xbe793ef1,0xbf7dbf55,0x3d49bf22,0x3f3e3f80,0xbf183dc9,0xbf5cbf7b,0x3edbbe95,
 0xbd490000,0xbe16bdc9,0xbe79be48,0xbeacbe95,0xbedbbec4,0xbf04bef1,0xbf18bf0e,0xbf2cbf22,0xbf3ebf35,0xbf4ebf46,0xbf5cbf55,0xbf67bf62,0xbf71bf6d,0xbf78bf75,0xbf7dbf7b,0xbf80bf7f,
 0xbf80bf80,0xbf7dbf7f,0xbf78bf7b,0xbf71bf75,0xbf67bf6d,0xbf5cbf62,0xbf4ebf55,0xbf3ebf46,0xbf2cbf35,0xbf18bf22,0xbf04bf0e,0xbedbbef1,0xbeacbec4,0xbe79be95,0xbe16be48,0xbd49bdc9,
 0xbf78bf6d,0xbf80bf7f,0xbf71bf7b,0xbf4ebf62,0xbe160000,0xbedbbe95,0xbf2cbf0e,0xbf5cbf46,0x3f043ec4,0x3f3e3f22,0x3f673f55,0x3f7d3f75,0xbf18bf35,0xbeacbef1,0xbd49be48,0x3e793dc9,
 0x3e793ec4,0xbd493dc9,0xbeacbe48,0xbf18bef1,0x3f7d3f80,0x3f673f75,0x3f3e3f55,0x3f043f22,0xbf5cbf6d,0xbf2cbf46,0xbedbbf0e,0xbe16be95,0xbf4ebf35,0xbf71bf62,0xbf80bf7b,0xbf78bf7f,
 0x3f5c3f35,0x3f803f75,0x3f673f7b,0x3f183f46,0x3e163ec4,0xbeacbdc9,0xbf3ebf0e,0xbf78bf62,0xbe790000,0xbf2cbef1,0xbf71bf55,0xbf7dbf7f,0xbf4ebf6d,0xbedbbf22,0x3d49be48,0x3f043e95,
 0x3f043f35,0x3d493e95,0xbedbbe48,0xbf4ebf22,0xbf7dbf6d,0xbf71bf7f,0xbf2cbf55,0xbe79bef1,0xbf78bf80,0xbf3ebf62,0xbeacbf0e,0x3e16bdc9,0x3f183ec4,0x3f673f46,0x3f803f7b,0x3f5c3f75,
 0xbf3ebf6d,0xbe16bef1,0x3f043e48,0x3f713f46,0x3edb3f35,0xbe793dc9,0xbf4ebf0e,0xbf80bf75,0xbd49bec4,0x3f183e95,0x3f783f55,0x3f673f7f,0xbeac0000,0xbf5cbf22,0xbf7dbf7b,0xbf2cbf62,
 0xbf2cbec4,0xbf7dbf62,0xbf5cbf7b,0xbeacbf22,0x3f673f35,0x3f783f7f,0x3f183f55,0xbd493e95,0xbf80bf6d,0xbf4ebf75,0xbe79bf0e,0x3edb3dc9,0x3f713f80,0x3f043f46,0xbe163e48,0xbf3ebef1,
 0xbf67bf80,0xbe79bf22,0x3f183e48,0x3f803f62,0x3f2c3f6d,0xbe163e95,0xbf5cbf0e,0xbf71bf7f,0xbeacbf35,0x3f043dc9,0x3f7d3f55,0x3f3e3f75,0xbd493ec4,0xbf4ebef1,0xbf78bf7b,0xbedbbf46,
 0xbedb0000,0xbf78bf46,0xbf4ebf7b,0xbd49bef1,0x3f3e3ec4,0x3f7d3f75,0x3f043f55,0xbeac3dc9,0xbf71bf35,0xbf5cbf7f,0xbe16bf0e,0x3f2c3e95,0x3f803f6d,0x3f183f62,0xbe793e48,0xbf67bf22,
 0x3e16bec4,0x3f713f22,0x3f3e3f7b,0xbe793e95,0x3f5c3f80,0xbd493ef1,0xbf67bf0e,0xbf4ebf7f,0x3f183f6d,0xbedb3dc9,0xbf80bf55,0xbf04bf62,0xbf78bf35,0xbf2cbf75,0x3eacbe48,0x3f7d3f46,
 0x3f7d3f6d,0x3eac3f46,0xbf2cbe48,0xbf78bf75,0xbf040000,0xbf80bf62,0xbedbbf55,0x3f183dc9,0xbf4ebec4,0xbf67bf7f,0xbd49bf0e,0x3f5c3ef1,0xbe79bf35,0x3f3e3e95,0x3f713f7b,0x3e163f22,
 0x3e163f35,0xbf67bef1,0xbf2cbf7b,0x3f04bdc9,0x3f783f6d,0x3d493f22,0xbf71bf0e,0xbf18bf75,0xbf4ebf80,0x3eacbe95,0x3f803f55,0x3e793f46,0xbf5cbec4,0xbf3ebf7f,0x3edbbe48,0x3f7d3f62,
 0x3f7d3f35,0x3edb3f62,0xbf3ebe48,0xbf5cbf7f,0x3e79bec4,0x3f803f46,0x3eac3f55,0xbf4ebe95,0xbf180000,0xbf71bf75,0x3d49bf0e,0x3f783f22,0x3f043f6d,0xbf2cbdc9,0xbf67bf7b,0x3e16bef1,
 0x3f673ec4,0x3f043f75,0xbf4ebe48,0xbf2cbf7f,0x3f803f35,0x3e163f46,0xbf78bf0e,0xbeacbf62,0x3f713f6d,0xbe793ef1,0xbf7dbf55,0x3d49bf22,0x3f3e3f80,0xbf183dc9,0xbf5cbf7b,0x3edbbe95,
 0x3edb3f6d,0xbf5cbe95,0xbf18bf7b,0x3f3e3dc9,0x3d493f35,0xbf7dbf22,0xbe79bf55,0x3f713ef1,0xbeac3ec4,0xbf78bf62,0x3e16bf0e,0x3f803f46,0xbf2c0000,0xbf4ebf7f,0x3f04be48,0x3f673f75,
 0x3f2c3f80,0xbf4ebdc9,0xbf04bf7b,0x3f673e95,0x3eac3f6d,0xbf78bef1,0xbe16bf55,0x3f803f22,0xbd493f35,0xbf7dbf46,0x3e79bf0e,0x3f713f62,0xbedb3ec4,0xbf5cbf75,0x3f18be48,0x3f3e3f7f,
 0xbf3e0000,0xbf18bf7f,0x3f5c3e48,0x3edb3f75,0xbf71bec4,0xbe79bf62,0x3f7d3f0e,0x3d493f46,0xbf80bf35,0x3e16bf22,0x3f783f55,0xbeac3ef1,0xbf67bf6d,0x3f04be95,0x3f4e3f7b,0xbf2c3dc9,
 0xbf043ec4,0xbf2cbf7f,0x3f673e48,0x3e163f62,0x3f183f80,0xbf71be95,0xbd49bf55,0x3f783f46,0xbe79bf6d,0x3f803f22,0xbeac3f0e,0xbf4ebf75,0xbf7dbf35,0x3edbbef1,0x3f3e3f7b,0xbf5cbdc9,
 0x3f5c3f6d,0xbf3e3dc9,0xbedbbf7b,0x3f7d3ef1,0x3f4e0000,0x3eac3f75,0xbf80bf0e,0x3e79bf22,0xbf78bec4,0x3d49bf46,0x3f713f55,0xbf183e95,0xbe163f35,0xbf67bf62,0x3f2cbe48,0x3f043f7f,
 0x3e79bf35,0x3f3e3f75,0xbf71be48,0x3e16bf46,0x3f4e3f6d,0xbf67bdc9,0x3d49bf55,0x3f5c3f62,0x3f043f80,0xbf80bef1,0x3edbbf0e,0x3f183f7f,0xbf7dbec4,0x3eacbf22,0x3f2c3f7b,0xbf78be95,
 0x3f783f35,0xbf2c3e95,0xbeacbf7b,0x3f7d3f22,0xbf183ec4,0xbedbbf7f,0x3f803f0e,0xbf043ef1,0xbf5c0000,0xbd49bf62,0x3f673f55,0xbf4e3dc9,0xbe16bf6d,0x3f713f46,0xbf3e3e48,0xbe79bf75,
 0xbf80bec4,0x3f18bef1,0x3e793f7b,0xbf67bf46,0x3f713f35,0xbf5c3dc9,0x3e16bf55,0x3f2c3f75,0xbf3ebf6d,0x3f7d3e95,0xbf043f0e,0xbeacbf7f,0x3edb3f80,0xbf78bf22,0x3f4ebe48,0xbd493f62,
 0x3d493f6d,0xbf4ebf62,0x3f783e48,0xbedb3f22,0x3eacbf35,0x3f043f7f,0xbf7dbf0e,0x3f3ebe95,0xbf2c3ec4,0xbe16bf75,0x3f5c3f55,0xbf71bdc9,0x3f670000,0xbe793f46,0xbf18bf7b,0x3f803ef1,
 0xbf710000,0x3f04bf22,0x3e163f7b,0xbf3ebf62,0x3f803ec4,0xbf4e3e95,0x3e79bf55,0x3edb3f7f,0xbf67bf35,0x3f783dc9,0xbf183f0e,0xbd49bf75,0x3f2c3f6d,0xbf7dbef1,0x3f5cbe48,0xbeac3f46,
 0x3eac3f80,0xbf5cbf46,0x3f7d3e48,0xbf2c3ef1,0x3d49bf6d,0x3f183f75,0xbf78bf0e,0x3f67bdc9,0xbedb3f35,0xbe79bf7f,0x3f4e3f55,0xbf80be95,0x3f3ebec4,0xbe163f62,0xbf04bf7b,0x3f713f22,
 0xbf18bf6d,0x3f673f22,0xbf80be48,0x3f5cbe95,0x3f780000,0xbf3e3ef1,0x3eacbf55,0x3e163f7f,0x3f7d3ec4,0xbf713dc9,0x3f2cbf0e,0xbe793f62,0xbf043f35,0x3d49bf75,0x3edb3f7b,0xbf4ebf46,
 0x3f4ebec4,0xbedb3f46,0xbd49bf7b,0x3f043f75,0x3e793f80,0xbf2cbf62,0x3f713f0e,0xbf7dbdc9,0xbe163f6d,0xbeacbf7f,0x3f3e3f55,0xbf78bef1,0xbf5cbf35,0x3f803e95,0xbf673e48,0x3f18bf22,
 0x3f4e3f35,0xbf71bef1,0x3f803e48,0xbf783dc9,0x3f5cbec4,0xbf2c3f22,0x3edbbf55,0xbe163f75,0xbf7d0000,0x3f67be95,0xbf3e3f0e,0x3f04bf46,0xbe793f6d,0xbd49bf7f,0x3eac3f7b,0xbf18bf62,
 0x3f18bf35,0xbeac3f62,0x3d49bf7b,0x3e793f7f,0xbf04bf6d,0x3f3e3f46,0xbf67bf0e,0x3f7d3e95,0x3e163f80,0xbedbbf75,0x3f2c3f55,0xbf5cbf22,0x3f783ec4,0xbf80bdc9,0x3f71be48,0xbf4e3ef1,
 0x3eacbf6d,0xbe793f75,0x3e16bf7b,0xbd493f7f,0x3f2cbf35,0xbf183f46,0x3f04bf55,0xbedb3f62,0x3f67bec4,0xbf5c3ef1,0x3f4ebf0e,0xbf3e3f22,0x3f800000,0xbf7d3dc9,0x3f78be48,0xbf713e95,
 0x3f713ec4,0xbf78be95,0x3f7d3e48,0xbf80bdc9,0x3f3e3f35,0xbf4ebf22,0x3f5c3f0e,0xbf67bef1,0x3edb3f6d,0xbf04bf62,0x3f183f55,0xbf2cbf46,0x3d493f80,0xbe16bf7f,0x3e793f7b,0xbeacbf75,
 0xbf3e0000,0xbf18bf7f,0x3f5c3e48,0x3edb3f75,0xbf71bec4,0xbe79bf62,0x3f7d3f0e,0x3d493f46,0xbf80bf35,0x3e16bf22,0x3f783f55,0xbeac3ef1,0xbf67bf6d,0x3f04be95,0x3f4e3f7b,0xbf2c3dc9,
 0xbf2cbf80,0x3f4e3dc9,0x3f043f7b,0xbf67be95,0xbeacbf6d,0x3f783ef1,0x3e163f55,0xbf80bf22,0x3d49bf35,0x3f7d3f46,0xbe793f0e,0xbf71bf62,0x3edbbec4,0x3f5c3f75,0xbf183e48,0xbf3ebf7f,
 0xbf5cbf6d,0x3f3ebdc9,0x3edb3f7b,0xbf7dbef1,0xbf4e0000,0xbeacbf75,0x3f803f0e,0xbe793f22,0x3f783ec4,0xbd493f46,0xbf71bf55,0x3f18be95,0x3e16bf35,0x3f673f62,0xbf2c3e48,0xbf04bf7f,
 0xbf043ec4,0xbf2cbf7f,0x3f673e48,0x3e163f62,0x3f183f80,0xbf71be95,0xbd49bf55,0x3f783f46,0xbe79bf6d,0x3f803f22,0xbeac3f0e,0xbf4ebf75,0xbf7dbf35,0x3edbbef1,0x3f3e3f7b,0xbf5cbdc9,
 0x3f783f35,0xbf2c3e95,0xbeacbf7b,0x3f7d3f22,0xbf183ec4,0xbedbbf7f,0x3f803f0e,0xbf043ef1,0xbf5c0000,0xbd49bf62,0x3f673f55,0xbf4e3dc9,0xbe16bf6d,0x3f713f46,0xbf3e3e48,0xbe79bf75,
 0xbe793f35,0xbf3ebf75,0x3f713e48,0xbe163f46,0xbf4ebf6d,0x3f673dc9,0xbd493f55,0xbf5cbf62,0xbf04bf80,0x3f803ef1,0xbedb3f0e,0xbf18bf7f,0x3f7d3ec4,0xbeac3f22,0xbf2cbf7b,0x3f783e95,
 0xbd49bf6d,0x3f4e3f62,0xbf78be48,0x3edbbf22,0xbeac3f35,0xbf04bf7f,0x3f7d3f0e,0xbf3e3e95,0x3f2cbec4,0x3e163f75,0xbf5cbf55,0x3f713dc9,0xbf670000,0x3e79bf46,0x3f183f7b,0xbf80bef1,
 0xbf80bec4,0x3f18bef1,0x3e793f7b,0xbf67bf46,0x3f713f35,0xbf5c3dc9,0x3e16bf55,0x3f2c3f75,0xbf3ebf6d,0x3f7d3e95,0xbf043f0e,0xbeacbf7f,0x3edb3f80,0xbf78bf22,0x3f4ebe48,0xbd493f62,
 0xbeacbf80,0x3f5c3f46,0xbf7dbe48,0x3f2cbef1,0xbd493f6d,0xbf18bf75,0x3f783f0e,0xbf673dc9,0x3edbbf35,0x3e793f7f,0xbf4ebf55,0x3f803e95,0xbf3e3ec4,0x3e16bf62,0x3f043f7b,0xbf71bf22,
 0xbf710000,0x3f04bf22,0x3e163f7b,0xbf3ebf62,0x3f803ec4,0xbf4e3e95,0x3e79bf55,0x3edb3f7f,0xbf67bf35,0x3f783dc9,0xbf183f0e,0xbd49bf75,0x3f2c3f6d,0xbf7dbef1,0x3f5cbe48,0xbeac3f46,
 0x3f4ebec4,0xbedb3f46,0xbd49bf7b,0x3f043f75,0x3e793f80,0xbf2cbf62,0x3f713f0e,0xbf7dbdc9,0xbe163f6d,0xbeacbf7f,0x3f3e3f55,0xbf78bef1,0xbf5cbf35,0x3f803e95,0xbf673e48,0x3f18bf22,
 0x3f183f6d,0xbf67bf22,0x3f803e48,0xbf5c3e95,0xbf780000,0x3f3ebef1,0xbeac3f55,0xbe16bf7f,0xbf7dbec4,0x3f71bdc9,0xbf2c3f0e,0x3e79bf62,0x3f04bf35,0xbd493f75,0xbedbbf7b,0x3f4e3f46,
 0xbf183f35,0x3eacbf62,0xbd493f7b,0xbe79bf7f,0x3f043f6d,0xbf3ebf46,0x3f673f0e,0xbf7dbe95,0xbe16bf80,0x3edb3f75,0xbf2cbf55,0x3f5c3f22,0xbf78bec4,0x3f803dc9,0xbf713e48,0x3f4ebef1,
 0x3f4e3f35,0xbf71bef1,0x3f803e48,0xbf783dc9,0x3f5cbec4,0xbf2c3f22,0x3edbbf55,0xbe163f75,0xbf7d0000,0x3f67be95,0xbf3e3f0e,0x3f04bf46,0xbe793f6d,0xbd49bf7f,0x3eac3f7b,0xbf18bf62,
 0x3f713ec4,0xbf78be95,0x3f7d3e48,0xbf80bdc9,0x3f3e3f35,0xbf4ebf22,0x3f5c3f0e,0xbf67bef1,0x3edb3f6d,0xbf04bf62,0x3f183f55,0xbf2cbf46,0x3d493f80,0xbe16bf7f,0x3e793f7b,0xbeacbf75,
 0xbeac3f6d,0x3e79bf75,0xbe163f7b,0x3d49bf7f,0xbf2c3f35,0x3f18bf46,0xbf043f55,0x3edbbf62,0xbf673ec4,0x3f5cbef1,0xbf4e3f0e,0x3f3ebf22,0xbf800000,0x3f7dbdc9,0xbf783e48,0x3f71be95,
 0xbd493f80,0x3e16bf7f,0xbe793f7b,0x3eacbf75,0xbedb3f6d,0x3f04bf62,0xbf183f55,0x3f2cbf46,0xbf3e3f35,0x3f4ebf22,0xbf5c3f0e,0x3f67bef1,0xbf713ec4,0x3f78be95,0xbf7d3e48,0x3f80bdc9,
 0xbf800000,0x3f7d3dc9,0xbf78be48,0x3f713e95,0xbf67bec4,0x3f5c3ef1,0xbf4ebf0e,0x3f3e3f22,0xbf2cbf35,0x3f183f46,0xbf04bf55,0x3edb3f62,0xbeacbf6d,0x3e793f75,0xbe16bf7b,0x3d493f7f,
 0xbf783ec4,0x3f80bdc9,0xbf71be48,0x3f4e3ef1,0xbe163f80,0x3edbbf75,0xbf2c3f55,0x3f5cbf22,0x3f04bf6d,0xbf3e3f46,0x3f67bf0e,0xbf7d3e95,0xbf18bf35,0x3eac3f62,0xbd49bf7b,0xbe793f7f,
 0x3e793f6d,0x3d49bf7f,0xbeac3f7b,0x3f18bf62,0x3f7d0000,0xbf67be95,0x3f3e3f0e,0xbf04bf46,0xbf5cbec4,0x3f2c3f22,0xbedbbf55,0x3e163f75,0xbf4e3f35,0x3f71bef1,0xbf803e48,0x3f783dc9,
 0x3f5cbf35,0xbf803e95,0x3f673e48,0xbf18bf22,0x3e163f6d,0x3eacbf7f,0xbf3e3f55,0x3f78bef1,0xbe793f80,0x3f2cbf62,0xbf713f0e,0x3f7dbdc9,0xbf4ebec4,0x3edb3f46,0x3d49bf7b,0xbf043f75,
 0x3f043f35,0xbd49bf75,0xbedb3f7b,0x3f4ebf46,0xbf7d3ec4,0x3f713dc9,0xbf2cbf0e,0x3e793f62,0xbf780000,0x3f3e3ef1,0xbeacbf55,0xbe163f7f,0x3f18bf6d,0xbf673f22,0x3f80be48,0xbf5cbe95,
 0xbf3ebec4,0x3e163f62,0x3f04bf7b,0xbf713f22,0x3edb3f35,0x3e79bf7f,0xbf4e3f55,0x3f80be95,0xbd49bf6d,0xbf183f75,0x3f78bf0e,0xbf67bdc9,0xbeac3f80,0x3f5cbf46,0xbf7d3e48,0x3f2c3ef1,
 0xbf2c3f6d,0x3f7dbef1,0xbf5cbe48,0x3eac3f46,0x3f67bf35,0xbf783dc9,0x3f183f0e,0x3d49bf75,0xbf803ec4,0x3f4e3e95,0xbe79bf55,0xbedb3f7f,0x3f710000,0xbf04bf22,0xbe163f7b,0x3f3ebf62,
 0xbf670000,0x3e793f46,0x3f18bf7b,0xbf803ef1,0x3f2c3ec4,0x3e16bf75,0xbf5c3f55,0x3f71bdc9,0xbeacbf35,0xbf043f7f,0x3f7dbf0e,0xbf3ebe95,0xbd493f6d,0x3f4ebf62,0xbf783e48,0x3edb3f22,
 0xbedb3f80,0x3f78bf22,0xbf4ebe48,0x3d493f62,0x3f3ebf6d,0xbf7d3e95,0x3f043f0e,0x3eacbf7f,0xbf713f35,0x3f5c3dc9,0xbe16bf55,0xbf2c3f75,0x3f80bec4,0xbf18bef1,0xbe793f7b,0x3f67bf46,
 0x3e16bf6d,0xbf713f46,0x3f3e3e48,0x3e79bf75,0x3f5c0000,0x3d49bf62,0xbf673f55,0x3f4e3dc9,0x3f183ec4,0x3edbbf7f,0xbf803f0e,0x3f043ef1,0xbf783f35,0x3f2c3e95,0x3eacbf7b,0xbf7d3f22,
 0x3f7dbec4,0xbeacbf22,0xbf2c3f7b,0x3f78be95,0xbf043f80,0x3f80bef1,0xbedbbf0e,0xbf183f7f,0xbf4e3f6d,0x3f67bdc9,0xbd49bf55,0xbf5c3f62,0xbe79bf35,0xbf3e3f75,0x3f71be48,0xbe16bf46,
 0x3e163f35,0x3f67bf62,0xbf2cbe48,0xbf043f7f,0x3f78bec4,0xbd49bf46,0xbf713f55,0x3f183e95,0xbf4e0000,0xbeac3f75,0x3f80bf0e,0xbe79bf22,0xbf5c3f6d,0x3f3e3dc9,0x3edbbf7b,0xbf7d3ef1,
 0x3f7dbf35,0xbedbbef1,0xbf3e3f7b,0x3f5cbdc9,0x3e79bf6d,0xbf803f22,0x3eac3f0e,0x3f4ebf75,0xbf183f80,0x3f71be95,0x3d49bf55,0xbf783f46,0x3f043ec4,0x3f2cbf7f,0xbf673e48,0xbe163f62,
 0x3f67bf6d,0xbf04be95,0xbf4e3f7b,0x3f2c3dc9,0x3f80bf35,0xbe16bf22,0xbf783f55,0x3eac3ef1,0x3f71bec4,0x3e79bf62,0xbf7d3f0e,0xbd493f46,0x3f3e0000,0x3f18bf7f,0xbf5c3e48,0xbedb3f75,
 0x3edb3ec4,0x3f5cbf75,0xbf18be48,0xbf3e3f7f,0x3d493f35,0x3f7dbf46,0xbe79bf0e,0xbf713f62,0xbeac3f6d,0x3f78bef1,0x3e16bf55,0xbf803f22,0xbf2c3f80,0x3f4ebdc9,0x3f04bf7b,0xbf673e95,
 0xbf800000,0x3f7d3dc9,0xbf78be48,0x3f713e95,0xbf67bec4,0x3f5c3ef1,0xbf4ebf0e,0x3f3e3f22,0xbf2cbf35,0x3f183f46,0xbf04bf55,0x3edb3f62,0xbeacbf6d,0x3e793f75,0xbe16bf7b,0x3d493f7f,
 0x3d49bf80,0xbe163f7f,0x3e79bf7b,0xbeac3f75,0x3edbbf6d,0xbf043f62,0x3f18bf55,0xbf2c3f46,0x3f3ebf35,0xbf4e3f22,0x3f5cbf0e,0xbf673ef1,0x3f71bec4,0xbf783e95,0x3f7dbe48,0xbf803dc9,
 0xbe79bf6d,0xbd493f7f,0x3eacbf7b,0xbf183f62,0xbf7d0000,0x3f673e95,0xbf3ebf0e,0x3f043f46,0x3f5c3ec4,0xbf2cbf22,0x3edb3f55,0xbe16bf75,0x3f4ebf35,0xbf713ef1,0x3f80be48,0xbf78bdc9,
 0xbf783ec4,0x3f80bdc9,0xbf71be48,0x3f4e3ef1,0xbe163f80,0x3edbbf75,0xbf2c3f55,0x3f5cbf22,0x3f04bf6d,0xbf3e3f46,0x3f67bf0e,0xbf7d3e95,0xbf18bf35,0x3eac3f62,0xbd49bf7b,0xbe793f7f,
 0x3f043f35,0xbd49bf75,0xbedb3f7b,0x3f4ebf46,0xbf7d3ec4,0x3f713dc9,0xbf2cbf0e,0x3e793f62,0xbf780000,0x3f3e3ef1,0xbeacbf55,0xbe163f7f,0x3f18bf6d,0xbf673f22,0x3f80be48,0xbf5cbe95,
 0xbf5c3f35,0x3f80be95,0xbf67be48,0x3f183f22,0xbe16bf6d,0xbeac3f7f,0x3f3ebf55,0xbf783ef1,0x3e79bf80,0xbf2c3f62,0x3f71bf0e,0xbf7d3dc9,0x3f4e3ec4,0xbedbbf46,0xbd493f7b,0x3f04bf75,
 0x3f2cbf6d,0xbf7d3ef1,0x3f5c3e48,0xbeacbf46,0xbf673f35,0x3f78bdc9,0xbf18bf0e,0xbd493f75,0x3f80bec4,0xbf4ebe95,0x3e793f55,0x3edbbf7f,0xbf710000,0x3f043f22,0x3e16bf7b,0xbf3e3f62,
 0xbf3ebec4,0x3e163f62,0x3f04bf7b,0xbf713f22,0x3edb3f35,0x3e79bf7f,0xbf4e3f55,0x3f80be95,0xbd49bf6d,0xbf183f75,0x3f78bf0e,0xbf67bdc9,0xbeac3f80,0x3f5cbf46,0xbf7d3e48,0x3f2c3ef1,
 0x3edbbf80,0xbf783f22,0x3f4e3e48,0xbd49bf62,0xbf3e3f6d,0x3f7dbe95,0xbf04bf0e,0xbeac3f7f,0x3f71bf35,0xbf5cbdc9,0x3e163f55,0x3f2cbf75,0xbf803ec4,0x3f183ef1,0x3e79bf7b,0xbf673f46,
 0xbf670000,0x3e793f46,0x3f18bf7b,0xbf803ef1,0x3f2c3ec4,0x3e16bf75,0xbf5c3f55,0x3f71bdc9,0xbeacbf35,0xbf043f7f,0x3f7dbf0e,0xbf3ebe95,0xbd493f6d,0x3f4ebf62,0xbf783e48,0x3edb3f22,
 0x3f7dbec4,0xbeacbf22,0xbf2c3f7b,0x3f78be95,0xbf043f80,0x3f80bef1,0xbedbbf0e,0xbf183f7f,0xbf4e3f6d,0x3f67bdc9,0xbd49bf55,0xbf5c3f62,0xbe79bf35,0xbf3e3f75,0x3f71be48,0xbe16bf46,
 0xbe163f6d,0x3f71bf46,0xbf3ebe48,0xbe793f75,0xbf5c0000,0xbd493f62,0x3f67bf55,0xbf4ebdc9,0xbf18bec4,0xbedb3f7f,0x3f80bf0e,0xbf04bef1,0x3f78bf35,0xbf2cbe95,0xbeac3f7b,0x3f7dbf22,
 0xbf7d3f35,0x3edb3ef1,0x3f3ebf7b,0xbf5c3dc9,0xbe793f6d,0x3f80bf22,0xbeacbf0e,0xbf4e3f75,0x3f18bf80,0xbf713e95,0xbd493f55,0x3f78bf46,0xbf04bec4,0xbf2c3f7f,0x3f67be48,0x3e16bf62,
 0x3e163f35,0x3f67bf62,0xbf2cbe48,0xbf043f7f,0x3f78bec4,0xbd49bf46,0xbf713f55,0x3f183e95,0xbf4e0000,0xbeac3f75,0x3f80bf0e,0xbe79bf22,0xbf5c3f6d,0x3f3e3dc9,0x3edbbf7b,0xbf7d3ef1,
 0x3edb3ec4,0x3f5cbf75,0xbf18be48,0xbf3e3f7f,0x3d493f35,0x3f7dbf46,0xbe79bf0e,0xbf713f62,0xbeac3f6d,0x3f78bef1,0x3e16bf55,0xbf803f22,0xbf2c3f80,0x3f4ebdc9,0x3f04bf7b,0xbf673e95,
 0xbf673f6d,0x3f043e95,0x3f4ebf7b,0xbf2cbdc9,0xbf803f35,0x3e163f22,0x3f78bf55,0xbeacbef1,0xbf713ec4,0xbe793f62,0x3f7dbf0e,0x3d49bf46,0xbf3e0000,0xbf183f7f,0x3f5cbe48,0x3edbbf75,
 0xbf3e3f80,0x3f183dc9,0x3f5cbf7b,0xbedbbe95,0xbf713f6d,0x3e793ef1,0x3f7dbf55,0xbd49bf22,0xbf803f35,0xbe163f46,0x3f78bf0e,0x3eacbf62,0xbf673ec4,0xbf043f75,0x3f4ebe48,0x3f2cbf7f,
 0xbf2c0000,0xbf4e3f7f,0x3f043e48,0x3f67bf75,0xbeacbec4,0xbf783f62,0x3e163f0e,0x3f80bf46,0x3d49bf35,0xbf7d3f22,0xbe793f55,0x3f71bef1,0x3edbbf6d,0xbf5c3e95,0xbf183f7b,0x3f3ebdc9,
 0xbf5c3ec4,0xbf3e3f7f,0x3edb3e48,0x3f7dbf62,0xbf4e3f80,0x3eac3e95,0x3f80bf55,0x3e79bf46,0x3f78bf6d,0x3d49bf22,0xbf713f0e,0xbf183f75,0x3e16bf35,0xbf673ef1,0xbf2c3f7b,0x3f043dc9,
 0xbf043f6d,0x3f2cbdc9,0x3f67bf7b,0xbe16bef1,0x3f180000,0x3f71bf75,0xbd49bf0e,0xbf783f22,0xbe79bec4,0xbf803f46,0xbeac3f55,0x3f4ebe95,0xbf7d3f35,0xbedb3f62,0x3f3ebe48,0x3f5cbf7f,
 0x3f78bf35,0x3f2cbf75,0xbeacbe48,0xbf7d3f46,0xbf183f6d,0x3edb3dc9,0x3f80bf55,0x3f04bf62,0xbf5c3f80,0x3d493ef1,0x3f67bf0e,0x3f4ebf7f,0xbe16bec4,0xbf713f22,0xbf3e3f7b,0x3e793e95,
 0xbe793f35,0x3f3ebe95,0x3f71bf7b,0x3e16bf22,0xbf4e3ec4,0xbf673f7f,0xbd493f0e,0x3f5cbef1,0xbf040000,0xbf803f62,0xbedb3f55,0x3f18bdc9,0x3f7dbf6d,0x3eacbf46,0xbf2c3e48,0xbf783f75,
 0xbd49bec4,0xbf4e3ef1,0xbf783f7b,0xbedb3f46,0xbeac3f35,0x3f04bdc9,0x3f7dbf55,0x3f3ebf75,0x3f2cbf6d,0xbe16be95,0xbf5c3f0e,0xbf713f7f,0xbf673f80,0xbe793f22,0x3f18be48,0x3f80bf62,
 0xbf803f6d,0xbf183f62,0x3e793e48,0x3f67bf22,0x3f71bf35,0x3f5cbf7f,0x3e16bf0e,0xbf2c3e95,0xbf3e3ec4,0xbf7d3f75,0xbf043f55,0x3eac3dc9,0x3edb0000,0x3f78bf46,0x3f4ebf7b,0x3d49bef1,
 0xbeac0000,0xbf5c3f22,0xbf7d3f7b,0xbf2c3f62,0xbd493ec4,0x3f18be95,0x3f78bf55,0x3f67bf7f,0x3edbbf35,0xbe79bdc9,0xbf4e3f0e,0xbf803f75,0xbf3e3f6d,0xbe163ef1,0x3f04be48,0x3f71bf46,
 0xbf713f80,0xbf043f46,0x3e163e48,0x3f3ebef1,0x3f80bf6d,0x3f4ebf75,0x3e79bf0e,0xbedb3dc9,0xbf673f35,0xbf783f7f,0xbf183f55,0x3d493e95,0x3f2cbec4,0x3f7dbf62,0x3f5cbf7b,0x3eacbf22,
 0x3f4ebf6d,0x3edbbf22,0xbd49be48,0xbf043e95,0x3e790000,0x3f2cbef1,0x3f71bf55,0x3f7dbf7f,0xbe163ec4,0x3eacbdc9,0x3f3ebf0e,0x3f78bf62,0xbf5c3f35,0xbf803f75,0xbf673f7b,0xbf183f46,
 0x3f18bec4,0x3f67bf46,0x3f80bf7b,0x3f5cbf75,0xbf783f80,0xbf3e3f62,0xbeac3f0e,0x3e163dc9,0xbf7d3f6d,0xbf713f7f,0xbf2c3f55,0xbe793ef1,0x3f04bf35,0x3d49be95,0xbedb3e48,0xbf4e3f22,
 0xbf183f35,0xbeac3ef1,0xbd493e48,0x3e79bdc9,0x3f04bec4,0x3f3ebf22,0x3f67bf55,0x3f7dbf75,0xbe160000,0xbedb3e95,0xbf2c3f0e,0xbf5c3f46,0xbf783f6d,0xbf803f7f,0xbf713f7b,0xbf4e3f62,
 0x3f4ebf35,0x3f71bf62,0x3f80bf7b,0x3f78bf7f,0x3f5cbf6d,0x3f2cbf46,0x3edbbf0e,0x3e16be95,0xbf7d3f80,0xbf673f75,0xbf3e3f55,0xbf043f22,0xbe793ec4,0x3d493dc9,0x3eacbe48,0x3f18bef1,
 0x3f71bf6d,0x3f78bf75,0x3f7dbf7b,0x3f80bf7f,0x3f3ebf35,0x3f4ebf46,0x3f5cbf55,0x3f67bf62,0x3edbbec4,0x3f04bef1,0x3f18bf0e,0x3f2cbf22,0x3d490000,0x3e16bdc9,0x3e79be48,0x3eacbe95,
 0xbeac3ec4,0xbe793e95,0xbe163e48,0xbd493dc9,0xbf2c3f35,0xbf183f22,0xbf043f0e,0xbedb3ef1,0xbf673f6d,0xbf5c3f62,0xbf4e3f55,0xbf3e3f46,0xbf803f80,0xbf7d3f7f,0xbf783f7b,0xbf713f75,
 0xbf2c0000,0xbf4e3f7f,0x3f043e48,0x3f67bf75,0xbeacbec4,0xbf783f62,0x3e163f0e,0x3f80bf46,0x3d49bf35,0xbf7d3f22,0xbe793f55,0x3f71bef1,0x3edbbf6d,0xbf5c3e95,0xbf183f7b,0x3f3ebdc9,
 0x3f3ebf80,0xbf18bdc9,0xbf5c3f7b,0x3edb3e95,0x3f71bf6d,0xbe79bef1,0xbf7d3f55,0x3d493f22,0x3f80bf35,0x3e16bf46,0xbf783f0e,0xbeac3f62,0x3f67bec4,0x3f04bf75,0xbf4e3e48,0xbf2c3f7f,
 0x3f04bf6d,0xbf2c3dc9,0xbf673f7b,0x3e163ef1,0xbf180000,0xbf713f75,0x3d493f0e,0x3f78bf22,0x3e793ec4,0x3f80bf46,0x3eacbf55,0xbf4e3e95,0x3f7dbf35,0x3edbbf62,0xbf3e3e48,0xbf5c3f7f,
 0xbf5c3ec4,0xbf3e3f7f,0x3edb3e48,0x3f7dbf62,0xbf4e3f80,0x3eac3e95,0x3f80bf55,0x3e79bf46,0x3f78bf6d,0x3d49bf22,0xbf713f0e,0xbf183f75,0x3e16bf35,0xbf673ef1,0xbf2c3f7b,0x3f043dc9,
 0xbe793f35,0x3f3ebe95,0x3f71bf7b,0x3e16bf22,0xbf4e3ec4,0xbf673f7f,0xbd493f0e,0x3f5cbef1,0xbf040000,0xbf803f62,0xbedb3f55,0x3f18bdc9,0x3f7dbf6d,0x3eacbf46,0xbf2c3e48,0xbf783f75,
 0xbf783f35,0xbf2c3f75,0x3eac3e48,0x3f7dbf46,0x3f18bf6d,0xbedbbdc9,0xbf803f55,0xbf043f62,0x3f5cbf80,0xbd49bef1,0xbf673f0e,0xbf4e3f7f,0x3e163ec4,0x3f71bf22,0x3f3ebf7b,0xbe79be95,
 0x3f80bf6d,0x3f18bf62,0xbe79be48,0xbf673f22,0xbf713f35,0xbf5c3f7f,0xbe163f0e,0x3f2cbe95,0x3f3ebec4,0x3f7dbf75,0x3f04bf55,0xbeacbdc9,0xbedb0000,0xbf783f46,0xbf4e3f7b,0xbd493ef1,
 0xbd49bec4,0xbf4e3ef1,0xbf783f7b,0xbedb3f46,0xbeac3f35,0x3f04bdc9,0x3f7dbf55,0x3f3ebf75,0x3f2cbf6d,0xbe16be95,0xbf5c3f0e,0xbf713f7f,0xbf673f80,0xbe793f22,0x3f18be48,0x3f80bf62,
 0x3f71bf80,0x3f04bf46,0xbe16be48,0xbf3e3ef1,0xbf803f6d,0xbf4e3f75,0xbe793f0e,0x3edbbdc9,0x3f67bf35,0x3f78bf7f,0x3f18bf55,0xbd49be95,0xbf2c3ec4,0xbf7d3f62,0xbf5c3f7b,0xbeac3f22,
 0xbeac0000,0xbf5c3f22,0xbf7d3f7b,0xbf2c3f62,0xbd493ec4,0x3f18be95,0x3f78bf55,0x3f67bf7f,0x3edbbf35,0xbe79bdc9,0xbf4e3f0e,0xbf803f75,0xbf3e3f6d,0xbe163ef1,0x3f04be48,0x3f71bf46,
 0x3f18bec4,0x3f67bf46,0x3f80bf7b,0x3f5cbf75,0xbf783f80,0xbf3e3f62,0xbeac3f0e,0x3e163dc9,0xbf7d3f6d,0xbf713f7f,0xbf2c3f55,0xbe793ef1,0x3f04bf35,0x3d49be95,0xbedb3e48,0xbf4e3f22,
 0xbf4e3f6d,0xbedb3f22,0x3d493e48,0x3f04be95,0xbe790000,0xbf2c3ef1,0xbf713f55,0xbf7d3f7f,0x3e16bec4,0xbeac3dc9,0xbf3e3f0e,0xbf783f62,0x3f5cbf35,0x3f80bf75,0x3f67bf7b,0x3f18bf46,
 0xbf4e3f35,0xbf713f62,0xbf803f7b,0xbf783f7f,0xbf5c3f6d,0xbf2c3f46,0xbedb3f0e,0xbe163e95,0x3f7dbf80,0x3f67bf75,0x3f3ebf55,0x3f04bf22,0x3e79bec4,0xbd49bdc9,0xbeac3e48,0xbf183ef1,
 0xbf183f35,0xbeac3ef1,0xbd493e48,0x3e79bdc9,0x3f04bec4,0x3f3ebf22,0x3f67bf55,0x3f7dbf75,0xbe160000,0xbedb3e95,0xbf2c3f0e,0xbf5c3f46,0xbf783f6d,0xbf803f7f,0xbf713f7b,0xbf4e3f62,
 0xbeac3ec4,0xbe793e95,0xbe163e48,0xbd493dc9,0xbf2c3f35,0xbf183f22,0xbf043f0e,0xbedb3ef1,0xbf673f6d,0xbf5c3f62,0xbf4e3f55,0xbf3e3f46,0xbf803f80,0xbf7d3f7f,0xbf783f7b,0xbf713f75,
 0xbf713f6d,0xbf783f75,0xbf7d3f7b,0xbf803f7f,0xbf3e3f35,0xbf4e3f46,0xbf5c3f55,0xbf673f62,0xbedb3ec4,0xbf043ef1,0xbf183f0e,0xbf2c3f22,0xbd490000,0xbe163dc9,0xbe793e48,0xbeac3e95,
};
__device__ __align__(128) const uint32_t g_Gimg[1792] = {
 0x00003d00,0x00003d00,0x00003d00,0x00003d00,0x00003d00,0x00003d00,0x00003d00,0x00003d00,0x00003d00,0x00003d00,0x00003d00,0x00003d00,0x00003d00,0x00003d00,0x00003d00,0x00003d00,
 0x00003d00,0x00003d00,0x00003d00,0x00003d00,0x00003d00,0x00003d00,0x00003d00,0x00003d00,0x00003d00,0x00003d00,0x00003d00,0x00003d00,0x00003d00,0x00003d00,0x00003d00,0x00003d00,
 0xbc5b3ce7,0xbc843cdc,0xbc983cce,0xbcac3cbe,0xbac93d00,0xbb963cfd,0xbbf93cf8,0xbc2c3cf1,0xbcf13c2c,0xbcf83bf9,0xbcfd3b96,0xbd003ac9,0xbcbe3cac,0xbcce3c98,0xbcdc3c84,0xbce73c5b,
 0xbce7bc5b,0xbcdcbc84,0xbccebc98,0xbcbebcac,0xbd00bac9,0xbcfdbb96,0xbcf8bbf9,0xbcf1bc2c,0xbc2cbcf1,0xbbf9bcf8,0xbb96bcfd,0xbac9bd00,0xbcacbcbe,0xbc98bcce,0xbc84bcdc,0xbc5bbce7,
 0xbcffbb49,0xbcf5bc15,0xbce2bc71,0xbcc6bca2,0xbca2bcc6,0xbc71bce2,0xbc15bcf5,0xbb49bcff,0xbb493cff,0xbc153cf5,0xbc713ce2,0xbca23cc6,0xbcc63ca2,0xbce23c71,0xbcf53c15,0xbcff3b49,
 0x3cff3b49,0x3cf53c15,0x3ce23c71,0x3cc63ca2,0x3ca23cc6,0x3c713ce2,0x3c153cf5,0x3b493cff,0x3b49bcff,0x3c15bcf5,0x3c71bce2,0x3ca2bcc6,0x3cc6bca2,0x3ce2bc71,0x3cf5bc15,0x3cffbb49,
 0x3c84bcdc,0x3cbebcac,0x3ce7bc5b,0x3cfdbb96,0xbc98bcce,0xbc2cbcf1,0xbac9bd00,0x3bf9bcf8,0xbcf83bf9,0xbd00bac9,0xbcf1bc2c,0xbccebc98,0xbb963cfd,0xbc5b3ce7,0xbcac3cbe,0xbcdc3c84,
 0xbcdcbc84,0xbcacbcbe,0xbc5bbce7,0xbb96bcfd,0xbcce3c98,0xbcf13c2c,0xbd003ac9,0xbcf8bbf9,0x3bf93cf8,0xbac93d00,0xbc2c3cf1,0xbc983cce,0x3cfd3b96,0x3ce73c5b,0x3cbe3cac,0x3c843cdc,
 0xbbc83cfb,0xbc8e3cd5,0xbcd53c8e,0xbcfb3bc8,0xbcfbbbc8,0xbcd5bc8e,0xbc8ebcd5,0xbbc8bcfb,0x3bc8bcfb,0x3c8ebcd5,0x3cd5bc8e,0x3cfbbbc8,0x3cfb3bc8,0x3cd53c8e,0x3c8e3cd5,0x3bc83cfb,
 0xbbc83cfb,0xbc8e3cd5,0xbcd53c8e,0xbcfb3bc8,0xbcfbbbc8,0xbcd5bc8e,0xbc8ebcd5,0xbbc8bcfb,0x3bc8bcfb,0x3c8ebcd5,0x3cd5bc8e,0x3cfbbbc8,0x3cfb3bc8,0x3cd53c8e,0x3c8e3cd5,0x3bc83cfb,
 0x3c98bcce,0x3ce7bc5b,0x3d003ac9,0x3cdc3c84,0xbcf8bbf9,0xbcbebcac,0xbc2cbcf1,0x3b96bcfd,0xbcfd3b96,0xbcf1bc2c,0xbcacbcbe,0xbbf9bcf8,0x3c843cdc,0x3ac93d00,0xbc5b3ce7,0xbcce3c98,
 0xbccebc98,0xbc5bbce7,0x3ac9bd00,0x3c84bcdc,0xbbf93cf8,0xbcac3cbe,0xbcf13c2c,0xbcfdbb96,0x3b963cfd,0xbc2c3cf1,0xbcbe3cac,0xbcf83bf9,0x3cdcbc84,0x3d00bac9,0x3ce73c5b,0x3c983cce,
 0xbcf5bc15,0xbca2bcc6,0xbb49bcff,0x3c71bce2,0x3ce2bc71,0x3cff3b49,0x3cc63ca2,0x3c153cf5,0x3c15bcf5,0x3cc6bca2,0x3cffbb49,0x3ce23c71,0x3c713ce2,0xbb493cff,0xbca23cc6,0xbcf53c15,
 0x3cf53c15,0x3ca23cc6,0x3b493cff,0xbc713ce2,0xbce23c71,0xbcffbb49,0xbcc6bca2,0xbc15bcf5,0xbc153cf5,0xbcc63ca2,0xbcff3b49,0xbce2bc71,0xbc71bce2,0x3b49bcff,0x3ca2bcc6,0x3cf5bc15,
 0xbcac3cbe,0xbcfd3b96,0xbcdcbc84,0xbc2cbcf1,0x3ce7bc5b,0x3cf83bf9,0x3c983cce,0xbac93d00,0xbd003ac9,0xbccebc98,0xbbf9bcf8,0x3c5bbce7,0x3cf13c2c,0x3c843cdc,0xbb963cfd,0xbcbe3cac,
 0xbcbebcac,0xbb96bcfd,0x3c84bcdc,0x3cf1bc2c,0x3c5b3ce7,0xbbf93cf8,0xbcce3c98,0xbd00bac9,0xbac9bd00,0x3c98bcce,0x3cf8bbf9,0x3ce73c5b,0xbc2c3cf1,0xbcdc3c84,0xbcfdbb96,0xbcacbcbe,
 0xbc443ced,0xbced3c44,0xbcedbc44,0xbc44bced,0x3c44bced,0x3cedbc44,0x3ced3c44,0x3c443ced,0xbc443ced,0xbced3c44,0xbcedbc44,0xbc44bced,0x3c44bced,0x3cedbc44,0x3ced3c44,0x3c443ced,
 0xbc443ced,0xbced3c44,0xbcedbc44,0xbc44bced,0x3c44bced,0x3cedbc44,0x3ced3c44,0x3c443ced,0xbc443ced,0xbced3c44,0xbcedbc44,0xbc44bced,0x3c44bced,0x3cedbc44,0x3ced3c44,0x3c443ced,
 0x3cbebcac,0x3cfd3b96,0x3c843cdc,0xbc2c3cf1,0xbc5b3ce7,0xbcf83bf9,0xbccebc98,0xbac9bd00,0x3d003ac9,0x3c983cce,0xbbf93cf8,0xbce73c5b,0xbcf13c2c,0xbcdcbc84,0xbb96bcfd,0x3cacbcbe,
 0x3cac3cbe,0xbb963cfd,0xbcdc3c84,0xbcf1bc2c,0xbce7bc5b,0xbbf9bcf8,0x3c98bcce,0x3d00bac9,0xbac93d00,0xbcce3c98,0xbcf8bbf9,0xbc5bbce7,0xbc2cbcf1,0x3c84bcdc,0x3cfdbb96,0x3cbe3cac,
 0xbce2bc71,0xbb49bcff,0x3cc6bca2,0x3cf53c15,0x3c153cf5,0xbca23cc6,0xbcffbb49,0xbc71bce2,0xbc713ce2,0xbcff3b49,0xbca2bcc6,0x3c15bcf5,0x3cf5bc15,0x3cc63ca2,0xbb493cff,0xbce23c71,
 0x3ce23c71,0x3b493cff,0xbcc63ca2,0xbcf5bc15,0xbc15bcf5,0x3ca2bcc6,0x3cff3b49,0x3c713ce2,0x3c71bce2,0x3cffbb49,0x3ca23cc6,0xbc153cf5,0xbcf53c15,0xbcc6bca2,0x3b49bcff,0x3ce2bc71,
 0xbcce3c98,0xbce7bc5b,0xbac9bd00,0x3cdcbc84,0xbbf9bcf8,0x3cbebcac,0x3cf13c2c,0x3b963cfd,0x3cfd3b96,0x3c2c3cf1,0xbcac3cbe,0xbcf8bbf9,0xbc843cdc,0xbd00bac9,0xbc5bbce7,0x3c98bcce,
 0x3c983cce,0xbc5b3ce7,0xbd003ac9,0xbc84bcdc,0xbcf83bf9,0xbcacbcbe,0x3c2cbcf1,0x3cfdbb96,0x3b96bcfd,0x3cf1bc2c,0x3cbe3cac,0xbbf93cf8,0x3cdc3c84,0xbac93d00,0xbce73c5b,0xbccebc98,
 0xbc8e3cd5,0xbcfbbbc8,0xbbc8bcfb,0x3cd5bc8e,0x3cd53c8e,0xbbc83cfb,0xbcfb3bc8,0xbc8ebcd5,0x3c8ebcd5,0x3cfb3bc8,0x3bc83cfb,0xbcd53c8e,0xbcd5bc8e,0x3bc8bcfb,0x3cfbbbc8,0x3c8e3cd5,
 0xbc8e3cd5,0xbcfbbbc8,0xbbc8bcfb,0x3cd5bc8e,0x3cd53c8e,0xbbc83cfb,0xbcfb3bc8,0xbc8ebcd5,0x3c8ebcd5,0x3cfb3bc8,0x3bc83cfb,0xbcd53c8e,0xbcd5bc8e,0x3bc8bcfb,0x3cfbbbc8,0x3c8e3cd5,
 0xbcdc3c84,0xbcbebcac,0x3c5bbce7,0x3cfd3b96,0xbccebc98,0x3c2cbcf1,0x3d003ac9,0x3bf93cf8,0x3cf83bf9,0x3ac93d00,0xbcf13c2c,0xbc98bcce,0x3b963cfd,0xbce73c5b,0xbcacbcbe,0x3c84bcdc,
 0x3c843cdc,0xbcac3cbe,0xbce7bc5b,0x3b96bcfd,0xbc983cce,0xbcf1bc2c,0x3ac9bd00,0x3cf8bbf9,0x3bf9bcf8,0x3d00bac9,0x3c2c3cf1,0xbcce3c98,0x3cfdbb96,0x3c5b3ce7,0xbcbe3cac,0xbcdcbc84,
 0xbcc6bca2,0x3c71bce2,0x3cf53c15,0xbb493cff,0xbcff3b49,0xbc15bcf5,0x3ce2bc71,0x3ca23cc6,0x3ca2bcc6,0x3ce23c71,0xbc153cf5,0xbcffbb49,0xbb49bcff,0x3cf5bc15,0x3c713ce2,0xbcc63ca2,
 0x3cc63ca2,0xbc713ce2,0xbcf5bc15,0x3b49bcff,0x3cffbb49,0x3c153cf5,0xbce23c71,0xbca2bcc6,0xbca23cc6,0xbce2bc71,0x3c15bcf5,0x3cff3b49,0x3b493cff,0xbcf53c15,0xbc71bce2,0x3cc6bca2,
 0x3ce7bc5b,0x3c843cdc,0xbcce3c98,0xbcacbcbe,0x3d00bac9,0x3b963cfd,0xbcf83bf9,0xbc2cbcf1,0x3cf13c2c,0xbbf93cf8,0xbcfdbb96,0x3ac9bd00,0x3cbe3cac,0xbc983cce,0xbcdcbc84,0x3c5bbce7,
 0x3c5b3ce7,0xbcdc3c84,0xbc98bcce,0x3cbebcac,0x3ac93d00,0xbcfd3b96,0xbbf9bcf8,0x3cf1bc2c,0xbc2c3cf1,0xbcf8bbf9,0x3b96bcfd,0x3d003ac9,0xbcac3cbe,0xbccebc98,0x3c84bcdc,0x3ce73c5b,
 0xbcb53cb5,0xbcb5bcb5,0x3cb5bcb5,0x3cb53cb5,0xbcb53cb5,0xbcb5bcb5,0x3cb5bcb5,0x3cb53cb5,0xbcb53cb5,0xbcb5bcb5,0x3cb5bcb5,0x3cb53cb5,0xbcb53cb5,0xbcb5bcb5,0x3cb5bcb5,0x3cb53cb5,
 0xbcb53cb5,0xbcb5bcb5,0x3cb5bcb5,0x3cb53cb5,0xbcb53cb5,0xbcb5bcb5,0x3cb5bcb5,0x3cb53cb5,0xbcb53cb5,0xbcb5bcb5,0x3cb5bcb5,0x3cb53cb5,0xbcb53cb5,0xbcb5bcb5,0x3cb5bcb5,0x3cb53cb5,
 0xbcf13c2c,0xbbf9bcf8,0x3cfdbb96,0x3ac93d00,0xbcbe3cac,0xbc98bcce,0x3cdcbc84,0x3c5b3ce7,0xbce7bc5b,0x3c84bcdc,0x3cce3c98,0xbcac3cbe,0xbd00bac9,0x3b96bcfd,0x3cf83bf9,0xbc2c3cf1,
 0xbc2cbcf1,0x3cf8bbf9,0x3b963cfd,0xbd003ac9,0xbcacbcbe,0x3ccebc98,0x3c843cdc,0xbce73c5b,0x3c5bbce7,0x3cdc3c84,0xbc983cce,0xbcbebcac,0x3ac9bd00,0x3cfd3b96,0xbbf93cf8,0xbcf1bc2c,
 0xbca2bcc6,0x3ce2bc71,0x3c153cf5,0xbcff3b49,0x3b49bcff,0x3cf53c15,0xbc713ce2,0xbcc6bca2,0xbcc63ca2,0xbc71bce2,0x3cf5bc15,0x3b493cff,0xbcffbb49,0x3c15bcf5,0x3ce23c71,0xbca23cc6,
 0x3ca23cc6,0xbce23c71,0xbc15bcf5,0x3cffbb49,0xbb493cff,0xbcf5bc15,0x3c71bce2,0x3cc63ca2,0x3cc6bca2,0x3c713ce2,0xbcf53c15,0xbb49bcff,0x3cff3b49,0xbc153cf5,0xbce2bc71,0x3ca2bcc6,
 0x3cf8bbf9,0xbac93d00,0xbcf1bc2c,0x3c98bcce,0x3b96bcfd,0x3ce73c5b,0xbcac3cbe,0xbc84bcdc,0xbcdcbc84,0x3cbebcac,0x3c5b3ce7,0xbcfd3b96,0xbcce3c98,0xbc2cbcf1,0x3d00bac9,0xbbf93cf8,
 0xbbf9bcf8,0x3d003ac9,0xbc2c3cf1,0xbccebc98,0xbcfdbb96,0x3c5bbce7,0x3cbe3cac,0xbcdc3c84,0xbc843cdc,0xbcacbcbe,0x3ce7bc5b,0x3b963cfd,0x3c983cce,0xbcf13c2c,0xbac9bd00,0x3cf83bf9,
 0xbcd53c8e,0xbbc8bcfb,0x3cfb3bc8,0xbc8e3cd5,0xbc8ebcd5,0x3cfbbbc8,0xbbc83cfb,0xbcd5bc8e,0x3cd5bc8e,0x3bc83cfb,0xbcfbbbc8,0x3c8ebcd5,0x3c8e3cd5,0xbcfb3bc8,0x3bc8bcfb,0x3cd53c8e,
 0xbcd53c8e,0xbbc8bcfb,0x3cfb3bc8,0xbc8e3cd5,0xbc8ebcd5,0x3cfbbbc8,0xbbc83cfb,0xbcd5bc8e,0x3cd5bc8e,0x3bc83cfb,0xbcfbbbc8,0x3c8ebcd5,0x3c8e3cd5,0xbcfb3bc8,0x3bc8bcfb,0x3cd53c8e,
 0x3cfdbb96,0xbc2c3cf1,0xbcacbcbe,0x3cf8bbf9,0xbc84bcdc,0x3d00bac9,0xbc5b3ce7,0xbc98bcce,0xbccebc98,0x3ce7bc5b,0xbac93d00,0xbcdcbc84,0xbbf93cf8,0xbcbebcac,0x3cf1bc2c,0xbb963cfd,
 0xbb96bcfd,0x3cf13c2c,0xbcbe3cac,0xbbf9bcf8,0xbcdc3c84,0xbac9bd00,0x3ce73c5b,0xbcce3c98,0xbc983cce,0xbc5bbce7,0x3d003ac9,0xbc843cdc,0x3cf83bf9,0xbcac3cbe,0xbc2cbcf1,0x3cfd3b96,
 0xbc71bce2,0x3cff3b49,0xbca23cc6,0xbc15bcf5,0x3cf53c15,0xbcc63ca2,0xbb49bcff,0x3ce23c71,0x3ce2bc71,0xbb493cff,0xbcc6bca2,0x3cf5bc15,0xbc153cf5,0xbca2bcc6,0x3cffbb49,0xbc713ce2,
 0x3c713ce2,0xbcffbb49,0x3ca2bcc6,0x3c153cf5,0xbcf5bc15,0x3cc6bca2,0x3b493cff,0xbce2bc71,0xbce23c71,0x3b49bcff,0x3cc63ca2,0xbcf53c15,0x3c15bcf5,0x3ca23cc6,0xbcff3b49,0x3c71bce2,
 0xbd003ac9,0x3c98bcce,0x3bf93cf8,0xbce7bc5b,0x3cf13c2c,0xbcdc3c84,0x3b96bcfd,0x3cac3cbe,0xbcbebcac,0x3cfdbb96,0xbc843cdc,0xbc2cbcf1,0x3c5b3ce7,0xbcf8bbf9,0x3ccebc98,0xbac93d00,
 0xbac9bd00,0x3cce3c98,0xbcf83bf9,0x3c5bbce7,0xbc2c3cf1,0xbc84bcdc,0x3cfd3b96,0xbcbe3cac,0x3cacbcbe,0x3b963cfd,0xbcdcbc84,0x3cf1bc2c,0xbce73c5b,0x3bf9bcf8,0x3c983cce,0xbd00bac9,
 0xbced3c44,0x3c44bced,0x3c443ced,0xbcedbc44,0x3cedbc44,0xbc443ced,0xbc44bced,0x3ced3c44,0xbced3c44,0x3c44bced,0x3c443ced,0xbcedbc44,0x3cedbc44,0xbc443ced,0xbc44bced,0x3ced3c44,
 0xbced3c44,0x3c44bced,0x3c443ced,0xbcedbc44,0x3cedbc44,0xbc443ced,0xbc44bced,0x3ced3c44,0xbced3c44,0x3c44bced,0x3c443ced,0xbcedbc44,0x3cedbc44,0xbc443ced,0xbc44bced,0x3ced3c44,
 0x3d003ac9,0xbcce3c98,0x3bf9bcf8,0x3c5b3ce7,0xbcf13c2c,0x3c84bcdc,0x3b963cfd,0xbcbebcac,0x3cac3cbe,0xbcfdbb96,0x3cdcbc84,0xbc2c3cf1,0xbce7bc5b,0x3cf8bbf9,0xbc983cce,0xbac9bd00,
 0xbac93d00,0xbc98bcce,0x3cf83bf9,0xbce73c5b,0xbc2cbcf1,0x3cdc3c84,0xbcfd3b96,0x3cacbcbe,0xbcbe3cac,0x3b96bcfd,0x3c843cdc,0xbcf1bc2c,0x3c5bbce7,0x3bf93cf8,0xbccebc98,0x3d00bac9,
 0xbc15bcf5,0x3cc63ca2,0xbcffbb49,0x3ce2bc71,0xbc713ce2,0xbb49bcff,0x3ca23cc6,0xbcf5bc15,0xbcf53c15,0x3ca2bcc6,0xbb493cff,0xbc71bce2,0x3ce23c71,0xbcff3b49,0x3cc6bca2,0xbc153cf5,
 0x3c153cf5,0xbcc6bca2,0x3cff3b49,0xbce23c71,0x3c71bce2,0x3b493cff,0xbca2bcc6,0x3cf53c15,0x3cf5bc15,0xbca23cc6,0x3b49bcff,0x3c713ce2,0xbce2bc71,0x3cffbb49,0xbcc63ca2,0x3c15bcf5,
 0xbcfdbb96,0x3cf1bc2c,0xbcac3cbe,0x3bf9bcf8,0x3c84bcdc,0xbac93d00,0xbc5bbce7,0x3cce3c98,0x3c983cce,0xbce7bc5b,0x3d00bac9,0xbcdc3c84,0xbcf83bf9,0x3cbebcac,0xbc2c3cf1,0xbb96bcfd,
 0xbb963cfd,0xbc2cbcf1,0x3cbe3cac,0xbcf8bbf9,0xbcdcbc84,0x3d003ac9,0xbce73c5b,0x3c98bcce,0x3ccebc98,0xbc5b3ce7,0xbac9bd00,0x3c843cdc,0x3bf93cf8,0xbcacbcbe,0x3cf13c2c,0xbcfd3b96,
 0xbcfb3bc8,0x3cd5bc8e,0xbc8e3cd5,0x3bc8bcfb,0x3bc83cfb,0xbc8ebcd5,0x3cd53c8e,0xbcfbbbc8,0x3cfbbbc8,0xbcd53c8e,0x3c8ebcd5,0xbbc83cfb,0xbbc8bcfb,0x3c8e3cd5,0xbcd5bc8e,0x3cfb3bc8,
 0xbcfb3bc8,0x3cd5bc8e,0xbc8e3cd5,0x3bc8bcfb,0x3bc83cfb,0xbc8ebcd5,0x3cd53c8e,0xbcfbbbc8,0x3cfbbbc8,0xbcd53c8e,0x3c8ebcd5,0xbbc83cfb,0xbbc8bcfb,0x3c8e3cd5,0xbcd5bc8e,0x3cfb3bc8,
 0xbcf8bbf9,0x3d00bac9,0xbcf13c2c,0x3ccebc98,0xbb96bcfd,0x3c5b3ce7,0xbcacbcbe,0x3cdc3c84,0x3c843cdc,0xbcbebcac,0x3ce73c5b,0xbcfdbb96,0xbc983cce,0x3c2cbcf1,0xbac93d00,0xbbf9bcf8,
 0xbbf93cf8,0xbac9bd00,0x3c2c3cf1,0xbc98bcce,0xbcfd3b96,0x3ce7bc5b,0xbcbe3cac,0x3c84bcdc,0x3cdcbc84,0xbcac3cbe,0x3c5bbce7,0xbb963cfd,0x3cce3c98,0xbcf1bc2c,0x3d003ac9,0xbcf83bf9,
 0xbb49bcff,0x3c153cf5,0xbc71bce2,0x3ca23cc6,0xbcc6bca2,0x3ce23c71,0xbcf5bc15,0x3cff3b49,0x3cffbb49,0xbcf53c15,0x3ce2bc71,0xbcc63ca2,0x3ca2bcc6,0xbc713ce2,0x3c15bcf5,0xbb493cff,
 0x3b493cff,0xbc15bcf5,0x3c713ce2,0xbca2bcc6,0x3cc63ca2,0xbce2bc71,0x3cf53c15,0xbcffbb49,0xbcff3b49,0x3cf5bc15,0xbce23c71,0x3cc6bca2,0xbca23cc6,0x3c71bce2,0xbc153cf5,0x3b49bcff,
 0x3cf13c2c,0xbcf8bbf9,0x3cfd3b96,0xbd00bac9,0x3cbe3cac,0xbccebc98,0x3cdc3c84,0xbce7bc5b,0x3c5b3ce7,0xbc84bcdc,0x3c983cce,0xbcacbcbe,0x3ac93d00,0xbb96bcfd,0x3bf93cf8,0xbc2cbcf1,
 0xbc2c3cf1,0x3bf9bcf8,0xbb963cfd,0x3ac9bd00,0xbcac3cbe,0x3c98bcce,0xbc843cdc,0x3c5bbce7,0xbce73c5b,0x3cdcbc84,0xbcce3c98,0x3cbebcac,0xbd003ac9,0x3cfdbb96,0xbcf83bf9,0x3cf1bc2c,
 0xbd000000,0x3d000000,0xbd000000,0x3d000000,0xbd000000,0x3d000000,0xbd000000,0x3d000000,0xbd000000,0x3d000000,0xbd000000,0x3d000000,0xbd000000,0x3d000000,0xbd000000,0x3d000000,
 0xbd000000,0x3d000000,0xbd000000,0x3d000000,0xbd000000,0x3d000000,0xbd000000,0x3d000000,0xbd000000,0x3d000000,0xbd000000,0x3d000000,0xbd000000,0x3d000000,0xbd000000,0x3d000000,
 0xbce7bc5b,0x3cdc3c84,0xbccebc98,0x3cbe3cac,0xbd00bac9,0x3cfd3b96,0xbcf8bbf9,0x3cf13c2c,0xbc2cbcf1,0x3bf93cf8,0xbb96bcfd,0x3ac93d00,0xbcacbcbe,0x3c983cce,0xbc84bcdc,0x3c5b3ce7,
 0x3c5bbce7,0xbc843cdc,0x3c98bcce,0xbcac3cbe,0x3ac9bd00,0xbb963cfd,0x3bf9bcf8,0xbc2c3cf1,0x3cf1bc2c,0xbcf83bf9,0x3cfdbb96,0xbd003ac9,0x3cbebcac,0xbcce3c98,0x3cdcbc84,0xbce73c5b,
 0x3b49bcff,0xbc153cf5,0x3c71bce2,0xbca23cc6,0x3cc6bca2,0xbce23c71,0x3cf5bc15,0xbcff3b49,0xbcffbb49,0x3cf53c15,0xbce2bc71,0x3cc63ca2,0xbca2bcc6,0x3c713ce2,0xbc15bcf5,0x3b493cff,
 0xbb493cff,0x3c15bcf5,0xbc713ce2,0x3ca2bcc6,0xbcc63ca2,0x3ce2bc71,0xbcf53c15,0x3cffbb49,0x3cff3b49,0xbcf5bc15,0x3ce23c71,0xbcc6bca2,0x3ca23cc6,0xbc71bce2,0x3c153cf5,0xbb49bcff,
 0x3cdc3c84,0xbcacbcbe,0x3c5b3ce7,0xbb96bcfd,0x3ccebc98,0xbcf13c2c,0x3d00bac9,0xbcf8bbf9,0xbbf9bcf8,0xbac93d00,0x3c2cbcf1,0xbc983cce,0xbcfdbb96,0x3ce73c5b,0xbcbebcac,0x3c843cdc,
 0x3c84bcdc,0xbcbe3cac,0x3ce7bc5b,0xbcfd3b96,0xbc98bcce,0x3c2c3cf1,0xbac9bd00,0xbbf93cf8,0xbcf83bf9,0x3d003ac9,0xbcf1bc2c,0x3cce3c98,0xbb963cfd,0x3c5bbce7,0xbcac3cbe,0x3cdcbc84,
 0xbcfbbbc8,0x3cd53c8e,0xbc8ebcd5,0x3bc83cfb,0x3bc8bcfb,0xbc8e3cd5,0x3cd5bc8e,0xbcfb3bc8,0x3cfb3bc8,0xbcd5bc8e,0x3c8e3cd5,0xbbc8bcfb,0xbbc83cfb,0x3c8ebcd5,0xbcd53c8e,0x3cfbbbc8,
 0xbcfbbbc8,0x3cd53c8e,0xbc8ebcd5,0x3bc83cfb,0x3bc8bcfb,0xbc8e3cd5,0x3cd5bc8e,0xbcfb3bc8,0x3cfb3bc8,0xbcd5bc8e,0x3c8e3cd5,0xbbc8bcfb,0xbbc83cfb,0x3c8ebcd5,0xbcd53c8e,0x3cfbbbc8,
 0x3cce3c98,0xbc5bbce7,0xbac93d00,0x3c84bcdc,0x3bf9bcf8,0xbcac3cbe,0x3cf1bc2c,0xbcfdbb96,0xbb96bcfd,0xbc2c3cf1,0x3cbebcac,0xbcf83bf9,0xbcdc3c84,0x3d00bac9,0xbce7bc5b,0x3c983cce,
 0x3c98bcce,0xbce73c5b,0x3d003ac9,0xbcdcbc84,0xbcf8bbf9,0x3cbe3cac,0xbc2cbcf1,0xbb963cfd,0xbcfd3b96,0x3cf13c2c,0xbcacbcbe,0x3bf93cf8,0x3c843cdc,0xbac9bd00,0xbc5b3ce7,0x3ccebc98,
 0x3c15bcf5,0xbcc63ca2,0x3cffbb49,0xbce2bc71,0x3c713ce2,0x3b49bcff,0xbca23cc6,0x3cf5bc15,0x3cf53c15,0xbca2bcc6,0x3b493cff,0x3c71bce2,0xbce23c71,0x3cff3b49,0xbcc6bca2,0x3c153cf5,
 0xbc153cf5,0x3cc6bca2,0xbcff3b49,0x3ce23c71,0xbc71bce2,0xbb493cff,0x3ca2bcc6,0xbcf53c15,0xbcf5bc15,0x3ca23cc6,0xbb49bcff,0xbc713ce2,0x3ce2bc71,0xbcffbb49,0x3cc63ca2,0xbc15bcf5,
 0xbcbebcac,0x3b963cfd,0x3c84bcdc,0xbcf13c2c,0x3c5b3ce7,0x3bf9bcf8,0xbcce3c98,0x3d003ac9,0xbac9bd00,0xbc983cce,0x3cf8bbf9,0xbce7bc5b,0xbc2c3cf1,0x3cdcbc84,0xbcfdbb96,0x3cac3cbe,
 0x3cacbcbe,0xbcfd3b96,0x3cdc3c84,0xbc2cbcf1,0xbce73c5b,0x3cf83bf9,0xbc98bcce,0xbac93d00,0x3d00bac9,0xbccebc98,0x3bf93cf8,0x3c5bbce7,0xbcf1bc2c,0x3c843cdc,0x3b96bcfd,0xbcbe3cac,
 0xbcedbc44,0x3c443ced,0x3c44bced,0xbced3c44,0x3ced3c44,0xbc44bced,0xbc443ced,0x3cedbc44,0xbcedbc44,0x3c443ced,0x3c44bced,0xbced3c44,0x3ced3c44,0xbc44bced,0xbc443ced,0x3cedbc44,
 0xbcedbc44,0x3c443ced,0x3c44bced,0xbced3c44,0x3ced3c44,0xbc44bced,0xbc443ced,0x3cedbc44,0xbcedbc44,0x3c443ced,0x3c44bced,0xbced3c44,0x3ced3c44,0xbc44bced,0xbc443ced,0x3cedbc44,
 0x3cac3cbe,0x3b96bcfd,0xbcdc3c84,0x3cf13c2c,0xbce7bc5b,0x3bf93cf8,0x3c98bcce,0xbd003ac9,0xbac93d00,0x3ccebc98,0xbcf8bbf9,0x3c5b3ce7,0xbc2cbcf1,0xbc843cdc,0x3cfdbb96,0xbcbebcac,
 0xbcbe3cac,0x3cfd3b96,0xbc84bcdc,0xbc2c3cf1,0x3c5bbce7,0xbcf83bf9,0x3cce3c98,0xbac9bd00,0xbd00bac9,0x3c983cce,0x3bf9bcf8,0xbce73c5b,0x3cf1bc2c,0xbcdcbc84,0x3b963cfd,0x3cacbcbe,
 0x3c71bce2,0xbcff3b49,0x3ca23cc6,0x3c15bcf5,0xbcf53c15,0x3cc63ca2,0x3b49bcff,0xbce23c71,0xbce2bc71,0x3b493cff,0x3cc6bca2,0xbcf5bc15,0x3c153cf5,0x3ca2bcc6,0xbcffbb49,0x3c713ce2,
 0xbc713ce2,0x3cffbb49,0xbca2bcc6,0xbc153cf5,0x3cf5bc15,0xbcc6bca2,0xbb493cff,0x3ce2bc71,0x3ce23c71,0xbb49bcff,0xbcc63ca2,0x3cf53c15,0xbc15bcf5,0xbca23cc6,0x3cff3b49,0xbc71bce2,
 0xbc98bcce,0xbc5b3ce7,0x3d00bac9,0xbc84bcdc,0x3cf8bbf9,0xbcacbcbe,0xbc2c3cf1,0x3cfdbb96,0xbb963cfd,0x3cf1bc2c,0xbcbebcac,0xbbf93cf8,0xbcdcbc84,0xbac93d00,0x3ce7bc5b,0xbccebc98,
 0xbcce3c98,0x3ce73c5b,0xbac9bd00,0xbcdc3c84,0xbbf9bcf8,0xbcbe3cac,0x3cf13c2c,0xbb96bcfd,0x3cfd3b96,0xbc2cbcf1,0xbcac3cbe,0x3cf83bf9,0xbc843cdc,0x3d003ac9,0xbc5bbce7,0xbc983cce,
 0xbcd5bc8e,0xbbc83cfb,0x3cfbbbc8,0xbc8ebcd5,0xbc8e3cd5,0x3cfb3bc8,0xbbc8bcfb,0xbcd53c8e,0x3cd53c8e,0x3bc8bcfb,0xbcfb3bc8,0x3c8e3cd5,0x3c8ebcd5,0xbcfbbbc8,0x3bc83cfb,0x3cd5bc8e,
 0xbcd5bc8e,0xbbc83cfb,0x3cfbbbc8,0xbc8ebcd5,0xbc8e3cd5,0x3cfb3bc8,0xbbc8bcfb,0xbcd53c8e,0x3cd53c8e,0x3bc8bcfb,0xbcfb3bc8,0x3c8e3cd5,0x3c8ebcd5,0xbcfbbbc8,0x3bc83cfb,0x3cd5bc8e,
 0xbc84bcdc,0xbcac3cbe,0x3ce73c5b,0x3b96bcfd,0x3c98bcce,0xbcf1bc2c,0xbac93d00,0x3cf8bbf9,0xbbf93cf8,0x3d00bac9,0xbc2cbcf1,0xbcce3c98,0xbcfd3b96,0x3c5b3ce7,0x3cbebcac,0xbcdcbc84,
 0xbcdc3c84,0x3cbe3cac,0x3c5bbce7,0xbcfdbb96,0xbccebc98,0xbc2c3cf1,0x3d003ac9,0xbbf9bcf8,0x3cf83bf9,0xbac9bd00,0xbcf13c2c,0x3c983cce,0x3b963cfd,0x3ce7bc5b,0xbcacbcbe,0xbc843cdc,
 0x3ca2bcc6,0xbce2bc71,0xbc153cf5,0x3cff3b49,0xbb49bcff,0xbcf53c15,0x3c713ce2,0x3cc6bca2,0x3cc63ca2,0x3c71bce2,0xbcf5bc15,0xbb493cff,0x3cffbb49,0xbc15bcf5,0xbce23c71,0x3ca23cc6,
 0xbca23cc6,0x3ce23c71,0x3c15bcf5,0xbcffbb49,0x3b493cff,0x3cf5bc15,0xbc71bce2,0xbcc63ca2,0xbcc6bca2,0xbc713ce2,0x3cf53c15,0x3b49bcff,0xbcff3b49,0x3c153cf5,0x3ce2bc71,0xbca2bcc6,
 0x3c5b3ce7,0x3cdcbc84,0xbc98bcce,0xbcbe3cac,0x3ac93d00,0x3cfdbb96,0xbbf9bcf8,0xbcf13c2c,0xbc2c3cf1,0x3cf83bf9,0x3b96bcfd,0xbd00bac9,0xbcac3cbe,0x3cce3c98,0x3c84bcdc,0xbce7bc5b,
 0xbce73c5b,0x3c843cdc,0x3ccebc98,0xbcacbcbe,0xbd003ac9,0x3b963cfd,0x3cf8bbf9,0xbc2cbcf1,0xbcf1bc2c,0xbbf93cf8,0x3cfd3b96,0x3ac9bd00,0xbcbebcac,0xbc983cce,0x3cdc3c84,0x3c5bbce7,
 0xbcb5bcb5,0xbcb53cb5,0x3cb53cb5,0x3cb5bcb5,0xbcb5bcb5,0xbcb53cb5,0x3cb53cb5,0x3cb5bcb5,0xbcb5bcb5,0xbcb53cb5,0x3cb53cb5,0x3cb5bcb5,0xbcb5bcb5,0xbcb53cb5,0x3cb53cb5,0x3cb5bcb5,
 0xbcb5bcb5,0xbcb53cb5,0x3cb53cb5,0x3cb5bcb5,0xbcb5bcb5,0xbcb53cb5,0x3cb53cb5,0x3cb5bcb5,0xbcb5bcb5,0xbcb53cb5,0x3cb53cb5,0x3cb5bcb5,0xbcb5bcb5,0xbcb53cb5,0x3cb53cb5,0x3cb5bcb5,
 0xbc2cbcf1,0xbcf83bf9,0x3b963cfd,0x3d00bac9,0xbcacbcbe,0xbcce3c98,0x3c843cdc,0x3ce7bc5b,0x3c5bbce7,0xbcdcbc84,0xbc983cce,0x3cbe3cac,0x3ac9bd00,0xbcfdbb96,0xbbf93cf8,0x3cf13c2c,
 0x3cf1bc2c,0xbbf9bcf8,0xbcfd3b96,0x3ac93d00,0x3cbebcac,0xbc98bcce,0xbcdc3c84,0x3c5b3ce7,0x3ce73c5b,0x3c84bcdc,0xbccebc98,0xbcac3cbe,0x3d003ac9,0x3b96bcfd,0xbcf8bbf9,0xbc2c3cf1,
 0x00000000,0x00000000,0x00000000,0x00000000,0x00000000,0x00000000,0x00000000,0x00000000,0x00000000,0x00000000,0x00000000,0x00000000,0x00000000,0x00000000,0x00000000,0x00000000,
 0x00000000,0x00000000,0x00000000,0x00000000,0x00000000,0x00000000,0x00000000,0x00000000,0x00000000,0x00000000,0x00000000,0x00000000,0x00000000,0x00000000,0x00000000,0x00000000,
 0x00000000,0x00000000,0x00000000,0x00000000,0x00000000,0x00000000,0x00000000,0x00000000,0x00000000,0x00000000,0x00000000,0x00000000,0x00000000,0x00000000,0x00000000,0x00000000,
 0x00000000,0x00000000,0x00000000,0x00000000,0x00000000,0x00000000,0x00000000,0x00000000,0x00000000,0x00000000,0x00000000,0x00000000,0x00000000,0x00000000,0x00000000,0x00000000,
 0x00000000,0x00000000,0x00000000,0x00000000,0x00000000,0x00000000,0x00000000,0x00000000,0x00000000,0x00000000,0x00000000,0x00000000,0x00000000,0x00000000,0x00000000,0x00000000,
 0x00000000,0x00000000,0x00000000,0x00000000,0x00000000,0x00000000,0x00000000,0x00000000,0x00000000,0x00000000,0x00000000,0x00000000,0x00000000,0x00000000,0x00000000,0x00000000,
 0x00000000,0x00000000,0x00000000,0x00000000,0x00000000,0x00000000,0x00000000,0x00000000,0x00000000,0x00000000,0x00000000,0x00000000,0x00000000,0x00000000,0x00000000,0x00000000,
 0x00000000,0x00000000,0x00000000,0x00000000,0x00000000,0x00000000,0x00000000,0x00000000,0x00000000,0x00000000,0x00000000,0x00000000,0x00000000,0x00000000,0x00000000,0x00000000,
 0x00000000,0x00000000,0x00000000,0x00000000,0x00000000,0x00000000,0x00000000,0x00000000,0x00000000,0x00000000,0x00000000,0x00000000,0x00000000,0x00000000,0x00000000,0x00000000,
 0x00000000,0x00000000,0x00000000,0x00000000,0x00000000,0x00000000,0x00000000,0x00000000,0x00000000,0x00000000,0x00000000,0x00000000,0x00000000,0x00000000,0x00000000,0x00000000,
 0x00000000,0x00000000,0x00000000,0x00000000,0x00000000,0x00000000,0x00000000,0x00000000,0x00000000,0x00000000,0x00000000,0x00000000,0x00000000,0x00000000,0x00000000,0x00000000,
 0x00000000,0x00000000,0x00000000,0x00000000,0x00000000,0x00000000,0x00000000,0x00000000,0x00000000,0x00000000,0x00000000,0x00000000,0x00000000,0x00000000,0x00000000,0x00000000,
};

template<int SA>
__device__ __forceinline__ void wgmma_main(float (&d)[80], uint64_t da, uint64_t db, int sd) {
  asm volatile("{\n.reg .pred p;\nsetp.ne.b32 p, %82, 0;\n"
    "wgmma.mma_async.sync.aligned.m64n160k16.f32.bf16.bf16 "
    "{%0, %1, %2, %3, %4, %5, %6, %7, %8, %9, %10, %11, %12, %13, %14, %15, %16, %17, %18, %19, %20, %21, %22, %23, %24, %25, %26, %27, %28, %29, %30, %31, %32, %33, %34, %35, %36, %37, %38, %39, %40, %41, %42, %43, %44, %45, %46, %47, %48, %49, %50, %51, %52, %53, %54, %55, %56, %57, %58, %59, %60, %61, %62, %63, %64, %65, %66, %67, %68, %69, %70, %71, %72, %73, %74, %75, %76, %77, %78, %79}, %80, %81, p, %83, 1, 1, 0;\n}\n"
    : "+f"(d[0]), "+f"(d[1]), "+f"(d[2]), "+f"(d[3]), "+f"(d[4]), "+f"(d[5]), "+f"(d[6]), "+f"(d[7]), "+f"(d[8]), "+f"(d[9]), "+f"(d[10]), "+f"(d[11]), "+f"(d[12]), "+f"(d[13]), "+f"(d[14]), "+f"(d[15]), "+f"(d[16]), "+f"(d[17]), "+f"(d[18]), "+f"(d[19]), "+f"(d[20]), "+f"(d[21]), "+f"(d[22]), "+f"(d[23]), "+f"(d[24]), "+f"(d[25]), "+f"(d[26]), "+f"(d[27]), "+f"(d[28]), "+f"(d[29]), "+f"(d[30]), "+f"(d[31]), "+f"(d[32]), "+f"(d[33]), "+f"(d[34]), "+f"(d[35]), "+f"(d[36]), "+f"(d[37]), "+f"(d[38]), "+f"(d[39]), "+f"(d[40]), "+f"(d[41]), "+f"(d[42]), "+f"(d[43]), "+f"(d[44]), "+f"(d[45]), "+f"(d[46]), "+f"(d[47]), "+f"(d[48]), "+f"(d[49]), "+f"(d[50]), "+f"(d[51]), "+f"(d[52]), "+f"(d[53]), "+f"(d[54]), "+f"(d[55]), "+f"(d[56]), "+f"(d[57]), "+f"(d[58]), "+f"(d[59]), "+f"(d[60]), "+f"(d[61]), "+f"(d[62]), "+f"(d[63]), "+f"(d[64]), "+f"(d[65]), "+f"(d[66]), "+f"(d[67]), "+f"(d[68]), "+f"(d[69]), "+f"(d[70]), "+f"(d[71]), "+f"(d[72]), "+f"(d[73]), "+f"(d[74]), "+f"(d[75]), "+f"(d[76]), "+f"(d[77]), "+f"(d[78]), "+f"(d[79])
    : "l"(da), "l"(db), "r"(sd), "n"(SA));
}
template<int SA>
__device__ __forceinline__ void wgmma_fwd(float (&d)[32], uint64_t da, uint64_t db, int sd) {
  asm volatile("{\n.reg .pred p;\nsetp.ne.b32 p, %34, 0;\n"
    "wgmma.mma_async.sync.aligned.m64n64k16.f32.bf16.bf16 "
    "{%0, %1, %2, %3, %4, %5, %6, %7, %8, %9, %10, %11, %12, %13, %14, %15, %16, %17, %18, %19, %20, %21, %22, %23, %24, %25, %26, %27, %28, %29, %30, %31}, %32, %33, p, %35, 1, 0, 1;\n}\n"
    : "+f"(d[0]), "+f"(d[1]), "+f"(d[2]), "+f"(d[3]), "+f"(d[4]), "+f"(d[5]), "+f"(d[6]), "+f"(d[7]), "+f"(d[8]), "+f"(d[9]), "+f"(d[10]), "+f"(d[11]), "+f"(d[12]), "+f"(d[13]), "+f"(d[14]), "+f"(d[15]), "+f"(d[16]), "+f"(d[17]), "+f"(d[18]), "+f"(d[19]), "+f"(d[20]), "+f"(d[21]), "+f"(d[22]), "+f"(d[23]), "+f"(d[24]), "+f"(d[25]), "+f"(d[26]), "+f"(d[27]), "+f"(d[28]), "+f"(d[29]), "+f"(d[30]), "+f"(d[31])
    : "l"(da), "l"(db), "r"(sd), "n"(SA));
}
template<int SA>
__device__ __forceinline__ void wgmma_inv(float (&d)[28], uint64_t da, uint64_t db, int sd) {
  asm volatile("{\n.reg .pred p;\nsetp.ne.b32 p, %30, 0;\n"
    "wgmma.mma_async.sync.aligned.m64n56k16.f32.bf16.bf16 "
    "{%0, %1, %2, %3, %4, %5, %6, %7, %8, %9, %10, %11, %12, %13, %14, %15, %16, %17, %18, %19, %20, %21, %22, %23, %24, %25, %26, %27}, %28, %29, p, %31, 1, 1, 0;\n}\n"
    : "+f"(d[0]), "+f"(d[1]), "+f"(d[2]), "+f"(d[3]), "+f"(d[4]), "+f"(d[5]), "+f"(d[6]), "+f"(d[7]), "+f"(d[8]), "+f"(d[9]), "+f"(d[10]), "+f"(d[11]), "+f"(d[12]), "+f"(d[13]), "+f"(d[14]), "+f"(d[15]), "+f"(d[16]), "+f"(d[17]), "+f"(d[18]), "+f"(d[19]), "+f"(d[20]), "+f"(d[21]), "+f"(d[22]), "+f"(d[23]), "+f"(d[24]), "+f"(d[25]), "+f"(d[26]), "+f"(d[27])
    : "l"(da), "l"(db), "r"(sd), "n"(SA));
}

__device__ __forceinline__ uint32_t s2u(const void* p) { return (uint32_t)__cvta_generic_to_shared(p); }
__device__ __forceinline__ void mbar_init(uint32_t a, int c) { asm volatile("mbarrier.init.shared::cta.b64 [%0], %1;" ::"r"(a), "r"(c)); }
__device__ __forceinline__ void mbar_expect(uint32_t a, int b) { asm volatile("mbarrier.arrive.expect_tx.shared::cta.b64 _, [%0], %1;" ::"r"(a), "r"(b) : "memory"); }
__device__ __forceinline__ void mbar_arrive(uint32_t a) { asm volatile("mbarrier.arrive.shared::cta.b64 _, [%0];" ::"r"(a) : "memory"); }
__device__ __forceinline__ void mbar_arrive_cluster(uint32_t a, uint32_t cta, uint32_t cnt) {
  asm volatile("{\n.reg .b32 r;\nmapa.shared::cluster.u32 r, %0, %1;\nmbarrier.arrive.shared::cluster.b64 _, [r], %2;\n}" ::"r"(a), "r"(cta), "r"(cnt) : "memory");
}
__device__ __forceinline__ void mbar_wait(uint32_t a, int ph) {
  asm volatile("{\n.reg .pred p;\n.reg .u32 c;\nmov.u32 c, 0;\nWAIT:\n"
               "mbarrier.try_wait.parity.shared::cta.b64 p, [%0], %1;\n@p bra DONE;\n"
               "add.u32 c, c, 1;\nsetp.lt.u32 p, c, 0x400000;\n@p bra WAIT;\ntrap;\nDONE:\n}" ::"r"(a), "r"(ph) : "memory");
}
__device__ __forceinline__ void flag_wait(const unsigned* p, unsigned target) {
  asm volatile("{\n.reg .pred p;\n.reg .u32 c, v;\nmov.u32 c, 0;\nWAIT:\n"
               "ld.acquire.gpu.global.u32 v, [%0];\nsetp.ge.u32 p, v, %1;\n@p bra DONE;\n"
               "add.u32 c, c, 1;\nsetp.lt.u32 p, c, 0x400000;\n@p bra WAIT;\ntrap;\nDONE:\n}" ::"l"(p), "r"(target) : "memory");
}
__device__ __forceinline__ bool elect_one() {
  uint32_t p;
  asm volatile("{\n.reg .pred P;\nelect.sync _|P, 0xffffffff;\nselp.u32 %0, 1, 0, P;\n}" : "=r"(p));
  return p != 0;
}
__device__ __forceinline__ void bulk_ld(uint32_t dst, const void* src, int bytes, uint32_t bar) {
  asm volatile("cp.async.bulk.shared::cluster.global.mbarrier::complete_tx::bytes [%0], [%1], %2, [%3];" ::"r"(dst), "l"(src), "r"(bytes), "r"(bar) : "memory");
}
__device__ __forceinline__ void bulk_ld_mc_h(uint32_t dst, const void* src, int bytes, uint32_t bar, uint16_t mask, uint64_t pol) {
  asm volatile("cp.async.bulk.shared::cluster.global.mbarrier::complete_tx::bytes.multicast::cluster.L2::cache_hint [%0], [%1], %2, [%3], %4, %5;" ::"r"(dst), "l"(src), "r"(bytes), "r"(bar), "h"(mask), "l"(pol) : "memory");
}
__device__ __forceinline__ void tma_ld2(uint32_t dst, const CUtensorMap* tm, int c0, int c1, uint32_t bar) {
  asm volatile("cp.async.bulk.tensor.2d.shared::cluster.global.mbarrier::complete_tx::bytes [%0], [%1, {%3,%4}], [%2];" ::"r"(dst), "l"(tm), "r"(bar), "r"(c0), "r"(c1) : "memory");
}
__device__ __forceinline__ void tma_ld3(uint32_t dst, const CUtensorMap* tm, int c0, int c1, int c2, uint32_t bar) {
  asm volatile("cp.async.bulk.tensor.3d.shared::cluster.global.mbarrier::complete_tx::bytes [%0], [%1, {%3,%4,%5}], [%2];" ::"r"(dst), "l"(tm), "r"(bar), "r"(c0), "r"(c1), "r"(c2) : "memory");
}
__device__ __forceinline__ void tma_ld3h(uint32_t dst, const CUtensorMap* tm, int c0, int c1, int c2, uint32_t bar, uint64_t pol) {
  asm volatile("cp.async.bulk.tensor.3d.shared::cluster.global.mbarrier::complete_tx::bytes.L2::cache_hint [%0], [%1, {%3,%4,%5}], [%2], %6;" ::"r"(dst), "l"(tm), "r"(bar), "r"(c0), "r"(c1), "r"(c2), "l"(pol) : "memory");
}
__device__ __forceinline__ uint64_t policy_evict_first() {
  uint64_t p;
  asm("createpolicy.fractional.L2::evict_first.b64 %0, 1.0;" : "=l"(p));
  return p;
}
__device__ __forceinline__ void tma_st3(const CUtensorMap* tm, uint32_t src, int c0, int c1, int c2) {
  asm volatile("cp.async.bulk.tensor.3d.global.shared::cta.bulk_group [%0, {%2,%3,%4}], [%1];" ::"l"(tm), "r"(src), "r"(c0), "r"(c1), "r"(c2) : "memory");
}
__device__ __forceinline__ void tma_st4(const CUtensorMap* tm, uint32_t src, int c0, int c1, int c2, int c3) {
  asm volatile("cp.async.bulk.tensor.4d.global.shared::cta.bulk_group [%0, {%2,%3,%4,%5}], [%1];" ::"l"(tm), "r"(src), "r"(c0), "r"(c1), "r"(c2), "r"(c3) : "memory");
}
__device__ __forceinline__ void tma_st5(const CUtensorMap* tm, uint32_t src, int c0) {
  asm volatile("cp.async.bulk.tensor.5d.global.shared::cta.bulk_group [%0, {%2,%3,%3,%3,%3}], [%1];" ::"l"(tm), "r"(src), "r"(c0), "r"(0) : "memory");
}
__device__ __forceinline__ void bulk_commit() { asm volatile("cp.async.bulk.commit_group;" ::: "memory"); }
template <int N> __device__ __forceinline__ void bulk_wait_read() { asm volatile("cp.async.bulk.wait_group.read %0;" ::"n"(N) : "memory"); }
template <int N> __device__ __forceinline__ void bulk_wait() { asm volatile("cp.async.bulk.wait_group %0;" ::"n"(N) : "memory"); }
__device__ __forceinline__ void fence_async_smem() { asm volatile("fence.proxy.async.shared::cta;" ::: "memory"); }
__device__ __forceinline__ void wg_fence() { asm volatile("wgmma.fence.sync.aligned;" ::: "memory"); }
__device__ __forceinline__ void wg_commit() { asm volatile("wgmma.commit_group.sync.aligned;" ::: "memory"); }
template <int N> __device__ __forceinline__ void wg_wait() { asm volatile("wgmma.wait_group.sync.aligned %0;" ::"n"(N) : "memory"); }
template <int R> __device__ __forceinline__ void fence_regs(float (&d)[R]) {
#pragma unroll
  for (int i = 0; i < R; i++) asm volatile("" : "+f"(d[i])::"memory");
}
__device__ __forceinline__ uint64_t mk_desc(uint32_t addr) {
  return (uint64_t)((addr & 0x3FFFF) >> 4) | (1ull << 16) | (64ull << 32) | (1ull << 62);
}
__device__ __forceinline__ uint32_t pack2(float lo, float hi) {
  uint32_t r;
  asm("cvt.rn.bf16x2.f32 %0, %1, %2;" : "=r"(r) : "f"(hi), "f"(lo));
  return r;
}
__device__ __forceinline__ void stsm4(uint32_t ad, uint32_t a, uint32_t b, uint32_t c, uint32_t d) {
  asm volatile("stmatrix.sync.aligned.m8n8.x4.shared.b16 [%0], {%1,%2,%3,%4};" ::"r"(ad), "r"(a), "r"(b), "r"(c), "r"(d) : "memory");
}
__device__ __forceinline__ void stsm4t(uint32_t ad, uint32_t a, uint32_t b, uint32_t c, uint32_t d) {
  asm volatile("stmatrix.sync.aligned.m8n8.x4.trans.shared.b16 [%0], {%1,%2,%3,%4};" ::"r"(ad), "r"(a), "r"(b), "r"(c), "r"(d) : "memory");
}

__device__ __forceinline__ void stsm2t(uint32_t ad, uint32_t a, uint32_t b) {
  asm volatile("stmatrix.sync.aligned.m8n8.x2.trans.shared.b16 [%0], {%1,%2};" ::"r"(ad), "r"(a), "r"(b) : "memory");
}
__device__ __forceinline__ void red_add(unsigned* p) { asm volatile("red.relaxed.gpu.global.add.u32 [%0], 1;" ::"l"(p) : "memory"); }
__device__ __forceinline__ void fence_release() { asm volatile("fence.release.gpu;" ::: "memory"); }
__device__ __forceinline__ void fence_async_global() { asm volatile("fence.proxy.async.global;" ::: "memory"); }
__device__ __forceinline__ void tma_pf3(const CUtensorMap* tm, int c0, int c1, int c2) {
  asm volatile("cp.async.bulk.prefetch.tensor.3d.L2.global [%0, {%1,%2,%3}];" ::"l"(tm), "r"(c0), "r"(c1), "r"(c2) : "memory");
}
__device__ __forceinline__ uint64_t policy_evict_unchanged() {
  uint64_t p;
  asm("createpolicy.fractional.L2::evict_unchanged.b64 %0, 1.0;" : "=l"(p));
  return p;
}
__device__ __forceinline__ void tma_ld4(uint32_t dst, const CUtensorMap* tm, int c1, uint32_t bar) {
  asm volatile("cp.async.bulk.tensor.4d.shared::cluster.global.mbarrier::complete_tx::bytes [%0], [%1, {%4,%3,%4,%4}], [%2];" ::"r"(dst), "l"(tm), "r"(bar), "r"(c1), "r"(0) : "memory");
}

__device__ __forceinline__ unsigned flag_peek(const unsigned* p) {
  unsigned v;
  asm volatile("ld.acquire.gpu.global.u32 %0, [%1];" : "=r"(v) : "l"(p) : "memory");
  return v;
}
__device__ __forceinline__ int lane_id() {
  int l;
  asm volatile("mov.u32 %0, %%laneid;" : "=r"(l));
  return l;
}
__device__ __forceinline__ void poll64x4(const unsigned long long* p, unsigned long long (&v)[4]) {
  asm volatile("{\n.reg .pred p;\n.reg .u32 c;\n.reg .b64 t, u;\nmov.u32 c, 0;\nWAIT:\n"
               "ld.relaxed.gpu.global.u64 %0, [%4];\nld.relaxed.gpu.global.u64 %1, [%4+512];\n"
               "ld.relaxed.gpu.global.u64 %2, [%4+1024];\nld.relaxed.gpu.global.u64 %3, [%4+1536];\n"
               "or.b64 t, %0, %1;\nor.b64 u, %2, %3;\nor.b64 t, t, u;\nsetp.ge.s64 p, t, 0;\n@p bra DONE;\n"
               "add.u32 c, c, 1;\nsetp.lt.u32 p, c, 0x400000;\n@p bra WAIT;\ntrap;\nDONE:\n}"
               : "=l"(v[0]), "=l"(v[1]), "=l"(v[2]), "=l"(v[3]) : "l"(p) : "memory");
}

constexpr int G_STAGE = WBLK + XBLK;
constexpr int OFF_XR = 4 * G_STAGE;
constexpr int OFF_WS = OFF_XR + 6 * 8192;
constexpr int OFF_F = OFF_WS + 2 * 8192;
constexpr int OFF_WRAW = OFF_F + 8192;
constexpr int OFF_BAR = OFF_WRAW + 8192;
constexpr int OFF_GB = OFF_BAR + 1024;
constexpr int SMEM_BYTES = OFF_GB + 512;
constexpr int OFF_H0B = 10 * 8192;
constexpr int OFF_E = OFF_WRAW + 3072;
constexpr int B_RAWX = 0, B_F = 48, B_ROLE = 56, B_H0 = 80, B_H1 = 96, B_YFREE = 120, B_H0C = 136,
              B_EMPTY = 144,
              B_STGX = 192, B_STGW = 240, B_Y = 256, B_OUT = 272, B_YP = 352,
              B_FULL = 432, B_RAWW = 464, B_DONE = 496, S_ROLE = 576, S_PROBE = 592;

struct Maps { CUtensorMap x, we, wo, xst[2], wst, yld[2], out, xe[2], w30; };

__device__ __forceinline__ int chunk_of(int n) { return n < 16 ? n : 31 - n; }
__device__ __forceinline__ bool has_x2(int id, int n, int g) { return (((id >> 5) ^ n) & 1) == 0 && ((n >> 1) & 1) == g; }
__device__ __forceinline__ int w_row(int id) { return (id & 62) | (id >> 6); }
__device__ __forceinline__ uint32_t x_base(int s, int idx, uint32_t pgmask, int& par) {
  const int page = idx >> 3, o = idx & 7;
  par = (s ^ (pgmask >> page) ^ __popc(o)) & 1;
  return (page << 21) | ((o & 3) << 16) | ((o >> 2) << 19);
}
__device__ __forceinline__ uint32_t spread5(int i) { return (((i >> 1) & 3) << 14) | (((i >> 3) & 1) << 18) | ((i >> 4) << 20) | ((i & 1) << 13); }
__device__ __forceinline__ int y_idx(int half, int dq, int piece) { return (PG_Y + 5 * half) * 8 + (dq * 5 + piece) * 2; }
__device__ __forceinline__ int tail_win(int tr) { return (tr & 1) + 4 * (tr >> 1); }
__device__ __forceinline__ uint32_t read_info(uint32_t bar, int i) {
  uint32_t v;
  mbar_wait(bar + B_ROLE + 8 * i, 0);
  asm volatile("ld.shared.b32 %0, [%1];" : "=r"(v) : "r"(bar + S_ROLE + 4 * i) : "memory");
  return v;
}
__device__ __forceinline__ void send_info(uint32_t bar, int i, uint32_t v) {
#pragma unroll
  for (int r = 0; r < 2; r++)
    asm volatile("{\n.reg .b32 a, m;\nmapa.shared::cluster.u32 a, %0, %2;\nmapa.shared::cluster.u32 m, %1, %2;\n"
                 "st.async.weak.shared::cluster.mbarrier::complete_tx::bytes.b32 [a], %3, [m];\n}"
                 ::"r"(bar + S_ROLE + 4 * i), "r"(bar + B_ROLE + 8 * i), "r"(r), "r"(v) : "memory");
}
__device__ __forceinline__ unsigned probe(uint8_t* p, int lane) {
  if (lane < 2) *(uint4*)(p + lane * 16) = make_uint4(0, 0, 0, 0);
  __syncwarp();
  unsigned v, t0 = 0, t1 = 0;
  if (lane == 0) {
    asm volatile("mov.u32 %0, %%clock;" : "=r"(t0)::"memory");
    asm volatile("atom.relaxed.gpu.global.exch.b32 %0, [%1], 0;" : "=r"(v) : "l"(p) : "memory");
    asm volatile("{\n.reg .pred p;\nsetp.ne.u32 p, %1, 0xffffffff;\nmov.u32 %0, 0;\n@p mov.u32 %0, %%clock;\n}" : "=r"(t1) : "r"(v) : "memory");
  }
  return t1 - t0;
}

template <bool ISX>
__device__ __forceinline__ void t_issue(float (&t)[32], uint32_t sb, uint32_t raw) {
  const uint64_t da = mk_desc(sb + OFF_F), db = mk_desc(raw);
  wg_fence();
#pragma unroll
  for (int kk = 0; kk < (ISX ? 4 : 1); kk++) wgmma_fwd<1>(t, da + 2 * kk, db + 128 * kk, kk);
  wg_commit();
}
template <bool ISX>
__device__ __forceinline__ void t_finish(float (&t)[32], uint32_t dst, uint32_t sbar, int sw, int wg, int w, int lane) {
  fence_regs(t);
  if (ISX) asm volatile("bar.sync %0, 128;" ::"r"(1 + wg) : "memory");
  const int m = lane >> 3, r = lane & 7;
  uint32_t ad = dst + (8 * w + r) * 128;
  if (ISX) ad += ((((m & 1) * 4 + (m >> 1)) ^ sw ^ r) << 4);
  else ad += (m & 1) * 4096 + (((m >> 1) ^ sw ^ r) << 4);
#pragma unroll
  for (int i = 0; i < 4; i++) {
    const uint32_t a = ISX ? ((ad ^ ((i & 1) * 32)) + (i >> 1) * 4096) : (ad ^ (i * 32));
    stsm4(a, pack2(t[8 * i], t[8 * i + 1]), pack2(t[8 * i + 2], t[8 * i + 3]), pack2(t[8 * i + 4], t[8 * i + 5]), pack2(t[8 * i + 6], t[8 * i + 7]));
  }
  __syncwarp();
  if (lane == 0) mbar_arrive(sbar);
}
template <int NT, int K0, int K1>
__device__ __forceinline__ void batch(float (&yr)[80], float (&yi)[80], float (&t)[32], uint32_t st, int wg, int sd, uint32_t fa, uint32_t raw) {
  const uint64_t w0 = mk_desc(st + wg * 8192), x0 = mk_desc(st + WBLK);
  const uint64_t da = mk_desc(fa), db = mk_desc(raw);
  wg_fence();
  if (NT) {
#pragma unroll
    for (int kk = 0; kk < NT; kk++) wgmma_fwd<1>(t, da + 2 * kk, db + 128 * kk, kk);
    wg_commit();
  }
#pragma unroll
  for (int kk = K0; kk < K1; kk++) {
    const uint64_t wr = w0 + kk * 128, wi = wr + 256, xr = x0 + kk * 2, xi = xr + 4;
    wgmma_main<1>(yr, wr, xr, kk ? 1 : sd);
    wgmma_main<1>(yi, wr, xi, kk ? 1 : sd);
    wgmma_main<1>(yr, wi, xi, 1);
    wgmma_main<-1>(yi, wi, xr, 1);
  }
  wg_commit();
}

#define X_WAIT() PROF_W(wraw, mbar_wait(bar + B_RAWX + 8 * (wg * 3 + xs), xph))
#define X_ISSUE() t_issue<true>(t, sb, sb + OFF_XR + (wg * 3 + xs) * 8192)
#define X_FINISH(sw) do { t_finish<true>(t, sb + OFF_XR + (wg * 3 + xs) * 8192, bar + B_STGX + 8 * (wg * 3 + xs), sw, wg, w, lane); \
                          if (++xs == 3) { xs = 0; xph ^= 1; } } while (0)
#define W_WAIT(n) PROF_W(wraw, mbar_wait(bar + B_RAWW + 8 * (wg * 2 + ((n) & 1)), ((n) >> 1) & 1))
#define WRAW(n) (sb + OFF_WRAW + (wg * 2 + ((n) & 1)) * 2048)
#define W_FINISH() t_finish<false>(t, sb + OFF_WS + wg * 8192, bar + B_STGW + 8 * wg, w_row(id) & 7, wg, w, lane)

__device__ __forceinline__ void gelu_store(float (&hz)[28], uint32_t ad) {
#pragma unroll
  for (int i = 0; i < 28; i++) {
    const float in = hz[i] * fmaf(hz[i] * hz[i], 8.f * 0.044715f * 0.7978845608028654f, 2.f * 0.7978845608028654f);
    float th;
    asm("tanh.approx.f32 %0, %1;" : "=f"(th) : "f"(in));
    hz[i] = fmaf(hz[i], th, hz[i]);
  }
#pragma unroll
  for (int jj = 0; jj < 3; jj++) {
    const float* c = hz + 8 * jj;
    stsm4t(ad + jj * 2048, pack2(c[0], c[1]), pack2(c[2], c[3]), pack2(c[4], c[5]), pack2(c[6], c[7]));
  }
  stsm2t(ad + 3 * 2048, pack2(hz[24], hz[25]), pack2(hz[26], hz[27]));
}

#define ONE(...) do { if (elect_one()) { __VA_ARGS__; } } while (0)
template <int g>
__device__ __forceinline__ void manager(const Maps& tm, const unsigned* ctr, const uint32_t sb, const int id) {
  const uint32_t bar = sb + OFF_BAR, rank = id & 1;
  const uint64_t pol = policy_evict_first();
  const int cl = w_row(id), b = id >> 6, u = (id >> 1) & 31;
  const unsigned* pf = ctr + (C_LOADED + (((cl >> 5) - WR) >> 1)) * 32 + (((cl >> 5) - WR) & 1);
  int li = 0;
  auto refill = [&](int sl, bool wait) {
    const uint32_t fb = bar + B_RAWX + 8 * (g * 3 + sl);
    int row = ((li & 1) ? 128 + (id & 31) : 2 * (id & 63) + g) * MT, col = (li >> 1) * 64;
    asm volatile("" : "+r"(row), "+r"(col));
    ONE(if (li < 32) mbar_expect(fb, 8192);
        if (wait) bulk_wait_read<0>();
        if (li < 32) tma_ld3h(sb + OFF_XR + (g * 3 + sl) * 8192, &tm.x, col, row, b, fb, pol));
    li += (li & 1) || has_x2(id, li >> 1, g) ? 1 : 2;
  };
#pragma unroll 1
  for (int sl = 0; sl < 3; sl++) refill(sl, false);
  int xs = 0, xph = 0, yp = 0;
  int wrow = (cl >> 5) * (WSLOT / 128) + rank * 128 + g * 64 + (cl & 31);
  const uint32_t pgmask = __shfl_sync(0xffffffffu, read_info(bar, 1), 0);
  auto store_y = [&](int half, int piece, uint32_t buf, uint32_t wait_bar, int ph) {
    int par;
    int c = x_base(b, y_idx(half, rank * 2 + g, piece) + (u >> 4), pgmask, par);
    c = (c + (par << 12) + (u & 15) * 256) >> 1;
    const CUtensorMap* m = &tm.xst[par];
    asm volatile("" : "+r"(c), "+l"(m));
    if (wait_bar) mbar_wait(wait_bar, ph);
    ONE(fence_async_smem(); tma_st5(m, buf, c); tma_st5(m, buf + 4096, c + 64));
  };
  mbar_wait(bar + B_STGW + 8 * g, 0);
  ONE(fence_async_smem(); tma_st4(&tm.wst, sb + OFF_WS + g * 8192, 0, 0, 0, wrow); bulk_commit());
#pragma unroll 1
  for (int n = 0; n < 32; n++) {
    unsigned freed = 128;
    if (2 * n + (cl >> 5) >= WR) asm volatile("ld.relaxed.gpu.global.u32 %0, [%1];" : "=r"(freed) : "l"(pf + n * 32) : "memory");
    if (n < 16) {
#pragma unroll 1
      for (int j = 0; j < (has_x2(id, n, g) ? 2 : 1); j++) {
        const int t = j ? 128 + (id & 31) : 2 * (id & 63) + g;
        int par0, par1;
        const uint32_t off0 = x_base(b, n * 10 + (t >> 5), pgmask, par0), off1 = x_base(b, n * 10 + 5 + (t >> 5), pgmask, par1);
        uint32_t buf = sb + OFF_XR + (g * 3 + xs) * 8192;
        int c0 = (off0 + (par0 << 12) + (t & 31) * 128) >> 1, c1 = (off1 + (par1 << 12) + (t & 31) * 128) >> 1;
        const CUtensorMap *m0 = &tm.xst[par0], *m1 = &tm.xst[par1];
        asm volatile("" : "+r"(buf), "+r"(c0), "+r"(c1), "+l"(m0), "+l"(m1));
        mbar_wait(bar + B_STGX + 8 * (g * 3 + xs), xph);
        ONE(fence_async_smem(); tma_st5(m0, buf, c0); tma_st5(m1, buf + 4096, c1); bulk_commit());
        refill(xs, true);
        if (++xs == 3) { xs = 0; xph ^= 1; }
      }
    }
    if (n > 16 + LW && n <= YFLUSH) {
#pragma unroll 1
      do {
        store_y(0, yp, sb + OFF_XR + (g * 3 + (yp < 3 ? yp : yp - 3)) * 8192, (yp == 0 || yp == 3) ? bar + B_Y + 8 * g : 0, yp & 1);
      } while (++yp < 2);
      ONE(bulk_commit(); bulk_wait_read<0>(); if (yp == 2) mbar_arrive(bar + B_YFREE + 8 * g));
    }
    if (__shfl_sync(0xffffffffu, freed, 0) < 128) flag_wait(pf + n * 32, 128);
    const int cp = chunk_of(n + 2) * 64 + cl, sl = g * 2 + (n & 1);
    if (n) mbar_wait(bar + B_STGW + 8 * g, n & 1);
    ONE(if (n) {
          fence_async_smem();
          tma_st4(&tm.wst, sb + OFF_WS + g * 8192, 0, 0, 0, wrow);
          bulk_commit();
        }
        if (n < 30) {
          mbar_expect(bar + B_RAWW + 8 * sl, 2048);
          tma_ld3h(sb + OFF_WRAW + sl * 2048, &tm.we + (cp >> 9), 0, 0, (cp & 511) * 8 + ((n + 2) >> 4) * 4 + rank * 2 + g, bar + B_RAWW + 8 * sl, pol);
        }
        if (n < 4) {
          tma_pf3(&tm.we, 0, 0, ((n + 4) * 64 + cl) * 8 + rank * 2 + g);
          tma_pf3(&tm.wo, 0, 0, (n * 64 + cl) * 8 + rank * 2 + g);
          tma_pf3(&tm.wo, 0, 0, ((n + 4) * 64 + cl) * 8 + rank * 2 + g);
        }
        bulk_wait<0>();
        mbar_arrive(bar + B_DONE + 8 * (n & 7));
        mbar_arrive(bar + B_RAWW + 8 * (sl ^ 1)));
    wrow += 2 * WSLOT / 128;
    if (wrow >= WR * WSLOT / 128) wrow -= WR * WSLOT / 128;
  }
  ONE(asm volatile("prefetch.tensormap [%0];" ::"l"(g ? &tm.out : &tm.xst[b]) : "memory"));
  flag_wait(&ctr[(C_LOADED + 31) * 32 + 1], 128);
#pragma unroll 1
  for (int p = 0; p < 5; p++) {
    store_y(1, p, sb + (p * 2 + g) * 8192, bar + B_YP + 8 * (g * 5 + p), 0);
    if (p == YA - 1) ONE(bulk_commit());
  }
  ONE(bulk_commit(); bulk_wait<1>(); mbar_arrive(bar + B_DONE); bulk_wait<0>(); mbar_arrive(bar + B_DONE + 8));
#pragma unroll 1
  for (int i = 0; i < 10; i++) {
    const int hf = i >= 5, k = i - 5 * hf;
    const uint32_t buf = sb + (hf ? 0 : k < 4 ? OFF_XR : OFF_H0B - 65536) + (2 * k + g) * 8192;
    mbar_wait(bar + B_OUT + 8 * (g * 5 + k), hf);
    ONE(fence_async_smem();
        tma_st3(&tm.out, buf, (hf * 4 + rank * 2 + (u & 1)) * 64, (32 * k + tail_win(u >> 1) + 2 * g) * MT, b);
        bulk_commit());
  }
  ONE(bulk_wait_read<0>(); if (g == 0) PROF_T(12));
}

__global__ void __cluster_dims__(2, 1, 1) __launch_bounds__(512, 1)
k1_main(uint8_t* xbuf, const void* __restrict__ fimg, const __nv_bfloat16* __restrict__ gamma,
        const __nv_bfloat16* __restrict__ beta, const __grid_constant__ Maps tm) {
  extern __shared__ __align__(1024) uint8_t smem_raw[];
  const uint32_t sb = s2u(smem_raw);
  const uint32_t bar = sb + OFF_BAR;
  const int warp = __shfl_sync(0xffffffffu, threadIdx.x >> 5, 0);
  const int bid = blockIdx.x;
  unsigned* ctr = (unsigned*)(xbuf + CTR_OFF);
  const uint32_t rank = bid & 1;
  if (bid == 0 && threadIdx.x < 4) asm volatile("st.relaxed.gpu.global.u64 [%0], %1;" ::"l"(&ctr[C_REG * 32 + 2 * threadIdx.x]), "l"(1ull << 63) : "memory");
  if (warp >= 12) {
    asm volatile("setmaxnreg.dec.sync.aligned.u32 24;");
    asm volatile("barrier.cluster.arrive.relaxed.aligned;" ::: "memory");
    {
      const int lane = lane_id(), k = bid >> 1;
      if (rank == 0 || k < XPAGES) {
        const uint32_t off = rank ? (k << 21) + 0xb0000 : (XPAGES << 21) + ((k >> 6) << 18) + (((k >> 4) & 3) << 14) + (k & 15) * 128;
        const unsigned lat = probe(xbuf + off + (warp & 1) * 4096 + (warp & 2) * 1024, lane);
        if (lane == 0) asm volatile("st.shared.b32 [%0], %1;" ::"r"(bar + S_PROBE + 4 * (warp & 3)), "r"(lat) : "memory");
      }
      asm volatile("bar.sync 4, 128;" ::: "memory");
      asm volatile("barrier.cluster.wait.aligned;" ::: "memory");
      if (warp == 14 && lane == 0) {
        uint32_t l0, l1, l2, l3;
        asm volatile("ld.shared.v4.b32 {%0, %1, %2, %3}, [%4];" : "=r"(l0), "=r"(l1), "=r"(l2), "=r"(l3) : "r"(bar + S_PROBE) : "memory");
        const int near = min(l1, l3) < min(l0, l2);
        if (rank) {
          send_info(bar, 2, near);
        } else {
          unsigned long long add = 1ull << (8 * near), v, *reg = (unsigned long long*)&ctr[C_REG * 32];
          if (k < XPAGES) add += (unsigned long long)(read_info(bar, 2) ^ near ^ 1) << (16 + k);
          PROF_T(14);
          asm volatile("{\n.reg .pred p;\n.reg .u32 c;\nmov.u32 c, 0;\nAGAIN:\n"
                       "atom.relaxed.gpu.global.add.u64 %0, [%1], %2;\nsetp.lt.s64 p, %0, 0;\n@p bra DONE;\n"
                       "add.u32 c, c, 1;\nsetp.lt.u32 p, c, 0x100000;\n@p bra AGAIN;\ntrap;\nDONE:\n}" : "=l"(v) : "l"(reg), "l"(add) : "memory");
          const int ticket = (v >> (8 * near)) & 255;
          if (ticket < 32) send_info(bar, 0, near * 32 + ticket);
          PROF_T(15); PROF_V(16, near);
          asm volatile("{\n.reg .pred p;\n.reg .u32 c, a, b;\nmov.u32 c, 0;\nWAIT:\n"
                       "ld.relaxed.gpu.global.u64 %0, [%1];\ncvt.u32.u64 a, %0;\nbfe.u32 b, a, 8, 8;\nand.b32 a, a, 255;\nadd.u32 a, a, b;\n"
                       "setp.ge.u32 p, a, 66;\n@p bra DONE;\n"
                       "add.u32 c, c, 1;\nsetp.lt.u32 p, c, 0x400000;\n@p bra WAIT;\ntrap;\nDONE:\n}" : "=l"(v) : "l"(reg) : "memory");
          if (ticket >= 32) {
            const int j = ticket - 32 + (int)((v >> (8 * (near ^ 1))) & 255);
            send_info(bar, 0, j < 32 ? (near ^ 1) * 32 + j : (near == 0 && ticket == 32 && j == 33) ? 64 : 32 + j);
          }
          send_info(bar, 1, (uint32_t)(v >> 16));
          PROF_T(13);
        }
      }
      __syncwarp();
      const int role = read_info(bar, 0);
      if (role < 64 && warp - 12 < NFL && elect_one()) {
#pragma unroll 1
        for (int n = warp - 12; n < 34; n += NFL) {
          mbar_wait(bar + B_DONE + 8 * (n & 7), (n >> 3) & 1);
          fence_release();
          if (n < 32) {
            red_add(&ctr[(C_FLAG + n + C_SIDE * ((role >> 5) ^ 1)) * 32]);
            red_add(&ctr[(C_FLAG + n + C_SIDE * (role >> 5)) * 32]);
          } else {
            red_add(&ctr[(C_Y + 2 * (n - 32) + rank + C_SIDE * (role >> 5)) * 32]);
          }
          if (n < 32) { PROF_T(64 + n); PROF_V(192 + n, tm0); } else { PROF_V(4, tm0); }
        }
      }
      if (role < 64 && warp == 15 && elect_one()) {
#pragma unroll 1
        for (int v = 0; v < 64; v++) {
          mbar_wait(bar + B_FULL + 8 * (v & 3), (v >> 2) & 1);
          mbar_arrive(bar + B_EMPTY + 8 * (v & 3));
          if (v < 64 - WR || v == 63) {
            red_add(&ctr[(C_LOADED + (v >> 1)) * 32 + (v & 1)]);
            red_add(&ctr[(C_LOADED + (v >> 1) + C_SIDE) * 32 + (v & 1)]);
          }
        }
      }
      __syncwarp();
    }
    asm volatile("barrier.cluster.arrive.relaxed.aligned;\nbarrier.cluster.wait.aligned;" ::: "memory");
    return;
  } else {
    if (elect_one()) {
      if (warp == 0) PROF_T(0);
      if (warp >= 6) asm volatile("prefetch.tensormap [%0];" ::"l"(&tm.x + (warp - 6)) : "memory");
      const int cnt = warp < 3 ? 1 : warp == 3 ? 5 : warp < 9 ? 4 : 2;
#pragma unroll
      for (int i = 0; i < 6; i++) mbar_init(bar + warp * 48 + 8 * i, cnt);
      if (warp == 1) {
        mbar_expect(bar + B_F, 8192);
        bulk_ld(sb + OFF_F, fimg, 8192, bar + B_F);
        mbar_expect(bar + B_ROLE, 4);
        mbar_expect(bar + B_ROLE + 8, 4);
        mbar_expect(bar + B_ROLE + 16, 4);
      }
      asm volatile("fence.mbarrier_init.release.cluster;" ::: "memory");
    }
    asm volatile("bar.sync 0, 384;" ::: "memory");
    asm volatile("barrier.cluster.arrive.relaxed.aligned;" ::: "memory");
    if (threadIdx.x == 64) PROF_T(20);
    if (bid < 128 && warp < 4 && elect_one()) {
      const int g = warp & 1;
      if (warp < 2) {
        tma_pf3(&tm.x, 0, (2 * (bid & 63) + g) * MT, bid >> 6);
        if (has_x2(bid, 0, g)) tma_pf3(&tm.x, 0, (128 + (bid & 31)) * MT, bid >> 6);
      } else {
        tma_pf3(&tm.we, 0, 0, (bid >> 1) * 8 + rank * 2 + g);
      }
    }
    __syncwarp();
  }
  if (warp >= 8) {
    asm volatile("setmaxnreg.dec.sync.aligned.u32 40;");
    asm volatile("barrier.cluster.wait.aligned;" ::: "memory");
    const int role = __shfl_sync(0xffffffffu, read_info(bar, 0), 0);
    const unsigned* lctr = ctr + (role >> 5) * C_SIDE * 32;
    if (role >= 64) {
    } else if (warp == 9 || warp == 10) {
      asm volatile("barrier.cluster.arrive.relaxed.aligned;" ::: "memory");
      if (warp == 9) manager<0>(tm, lctr, sb, role * 2 + rank); else manager<1>(tm, lctr, sb, role * 2 + rank);
      __syncwarp();
      asm volatile("barrier.cluster.wait.aligned;" ::: "memory");
      return;
    } else if (warp == 11) {
      const uint8_t* ws = xbuf + (PG_W << 21) + ((role & 31) * 2 + rank) * WBLK;
      int slot = 0;
#pragma unroll 1
      for (int v = 0; v < 64; v++) {
        const uint8_t* src = ws + (size_t)slot * WSLOT;
        uint32_t dst = sb + (v & 3) * G_STAGE, fb = bar + B_FULL + 8 * (v & 3);
        asm volatile("" : "+l"(src), "+r"(dst), "+r"(fb));
        if (++slot == WR) slot = 0;
        const unsigned* fp = &lctr[(C_FLAG + (v >> 1)) * 32];
        const bool ready = (v & 1) || __shfl_sync(0xffffffffu, flag_peek(fp), 0) >= 128;
        mbar_wait(bar + B_EMPTY + 8 * (v & 3), ((v >> 2) & 1) ^ 1);
        ONE(mbar_expect(fb, WBLK));
        if (!ready) flag_wait(fp, 128);
        ONE(fence_async_global(); bulk_ld(dst, src, WBLK, fb));
      }
    } else {
      const uint32_t pgmask = __shfl_sync(0xffffffffu, read_info(bar, 1), 0);
      const int b = role >> 5, u = role & 31;
      const uint64_t pef = policy_evict_first(), pen = policy_evict_unchanged();
      const uint8_t* xs = xbuf + spread5(u);
      const int skip = rank * 2048;
#pragma unroll 1
      for (int v = 0; v < 64; v++) {
        const int n = v >> 1;
        uint64_t polx = (n < XKEEP || n >= 16) ? pef : pen;
        uint32_t dst = sb + (v & 3) * G_STAGE + WBLK + rank * 8192, fb = bar + B_FULL + 8 * (v & 3);
        const uint8_t* src[3];
#pragma unroll
        for (int g = 0; g < 3; g++) {
          int par;
          const uint32_t o = x_base(b ^ u, chunk_of(n) * 10 + (v & 1) * 5 + rank * 2 + g, pgmask, par);
          src[g] = xs + o + (par << 12) + (g ? 0 : skip);
        }
        asm volatile("" : "+l"(src[0]), "+l"(src[1]), "+l"(src[2]), "+l"(polx), "+r"(dst), "+r"(fb));
        const unsigned* fp = &lctr[(C_FLAG + n) * 32];
        const bool ready = (v & 1) || v >= 32 || __shfl_sync(0xffffffffu, flag_peek(fp), 0) >= 128;
        mbar_wait(bar + B_EMPTY + 8 * (v & 3), ((v >> 2) & 1) ^ 1);
        ONE(mbar_expect(fb, XBLK));
        if (!ready) flag_wait(fp, 128);
        ONE(fence_async_global();
            bulk_ld_mc_h(dst + skip, src[0], 4096 - skip, fb, 3, polx);
            bulk_ld_mc_h(dst + 4096, src[1], 4096, fb, 3, polx);
            bulk_ld_mc_h(dst + 8192, src[2], 2048 + skip, fb, 3, polx));
      }
      const int dq = rank * 2 + (u & 1), t0 = (u >> 1) * 10, tw = tail_win(u >> 1);
      int row[5];
      const CUtensorMap* mp[5];
      auto locate = [&](int half) {
#pragma unroll
        for (int k = 0; k < 5; k++) {
          int par;
          row[k] = x_base(b ^ tw, y_idx(half, dq, k), pgmask, par);
          row[k] = (row[k] + spread5(tw) + (par << 12)) >> 7;
          mp[k] = &tm.yld[par];
          asm volatile("" : "+r"(row[k]), "+l"(mp[k]));
        }
      };
      locate(0);
      flag_wait(&ctr[C_E * 32], 4);
      flag_wait(&lctr[(C_FLAG + YFLUSH) * 32], 128);
      ONE(fence_async_global();
          mbar_expect(bar + B_H0C, 6 * 8192);
          for (int i = 0; i < 3; i++) tma_ld4(sb + OFF_XR + i * 16384, mp[i], row[i], bar + B_H0C));
      static_assert(YFLUSH >= 23, "phase of the B_DONE ring");
      mbar_wait(bar + B_DONE + 8 * 7, 1);
      ONE(mbar_expect(bar + B_H0, 2 * 8192 + 7168 + 5120 + 512);
          bulk_ld(sb + OFF_F, g_Gimg, 7168, bar + B_H0);
          tma_ld4(sb + OFF_WS, mp[3], row[3], bar + B_H0);
          for (int hf = 0; hf < 2; hf++) {
            bulk_ld(sb + OFF_E + hf * 2560, g_E + ((b * 8 + hf * 4 + dq) * NT + t0) * 64, 2560, bar + B_H0);
            bulk_ld(sb + OFF_GB + hf * 256, gamma + (hf * 4 + dq) * 64, 128, bar + B_H0);
            bulk_ld(sb + OFF_GB + hf * 256 + 128, beta + (hf * 4 + dq) * 64, 128, bar + B_H0);
          });
      mbar_wait(bar + B_EMPTY + 8 * 2, 1);
      ONE(mbar_expect(bar + B_H0 + 8, 16384);
          tma_ld4(sb + OFF_H0B, mp[4], row[4], bar + B_H0 + 8);
          for (int i = 0; i < 3; i++) mbar_expect(bar + B_H1 + 8 * i, i < 2 ? 32768 : 16384));
      locate(1);
      flag_wait(&lctr[(C_Y + rank) * 32], 32);
      ONE(fence_async_global();
          for (int i = 0; i < YA; i++) tma_ld4(sb + i * 16384, mp[i], row[i], bar + B_H1 + 8 * (i >> 1));
          PROF_T(5));
      flag_wait(&lctr[(C_Y + 2 + rank) * 32], 32);
      ONE(fence_async_global();
          for (int i = YA; i < 5; i++) tma_ld4(sb + i * 16384, mp[i], row[i], bar + B_H1 + 8 * (i >> 1));
          PROF_T(1));
      const int lane = lane_id();
      unsigned old = 0;
      if (lane == 0) old = atomicAdd(&ctr[C_EXIT * 32], 1);
      if (__shfl_sync(0xffffffffu, old, 0) == 127) {
#pragma unroll
        for (int i = 0; i < 6; i++) *(uint4*)&ctr[((i >> 1) * 128 + (i & 1) * C_SIDE + lane) * 32] = make_uint4(0, 0, 0, 0);
      }
    }
    asm volatile("barrier.cluster.arrive.relaxed.aligned;\nbarrier.cluster.wait.aligned;" ::: "memory");
  } else {
    asm volatile("setmaxnreg.inc.sync.aligned.u32 224;");
    const int wg = warp >> 2, w = warp & 3;
    int lane = lane_id();
    asm volatile("barrier.cluster.wait.aligned;" ::: "memory");
    mbar_wait(bar + B_F, 0);
    const int id = __shfl_sync(0xffffffffu, read_info(bar, 0), 0) * 2 + rank;
    if (id >= 128) {
      float ea[80], eb[80];
      const int b = (id >> 1) & 1;
      constexpr int ES = 32768 + 2 * XBLK;
#pragma unroll 1
      for (int k = -3; k < 8; k++) {
        const int sl = (k + 3) % 3;
        if (k >= 0) {
          mbar_wait(bar + B_RAWX + 8 * sl, (k / 3) & 1);
          const uint64_t da = mk_desc(sb + sl * ES + wg * 16384), db = mk_desc(sb + sl * ES + 32768);
          wg_fence();
#pragma unroll
          for (int kk = 0; kk < 8; kk++) {
            const uint64_t a0 = da + (kk & 3) * 128, b0 = db + (kk & 3) * 2 + (kk >> 2) * (XBLK >> 4);
            wgmma_main<1>(ea, a0, b0, (k | kk) != 0);
            wgmma_main<1>(eb, a0 + 512, b0, (k | kk) != 0);
          }
          wg_commit();
          wg_wait<0>();
          asm volatile("bar.sync 3, 256;" ::: "memory");
        }
        if (k + 3 < 8 && warp == 0 && elect_one()) {
          if (k == -3) {
            for (int i = 0; i < 64; i++) {
              unsigned v;
              asm volatile("ld.relaxed.gpu.global.u32 %0, [%1];" : "=r"(v) : "l"(&ctr[(C_FLAG + 14) * 32]) : "memory");
              if (v >= 128) break;
              __nanosleep(500);
            }
          }
          const uint32_t dst = sb + sl * ES, fb = bar + B_RAWX + 8 * sl;
          mbar_expect(fb, ES);
          for (int q = 0; q < 4; q++) tma_ld2(dst + q * 8192, &tm.w30, rank * 256 + q * 64, (k + 3) * 64, fb);
          for (int q = 0; q < 2; q++) tma_ld3(dst + 32768 + q * XBLK, &tm.xe[q], (k + 3) * 64, 0, b, fb);
        }
        __syncwarp();
      }
      fence_regs(ea);
      fence_regs(eb);
      float* e0 = g_E + ((b * 8 + rank * 4 + wg * 2) * NT + 10 * (lane & 2) + (lane & 1)) * 64 + 16 * w + (lane >> 2);
#pragma unroll
      for (int i = 0; i < 80; i++) {
        const int o = (40 * ((i >> 2) & 3) + 2 * (i >> 4) + 10 * (i & 1)) * 64 + ((i >> 1) & 1) * 8;
        e0[o] = ea[i];
        e0[o + NT * 64] = eb[i];
      }
      asm volatile("bar.sync 3, 256;" ::: "memory");
      if (threadIdx.x == 0) {
        fence_release();
        red_add(&ctr[C_E * 32]);
        PROF_T(28);
      }
      asm volatile("barrier.cluster.arrive.relaxed.aligned;\nbarrier.cluster.wait.aligned;" ::: "memory");
      return;
    }
    if (w < 2 && elect_one()) {
      const uint32_t fb = bar + B_RAWW + 8 * (wg * 2 + w);
      mbar_expect(fb, 2048);
      tma_ld3h(sb + OFF_WRAW + (wg * 2 + w) * 2048, &tm.we, 0, 0, (w * 64 + w_row(id)) * 8 + rank * 2 + wg, fb, policy_evict_first());
      if (!w) mbar_arrive(fb);
    }
    __syncwarp();
    {
      float yr[80], yi[80], t[32];

      int xs = 0, xph = 0;
      if (threadIdx.x == 0) PROF_T(24);
      W_WAIT(0);
      t_issue<false>(t, sb, WRAW(0));
      wg_wait<0>();
      W_FINISH();
      if (threadIdx.x == 0) PROF_T(25);
#pragma unroll 1
      for (int m = 0; m <= LW; m++) {
        X_WAIT();
        X_ISSUE();
        wg_wait<0>();
        X_FINISH((2 * id + wg) & 7);
        if (threadIdx.x == 0 && m == 0) PROF_T(26);
        if (has_x2(id, m, wg)) {
          X_WAIT();
          X_ISSUE();
          wg_wait<0>();
          X_FINISH(id & 7);
        }
        if (m < LW && m) {
          W_WAIT(m);
          t_issue<false>(t, sb, WRAW(m));
          wg_wait<0>();
          W_FINISH();
        }
      }
      if (threadIdx.x == 0) PROF_T(27);
      const int ym = lane >> 3, yr8 = lane & 7;
      const uint32_t yad = (ym >> 1) * 4096 + yr8 * 128 + (((2 * w + (ym & 1)) ^ yr8) << 4);
#define STAGE_PROF0()
#define STAGE_PROF1()
#define STAGE_BEGIN() PROF_W(wfull, mbar_wait(bar + B_FULL + 8 * (v & 3), (v >> 2) & 1)); STAGE_PROF0(); const uint32_t st = sb + (v & 3) * G_STAGE
#define RELEASE(vv) do { if (w == 0 && lane < 2) mbar_arrive_cluster(bar + B_EMPTY + 8 * ((vv) & 3), lane, 1); } while (0)
#define XRAW (sb + OFF_XR + (wg * 3 + xs) * 8192)
#define STAGE_W0(mw, sd) do { W_WAIT(mw); batch<1, 0, 2>(yr, yi, t, st, wg, sd, sb + OFF_F, WRAW(mw)); wg_wait<1>(); W_FINISH(); wg_wait<0>(); RELEASE(v); } while (0)
#define STAGE_PLAIN0(sd) do { batch<0, 0, 2>(yr, yi, t, st, wg, sd, 0, 0); wg_wait<0>(); RELEASE(v); } while (0)
#define STAGE_W1(mw, sd) do { W_WAIT(mw); batch<1, 0, 1>(yr, yi, t, st, wg, sd, sb + OFF_F, WRAW(mw)); wg_wait<1>(); if (sd) RELEASE(v - 1); \
                              W_FINISH(); batch<0, 1, 2>(yr, yi, t, st, wg, 1, 0, 0); } while (0)
      constexpr int VX = 31 - 2 * LW;
#pragma unroll 1
      for (int v = 0; v < VX; v++) {
        const int m = ((v + 1) >> 1) + LW;
        STAGE_BEGIN();
        if (!(v & 1)) {
          STAGE_W1(m, v != 0);
        } else {
          X_WAIT();
          batch<4, 0, 1>(yr, yi, t, st, wg, 1, sb + OFF_F, XRAW);
          wg_wait<1>();
          RELEASE(v - 1);
          X_FINISH((2 * id + wg) & 7);
          if (has_x2(id, m, wg)) {
            X_WAIT();
            batch<4, 1, 2>(yr, yi, t, st, wg, 1, sb + OFF_F, XRAW);
            wg_wait<1>();
            X_FINISH(id & 7);
          } else {
            batch<0, 1, 2>(yr, yi, t, st, wg, 1, 0, 0);
          }
        }
        STAGE_PROF1();
      }
      wg_wait<0>();
      RELEASE(VX - 1);
#pragma unroll 1
      for (int v = VX; v < 32; v++) {
        const int m = ((v + 1) >> 1) + LW;
        STAGE_BEGIN();
        if (!(v & 1) || v == 31) STAGE_W0(m, 1); else STAGE_PLAIN0(1);
        STAGE_PROF1();
      }
      fence_regs(yr);
      fence_regs(yi);
      {
        uint32_t hold[32];
#pragma unroll
        for (int j = 0; j < 20; j++) {
          const uint32_t p0 = pack2(yr[4 * j], yr[4 * j + 1]), p1 = pack2(yr[4 * j + 2], yr[4 * j + 3]);
          const uint32_t p2 = pack2(yi[4 * j], yi[4 * j + 1]), p3 = pack2(yi[4 * j + 2], yi[4 * j + 3]);
          if (j < 12) {
            stsm4t(sb + OFF_XR + wg * 3 * 8192 + yad + (j >> 2) * 8192 + (j & 3) * 1024, p0, p1, p2, p3);
          } else {
            hold[4 * j - 48] = p0; hold[4 * j - 47] = p1; hold[4 * j - 46] = p2; hold[4 * j - 45] = p3;
          }
        }
#pragma unroll
        for (int j = 0; j < 32; j++) asm volatile("" : "+r"(hold[j])::"memory");
        __syncwarp();
        if (lane == 0) mbar_arrive(bar + B_Y + 8 * wg);
        if (threadIdx.x == 0) PROF_T(2);
#pragma unroll
        for (int v = 32; v < 34; v++) {
          STAGE_BEGIN();
          STAGE_PLAIN0(v != 32);
          STAGE_PROF1();
        }
        mbar_wait(bar + B_YFREE + 8 * wg, 0);
#pragma unroll
        for (int j = 0; j < 8; j++)
          stsm4t(sb + OFF_XR + wg * 3 * 8192 + yad + (j >> 2) * 8192 + (j & 3) * 1024, hold[4 * j], hold[4 * j + 1], hold[4 * j + 2], hold[4 * j + 3]);
        __syncwarp();
        if (lane == 0) mbar_arrive(bar + B_Y + 8 * wg);
#pragma unroll
        for (int j = 0; j < 32; j++) t[j] = __uint_as_float(hold[j]);
      }
#pragma unroll 1
      for (int v = 34; v < 64; v++) {
        const int m = (v >> 1) + LW;
        STAGE_BEGIN();
        if (!(v & 1) && m < 32) {
          STAGE_W0(m, 1);
        } else {
          STAGE_PLAIN0(1);
          if (v == 49 && wg == 0) part_ptr(xbuf, id >> 6, w >> 1, rank * 2 + ((id >> 1) & 1), (id >> 2) & 15)[(w & 1) * 32 + lane] = ~0ull;
        }
        STAGE_PROF1();
      }
      wg_wait<0>();
      fence_regs(yr);
      fence_regs(yi);
      mbar_wait(bar + B_EMPTY + 8 * 2, 1);
#pragma unroll
      for (int j = 0; j < 20; j++) {
        stsm4t(sb + wg * 8192 + yad + (j >> 2) * 16384 + (j & 3) * 1024, pack2(yr[4 * j], yr[4 * j + 1]), pack2(yr[4 * j + 2], yr[4 * j + 3]),
               pack2(yi[4 * j], yi[4 * j + 1]), pack2(yi[4 * j + 2], yi[4 * j + 3]));
        if ((j & 3) == 3) {
          __syncwarp();
          if (lane == 0) mbar_arrive(bar + B_YP + 8 * (wg * 5 + (j >> 2)));
        }
      }
      if (threadIdx.x == 0) PROF_T(3);
    }
    asm volatile("barrier.cluster.arrive.relaxed.aligned;" ::: "memory");
    lane = lane_id();
    const int tid = warp * 32 + lane, b = id >> 6, u = (id >> 1) & 31;
    const int dq = rank * 2 + (u & 1), tr = u >> 1;
    const int a = lane & 3, d0 = 16 * w + (lane >> 2);
    float2* s_red = (float2*)(smem_raw + OFF_WRAW);
    const uint32_t oad = wg * 8192 + ((lane >> 4) * 8 + (lane & 7)) * 128 + (((2 * w + ((lane >> 3) & 1)) ^ (lane & 7)) << 4);
    float hz[28];
#pragma unroll
    for (int i = 0; i < 28; i++) hz[i] = 0.f;
#pragma unroll 1
    for (int hf = 0; hf < 2; hf++) {
      const uint32_t base = sb + (hf ? 0 : OFF_XR), last = hf ? 0 : OFF_H0B - 65536 - OFF_XR;
      float acc[5][28];
      float q1[4] = {0.f, 0.f, 0.f, 0.f}, q2[4] = {0.f, 0.f, 0.f, 0.f};
      if (hf == 0) { mbar_wait(bar + B_H0, 0); mbar_wait(bar + B_H0C, 0); }
      const float* se = (const float*)(smem_raw + OFF_E + hf * 2560) + wg * 64 + d0;
#pragma unroll
      for (int k2 = 0; k2 < 4; k2++) {
        if (k2 < 3) {
          if (hf) mbar_wait(bar + B_H1 + 8 * k2, 0);
          else if (k2 == 2) mbar_wait(bar + B_H0 + 8, 0);
          const uint64_t da = mk_desc(base + (4 * k2 + wg) * 8192 + (k2 == 2 ? last : 0)), db = mk_desc(sb + OFF_F);
          wg_fence();
#pragma unroll
          for (int kk = 0; kk < 4; kk++) {
            wgmma_inv<1>(acc[2 * k2], da + 128 * kk, db + 2 * kk, kk);
            if (k2 < 2) wgmma_inv<1>(acc[2 * k2 + 1], da + 1024 + 128 * kk, db + 2 * kk, kk);
          }
          wg_commit();
        }
        if (k2 > 0) {
          if (k2 < 3) wg_wait<1>(); else wg_wait<0>();
#pragma unroll
          for (int k = 2 * k2 - 2; k < 2 * k2 && k < 5; k++) {
            fence_regs(acc[k]);
            if (a == 0) {
              acc[k][25] += se[k * 128];
              acc[k][27] += se[k * 128 + 8];
            }
            if (k == 4 && tr == 15 && wg == 1) {
#pragma unroll
              for (int i = 16; i < 28; i++)
                if (8 * (i >> 2) + (i & 1) + 2 * a >= LOUT - (NT - 1) * MT) acc[k][i] = 0.f;
            }
#pragma unroll
            for (int i = 0; i < 28; i++) {
              q1[i & 3] += acc[k][i];
              q2[i & 3] = fmaf(acc[k][i], acc[k][i], q2[i & 3]);
            }
            fence_regs(q1);
            fence_regs(q2);
          }
        }
      }
      float s1[2] = {q1[0] + q1[1], q1[2] + q1[3]}, s2[2] = {q2[0] + q2[1], q2[2] + q2[3]};
#pragma unroll
      for (int i = 0; i < 2; i++) {
#pragma unroll
        for (int o = 1; o < 4; o <<= 1) {
          s1[i] += __shfl_xor_sync(0xffffffffu, s1[i], o);
          s2[i] += __shfl_xor_sync(0xffffffffu, s2[i], o);
        }
      }
      if (a == 0) {
        s_red[wg * 64 + d0] = make_float2(s1[0], s2[0]);
        s_red[wg * 64 + d0 + 8] = make_float2(s1[1], s2[1]);
      }
      asm volatile("bar.sync 3, 256;" ::: "memory");
      if (tid == 0) PROF_T(6 + 3 * hf);
      if (tid < 64) {
        const float2 p0 = s_red[tid], p1 = s_red[64 + tid];
        const float x1 = p0.x + p1.x, x2 = p0.y + p1.y;
        const unsigned long long v = ((unsigned long long)(__float_as_uint(x2) & 0x7fffffffu) << 32) | __float_as_uint(x1);
        asm volatile("st.relaxed.gpu.global.u64 [%0], %1;" ::"l"(part_ptr(xbuf, b, hf, dq, tr) + tid), "l"(v) : "memory");
      }
      if (hf) {
        gelu_store(hz, sb + OFF_H0B + oad);
        __syncwarp();
        if (lane == 0) mbar_arrive(bar + B_OUT + 8 * (wg * 5 + 4));
      }
      {
        const unsigned long long* q = part_ptr(xbuf, b, hf, dq, (tid >> 6) * 4) + (tid & 63);
        unsigned long long v[4];
        poll64x4(q, v);
        float x1 = 0.f, x2 = 0.f;
#pragma unroll
        for (int i = 0; i < 4; i++) {
          x1 += __uint_as_float((uint32_t)v[i]);
          x2 += __uint_as_float((uint32_t)(v[i] >> 32));
        }
        s_red[128 + tid] = make_float2(x1, x2);
      }
      asm volatile("bar.sync 3, 256;" ::: "memory");
      if (tid == 0) PROF_T(7 + 3 * hf);
#pragma unroll
      for (int i = 0; i < 2; i++) {
        const float2 q0 = s_red[128 + d0 + 8 * i], q1 = s_red[192 + d0 + 8 * i], q2 = s_red[256 + d0 + 8 * i], q3 = s_red[320 + d0 + 8 * i];
        const float mu = ((q0.x + q1.x) + (q2.x + q3.x)) * (1.f / LOUT);
        const float var = fmaxf(((q0.y + q1.y) + (q2.y + q3.y)) * (1.f / LOUT) - mu * mu, 0.f);
        const __nv_bfloat16* gb = (const __nv_bfloat16*)(smem_raw + OFF_GB + hf * 256) + d0 + 8 * i;
        s1[i] = 0.5f * __bfloat162float(gb[0]) * rsqrtf(var + 1e-5f);
        s2[i] = 0.5f * __bfloat162float(gb[64]) - mu * s1[i];
      }
#pragma unroll
      for (int k = 0; k < 5; k++) {
#pragma unroll
        for (int i = 0; i < 28; i++) hz[i] = fmaf(acc[k][i], s1[(i >> 1) & 1], s2[(i >> 1) & 1]);
        if (k == 4) break;
        gelu_store(hz, base + oad + k * 16384);
        float z;
        asm volatile("ld.volatile.shared.f32 %0, [%1];" : "=f"(z) : "r"(sb + OFF_F + 55 * 128) : "memory");
        s2[0] += z;
        s2[1] += z;
        __syncwarp();
        if (lane == 0) mbar_arrive(bar + B_OUT + 8 * (wg * 5 + k));
      }
      if (tid == 0) PROF_T(8 + 3 * hf);
    }
    gelu_store(hz, sb + 4 * 16384 + oad);
    __syncwarp();
    if (lane == 0) mbar_arrive(bar + B_OUT + 8 * (wg * 5 + 4));
    asm volatile("barrier.cluster.wait.aligned;" ::: "memory");
  }
}

__global__ void __launch_bounds__(256) fb_conv(const __nv_bfloat16* __restrict__ x, const __nv_bfloat16* __restrict__ w, float* __restrict__ h) {
  __shared__ float sx[16][65], sw[16][64];
  const int b = blockIdx.z, l0 = blockIdx.y * 64, d0 = blockIdx.x * 64, tx = threadIdx.x & 15, ty = threadIdx.x >> 4;
  float acc[4][4] = {};
  for (int k0 = 0; k0 < 31 * 512; k0 += 16) {
    for (int i = threadIdx.x; i < 1024; i += 256) {
      const int l = min(l0 + (i >> 4), LOUT - 1);
      sx[i & 15][i >> 4] = __bfloat162float(x[((size_t)b * 16000 + 2 * l) * 512 + k0 + (i & 15)]);
      sw[i >> 6][i & 63] = __bfloat162float(w[(size_t)(k0 + (i >> 6)) * 512 + d0 + (i & 63)]);
    }
    __syncthreads();
#pragma unroll
    for (int k = 0; k < 16; k++)
#pragma unroll
      for (int i = 0; i < 4; i++)
#pragma unroll
        for (int j = 0; j < 4; j++) acc[i][j] = fmaf(sx[k][ty * 4 + i], sw[k][tx * 4 + j], acc[i][j]);
    __syncthreads();
  }
  for (int i = 0; i < 4; i++)
    for (int j = 0; j < 4; j++)
      if (l0 + ty * 4 + i < LOUT) h[((size_t)b * LOUT + l0 + ty * 4 + i) * 512 + d0 + tx * 4 + j] = acc[i][j];
}
__global__ void __launch_bounds__(256) fb_norm(const float* __restrict__ h, const __nv_bfloat16* __restrict__ gamma,
                                               const __nv_bfloat16* __restrict__ beta, __nv_bfloat16* __restrict__ out) {
  __shared__ float r[2][32][8];
  const int c = threadIdx.x & 7, q = threadIdx.x >> 3, d = blockIdx.x * 8 + c;
  const size_t base = (size_t)blockIdx.y * LOUT * 512 + d;
  float mu = 0.f, var = 0.f;
  for (int pass = 0; pass < 2; pass++) {
    float s = 0.f;
    for (int l = q; l < LOUT; l += 32) {
      const float v = h[base + (size_t)l * 512] - mu;
      s += pass ? v * v : v;
    }
    r[pass][q][c] = s;
    __syncthreads();
    s = 0.f;
    for (int i = 0; i < 32; i++) s += r[pass][i][c];
    if (pass) var = s / LOUT; else mu = s / LOUT;
  }
  const float g = __bfloat162float(gamma[d]) * rsqrtf(var + 1e-5f), be = __bfloat162float(beta[d]);
  for (int l = q; l < LOUT; l += 32) {
    const float z = (h[base + (size_t)l * 512] - mu) * g + be;
    out[base + (size_t)l * 512] = __float2bfloat16(0.5f * z * (1.f + tanhf(0.7978845608028654f * (z + 0.044715f * z * z * z))));
  }
}

typedef CUresult (*EncFn)(CUtensorMap*, CUtensorMapDataType, cuuint32_t, void*, const cuuint64_t*, const cuuint64_t*, const cuuint32_t*,
                          const cuuint32_t*, CUtensorMapInterleave, CUtensorMapSwizzle, CUtensorMapL2promotion, CUtensorMapFloatOOBfill);

void encode(EncFn fn, CUtensorMap* m, int rank, void* base, const cuuint64_t* dims, const cuuint64_t* strides, const cuuint32_t* box,
            CUtensorMapL2promotion promo) {
  cuuint32_t es[5] = {1, 1, 1, 1, 1};
  fn(m, CU_TENSOR_MAP_DATA_TYPE_BFLOAT16, rank, base, dims, strides, box, es, CU_TENSOR_MAP_INTERLEAVE_NONE, CU_TENSOR_MAP_SWIZZLE_128B, promo,
     CU_TENSOR_MAP_FLOAT_OOB_FILL_NONE);
}

}

extern "C" void kernel_launch(void* const* d_in, const int* in_sizes, int n_in, void* d_out, int out_size) {
  (void)in_sizes; (void)n_in; (void)out_size;
  const __nv_bfloat16* x = (const __nv_bfloat16*)d_in[0];
  const __nv_bfloat16* w = (const __nv_bfloat16*)d_in[1];
  const __nv_bfloat16* gamma = (const __nv_bfloat16*)d_in[2];
  const __nv_bfloat16* beta = (const __nv_bfloat16*)d_in[3];
  void* fnp = nullptr;
  cudaDriverEntryPointQueryResult qr;
  cudaGetDriverEntryPoint("cuTensorMapEncodeTiled", &fnp, cudaEnableDefault, &qr);
  EncFn fn = (EncFn)fnp;
  void *fptr = nullptr, *xptr = nullptr;
  cudaGetSymbolAddress(&fptr, g_Fimg);
  cudaGetSymbolAddress(&xptr, g_X);
  xptr = (void*)(((uintptr_t)xptr + (1u << 21) - 1) & ~(uintptr_t)((1u << 21) - 1));
  const CUtensorMapL2promotion P0 = CU_TENSOR_MAP_L2_PROMOTION_NONE, P128 = CU_TENSOR_MAP_L2_PROMOTION_L2_128B;
  Maps m;
  {
    cuuint64_t d[3] = {1024, 8000, 2}, s[2] = {2048, 8000ull * 2048};
    cuuint32_t bx[3] = {64, 64, 1};
    encode(fn, &m.x, 3, (void*)x, d, s, bx, P128);
  }
  for (int ph = 0; ph < 2; ph++) {
    cuuint64_t d[3] = {64, (cuuint64_t)(16 - ph), 4096}, s[2] = {2ull * 262144 * 2, 128};
    cuuint32_t bx[3] = {64, 16, 1};
    encode(fn, ph ? &m.wo : &m.we, 3, (void*)(w + (size_t)ph * 262144), d, s, bx, P128);
  }
  for (int par = 0; par < 2; par++) {
    cuuint64_t d[5] = {(cuuint64_t)XPAGES << 20, 2, 4, 2, 2}, s[4] = {par ? 0x1000u : 0x3000u, 1u << 14, 1u << 18, 1u << 20};
    cuuint32_t bx[5] = {64, 2, 4, 2, 2};
    encode(fn, &m.xst[par], 5, xptr, d, s, bx, P0);
  }
  {
    cuuint64_t d[4] = {64, 32, 2, (cuuint64_t)WR * WSLOT / 128}, s[3] = {2ull * WBLK, 4096, 128};
    cuuint32_t bx[4] = {64, 32, 2, 1};
    encode(fn, &m.wst, 4, (char*)xptr + ((size_t)PG_W << 21), d, s, bx, P0);
  }
  for (int par = 0; par < 2; par++) {
    cuuint64_t d[4] = {64, (cuuint64_t)XPAGES << 14, 2, 2}, s[3] = {128, par ? 0xf000u : 0x11000u, 1u << 14};
    cuuint32_t bx[4] = {64, 32, 2, 2};
    encode(fn, &m.yld[par], 4, xptr, d, s, bx, P128);
  }
  {
    cuuint64_t d[3] = {512, LOUT, 2}, s[2] = {1024, (cuuint64_t)LOUT * 1024};
    cuuint32_t bx[3] = {64, MT, 1};
    encode(fn, &m.out, 3, d_out, d, s, bx, P0);
  }
  for (int q = 0; q < 2; q++) {
    cuuint64_t d[3] = {512, (cuuint64_t)(NT - q), 2}, s[2] = {MT * 2048, 8000ull * 2048};
    cuuint32_t bx[3] = {64, NT, 1};
    encode(fn, &m.xe[q], 3, (void*)(x + q * 64 * 1024), d, s, bx, P128);
  }
  {
    cuuint64_t d[2] = {512, 512}, s[1] = {1024};
    cuuint32_t bx[2] = {64, 64};
    encode(fn, &m.w30, 2, (void*)(w + 30 * 262144), d, s, bx, P128);
  }
  cudaFuncSetAttribute(k1_main, cudaFuncAttributeMaxDynamicSharedMemorySize, SMEM_BYTES);
  cudaLaunchConfig_t cfg = {};
  cfg.gridDim = dim3(132);
  cfg.blockDim = dim3(512);
  cfg.dynamicSmemBytes = SMEM_BYTES;
  int clusters = 0;
  cudaOccupancyMaxActiveClusters(&clusters, k1_main, &cfg);
  if (clusters < 66) {
    fb_conv<<<dim3(8, (LOUT + 63) / 64, 2), 256>>>(x, w, (float*)xptr);
    fb_norm<<<dim3(64, 2), 256>>>((const float*)xptr, gamma, beta, (__nv_bfloat16*)d_out);
    return;
  }
  k1_main<<<132, 512, SMEM_BYTES>>>((uint8_t*)xptr, fptr, gamma, beta, m);
}
```

```cpp
#include <cuda_runtime.h>
#include <cuda_bf16.h>
#include <cuda.h>
#include <stdint.h>

namespace {

constexpr int LOUT = 7985;
constexpr int MT = 50;
constexpr int NT = 160;
constexpr int XBLK = NT * 128;
constexpr int WBLK = 16384;
constexpr int LW = 4;
constexpr int WR = 10;
constexpr int WSLOT = 64 * WBLK;
constexpr int PG_Y = 20, PG_W = 25, XPAGES = 30;
constexpr int YA = 2;
constexpr int NFL = 2;
constexpr int XKEEP = 9;
constexpr int YFLUSH = 20 + LW;

__device__ __align__(1024) uint8_t g_X[(XPAGES + 2) << 21];
__device__ __align__(128) float g_E[16 * NT * 64];
constexpr int CTR_OFF = (XPAGES << 21) + 0x100000, PART_OFF = CTR_OFF + 0x40000;
constexpr int C_FLAG = 0, C_LOADED = 128  , C_Y = 256, C_E = 260, C_REG = 261, C_EXIT = 262, C_SIDE = 32;
__device__ __forceinline__ unsigned long long* part_ptr(uint8_t* xbuf, int side, int hf, int dq, int tr) {
  return (unsigned long long*)(xbuf + PART_OFF + ((hf * 4 + dq) * 2 + (tr >> 3)) * 8192 + ((side ^ hf ^ (tr >> 3)) << 12) + (tr & 7) * 512);
}

__device__ __align__(128) const uint32_t g_Fimg[2048] = {
 0x3f803f80,0x3f7d3f7f,0x3f783f7b,0x3f713f75,0x3f673f6d,0x3f5c3f62,0x3f4e3f55,0x3f3e3f46,0x3f2c3f35,0x3f183f22,0x3f043f0e,0x3edb3ef1,0x3eac3ec4,0x3e793e95,0x3e163e48,0x3d493dc9,
 0xbd490000,0xbe16bdc9,0xbe79be48,0xbeacbe95,0xbedbbec4,0xbf04bef1,0xbf18bf0e,0xbf2cbf22,0xbf3ebf35,0xbf4ebf46,0xbf5cbf55,0xbf67bf62,0xbf71bf6d,0xbf78bf75,0xbf7dbf7b,0xbf80bf7f,
 0x3e793ec4,0xbd493dc9,0xbeacbe48,0xbf18bef1,0x3f7d3f80,0x3f673f75,0x3f3e3f55,0x3f043f22,0xbf5cbf6d,0xbf2cbf46,0xbedbbf0e,0xbe16be95,0xbf4ebf35,0xbf71bf62,0xbf80bf7b,0xbf78bf7f,
 0x3f783f6d,0x3f803f7f,0x3f713f7b,0x3f4e3f62,0x3e160000,0x3edb3e95,0x3f2c3f0e,0x3f5c3f46,0xbf04bec4,0xbf3ebf22,0xbf67bf55,0xbf7dbf75,0x3f183f35,0x3eac3ef1,0x3d493e48,0xbe79bdc9,
 0xbf04bf35,0xbd49be95,0x3edb3e48,0x3f4e3f22,0x3f7d3f6d,0x3f713f7f,0x3f2c3f55,0x3e793ef1,0x3f783f80,0x3f3e3f62,0x3eac3f0e,0xbe163dc9,0xbf18bec4,0xbf67bf46,0xbf80bf7b,0xbf5cbf75,
 0x3f5c3f35,0x3f803f75,0x3f673f7b,0x3f183f46,0x3e163ec4,0xbeacbdc9,0xbf3ebf0e,0xbf78bf62,0xbe790000,0xbf2cbef1,0xbf71bf55,0xbf7dbf7f,0xbf4ebf6d,0xbedbbf22,0x3d49be48,0x3f043e95,
 0xbf2cbec4,0xbf7dbf62,0xbf5cbf7b,0xbeacbf22,0x3f673f35,0x3f783f7f,0x3f183f55,0xbd493e95,0xbf80bf6d,0xbf4ebf75,0xbe79bf0e,0x3edb3dc9,0x3f713f80,0x3f043f46,0xbe163e48,0xbf3ebef1,
 0x3f3e3f6d,0x3e163ef1,0xbf04be48,0xbf71bf46,0xbedbbf35,0x3e79bdc9,0x3f4e3f0e,0x3f803f75,0x3d493ec4,0xbf18be95,0xbf78bf55,0xbf67bf7f,0x3eac0000,0x3f5c3f22,0x3f7d3f7b,0x3f2c3f62,
 0xbedb0000,0xbf78bf46,0xbf4ebf7b,0xbd49bef1,0x3f3e3ec4,0x3f7d3f75,0x3f043f55,0xbeac3dc9,0xbf71bf35,0xbf5cbf7f,0xbe16bf0e,0x3f2c3e95,0x3f803f6d,0x3f183f62,0xbe793e48,0xbf67bf22,
 0x3f673f80,0x3e793f22,0xbf18be48,0xbf80bf62,0xbf2cbf6d,0x3e16be95,0x3f5c3f0e,0x3f713f7f,0x3eac3f35,0xbf04bdc9,0xbf7dbf55,0xbf3ebf75,0x3d49bec4,0x3f4e3ef1,0x3f783f7b,0x3edb3f46,
 0xbf7dbf6d,0xbeacbf46,0x3f2c3e48,0x3f783f75,0x3f040000,0x3f803f62,0x3edb3f55,0xbf18bdc9,0x3f4e3ec4,0x3f673f7f,0x3d493f0e,0xbf5cbef1,0x3e793f35,0xbf3ebe95,0xbf71bf7b,0xbe16bf22,
 0x3e16bec4,0x3f713f22,0x3f3e3f7b,0xbe793e95,0x3f5c3f80,0xbd493ef1,0xbf67bf0e,0xbf4ebf7f,0x3f183f6d,0xbedb3dc9,0xbf80bf55,0xbf04bf62,0xbf78bf35,0xbf2cbf75,0x3eacbe48,0x3f7d3f46,
 0x3f7d3f35,0x3edb3f62,0xbf3ebe48,0xbf5cbf7f,0x3e79bec4,0x3f803f46,0x3eac3f55,0xbf4ebe95,0xbf180000,0xbf71bf75,0x3d49bf0e,0x3f783f22,0x3f043f6d,0xbf2cbdc9,0xbf67bf7b,0x3e16bef1,
 0xbe16bf35,0x3f673ef1,0x3f2c3f7b,0xbf043dc9,0xbf78bf6d,0xbd49bf22,0x3f713f0e,0x3f183f75,0x3f4e3f80,0xbeac3e95,0xbf80bf55,0xbe79bf46,0x3f5c3ec4,0x3f3e3f7f,0xbedb3e48,0xbf7dbf62,
 0xbedbbf6d,0x3f5c3e95,0x3f183f7b,0xbf3ebdc9,0xbd49bf35,0x3f7d3f22,0x3e793f55,0xbf71bef1,0x3eacbec4,0x3f783f62,0xbe163f0e,0xbf80bf46,0x3f2c0000,0x3f4e3f7f,0xbf043e48,0xbf67bf75,
 0x3f673ec4,0x3f043f75,0xbf4ebe48,0xbf2cbf7f,0x3f803f35,0x3e163f46,0xbf78bf0e,0xbeacbf62,0x3f713f6d,0xbe793ef1,0xbf7dbf55,0x3d49bf22,0x3f3e3f80,0xbf183dc9,0xbf5cbf7b,0x3edbbe95,
 0xbd490000,0xbe16bdc9,0xbe79be48,0xbeacbe95,0xbedbbec4,0xbf04bef1,0xbf18bf0e,0xbf2cbf22,0xbf3ebf35,0xbf4ebf46,0xbf5cbf55,0xbf67bf62,0xbf71bf6d,0xbf78bf75,0xbf7dbf7b,0xbf80bf7f,
 0xbf80bf80,0xbf7dbf7f,0xbf78bf7b,0xbf71bf75,0xbf67bf6d,0xbf5cbf62,0xbf4ebf55,0xbf3ebf46,0xbf2cbf35,0xbf18bf22,0xbf04bf0e,0xbedbbef1,0xbeacbec4,0xbe79be95,0xbe16be48,0xbd49bdc9,
 0xbf78bf6d,0xbf80bf7f,0xbf71bf7b,0xbf4ebf62,0xbe160000,0xbedbbe95,0xbf2cbf0e,0xbf5cbf46,0x3f043ec4,0x3f3e3f22,0x3f673f55,0x3f7d3f75,0xbf18bf35,0xbeacbef1,0xbd49be48,0x3e793dc9,
 0x3e793ec4,0xbd493dc9,0xbeacbe48,0xbf18bef1,0x3f7d3f80,0x3f673f75,0x3f3e3f55,0x3f043f22,0xbf5cbf6d,0xbf2cbf46,0xbedbbf0e,0xbe16be95,0xbf4ebf35,0xbf71bf62,0xbf80bf7b,0xbf78bf7f,
 0x3f5c3f35,0x3f803f75,0x3f673f7b,0x3f183f46,0x3e163ec4,0xbeacbdc9,0xbf3ebf0e,0xbf78bf62,0xbe790000,0xbf2cbef1,0xbf71bf55,0xbf7dbf7f,0xbf4ebf6d,0xbedbbf22,0x3d49be48,0x3f043e95,
 0x3f043f35,0x3d493e95,0xbedbbe48,0xbf4ebf22,0xbf7dbf6d,0xbf71bf7f,0xbf2cbf55,0xbe79bef1,0xbf78bf80,0xbf3ebf62,0xbeacbf0e,0x3e16bdc9,0x3f183ec4,0x3f673f46,0x3f803f7b,0x3f5c3f75,
 0xbf3ebf6d,0xbe16bef1,0x3f043e48,0x3f713f46,0x3edb3f35,0xbe793dc9,0xbf4ebf0e,0xbf80bf75,0xbd49bec4,0x3f183e95,0x3f783f55,0x3f673f7f,0xbeac0000,0xbf5cbf22,0xbf7dbf7b,0xbf2cbf62,
 0xbf2cbec4,0xbf7dbf62,0xbf5cbf7b,0xbeacbf22,0x3f673f35,0x3f783f7f,0x3f183f55,0xbd493e95,0xbf80bf6d,0xbf4ebf75,0xbe79bf0e,0x3edb3dc9,0x3f713f80,0x3f043f46,0xbe163e48,0xbf3ebef1,
 0xbf67bf80,0xbe79bf22,0x3f183e48,0x3f803f62,0x3f2c3f6d,0xbe163e95,0xbf5cbf0e,0xbf71bf7f,0xbeacbf35,0x3f043dc9,0x3f7d3f55,0x3f3e3f75,0xbd493ec4,0xbf4ebef1,0xbf78bf7b,0xbedbbf46,
 0xbedb0000,0xbf78bf46,0xbf4ebf7b,0xbd49bef1,0x3f3e3ec4,0x3f7d3f75,0x3f043f55,0xbeac3dc9,0xbf71bf35,0xbf5cbf7f,0xbe16bf0e,0x3f2c3e95,0x3f803f6d,0x3f183f62,0xbe793e48,0xbf67bf22,
 0x3e16bec4,0x3f713f22,0x3f3e3f7b,0xbe793e95,0x3f5c3f80,0xbd493ef1,0xbf67bf0e,0xbf4ebf7f,0x3f183f6d,0xbedb3dc9,0xbf80bf55,0xbf04bf62,0xbf78bf35,0xbf2cbf75,0x3eacbe48,0x3f7d3f46,
 0x3f7d3f6d,0x3eac3f46,0xbf2cbe48,0xbf78bf75,0xbf040000,0xbf80bf62,0xbedbbf55,0x3f183dc9,0xbf4ebec4,0xbf67bf7f,0xbd49bf0e,0x3f5c3ef1,0xbe79bf35,0x3f3e3e95,0x3f713f7b,0x3e163f22,
 0x3e163f35,0xbf67bef1,0xbf2cbf7b,0x3f04bdc9,0x3f783f6d,0x3d493f22,0xbf71bf0e,0xbf18bf75,0xbf4ebf80,0x3eacbe95,0x3f803f55,0x3e793f46,0xbf5cbec4,0xbf3ebf7f,0x3edbbe48,0x3f7d3f62,
 0x3f7d3f35,0x3edb3f62,0xbf3ebe48,0xbf5cbf7f,0x3e79bec4,0x3f803f46,0x3eac3f55,0xbf4ebe95,0xbf180000,0xbf71bf75,0x3d49bf0e,0x3f783f22,0x3f043f6d,0xbf2cbdc9,0xbf67bf7b,0x3e16bef1,
 0x3f673ec4,0x3f043f75,0xbf4ebe48,0xbf2cbf7f,0x3f803f35,0x3e163f46,0xbf78bf0e,0xbeacbf62,0x3f713f6d,0xbe793ef1,0xbf7dbf55,0x3d49bf22,0x3f3e3f80,0xbf183dc9,0xbf5cbf7b,0x3edbbe95,
 0x3edb3f6d,0xbf5cbe95,0xbf18bf7b,0x3f3e3dc9,0x3d493f35,0xbf7dbf22,0xbe79bf55,0x3f713ef1,0xbeac3ec4,0xbf78bf62,0x3e16bf0e,0x3f803f46,0xbf2c0000,0xbf4ebf7f,0x3f04be48,0x3f673f75,
 0x3f2c3f80,0xbf4ebdc9,0xbf04bf7b,0x3f673e95,0x3eac3f6d,0xbf78bef1,0xbe16bf55,0x3f803f22,0xbd493f35,0xbf7dbf46,0x3e79bf0e,0x3f713f62,0xbedb3ec4,0xbf5cbf75,0x3f18be48,0x3f3e3f7f,
 0xbf3e0000,0xbf18bf7f,0x3f5c3e48,0x3edb3f75,0xbf71bec4,0xbe79bf62,0x3f7d3f0e,0x3d493f46,0xbf80bf35,0x3e16bf22,0x3f783f55,0xbeac3ef1,0xbf67bf6d,0x3f04be95,0x3f4e3f7b,0xbf2c3dc9,
 0xbf043ec4,0xbf2cbf7f,0x3f673e48,0x3e163f62,0x3f183f80,0xbf71be95,0xbd49bf55,0x3f783f46,0xbe79bf6d,0x3f803f22,0xbeac3f0e,0xbf4ebf75,0xbf7dbf35,0x3edbbef1,0x3f3e3f7b,0xbf5cbdc9,
 0x3f5c3f6d,0xbf3e3dc9,0xbedbbf7b,0x3f7d3ef1,0x3f4e0000,0x3eac3f75,0xbf80bf0e,0x3e79bf22,0xbf78bec4,0x3d49bf46,0x3f713f55,0xbf183e95,0xbe163f35,0xbf67bf62,0x3f2cbe48,0x3f043f7f,
 0x3e79bf35,0x3f3e3f75,0xbf71be48,0x3e16bf46,0x3f4e3f6d,0xbf67bdc9,0x3d49bf55,0x3f5c3f62,0x3f043f80,0xbf80bef1,0x3edbbf0e,0x3f183f7f,0xbf7dbec4,0x3eacbf22,0x3f2c3f7b,0xbf78be95,
 0x3f783f35,0xbf2c3e95,0xbeacbf7b,0x3f7d3f22,0xbf183ec4,0xbedbbf7f,0x3f803f0e,0xbf043ef1,0xbf5c0000,0xbd49bf62,0x3f673f55,0xbf4e3dc9,0xbe16bf6d,0x3f713f46,0xbf3e3e48,0xbe79bf75,
 0xbf80bec4,0x3f18bef1,0x3e793f7b,0xbf67bf46,0x3f713f35,0xbf5c3dc9,0x3e16bf55,0x3f2c3f75,0xbf3ebf6d,0x3f7d3e95,0xbf043f0e,0xbeacbf7f,0x3edb3f80,0xbf78bf22,0x3f4ebe48,0xbd493f62,
 0x3d493f6d,0xbf4ebf62,0x3f783e48,0xbedb3f22,0x3eacbf35,0x3f043f7f,0xbf7dbf0e,0x3f3ebe95,0xbf2c3ec4,0xbe16bf75,0x3f5c3f55,0xbf71bdc9,0x3f670000,0xbe793f46,0xbf18bf7b,0x3f803ef1,
 0xbf710000,0x3f04bf22,0x3e163f7b,0xbf3ebf62,0x3f803ec4,0xbf4e3e95,0x3e79bf55,0x3edb3f7f,0xbf67bf35,0x3f783dc9,0xbf183f0e,0xbd49bf75,0x3f2c3f6d,0xbf7dbef1,0x3f5cbe48,0xbeac3f46,
 0x3eac3f80,0xbf5cbf46,0x3f7d3e48,0xbf2c3ef1,0x3d49bf6d,0x3f183f75,0xbf78bf0e,0x3f67bdc9,0xbedb3f35,0xbe79bf7f,0x3f4e3f55,0xbf80be95,0x3f3ebec4,0xbe163f62,0xbf04bf7b,0x3f713f22,
 0xbf18bf6d,0x3f673f22,0xbf80be48,0x3f5cbe95,0x3f780000,0xbf3e3ef1,0x3eacbf55,0x3e163f7f,0x3f7d3ec4,0xbf713dc9,0x3f2cbf0e,0xbe793f62,0xbf043f35,0x3d49bf75,0x3edb3f7b,0xbf4ebf46,
 0x3f4ebec4,0xbedb3f46,0xbd49bf7b,0x3f043f75,0x3e793f80,0xbf2cbf62,0x3f713f0e,0xbf7dbdc9,0xbe163f6d,0xbeacbf7f,0x3f3e3f55,0xbf78bef1,0xbf5cbf35,0x3f803e95,0xbf673e48,0x3f18bf22,
 0x3f4e3f35,0xbf71bef1,0x3f803e48,0xbf783dc9,0x3f5cbec4,0xbf2c3f22,0x3edbbf55,0xbe163f75,0xbf7d0000,0x3f67be95,0xbf3e3f0e,0x3f04bf46,0xbe793f6d,0xbd49bf7f,0x3eac3f7b,0xbf18bf62,
 0x3f18bf35,0xbeac3f62,0x3d49bf7b,0x3e793f7f,0xbf04bf6d,0x3f3e3f46,0xbf67bf0e,0x3f7d3e95,0x3e163f80,0xbedbbf75,0x3f2c3f55,0xbf5cbf22,0x3f783ec4,0xbf80bdc9,0x3f71be48,0xbf4e3ef1,
 0x3eacbf6d,0xbe793f75,0x3e16bf7b,0xbd493f7f,0x3f2cbf35,0xbf183f46,0x3f04bf55,0xbedb3f62,0x3f67bec4,0xbf5c3ef1,0x3f4ebf0e,0xbf3e3f22,0x3f800000,0xbf7d3dc9,0x3f78be48,0xbf713e95,
 0x3f713ec4,0xbf78be95,0x3f7d3e48,0xbf80bdc9,0x3f3e3f35,0xbf4ebf22,0x3f5c3f0e,0xbf67bef1,0x3edb3f6d,0xbf04bf62,0x3f183f55,0xbf2cbf46,0x3d493f80,0xbe16bf7f,0x3e793f7b,0xbeacbf75,
 0xbf3e0000,0xbf18bf7f,0x3f5c3e48,0x3edb3f75,0xbf71bec4,0xbe79bf62,0x3f7d3f0e,0x3d493f46,0xbf80bf35,0x3e16bf22,0x3f783f55,0xbeac3ef1,0xbf67bf6d,0x3f04be95,0x3f4e3f7b,0xbf2c3dc9,
 0xbf2cbf80,0x3f4e3dc9,0x3f043f7b,0xbf67be95,0xbeacbf6d,0x3f783ef1,0x3e163f55,0xbf80bf22,0x3d49bf35,0x3f7d3f46,0xbe793f0e,0xbf71bf62,0x3edbbec4,0x3f5c3f75,0xbf183e48,0xbf3ebf7f,
 0xbf5cbf6d,0x3f3ebdc9,0x3edb3f7b,0xbf7dbef1,0xbf4e0000,0xbeacbf75,0x3f803f0e,0xbe793f22,0x3f783ec4,0xbd493f46,0xbf71bf55,0x3f18be95,0x3e16bf35,0x3f673f62,0xbf2c3e48,0xbf04bf7f,
 0xbf043ec4,0xbf2cbf7f,0x3f673e48,0x3e163f62,0x3f183f80,0xbf71be95,0xbd49bf55,0x3f783f46,0xbe79bf6d,0x3f803f22,0xbeac3f0e,0xbf4ebf75,0xbf7dbf35,0x3edbbef1,0x3f3e3f7b,0xbf5cbdc9,
 0x3f783f35,0xbf2c3e95,0xbeacbf7b,0x3f7d3f22,0xbf183ec4,0xbedbbf7f,0x3f803f0e,0xbf043ef1,0xbf5c0000,0xbd49bf62,0x3f673f55,0xbf4e3dc9,0xbe16bf6d,0x3f713f46,0xbf3e3e48,0xbe79bf75,
 0xbe793f35,0xbf3ebf75,0x3f713e48,0xbe163f46,0xbf4ebf6d,0x3f673dc9,0xbd493f55,0xbf5cbf62,0xbf04bf80,0x3f803ef1,0xbedb3f0e,0xbf18bf7f,0x3f7d3ec4,0xbeac3f22,0xbf2cbf7b,0x3f783e95,
 0xbd49bf6d,0x3f4e3f62,0xbf78be48,0x3edbbf22,0xbeac3f35,0xbf04bf7f,0x3f7d3f0e,0xbf3e3e95,0x3f2cbec4,0x3e163f75,0xbf5cbf55,0x3f713dc9,0xbf670000,0x3e79bf46,0x3f183f7b,0xbf80bef1,
 0xbf80bec4,0x3f18bef1,0x3e793f7b,0xbf67bf46,0x3f713f35,0xbf5c3dc9,0x3e16bf55,0x3f2c3f75,0xbf3ebf6d,0x3f7d3e95,0xbf043f0e,0xbeacbf7f,0x3edb3f80,0xbf78bf22,0x3f4ebe48,0xbd493f62,
 0xbeacbf80,0x3f5c3f46,0xbf7dbe48,0x3f2cbef1,0xbd493f6d,0xbf18bf75,0x3f783f0e,0xbf673dc9,0x3edbbf35,0x3e793f7f,0xbf4ebf55,0x3f803e95,0xbf3e3ec4,0x3e16bf62,0x3f043f7b,0xbf71bf22,
 0xbf710000,0x3f04bf22,0x3e163f7b,0xbf3ebf62,0x3f803ec4,0xbf4e3e95,0x3e79bf55,0x3edb3f7f,0xbf67bf35,0x3f783dc9,0xbf183f0e,0xbd49bf75,0x3f2c3f6d,0xbf7dbef1,0x3f5cbe48,0xbeac3f46,
 0x3f4ebec4,0xbedb3f46,0xbd49bf7b,0x3f043f75,0x3e793f80,0xbf2cbf62,0x3f713f0e,0xbf7dbdc9,0xbe163f6d,0xbeacbf7f,0x3f3e3f55,0xbf78bef1,0xbf5cbf35,0x3f803e95,0xbf673e48,0x3f18bf22,
 0x3f183f6d,0xbf67bf22,0x3f803e48,0xbf5c3e95,0xbf780000,0x3f3ebef1,0xbeac3f55,0xbe16bf7f,0xbf7dbec4,0x3f71bdc9,0xbf2c3f0e,0x3e79bf62,0x3f04bf35,0xbd493f75,0xbedbbf7b,0x3f4e3f46,
 0xbf183f35,0x3eacbf62,0xbd493f7b,0xbe79bf7f,0x3f043f6d,0xbf3ebf46,0x3f673f0e,0xbf7dbe95,0xbe16bf80,0x3edb3f75,0xbf2cbf55,0x3f5c3f22,0xbf78bec4,0x3f803dc9,0xbf713e48,0x3f4ebef1,
 0x3f4e3f35,0xbf71bef1,0x3f803e48,0xbf783dc9,0x3f5cbec4,0xbf2c3f22,0x3edbbf55,0xbe163f75,0xbf7d0000,0x3f67be95,0xbf3e3f0e,0x3f04bf46,0xbe793f6d,0xbd49bf7f,0x3eac3f7b,0xbf18bf62,
 0x3f713ec4,0xbf78be95,0x3f7d3e48,0xbf80bdc9,0x3f3e3f35,0xbf4ebf22,0x3f5c3f0e,0xbf67bef1,0x3edb3f6d,0xbf04bf62,0x3f183f55,0xbf2cbf46,0x3d493f80,0xbe16bf7f,0x3e793f7b,0xbeacbf75,
 0xbeac3f6d,0x3e79bf75,0xbe163f7b,0x3d49bf7f,0xbf2c3f35,0x3f18bf46,0xbf043f55,0x3edbbf62,0xbf673ec4,0x3f5cbef1,0xbf4e3f0e,0x3f3ebf22,0xbf800000,0x3f7dbdc9,0xbf783e48,0x3f71be95,
 0xbd493f80,0x3e16bf7f,0xbe793f7b,0x3eacbf75,0xbedb3f6d,0x3f04bf62,0xbf183f55,0x3f2cbf46,0xbf3e3f35,0x3f4ebf22,0xbf5c3f0e,0x3f67bef1,0xbf713ec4,0x3f78be95,0xbf7d3e48,0x3f80bdc9,
 0xbf800000,0x3f7d3dc9,0xbf78be48,0x3f713e95,0xbf67bec4,0x3f5c3ef1,0xbf4ebf0e,0x3f3e3f22,0xbf2cbf35,0x3f183f46,0xbf04bf55,0x3edb3f62,0xbeacbf6d,0x3e793f75,0xbe16bf7b,0x3d493f7f,
 0xbf783ec4,0x3f80bdc9,0xbf71be48,0x3f4e3ef1,0xbe163f80,0x3edbbf75,0xbf2c3f55,0x3f5cbf22,0x3f04bf6d,0xbf3e3f46,0x3f67bf0e,0xbf7d3e95,0xbf18bf35,0x3eac3f62,0xbd49bf7b,0xbe793f7f,
 0x3e793f6d,0x3d49bf7f,0xbeac3f7b,0x3f18bf62,0x3f7d0000,0xbf67be95,0x3f3e3f0e,0xbf04bf46,0xbf5cbec4,0x3f2c3f22,0xbedbbf55,0x3e163f75,0xbf4e3f35,0x3f71bef1,0xbf803e48,0x3f783dc9,
 0x3f5cbf35,0xbf803e95,0x3f673e48,0xbf18bf22,0x3e163f6d,0x3eacbf7f,0xbf3e3f55,0x3f78bef1,0xbe793f80,0x3f2cbf62,0xbf713f0e,0x3f7dbdc9,0xbf4ebec4,0x3edb3f46,0x3d49bf7b,0xbf043f75,
 0x3f043f35,0xbd49bf75,0xbedb3f7b,0x3f4ebf46,0xbf7d3ec4,0x3f713dc9,0xbf2cbf0e,0x3e793f62,0xbf780000,0x3f3e3ef1,0xbeacbf55,0xbe163f7f,0x3f18bf6d,0xbf673f22,0x3f80be48,0xbf5cbe95,
 0xbf3ebec4,0x3e163f62,0x3f04bf7b,0xbf713f22,0x3edb3f35,0x3e79bf7f,0xbf4e3f55,0x3f80be95,0xbd49bf6d,0xbf183f75,0x3f78bf0e,0xbf67bdc9,0xbeac3f80,0x3f5cbf46,0xbf7d3e48,0x3f2c3ef1,
 0xbf2c3f6d,0x3f7dbef1,0xbf5cbe48,0x3eac3f46,0x3f67bf35,0xbf783dc9,0x3f183f0e,0x3d49bf75,0xbf803ec4,0x3f4e3e95,0xbe79bf55,0xbedb3f7f,0x3f710000,0xbf04bf22,0xbe163f7b,0x3f3ebf62,
 0xbf670000,0x3e793f46,0x3f18bf7b,0xbf803ef1,0x3f2c3ec4,0x3e16bf75,0xbf5c3f55,0x3f71bdc9,0xbeacbf35,0xbf043f7f,0x3f7dbf0e,0xbf3ebe95,0xbd493f6d,0x3f4ebf62,0xbf783e48,0x3edb3f22,
 0xbedb3f80,0x3f78bf22,0xbf4ebe48,0x3d493f62,0x3f3ebf6d,0xbf7d3e95,0x3f043f0e,0x3eacbf7f,0xbf713f35,0x3f5c3dc9,0xbe16bf55,0xbf2c3f75,0x3f80bec4,0xbf18bef1,0xbe793f7b,0x3f67bf46,
 0x3e16bf6d,0xbf713f46,0x3f3e3e48,0x3e79bf75,0x3f5c0000,0x3d49bf62,0xbf673f55,0x3f4e3dc9,0x3f183ec4,0x3edbbf7f,0xbf803f0e,0x3f043ef1,0xbf783f35,0x3f2c3e95,0x3eacbf7b,0xbf7d3f22,
 0x3f7dbec4,0xbeacbf22,0xbf2c3f7b,0x3f78be95,0xbf043f80,0x3f80bef1,0xbedbbf0e,0xbf183f7f,0xbf4e3f6d,0x3f67bdc9,0xbd49bf55,0xbf5c3f62,0xbe79bf35,0xbf3e3f75,0x3f71be48,0xbe16bf46,
 0x3e163f35,0x3f67bf62,0xbf2cbe48,0xbf043f7f,0x3f78bec4,0xbd49bf46,0xbf713f55,0x3f183e95,0xbf4e0000,0xbeac3f75,0x3f80bf0e,0xbe79bf22,0xbf5c3f6d,0x3f3e3dc9,0x3edbbf7b,0xbf7d3ef1,
 0x3f7dbf35,0xbedbbef1,0xbf3e3f7b,0x3f5cbdc9,0x3e79bf6d,0xbf803f22,0x3eac3f0e,0x3f4ebf75,0xbf183f80,0x3f71be95,0x3d49bf55,0xbf783f46,0x3f043ec4,0x3f2cbf7f,0xbf673e48,0xbe163f62,
 0x3f67bf6d,0xbf04be95,0xbf4e3f7b,0x3f2c3dc9,0x3f80bf35,0xbe16bf22,0xbf783f55,0x3eac3ef1,0x3f71bec4,0x3e79bf62,0xbf7d3f0e,0xbd493f46,0x3f3e0000,0x3f18bf7f,0xbf5c3e48,0xbedb3f75,
 0x3edb3ec4,0x3f5cbf75,0xbf18be48,0xbf3e3f7f,0x3d493f35,0x3f7dbf46,0xbe79bf0e,0xbf713f62,0xbeac3f6d,0x3f78bef1,0x3e16bf55,0xbf803f22,0xbf2c3f80,0x3f4ebdc9,0x3f04bf7b,0xbf673e95,
 0xbf800000,0x3f7d3dc9,0xbf78be48,0x3f713e95,0xbf67bec4,0x3f5c3ef1,0xbf4ebf0e,0x3f3e3f22,0xbf2cbf35,0x3f183f46,0xbf04bf55,0x3edb3f62,0xbeacbf6d,0x3e793f75,0xbe16bf7b,0x3d493f7f,
 0x3d49bf80,0xbe163f7f,0x3e79bf7b,0xbeac3f75,0x3edbbf6d,0xbf043f62,0x3f18bf55,0xbf2c3f46,0x3f3ebf35,0xbf4e3f22,0x3f5cbf0e,0xbf673ef1,0x3f71bec4,0xbf783e95,0x3f7dbe48,0xbf803dc9,
 0xbe79bf6d,0xbd493f7f,0x3eacbf7b,0xbf183f62,0xbf7d0000,0x3f673e95,0xbf3ebf0e,0x3f043f46,0x3f5c3ec4,0xbf2cbf22,0x3edb3f55,0xbe16bf75,0x3f4ebf35,0xbf713ef1,0x3f80be48,0xbf78bdc9,
 0xbf783ec4,0x3f80bdc9,0xbf71be48,0x3f4e3ef1,0xbe163f80,0x3edbbf75,0xbf2c3f55,0x3f5cbf22,0x3f04bf6d,0xbf3e3f46,0x3f67bf0e,0xbf7d3e95,0xbf18bf35,0x3eac3f62,0xbd49bf7b,0xbe793f7f,
 0x3f043f35,0xbd49bf75,0xbedb3f7b,0x3f4ebf46,0xbf7d3ec4,0x3f713dc9,0xbf2cbf0e,0x3e793f62,0xbf780000,0x3f3e3ef1,0xbeacbf55,0xbe163f7f,0x3f18bf6d,0xbf673f22,0x3f80be48,0xbf5cbe95,
 0xbf5c3f35,0x3f80be95,0xbf67be48,0x3f183f22,0xbe16bf6d,0xbeac3f7f,0x3f3ebf55,0xbf783ef1,0x3e79bf80,0xbf2c3f62,0x3f71bf0e,0xbf7d3dc9,0x3f4e3ec4,0xbedbbf46,0xbd493f7b,0x3f04bf75,
 0x3f2cbf6d,0xbf7d3ef1,0x3f5c3e48,0xbeacbf46,0xbf673f35,0x3f78bdc9,0xbf18bf0e,0xbd493f75,0x3f80bec4,0xbf4ebe95,0x3e793f55,0x3edbbf7f,0xbf710000,0x3f043f22,0x3e16bf7b,0xbf3e3f62,
 0xbf3ebec4,0x3e163f62,0x3f04bf7b,0xbf713f22,0x3edb3f35,0x3e79bf7f,0xbf4e3f55,0x3f80be95,0xbd49bf6d,0xbf183f75,0x3f78bf0e,0xbf67bdc9,0xbeac3f80,0x3f5cbf46,0xbf7d3e48,0x3f2c3ef1,
 0x3edbbf80,0xbf783f22,0x3f4e3e48,0xbd49bf62,0xbf3e3f6d,0x3f7dbe95,0xbf04bf0e,0xbeac3f7f,0x3f71bf35,0xbf5cbdc9,0x3e163f55,0x3f2cbf75,0xbf803ec4,0x3f183ef1,0x3e79bf7b,0xbf673f46,
 0xbf670000,0x3e793f46,0x3f18bf7b,0xbf803ef1,0x3f2c3ec4,0x3e16bf75,0xbf5c3f55,0x3f71bdc9,0xbeacbf35,0xbf043f7f,0x3f7dbf0e,0xbf3ebe95,0xbd493f6d,0x3f4ebf62,0xbf783e48,0x3edb3f22,
 0x3f7dbec4,0xbeacbf22,0xbf2c3f7b,0x3f78be95,0xbf043f80,0x3f80bef1,0xbedbbf0e,0xbf183f7f,0xbf4e3f6d,0x3f67bdc9,0xbd49bf55,0xbf5c3f62,0xbe79bf35,0xbf3e3f75,0x3f71be48,0xbe16bf46,
 0xbe163f6d,0x3f71bf46,0xbf3ebe48,0xbe793f75,0xbf5c0000,0xbd493f62,0x3f67bf55,0xbf4ebdc9,0xbf18bec4,0xbedb3f7f,0x3f80bf0e,0xbf04bef1,0x3f78bf35,0xbf2cbe95,0xbeac3f7b,0x3f7dbf22,
 0xbf7d3f35,0x3edb3ef1,0x3f3ebf7b,0xbf5c3dc9,0xbe793f6d,0x3f80bf22,0xbeacbf0e,0xbf4e3f75,0x3f18bf80,0xbf713e95,0xbd493f55,0x3f78bf46,0xbf04bec4,0xbf2c3f7f,0x3f67be48,0x3e16bf62,
 0x3e163f35,0x3f67bf62,0xbf2cbe48,0xbf043f7f,0x3f78bec4,0xbd49bf46,0xbf713f55,0x3f183e95,0xbf4e0000,0xbeac3f75,0x3f80bf0e,0xbe79bf22,0xbf5c3f6d,0x3f3e3dc9,0x3edbbf7b,0xbf7d3ef1,
 0x3edb3ec4,0x3f5cbf75,0xbf18be48,0xbf3e3f7f,0x3d493f35,0x3f7dbf46,0xbe79bf0e,0xbf713f62,0xbeac3f6d,0x3f78bef1,0x3e16bf55,0xbf803f22,0xbf2c3f80,0x3f4ebdc9,0x3f04bf7b,0xbf673e95,
 0xbf673f6d,0x3f043e95,0x3f4ebf7b,0xbf2cbdc9,0xbf803f35,0x3e163f22,0x3f78bf55,0xbeacbef1,0xbf713ec4,0xbe793f62,0x3f7dbf0e,0x3d49bf46,0xbf3e0000,0xbf183f7f,0x3f5cbe48,0x3edbbf75,
 0xbf3e3f80,0x3f183dc9,0x3f5cbf7b,0xbedbbe95,0xbf713f6d,0x3e793ef1,0x3f7dbf55,0xbd49bf22,0xbf803f35,0xbe163f46,0x3f78bf0e,0x3eacbf62,0xbf673ec4,0xbf043f75,0x3f4ebe48,0x3f2cbf7f,
 0xbf2c0000,0xbf4e3f7f,0x3f043e48,0x3f67bf75,0xbeacbec4,0xbf783f62,0x3e163f0e,0x3f80bf46,0x3d49bf35,0xbf7d3f22,0xbe793f55,0x3f71bef1,0x3edbbf6d,0xbf5c3e95,0xbf183f7b,0x3f3ebdc9,
 0xbf5c3ec4,0xbf3e3f7f,0x3edb3e48,0x3f7dbf62,0xbf4e3f80,0x3eac3e95,0x3f80bf55,0x3e79bf46,0x3f78bf6d,0x3d49bf22,0xbf713f0e,0xbf183f75,0x3e16bf35,0xbf673ef1,0xbf2c3f7b,0x3f043dc9,
 0xbf043f6d,0x3f2cbdc9,0x3f67bf7b,0xbe16bef1,0x3f180000,0x3f71bf75,0xbd49bf0e,0xbf783f22,0xbe79bec4,0xbf803f46,0xbeac3f55,0x3f4ebe95,0xbf7d3f35,0xbedb3f62,0x3f3ebe48,0x3f5cbf7f,
 0x3f78bf35,0x3f2cbf75,0xbeacbe48,0xbf7d3f46,0xbf183f6d,0x3edb3dc9,0x3f80bf55,0x3f04bf62,0xbf5c3f80,0x3d493ef1,0x3f67bf0e,0x3f4ebf7f,0xbe16bec4,0xbf713f22,0xbf3e3f7b,0x3e793e95,
 0xbe793f35,0x3f3ebe95,0x3f71bf7b,0x3e16bf22,0xbf4e3ec4,0xbf673f7f,0xbd493f0e,0x3f5cbef1,0xbf040000,0xbf803f62,0xbedb3f55,0x3f18bdc9,0x3f7dbf6d,0x3eacbf46,0xbf2c3e48,0xbf783f75,
 0xbd49bec4,0xbf4e3ef1,0xbf783f7b,0xbedb3f46,0xbeac3f35,0x3f04bdc9,0x3f7dbf55,0x3f3ebf75,0x3f2cbf6d,0xbe16be95,0xbf5c3f0e,0xbf713f7f,0xbf673f80,0xbe793f22,0x3f18be48,0x3f80bf62,
 0xbf803f6d,0xbf183f62,0x3e793e48,0x3f67bf22,0x3f71bf35,0x3f5cbf7f,0x3e16bf0e,0xbf2c3e95,0xbf3e3ec4,0xbf7d3f75,0xbf043f55,0x3eac3dc9,0x3edb0000,0x3f78bf46,0x3f4ebf7b,0x3d49bef1,
 0xbeac0000,0xbf5c3f22,0xbf7d3f7b,0xbf2c3f62,0xbd493ec4,0x3f18be95,0x3f78bf55,0x3f67bf7f,0x3edbbf35,0xbe79bdc9,0xbf4e3f0e,0xbf803f75,0xbf3e3f6d,0xbe163ef1,0x3f04be48,0x3f71bf46,
 0xbf713f80,0xbf043f46,0x3e163e48,0x3f3ebef1,0x3f80bf6d,0x3f4ebf75,0x3e79bf0e,0xbedb3dc9,0xbf673f35,0xbf783f7f,0xbf183f55,0x3d493e95,0x3f2cbec4,0x3f7dbf62,0x3f5cbf7b,0x3eacbf22,
 0x3f4ebf6d,0x3edbbf22,0xbd49be48,0xbf043e95,0x3e790000,0x3f2cbef1,0x3f71bf55,0x3f7dbf7f,0xbe163ec4,0x3eacbdc9,0x3f3ebf0e,0x3f78bf62,0xbf5c3f35,0xbf803f75,0xbf673f7b,0xbf183f46,
 0x3f18bec4,0x3f67bf46,0x3f80bf7b,0x3f5cbf75,0xbf783f80,0xbf3e3f62,0xbeac3f0e,0x3e163dc9,0xbf7d3f6d,0xbf713f7f,0xbf2c3f55,0xbe793ef1,0x3f04bf35,0x3d49be95,0xbedb3e48,0xbf4e3f22,
 0xbf183f35,0xbeac3ef1,0xbd493e48,0x3e79bdc9,0x3f04bec4,0x3f3ebf22,0x3f67bf55,0x3f7dbf75,0xbe160000,0xbedb3e95,0xbf2c3f0e,0xbf5c3f46,0xbf783f6d,0xbf803f7f,0xbf713f7b,0xbf4e3f62,
 0x3f4ebf35,0x3f71bf62,0x3f80bf7b,0x3f78bf7f,0x3f5cbf6d,0x3f2cbf46,0x3edbbf0e,0x3e16be95,0xbf7d3f80,0xbf673f75,0xbf3e3f55,0xbf043f22,0xbe793ec4,0x3d493dc9,0x3eacbe48,0x3f18bef1,
 0x3f71bf6d,0x3f78bf75,0x3f7dbf7b,0x3f80bf7f,0x3f3ebf35,0x3f4ebf46,0x3f5cbf55,0x3f67bf62,0x3edbbec4,0x3f04bef1,0x3f18bf0e,0x3f2cbf22,0x3d490000,0x3e16bdc9,0x3e79be48,0x3eacbe95,
 0xbeac3ec4,0xbe793e95,0xbe163e48,0xbd493dc9,0xbf2c3f35,0xbf183f22,0xbf043f0e,0xbedb3ef1,0xbf673f6d,0xbf5c3f62,0xbf4e3f55,0xbf3e3f46,0xbf803f80,0xbf7d3f7f,0xbf783f7b,0xbf713f75,
 0xbf2c0000,0xbf4e3f7f,0x3f043e48,0x3f67bf75,0xbeacbec4,0xbf783f62,0x3e163f0e,0x3f80bf46,0x3d49bf35,0xbf7d3f22,0xbe793f55,0x3f71bef1,0x3edbbf6d,0xbf5c3e95,0xbf183f7b,0x3f3ebdc9,
 0x3f3ebf80,0xbf18bdc9,0xbf5c3f7b,0x3edb3e95,0x3f71bf6d,0xbe79bef1,0xbf7d3f55,0x3d493f22,0x3f80bf35,0x3e16bf46,0xbf783f0e,0xbeac3f62,0x3f67bec4,0x3f04bf75,0xbf4e3e48,0xbf2c3f7f,
 0x3f04bf6d,0xbf2c3dc9,0xbf673f7b,0x3e163ef1,0xbf180000,0xbf713f75,0x3d493f0e,0x3f78bf22,0x3e793ec4,0x3f80bf46,0x3eacbf55,0xbf4e3e95,0x3f7dbf35,0x3edbbf62,0xbf3e3e48,0xbf5c3f7f,
 0xbf5c3ec4,0xbf3e3f7f,0x3edb3e48,0x3f7dbf62,0xbf4e3f80,0x3eac3e95,0x3f80bf55,0x3e79bf46,0x3f78bf6d,0x3d49bf22,0xbf713f0e,0xbf183f75,0x3e16bf35,0xbf673ef1,0xbf2c3f7b,0x3f043dc9,
 0xbe793f35,0x3f3ebe95,0x3f71bf7b,0x3e16bf22,0xbf4e3ec4,0xbf673f7f,0xbd493f0e,0x3f5cbef1,0xbf040000,0xbf803f62,0xbedb3f55,0x3f18bdc9,0x3f7dbf6d,0x3eacbf46,0xbf2c3e48,0xbf783f75,
 0xbf783f35,0xbf2c3f75,0x3eac3e48,0x3f7dbf46,0x3f18bf6d,0xbedbbdc9,0xbf803f55,0xbf043f62,0x3f5cbf80,0xbd49bef1,0xbf673f0e,0xbf4e3f7f,0x3e163ec4,0x3f71bf22,0x3f3ebf7b,0xbe79be95,
 0x3f80bf6d,0x3f18bf62,0xbe79be48,0xbf673f22,0xbf713f35,0xbf5c3f7f,0xbe163f0e,0x3f2cbe95,0x3f3ebec4,0x3f7dbf75,0x3f04bf55,0xbeacbdc9,0xbedb0000,0xbf783f46,0xbf4e3f7b,0xbd493ef1,
 0xbd49bec4,0xbf4e3ef1,0xbf783f7b,0xbedb3f46,0xbeac3f35,0x3f04bdc9,0x3f7dbf55,0x3f3ebf75,0x3f2cbf6d,0xbe16be95,0xbf5c3f0e,0xbf713f7f,0xbf673f80,0xbe793f22,0x3f18be48,0x3f80bf62,
 0x3f71bf80,0x3f04bf46,0xbe16be48,0xbf3e3ef1,0xbf803f6d,0xbf4e3f75,0xbe793f0e,0x3edbbdc9,0x3f67bf35,0x3f78bf7f,0x3f18bf55,0xbd49be95,0xbf2c3ec4,0xbf7d3f62,0xbf5c3f7b,0xbeac3f22,
 0xbeac0000,0xbf5c3f22,0xbf7d3f7b,0xbf2c3f62,0xbd493ec4,0x3f18be95,0x3f78bf55,0x3f67bf7f,0x3edbbf35,0xbe79bdc9,0xbf4e3f0e,0xbf803f75,0xbf3e3f6d,0xbe163ef1,0x3f04be48,0x3f71bf46,
 0x3f18bec4,0x3f67bf46,0x3f80bf7b,0x3f5cbf75,0xbf783f80,0xbf3e3f62,0xbeac3f0e,0x3e163dc9,0xbf7d3f6d,0xbf713f7f,0xbf2c3f55,0xbe793ef1,0x3f04bf35,0x3d49be95,0xbedb3e48,0xbf4e3f22,
 0xbf4e3f6d,0xbedb3f22,0x3d493e48,0x3f04be95,0xbe790000,0xbf2c3ef1,0xbf713f55,0xbf7d3f7f,0x3e16bec4,0xbeac3dc9,0xbf3e3f0e,0xbf783f62,0x3f5cbf35,0x3f80bf75,0x3f67bf7b,0x3f18bf46,
 0xbf4e3f35,0xbf713f62,0xbf803f7b,0xbf783f7f,0xbf5c3f6d,0xbf2c3f46,0xbedb3f0e,0xbe163e95,0x3f7dbf80,0x3f67bf75,0x3f3ebf55,0x3f04bf22,0x3e79bec4,0xbd49bdc9,0xbeac3e48,0xbf183ef1,
 0xbf183f35,0xbeac3ef1,0xbd493e48,0x3e79bdc9,0x3f04bec4,0x3f3ebf22,0x3f67bf55,0x3f7dbf75,0xbe160000,0xbedb3e95,0xbf2c3f0e,0xbf5c3f46,0xbf783f6d,0xbf803f7f,0xbf713f7b,0xbf4e3f62,
 0xbeac3ec4,0xbe793e95,0xbe163e48,0xbd493dc9,0xbf2c3f35,0xbf183f22,0xbf043f0e,0xbedb3ef1,0xbf673f6d,0xbf5c3f62,0xbf4e3f55,0xbf3e3f46,0xbf803f80,0xbf7d3f7f,0xbf783f7b,0xbf713f75,
 0xbf713f6d,0xbf783f75,0xbf7d3f7b,0xbf803f7f,0xbf3e3f35,0xbf4e3f46,0xbf5c3f55,0xbf673f62,0xbedb3ec4,0xbf043ef1,0xbf183f0e,0xbf2c3f22,0xbd490000,0xbe163dc9,0xbe793e48,0xbeac3e95,
};
__device__ __align__(128) const uint32_t g_Gimg[1792] = {
 0x00003d00,0x00003d00,0x00003d00,0x00003d00,0x00003d00,0x00003d00,0x00003d00,0x00003d00,0x00003d00,0x00003d00,0x00003d00,0x00003d00,0x00003d00,0x00003d00,0x00003d00,0x00003d00,
 0x00003d00,0x00003d00,0x00003d00,0x00003d00,0x00003d00,0x00003d00,0x00003d00,0x00003d00,0x00003d00,0x00003d00,0x00003d00,0x00003d00,0x00003d00,0x00003d00,0x00003d00,0x00003d00,
 0xbc5b3ce7,0xbc843cdc,0xbc983cce,0xbcac3cbe,0xbac93d00,0xbb963cfd,0xbbf93cf8,0xbc2c3cf1,0xbcf13c2c,0xbcf83bf9,0xbcfd3b96,0xbd003ac9,0xbcbe3cac,0xbcce3c98,0xbcdc3c84,0xbce73c5b,
 0xbce7bc5b,0xbcdcbc84,0xbccebc98,0xbcbebcac,0xbd00bac9,0xbcfdbb96,0xbcf8bbf9,0xbcf1bc2c,0xbc2cbcf1,0xbbf9bcf8,0xbb96bcfd,0xbac9bd00,0xbcacbcbe,0xbc98bcce,0xbc84bcdc,0xbc5bbce7,
 0xbcffbb49,0xbcf5bc15,0xbce2bc71,0xbcc6bca2,0xbca2bcc6,0xbc71bce2,0xbc15bcf5,0xbb49bcff,0xbb493cff,0xbc153cf5,0xbc713ce2,0xbca23cc6,0xbcc63ca2,0xbce23c71,0xbcf53c15,0xbcff3b49,
 0x3cff3b49,0x3cf53c15,0x3ce23c71,0x3cc63ca2,0x3ca23cc6,0x3c713ce2,0x3c153cf5,0x3b493cff,0x3b49bcff,0x3c15bcf5,0x3c71bce2,0x3ca2bcc6,0x3cc6bca2,0x3ce2bc71,0x3cf5bc15,0x3cffbb49,
 0x3c84bcdc,0x3cbebcac,0x3ce7bc5b,0x3cfdbb96,0xbc98bcce,0xbc2cbcf1,0xbac9bd00,0x3bf9bcf8,0xbcf83bf9,0xbd00bac9,0xbcf1bc2c,0xbccebc98,0xbb963cfd,0xbc5b3ce7,0xbcac3cbe,0xbcdc3c84,
 0xbcdcbc84,0xbcacbcbe,0xbc5bbce7,0xbb96bcfd,0xbcce3c98,0xbcf13c2c,0xbd003ac9,0xbcf8bbf9,0x3bf93cf8,0xbac93d00,0xbc2c3cf1,0xbc983cce,0x3cfd3b96,0x3ce73c5b,0x3cbe3cac,0x3c843cdc,
 0xbbc83cfb,0xbc8e3cd5,0xbcd53c8e,0xbcfb3bc8,0xbcfbbbc8,0xbcd5bc8e,0xbc8ebcd5,0xbbc8bcfb,0x3bc8bcfb,0x3c8ebcd5,0x3cd5bc8e,0x3cfbbbc8,0x3cfb3bc8,0x3cd53c8e,0x3c8e3cd5,0x3bc83cfb,
 0xbbc83cfb,0xbc8e3cd5,0xbcd53c8e,0xbcfb3bc8,0xbcfbbbc8,0xbcd5bc8e,0xbc8ebcd5,0xbbc8bcfb,0x3bc8bcfb,0x3c8ebcd5,0x3cd5bc8e,0x3cfbbbc8,0x3cfb3bc8,0x3cd53c8e,0x3c8e3cd5,0x3bc83cfb,
 0x3c98bcce,0x3ce7bc5b,0x3d003ac9,0x3cdc3c84,0xbcf8bbf9,0xbcbebcac,0xbc2cbcf1,0x3b96bcfd,0xbcfd3b96,0xbcf1bc2c,0xbcacbcbe,0xbbf9bcf8,0x3c843cdc,0x3ac93d00,0xbc5b3ce7,0xbcce3c98,
 0xbccebc98,0xbc5bbce7,0x3ac9bd00,0x3c84bcdc,0xbbf93cf8,0xbcac3cbe,0xbcf13c2c,0xbcfdbb96,0x3b963cfd,0xbc2c3cf1,0xbcbe3cac,0xbcf83bf9,0x3cdcbc84,0x3d00bac9,0x3ce73c5b,0x3c983cce,
 0xbcf5bc15,0xbca2bcc6,0xbb49bcff,0x3c71bce2,0x3ce2bc71,0x3cff3b49,0x3cc63ca2,0x3c153cf5,0x3c15bcf5,0x3cc6bca2,0x3cffbb49,0x3ce23c71,0x3c713ce2,0xbb493cff,0xbca23cc6,0xbcf53c15,
 0x3cf53c15,0x3ca23cc6,0x3b493cff,0xbc713ce2,0xbce23c71,0xbcffbb49,0xbcc6bca2,0xbc15bcf5,0xbc153cf5,0xbcc63ca2,0xbcff3b49,0xbce2bc71,0xbc71bce2,0x3b49bcff,0x3ca2bcc6,0x3cf5bc15,
 0xbcac3cbe,0xbcfd3b96,0xbcdcbc84,0xbc2cbcf1,0x3ce7bc5b,0x3cf83bf9,0x3c983cce,0xbac93d00,0xbd003ac9,0xbccebc98,0xbbf9bcf8,0x3c5bbce7,0x3cf13c2c,0x3c843cdc,0xbb963cfd,0xbcbe3cac,
 0xbcbebcac,0xbb96bcfd,0x3c84bcdc,0x3cf1bc2c,0x3c5b3ce7,0xbbf93cf8,0xbcce3c98,0xbd00bac9,0xbac9bd00,0x3c98bcce,0x3cf8bbf9,0x3ce73c5b,0xbc2c3cf1,0xbcdc3c84,0xbcfdbb96,0xbcacbcbe,
 0xbc443ced,0xbced3c44,0xbcedbc44,0xbc44bced,0x3c44bced,0x3cedbc44,0x3ced3c44,0x3c443ced,0xbc443ced,0xbced3c44,0xbcedbc44,0xbc44bced,0x3c44bced,0x3cedbc44,0x3ced3c44,0x3c443ced,
 0xbc443ced,0xbced3c44,0xbcedbc44,0xbc44bced,0x3c44bced,0x3cedbc44,0x3ced3c44,0x3c443ced,0xbc443ced,0xbced3c44,0xbcedbc44,0xbc44bced,0x3c44bced,0x3cedbc44,0x3ced3c44,0x3c443ced,
 0x3cbebcac,0x3cfd3b96,0x3c843cdc,0xbc2c3cf1,0xbc5b3ce7,0xbcf83bf9,0xbccebc98,0xbac9bd00,0x3d003ac9,0x3c983cce,0xbbf93cf8,0xbce73c5b,0xbcf13c2c,0xbcdcbc84,0xbb96bcfd,0x3cacbcbe,
 0x3cac3cbe,0xbb963cfd,0xbcdc3c84,0xbcf1bc2c,0xbce7bc5b,0xbbf9bcf8,0x3c98bcce,0x3d00bac9,0xbac93d00,0xbcce3c98,0xbcf8bbf9,0xbc5bbce7,0xbc2cbcf1,0x3c84bcdc,0x3cfdbb96,0x3cbe3cac,
 0xbce2bc71,0xbb49bcff,0x3cc6bca2,0x3cf53c15,0x3c153cf5,0xbca23cc6,0xbcffbb49,0xbc71bce2,0xbc713ce2,0xbcff3b49,0xbca2bcc6,0x3c15bcf5,0x3cf5bc15,0x3cc63ca2,0xbb493cff,0xbce23c71,
 0x3ce23c71,0x3b493cff,0xbcc63ca2,0xbcf5bc15,0xbc15bcf5,0x3ca2bcc6,0x3cff3b49,0x3c713ce2,0x3c71bce2,0x3cffbb49,0x3ca23cc6,0xbc153cf5,0xbcf53c15,0xbcc6bca2,0x3b49bcff,0x3ce2bc71,
 0xbcce3c98,0xbce7bc5b,0xbac9bd00,0x3cdcbc84,0xbbf9bcf8,0x3cbebcac,0x3cf13c2c,0x3b963cfd,0x3cfd3b96,0x3c2c3cf1,0xbcac3cbe,0xbcf8bbf9,0xbc843cdc,0xbd00bac9,0xbc5bbce7,0x3c98bcce,
 0x3c983cce,0xbc5b3ce7,0xbd003ac9,0xbc84bcdc,0xbcf83bf9,0xbcacbcbe,0x3c2cbcf1,0x3cfdbb96,0x3b96bcfd,0x3cf1bc2c,0x3cbe3cac,0xbbf93cf8,0x3cdc3c84,0xbac93d00,0xbce73c5b,0xbccebc98,
 0xbc8e3cd5,0xbcfbbbc8,0xbbc8bcfb,0x3cd5bc8e,0x3cd53c8e,0xbbc83cfb,0xbcfb3bc8,0xbc8ebcd5,0x3c8ebcd5,0x3cfb3bc8,0x3bc83cfb,0xbcd53c8e,0xbcd5bc8e,0x3bc8bcfb,0x3cfbbbc8,0x3c8e3cd5,
 0xbc8e3cd5,0xbcfbbbc8,0xbbc8bcfb,0x3cd5bc8e,0x3cd53c8e,0xbbc83cfb,0xbcfb3bc8,0xbc8ebcd5,0x3c8ebcd5,0x3cfb3bc8,0x3bc83cfb,0xbcd53c8e,0xbcd5bc8e,0x3bc8bcfb,0x3cfbbbc8,0x3c8e3cd5,
 0xbcdc3c84,0xbcbebcac,0x3c5bbce7,0x3cfd3b96,0xbccebc98,0x3c2cbcf1,0x3d003ac9,0x3bf93cf8,0x3cf83bf9,0x3ac93d00,0xbcf13c2c,0xbc98bcce,0x3b963cfd,0xbce73c5b,0xbcacbcbe,0x3c84bcdc,
 0x3c843cdc,0xbcac3cbe,0xbce7bc5b,0x3b96bcfd,0xbc983cce,0xbcf1bc2c,0x3ac9bd00,0x3cf8bbf9,0x3bf9bcf8,0x3d00bac9,0x3c2c3cf1,0xbcce3c98,0x3cfdbb96,0x3c5b3ce7,0xbcbe3cac,0xbcdcbc84,
 0xbcc6bca2,0x3c71bce2,0x3cf53c15,0xbb493cff,0xbcff3b49,0xbc15bcf5,0x3ce2bc71,0x3ca23cc6,0x3ca2bcc6,0x3ce23c71,0xbc153cf5,0xbcffbb49,0xbb49bcff,0x3cf5bc15,0x3c713ce2,0xbcc63ca2,
 0x3cc63ca2,0xbc713ce2,0xbcf5bc15,0x3b49bcff,0x3cffbb49,0x3c153cf5,0xbce23c71,0xbca2bcc6,0xbca23cc6,0xbce2bc71,0x3c15bcf5,0x3cff3b49,0x3b493cff,0xbcf53c15,0xbc71bce2,0x3cc6bca2,
 0x3ce7bc5b,0x3c843cdc,0xbcce3c98,0xbcacbcbe,0x3d00bac9,0x3b963cfd,0xbcf83bf9,0xbc2cbcf1,0x3cf13c2c,0xbbf93cf8,0xbcfdbb96,0x3ac9bd00,0x3cbe3cac,0xbc983cce,0xbcdcbc84,0x3c5bbce7,
 0x3c5b3ce7,0xbcdc3c84,0xbc98bcce,0x3cbebcac,0x3ac93d00,0xbcfd3b96,0xbbf9bcf8,0x3cf1bc2c,0xbc2c3cf1,0xbcf8bbf9,0x3b96bcfd,0x3d003ac9,0xbcac3cbe,0xbccebc98,0x3c84bcdc,0x3ce73c5b,
 0xbcb53cb5,0xbcb5bcb5,0x3cb5bcb5,0x3cb53cb5,0xbcb53cb5,0xbcb5bcb5,0x3cb5bcb5,0x3cb53cb5,0xbcb53cb5,0xbcb5bcb5,0x3cb5bcb5,0x3cb53cb5,0xbcb53cb5,0xbcb5bcb5,0x3cb5bcb5,0x3cb53cb5,
 0xbcb53cb5,0xbcb5bcb5,0x3cb5bcb5,0x3cb53cb5,0xbcb53cb5,0xbcb5bcb5,0x3cb5bcb5,0x3cb53cb5,0xbcb53cb5,0xbcb5bcb5,0x3cb5bcb5,0x3cb53cb5,0xbcb53cb5,0xbcb5bcb5,0x3cb5bcb5,0x3cb53cb5,
 0xbcf13c2c,0xbbf9bcf8,0x3cfdbb96,0x3ac93d00,0xbcbe3cac,0xbc98bcce,0x3cdcbc84,0x3c5b3ce7,0xbce7bc5b,0x3c84bcdc,0x3cce3c98,0xbcac3cbe,0xbd00bac9,0x3b96bcfd,0x3cf83bf9,0xbc2c3cf1,
 0xbc2cbcf1,0x3cf8bbf9,0x3b963cfd,0xbd003ac9,0xbcacbcbe,0x3ccebc98,0x3c843cdc,0xbce73c5b,0x3c5bbce7,0x3cdc3c84,0xbc983cce,0xbcbebcac,0x3ac9bd00,0x3cfd3b96,0xbbf93cf8,0xbcf1bc2c,
 0xbca2bcc6,0x3ce2bc71,0x3c153cf5,0xbcff3b49,0x3b49bcff,0x3cf53c15,0xbc713ce2,0xbcc6bca2,0xbcc63ca2,0xbc71bce2,0x3cf5bc15,0x3b493cff,0xbcffbb49,0x3c15bcf5,0x3ce23c71,0xbca23cc6,
 0x3ca23cc6,0xbce23c71,0xbc15bcf5,0x3cffbb49,0xbb493cff,0xbcf5bc15,0x3c71bce2,0x3cc63ca2,0x3cc6bca2,0x3c713ce2,0xbcf53c15,0xbb49bcff,0x3cff3b49,0xbc153cf5,0xbce2bc71,0x3ca2bcc6,
 0x3cf8bbf9,0xbac93d00,0xbcf1bc2c,0x3c98bcce,0x3b96bcfd,0x3ce73c5b,0xbcac3cbe,0xbc84bcdc,0xbcdcbc84,0x3cbebcac,0x3c5b3ce7,0xbcfd3b96,0xbcce3c98,0xbc2cbcf1,0x3d00bac9,0xbbf93cf8,
 0xbbf9bcf8,0x3d003ac9,0xbc2c3cf1,0xbccebc98,0xbcfdbb96,0x3c5bbce7,0x3cbe3cac,0xbcdc3c84,0xbc843cdc,0xbcacbcbe,0x3ce7bc5b,0x3b963cfd,0x3c983cce,0xbcf13c2c,0xbac9bd00,0x3cf83bf9,
 0xbcd53c8e,0xbbc8bcfb,0x3cfb3bc8,0xbc8e3cd5,0xbc8ebcd5,0x3cfbbbc8,0xbbc83cfb,0xbcd5bc8e,0x3cd5bc8e,0x3bc83cfb,0xbcfbbbc8,0x3c8ebcd5,0x3c8e3cd5,0xbcfb3bc8,0x3bc8bcfb,0x3cd53c8e,
 0xbcd53c8e,0xbbc8bcfb,0x3cfb3bc8,0xbc8e3cd5,0xbc8ebcd5,0x3cfbbbc8,0xbbc83cfb,0xbcd5bc8e,0x3cd5bc8e,0x3bc83cfb,0xbcfbbbc8,0x3c8ebcd5,0x3c8e3cd5,0xbcfb3bc8,0x3bc8bcfb,0x3cd53c8e,
 0x3cfdbb96,0xbc2c3cf1,0xbcacbcbe,0x3cf8bbf9,0xbc84bcdc,0x3d00bac9,0xbc5b3ce7,0xbc98bcce,0xbccebc98,0x3ce7bc5b,0xbac93d00,0xbcdcbc84,0xbbf93cf8,0xbcbebcac,0x3cf1bc2c,0xbb963cfd,
 0xbb96bcfd,0x3cf13c2c,0xbcbe3cac,0xbbf9bcf8,0xbcdc3c84,0xbac9bd00,0x3ce73c5b,0xbcce3c98,0xbc983cce,0xbc5bbce7,0x3d003ac9,0xbc843cdc,0x3cf83bf9,0xbcac3cbe,0xbc2cbcf1,0x3cfd3b96,
 0xbc71bce2,0x3cff3b49,0xbca23cc6,0xbc15bcf5,0x3cf53c15,0xbcc63ca2,0xbb49bcff,0x3ce23c71,0x3ce2bc71,0xbb493cff,0xbcc6bca2,0x3cf5bc15,0xbc153cf5,0xbca2bcc6,0x3cffbb49,0xbc713ce2,
 0x3c713ce2,0xbcffbb49,0x3ca2bcc6,0x3c153cf5,0xbcf5bc15,0x3cc6bca2,0x3b493cff,0xbce2bc71,0xbce23c71,0x3b49bcff,0x3cc63ca2,0xbcf53c15,0x3c15bcf5,0x3ca23cc6,0xbcff3b49,0x3c71bce2,
 0xbd003ac9,0x3c98bcce,0x3bf93cf8,0xbce7bc5b,0x3cf13c2c,0xbcdc3c84,0x3b96bcfd,0x3cac3cbe,0xbcbebcac,0x3cfdbb96,0xbc843cdc,0xbc2cbcf1,0x3c5b3ce7,0xbcf8bbf9,0x3ccebc98,0xbac93d00,
 0xbac9bd00,0x3cce3c98,0xbcf83bf9,0x3c5bbce7,0xbc2c3cf1,0xbc84bcdc,0x3cfd3b96,0xbcbe3cac,0x3cacbcbe,0x3b963cfd,0xbcdcbc84,0x3cf1bc2c,0xbce73c5b,0x3bf9bcf8,0x3c983cce,0xbd00bac9,
 0xbced3c44,0x3c44bced,0x3c443ced,0xbcedbc44,0x3cedbc44,0xbc443ced,0xbc44bced,0x3ced3c44,0xbced3c44,0x3c44bced,0x3c443ced,0xbcedbc44,0x3cedbc44,0xbc443ced,0xbc44bced,0x3ced3c44,
 0xbced3c44,0x3c44bced,0x3c443ced,0xbcedbc44,0x3cedbc44,0xbc443ced,0xbc44bced,0x3ced3c44,0xbced3c44,0x3c44bced,0x3c443ced,0xbcedbc44,0x3cedbc44,0xbc443ced,0xbc44bced,0x3ced3c44,
 0x3d003ac9,0xbcce3c98,0x3bf9bcf8,0x3c5b3ce7,0xbcf13c2c,0x3c84bcdc,0x3b963cfd,0xbcbebcac,0x3cac3cbe,0xbcfdbb96,0x3cdcbc84,0xbc2c3cf1,0xbce7bc5b,0x3cf8bbf9,0xbc983cce,0xbac9bd00,
 0xbac93d00,0xbc98bcce,0x3cf83bf9,0xbce73c5b,0xbc2cbcf1,0x3cdc3c84,0xbcfd3b96,0x3cacbcbe,0xbcbe3cac,0x3b96bcfd,0x3c843cdc,0xbcf1bc2c,0x3c5bbce7,0x3bf93cf8,0xbccebc98,0x3d00bac9,
 0xbc15bcf5,0x3cc63ca2,0xbcffbb49,0x3ce2bc71,0xbc713ce2,0xbb49bcff,0x3ca23cc6,0xbcf5bc15,0xbcf53c15,0x3ca2bcc6,0xbb493cff,0xbc71bce2,0x3ce23c71,0xbcff3b49,0x3cc6bca2,0xbc153cf5,
 0x3c153cf5,0xbcc6bca2,0x3cff3b49,0xbce23c71,0x3c71bce2,0x3b493cff,0xbca2bcc6,0x3cf53c15,0x3cf5bc15,0xbca23cc6,0x3b49bcff,0x3c713ce2,0xbce2bc71,0x3cffbb49,0xbcc63ca2,0x3c15bcf5,
 0xbcfdbb96,0x3cf1bc2c,0xbcac3cbe,0x3bf9bcf8,0x3c84bcdc,0xbac93d00,0xbc5bbce7,0x3cce3c98,0x3c983cce,0xbce7bc5b,0x3d00bac9,0xbcdc3c84,0xbcf83bf9,0x3cbebcac,0xbc2c3cf1,0xbb96bcfd,
 0xbb963cfd,0xbc2cbcf1,0x3cbe3cac,0xbcf8bbf9,0xbcdcbc84,0x3d003ac9,0xbce73c5b,0x3c98bcce,0x3ccebc98,0xbc5b3ce7,0xbac9bd00,0x3c843cdc,0x3bf93cf8,0xbcacbcbe,0x3cf13c2c,0xbcfd3b96,
 0xbcfb3bc8,0x3cd5bc8e,0xbc8e3cd5,0x3bc8bcfb,0x3bc83cfb,0xbc8ebcd5,0x3cd53c8e,0xbcfbbbc8,0x3cfbbbc8,0xbcd53c8e,0x3c8ebcd5,0xbbc83cfb,0xbbc8bcfb,0x3c8e3cd5,0xbcd5bc8e,0x3cfb3bc8,
 0xbcfb3bc8,0x3cd5bc8e,0xbc8e3cd5,0x3bc8bcfb,0x3bc83cfb,0xbc8ebcd5,0x3cd53c8e,0xbcfbbbc8,0x3cfbbbc8,0xbcd53c8e,0x3c8ebcd5,0xbbc83cfb,0xbbc8bcfb,0x3c8e3cd5,0xbcd5bc8e,0x3cfb3bc8,
 0xbcf8bbf9,0x3d00bac9,0xbcf13c2c,0x3ccebc98,0xbb96bcfd,0x3c5b3ce7,0xbcacbcbe,0x3cdc3c84,0x3c843cdc,0xbcbebcac,0x3ce73c5b,0xbcfdbb96,0xbc983cce,0x3c2cbcf1,0xbac93d00,0xbbf9bcf8,
 0xbbf93cf8,0xbac9bd00,0x3c2c3cf1,0xbc98bcce,0xbcfd3b96,0x3ce7bc5b,0xbcbe3cac,0x3c84bcdc,0x3cdcbc84,0xbcac3cbe,0x3c5bbce7,0xbb963cfd,0x3cce3c98,0xbcf1bc2c,0x3d003ac9,0xbcf83bf9,
 0xbb49bcff,0x3c153cf5,0xbc71bce2,0x3ca23cc6,0xbcc6bca2,0x3ce23c71,0xbcf5bc15,0x3cff3b49,0x3cffbb49,0xbcf53c15,0x3ce2bc71,0xbcc63ca2,0x3ca2bcc6,0xbc713ce2,0x3c15bcf5,0xbb493cff,
 0x3b493cff,0xbc15bcf5,0x3c713ce2,0xbca2bcc6,0x3cc63ca2,0xbce2bc71,0x3cf53c15,0xbcffbb49,0xbcff3b49,0x3cf5bc15,0xbce23c71,0x3cc6bca2,0xbca23cc6,0x3c71bce2,0xbc153cf5,0x3b49bcff,
 0x3cf13c2c,0xbcf8bbf9,0x3cfd3b96,0xbd00bac9,0x3cbe3cac,0xbccebc98,0x3cdc3c84,0xbce7bc5b,0x3c5b3ce7,0xbc84bcdc,0x3c983cce,0xbcacbcbe,0x3ac93d00,0xbb96bcfd,0x3bf93cf8,0xbc2cbcf1,
 0xbc2c3cf1,0x3bf9bcf8,0xbb963cfd,0x3ac9bd00,0xbcac3cbe,0x3c98bcce,0xbc843cdc,0x3c5bbce7,0xbce73c5b,0x3cdcbc84,0xbcce3c98,0x3cbebcac,0xbd003ac9,0x3cfdbb96,0xbcf83bf9,0x3cf1bc2c,
 0xbd000000,0x3d000000,0xbd000000,0x3d000000,0xbd000000,0x3d000000,0xbd000000,0x3d000000,0xbd000000,0x3d000000,0xbd000000,0x3d000000,0xbd000000,0x3d000000,0xbd000000,0x3d000000,
 0xbd000000,0x3d000000,0xbd000000,0x3d000000,0xbd000000,0x3d000000,0xbd000000,0x3d000000,0xbd000000,0x3d000000,0xbd000000,0x3d000000,0xbd000000,0x3d000000,0xbd000000,0x3d000000,
 0xbce7bc5b,0x3cdc3c84,0xbccebc98,0x3cbe3cac,0xbd00bac9,0x3cfd3b96,0xbcf8bbf9,0x3cf13c2c,0xbc2cbcf1,0x3bf93cf8,0xbb96bcfd,0x3ac93d00,0xbcacbcbe,0x3c983cce,0xbc84bcdc,0x3c5b3ce7,
 0x3c5bbce7,0xbc843cdc,0x3c98bcce,0xbcac3cbe,0x3ac9bd00,0xbb963cfd,0x3bf9bcf8,0xbc2c3cf1,0x3cf1bc2c,0xbcf83bf9,0x3cfdbb96,0xbd003ac9,0x3cbebcac,0xbcce3c98,0x3cdcbc84,0xbce73c5b,
 0x3b49bcff,0xbc153cf5,0x3c71bce2,0xbca23cc6,0x3cc6bca2,0xbce23c71,0x3cf5bc15,0xbcff3b49,0xbcffbb49,0x3cf53c15,0xbce2bc71,0x3cc63ca2,0xbca2bcc6,0x3c713ce2,0xbc15bcf5,0x3b493cff,
 0xbb493cff,0x3c15bcf5,0xbc713ce2,0x3ca2bcc6,0xbcc63ca2,0x3ce2bc71,0xbcf53c15,0x3cffbb49,0x3cff3b49,0xbcf5bc15,0x3ce23c71,0xbcc6bca2,0x3ca23cc6,0xbc71bce2,0x3c153cf5,0xbb49bcff,
 0x3cdc3c84,0xbcacbcbe,0x3c5b3ce7,0xbb96bcfd,0x3ccebc98,0xbcf13c2c,0x3d00bac9,0xbcf8bbf9,0xbbf9bcf8,0xbac93d00,0x3c2cbcf1,0xbc983cce,0xbcfdbb96,0x3ce73c5b,0xbcbebcac,0x3c843cdc,
 0x3c84bcdc,0xbcbe3cac,0x3ce7bc5b,0xbcfd3b96,0xbc98bcce,0x3c2c3cf1,0xbac9bd00,0xbbf93cf8,0xbcf83bf9,0x3d003ac9,0xbcf1bc2c,0x3cce3c98,0xbb963cfd,0x3c5bbce7,0xbcac3cbe,0x3cdcbc84,
 0xbcfbbbc8,0x3cd53c8e,0xbc8ebcd5,0x3bc83cfb,0x3bc8bcfb,0xbc8e3cd5,0x3cd5bc8e,0xbcfb3bc8,0x3cfb3bc8,0xbcd5bc8e,0x3c8e3cd5,0xbbc8bcfb,0xbbc83cfb,0x3c8ebcd5,0xbcd53c8e,0x3cfbbbc8,
 0xbcfbbbc8,0x3cd53c8e,0xbc8ebcd5,0x3bc83cfb,0x3bc8bcfb,0xbc8e3cd5,0x3cd5bc8e,0xbcfb3bc8,0x3cfb3bc8,0xbcd5bc8e,0x3c8e3cd5,0xbbc8bcfb,0xbbc83cfb,0x3c8ebcd5,0xbcd53c8e,0x3cfbbbc8,
 0x3cce3c98,0xbc5bbce7,0xbac93d00,0x3c84bcdc,0x3bf9bcf8,0xbcac3cbe,0x3cf1bc2c,0xbcfdbb96,0xbb96bcfd,0xbc2c3cf1,0x3cbebcac,0xbcf83bf9,0xbcdc3c84,0x3d00bac9,0xbce7bc5b,0x3c983cce,
 0x3c98bcce,0xbce73c5b,0x3d003ac9,0xbcdcbc84,0xbcf8bbf9,0x3cbe3cac,0xbc2cbcf1,0xbb963cfd,0xbcfd3b96,0x3cf13c2c,0xbcacbcbe,0x3bf93cf8,0x3c843cdc,0xbac9bd00,0xbc5b3ce7,0x3ccebc98,
 0x3c15bcf5,0xbcc63ca2,0x3cffbb49,0xbce2bc71,0x3c713ce2,0x3b49bcff,0xbca23cc6,0x3cf5bc15,0x3cf53c15,0xbca2bcc6,0x3b493cff,0x3c71bce2,0xbce23c71,0x3cff3b49,0xbcc6bca2,0x3c153cf5,
 0xbc153cf5,0x3cc6bca2,0xbcff3b49,0x3ce23c71,0xbc71bce2,0xbb493cff,0x3ca2bcc6,0xbcf53c15,0xbcf5bc15,0x3ca23cc6,0xbb49bcff,0xbc713ce2,0x3ce2bc71,0xbcffbb49,0x3cc63ca2,0xbc15bcf5,
 0xbcbebcac,0x3b963cfd,0x3c84bcdc,0xbcf13c2c,0x3c5b3ce7,0x3bf9bcf8,0xbcce3c98,0x3d003ac9,0xbac9bd00,0xbc983cce,0x3cf8bbf9,0xbce7bc5b,0xbc2c3cf1,0x3cdcbc84,0xbcfdbb96,0x3cac3cbe,
 0x3cacbcbe,0xbcfd3b96,0x3cdc3c84,0xbc2cbcf1,0xbce73c5b,0x3cf83bf9,0xbc98bcce,0xbac93d00,0x3d00bac9,0xbccebc98,0x3bf93cf8,0x3c5bbce7,0xbcf1bc2c,0x3c843cdc,0x3b96bcfd,0xbcbe3cac,
 0xbcedbc44,0x3c443ced,0x3c44bced,0xbced3c44,0x3ced3c44,0xbc44bced,0xbc443ced,0x3cedbc44,0xbcedbc44,0x3c443ced,0x3c44bced,0xbced3c44,0x3ced3c44,0xbc44bced,0xbc443ced,0x3cedbc44,
 0xbcedbc44,0x3c443ced,0x3c44bced,0xbced3c44,0x3ced3c44,0xbc44bced,0xbc443ced,0x3cedbc44,0xbcedbc44,0x3c443ced,0x3c44bced,0xbced3c44,0x3ced3c44,0xbc44bced,0xbc443ced,0x3cedbc44,
 0x3cac3cbe,0x3b96bcfd,0xbcdc3c84,0x3cf13c2c,0xbce7bc5b,0x3bf93cf8,0x3c98bcce,0xbd003ac9,0xbac93d00,0x3ccebc98,0xbcf8bbf9,0x3c5b3ce7,0xbc2cbcf1,0xbc843cdc,0x3cfdbb96,0xbcbebcac,
 0xbcbe3cac,0x3cfd3b96,0xbc84bcdc,0xbc2c3cf1,0x3c5bbce7,0xbcf83bf9,0x3cce3c98,0xbac9bd00,0xbd00bac9,0x3c983cce,0x3bf9bcf8,0xbce73c5b,0x3cf1bc2c,0xbcdcbc84,0x3b963cfd,0x3cacbcbe,
 0x3c71bce2,0xbcff3b49,0x3ca23cc6,0x3c15bcf5,0xbcf53c15,0x3cc63ca2,0x3b49bcff,0xbce23c71,0xbce2bc71,0x3b493cff,0x3cc6bca2,0xbcf5bc15,0x3c153cf5,0x3ca2bcc6,0xbcffbb49,0x3c713ce2,
 0xbc713ce2,0x3cffbb49,0xbca2bcc6,0xbc153cf5,0x3cf5bc15,0xbcc6bca2,0xbb493cff,0x3ce2bc71,0x3ce23c71,0xbb49bcff,0xbcc63ca2,0x3cf53c15,0xbc15bcf5,0xbca23cc6,0x3cff3b49,0xbc71bce2,
 0xbc98bcce,0xbc5b3ce7,0x3d00bac9,0xbc84bcdc,0x3cf8bbf9,0xbcacbcbe,0xbc2c3cf1,0x3cfdbb96,0xbb963cfd,0x3cf1bc2c,0xbcbebcac,0xbbf93cf8,0xbcdcbc84,0xbac93d00,0x3ce7bc5b,0xbccebc98,
 0xbcce3c98,0x3ce73c5b,0xbac9bd00,0xbcdc3c84,0xbbf9bcf8,0xbcbe3cac,0x3cf13c2c,0xbb96bcfd,0x3cfd3b96,0xbc2cbcf1,0xbcac3cbe,0x3cf83bf9,0xbc843cdc,0x3d003ac9,0xbc5bbce7,0xbc983cce,
 0xbcd5bc8e,0xbbc83cfb,0x3cfbbbc8,0xbc8ebcd5,0xbc8e3cd5,0x3cfb3bc8,0xbbc8bcfb,0xbcd53c8e,0x3cd53c8e,0x3bc8bcfb,0xbcfb3bc8,0x3c8e3cd5,0x3c8ebcd5,0xbcfbbbc8,0x3bc83cfb,0x3cd5bc8e,
 0xbcd5bc8e,0xbbc83cfb,0x3cfbbbc8,0xbc8ebcd5,0xbc8e3cd5,0x3cfb3bc8,0xbbc8bcfb,0xbcd53c8e,0x3cd53c8e,0x3bc8bcfb,0xbcfb3bc8,0x3c8e3cd5,0x3c8ebcd5,0xbcfbbbc8,0x3bc83cfb,0x3cd5bc8e,
 0xbc84bcdc,0xbcac3cbe,0x3ce73c5b,0x3b96bcfd,0x3c98bcce,0xbcf1bc2c,0xbac93d00,0x3cf8bbf9,0xbbf93cf8,0x3d00bac9,0xbc2cbcf1,0xbcce3c98,0xbcfd3b96,0x3c5b3ce7,0x3cbebcac,0xbcdcbc84,
 0xbcdc3c84,0x3cbe3cac,0x3c5bbce7,0xbcfdbb96,0xbccebc98,0xbc2c3cf1,0x3d003ac9,0xbbf9bcf8,0x3cf83bf9,0xbac9bd00,0xbcf13c2c,0x3c983cce,0x3b963cfd,0x3ce7bc5b,0xbcacbcbe,0xbc843cdc,
 0x3ca2bcc6,0xbce2bc71,0xbc153cf5,0x3cff3b49,0xbb49bcff,0xbcf53c15,0x3c713ce2,0x3cc6bca2,0x3cc63ca2,0x3c71bce2,0xbcf5bc15,0xbb493cff,0x3cffbb49,0xbc15bcf5,0xbce23c71,0x3ca23cc6,
 0xbca23cc6,0x3ce23c71,0x3c15bcf5,0xbcffbb49,0x3b493cff,0x3cf5bc15,0xbc71bce2,0xbcc63ca2,0xbcc6bca2,0xbc713ce2,0x3cf53c15,0x3b49bcff,0xbcff3b49,0x3c153cf5,0x3ce2bc71,0xbca2bcc6,
 0x3c5b3ce7,0x3cdcbc84,0xbc98bcce,0xbcbe3cac,0x3ac93d00,0x3cfdbb96,0xbbf9bcf8,0xbcf13c2c,0xbc2c3cf1,0x3cf83bf9,0x3b96bcfd,0xbd00bac9,0xbcac3cbe,0x3cce3c98,0x3c84bcdc,0xbce7bc5b,
 0xbce73c5b,0x3c843cdc,0x3ccebc98,0xbcacbcbe,0xbd003ac9,0x3b963cfd,0x3cf8bbf9,0xbc2cbcf1,0xbcf1bc2c,0xbbf93cf8,0x3cfd3b96,0x3ac9bd00,0xbcbebcac,0xbc983cce,0x3cdc3c84,0x3c5bbce7,
 0xbcb5bcb5,0xbcb53cb5,0x3cb53cb5,0x3cb5bcb5,0xbcb5bcb5,0xbcb53cb5,0x3cb53cb5,0x3cb5bcb5,0xbcb5bcb5,0xbcb53cb5,0x3cb53cb5,0x3cb5bcb5,0xbcb5bcb5,0xbcb53cb5,0x3cb53cb5,0x3cb5bcb5,
 0xbcb5bcb5,0xbcb53cb5,0x3cb53cb5,0x3cb5bcb5,0xbcb5bcb5,0xbcb53cb5,0x3cb53cb5,0x3cb5bcb5,0xbcb5bcb5,0xbcb53cb5,0x3cb53cb5,0x3cb5bcb5,0xbcb5bcb5,0xbcb53cb5,0x3cb53cb5,0x3cb5bcb5,
 0xbc2cbcf1,0xbcf83bf9,0x3b963cfd,0x3d00bac9,0xbcacbcbe,0xbcce3c98,0x3c843cdc,0x3ce7bc5b,0x3c5bbce7,0xbcdcbc84,0xbc983cce,0x3cbe3cac,0x3ac9bd00,0xbcfdbb96,0xbbf93cf8,0x3cf13c2c,
 0x3cf1bc2c,0xbbf9bcf8,0xbcfd3b96,0x3ac93d00,0x3cbebcac,0xbc98bcce,0xbcdc3c84,0x3c5b3ce7,0x3ce73c5b,0x3c84bcdc,0xbccebc98,0xbcac3cbe,0x3d003ac9,0x3b96bcfd,0xbcf8bbf9,0xbc2c3cf1,
 0x00000000,0x00000000,0x00000000,0x00000000,0x00000000,0x00000000,0x00000000,0x00000000,0x00000000,0x00000000,0x00000000,0x00000000,0x00000000,0x00000000,0x00000000,0x00000000,
 0x00000000,0x00000000,0x00000000,0x00000000,0x00000000,0x00000000,0x00000000,0x00000000,0x00000000,0x00000000,0x00000000,0x00000000,0x00000000,0x00000000,0x00000000,0x00000000,
 0x00000000,0x00000000,0x00000000,0x00000000,0x00000000,0x00000000,0x00000000,0x00000000,0x00000000,0x00000000,0x00000000,0x00000000,0x00000000,0x00000000,0x00000000,0x00000000,
 0x00000000,0x00000000,0x00000000,0x00000000,0x00000000,0x00000000,0x00000000,0x00000000,0x00000000,0x00000000,0x00000000,0x00000000,0x00000000,0x00000000,0x00000000,0x00000000,
 0x00000000,0x00000000,0x00000000,0x00000000,0x00000000,0x00000000,0x00000000,0x00000000,0x00000000,0x00000000,0x00000000,0x00000000,0x00000000,0x00000000,0x00000000,0x00000000,
 0x00000000,0x00000000,0x00000000,0x00000000,0x00000000,0x00000000,0x00000000,0x00000000,0x00000000,0x00000000,0x00000000,0x00000000,0x00000000,0x00000000,0x00000000,0x00000000,
 0x00000000,0x00000000,0x00000000,0x00000000,0x00000000,0x00000000,0x00000000,0x00000000,0x00000000,0x00000000,0x00000000,0x00000000,0x00000000,0x00000000,0x00000000,0x00000000,
 0x00000000,0x00000000,0x00000000,0x00000000,0x00000000,0x00000000,0x00000000,0x00000000,0x00000000,0x00000000,0x00000000,0x00000000,0x00000000,0x00000000,0x00000000,0x00000000,
 0x00000000,0x00000000,0x00000000,0x00000000,0x00000000,0x00000000,0x00000000,0x00000000,0x00000000,0x00000000,0x00000000,0x00000000,0x00000000,0x00000000,0x00000000,0x00000000,
 0x00000000,0x00000000,0x00000000,0x00000000,0x00000000,0x00000000,0x00000000,0x00000000,0x00000000,0x00000000,0x00000000,0x00000000,0x00000000,0x00000000,0x00000000,0x00000000,
 0x00000000,0x00000000,0x00000000,0x00000000,0x00000000,0x00000000,0x00000000,0x00000000,0x00000000,0x00000000,0x00000000,0x00000000,0x00000000,0x00000000,0x00000000,0x00000000,
 0x00000000,0x00000000,0x00000000,0x00000000,0x00000000,0x00000000,0x00000000,0x00000000,0x00000000,0x00000000,0x00000000,0x00000000,0x00000000,0x00000000,0x00000000,0x00000000,
};

template<int SA>
__device__ __forceinline__ void wgmma_main(float (&d)[80], uint64_t da, uint64_t db, int sd) {
  asm volatile("{\n.reg .pred p;\nsetp.ne.b32 p, %82, 0;\n"
    "wgmma.mma_async.sync.aligned.m64n160k16.f32.bf16.bf16 "
    "{%0, %1, %2, %3, %4, %5, %6, %7, %8, %9, %10, %11, %12, %13, %14, %15, %16, %17, %18, %19, %20, %21, %22, %23, %24, %25, %26, %27, %28, %29, %30, %31, %32, %33, %34, %35, %36, %37, %38, %39, %40, %41, %42, %43, %44, %45, %46, %47, %48, %49, %50, %51, %52, %53, %54, %55, %56, %57, %58, %59, %60, %61, %62, %63, %64, %65, %66, %67, %68, %69, %70, %71, %72, %73, %74, %75, %76, %77, %78, %79}, %80, %81, p, %83, 1, 1, 0;\n}\n"
    : "+f"(d[0]), "+f"(d[1]), "+f"(d[2]), "+f"(d[3]), "+f"(d[4]), "+f"(d[5]), "+f"(d[6]), "+f"(d[7]), "+f"(d[8]), "+f"(d[9]), "+f"(d[10]), "+f"(d[11]), "+f"(d[12]), "+f"(d[13]), "+f"(d[14]), "+f"(d[15]), "+f"(d[16]), "+f"(d[17]), "+f"(d[18]), "+f"(d[19]), "+f"(d[20]), "+f"(d[21]), "+f"(d[22]), "+f"(d[23]), "+f"(d[24]), "+f"(d[25]), "+f"(d[26]), "+f"(d[27]), "+f"(d[28]), "+f"(d[29]), "+f"(d[30]), "+f"(d[31]), "+f"(d[32]), "+f"(d[33]), "+f"(d[34]), "+f"(d[35]), "+f"(d[36]), "+f"(d[37]), "+f"(d[38]), "+f"(d[39]), "+f"(d[40]), "+f"(d[41]), "+f"(d[42]), "+f"(d[43]), "+f"(d[44]), "+f"(d[45]), "+f"(d[46]), "+f"(d[47]), "+f"(d[48]), "+f"(d[49]), "+f"(d[50]), "+f"(d[51]), "+f"(d[52]), "+f"(d[53]), "+f"(d[54]), "+f"(d[55]), "+f"(d[56]), "+f"(d[57]), "+f"(d[58]), "+f"(d[59]), "+f"(d[60]), "+f"(d[61]), "+f"(d[62]), "+f"(d[63]), "+f"(d[64]), "+f"(d[65]), "+f"(d[66]), "+f"(d[67]), "+f"(d[68]), "+f"(d[69]), "+f"(d[70]), "+f"(d[71]), "+f"(d[72]), "+f"(d[73]), "+f"(d[74]), "+f"(d[75]), "+f"(d[76]), "+f"(d[77]), "+f"(d[78]), "+f"(d[79])
    : "l"(da), "l"(db), "r"(sd), "n"(SA));
}
template<int SA>
__device__ __forceinline__ void wgmma_fwd(float (&d)[32], uint64_t da, uint64_t db, int sd) {
  asm volatile("{\n.reg .pred p;\nsetp.ne.b32 p, %34, 0;\n"
    "wgmma.mma_async.sync.aligned.m64n64k16.f32.bf16.bf16 "
    "{%0, %1, %2, %3, %4, %5, %6, %7, %8, %9, %10, %11, %12, %13, %14, %15, %16, %17, %18, %19, %20, %21, %22, %23, %24, %25, %26, %27, %28, %29, %30, %31}, %32, %33, p, %35, 1, 0, 1;\n}\n"
    : "+f"(d[0]), "+f"(d[1]), "+f"(d[2]), "+f"(d[3]), "+f"(d[4]), "+f"(d[5]), "+f"(d[6]), "+f"(d[7]), "+f"(d[8]), "+f"(d[9]), "+f"(d[10]), "+f"(d[11]), "+f"(d[12]), "+f"(d[13]), "+f"(d[14]), "+f"(d[15]), "+f"(d[16]), "+f"(d[17]), "+f"(d[18]), "+f"(d[19]), "+f"(d[20]), "+f"(d[21]), "+f"(d[22]), "+f"(d[23]), "+f"(d[24]), "+f"(d[25]), "+f"(d[26]), "+f"(d[27]), "+f"(d[28]), "+f"(d[29]), "+f"(d[30]), "+f"(d[31])
    : "l"(da), "l"(db), "r"(sd), "n"(SA));
}
template<int SA>
__device__ __forceinline__ void wgmma_inv(float (&d)[28], uint64_t da, uint64_t db, int sd) {
  asm volatile("{\n.reg .pred p;\nsetp.ne.b32 p, %30, 0;\n"
    "wgmma.mma_async.sync.aligned.m64n56k16.f32.bf16.bf16 "
    "{%0, %1, %2, %3, %4, %5, %6, %7, %8, %9, %10, %11, %12, %13, %14, %15, %16, %17, %18, %19, %20, %21, %22, %23, %24, %25, %26, %27}, %28, %29, p, %31, 1, 1, 0;\n}\n"
    : "+f"(d[0]), "+f"(d[1]), "+f"(d[2]), "+f"(d[3]), "+f"(d[4]), "+f"(d[5]), "+f"(d[6]), "+f"(d[7]), "+f"(d[8]), "+f"(d[9]), "+f"(d[10]), "+f"(d[11]), "+f"(d[12]), "+f"(d[13]), "+f"(d[14]), "+f"(d[15]), "+f"(d[16]), "+f"(d[17]), "+f"(d[18]), "+f"(d[19]), "+f"(d[20]), "+f"(d[21]), "+f"(d[22]), "+f"(d[23]), "+f"(d[24]), "+f"(d[25]), "+f"(d[26]), "+f"(d[27])
    : "l"(da), "l"(db), "r"(sd), "n"(SA));
}


__device__ __forceinline__ uint32_t s2u(const void* p) { return (uint32_t)__cvta_generic_to_shared(p); }
__device__ __forceinline__ void mbar_init(uint32_t a, int c) { asm volatile("mbarrier.init.shared::cta.b64 [%0], %1;" ::"r"(a), "r"(c)); }
__device__ __forceinline__ void mbar_expect(uint32_t a, int b) { asm volatile("mbarrier.arrive.expect_tx.shared::cta.b64 _, [%0], %1;" ::"r"(a), "r"(b) : "memory"); }
__device__ __forceinline__ void mbar_arrive(uint32_t a) { asm volatile("mbarrier.arrive.shared::cta.b64 _, [%0];" ::"r"(a) : "memory"); }
__device__ __forceinline__ void mbar_arrive_cluster(uint32_t a, uint32_t cta, uint32_t cnt) {
  asm volatile("{\n.reg .b32 r;\nmapa.shared::cluster.u32 r, %0, %1;\nmbarrier.arrive.shared::cluster.b64 _, [r], %2;\n}" ::"r"(a), "r"(cta), "r"(cnt) : "memory");
}
__device__ __forceinline__ void mbar_wait(uint32_t a, int ph) {
  asm volatile("{\n.reg .pred p;\n.reg .u32 c;\nmov.u32 c, 0;\nWAIT:\n"
               "mbarrier.try_wait.parity.shared::cta.b64 p, [%0], %1;\n@p bra DONE;\n"
               "add.u32 c, c, 1;\nsetp.lt.u32 p, c, 0x400000;\n@p bra WAIT;\ntrap;\nDONE:\n}" ::"r"(a), "r"(ph) : "memory");
}
__device__ __forceinline__ void flag_wait(const unsigned* p, unsigned target) {
  asm volatile("{\n.reg .pred p;\n.reg .u32 c, v;\nmov.u32 c, 0;\nWAIT:\n"
               "ld.acquire.gpu.global.u32 v, [%0];\nsetp.ge.u32 p, v, %1;\n@p bra DONE;\n"
               "add.u32 c, c, 1;\nsetp.lt.u32 p, c, 0x400000;\n@p bra WAIT;\ntrap;\nDONE:\n}" ::"l"(p), "r"(target) : "memory");
}
__device__ __forceinline__ bool elect_one() {
  uint32_t p;
  asm volatile("{\n.reg .pred P;\nelect.sync _|P, 0xffffffff;\nselp.u32 %0, 1, 0, P;\n}" : "=r"(p));
  return p != 0;
}
__device__ __forceinline__ void bulk_ld(uint32_t dst, const void* src, int bytes, uint32_t bar) {
  asm volatile("cp.async.bulk.shared::cluster.global.mbarrier::complete_tx::bytes [%0], [%1], %2, [%3];" ::"r"(dst), "l"(src), "r"(bytes), "r"(bar) : "memory");
}
__device__ __forceinline__ void bulk_ld_mc_h(uint32_t dst, const void* src, int bytes, uint32_t bar, uint16_t mask, uint64_t pol) {
  asm volatile("cp.async.bulk.shared::cluster.global.mbarrier::complete_tx::bytes.multicast::cluster.L2::cache_hint [%0], [%1], %2, [%3], %4, %5;" ::"r"(dst), "l"(src), "r"(bytes), "r"(bar), "h"(mask), "l"(pol) : "memory");
}
__device__ __forceinline__ void tma_ld2(uint32_t dst, const CUtensorMap* tm, int c0, int c1, uint32_t bar) {
  asm volatile("cp.async.bulk.tensor.2d.shared::cluster.global.mbarrier::complete_tx::bytes [%0], [%1, {%3,%4}], [%2];" ::"r"(dst), "l"(tm), "r"(bar), "r"(c0), "r"(c1) : "memory");
}
__device__ __forceinline__ void tma_ld3(uint32_t dst, const CUtensorMap* tm, int c0, int c1, int c2, uint32_t bar) {
  asm volatile("cp.async.bulk.tensor.3d.shared::cluster.global.mbarrier::complete_tx::bytes [%0], [%1, {%3,%4,%5}], [%2];" ::"r"(dst), "l"(tm), "r"(bar), "r"(c0), "r"(c1), "r"(c2) : "memory");
}
__device__ __forceinline__ void tma_ld3h(uint32_t dst, const CUtensorMap* tm, int c0, int c1, int c2, uint32_t bar, uint64_t pol) {
  asm volatile("cp.async.bulk.tensor.3d.shared::cluster.global.mbarrier::complete_tx::bytes.L2::cache_hint [%0], [%1, {%3,%4,%5}], [%2], %6;" ::"r"(dst), "l"(tm), "r"(bar), "r"(c0), "r"(c1), "r"(c2), "l"(pol) : "memory");
}
__device__ __forceinline__ uint64_t policy_evict_first() {
  uint64_t p;
  asm("createpolicy.fractional.L2::evict_first.b64 %0, 1.0;" : "=l"(p));
  return p;
}
__device__ __forceinline__ void tma_st3(const CUtensorMap* tm, uint32_t src, int c0, int c1, int c2) {
  asm volatile("cp.async.bulk.tensor.3d.global.shared::cta.bulk_group [%0, {%2,%3,%4}], [%1];" ::"l"(tm), "r"(src), "r"(c0), "r"(c1), "r"(c2) : "memory");
}
__device__ __forceinline__ void tma_st4(const CUtensorMap* tm, uint32_t src, int c0, int c1, int c2, int c3) {
  asm volatile("cp.async.bulk.tensor.4d.global.shared::cta.bulk_group [%0, {%2,%3,%4,%5}], [%1];" ::"l"(tm), "r"(src), "r"(c0), "r"(c1), "r"(c2), "r"(c3) : "memory");
}
__device__ __forceinline__ void tma_st5(const CUtensorMap* tm, uint32_t src, int c0) {
  asm volatile("cp.async.bulk.tensor.5d.global.shared::cta.bulk_group [%0, {%2,%3,%3,%3,%3}], [%1];" ::"l"(tm), "r"(src), "r"(c0), "r"(0) : "memory");
}
__device__ __forceinline__ void bulk_commit() { asm volatile("cp.async.bulk.commit_group;" ::: "memory"); }
template <int N> __device__ __forceinline__ void bulk_wait_read() { asm volatile("cp.async.bulk.wait_group.read %0;" ::"n"(N) : "memory"); }
template <int N> __device__ __forceinline__ void bulk_wait() { asm volatile("cp.async.bulk.wait_group %0;" ::"n"(N) : "memory"); }
__device__ __forceinline__ void fence_async_smem() { asm volatile("fence.proxy.async.shared::cta;" ::: "memory"); }
__device__ __forceinline__ void wg_fence() { asm volatile("wgmma.fence.sync.aligned;" ::: "memory"); }
__device__ __forceinline__ void wg_commit() { asm volatile("wgmma.commit_group.sync.aligned;" ::: "memory"); }
template <int N> __device__ __forceinline__ void wg_wait() { asm volatile("wgmma.wait_group.sync.aligned %0;" ::"n"(N) : "memory"); }
template <int R> __device__ __forceinline__ void fence_regs(float (&d)[R]) {
#pragma unroll
  for (int i = 0; i < R; i++) asm volatile("" : "+f"(d[i])::"memory");
}
__device__ __forceinline__ uint64_t mk_desc(uint32_t addr) {
  return (uint64_t)((addr & 0x3FFFF) >> 4) | (1ull << 16) | (64ull << 32) | (1ull << 62);
}
__device__ __forceinline__ uint32_t pack2(float lo, float hi) {
  uint32_t r;
  asm("cvt.rn.bf16x2.f32 %0, %1, %2;" : "=r"(r) : "f"(hi), "f"(lo));
  return r;
}
__device__ __forceinline__ void stsm4(uint32_t ad, uint32_t a, uint32_t b, uint32_t c, uint32_t d) {
  asm volatile("stmatrix.sync.aligned.m8n8.x4.shared.b16 [%0], {%1,%2,%3,%4};" ::"r"(ad), "r"(a), "r"(b), "r"(c), "r"(d) : "memory");
}
__device__ __forceinline__ void stsm4t(uint32_t ad, uint32_t a, uint32_t b, uint32_t c, uint32_t d) {
  asm volatile("stmatrix.sync.aligned.m8n8.x4.trans.shared.b16 [%0], {%1,%2,%3,%4};" ::"r"(ad), "r"(a), "r"(b), "r"(c), "r"(d) : "memory");
}

__device__ __forceinline__ void stsm2t(uint32_t ad, uint32_t a, uint32_t b) {
  asm volatile("stmatrix.sync.aligned.m8n8.x2.trans.shared.b16 [%0], {%1,%2};" ::"r"(ad), "r"(a), "r"(b) : "memory");
}
__device__ __forceinline__ void red_add(unsigned* p) { asm volatile("red.relaxed.gpu.global.add.u32 [%0], 1;" ::"l"(p) : "memory"); }
__device__ __forceinline__ void fence_release() { asm volatile("fence.release.gpu;" ::: "memory"); }
__device__ __forceinline__ void fence_async_global() { asm volatile("fence.proxy.async.global;" ::: "memory"); }
__device__ __forceinline__ void tma_pf3(const CUtensorMap* tm, int c0, int c1, int c2) {
  asm volatile("cp.async.bulk.prefetch.tensor.3d.L2.global [%0, {%1,%2,%3}];" ::"l"(tm), "r"(c0), "r"(c1), "r"(c2) : "memory");
}
__device__ __forceinline__ void tma_ld4(uint32_t dst, const CUtensorMap* tm, int c1, uint32_t bar) {
  asm volatile("cp.async.bulk.tensor.4d.shared::cluster.global.mbarrier::complete_tx::bytes [%0], [%1, {%4,%3,%4,%4}], [%2];" ::"r"(dst), "l"(tm), "r"(bar), "r"(c1), "r"(0) : "memory");
}
__device__ __forceinline__ void bulk_ld_mc(uint32_t dst, const void* src, int bytes, uint32_t bar, uint16_t mask) {
  asm volatile("cp.async.bulk.shared::cluster.global.mbarrier::complete_tx::bytes.multicast::cluster [%0], [%1], %2, [%3], %4;" ::"r"(dst), "l"(src), "r"(bytes), "r"(bar), "h"(mask) : "memory");
}

__device__ __forceinline__ unsigned flag_peek(const unsigned* p) {
  unsigned v;
  asm volatile("ld.acquire.gpu.global.u32 %0, [%1];" : "=r"(v) : "l"(p) : "memory");
  return v;
}
__device__ __forceinline__ int lane_id() {
  int l;
  asm volatile("mov.u32 %0, %%laneid;" : "=r"(l));
  return l;
}
__device__ __forceinline__ void poll64x4(const unsigned long long* p, unsigned long long (&v)[4]) {
  asm volatile("{\n.reg .pred p;\n.reg .u32 c;\n.reg .b64 t, u;\nmov.u32 c, 0;\nWAIT:\n"
               "ld.relaxed.gpu.global.u64 %0, [%4];\nld.relaxed.gpu.global.u64 %1, [%4+512];\n"
               "ld.relaxed.gpu.global.u64 %2, [%4+1024];\nld.relaxed.gpu.global.u64 %3, [%4+1536];\n"
               "or.b64 t, %0, %1;\nor.b64 u, %2, %3;\nor.b64 t, t, u;\nsetp.ge.s64 p, t, 0;\n@p bra DONE;\n"
               "add.u32 c, c, 1;\nsetp.lt.u32 p, c, 0x400000;\n@p bra WAIT;\ntrap;\nDONE:\n}"
               : "=l"(v[0]), "=l"(v[1]), "=l"(v[2]), "=l"(v[3]) : "l"(p) : "memory");
}

constexpr int G_STAGE = WBLK + XBLK;
constexpr int OFF_XR = 4 * G_STAGE;
constexpr int OFF_WS = OFF_XR + 6 * 8192;
constexpr int OFF_F = OFF_WS + 2 * 8192;
constexpr int OFF_WRAW = OFF_F + 8192;
constexpr int OFF_BAR = OFF_WRAW + 8192;
constexpr int OFF_GB = OFF_BAR + 1024;
constexpr int SMEM_BYTES = OFF_GB + 512;
constexpr int OFF_H0B = 10 * 8192;
constexpr int OFF_E = OFF_WRAW + 3072;
constexpr int B_RAWX = 0, B_F = 48, B_ROLE = 56, B_H0 = 80, B_H1 = 96, B_YFREE = 120, B_H0C = 136,
              B_EMPTY = 144,
              B_STGX = 192, B_STGW = 240, B_Y = 256, B_OUT = 272, B_YP = 352,
              B_FULL = 432, B_RAWW = 464, B_DONE = 496, S_ROLE = 576, S_PROBE = 592;

static_assert(B_YP == B_OUT + 80, "");
struct Maps { CUtensorMap x, we, wo, xst[2], wst, yld[2], out, xe[2], w30; };

__device__ __forceinline__ int chunk_of(int n) { return n < 16 ? n : 31 - n; }
__device__ __forceinline__ bool has_x2(int id, int n, int g) { return (((id >> 5) ^ n) & 1) == 0 && ((n >> 1) & 1) == g; }
__device__ __forceinline__ int w_row(int id) { return (id & 62) | (id >> 6); }
__device__ __forceinline__ uint32_t x_base(int s, int idx, uint32_t pgmask, int& par) {
  const int page = idx >> 3, o = idx & 7;
  par = (s ^ (pgmask >> page) ^ __popc(o)) & 1;
  return (page << 21) | ((o & 3) << 16) | ((o >> 2) << 19);
}
__device__ __forceinline__ uint32_t spread5(int i) { return (((i >> 1) & 3) << 14) | (((i >> 3) & 1) << 18) | ((i >> 4) << 20) | ((i & 1) << 13); }
__device__ __forceinline__ int y_idx(int half, int dq, int piece) { return (PG_Y + 5 * half) * 8 + (dq * 5 + piece) * 2; }
__device__ __forceinline__ int tail_win(int tr) { return (tr & 1) + 4 * (tr >> 1); }
__device__ __forceinline__ uint32_t read_info(uint32_t bar, int i) {
  uint32_t v;
  mbar_wait(bar + B_ROLE + 8 * i, 0);
  asm volatile("ld.shared.b32 %0, [%1];" : "=r"(v) : "r"(bar + S_ROLE + 4 * i) : "memory");
  return v;
}
__device__ __forceinline__ void send_info(uint32_t bar, int i, uint32_t v) {
#pragma unroll
  for (int r = 0; r < 2; r++)
    asm volatile("{\n.reg .b32 a, m;\nmapa.shared::cluster.u32 a, %0, %2;\nmapa.shared::cluster.u32 m, %1, %2;\n"
                 "st.async.weak.shared::cluster.mbarrier::complete_tx::bytes.b32 [a], %3, [m];\n}"
                 ::"r"(bar + S_ROLE + 4 * i), "r"(bar + B_ROLE + 8 * i), "r"(r), "r"(v) : "memory");
}
__device__ __forceinline__ unsigned probe(uint8_t* p, int lane) {
  if (lane < 2) *(uint4*)(p + lane * 16) = make_uint4(0, 0, 0, 0);
  __syncwarp();
  unsigned v, t0 = 0, t1 = 0;
  if (lane == 0) {
    asm volatile("mov.u32 %0, %%clock;" : "=r"(t0)::"memory");
    asm volatile("atom.relaxed.gpu.global.exch.b32 %0, [%1], 0;" : "=r"(v) : "l"(p) : "memory");
    asm volatile("{\n.reg .pred p;\nsetp.ne.u32 p, %1, 0xffffffff;\nmov.u32 %0, 0;\n@p mov.u32 %0, %%clock;\n}" : "=r"(t1) : "r"(v) : "memory");
  }
  return t1 - t0;
}

template <bool ISX>
__device__ __forceinline__ void t_issue(float (&t)[32], uint32_t sb, uint32_t raw) {
  const uint64_t da = mk_desc(sb + OFF_F), db = mk_desc(raw);
  wg_fence();
#pragma unroll
  for (int kk = 0; kk < (ISX ? 4 : 1); kk++) wgmma_fwd<1>(t, da + 2 * kk, db + 128 * kk, kk);
  wg_commit();
}
template <bool ISX>
__device__ __forceinline__ void t_finish(float (&t)[32], uint32_t dst, uint32_t sbar, int sw, int wg, int w, int lane) {
  fence_regs(t);
  if (ISX) asm volatile("bar.sync %0, 128;" ::"r"(1 + wg) : "memory");
  const int m = lane >> 3, r = lane & 7;
  uint32_t ad = dst + (8 * w + r) * 128;
  if (ISX) ad += ((((m & 1) * 4 + (m >> 1)) ^ sw ^ r) << 4);
  else ad += (m & 1) * 4096 + (((m >> 1) ^ sw ^ r) << 4);
#pragma unroll
  for (int i = 0; i < 4; i++) {
    const uint32_t a = ISX ? ((ad ^ ((i & 1) * 32)) + (i >> 1) * 4096) : (ad ^ (i * 32));
    stsm4(a, pack2(t[8 * i], t[8 * i + 1]), pack2(t[8 * i + 2], t[8 * i + 3]), pack2(t[8 * i + 4], t[8 * i + 5]), pack2(t[8 * i + 6], t[8 * i + 7]));
  }
  __syncwarp();
  if (lane == 0) mbar_arrive(sbar);
}
template <int NT, int K0, int K1>
__device__ __forceinline__ void batch(float (&yr)[80], float (&yi)[80], float (&t)[32], uint32_t st, int wg, int sd, uint32_t fa, uint32_t raw) {
  const uint64_t w0 = mk_desc(st + wg * 8192), x0 = mk_desc(st + WBLK);
  const uint64_t da = mk_desc(fa), db = mk_desc(raw);
  wg_fence();
  if (NT) {
#pragma unroll
    for (int kk = 0; kk < NT; kk++) wgmma_fwd<1>(t, da + 2 * kk, db + 128 * kk, kk);
    wg_commit();
  }
#pragma unroll
  for (int kk = K0; kk < K1; kk++) {
    const uint64_t wr = w0 + kk * 128, wi = wr + 256, xr = x0 + kk * 2, xi = xr + 4;
    wgmma_main<1>(yr, wr, xr, kk ? 1 : sd);
    wgmma_main<1>(yi, wr, xi, kk ? 1 : sd);
    wgmma_main<1>(yr, wi, xi, 1);
    wgmma_main<-1>(yi, wi, xr, 1);
  }
  wg_commit();
}

#define X_WAIT() mbar_wait(bar + B_RAWX + 8 * (wg * 3 + xs), xph)
#define X_ISSUE() t_issue<true>(t, sb, sb + OFF_XR + (wg * 3 + xs) * 8192)
#define X_FINISH(sw) do { t_finish<true>(t, sb + OFF_XR + (wg * 3 + xs) * 8192, bar + B_STGX + 8 * (wg * 3 + xs), sw, wg, w, lane); \
                          if (++xs == 3) { xs = 0; xph ^= 1; } } while (0)
#define W_WAIT(n) mbar_wait(bar + B_RAWW + 8 * (wg * 2 + ((n) & 1)), ((n) >> 1) & 1)
#define WRAW(n) (sb + OFF_WRAW + (wg * 2 + ((n) & 1)) * 2048)
#define W_FINISH() t_finish<false>(t, sb + OFF_WS + wg * 8192, bar + B_STGW + 8 * wg, w_row(id) & 7, wg, w, lane)

__device__ __forceinline__ void gelu_store(float (&hz)[28], uint32_t ad) {
#pragma unroll
  for (int i = 0; i < 28; i++) {
    const float in = hz[i] * fmaf(hz[i] * hz[i], 8.f * 0.044715f * 0.7978845608028654f, 2.f * 0.7978845608028654f);
    float th;
    asm("tanh.approx.f32 %0, %1;" : "=f"(th) : "f"(in));
    hz[i] = fmaf(hz[i], th, hz[i]);
  }
#pragma unroll
  for (int jj = 0; jj < 3; jj++) {
    const float* c = hz + 8 * jj;
    stsm4t(ad + jj * 2048, pack2(c[0], c[1]), pack2(c[2], c[3]), pack2(c[4], c[5]), pack2(c[6], c[7]));
  }
  stsm2t(ad + 3 * 2048, pack2(hz[24], hz[25]), pack2(hz[26], hz[27]));
}

#define ONE(...) do { if (elect_one()) { __VA_ARGS__; } } while (0)
template <int g>
__device__ __forceinline__ void manager(const Maps& tm, const unsigned* ctr, const uint32_t sb, const int id) {
  const uint32_t bar = sb + OFF_BAR, rank = id & 1;
  const uint64_t pol = policy_evict_first();
  const int cl = w_row(id), b = id >> 6, u = (id >> 1) & 31;
  const unsigned* pf = ctr + (C_LOADED + (((cl >> 5) - WR) >> 1)) * 32 + (((cl >> 5) - WR) & 1);
  int li = 0;
  auto refill = [&](int sl, bool wait) {
    const uint32_t fb = bar + B_RAWX + 8 * (g * 3 + sl);
    int row = ((li & 1) ? 128 + (id & 31) : 2 * (id & 63) + g) * MT, col = (li >> 1) * 64;
    asm volatile("" : "+r"(row), "+r"(col));
    ONE(if (li < 32) mbar_expect(fb, 8192);
        if (wait) bulk_wait_read<0>();
        if (li < 32) tma_ld3h(sb + OFF_XR + (g * 3 + sl) * 8192, &tm.x, col, row, b, fb, pol));
    li += (li & 1) || has_x2(id, li >> 1, g) ? 1 : 2;
  };
#pragma unroll 1
  for (int sl = 0; sl < 3; sl++) refill(sl, false);
  int xs = 0, xph = 0, yp = 0;
  int wrow = (cl >> 5) * (WSLOT / 128) + rank * 128 + g * 64 + (cl & 31);
  const uint32_t pgmask = __shfl_sync(0xffffffffu, read_info(bar, 1), 0);
  auto store_y = [&](int half, int piece, uint32_t buf, uint32_t wait_bar, int ph) {
    int par;
    int c = x_base(b, y_idx(half, rank * 2 + g, piece) + (u >> 4), pgmask, par);
    c = (c + (par << 12) + (u & 15) * 256) >> 1;
    const CUtensorMap* m = &tm.xst[par];
    asm volatile("" : "+r"(c), "+l"(m));
    if (wait_bar) mbar_wait(wait_bar, ph);
    ONE(fence_async_smem(); tma_st5(m, buf, c); tma_st5(m, buf + 4096, c + 64));
  };
  mbar_wait(bar + B_STGW + 8 * g, 0);
  ONE(fence_async_smem(); tma_st4(&tm.wst, sb + OFF_WS + g * 8192, 0, 0, 0, wrow); bulk_commit());
#pragma unroll 1
  for (int n = 0; n < 32; n++) {
    unsigned freed = 128;
    if (2 * n + (cl >> 5) >= WR) asm volatile("ld.relaxed.gpu.global.u32 %0, [%1];" : "=r"(freed) : "l"(pf + n * 32) : "memory");
    if (n < 16) {
#pragma unroll 1
      for (int j = 0; j < (has_x2(id, n, g) ? 2 : 1); j++) {
        const int t = j ? 128 + (id & 31) : 2 * (id & 63) + g;
        int par0, par1;
        const uint32_t off0 = x_base(b, n * 10 + (t >> 5), pgmask, par0), off1 = x_base(b, n * 10 + 5 + (t >> 5), pgmask, par1);
        uint32_t buf = sb + OFF_XR + (g * 3 + xs) * 8192;
        int c0 = (off0 + (par0 << 12) + (t & 31) * 128) >> 1, c1 = (off1 + (par1 << 12) + (t & 31) * 128) >> 1;
        const CUtensorMap *m0 = &tm.xst[par0], *m1 = &tm.xst[par1];
        asm volatile("" : "+r"(buf), "+r"(c0), "+r"(c1), "+l"(m0), "+l"(m1));
        mbar_wait(bar + B_STGX + 8 * (g * 3 + xs), xph);
        ONE(fence_async_smem(); tma_st5(m0, buf, c0); tma_st5(m1, buf + 4096, c1); bulk_commit());
        refill(xs, true);
        if (++xs == 3) { xs = 0; xph ^= 1; }
      }
    }
    if (n > 16 + LW && n <= YFLUSH) {
#pragma unroll 1
      do {
        store_y(0, yp, sb + OFF_XR + (g * 3 + (yp < 3 ? yp : yp - 3)) * 8192, (yp == 0 || yp == 3) ? bar + B_Y + 8 * g : 0, yp & 1);
      } while (++yp < 2);
      ONE(bulk_commit(); bulk_wait_read<0>(); if (yp == 2) mbar_arrive(bar + B_YFREE + 8 * g));
    }
    if (__shfl_sync(0xffffffffu, freed, 0) < 128) flag_wait(pf + n * 32, 128);
    const int cp = chunk_of(n + 2) * 64 + cl, sl = g * 2 + (n & 1);
    if (n) mbar_wait(bar + B_STGW + 8 * g, n & 1);
    ONE(if (n) {
          fence_async_smem();
          tma_st4(&tm.wst, sb + OFF_WS + g * 8192, 0, 0, 0, wrow);
          bulk_commit();
        }
        if (n < 30) {
          mbar_expect(bar + B_RAWW + 8 * sl, 2048);
          tma_ld3h(sb + OFF_WRAW + sl * 2048, &tm.we + (cp >> 9), 0, 0, (cp & 511) * 8 + ((n + 2) >> 4) * 4 + rank * 2 + g, bar + B_RAWW + 8 * sl, pol);
        }
        if (n < 4) {
          tma_pf3(&tm.we, 0, 0, ((n + 4) * 64 + cl) * 8 + rank * 2 + g);
          tma_pf3(&tm.wo, 0, 0, (n * 64 + cl) * 8 + rank * 2 + g);
          tma_pf3(&tm.wo, 0, 0, ((n + 4) * 64 + cl) * 8 + rank * 2 + g);
        }
        bulk_wait<0>();
        mbar_arrive(bar + B_DONE + 8 * (n & 7));
        mbar_arrive(bar + B_RAWW + 8 * (sl ^ 1)));
    wrow += 2 * WSLOT / 128;
    if (wrow >= WR * WSLOT / 128) wrow -= WR * WSLOT / 128;
  }
  ONE(asm volatile("prefetch.tensormap [%0];" ::"l"(g ? &tm.out : &tm.xst[b]) : "memory"));
  flag_wait(&ctr[(C_LOADED + 31) * 32 + 1], 128);
#pragma unroll 1
  for (int p = 0; p < 5; p++) {
    store_y(1, p, sb + (p * 2 + g) * 8192, bar + B_YP + 8 * (g * 5 + p), 0);
    if (p == YA - 1) ONE(bulk_commit());
  }
  ONE(bulk_commit(); bulk_wait<1>(); mbar_arrive(bar + B_DONE); bulk_wait<0>(); mbar_arrive(bar + B_DONE + 8));
  mbar_wait(bar + B_H1, 0);
#pragma unroll 1
  for (int i = 0; i < 10; i++) {
    const int hf = i >= 5, k = i - 5 * hf;
    const uint32_t buf = sb + (hf ? 0 : k < 4 ? OFF_XR : OFF_H0B - 65536) + (2 * k + g) * 8192;
    mbar_wait(bar + B_OUT + 80 * hf + 8 * (g * 5 + k), hf);
    ONE(fence_async_smem();
        tma_st3(&tm.out, buf, (hf * 4 + rank * 2 + (u & 1)) * 64, (32 * k + tail_win(u >> 1) + 2 * g) * MT, b);
        bulk_commit());
  }
  ONE(bulk_wait_read<0>());
}

__global__ void __cluster_dims__(2, 1, 1) __launch_bounds__(512, 1)
k1_main(uint8_t* xbuf, const void* __restrict__ fimg, const __nv_bfloat16* __restrict__ gamma,
        const __nv_bfloat16* __restrict__ beta, const __grid_constant__ Maps tm) {
  extern __shared__ __align__(1024) uint8_t smem_raw[];
  const uint32_t sb = s2u(smem_raw);
  const uint32_t bar = sb + OFF_BAR;
  const int warp = __shfl_sync(0xffffffffu, threadIdx.x >> 5, 0);
  const int bid = blockIdx.x;
  unsigned* ctr = (unsigned*)(xbuf + CTR_OFF);
  const uint32_t rank = bid & 1;
  if (bid == 0 && threadIdx.x < 4) asm volatile("st.relaxed.gpu.global.u64 [%0], %1;" ::"l"(&ctr[C_REG * 32 + 2 * threadIdx.x]), "l"(1ull << 63) : "memory");
  if (warp >= 12) {
    asm volatile("setmaxnreg.dec.sync.aligned.u32 24;");
    asm volatile("barrier.cluster.arrive.relaxed.aligned;" ::: "memory");
    {
      const int lane = lane_id(), k = bid >> 1;
      if (rank == 0 || k < XPAGES) {
        const uint32_t off = rank ? (k << 21) + 0xb0000 : (XPAGES << 21) + ((k >> 6) << 18) + (((k >> 4) & 3) << 14) + (k & 15) * 128;
        const unsigned lat = probe(xbuf + off + (warp & 1) * 4096 + (warp & 2) * 1024, lane);
        if (lane == 0) asm volatile("st.shared.b32 [%0], %1;" ::"r"(bar + S_PROBE + 4 * (warp & 3)), "r"(lat) : "memory");
      }
      asm volatile("bar.sync 4, 128;" ::: "memory");
      asm volatile("barrier.cluster.wait.aligned;" ::: "memory");
      if (warp == 14 && lane == 0) {
        uint32_t l0, l1, l2, l3;
        asm volatile("ld.shared.v4.b32 {%0, %1, %2, %3}, [%4];" : "=r"(l0), "=r"(l1), "=r"(l2), "=r"(l3) : "r"(bar + S_PROBE) : "memory");
        const int near = min(l1, l3) < min(l0, l2);
        if (rank) {
          send_info(bar, 2, near);
        } else {
          unsigned long long add = 1ull << (8 * near), v, *reg = (unsigned long long*)&ctr[C_REG * 32];
          if (k < XPAGES) add += (unsigned long long)(read_info(bar, 2) ^ near ^ 1) << (16 + k);
          asm volatile("{\n.reg .pred p;\n.reg .u32 c;\nmov.u32 c, 0;\nAGAIN:\n"
                       "atom.relaxed.gpu.global.add.u64 %0, [%1], %2;\nsetp.lt.s64 p, %0, 0;\n@p bra DONE;\n"
                       "add.u32 c, c, 1;\nsetp.lt.u32 p, c, 0x8000;\n@p bra AGAIN;\ntrap;\nDONE:\n}" : "=l"(v) : "l"(reg), "l"(add) : "memory");
          const int ticket = (v >> (8 * near)) & 255;
          if (ticket < 32) send_info(bar, 0, near * 32 + ticket);
          asm volatile("{\n.reg .pred p;\n.reg .u32 c, a, b;\nmov.u32 c, 0;\nWAIT:\n"
                       "ld.relaxed.gpu.global.u64 %0, [%1];\ncvt.u32.u64 a, %0;\nbfe.u32 b, a, 8, 8;\nand.b32 a, a, 255;\nadd.u32 a, a, b;\n"
                       "setp.ge.u32 p, a, 66;\n@p bra DONE;\n"
                       "add.u32 c, c, 1;\nsetp.lt.u32 p, c, 0x400000;\n@p bra WAIT;\ntrap;\nDONE:\n}" : "=l"(v) : "l"(reg) : "memory");
          if (ticket >= 32) {
            const int j = ticket - 32 + (int)((v >> (8 * (near ^ 1))) & 255);
            send_info(bar, 0, j < 32 ? (near ^ 1) * 32 + j : (near == 0 && ticket == 32 && j == 33) ? 64 : 32 + j);
          }
          send_info(bar, 1, (uint32_t)(v >> 16));
        }
      }
      __syncwarp();
      const int role = read_info(bar, 0);
      if (role < 64 && warp - 12 < NFL && elect_one()) {
#pragma unroll 1
        for (int n = warp - 12; n < 34; n += NFL) {
          mbar_wait(bar + B_DONE + 8 * (n & 7), (n >> 3) & 1);
          fence_release();
          if (n < 32) {
            red_add(&ctr[(C_FLAG + n + C_SIDE * ((role >> 5) ^ 1)) * 32]);
            red_add(&ctr[(C_FLAG + n + C_SIDE * (role >> 5)) * 32]);
          } else {
            red_add(&ctr[(C_Y + 2 * (n - 32) + rank + C_SIDE * (role >> 5)) * 32]);
          }
        }
      }
      if (role < 64 && warp == 15 && elect_one()) {
#pragma unroll 1
        for (int v = 0; v < 64; v++) {
          mbar_wait(bar + B_FULL + 8 * (v & 3), (v >> 2) & 1);
          mbar_arrive(bar + B_EMPTY + 8 * (v & 3));
          if (v < 64 - WR || v == 63) {
            red_add(&ctr[(C_LOADED + (v >> 1)) * 32 + (v & 1)]);
            red_add(&ctr[(C_LOADED + (v >> 1) + C_SIDE) * 32 + (v & 1)]);
          }
        }
      }
      __syncwarp();
    }
    asm volatile("barrier.cluster.arrive.relaxed.aligned;\nbarrier.cluster.wait.aligned;" ::: "memory");
    return;
  } else {
    if (elect_one()) {
      if (warp >= 6) asm volatile("prefetch.tensormap [%0];" ::"l"(&tm.x + (warp - 6)) : "memory");
      const int cnt = warp < 3 ? 1 : warp == 3 ? 5 : warp < 9 ? 4 : 2;
#pragma unroll
      for (int i = 0; i < 6; i++) mbar_init(bar + warp * 48 + 8 * i, cnt);
      asm volatile("fence.mbarrier_init.release.cluster;" ::: "memory");
      if (warp == 1) {
        mbar_expect(bar + B_F, 8192);
        bulk_ld(sb + OFF_F, fimg, 8192, bar + B_F);
        mbar_expect(bar + B_ROLE, 4);
        mbar_expect(bar + B_ROLE + 8, 4);
        mbar_expect(bar + B_ROLE + 16, 4);
      }
    }
    asm volatile("bar.sync 0, 384;" ::: "memory");
    asm volatile("barrier.cluster.arrive.relaxed.aligned;" ::: "memory");
    if (bid < 128 && warp < 4 && elect_one()) {
      const int g = warp & 1;
      if (warp < 2) {
        tma_pf3(&tm.x, 0, (2 * (bid & 63) + g) * MT, bid >> 6);
        if (has_x2(bid, 0, g)) tma_pf3(&tm.x, 0, (128 + (bid & 31)) * MT, bid >> 6);
      } else {
        tma_pf3(&tm.we, 0, 0, (bid >> 1) * 8 + rank * 2 + g);
      }
    }
    __syncwarp();
  }
  if (warp >= 8) {
    asm volatile("setmaxnreg.dec.sync.aligned.u32 40;");
    asm volatile("barrier.cluster.wait.aligned;" ::: "memory");
    const int role = __shfl_sync(0xffffffffu, read_info(bar, 0), 0);
    const unsigned* lctr = ctr + (role >> 5) * C_SIDE * 32;
    if (role >= 64) {
    } else if (warp == 9 || warp == 10) {
      asm volatile("barrier.cluster.arrive.relaxed.aligned;" ::: "memory");
      if (warp == 9) manager<0>(tm, lctr, sb, role * 2 + rank); else manager<1>(tm, lctr, sb, role * 2 + rank);
      __syncwarp();
      asm volatile("barrier.cluster.wait.aligned;" ::: "memory");
      return;
    } else if (warp == 11) {
      const uint8_t* ws = xbuf + (PG_W << 21) + ((role & 31) * 2 + rank) * WBLK;
      int slot = 0;
#pragma unroll 1
      for (int v = 0; v < 64; v++) {
        const uint8_t* src = ws + (size_t)slot * WSLOT;
        uint32_t dst = sb + (v & 3) * G_STAGE, fb = bar + B_FULL + 8 * (v & 3);
        asm volatile("" : "+l"(src), "+r"(dst), "+r"(fb));
        if (++slot == WR) slot = 0;
        const unsigned* fp = &lctr[(C_FLAG + (v >> 1)) * 32];
        const bool ready = (v & 1) || __shfl_sync(0xffffffffu, flag_peek(fp), 0) >= 128;
        mbar_wait(bar + B_EMPTY + 8 * (v & 3), ((v >> 2) & 1) ^ 1);
        ONE(mbar_expect(fb, WBLK));
        if (!ready) flag_wait(fp, 128);
        ONE(fence_async_global(); bulk_ld(dst, src, WBLK, fb));
      }
    } else {
      const uint32_t pgmask = __shfl_sync(0xffffffffu, read_info(bar, 1), 0);
      const int b = role >> 5, u = role & 31;
      const uint64_t pef = policy_evict_first();
      const uint8_t* xs = xbuf + spread5(u);
      const int skip = rank * 2048;
#pragma unroll 1
      for (int v = 0; v < 64; v++) {
        const int n = v >> 1;
        uint32_t dst = sb + (v & 3) * G_STAGE + WBLK + rank * 8192, fb = bar + B_FULL + 8 * (v & 3);
        const uint8_t* src[3];
#pragma unroll
        for (int g = 0; g < 3; g++) {
          int par;
          const uint32_t o = x_base(b ^ u, chunk_of(n) * 10 + (v & 1) * 5 + rank * 2 + g, pgmask, par);
          src[g] = xs + o + (par << 12) + (g ? 0 : skip);
        }
        asm volatile("" : "+l"(src[0]), "+l"(src[1]), "+l"(src[2]), "+r"(dst), "+r"(fb));
        const unsigned* fp = &lctr[(C_FLAG + n) * 32];
        const bool ready = (v & 1) || v >= 32 || __shfl_sync(0xffffffffu, flag_peek(fp), 0) >= 128;
        mbar_wait(bar + B_EMPTY + 8 * (v & 3), ((v >> 2) & 1) ^ 1);
        ONE(mbar_expect(fb, XBLK));
        if (!ready) flag_wait(fp, 128);
        ONE(fence_async_global();
            if (n < XKEEP || n >= 16) {
              bulk_ld_mc_h(dst + skip, src[0], 4096 - skip, fb, 3, pef);
              bulk_ld_mc_h(dst + 4096, src[1], 4096, fb, 3, pef);
              bulk_ld_mc_h(dst + 8192, src[2], 2048 + skip, fb, 3, pef);
            } else {
              bulk_ld_mc(dst + skip, src[0], 4096 - skip, fb, 3);
              bulk_ld_mc(dst + 4096, src[1], 4096, fb, 3);
              bulk_ld_mc(dst + 8192, src[2], 2048 + skip, fb, 3);
            });
      }
      const int dq = rank * 2 + (u & 1), t0 = (u >> 1) * 10, tw = tail_win(u >> 1);
      int row[5];
      const CUtensorMap* mp[5];
      auto locate = [&](int half) {
#pragma unroll
        for (int k = 0; k < 5; k++) {
          int par;
          row[k] = x_base(b ^ tw, y_idx(half, dq, k), pgmask, par);
          row[k] = (row[k] + spread5(tw) + (par << 12)) >> 7;
          mp[k] = &tm.yld[par];
          asm volatile("" : "+r"(row[k]), "+l"(mp[k]));
        }
      };
      locate(0);
      flag_wait(&ctr[C_E * 32], 4);
      flag_wait(&lctr[(C_FLAG + YFLUSH) * 32], 128);
      ONE(fence_async_global();
          mbar_expect(bar + B_H0C, 6 * 8192);
          for (int i = 0; i < 3; i++) tma_ld4(sb + OFF_XR + i * 16384, mp[i], row[i], bar + B_H0C));
      static_assert(YFLUSH >= 23, "phase of the B_DONE ring");
      mbar_wait(bar + B_DONE + 8 * 7, 1);
      ONE(mbar_expect(bar + B_H0, 2 * 8192 + 7168 + 5120 + 512);
          bulk_ld(sb + OFF_F, g_Gimg, 7168, bar + B_H0);
          tma_ld4(sb + OFF_WS, mp[3], row[3], bar + B_H0);
          for (int hf = 0; hf < 2; hf++) {
            bulk_ld(sb + OFF_E + hf * 2560, g_E + ((b * 8 + hf * 4 + dq) * NT + t0) * 64, 2560, bar + B_H0);
            bulk_ld(sb + OFF_GB + hf * 256, gamma + (hf * 4 + dq) * 64, 128, bar + B_H0);
            bulk_ld(sb + OFF_GB + hf * 256 + 128, beta + (hf * 4 + dq) * 64, 128, bar + B_H0);
          });
      mbar_wait(bar + B_EMPTY + 8 * 2, 1);
      ONE(mbar_expect(bar + B_H0 + 8, 16384);
          tma_ld4(sb + OFF_H0B, mp[4], row[4], bar + B_H0 + 8);
          for (int i = 0; i < 3; i++) mbar_expect(bar + B_H1 + 8 * i, i < 2 ? 32768 : 16384));
      locate(1);
      flag_wait(&lctr[(C_Y + rank) * 32], 32);
      ONE(fence_async_global();
          for (int i = 0; i < YA; i++) tma_ld4(sb + i * 16384, mp[i], row[i], bar + B_H1 + 8 * (i >> 1)));
      flag_wait(&lctr[(C_Y + 2 + rank) * 32], 32);
      ONE(fence_async_global();
          for (int i = YA; i < 5; i++) tma_ld4(sb + i * 16384, mp[i], row[i], bar + B_H1 + 8 * (i >> 1)));
      const int lane = lane_id();
      unsigned old = 0;
      if (lane == 0) old = atomicAdd(&ctr[C_EXIT * 32], 1);
      if (__shfl_sync(0xffffffffu, old, 0) == 127) {
#pragma unroll
        for (int i = 0; i < 6; i++) *(uint4*)&ctr[((i >> 1) * 128 + (i & 1) * C_SIDE + lane) * 32] = make_uint4(0, 0, 0, 0);
      }
    }
    asm volatile("barrier.cluster.arrive.relaxed.aligned;\nbarrier.cluster.wait.aligned;" ::: "memory");
  } else {
    asm volatile("setmaxnreg.inc.sync.aligned.u32 224;");
    const int wg = warp >> 2, w = warp & 3;
    int lane = lane_id();
    asm volatile("barrier.cluster.wait.aligned;" ::: "memory");
    mbar_wait(bar + B_F, 0);
    const int id = __shfl_sync(0xffffffffu, read_info(bar, 0), 0) * 2 + rank;
    if (id >= 128) {
      float ea[80], eb[80];
      const int b = (id >> 1) & 1;
      constexpr int ES = 32768 + 2 * XBLK;
#pragma unroll 1
      for (int k = -3; k < 8; k++) {
        const int sl = (k + 3) % 3;
        if (k >= 0) {
          mbar_wait(bar + B_RAWX + 8 * sl, (k / 3) & 1);
          const uint64_t da = mk_desc(sb + sl * ES + wg * 16384), db = mk_desc(sb + sl * ES + 32768);
          wg_fence();
#pragma unroll
          for (int kk = 0; kk < 8; kk++) {
            const uint64_t a0 = da + (kk & 3) * 128, b0 = db + (kk & 3) * 2 + (kk >> 2) * (XBLK >> 4);
            wgmma_main<1>(ea, a0, b0, (k | kk) != 0);
            wgmma_main<1>(eb, a0 + 512, b0, (k | kk) != 0);
          }
          wg_commit();
          wg_wait<0>();
          asm volatile("bar.sync 3, 256;" ::: "memory");
        }
        if (k + 3 < 8 && warp == 0 && elect_one()) {
          if (k == -3) {
            for (int i = 0; i < 64; i++) {
              unsigned v;
              asm volatile("ld.relaxed.gpu.global.u32 %0, [%1];" : "=r"(v) : "l"(&ctr[(C_FLAG + 14) * 32]) : "memory");
              if (v >= 128) break;
              __nanosleep(500);
            }
          }
          const uint32_t dst = sb + sl * ES, fb = bar + B_RAWX + 8 * sl;
          mbar_expect(fb, ES);
          for (int q = 0; q < 4; q++) tma_ld2(dst + q * 8192, &tm.w30, rank * 256 + q * 64, (k + 3) * 64, fb);
          for (int q = 0; q < 2; q++) tma_ld3(dst + 32768 + q * XBLK, &tm.xe[q], (k + 3) * 64, 0, b, fb);
        }
        __syncwarp();
      }
      fence_regs(ea);
      fence_regs(eb);
      float* e0 = g_E + ((b * 8 + rank * 4 + wg * 2) * NT + 10 * (lane & 2) + (lane & 1)) * 64 + 16 * w + (lane >> 2);
#pragma unroll
      for (int i = 0; i < 80; i++) {
        const int o = (40 * ((i >> 2) & 3) + 2 * (i >> 4) + 10 * (i & 1)) * 64 + ((i >> 1) & 1) * 8;
        e0[o] = ea[i];
        e0[o + NT * 64] = eb[i];
      }
      asm volatile("bar.sync 3, 256;" ::: "memory");
      if (threadIdx.x == 0) {
        fence_release();
        red_add(&ctr[C_E * 32]);
      }
      asm volatile("barrier.cluster.arrive.relaxed.aligned;\nbarrier.cluster.wait.aligned;" ::: "memory");
      return;
    }
    if (w < 2 && elect_one()) {
      const uint32_t fb = bar + B_RAWW + 8 * (wg * 2 + w);
      mbar_expect(fb, 2048);
      tma_ld3h(sb + OFF_WRAW + (wg * 2 + w) * 2048, &tm.we, 0, 0, (w * 64 + w_row(id)) * 8 + rank * 2 + wg, fb, policy_evict_first());
      if (!w) mbar_arrive(fb);
    }
    __syncwarp();
    {
      float yr[80], yi[80], t[32];
      int xs = 0, xph = 0;
      W_WAIT(0);
      t_issue<false>(t, sb, WRAW(0));
      wg_wait<0>();
      W_FINISH();
#pragma unroll 1
      for (int m = 0; m <= LW; m++) {
        X_WAIT();
        X_ISSUE();
        wg_wait<0>();
        X_FINISH((2 * id + wg) & 7);
        if (has_x2(id, m, wg)) {
          X_WAIT();
          X_ISSUE();
          wg_wait<0>();
          X_FINISH(id & 7);
        }
        if (m < LW && m) {
          W_WAIT(m);
          t_issue<false>(t, sb, WRAW(m));
          wg_wait<0>();
          W_FINISH();
        }
      }
      const int ym = lane >> 3, yr8 = lane & 7;
      const uint32_t yad = (ym >> 1) * 4096 + yr8 * 128 + (((2 * w + (ym & 1)) ^ yr8) << 4);
#define STAGE_BEGIN() mbar_wait(bar + B_FULL + 8 * (v & 3), (v >> 2) & 1); const uint32_t st = sb + (v & 3) * G_STAGE
#define RELEASE(vv) do { if (w == 0 && lane < 2) mbar_arrive_cluster(bar + B_EMPTY + 8 * ((vv) & 3), lane, 1); } while (0)
#define XRAW (sb + OFF_XR + (wg * 3 + xs) * 8192)
#define STAGE_W0(mw, sd) do { W_WAIT(mw); batch<1, 0, 2>(yr, yi, t, st, wg, sd, sb + OFF_F, WRAW(mw)); wg_wait<1>(); W_FINISH(); wg_wait<0>(); RELEASE(v); } while (0)
#define STAGE_PLAIN0(sd) do { batch<0, 0, 2>(yr, yi, t, st, wg, sd, 0, 0); wg_wait<0>(); RELEASE(v); } while (0)
#define STAGE_W1(mw, sd) do { W_WAIT(mw); batch<1, 0, 1>(yr, yi, t, st, wg, sd, sb + OFF_F, WRAW(mw)); wg_wait<1>(); if (sd) RELEASE(v - 1); \
                              W_FINISH(); batch<0, 1, 2>(yr, yi, t, st, wg, 1, 0, 0); } while (0)
      constexpr int VX = 31 - 2 * LW;
#pragma unroll 1
      for (int v = 0; v < VX; v++) {
        const int m = ((v + 1) >> 1) + LW;
        STAGE_BEGIN();
        if (!(v & 1)) {
          STAGE_W1(m, v != 0);
        } else {
          X_WAIT();
          batch<4, 0, 1>(yr, yi, t, st, wg, 1, sb + OFF_F, XRAW);
          wg_wait<1>();
          RELEASE(v - 1);
          X_FINISH((2 * id + wg) & 7);
          if (has_x2(id, m, wg)) {
            X_WAIT();
            batch<4, 1, 2>(yr, yi, t, st, wg, 1, sb + OFF_F, XRAW);
            wg_wait<1>();
            X_FINISH(id & 7);
          } else {
            batch<0, 1, 2>(yr, yi, t, st, wg, 1, 0, 0);
          }
        }
      }
      wg_wait<0>();
      RELEASE(VX - 1);
#pragma unroll 1
      for (int v = VX; v < 32; v++) {
        const int m = ((v + 1) >> 1) + LW;
        STAGE_BEGIN();
        if (!(v & 1) || v == 31) STAGE_W0(m, 1); else STAGE_PLAIN0(1);
      }
      fence_regs(yr);
      fence_regs(yi);
      {
        uint32_t hold[32];
#pragma unroll
        for (int j = 0; j < 20; j++) {
          const uint32_t p0 = pack2(yr[4 * j], yr[4 * j + 1]), p1 = pack2(yr[4 * j + 2], yr[4 * j + 3]);
          const uint32_t p2 = pack2(yi[4 * j], yi[4 * j + 1]), p3 = pack2(yi[4 * j + 2], yi[4 * j + 3]);
          if (j < 12) {
            stsm4t(sb + OFF_XR + wg * 3 * 8192 + yad + (j >> 2) * 8192 + (j & 3) * 1024, p0, p1, p2, p3);
          } else {
            hold[4 * j - 48] = p0; hold[4 * j - 47] = p1; hold[4 * j - 46] = p2; hold[4 * j - 45] = p3;
          }
        }
#pragma unroll
        for (int j = 0; j < 32; j++) asm volatile("" : "+r"(hold[j])::"memory");
        __syncwarp();
        if (lane == 0) mbar_arrive(bar + B_Y + 8 * wg);
#pragma unroll
        for (int v = 32; v < 34; v++) {
          STAGE_BEGIN();
          STAGE_PLAIN0(v != 32);
        }
        mbar_wait(bar + B_YFREE + 8 * wg, 0);
#pragma unroll
        for (int j = 0; j < 8; j++)
          stsm4t(sb + OFF_XR + wg * 3 * 8192 + yad + (j >> 2) * 8192 + (j & 3) * 1024, hold[4 * j], hold[4 * j + 1], hold[4 * j + 2], hold[4 * j + 3]);
        __syncwarp();
        if (lane == 0) mbar_arrive(bar + B_Y + 8 * wg);
#pragma unroll
        for (int j = 0; j < 32; j++) t[j] = __uint_as_float(hold[j]);
      }
#pragma unroll 1
      for (int v = 34; v < 64; v++) {
        const int m = (v >> 1) + LW;
        STAGE_BEGIN();
        if (!(v & 1) && m < 32) {
          STAGE_W0(m, 1);
        } else {
          STAGE_PLAIN0(1);
          if (v == 49 && wg == 0) part_ptr(xbuf, id >> 6, w >> 1, rank * 2 + ((id >> 1) & 1), (id >> 2) & 15)[(w & 1) * 32 + lane] = ~0ull;
        }
      }
      wg_wait<0>();
      fence_regs(yr);
      fence_regs(yi);
      mbar_wait(bar + B_EMPTY + 8 * 2, 1);
#pragma unroll
      for (int j = 0; j < 20; j++) {
        stsm4t(sb + wg * 8192 + yad + (j >> 2) * 16384 + (j & 3) * 1024, pack2(yr[4 * j], yr[4 * j + 1]), pack2(yr[4 * j + 2], yr[4 * j + 3]),
               pack2(yi[4 * j], yi[4 * j + 1]), pack2(yi[4 * j + 2], yi[4 * j + 3]));
        if ((j & 3) == 3) {
          __syncwarp();
          if (lane == 0) mbar_arrive(bar + B_YP + 8 * (wg * 5 + (j >> 2)));
        }
      }
    }
    asm volatile("barrier.cluster.arrive.relaxed.aligned;" ::: "memory");
    lane = lane_id();
    const int tid = warp * 32 + lane, b = id >> 6, u = (id >> 1) & 31;
    const int dq = rank * 2 + (u & 1), tr = u >> 1;
    const int a = lane & 3, d0 = 16 * w + (lane >> 2);
    float2* s_red = (float2*)(smem_raw + OFF_WRAW);
    const uint32_t oad = wg * 8192 + ((lane >> 4) * 8 + (lane & 7)) * 128 + (((2 * w + ((lane >> 3) & 1)) ^ (lane & 7)) << 4);
    float hz[28];
#pragma unroll
    for (int i = 0; i < 28; i++) hz[i] = 0.f;
#pragma unroll 1
    for (int hf = 0; hf < 2; hf++) {
      const uint32_t base = sb + (hf ? 0 : OFF_XR), last = hf ? 0 : OFF_H0B - 65536 - OFF_XR;
      float acc[5][28];
      float q1[4] = {0.f, 0.f, 0.f, 0.f}, q2[4] = {0.f, 0.f, 0.f, 0.f};
      if (hf == 0) { mbar_wait(bar + B_H0, 0); mbar_wait(bar + B_H0C, 0); }
      const float* se = (const float*)(smem_raw + OFF_E + hf * 2560) + wg * 64 + d0;
#pragma unroll
      for (int k2 = 0; k2 < 4; k2++) {
        if (k2 < 3) {
          if (hf) mbar_wait(bar + B_H1 + 8 * k2, 0);
          else if (k2 == 2) mbar_wait(bar + B_H0 + 8, 0);
          const uint64_t da = mk_desc(base + (4 * k2 + wg) * 8192 + (k2 == 2 ? last : 0)), db = mk_desc(sb + OFF_F);
          wg_fence();
#pragma unroll
          for (int kk = 0; kk < 4; kk++) {
            wgmma_inv<1>(acc[2 * k2], da + 128 * kk, db + 2 * kk, kk);
            if (k2 < 2) wgmma_inv<1>(acc[2 * k2 + 1], da + 1024 + 128 * kk, db + 2 * kk, kk);
          }
          wg_commit();
        }
        if (k2 > 0) {
          if (k2 < 3) wg_wait<1>(); else wg_wait<0>();
#pragma unroll
          for (int k = 2 * k2 - 2; k < 2 * k2 && k < 5; k++) {
            fence_regs(acc[k]);
            if (a == 0) {
              acc[k][25] += se[k * 128];
              acc[k][27] += se[k * 128 + 8];
            }
            if (k == 4 && tr == 15 && wg == 1) {
#pragma unroll
              for (int i = 16; i < 28; i++)
                if (8 * (i >> 2) + (i & 1) + 2 * a >= LOUT - (NT - 1) * MT) acc[k][i] = 0.f;
            }
#pragma unroll
            for (int i = 0; i < 28; i++) {
              q1[i & 3] += acc[k][i];
              q2[i & 3] = fmaf(acc[k][i], acc[k][i], q2[i & 3]);
            }
            fence_regs(q1);
            fence_regs(q2);
          }
        }
      }
      float s1[2] = {q1[0] + q1[1], q1[2] + q1[3]}, s2[2] = {q2[0] + q2[1], q2[2] + q2[3]};
#pragma unroll
      for (int i = 0; i < 2; i++) {
#pragma unroll
        for (int o = 1; o < 4; o <<= 1) {
          s1[i] += __shfl_xor_sync(0xffffffffu, s1[i], o);
          s2[i] += __shfl_xor_sync(0xffffffffu, s2[i], o);
        }
      }
      if (a == 0) {
        s_red[wg * 64 + d0] = make_float2(s1[0], s2[0]);
        s_red[wg * 64 + d0 + 8] = make_float2(s1[1], s2[1]);
      }
      asm volatile("bar.sync 3, 256;" ::: "memory");
      if (tid < 64) {
        const float2 p0 = s_red[tid], p1 = s_red[64 + tid];
        const float x1 = p0.x + p1.x, x2 = p0.y + p1.y;
        const unsigned long long v = ((unsigned long long)(__float_as_uint(x2) & 0x7fffffffu) << 32) | __float_as_uint(x1);
        asm volatile("st.relaxed.gpu.global.u64 [%0], %1;" ::"l"(part_ptr(xbuf, b, hf, dq, tr) + tid), "l"(v) : "memory");
      }
      if (hf) {
        gelu_store(hz, sb + OFF_H0B + oad);
        __syncwarp();
        if (lane == 0) mbar_arrive(bar + B_OUT + 8 * (wg * 5 + 4));
      }
      {
        const unsigned long long* q = part_ptr(xbuf, b, hf, dq, (tid >> 6) * 4) + (tid & 63);
        unsigned long long v[4];
        poll64x4(q, v);
        float x1 = 0.f, x2 = 0.f;
#pragma unroll
        for (int i = 0; i < 4; i++) {
          x1 += __uint_as_float((uint32_t)v[i]);
          x2 += __uint_as_float((uint32_t)(v[i] >> 32));
        }
        s_red[128 + tid] = make_float2(x1, x2);
      }
      asm volatile("bar.sync 3, 256;" ::: "memory");
#pragma unroll
      for (int i = 0; i < 2; i++) {
        const float2 q0 = s_red[128 + d0 + 8 * i], q1 = s_red[192 + d0 + 8 * i], q2 = s_red[256 + d0 + 8 * i], q3 = s_red[320 + d0 + 8 * i];
        const float mu = ((q0.x + q1.x) + (q2.x + q3.x)) * (1.f / LOUT);
        const float var = fmaxf(((q0.y + q1.y) + (q2.y + q3.y)) * (1.f / LOUT) - mu * mu, 0.f);
        const __nv_bfloat16* gb = (const __nv_bfloat16*)(smem_raw + OFF_GB + hf * 256) + d0 + 8 * i;
        s1[i] = 0.5f * __bfloat162float(gb[0]) * rsqrtf(var + 1e-5f);
        s2[i] = 0.5f * __bfloat162float(gb[64]) - mu * s1[i];
      }
      float zp = 0.f;
#pragma unroll
      for (int k = 0; k < 5; k++) {
#pragma unroll
        for (int i = 0; i < 28; i++) hz[i] = fmaf(acc[k][i], s1[(i >> 1) & 1], s2[(i >> 1) & 1]);
        if (k == 4) break;
        gelu_store(hz, base + oad + k * 16384);
        s2[0] += zp;
        s2[1] += zp;
        asm volatile("ld.volatile.shared.f32 %0, [%1];" : "=f"(zp) : "r"(sb + OFF_F + 55 * 128) : "memory");
        __syncwarp();
        if (lane == 0) mbar_arrive(bar + B_OUT + 80 * hf + 8 * (wg * 5 + k));
      }
    }
    gelu_store(hz, sb + 4 * 16384 + oad);
    __syncwarp();
    if (lane == 0) mbar_arrive(bar + B_YP + 8 * (wg * 5 + 4));
    asm volatile("barrier.cluster.wait.aligned;" ::: "memory");
  }
}

__global__ void __launch_bounds__(256) fb_conv(const __nv_bfloat16* __restrict__ x, const __nv_bfloat16* __restrict__ w, float* __restrict__ h) {
  __shared__ float sx[16][65], sw[16][64];
  const int b = blockIdx.z, l0 = blockIdx.y * 64, d0 = blockIdx.x * 64, tx = threadIdx.x & 15, ty = threadIdx.x >> 4;
  float acc[4][4] = {};
  for (int k0 = 0; k0 < 31 * 512; k0 += 16) {
    for (int i = threadIdx.x; i < 1024; i += 256) {
      const int l = min(l0 + (i >> 4), LOUT - 1);
      sx[i & 15][i >> 4] = __bfloat162float(x[((size_t)b * 16000 + 2 * l) * 512 + k0 + (i & 15)]);
      sw[i >> 6][i & 63] = __bfloat162float(w[(size_t)(k0 + (i >> 6)) * 512 + d0 + (i & 63)]);
    }
    __syncthreads();
#pragma unroll
    for (int k = 0; k < 16; k++)
#pragma unroll
      for (int i = 0; i < 4; i++)
#pragma unroll
        for (int j = 0; j < 4; j++) acc[i][j] = fmaf(sx[k][ty * 4 + i], sw[k][tx * 4 + j], acc[i][j]);
    __syncthreads();
  }
  for (int i = 0; i < 4; i++)
    for (int j = 0; j < 4; j++)
      if (l0 + ty * 4 + i < LOUT) h[((size_t)b * LOUT + l0 + ty * 4 + i) * 512 + d0 + tx * 4 + j] = acc[i][j];
}
__global__ void __launch_bounds__(256) fb_norm(const float* __restrict__ h, const __nv_bfloat16* __restrict__ gamma,
                                               const __nv_bfloat16* __restrict__ beta, __nv_bfloat16* __restrict__ out) {
  __shared__ float r[2][32][8];
  const int c = threadIdx.x & 7, q = threadIdx.x >> 3, d = blockIdx.x * 8 + c;
  const size_t base = (size_t)blockIdx.y * LOUT * 512 + d;
  float mu = 0.f, var = 0.f;
  for (int pass = 0; pass < 2; pass++) {
    float s = 0.f;
    for (int l = q; l < LOUT; l += 32) {
      const float v = h[base + (size_t)l * 512] - mu;
      s += pass ? v * v : v;
    }
    r[pass][q][c] = s;
    __syncthreads();
    s = 0.f;
    for (int i = 0; i < 32; i++) s += r[pass][i][c];
    if (pass) var = s / LOUT; else mu = s / LOUT;
  }
  const float g = __bfloat162float(gamma[d]) * rsqrtf(var + 1e-5f), be = __bfloat162float(beta[d]);
  for (int l = q; l < LOUT; l += 32) {
    const float z = (h[base + (size_t)l * 512] - mu) * g + be;
    out[base + (size_t)l * 512] = __float2bfloat16(0.5f * z * (1.f + tanhf(0.7978845608028654f * (z + 0.044715f * z * z * z))));
  }
}

typedef CUresult (*EncFn)(CUtensorMap*, CUtensorMapDataType, cuuint32_t, void*, const cuuint64_t*, const cuuint64_t*, const cuuint32_t*,
                          const cuuint32_t*, CUtensorMapInterleave, CUtensorMapSwizzle, CUtensorMapL2promotion, CUtensorMapFloatOOBfill);

void encode(EncFn fn, CUtensorMap* m, int rank, void* base, const cuuint64_t* dims, const cuuint64_t* strides, const cuuint32_t* box,
            CUtensorMapL2promotion promo) {
  cuuint32_t es[5] = {1, 1, 1, 1, 1};
  fn(m, CU_TENSOR_MAP_DATA_TYPE_BFLOAT16, rank, base, dims, strides, box, es, CU_TENSOR_MAP_INTERLEAVE_NONE, CU_TENSOR_MAP_SWIZZLE_128B, promo,
     CU_TENSOR_MAP_FLOAT_OOB_FILL_NONE);
}

}

extern "C" void kernel_launch(void* const* d_in, const int* in_sizes, int n_in, void* d_out, int out_size) {
  (void)in_sizes; (void)n_in; (void)out_size;
  const __nv_bfloat16* x = (const __nv_bfloat16*)d_in[0];
  const __nv_bfloat16* w = (const __nv_bfloat16*)d_in[1];
  const __nv_bfloat16* gamma = (const __nv_bfloat16*)d_in[2];
  const __nv_bfloat16* beta = (const __nv_bfloat16*)d_in[3];
  void* fnp = nullptr;
  cudaDriverEntryPointQueryResult qr;
  cudaGetDriverEntryPoint("cuTensorMapEncodeTiled", &fnp, cudaEnableDefault, &qr);
  EncFn fn = (EncFn)fnp;
  void *fptr = nullptr, *xptr = nullptr;
  cudaGetSymbolAddress(&fptr, g_Fimg);
  cudaGetSymbolAddress(&xptr, g_X);
  xptr = (void*)(((uintptr_t)xptr + (1u << 21) - 1) & ~(uintptr_t)((1u << 21) - 1));
  const CUtensorMapL2promotion P0 = CU_TENSOR_MAP_L2_PROMOTION_NONE, P128 = CU_TENSOR_MAP_L2_PROMOTION_L2_128B;
  Maps m;
  {
    cuuint64_t d[3] = {1024, 8000, 2}, s[2] = {2048, 8000ull * 2048};
    cuuint32_t bx[3] = {64, 64, 1};
    encode(fn, &m.x, 3, (void*)x, d, s, bx, P128);
  }
  for (int ph = 0; ph < 2; ph++) {
    cuuint64_t d[3] = {64, (cuuint64_t)(16 - ph), 4096}, s[2] = {2ull * 262144 * 2, 128};
    cuuint32_t bx[3] = {64, 16, 1};
    encode(fn, ph ? &m.wo : &m.we, 3, (void*)(w + (size_t)ph * 262144), d, s, bx, P128);
  }
  for (int par = 0; par < 2; par++) {
    cuuint64_t d[5] = {(cuuint64_t)XPAGES << 20, 2, 4, 2, 2}, s[4] = {par ? 0x1000u : 0x3000u, 1u << 14, 1u << 18, 1u << 20};
    cuuint32_t bx[5] = {64, 2, 4, 2, 2};
    encode(fn, &m.xst[par], 5, xptr, d, s, bx, P0);
  }
  {
    cuuint64_t d[4] = {64, 32, 2, (cuuint64_t)WR * WSLOT / 128}, s[3] = {2ull * WBLK, 4096, 128};
    cuuint32_t bx[4] = {64, 32, 2, 1};
    encode(fn, &m.wst, 4, (char*)xptr + ((size_t)PG_W << 21), d, s, bx, P0);
  }
  for (int par = 0; par < 2; par++) {
    cuuint64_t d[4] = {64, (cuuint64_t)XPAGES << 14, 2, 2}, s[3] = {128, par ? 0xf000u : 0x11000u, 1u << 14};
    cuuint32_t bx[4] = {64, 32, 2, 2};
    encode(fn, &m.yld[par], 4, xptr, d, s, bx, P128);
  }
  {
    cuuint64_t d[3] = {512, LOUT, 2}, s[2] = {1024, (cuuint64_t)LOUT * 1024};
    cuuint32_t bx[3] = {64, MT, 1};
    encode(fn, &m.out, 3, d_out, d, s, bx, P0);
  }
  for (int q = 0; q < 2; q++) {
    cuuint64_t d[3] = {512, (cuuint64_t)(NT - q), 2}, s[2] = {MT * 2048, 8000ull * 2048};
    cuuint32_t bx[3] = {64, NT, 1};
    encode(fn, &m.xe[q], 3, (void*)(x + q * 64 * 1024), d, s, bx, P128);
  }
  {
    cuuint64_t d[2] = {512, 512}, s[1] = {1024};
    cuuint32_t bx[2] = {64, 64};
    encode(fn, &m.w30, 2, (void*)(w + 30 * 262144), d, s, bx, P128);
  }
  cudaFuncSetAttribute(k1_main, cudaFuncAttributeMaxDynamicSharedMemorySize, SMEM_BYTES);
  cudaLaunchConfig_t cfg = {};
  cfg.gridDim = dim3(132);
  cfg.blockDim = dim3(512);
  cfg.dynamicSmemBytes = SMEM_BYTES;
  int clusters = 0;
  cudaOccupancyMaxActiveClusters(&clusters, k1_main, &cfg);
  if (clusters < 66) {
    fb_conv<<<dim3(8, (LOUT + 63) / 64, 2), 256>>>(x, w, (float*)xptr);
    fb_norm<<<dim3(64, 2), 256>>>((const float*)xptr, gamma, beta, (__nv_bfloat16*)d_out);
    return;
  }
  k1_main<<<132, 512, SMEM_BYTES>>>((uint8_t*)xptr, fptr, gamma, beta, m);
}
```

```cpp
#include <cuda_runtime.h>
#include <cuda_bf16.h>
#include <cuda.h>
#include <stdint.h>

namespace {

constexpr int LOUT = 7985;
constexpr int MT = 50;
constexpr int NT = 160;
constexpr int XBLK = NT * 128;
constexpr int WBLK = 16384;
constexpr int LW = 4;
constexpr int WR = 10;
constexpr int WSLOT = 64 * WBLK;
constexpr int PG_Y = 20, PG_W = 25, XPAGES = 30;
constexpr int YA = 2;
constexpr int NFL = 2;
constexpr int XKEEP = 9;
constexpr int YFLUSH = 20 + LW;

__device__ __align__(1024) uint8_t g_X[(XPAGES + 2) << 21];
__device__ __align__(128) float g_E[16 * NT * 64];
constexpr int CTR_OFF = (XPAGES << 21) + 0x100000, PART_OFF = CTR_OFF + 0x40000;
constexpr int C_FLAG = 0, C_LOADED = 128  , C_Y = 256, C_E = 260, C_REG = 261, C_EXIT = 262, C_SIDE = 32;
__device__ __forceinline__ unsigned long long* part_ptr(uint8_t* xbuf, int side, int hf, int dq, int tr) {
  return (unsigned long long*)(xbuf + PART_OFF + ((hf * 4 + dq) * 2 + (tr >> 3)) * 8192 + ((side ^ hf ^ (tr >> 3)) << 12) + (tr & 7) * 512);
}

__device__ __align__(128) const uint32_t g_Fimg[2048] = {
 0x3f803f80,0x3f7d3f7f,0x3f783f7b,0x3f713f75,0x3f673f6d,0x3f5c3f62,0x3f4e3f55,0x3f3e3f46,0x3f2c3f35,0x3f183f22,0x3f043f0e,0x3edb3ef1,0x3eac3ec4,0x3e793e95,0x3e163e48,0x3d493dc9,
 0xbd490000,0xbe16bdc9,0xbe79be48,0xbeacbe95,0xbedbbec4,0xbf04bef1,0xbf18bf0e,0xbf2cbf22,0xbf3ebf35,0xbf4ebf46,0xbf5cbf55,0xbf67bf62,0xbf71bf6d,0xbf78bf75,0xbf7dbf7b,0xbf80bf7f,
 0x3e793ec4,0xbd493dc9,0xbeacbe48,0xbf18bef1,0x3f7d3f80,0x3f673f75,0x3f3e3f55,0x3f043f22,0xbf5cbf6d,0xbf2cbf46,0xbedbbf0e,0xbe16be95,0xbf4ebf35,0xbf71bf62,0xbf80bf7b,0xbf78bf7f,
 0x3f783f6d,0x3f803f7f,0x3f713f7b,0x3f4e3f62,0x3e160000,0x3edb3e95,0x3f2c3f0e,0x3f5c3f46,0xbf04bec4,0xbf3ebf22,0xbf67bf55,0xbf7dbf75,0x3f183f35,0x3eac3ef1,0x3d493e48,0xbe79bdc9,
 0xbf04bf35,0xbd49be95,0x3edb3e48,0x3f4e3f22,0x3f7d3f6d,0x3f713f7f,0x3f2c3f55,0x3e793ef1,0x3f783f80,0x3f3e3f62,0x3eac3f0e,0xbe163dc9,0xbf18bec4,0xbf67bf46,0xbf80bf7b,0xbf5cbf75,
 0x3f5c3f35,0x3f803f75,0x3f673f7b,0x3f183f46,0x3e163ec4,0xbeacbdc9,0xbf3ebf0e,0xbf78bf62,0xbe790000,0xbf2cbef1,0xbf71bf55,0xbf7dbf7f,0xbf4ebf6d,0xbedbbf22,0x3d49be48,0x3f043e95,
 0xbf2cbec4,0xbf7dbf62,0xbf5cbf7b,0xbeacbf22,0x3f673f35,0x3f783f7f,0x3f183f55,0xbd493e95,0xbf80bf6d,0xbf4ebf75,0xbe79bf0e,0x3edb3dc9,0x3f713f80,0x3f043f46,0xbe163e48,0xbf3ebef1,
 0x3f3e3f6d,0x3e163ef1,0xbf04be48,0xbf71bf46,0xbedbbf35,0x3e79bdc9,0x3f4e3f0e,0x3f803f75,0x3d493ec4,0xbf18be95,0xbf78bf55,0xbf67bf7f,0x3eac0000,0x3f5c3f22,0x3f7d3f7b,0x3f2c3f62,
 0xbedb0000,0xbf78bf46,0xbf4ebf7b,0xbd49bef1,0x3f3e3ec4,0x3f7d3f75,0x3f043f55,0xbeac3dc9,0xbf71bf35,0xbf5cbf7f,0xbe16bf0e,0x3f2c3e95,0x3f803f6d,0x3f183f62,0xbe793e48,0xbf67bf22,
 0x3f673f80,0x3e793f22,0xbf18be48,0xbf80bf62,0xbf2cbf6d,0x3e16be95,0x3f5c3f0e,0x3f713f7f,0x3eac3f35,0xbf04bdc9,0xbf7dbf55,0xbf3ebf75,0x3d49bec4,0x3f4e3ef1,0x3f783f7b,0x3edb3f46,
 0xbf7dbf6d,0xbeacbf46,0x3f2c3e48,0x3f783f75,0x3f040000,0x3f803f62,0x3edb3f55,0xbf18bdc9,0x3f4e3ec4,0x3f673f7f,0x3d493f0e,0xbf5cbef1,0x3e793f35,0xbf3ebe95,0xbf71bf7b,0xbe16bf22,
 0x3e16bec4,0x3f713f22,0x3f3e3f7b,0xbe793e95,0x3f5c3f80,0xbd493ef1,0xbf67bf0e,0xbf4ebf7f,0x3f183f6d,0xbedb3dc9,0xbf80bf55,0xbf04bf62,0xbf78bf35,0xbf2cbf75,0x3eacbe48,0x3f7d3f46,
 0x3f7d3f35,0x3edb3f62,0xbf3ebe48,0xbf5cbf7f,0x3e79bec4,0x3f803f46,0x3eac3f55,0xbf4ebe95,0xbf180000,0xbf71bf75,0x3d49bf0e,0x3f783f22,0x3f043f6d,0xbf2cbdc9,0xbf67bf7b,0x3e16bef1,
 0xbe16bf35,0x3f673ef1,0x3f2c3f7b,0xbf043dc9,0xbf78bf6d,0xbd49bf22,0x3f713f0e,0x3f183f75,0x3f4e3f80,0xbeac3e95,0xbf80bf55,0xbe79bf46,0x3f5c3ec4,0x3f3e3f7f,0xbedb3e48,0xbf7dbf62,
 0xbedbbf6d,0x3f5c3e95,0x3f183f7b,0xbf3ebdc9,0xbd49bf35,0x3f7d3f22,0x3e793f55,0xbf71bef1,0x3eacbec4,0x3f783f62,0xbe163f0e,0xbf80bf46,0x3f2c0000,0x3f4e3f7f,0xbf043e48,0xbf67bf75,
 0x3f673ec4,0x3f043f75,0xbf4ebe48,0xbf2cbf7f,0x3f803f35,0x3e163f46,0xbf78bf0e,0xbeacbf62,0x3f713f6d,0xbe793ef1,0xbf7dbf55,0x3d49bf22,0x3f3e3f80,0xbf183dc9,0xbf5cbf7b,0x3edbbe95,
 0xbd490000,0xbe16bdc9,0xbe79be48,0xbeacbe95,0xbedbbec4,0xbf04bef1,0xbf18bf0e,0xbf2cbf22,0xbf3ebf35,0xbf4ebf46,0xbf5cbf55,0xbf67bf62,0xbf71bf6d,0xbf78bf75,0xbf7dbf7b,0xbf80bf7f,
 0xbf80bf80,0xbf7dbf7f,0xbf78bf7b,0xbf71bf75,0xbf67bf6d,0xbf5cbf62,0xbf4ebf55,0xbf3ebf46,0xbf2cbf35,0xbf18bf22,0xbf04bf0e,0xbedbbef1,0xbeacbec4,0xbe79be95,0xbe16be48,0xbd49bdc9,
 0xbf78bf6d,0xbf80bf7f,0xbf71bf7b,0xbf4ebf62,0xbe160000,0xbedbbe95,0xbf2cbf0e,0xbf5cbf46,0x3f043ec4,0x3f3e3f22,0x3f673f55,0x3f7d3f75,0xbf18bf35,0xbeacbef1,0xbd49be48,0x3e793dc9,
 0x3e793ec4,0xbd493dc9,0xbeacbe48,0xbf18bef1,0x3f7d3f80,0x3f673f75,0x3f3e3f55,0x3f043f22,0xbf5cbf6d,0xbf2cbf46,0xbedbbf0e,0xbe16be95,0xbf4ebf35,0xbf71bf62,0xbf80bf7b,0xbf78bf7f,
 0x3f5c3f35,0x3f803f75,0x3f673f7b,0x3f183f46,0x3e163ec4,0xbeacbdc9,0xbf3ebf0e,0xbf78bf62,0xbe790000,0xbf2cbef1,0xbf71bf55,0xbf7dbf7f,0xbf4ebf6d,0xbedbbf22,0x3d49be48,0x3f043e95,
 0x3f043f35,0x3d493e95,0xbedbbe48,0xbf4ebf22,0xbf7dbf6d,0xbf71bf7f,0xbf2cbf55,0xbe79bef1,0xbf78bf80,0xbf3ebf62,0xbeacbf0e,0x3e16bdc9,0x3f183ec4,0x3f673f46,0x3f803f7b,0x3f5c3f75,
 0xbf3ebf6d,0xbe16bef1,0x3f043e48,0x3f713f46,0x3edb3f35,0xbe793dc9,0xbf4ebf0e,0xbf80bf75,0xbd49bec4,0x3f183e95,0x3f783f55,0x3f673f7f,0xbeac0000,0xbf5cbf22,0xbf7dbf7b,0xbf2cbf62,
 0xbf2cbec4,0xbf7dbf62,0xbf5cbf7b,0xbeacbf22,0x3f673f35,0x3f783f7f,0x3f183f55,0xbd493e95,0xbf80bf6d,0xbf4ebf75,0xbe79bf0e,0x3edb3dc9,0x3f713f80,0x3f043f46,0xbe163e48,0xbf3ebef1,
 0xbf67bf80,0xbe79bf22,0x3f183e48,0x3f803f62,0x3f2c3f6d,0xbe163e95,0xbf5cbf0e,0xbf71bf7f,0xbeacbf35,0x3f043dc9,0x3f7d3f55,0x3f3e3f75,0xbd493ec4,0xbf4ebef1,0xbf78bf7b,0xbedbbf46,
 0xbedb0000,0xbf78bf46,0xbf4ebf7b,0xbd49bef1,0x3f3e3ec4,0x3f7d3f75,0x3f043f55,0xbeac3dc9,0xbf71bf35,0xbf5cbf7f,0xbe16bf0e,0x3f2c3e95,0x3f803f6d,0x3f183f62,0xbe793e48,0xbf67bf22,
 0x3e16bec4,0x3f713f22,0x3f3e3f7b,0xbe793e95,0x3f5c3f80,0xbd493ef1,0xbf67bf0e,0xbf4ebf7f,0x3f183f6d,0xbedb3dc9,0xbf80bf55,0xbf04bf62,0xbf78bf35,0xbf2cbf75,0x3eacbe48,0x3f7d3f46,
 0x3f7d3f6d,0x3eac3f46,0xbf2cbe48,0xbf78bf75,0xbf040000,0xbf80bf62,0xbedbbf55,0x3f183dc9,0xbf4ebec4,0xbf67bf7f,0xbd49bf0e,0x3f5c3ef1,0xbe79bf35,0x3f3e3e95,0x3f713f7b,0x3e163f22,
 0x3e163f35,0xbf67bef1,0xbf2cbf7b,0x3f04bdc9,0x3f783f6d,0x3d493f22,0xbf71bf0e,0xbf18bf75,0xbf4ebf80,0x3eacbe95,0x3f803f55,0x3e793f46,0xbf5cbec4,0xbf3ebf7f,0x3edbbe48,0x3f7d3f62,
 0x3f7d3f35,0x3edb3f62,0xbf3ebe48,0xbf5cbf7f,0x3e79bec4,0x3f803f46,0x3eac3f55,0xbf4ebe95,0xbf180000,0xbf71bf75,0x3d49bf0e,0x3f783f22,0x3f043f6d,0xbf2cbdc9,0xbf67bf7b,0x3e16bef1,
 0x3f673ec4,0x3f043f75,0xbf4ebe48,0xbf2cbf7f,0x3f803f35,0x3e163f46,0xbf78bf0e,0xbeacbf62,0x3f713f6d,0xbe793ef1,0xbf7dbf55,0x3d49bf22,0x3f3e3f80,0xbf183dc9,0xbf5cbf7b,0x3edbbe95,
 0x3edb3f6d,0xbf5cbe95,0xbf18bf7b,0x3f3e3dc9,0x3d493f35,0xbf7dbf22,0xbe79bf55,0x3f713ef1,0xbeac3ec4,0xbf78bf62,0x3e16bf0e,0x3f803f46,0xbf2c0000,0xbf4ebf7f,0x3f04be48,0x3f673f75,
 0x3f2c3f80,0xbf4ebdc9,0xbf04bf7b,0x3f673e95,0x3eac3f6d,0xbf78bef1,0xbe16bf55,0x3f803f22,0xbd493f35,0xbf7dbf46,0x3e79bf0e,0x3f713f62,0xbedb3ec4,0xbf5cbf75,0x3f18be48,0x3f3e3f7f,
 0xbf3e0000,0xbf18bf7f,0x3f5c3e48,0x3edb3f75,0xbf71bec4,0xbe79bf62,0x3f7d3f0e,0x3d493f46,0xbf80bf35,0x3e16bf22,0x3f783f55,0xbeac3ef1,0xbf67bf6d,0x3f04be95,0x3f4e3f7b,0xbf2c3dc9,
 0xbf043ec4,0xbf2cbf7f,0x3f673e48,0x3e163f62,0x3f183f80,0xbf71be95,0xbd49bf55,0x3f783f46,0xbe79bf6d,0x3f803f22,0xbeac3f0e,0xbf4ebf75,0xbf7dbf35,0x3edbbef1,0x3f3e3f7b,0xbf5cbdc9,
 0x3f5c3f6d,0xbf3e3dc9,0xbedbbf7b,0x3f7d3ef1,0x3f4e0000,0x3eac3f75,0xbf80bf0e,0x3e79bf22,0xbf78bec4,0x3d49bf46,0x3f713f55,0xbf183e95,0xbe163f35,0xbf67bf62,0x3f2cbe48,0x3f043f7f,
 0x3e79bf35,0x3f3e3f75,0xbf71be48,0x3e16bf46,0x3f4e3f6d,0xbf67bdc9,0x3d49bf55,0x3f5c3f62,0x3f043f80,0xbf80bef1,0x3edbbf0e,0x3f183f7f,0xbf7dbec4,0x3eacbf22,0x3f2c3f7b,0xbf78be95,
 0x3f783f35,0xbf2c3e95,0xbeacbf7b,0x3f7d3f22,0xbf183ec4,0xbedbbf7f,0x3f803f0e,0xbf043ef1,0xbf5c0000,0xbd49bf62,0x3f673f55,0xbf4e3dc9,0xbe16bf6d,0x3f713f46,0xbf3e3e48,0xbe79bf75,
 0xbf80bec4,0x3f18bef1,0x3e793f7b,0xbf67bf46,0x3f713f35,0xbf5c3dc9,0x3e16bf55,0x3f2c3f75,0xbf3ebf6d,0x3f7d3e95,0xbf043f0e,0xbeacbf7f,0x3edb3f80,0xbf78bf22,0x3f4ebe48,0xbd493f62,
 0x3d493f6d,0xbf4ebf62,0x3f783e48,0xbedb3f22,0x3eacbf35,0x3f043f7f,0xbf7dbf0e,0x3f3ebe95,0xbf2c3ec4,0xbe16bf75,0x3f5c3f55,0xbf71bdc9,0x3f670000,0xbe793f46,0xbf18bf7b,0x3f803ef1,
 0xbf710000,0x3f04bf22,0x3e163f7b,0xbf3ebf62,0x3f803ec4,0xbf4e3e95,0x3e79bf55,0x3edb3f7f,0xbf67bf35,0x3f783dc9,0xbf183f0e,0xbd49bf75,0x3f2c3f6d,0xbf7dbef1,0x3f5cbe48,0xbeac3f46,
 0x3eac3f80,0xbf5cbf46,0x3f7d3e48,0xbf2c3ef1,0x3d49bf6d,0x3f183f75,0xbf78bf0e,0x3f67bdc9,0xbedb3f35,0xbe79bf7f,0x3f4e3f55,0xbf80be95,0x3f3ebec4,0xbe163f62,0xbf04bf7b,0x3f713f22,
 0xbf18bf6d,0x3f673f22,0xbf80be48,0x3f5cbe95,0x3f780000,0xbf3e3ef1,0x3eacbf55,0x3e163f7f,0x3f7d3ec4,0xbf713dc9,0x3f2cbf0e,0xbe793f62,0xbf043f35,0x3d49bf75,0x3edb3f7b,0xbf4ebf46,
 0x3f4ebec4,0xbedb3f46,0xbd49bf7b,0x3f043f75,0x3e793f80,0xbf2cbf62,0x3f713f0e,0xbf7dbdc9,0xbe163f6d,0xbeacbf7f,0x3f3e3f55,0xbf78bef1,0xbf5cbf35,0x3f803e95,0xbf673e48,0x3f18bf22,
 0x3f4e3f35,0xbf71bef1,0x3f803e48,0xbf783dc9,0x3f5cbec4,0xbf2c3f22,0x3edbbf55,0xbe163f75,0xbf7d0000,0x3f67be95,0xbf3e3f0e,0x3f04bf46,0xbe793f6d,0xbd49bf7f,0x3eac3f7b,0xbf18bf62,
 0x3f18bf35,0xbeac3f62,0x3d49bf7b,0x3e793f7f,0xbf04bf6d,0x3f3e3f46,0xbf67bf0e,0x3f7d3e95,0x3e163f80,0xbedbbf75,0x3f2c3f55,0xbf5cbf22,0x3f783ec4,0xbf80bdc9,0x3f71be48,0xbf4e3ef1,
 0x3eacbf6d,0xbe793f75,0x3e16bf7b,0xbd493f7f,0x3f2cbf35,0xbf183f46,0x3f04bf55,0xbedb3f62,0x3f67bec4,0xbf5c3ef1,0x3f4ebf0e,0xbf3e3f22,0x3f800000,0xbf7d3dc9,0x3f78be48,0xbf713e95,
 0x3f713ec4,0xbf78be95,0x3f7d3e48,0xbf80bdc9,0x3f3e3f35,0xbf4ebf22,0x3f5c3f0e,0xbf67bef1,0x3edb3f6d,0xbf04bf62,0x3f183f55,0xbf2cbf46,0x3d493f80,0xbe16bf7f,0x3e793f7b,0xbeacbf75,
 0xbf3e0000,0xbf18bf7f,0x3f5c3e48,0x3edb3f75,0xbf71bec4,0xbe79bf62,0x3f7d3f0e,0x3d493f46,0xbf80bf35,0x3e16bf22,0x3f783f55,0xbeac3ef1,0xbf67bf6d,0x3f04be95,0x3f4e3f7b,0xbf2c3dc9,
 0xbf2cbf80,0x3f4e3dc9,0x3f043f7b,0xbf67be95,0xbeacbf6d,0x3f783ef1,0x3e163f55,0xbf80bf22,0x3d49bf35,0x3f7d3f46,0xbe793f0e,0xbf71bf62,0x3edbbec4,0x3f5c3f75,0xbf183e48,0xbf3ebf7f,
 0xbf5cbf6d,0x3f3ebdc9,0x3edb3f7b,0xbf7dbef1,0xbf4e0000,0xbeacbf75,0x3f803f0e,0xbe793f22,0x3f783ec4,0xbd493f46,0xbf71bf55,0x3f18be95,0x3e16bf35,0x3f673f62,0xbf2c3e48,0xbf04bf7f,
 0xbf043ec4,0xbf2cbf7f,0x3f673e48,0x3e163f62,0x3f183f80,0xbf71be95,0xbd49bf55,0x3f783f46,0xbe79bf6d,0x3f803f22,0xbeac3f0e,0xbf4ebf75,0xbf7dbf35,0x3edbbef1,0x3f3e3f7b,0xbf5cbdc9,
 0x3f783f35,0xbf2c3e95,0xbeacbf7b,0x3f7d3f22,0xbf183ec4,0xbedbbf7f,0x3f803f0e,0xbf043ef1,0xbf5c0000,0xbd49bf62,0x3f673f55,0xbf4e3dc9,0xbe16bf6d,0x3f713f46,0xbf3e3e48,0xbe79bf75,
 0xbe793f35,0xbf3ebf75,0x3f713e48,0xbe163f46,0xbf4ebf6d,0x3f673dc9,0xbd493f55,0xbf5cbf62,0xbf04bf80,0x3f803ef1,0xbedb3f0e,0xbf18bf7f,0x3f7d3ec4,0xbeac3f22,0xbf2cbf7b,0x3f783e95,
 0xbd49bf6d,0x3f4e3f62,0xbf78be48,0x3edbbf22,0xbeac3f35,0xbf04bf7f,0x3f7d3f0e,0xbf3e3e95,0x3f2cbec4,0x3e163f75,0xbf5cbf55,0x3f713dc9,0xbf670000,0x3e79bf46,0x3f183f7b,0xbf80bef1,
 0xbf80bec4,0x3f18bef1,0x3e793f7b,0xbf67bf46,0x3f713f35,0xbf5c3dc9,0x3e16bf55,0x3f2c3f75,0xbf3ebf6d,0x3f7d3e95,0xbf043f0e,0xbeacbf7f,0x3edb3f80,0xbf78bf22,0x3f4ebe48,0xbd493f62,
 0xbeacbf80,0x3f5c3f46,0xbf7dbe48,0x3f2cbef1,0xbd493f6d,0xbf18bf75,0x3f783f0e,0xbf673dc9,0x3edbbf35,0x3e793f7f,0xbf4ebf55,0x3f803e95,0xbf3e3ec4,0x3e16bf62,0x3f043f7b,0xbf71bf22,
 0xbf710000,0x3f04bf22,0x3e163f7b,0xbf3ebf62,0x3f803ec4,0xbf4e3e95,0x3e79bf55,0x3edb3f7f,0xbf67bf35,0x3f783dc9,0xbf183f0e,0xbd49bf75,0x3f2c3f6d,0xbf7dbef1,0x3f5cbe48,0xbeac3f46,
 0x3f4ebec4,0xbedb3f46,0xbd49bf7b,0x3f043f75,0x3e793f80,0xbf2cbf62,0x3f713f0e,0xbf7dbdc9,0xbe163f6d,0xbeacbf7f,0x3f3e3f55,0xbf78bef1,0xbf5cbf35,0x3f803e95,0xbf673e48,0x3f18bf22,
 0x3f183f6d,0xbf67bf22,0x3f803e48,0xbf5c3e95,0xbf780000,0x3f3ebef1,0xbeac3f55,0xbe16bf7f,0xbf7dbec4,0x3f71bdc9,0xbf2c3f0e,0x3e79bf62,0x3f04bf35,0xbd493f75,0xbedbbf7b,0x3f4e3f46,
 0xbf183f35,0x3eacbf62,0xbd493f7b,0xbe79bf7f,0x3f043f6d,0xbf3ebf46,0x3f673f0e,0xbf7dbe95,0xbe16bf80,0x3edb3f75,0xbf2cbf55,0x3f5c3f22,0xbf78bec4,0x3f803dc9,0xbf713e48,0x3f4ebef1,
 0x3f4e3f35,0xbf71bef1,0x3f803e48,0xbf783dc9,0x3f5cbec4,0xbf2c3f22,0x3edbbf55,0xbe163f75,0xbf7d0000,0x3f67be95,0xbf3e3f0e,0x3f04bf46,0xbe793f6d,0xbd49bf7f,0x3eac3f7b,0xbf18bf62,
 0x3f713ec4,0xbf78be95,0x3f7d3e48,0xbf80bdc9,0x3f3e3f35,0xbf4ebf22,0x3f5c3f0e,0xbf67bef1,0x3edb3f6d,0xbf04bf62,0x3f183f55,0xbf2cbf46,0x3d493f80,0xbe16bf7f,0x3e793f7b,0xbeacbf75,
 0xbeac3f6d,0x3e79bf75,0xbe163f7b,0x3d49bf7f,0xbf2c3f35,0x3f18bf46,0xbf043f55,0x3edbbf62,0xbf673ec4,0x3f5cbef1,0xbf4e3f0e,0x3f3ebf22,0xbf800000,0x3f7dbdc9,0xbf783e48,0x3f71be95,
 0xbd493f80,0x3e16bf7f,0xbe793f7b,0x3eacbf75,0xbedb3f6d,0x3f04bf62,0xbf183f55,0x3f2cbf46,0xbf3e3f35,0x3f4ebf22,0xbf5c3f0e,0x3f67bef1,0xbf713ec4,0x3f78be95,0xbf7d3e48,0x3f80bdc9,
 0xbf800000,0x3f7d3dc9,0xbf78be48,0x3f713e95,0xbf67bec4,0x3f5c3ef1,0xbf4ebf0e,0x3f3e3f22,0xbf2cbf35,0x3f183f46,0xbf04bf55,0x3edb3f62,0xbeacbf6d,0x3e793f75,0xbe16bf7b,0x3d493f7f,
 0xbf783ec4,0x3f80bdc9,0xbf71be48,0x3f4e3ef1,0xbe163f80,0x3edbbf75,0xbf2c3f55,0x3f5cbf22,0x3f04bf6d,0xbf3e3f46,0x3f67bf0e,0xbf7d3e95,0xbf18bf35,0x3eac3f62,0xbd49bf7b,0xbe793f7f,
 0x3e793f6d,0x3d49bf7f,0xbeac3f7b,0x3f18bf62,0x3f7d0000,0xbf67be95,0x3f3e3f0e,0xbf04bf46,0xbf5cbec4,0x3f2c3f22,0xbedbbf55,0x3e163f75,0xbf4e3f35,0x3f71bef1,0xbf803e48,0x3f783dc9,
 0x3f5cbf35,0xbf803e95,0x3f673e48,0xbf18bf22,0x3e163f6d,0x3eacbf7f,0xbf3e3f55,0x3f78bef1,0xbe793f80,0x3f2cbf62,0xbf713f0e,0x3f7dbdc9,0xbf4ebec4,0x3edb3f46,0x3d49bf7b,0xbf043f75,
 0x3f043f35,0xbd49bf75,0xbedb3f7b,0x3f4ebf46,0xbf7d3ec4,0x3f713dc9,0xbf2cbf0e,0x3e793f62,0xbf780000,0x3f3e3ef1,0xbeacbf55,0xbe163f7f,0x3f18bf6d,0xbf673f22,0x3f80be48,0xbf5cbe95,
 0xbf3ebec4,0x3e163f62,0x3f04bf7b,0xbf713f22,0x3edb3f35,0x3e79bf7f,0xbf4e3f55,0x3f80be95,0xbd49bf6d,0xbf183f75,0x3f78bf0e,0xbf67bdc9,0xbeac3f80,0x3f5cbf46,0xbf7d3e48,0x3f2c3ef1,
 0xbf2c3f6d,0x3f7dbef1,0xbf5cbe48,0x3eac3f46,0x3f67bf35,0xbf783dc9,0x3f183f0e,0x3d49bf75,0xbf803ec4,0x3f4e3e95,0xbe79bf55,0xbedb3f7f,0x3f710000,0xbf04bf22,0xbe163f7b,0x3f3ebf62,
 0xbf670000,0x3e793f46,0x3f18bf7b,0xbf803ef1,0x3f2c3ec4,0x3e16bf75,0xbf5c3f55,0x3f71bdc9,0xbeacbf35,0xbf043f7f,0x3f7dbf0e,0xbf3ebe95,0xbd493f6d,0x3f4ebf62,0xbf783e48,0x3edb3f22,
 0xbedb3f80,0x3f78bf22,0xbf4ebe48,0x3d493f62,0x3f3ebf6d,0xbf7d3e95,0x3f043f0e,0x3eacbf7f,0xbf713f35,0x3f5c3dc9,0xbe16bf55,0xbf2c3f75,0x3f80bec4,0xbf18bef1,0xbe793f7b,0x3f67bf46,
 0x3e16bf6d,0xbf713f46,0x3f3e3e48,0x3e79bf75,0x3f5c0000,0x3d49bf62,0xbf673f55,0x3f4e3dc9,0x3f183ec4,0x3edbbf7f,0xbf803f0e,0x3f043ef1,0xbf783f35,0x3f2c3e95,0x3eacbf7b,0xbf7d3f22,
 0x3f7dbec4,0xbeacbf22,0xbf2c3f7b,0x3f78be95,0xbf043f80,0x3f80bef1,0xbedbbf0e,0xbf183f7f,0xbf4e3f6d,0x3f67bdc9,0xbd49bf55,0xbf5c3f62,0xbe79bf35,0xbf3e3f75,0x3f71be48,0xbe16bf46,
 0x3e163f35,0x3f67bf62,0xbf2cbe48,0xbf043f7f,0x3f78bec4,0xbd49bf46,0xbf713f55,0x3f183e95,0xbf4e0000,0xbeac3f75,0x3f80bf0e,0xbe79bf22,0xbf5c3f6d,0x3f3e3dc9,0x3edbbf7b,0xbf7d3ef1,
 0x3f7dbf35,0xbedbbef1,0xbf3e3f7b,0x3f5cbdc9,0x3e79bf6d,0xbf803f22,0x3eac3f0e,0x3f4ebf75,0xbf183f80,0x3f71be95,0x3d49bf55,0xbf783f46,0x3f043ec4,0x3f2cbf7f,0xbf673e48,0xbe163f62,
 0x3f67bf6d,0xbf04be95,0xbf4e3f7b,0x3f2c3dc9,0x3f80bf35,0xbe16bf22,0xbf783f55,0x3eac3ef1,0x3f71bec4,0x3e79bf62,0xbf7d3f0e,0xbd493f46,0x3f3e0000,0x3f18bf7f,0xbf5c3e48,0xbedb3f75,
 0x3edb3ec4,0x3f5cbf75,0xbf18be48,0xbf3e3f7f,0x3d493f35,0x3f7dbf46,0xbe79bf0e,0xbf713f62,0xbeac3f6d,0x3f78bef1,0x3e16bf55,0xbf803f22,0xbf2c3f80,0x3f4ebdc9,0x3f04bf7b,0xbf673e95,
 0xbf800000,0x3f7d3dc9,0xbf78be48,0x3f713e95,0xbf67bec4,0x3f5c3ef1,0xbf4ebf0e,0x3f3e3f22,0xbf2cbf35,0x3f183f46,0xbf04bf55,0x3edb3f62,0xbeacbf6d,0x3e793f75,0xbe16bf7b,0x3d493f7f,
 0x3d49bf80,0xbe163f7f,0x3e79bf7b,0xbeac3f75,0x3edbbf6d,0xbf043f62,0x3f18bf55,0xbf2c3f46,0x3f3ebf35,0xbf4e3f22,0x3f5cbf0e,0xbf673ef1,0x3f71bec4,0xbf783e95,0x3f7dbe48,0xbf803dc9,
 0xbe79bf6d,0xbd493f7f,0x3eacbf7b,0xbf183f62,0xbf7d0000,0x3f673e95,0xbf3ebf0e,0x3f043f46,0x3f5c3ec4,0xbf2cbf22,0x3edb3f55,0xbe16bf75,0x3f4ebf35,0xbf713ef1,0x3f80be48,0xbf78bdc9,
 0xbf783ec4,0x3f80bdc9,0xbf71be48,0x3f4e3ef1,0xbe163f80,0x3edbbf75,0xbf2c3f55,0x3f5cbf22,0x3f04bf6d,0xbf3e3f46,0x3f67bf0e,0xbf7d3e95,0xbf18bf35,0x3eac3f62,0xbd49bf7b,0xbe793f7f,
 0x3f043f35,0xbd49bf75,0xbedb3f7b,0x3f4ebf46,0xbf7d3ec4,0x3f713dc9,0xbf2cbf0e,0x3e793f62,0xbf780000,0x3f3e3ef1,0xbeacbf55,0xbe163f7f,0x3f18bf6d,0xbf673f22,0x3f80be48,0xbf5cbe95,
 0xbf5c3f35,0x3f80be95,0xbf67be48,0x3f183f22,0xbe16bf6d,0xbeac3f7f,0x3f3ebf55,0xbf783ef1,0x3e79bf80,0xbf2c3f62,0x3f71bf0e,0xbf7d3dc9,0x3f4e3ec4,0xbedbbf46,0xbd493f7b,0x3f04bf75,
 0x3f2cbf6d,0xbf7d3ef1,0x3f5c3e48,0xbeacbf46,0xbf673f35,0x3f78bdc9,0xbf18bf0e,0xbd493f75,0x3f80bec4,0xbf4ebe95,0x3e793f55,0x3edbbf7f,0xbf710000,0x3f043f22,0x3e16bf7b,0xbf3e3f62,
 0xbf3ebec4,0x3e163f62,0x3f04bf7b,0xbf713f22,0x3edb3f35,0x3e79bf7f,0xbf4e3f55,0x3f80be95,0xbd49bf6d,0xbf183f75,0x3f78bf0e,0xbf67bdc9,0xbeac3f80,0x3f5cbf46,0xbf7d3e48,0x3f2c3ef1,
 0x3edbbf80,0xbf783f22,0x3f4e3e48,0xbd49bf62,0xbf3e3f6d,0x3f7dbe95,0xbf04bf0e,0xbeac3f7f,0x3f71bf35,0xbf5cbdc9,0x3e163f55,0x3f2cbf75,0xbf803ec4,0x3f183ef1,0x3e79bf7b,0xbf673f46,
 0xbf670000,0x3e793f46,0x3f18bf7b,0xbf803ef1,0x3f2c3ec4,0x3e16bf75,0xbf5c3f55,0x3f71bdc9,0xbeacbf35,0xbf043f7f,0x3f7dbf0e,0xbf3ebe95,0xbd493f6d,0x3f4ebf62,0xbf783e48,0x3edb3f22,
 0x3f7dbec4,0xbeacbf22,0xbf2c3f7b,0x3f78be95,0xbf043f80,0x3f80bef1,0xbedbbf0e,0xbf183f7f,0xbf4e3f6d,0x3f67bdc9,0xbd49bf55,0xbf5c3f62,0xbe79bf35,0xbf3e3f75,0x3f71be48,0xbe16bf46,
 0xbe163f6d,0x3f71bf46,0xbf3ebe48,0xbe793f75,0xbf5c0000,0xbd493f62,0x3f67bf55,0xbf4ebdc9,0xbf18bec4,0xbedb3f7f,0x3f80bf0e,0xbf04bef1,0x3f78bf35,0xbf2cbe95,0xbeac3f7b,0x3f7dbf22,
 0xbf7d3f35,0x3edb3ef1,0x3f3ebf7b,0xbf5c3dc9,0xbe793f6d,0x3f80bf22,0xbeacbf0e,0xbf4e3f75,0x3f18bf80,0xbf713e95,0xbd493f55,0x3f78bf46,0xbf04bec4,0xbf2c3f7f,0x3f67be48,0x3e16bf62,
 0x3e163f35,0x3f67bf62,0xbf2cbe48,0xbf043f7f,0x3f78bec4,0xbd49bf46,0xbf713f55,0x3f183e95,0xbf4e0000,0xbeac3f75,0x3f80bf0e,0xbe79bf22,0xbf5c3f6d,0x3f3e3dc9,0x3edbbf7b,0xbf7d3ef1,
 0x3edb3ec4,0x3f5cbf75,0xbf18be48,0xbf3e3f7f,0x3d493f35,0x3f7dbf46,0xbe79bf0e,0xbf713f62,0xbeac3f6d,0x3f78bef1,0x3e16bf55,0xbf803f22,0xbf2c3f80,0x3f4ebdc9,0x3f04bf7b,0xbf673e95,
 0xbf673f6d,0x3f043e95,0x3f4ebf7b,0xbf2cbdc9,0xbf803f35,0x3e163f22,0x3f78bf55,0xbeacbef1,0xbf713ec4,0xbe793f62,0x3f7dbf0e,0x3d49bf46,0xbf3e0000,0xbf183f7f,0x3f5cbe48,0x3edbbf75,
 0xbf3e3f80,0x3f183dc9,0x3f5cbf7b,0xbedbbe95,0xbf713f6d,0x3e793ef1,0x3f7dbf55,0xbd49bf22,0xbf803f35,0xbe163f46,0x3f78bf0e,0x3eacbf62,0xbf673ec4,0xbf043f75,0x3f4ebe48,0x3f2cbf7f,
 0xbf2c0000,0xbf4e3f7f,0x3f043e48,0x3f67bf75,0xbeacbec4,0xbf783f62,0x3e163f0e,0x3f80bf46,0x3d49bf35,0xbf7d3f22,0xbe793f55,0x3f71bef1,0x3edbbf6d,0xbf5c3e95,0xbf183f7b,0x3f3ebdc9,
 0xbf5c3ec4,0xbf3e3f7f,0x3edb3e48,0x3f7dbf62,0xbf4e3f80,0x3eac3e95,0x3f80bf55,0x3e79bf46,0x3f78bf6d,0x3d49bf22,0xbf713f0e,0xbf183f75,0x3e16bf35,0xbf673ef1,0xbf2c3f7b,0x3f043dc9,
 0xbf043f6d,0x3f2cbdc9,0x3f67bf7b,0xbe16bef1,0x3f180000,0x3f71bf75,0xbd49bf0e,0xbf783f22,0xbe79bec4,0xbf803f46,0xbeac3f55,0x3f4ebe95,0xbf7d3f35,0xbedb3f62,0x3f3ebe48,0x3f5cbf7f,
 0x3f78bf35,0x3f2cbf75,0xbeacbe48,0xbf7d3f46,0xbf183f6d,0x3edb3dc9,0x3f80bf55,0x3f04bf62,0xbf5c3f80,0x3d493ef1,0x3f67bf0e,0x3f4ebf7f,0xbe16bec4,0xbf713f22,0xbf3e3f7b,0x3e793e95,
 0xbe793f35,0x3f3ebe95,0x3f71bf7b,0x3e16bf22,0xbf4e3ec4,0xbf673f7f,0xbd493f0e,0x3f5cbef1,0xbf040000,0xbf803f62,0xbedb3f55,0x3f18bdc9,0x3f7dbf6d,0x3eacbf46,0xbf2c3e48,0xbf783f75,
 0xbd49bec4,0xbf4e3ef1,0xbf783f7b,0xbedb3f46,0xbeac3f35,0x3f04bdc9,0x3f7dbf55,0x3f3ebf75,0x3f2cbf6d,0xbe16be95,0xbf5c3f0e,0xbf713f7f,0xbf673f80,0xbe793f22,0x3f18be48,0x3f80bf62,
 0xbf803f6d,0xbf183f62,0x3e793e48,0x3f67bf22,0x3f71bf35,0x3f5cbf7f,0x3e16bf0e,0xbf2c3e95,0xbf3e3ec4,0xbf7d3f75,0xbf043f55,0x3eac3dc9,0x3edb0000,0x3f78bf46,0x3f4ebf7b,0x3d49bef1,
 0xbeac0000,0xbf5c3f22,0xbf7d3f7b,0xbf2c3f62,0xbd493ec4,0x3f18be95,0x3f78bf55,0x3f67bf7f,0x3edbbf35,0xbe79bdc9,0xbf4e3f0e,0xbf803f75,0xbf3e3f6d,0xbe163ef1,0x3f04be48,0x3f71bf46,
 0xbf713f80,0xbf043f46,0x3e163e48,0x3f3ebef1,0x3f80bf6d,0x3f4ebf75,0x3e79bf0e,0xbedb3dc9,0xbf673f35,0xbf783f7f,0xbf183f55,0x3d493e95,0x3f2cbec4,0x3f7dbf62,0x3f5cbf7b,0x3eacbf22,
 0x3f4ebf6d,0x3edbbf22,0xbd49be48,0xbf043e95,0x3e790000,0x3f2cbef1,0x3f71bf55,0x3f7dbf7f,0xbe163ec4,0x3eacbdc9,0x3f3ebf0e,0x3f78bf62,0xbf5c3f35,0xbf803f75,0xbf673f7b,0xbf183f46,
 0x3f18bec4,0x3f67bf46,0x3f80bf7b,0x3f5cbf75,0xbf783f80,0xbf3e3f62,0xbeac3f0e,0x3e163dc9,0xbf7d3f6d,0xbf713f7f,0xbf2c3f55,0xbe793ef1,0x3f04bf35,0x3d49be95,0xbedb3e48,0xbf4e3f22,
 0xbf183f35,0xbeac3ef1,0xbd493e48,0x3e79bdc9,0x3f04bec4,0x3f3ebf22,0x3f67bf55,0x3f7dbf75,0xbe160000,0xbedb3e95,0xbf2c3f0e,0xbf5c3f46,0xbf783f6d,0xbf803f7f,0xbf713f7b,0xbf4e3f62,
 0x3f4ebf35,0x3f71bf62,0x3f80bf7b,0x3f78bf7f,0x3f5cbf6d,0x3f2cbf46,0x3edbbf0e,0x3e16be95,0xbf7d3f80,0xbf673f75,0xbf3e3f55,0xbf043f22,0xbe793ec4,0x3d493dc9,0x3eacbe48,0x3f18bef1,
 0x3f71bf6d,0x3f78bf75,0x3f7dbf7b,0x3f80bf7f,0x3f3ebf35,0x3f4ebf46,0x3f5cbf55,0x3f67bf62,0x3edbbec4,0x3f04bef1,0x3f18bf0e,0x3f2cbf22,0x3d490000,0x3e16bdc9,0x3e79be48,0x3eacbe95,
 0xbeac3ec4,0xbe793e95,0xbe163e48,0xbd493dc9,0xbf2c3f35,0xbf183f22,0xbf043f0e,0xbedb3ef1,0xbf673f6d,0xbf5c3f62,0xbf4e3f55,0xbf3e3f46,0xbf803f80,0xbf7d3f7f,0xbf783f7b,0xbf713f75,
 0xbf2c0000,0xbf4e3f7f,0x3f043e48,0x3f67bf75,0xbeacbec4,0xbf783f62,0x3e163f0e,0x3f80bf46,0x3d49bf35,0xbf7d3f22,0xbe793f55,0x3f71bef1,0x3edbbf6d,0xbf5c3e95,0xbf183f7b,0x3f3ebdc9,
 0x3f3ebf80,0xbf18bdc9,0xbf5c3f7b,0x3edb3e95,0x3f71bf6d,0xbe79bef1,0xbf7d3f55,0x3d493f22,0x3f80bf35,0x3e16bf46,0xbf783f0e,0xbeac3f62,0x3f67bec4,0x3f04bf75,0xbf4e3e48,0xbf2c3f7f,
 0x3f04bf6d,0xbf2c3dc9,0xbf673f7b,0x3e163ef1,0xbf180000,0xbf713f75,0x3d493f0e,0x3f78bf22,0x3e793ec4,0x3f80bf46,0x3eacbf55,0xbf4e3e95,0x3f7dbf35,0x3edbbf62,0xbf3e3e48,0xbf5c3f7f,
 0xbf5c3ec4,0xbf3e3f7f,0x3edb3e48,0x3f7dbf62,0xbf4e3f80,0x3eac3e95,0x3f80bf55,0x3e79bf46,0x3f78bf6d,0x3d49bf22,0xbf713f0e,0xbf183f75,0x3e16bf35,0xbf673ef1,0xbf2c3f7b,0x3f043dc9,
 0xbe793f35,0x3f3ebe95,0x3f71bf7b,0x3e16bf22,0xbf4e3ec4,0xbf673f7f,0xbd493f0e,0x3f5cbef1,0xbf040000,0xbf803f62,0xbedb3f55,0x3f18bdc9,0x3f7dbf6d,0x3eacbf46,0xbf2c3e48,0xbf783f75,
 0xbf783f35,0xbf2c3f75,0x3eac3e48,0x3f7dbf46,0x3f18bf6d,0xbedbbdc9,0xbf803f55,0xbf043f62,0x3f5cbf80,0xbd49bef1,0xbf673f0e,0xbf4e3f7f,0x3e163ec4,0x3f71bf22,0x3f3ebf7b,0xbe79be95,
 0x3f80bf6d,0x3f18bf62,0xbe79be48,0xbf673f22,0xbf713f35,0xbf5c3f7f,0xbe163f0e,0x3f2cbe95,0x3f3ebec4,0x3f7dbf75,0x3f04bf55,0xbeacbdc9,0xbedb0000,0xbf783f46,0xbf4e3f7b,0xbd493ef1,
 0xbd49bec4,0xbf4e3ef1,0xbf783f7b,0xbedb3f46,0xbeac3f35,0x3f04bdc9,0x3f7dbf55,0x3f3ebf75,0x3f2cbf6d,0xbe16be95,0xbf5c3f0e,0xbf713f7f,0xbf673f80,0xbe793f22,0x3f18be48,0x3f80bf62,
 0x3f71bf80,0x3f04bf46,0xbe16be48,0xbf3e3ef1,0xbf803f6d,0xbf4e3f75,0xbe793f0e,0x3edbbdc9,0x3f67bf35,0x3f78bf7f,0x3f18bf55,0xbd49be95,0xbf2c3ec4,0xbf7d3f62,0xbf5c3f7b,0xbeac3f22,
 0xbeac0000,0xbf5c3f22,0xbf7d3f7b,0xbf2c3f62,0xbd493ec4,0x3f18be95,0x3f78bf55,0x3f67bf7f,0x3edbbf35,0xbe79bdc9,0xbf4e3f0e,0xbf803f75,0xbf3e3f6d,0xbe163ef1,0x3f04be48,0x3f71bf46,
 0x3f18bec4,0x3f67bf46,0x3f80bf7b,0x3f5cbf75,0xbf783f80,0xbf3e3f62,0xbeac3f0e,0x3e163dc9,0xbf7d3f6d,0xbf713f7f,0xbf2c3f55,0xbe793ef1,0x3f04bf35,0x3d49be95,0xbedb3e48,0xbf4e3f22,
 0xbf4e3f6d,0xbedb3f22,0x3d493e48,0x3f04be95,0xbe790000,0xbf2c3ef1,0xbf713f55,0xbf7d3f7f,0x3e16bec4,0xbeac3dc9,0xbf3e3f0e,0xbf783f62,0x3f5cbf35,0x3f80bf75,0x3f67bf7b,0x3f18bf46,
 0xbf4e3f35,0xbf713f62,0xbf803f7b,0xbf783f7f,0xbf5c3f6d,0xbf2c3f46,0xbedb3f0e,0xbe163e95,0x3f7dbf80,0x3f67bf75,0x3f3ebf55,0x3f04bf22,0x3e79bec4,0xbd49bdc9,0xbeac3e48,0xbf183ef1,
 0xbf183f35,0xbeac3ef1,0xbd493e48,0x3e79bdc9,0x3f04bec4,0x3f3ebf22,0x3f67bf55,0x3f7dbf75,0xbe160000,0xbedb3e95,0xbf2c3f0e,0xbf5c3f46,0xbf783f6d,0xbf803f7f,0xbf713f7b,0xbf4e3f62,
 0xbeac3ec4,0xbe793e95,0xbe163e48,0xbd493dc9,0xbf2c3f35,0xbf183f22,0xbf043f0e,0xbedb3ef1,0xbf673f6d,0xbf5c3f62,0xbf4e3f55,0xbf3e3f46,0xbf803f80,0xbf7d3f7f,0xbf783f7b,0xbf713f75,
 0xbf713f6d,0xbf783f75,0xbf7d3f7b,0xbf803f7f,0xbf3e3f35,0xbf4e3f46,0xbf5c3f55,0xbf673f62,0xbedb3ec4,0xbf043ef1,0xbf183f0e,0xbf2c3f22,0xbd490000,0xbe163dc9,0xbe793e48,0xbeac3e95,
};
__device__ __align__(128) const uint32_t g_Gimg[1792] = {
 0x00003d00,0x00003d00,0x00003d00,0x00003d00,0x00003d00,0x00003d00,0x00003d00,0x00003d00,0x00003d00,0x00003d00,0x00003d00,0x00003d00,0x00003d00,0x00003d00,0x00003d00,0x00003d00,
 0x00003d00,0x00003d00,0x00003d00,0x00003d00,0x00003d00,0x00003d00,0x00003d00,0x00003d00,0x00003d00,0x00003d00,0x00003d00,0x00003d00,0x00003d00,0x00003d00,0x00003d00,0x00003d00,
 0xbc5b3ce7,0xbc843cdc,0xbc983cce,0xbcac3cbe,0xbac93d00,0xbb963cfd,0xbbf93cf8,0xbc2c3cf1,0xbcf13c2c,0xbcf83bf9,0xbcfd3b96,0xbd003ac9,0xbcbe3cac,0xbcce3c98,0xbcdc3c84,0xbce73c5b,
 0xbce7bc5b,0xbcdcbc84,0xbccebc98,0xbcbebcac,0xbd00bac9,0xbcfdbb96,0xbcf8bbf9,0xbcf1bc2c,0xbc2cbcf1,0xbbf9bcf8,0xbb96bcfd,0xbac9bd00,0xbcacbcbe,0xbc98bcce,0xbc84bcdc,0xbc5bbce7,
 0xbcffbb49,0xbcf5bc15,0xbce2bc71,0xbcc6bca2,0xbca2bcc6,0xbc71bce2,0xbc15bcf5,0xbb49bcff,0xbb493cff,0xbc153cf5,0xbc713ce2,0xbca23cc6,0xbcc63ca2,0xbce23c71,0xbcf53c15,0xbcff3b49,
 0x3cff3b49,0x3cf53c15,0x3ce23c71,0x3cc63ca2,0x3ca23cc6,0x3c713ce2,0x3c153cf5,0x3b493cff,0x3b49bcff,0x3c15bcf5,0x3c71bce2,0x3ca2bcc6,0x3cc6bca2,0x3ce2bc71,0x3cf5bc15,0x3cffbb49,
 0x3c84bcdc,0x3cbebcac,0x3ce7bc5b,0x3cfdbb96,0xbc98bcce,0xbc2cbcf1,0xbac9bd00,0x3bf9bcf8,0xbcf83bf9,0xbd00bac9,0xbcf1bc2c,0xbccebc98,0xbb963cfd,0xbc5b3ce7,0xbcac3cbe,0xbcdc3c84,
 0xbcdcbc84,0xbcacbcbe,0xbc5bbce7,0xbb96bcfd,0xbcce3c98,0xbcf13c2c,0xbd003ac9,0xbcf8bbf9,0x3bf93cf8,0xbac93d00,0xbc2c3cf1,0xbc983cce,0x3cfd3b96,0x3ce73c5b,0x3cbe3cac,0x3c843cdc,
 0xbbc83cfb,0xbc8e3cd5,0xbcd53c8e,0xbcfb3bc8,0xbcfbbbc8,0xbcd5bc8e,0xbc8ebcd5,0xbbc8bcfb,0x3bc8bcfb,0x3c8ebcd5,0x3cd5bc8e,0x3cfbbbc8,0x3cfb3bc8,0x3cd53c8e,0x3c8e3cd5,0x3bc83cfb,
 0xbbc83cfb,0xbc8e3cd5,0xbcd53c8e,0xbcfb3bc8,0xbcfbbbc8,0xbcd5bc8e,0xbc8ebcd5,0xbbc8bcfb,0x3bc8bcfb,0x3c8ebcd5,0x3cd5bc8e,0x3cfbbbc8,0x3cfb3bc8,0x3cd53c8e,0x3c8e3cd5,0x3bc83cfb,
 0x3c98bcce,0x3ce7bc5b,0x3d003ac9,0x3cdc3c84,0xbcf8bbf9,0xbcbebcac,0xbc2cbcf1,0x3b96bcfd,0xbcfd3b96,0xbcf1bc2c,0xbcacbcbe,0xbbf9bcf8,0x3c843cdc,0x3ac93d00,0xbc5b3ce7,0xbcce3c98,
 0xbccebc98,0xbc5bbce7,0x3ac9bd00,0x3c84bcdc,0xbbf93cf8,0xbcac3cbe,0xbcf13c2c,0xbcfdbb96,0x3b963cfd,0xbc2c3cf1,0xbcbe3cac,0xbcf83bf9,0x3cdcbc84,0x3d00bac9,0x3ce73c5b,0x3c983cce,
 0xbcf5bc15,0xbca2bcc6,0xbb49bcff,0x3c71bce2,0x3ce2bc71,0x3cff3b49,0x3cc63ca2,0x3c153cf5,0x3c15bcf5,0x3cc6bca2,0x3cffbb49,0x3ce23c71,0x3c713ce2,0xbb493cff,0xbca23cc6,0xbcf53c15,
 0x3cf53c15,0x3ca23cc6,0x3b493cff,0xbc713ce2,0xbce23c71,0xbcffbb49,0xbcc6bca2,0xbc15bcf5,0xbc153cf5,0xbcc63ca2,0xbcff3b49,0xbce2bc71,0xbc71bce2,0x3b49bcff,0x3ca2bcc6,0x3cf5bc15,
 0xbcac3cbe,0xbcfd3b96,0xbcdcbc84,0xbc2cbcf1,0x3ce7bc5b,0x3cf83bf9,0x3c983cce,0xbac93d00,0xbd003ac9,0xbccebc98,0xbbf9bcf8,0x3c5bbce7,0x3cf13c2c,0x3c843cdc,0xbb963cfd,0xbcbe3cac,
 0xbcbebcac,0xbb96bcfd,0x3c84bcdc,0x3cf1bc2c,0x3c5b3ce7,0xbbf93cf8,0xbcce3c98,0xbd00bac9,0xbac9bd00,0x3c98bcce,0x3cf8bbf9,0x3ce73c5b,0xbc2c3cf1,0xbcdc3c84,0xbcfdbb96,0xbcacbcbe,
 0xbc443ced,0xbced3c44,0xbcedbc44,0xbc44bced,0x3c44bced,0x3cedbc44,0x3ced3c44,0x3c443ced,0xbc443ced,0xbced3c44,0xbcedbc44,0xbc44bced,0x3c44bced,0x3cedbc44,0x3ced3c44,0x3c443ced,
 0xbc443ced,0xbced3c44,0xbcedbc44,0xbc44bced,0x3c44bced,0x3cedbc44,0x3ced3c44,0x3c443ced,0xbc443ced,0xbced3c44,0xbcedbc44,0xbc44bced,0x3c44bced,0x3cedbc44,0x3ced3c44,0x3c443ced,
 0x3cbebcac,0x3cfd3b96,0x3c843cdc,0xbc2c3cf1,0xbc5b3ce7,0xbcf83bf9,0xbccebc98,0xbac9bd00,0x3d003ac9,0x3c983cce,0xbbf93cf8,0xbce73c5b,0xbcf13c2c,0xbcdcbc84,0xbb96bcfd,0x3cacbcbe,
 0x3cac3cbe,0xbb963cfd,0xbcdc3c84,0xbcf1bc2c,0xbce7bc5b,0xbbf9bcf8,0x3c98bcce,0x3d00bac9,0xbac93d00,0xbcce3c98,0xbcf8bbf9,0xbc5bbce7,0xbc2cbcf1,0x3c84bcdc,0x3cfdbb96,0x3cbe3cac,
 0xbce2bc71,0xbb49bcff,0x3cc6bca2,0x3cf53c15,0x3c153cf5,0xbca23cc6,0xbcffbb49,0xbc71bce2,0xbc713ce2,0xbcff3b49,0xbca2bcc6,0x3c15bcf5,0x3cf5bc15,0x3cc63ca2,0xbb493cff,0xbce23c71,
 0x3ce23c71,0x3b493cff,0xbcc63ca2,0xbcf5bc15,0xbc15bcf5,0x3ca2bcc6,0x3cff3b49,0x3c713ce2,0x3c71bce2,0x3cffbb49,0x3ca23cc6,0xbc153cf5,0xbcf53c15,0xbcc6bca2,0x3b49bcff,0x3ce2bc71,
 0xbcce3c98,0xbce7bc5b,0xbac9bd00,0x3cdcbc84,0xbbf9bcf8,0x3cbebcac,0x3cf13c2c,0x3b963cfd,0x3cfd3b96,0x3c2c3cf1,0xbcac3cbe,0xbcf8bbf9,0xbc843cdc,0xbd00bac9,0xbc5bbce7,0x3c98bcce,
 0x3c983cce,0xbc5b3ce7,0xbd003ac9,0xbc84bcdc,0xbcf83bf9,0xbcacbcbe,0x3c2cbcf1,0x3cfdbb96,0x3b96bcfd,0x3cf1bc2c,0x3cbe3cac,0xbbf93cf8,0x3cdc3c84,0xbac93d00,0xbce73c5b,0xbccebc98,
 0xbc8e3cd5,0xbcfbbbc8,0xbbc8bcfb,0x3cd5bc8e,0x3cd53c8e,0xbbc83cfb,0xbcfb3bc8,0xbc8ebcd5,0x3c8ebcd5,0x3cfb3bc8,0x3bc83cfb,0xbcd53c8e,0xbcd5bc8e,0x3bc8bcfb,0x3cfbbbc8,0x3c8e3cd5,
 0xbc8e3cd5,0xbcfbbbc8,0xbbc8bcfb,0x3cd5bc8e,0x3cd53c8e,0xbbc83cfb,0xbcfb3bc8,0xbc8ebcd5,0x3c8ebcd5,0x3cfb3bc8,0x3bc83cfb,0xbcd53c8e,0xbcd5bc8e,0x3bc8bcfb,0x3cfbbbc8,0x3c8e3cd5,
 0xbcdc3c84,0xbcbebcac,0x3c5bbce7,0x3cfd3b96,0xbccebc98,0x3c2cbcf1,0x3d003ac9,0x3bf93cf8,0x3cf83bf9,0x3ac93d00,0xbcf13c2c,0xbc98bcce,0x3b963cfd,0xbce73c5b,0xbcacbcbe,0x3c84bcdc,
 0x3c843cdc,0xbcac3cbe,0xbce7bc5b,0x3b96bcfd,0xbc983cce,0xbcf1bc2c,0x3ac9bd00,0x3cf8bbf9,0x3bf9bcf8,0x3d00bac9,0x3c2c3cf1,0xbcce3c98,0x3cfdbb96,0x3c5b3ce7,0xbcbe3cac,0xbcdcbc84,
 0xbcc6bca2,0x3c71bce2,0x3cf53c15,0xbb493cff,0xbcff3b49,0xbc15bcf5,0x3ce2bc71,0x3ca23cc6,0x3ca2bcc6,0x3ce23c71,0xbc153cf5,0xbcffbb49,0xbb49bcff,0x3cf5bc15,0x3c713ce2,0xbcc63ca2,
 0x3cc63ca2,0xbc713ce2,0xbcf5bc15,0x3b49bcff,0x3cffbb49,0x3c153cf5,0xbce23c71,0xbca2bcc6,0xbca23cc6,0xbce2bc71,0x3c15bcf5,0x3cff3b49,0x3b493cff,0xbcf53c15,0xbc71bce2,0x3cc6bca2,
 0x3ce7bc5b,0x3c843cdc,0xbcce3c98,0xbcacbcbe,0x3d00bac9,0x3b963cfd,0xbcf83bf9,0xbc2cbcf1,0x3cf13c2c,0xbbf93cf8,0xbcfdbb96,0x3ac9bd00,0x3cbe3cac,0xbc983cce,0xbcdcbc84,0x3c5bbce7,
 0x3c5b3ce7,0xbcdc3c84,0xbc98bcce,0x3cbebcac,0x3ac93d00,0xbcfd3b96,0xbbf9bcf8,0x3cf1bc2c,0xbc2c3cf1,0xbcf8bbf9,0x3b96bcfd,0x3d003ac9,0xbcac3cbe,0xbccebc98,0x3c84bcdc,0x3ce73c5b,
 0xbcb53cb5,0xbcb5bcb5,0x3cb5bcb5,0x3cb53cb5,0xbcb53cb5,0xbcb5bcb5,0x3cb5bcb5,0x3cb53cb5,0xbcb53cb5,0xbcb5bcb5,0x3cb5bcb5,0x3cb53cb5,0xbcb53cb5,0xbcb5bcb5,0x3cb5bcb5,0x3cb53cb5,
 0xbcb53cb5,0xbcb5bcb5,0x3cb5bcb5,0x3cb53cb5,0xbcb53cb5,0xbcb5bcb5,0x3cb5bcb5,0x3cb53cb5,0xbcb53cb5,0xbcb5bcb5,0x3cb5bcb5,0x3cb53cb5,0xbcb53cb5,0xbcb5bcb5,0x3cb5bcb5,0x3cb53cb5,
 0xbcf13c2c,0xbbf9bcf8,0x3cfdbb96,0x3ac93d00,0xbcbe3cac,0xbc98bcce,0x3cdcbc84,0x3c5b3ce7,0xbce7bc5b,0x3c84bcdc,0x3cce3c98,0xbcac3cbe,0xbd00bac9,0x3b96bcfd,0x3cf83bf9,0xbc2c3cf1,
 0xbc2cbcf1,0x3cf8bbf9,0x3b963cfd,0xbd003ac9,0xbcacbcbe,0x3ccebc98,0x3c843cdc,0xbce73c5b,0x3c5bbce7,0x3cdc3c84,0xbc983cce,0xbcbebcac,0x3ac9bd00,0x3cfd3b96,0xbbf93cf8,0xbcf1bc2c,
 0xbca2bcc6,0x3ce2bc71,0x3c153cf5,0xbcff3b49,0x3b49bcff,0x3cf53c15,0xbc713ce2,0xbcc6bca2,0xbcc63ca2,0xbc71bce2,0x3cf5bc15,0x3b493cff,0xbcffbb49,0x3c15bcf5,0x3ce23c71,0xbca23cc6,
 0x3ca23cc6,0xbce23c71,0xbc15bcf5,0x3cffbb49,0xbb493cff,0xbcf5bc15,0x3c71bce2,0x3cc63ca2,0x3cc6bca2,0x3c713ce2,0xbcf53c15,0xbb49bcff,0x3cff3b49,0xbc153cf5,0xbce2bc71,0x3ca2bcc6,
 0x3cf8bbf9,0xbac93d00,0xbcf1bc2c,0x3c98bcce,0x3b96bcfd,0x3ce73c5b,0xbcac3cbe,0xbc84bcdc,0xbcdcbc84,0x3cbebcac,0x3c5b3ce7,0xbcfd3b96,0xbcce3c98,0xbc2cbcf1,0x3d00bac9,0xbbf93cf8,
 0xbbf9bcf8,0x3d003ac9,0xbc2c3cf1,0xbccebc98,0xbcfdbb96,0x3c5bbce7,0x3cbe3cac,0xbcdc3c84,0xbc843cdc,0xbcacbcbe,0x3ce7bc5b,0x3b963cfd,0x3c983cce,0xbcf13c2c,0xbac9bd00,0x3cf83bf9,
 0xbcd53c8e,0xbbc8bcfb,0x3cfb3bc8,0xbc8e3cd5,0xbc8ebcd5,0x3cfbbbc8,0xbbc83cfb,0xbcd5bc8e,0x3cd5bc8e,0x3bc83cfb,0xbcfbbbc8,0x3c8ebcd5,0x3c8e3cd5,0xbcfb3bc8,0x3bc8bcfb,0x3cd53c8e,
 0xbcd53c8e,0xbbc8bcfb,0x3cfb3bc8,0xbc8e3cd5,0xbc8ebcd5,0x3cfbbbc8,0xbbc83cfb,0xbcd5bc8e,0x3cd5bc8e,0x3bc83cfb,0xbcfbbbc8,0x3c8ebcd5,0x3c8e3cd5,0xbcfb3bc8,0x3bc8bcfb,0x3cd53c8e,
 0x3cfdbb96,0xbc2c3cf1,0xbcacbcbe,0x3cf8bbf9,0xbc84bcdc,0x3d00bac9,0xbc5b3ce7,0xbc98bcce,0xbccebc98,0x3ce7bc5b,0xbac93d00,0xbcdcbc84,0xbbf93cf8,0xbcbebcac,0x3cf1bc2c,0xbb963cfd,
 0xbb96bcfd,0x3cf13c2c,0xbcbe3cac,0xbbf9bcf8,0xbcdc3c84,0xbac9bd00,0x3ce73c5b,0xbcce3c98,0xbc983cce,0xbc5bbce7,0x3d003ac9,0xbc843cdc,0x3cf83bf9,0xbcac3cbe,0xbc2cbcf1,0x3cfd3b96,
 0xbc71bce2,0x3cff3b49,0xbca23cc6,0xbc15bcf5,0x3cf53c15,0xbcc63ca2,0xbb49bcff,0x3ce23c71,0x3ce2bc71,0xbb493cff,0xbcc6bca2,0x3cf5bc15,0xbc153cf5,0xbca2bcc6,0x3cffbb49,0xbc713ce2,
 0x3c713ce2,0xbcffbb49,0x3ca2bcc6,0x3c153cf5,0xbcf5bc15,0x3cc6bca2,0x3b493cff,0xbce2bc71,0xbce23c71,0x3b49bcff,0x3cc63ca2,0xbcf53c15,0x3c15bcf5,0x3ca23cc6,0xbcff3b49,0x3c71bce2,
 0xbd003ac9,0x3c98bcce,0x3bf93cf8,0xbce7bc5b,0x3cf13c2c,0xbcdc3c84,0x3b96bcfd,0x3cac3cbe,0xbcbebcac,0x3cfdbb96,0xbc843cdc,0xbc2cbcf1,0x3c5b3ce7,0xbcf8bbf9,0x3ccebc98,0xbac93d00,
 0xbac9bd00,0x3cce3c98,0xbcf83bf9,0x3c5bbce7,0xbc2c3cf1,0xbc84bcdc,0x3cfd3b96,0xbcbe3cac,0x3cacbcbe,0x3b963cfd,0xbcdcbc84,0x3cf1bc2c,0xbce73c5b,0x3bf9bcf8,0x3c983cce,0xbd00bac9,
 0xbced3c44,0x3c44bced,0x3c443ced,0xbcedbc44,0x3cedbc44,0xbc443ced,0xbc44bced,0x3ced3c44,0xbced3c44,0x3c44bced,0x3c443ced,0xbcedbc44,0x3cedbc44,0xbc443ced,0xbc44bced,0x3ced3c44,
 0xbced3c44,0x3c44bced,0x3c443ced,0xbcedbc44,0x3cedbc44,0xbc443ced,0xbc44bced,0x3ced3c44,0xbced3c44,0x3c44bced,0x3c443ced,0xbcedbc44,0x3cedbc44,0xbc443ced,0xbc44bced,0x3ced3c44,
 0x3d003ac9,0xbcce3c98,0x3bf9bcf8,0x3c5b3ce7,0xbcf13c2c,0x3c84bcdc,0x3b963cfd,0xbcbebcac,0x3cac3cbe,0xbcfdbb96,0x3cdcbc84,0xbc2c3cf1,0xbce7bc5b,0x3cf8bbf9,0xbc983cce,0xbac9bd00,
 0xbac93d00,0xbc98bcce,0x3cf83bf9,0xbce73c5b,0xbc2cbcf1,0x3cdc3c84,0xbcfd3b96,0x3cacbcbe,0xbcbe3cac,0x3b96bcfd,0x3c843cdc,0xbcf1bc2c,0x3c5bbce7,0x3bf93cf8,0xbccebc98,0x3d00bac9,
 0xbc15bcf5,0x3cc63ca2,0xbcffbb49,0x3ce2bc71,0xbc713ce2,0xbb49bcff,0x3ca23cc6,0xbcf5bc15,0xbcf53c15,0x3ca2bcc6,0xbb493cff,0xbc71bce2,0x3ce23c71,0xbcff3b49,0x3cc6bca2,0xbc153cf5,
 0x3c153cf5,0xbcc6bca2,0x3cff3b49,0xbce23c71,0x3c71bce2,0x3b493cff,0xbca2bcc6,0x3cf53c15,0x3cf5bc15,0xbca23cc6,0x3b49bcff,0x3c713ce2,0xbce2bc71,0x3cffbb49,0xbcc63ca2,0x3c15bcf5,
 0xbcfdbb96,0x3cf1bc2c,0xbcac3cbe,0x3bf9bcf8,0x3c84bcdc,0xbac93d00,0xbc5bbce7,0x3cce3c98,0x3c983cce,0xbce7bc5b,0x3d00bac9,0xbcdc3c84,0xbcf83bf9,0x3cbebcac,0xbc2c3cf1,0xbb96bcfd,
 0xbb963cfd,0xbc2cbcf1,0x3cbe3cac,0xbcf8bbf9,0xbcdcbc84,0x3d003ac9,0xbce73c5b,0x3c98bcce,0x3ccebc98,0xbc5b3ce7,0xbac9bd00,0x3c843cdc,0x3bf93cf8,0xbcacbcbe,0x3cf13c2c,0xbcfd3b96,
 0xbcfb3bc8,0x3cd5bc8e,0xbc8e3cd5,0x3bc8bcfb,0x3bc83cfb,0xbc8ebcd5,0x3cd53c8e,0xbcfbbbc8,0x3cfbbbc8,0xbcd53c8e,0x3c8ebcd5,0xbbc83cfb,0xbbc8bcfb,0x3c8e3cd5,0xbcd5bc8e,0x3cfb3bc8,
 0xbcfb3bc8,0x3cd5bc8e,0xbc8e3cd5,0x3bc8bcfb,0x3bc83cfb,0xbc8ebcd5,0x3cd53c8e,0xbcfbbbc8,0x3cfbbbc8,0xbcd53c8e,0x3c8ebcd5,0xbbc83cfb,0xbbc8bcfb,0x3c8e3cd5,0xbcd5bc8e,0x3cfb3bc8,
 0xbcf8bbf9,0x3d00bac9,0xbcf13c2c,0x3ccebc98,0xbb96bcfd,0x3c5b3ce7,0xbcacbcbe,0x3cdc3c84,0x3c843cdc,0xbcbebcac,0x3ce73c5b,0xbcfdbb96,0xbc983cce,0x3c2cbcf1,0xbac93d00,0xbbf9bcf8,
 0xbbf93cf8,0xbac9bd00,0x3c2c3cf1,0xbc98bcce,0xbcfd3b96,0x3ce7bc5b,0xbcbe3cac,0x3c84bcdc,0x3cdcbc84,0xbcac3cbe,0x3c5bbce7,0xbb963cfd,0x3cce3c98,0xbcf1bc2c,0x3d003ac9,0xbcf83bf9,
 0xbb49bcff,0x3c153cf5,0xbc71bce2,0x3ca23cc6,0xbcc6bca2,0x3ce23c71,0xbcf5bc15,0x3cff3b49,0x3cffbb49,0xbcf53c15,0x3ce2bc71,0xbcc63ca2,0x3ca2bcc6,0xbc713ce2,0x3c15bcf5,0xbb493cff,
 0x3b493cff,0xbc15bcf5,0x3c713ce2,0xbca2bcc6,0x3cc63ca2,0xbce2bc71,0x3cf53c15,0xbcffbb49,0xbcff3b49,0x3cf5bc15,0xbce23c71,0x3cc6bca2,0xbca23cc6,0x3c71bce2,0xbc153cf5,0x3b49bcff,
 0x3cf13c2c,0xbcf8bbf9,0x3cfd3b96,0xbd00bac9,0x3cbe3cac,0xbccebc98,0x3cdc3c84,0xbce7bc5b,0x3c5b3ce7,0xbc84bcdc,0x3c983cce,0xbcacbcbe,0x3ac93d00,0xbb96bcfd,0x3bf93cf8,0xbc2cbcf1,
 0xbc2c3cf1,0x3bf9bcf8,0xbb963cfd,0x3ac9bd00,0xbcac3cbe,0x3c98bcce,0xbc843cdc,0x3c5bbce7,0xbce73c5b,0x3cdcbc84,0xbcce3c98,0x3cbebcac,0xbd003ac9,0x3cfdbb96,0xbcf83bf9,0x3cf1bc2c,
 0xbd000000,0x3d000000,0xbd000000,0x3d000000,0xbd000000,0x3d000000,0xbd000000,0x3d000000,0xbd000000,0x3d000000,0xbd000000,0x3d000000,0xbd000000,0x3d000000,0xbd000000,0x3d000000,
 0xbd000000,0x3d000000,0xbd000000,0x3d000000,0xbd000000,0x3d000000,0xbd000000,0x3d000000,0xbd000000,0x3d000000,0xbd000000,0x3d000000,0xbd000000,0x3d000000,0xbd000000,0x3d000000,
 0xbce7bc5b,0x3cdc3c84,0xbccebc98,0x3cbe3cac,0xbd00bac9,0x3cfd3b96,0xbcf8bbf9,0x3cf13c2c,0xbc2cbcf1,0x3bf93cf8,0xbb96bcfd,0x3ac93d00,0xbcacbcbe,0x3c983cce,0xbc84bcdc,0x3c5b3ce7,
 0x3c5bbce7,0xbc843cdc,0x3c98bcce,0xbcac3cbe,0x3ac9bd00,0xbb963cfd,0x3bf9bcf8,0xbc2c3cf1,0x3cf1bc2c,0xbcf83bf9,0x3cfdbb96,0xbd003ac9,0x3cbebcac,0xbcce3c98,0x3cdcbc84,0xbce73c5b,
 0x3b49bcff,0xbc153cf5,0x3c71bce2,0xbca23cc6,0x3cc6bca2,0xbce23c71,0x3cf5bc15,0xbcff3b49,0xbcffbb49,0x3cf53c15,0xbce2bc71,0x3cc63ca2,0xbca2bcc6,0x3c713ce2,0xbc15bcf5,0x3b493cff,
 0xbb493cff,0x3c15bcf5,0xbc713ce2,0x3ca2bcc6,0xbcc63ca2,0x3ce2bc71,0xbcf53c15,0x3cffbb49,0x3cff3b49,0xbcf5bc15,0x3ce23c71,0xbcc6bca2,0x3ca23cc6,0xbc71bce2,0x3c153cf5,0xbb49bcff,
 0x3cdc3c84,0xbcacbcbe,0x3c5b3ce7,0xbb96bcfd,0x3ccebc98,0xbcf13c2c,0x3d00bac9,0xbcf8bbf9,0xbbf9bcf8,0xbac93d00,0x3c2cbcf1,0xbc983cce,0xbcfdbb96,0x3ce73c5b,0xbcbebcac,0x3c843cdc,
 0x3c84bcdc,0xbcbe3cac,0x3ce7bc5b,0xbcfd3b96,0xbc98bcce,0x3c2c3cf1,0xbac9bd00,0xbbf93cf8,0xbcf83bf9,0x3d003ac9,0xbcf1bc2c,0x3cce3c98,0xbb963cfd,0x3c5bbce7,0xbcac3cbe,0x3cdcbc84,
 0xbcfbbbc8,0x3cd53c8e,0xbc8ebcd5,0x3bc83cfb,0x3bc8bcfb,0xbc8e3cd5,0x3cd5bc8e,0xbcfb3bc8,0x3cfb3bc8,0xbcd5bc8e,0x3c8e3cd5,0xbbc8bcfb,0xbbc83cfb,0x3c8ebcd5,0xbcd53c8e,0x3cfbbbc8,
 0xbcfbbbc8,0x3cd53c8e,0xbc8ebcd5,0x3bc83cfb,0x3bc8bcfb,0xbc8e3cd5,0x3cd5bc8e,0xbcfb3bc8,0x3cfb3bc8,0xbcd5bc8e,0x3c8e3cd5,0xbbc8bcfb,0xbbc83cfb,0x3c8ebcd5,0xbcd53c8e,0x3cfbbbc8,
 0x3cce3c98,0xbc5bbce7,0xbac93d00,0x3c84bcdc,0x3bf9bcf8,0xbcac3cbe,0x3cf1bc2c,0xbcfdbb96,0xbb96bcfd,0xbc2c3cf1,0x3cbebcac,0xbcf83bf9,0xbcdc3c84,0x3d00bac9,0xbce7bc5b,0x3c983cce,
 0x3c98bcce,0xbce73c5b,0x3d003ac9,0xbcdcbc84,0xbcf8bbf9,0x3cbe3cac,0xbc2cbcf1,0xbb963cfd,0xbcfd3b96,0x3cf13c2c,0xbcacbcbe,0x3bf93cf8,0x3c843cdc,0xbac9bd00,0xbc5b3ce7,0x3ccebc98,
 0x3c15bcf5,0xbcc63ca2,0x3cffbb49,0xbce2bc71,0x3c713ce2,0x3b49bcff,0xbca23cc6,0x3cf5bc15,0x3cf53c15,0xbca2bcc6,0x3b493cff,0x3c71bce2,0xbce23c71,0x3cff3b49,0xbcc6bca2,0x3c153cf5,
 0xbc153cf5,0x3cc6bca2,0xbcff3b49,0x3ce23c71,0xbc71bce2,0xbb493cff,0x3ca2bcc6,0xbcf53c15,0xbcf5bc15,0x3ca23cc6,0xbb49bcff,0xbc713ce2,0x3ce2bc71,0xbcffbb49,0x3cc63ca2,0xbc15bcf5,
 0xbcbebcac,0x3b963cfd,0x3c84bcdc,0xbcf13c2c,0x3c5b3ce7,0x3bf9bcf8,0xbcce3c98,0x3d003ac9,0xbac9bd00,0xbc983cce,0x3cf8bbf9,0xbce7bc5b,0xbc2c3cf1,0x3cdcbc84,0xbcfdbb96,0x3cac3cbe,
 0x3cacbcbe,0xbcfd3b96,0x3cdc3c84,0xbc2cbcf1,0xbce73c5b,0x3cf83bf9,0xbc98bcce,0xbac93d00,0x3d00bac9,0xbccebc98,0x3bf93cf8,0x3c5bbce7,0xbcf1bc2c,0x3c843cdc,0x3b96bcfd,0xbcbe3cac,
 0xbcedbc44,0x3c443ced,0x3c44bced,0xbced3c44,0x3ced3c44,0xbc44bced,0xbc443ced,0x3cedbc44,0xbcedbc44,0x3c443ced,0x3c44bced,0xbced3c44,0x3ced3c44,0xbc44bced,0xbc443ced,0x3cedbc44,
 0xbcedbc44,0x3c443ced,0x3c44bced,0xbced3c44,0x3ced3c44,0xbc44bced,0xbc443ced,0x3cedbc44,0xbcedbc44,0x3c443ced,0x3c44bced,0xbced3c44,0x3ced3c44,0xbc44bced,0xbc443ced,0x3cedbc44,
 0x3cac3cbe,0x3b96bcfd,0xbcdc3c84,0x3cf13c2c,0xbce7bc5b,0x3bf93cf8,0x3c98bcce,0xbd003ac9,0xbac93d00,0x3ccebc98,0xbcf8bbf9,0x3c5b3ce7,0xbc2cbcf1,0xbc843cdc,0x3cfdbb96,0xbcbebcac,
 0xbcbe3cac,0x3cfd3b96,0xbc84bcdc,0xbc2c3cf1,0x3c5bbce7,0xbcf83bf9,0x3cce3c98,0xbac9bd00,0xbd00bac9,0x3c983cce,0x3bf9bcf8,0xbce73c5b,0x3cf1bc2c,0xbcdcbc84,0x3b963cfd,0x3cacbcbe,
 0x3c71bce2,0xbcff3b49,0x3ca23cc6,0x3c15bcf5,0xbcf53c15,0x3cc63ca2,0x3b49bcff,0xbce23c71,0xbce2bc71,0x3b493cff,0x3cc6bca2,0xbcf5bc15,0x3c153cf5,0x3ca2bcc6,0xbcffbb49,0x3c713ce2,
 0xbc713ce2,0x3cffbb49,0xbca2bcc6,0xbc153cf5,0x3cf5bc15,0xbcc6bca2,0xbb493cff,0x3ce2bc71,0x3ce23c71,0xbb49bcff,0xbcc63ca2,0x3cf53c15,0xbc15bcf5,0xbca23cc6,0x3cff3b49,0xbc71bce2,
 0xbc98bcce,0xbc5b3ce7,0x3d00bac9,0xbc84bcdc,0x3cf8bbf9,0xbcacbcbe,0xbc2c3cf1,0x3cfdbb96,0xbb963cfd,0x3cf1bc2c,0xbcbebcac,0xbbf93cf8,0xbcdcbc84,0xbac93d00,0x3ce7bc5b,0xbccebc98,
 0xbcce3c98,0x3ce73c5b,0xbac9bd00,0xbcdc3c84,0xbbf9bcf8,0xbcbe3cac,0x3cf13c2c,0xbb96bcfd,0x3cfd3b96,0xbc2cbcf1,0xbcac3cbe,0x3cf83bf9,0xbc843cdc,0x3d003ac9,0xbc5bbce7,0xbc983cce,
 0xbcd5bc8e,0xbbc83cfb,0x3cfbbbc8,0xbc8ebcd5,0xbc8e3cd5,0x3cfb3bc8,0xbbc8bcfb,0xbcd53c8e,0x3cd53c8e,0x3bc8bcfb,0xbcfb3bc8,0x3c8e3cd5,0x3c8ebcd5,0xbcfbbbc8,0x3bc83cfb,0x3cd5bc8e,
 0xbcd5bc8e,0xbbc83cfb,0x3cfbbbc8,0xbc8ebcd5,0xbc8e3cd5,0x3cfb3bc8,0xbbc8bcfb,0xbcd53c8e,0x3cd53c8e,0x3bc8bcfb,0xbcfb3bc8,0x3c8e3cd5,0x3c8ebcd5,0xbcfbbbc8,0x3bc83cfb,0x3cd5bc8e,
 0xbc84bcdc,0xbcac3cbe,0x3ce73c5b,0x3b96bcfd,0x3c98bcce,0xbcf1bc2c,0xbac93d00,0x3cf8bbf9,0xbbf93cf8,0x3d00bac9,0xbc2cbcf1,0xbcce3c98,0xbcfd3b96,0x3c5b3ce7,0x3cbebcac,0xbcdcbc84,
 0xbcdc3c84,0x3cbe3cac,0x3c5bbce7,0xbcfdbb96,0xbccebc98,0xbc2c3cf1,0x3d003ac9,0xbbf9bcf8,0x3cf83bf9,0xbac9bd00,0xbcf13c2c,0x3c983cce,0x3b963cfd,0x3ce7bc5b,0xbcacbcbe,0xbc843cdc,
 0x3ca2bcc6,0xbce2bc71,0xbc153cf5,0x3cff3b49,0xbb49bcff,0xbcf53c15,0x3c713ce2,0x3cc6bca2,0x3cc63ca2,0x3c71bce2,0xbcf5bc15,0xbb493cff,0x3cffbb49,0xbc15bcf5,0xbce23c71,0x3ca23cc6,
 0xbca23cc6,0x3ce23c71,0x3c15bcf5,0xbcffbb49,0x3b493cff,0x3cf5bc15,0xbc71bce2,0xbcc63ca2,0xbcc6bca2,0xbc713ce2,0x3cf53c15,0x3b49bcff,0xbcff3b49,0x3c153cf5,0x3ce2bc71,0xbca2bcc6,
 0x3c5b3ce7,0x3cdcbc84,0xbc98bcce,0xbcbe3cac,0x3ac93d00,0x3cfdbb96,0xbbf9bcf8,0xbcf13c2c,0xbc2c3cf1,0x3cf83bf9,0x3b96bcfd,0xbd00bac9,0xbcac3cbe,0x3cce3c98,0x3c84bcdc,0xbce7bc5b,
 0xbce73c5b,0x3c843cdc,0x3ccebc98,0xbcacbcbe,0xbd003ac9,0x3b963cfd,0x3cf8bbf9,0xbc2cbcf1,0xbcf1bc2c,0xbbf93cf8,0x3cfd3b96,0x3ac9bd00,0xbcbebcac,0xbc983cce,0x3cdc3c84,0x3c5bbce7,
 0xbcb5bcb5,0xbcb53cb5,0x3cb53cb5,0x3cb5bcb5,0xbcb5bcb5,0xbcb53cb5,0x3cb53cb5,0x3cb5bcb5,0xbcb5bcb5,0xbcb53cb5,0x3cb53cb5,0x3cb5bcb5,0xbcb5bcb5,0xbcb53cb5,0x3cb53cb5,0x3cb5bcb5,
 0xbcb5bcb5,0xbcb53cb5,0x3cb53cb5,0x3cb5bcb5,0xbcb5bcb5,0xbcb53cb5,0x3cb53cb5,0x3cb5bcb5,0xbcb5bcb5,0xbcb53cb5,0x3cb53cb5,0x3cb5bcb5,0xbcb5bcb5,0xbcb53cb5,0x3cb53cb5,0x3cb5bcb5,
 0xbc2cbcf1,0xbcf83bf9,0x3b963cfd,0x3d00bac9,0xbcacbcbe,0xbcce3c98,0x3c843cdc,0x3ce7bc5b,0x3c5bbce7,0xbcdcbc84,0xbc983cce,0x3cbe3cac,0x3ac9bd00,0xbcfdbb96,0xbbf93cf8,0x3cf13c2c,
 0x3cf1bc2c,0xbbf9bcf8,0xbcfd3b96,0x3ac93d00,0x3cbebcac,0xbc98bcce,0xbcdc3c84,0x3c5b3ce7,0x3ce73c5b,0x3c84bcdc,0xbccebc98,0xbcac3cbe,0x3d003ac9,0x3b96bcfd,0xbcf8bbf9,0xbc2c3cf1,
 0x00000000,0x00000000,0x00000000,0x00000000,0x00000000,0x00000000,0x00000000,0x00000000,0x00000000,0x00000000,0x00000000,0x00000000,0x00000000,0x00000000,0x00000000,0x00000000,
 0x00000000,0x00000000,0x00000000,0x00000000,0x00000000,0x00000000,0x00000000,0x00000000,0x00000000,0x00000000,0x00000000,0x00000000,0x00000000,0x00000000,0x00000000,0x00000000,
 0x00000000,0x00000000,0x00000000,0x00000000,0x00000000,0x00000000,0x00000000,0x00000000,0x00000000,0x00000000,0x00000000,0x00000000,0x00000000,0x00000000,0x00000000,0x00000000,
 0x00000000,0x00000000,0x00000000,0x00000000,0x00000000,0x00000000,0x00000000,0x00000000,0x00000000,0x00000000,0x00000000,0x00000000,0x00000000,0x00000000,0x00000000,0x00000000,
 0x00000000,0x00000000,0x00000000,0x00000000,0x00000000,0x00000000,0x00000000,0x00000000,0x00000000,0x00000000,0x00000000,0x00000000,0x00000000,0x00000000,0x00000000,0x00000000,
 0x00000000,0x00000000,0x00000000,0x00000000,0x00000000,0x00000000,0x00000000,0x00000000,0x00000000,0x00000000,0x00000000,0x00000000,0x00000000,0x00000000,0x00000000,0x00000000,
 0x00000000,0x00000000,0x00000000,0x00000000,0x00000000,0x00000000,0x00000000,0x00000000,0x00000000,0x00000000,0x00000000,0x00000000,0x00000000,0x00000000,0x00000000,0x00000000,
 0x00000000,0x00000000,0x00000000,0x00000000,0x00000000,0x00000000,0x00000000,0x00000000,0x00000000,0x00000000,0x00000000,0x00000000,0x00000000,0x00000000,0x00000000,0x00000000,
 0x00000000,0x00000000,0x00000000,0x00000000,0x00000000,0x00000000,0x00000000,0x00000000,0x00000000,0x00000000,0x00000000,0x00000000,0x00000000,0x00000000,0x00000000,0x00000000,
 0x00000000,0x00000000,0x00000000,0x00000000,0x00000000,0x00000000,0x00000000,0x00000000,0x00000000,0x00000000,0x00000000,0x00000000,0x00000000,0x00000000,0x00000000,0x00000000,
 0x00000000,0x00000000,0x00000000,0x00000000,0x00000000,0x00000000,0x00000000,0x00000000,0x00000000,0x00000000,0x00000000,0x00000000,0x00000000,0x00000000,0x00000000,0x00000000,
 0x00000000,0x00000000,0x00000000,0x00000000,0x00000000,0x00000000,0x00000000,0x00000000,0x00000000,0x00000000,0x00000000,0x00000000,0x00000000,0x00000000,0x00000000,0x00000000,
};

template<int SA>
__device__ __forceinline__ void wgmma_main(float (&d)[80], uint64_t da, uint64_t db, int sd) {
  asm volatile("{\n.reg .pred p;\nsetp.ne.b32 p, %82, 0;\n"
    "wgmma.mma_async.sync.aligned.m64n160k16.f32.bf16.bf16 "
    "{%0, %1, %2, %3, %4, %5, %6, %7, %8, %9, %10, %11, %12, %13, %14, %15, %16, %17, %18, %19, %20, %21, %22, %23, %24, %25, %26, %27, %28, %29, %30, %31, %32, %33, %34, %35, %36, %37, %38, %39, %40, %41, %42, %43, %44, %45, %46, %47, %48, %49, %50, %51, %52, %53, %54, %55, %56, %57, %58, %59, %60, %61, %62, %63, %64, %65, %66, %67, %68, %69, %70, %71, %72, %73, %74, %75, %76, %77, %78, %79}, %80, %81, p, %83, 1, 1, 0;\n}\n"
    : "+f"(d[0]), "+f"(d[1]), "+f"(d[2]), "+f"(d[3]), "+f"(d[4]), "+f"(d[5]), "+f"(d[6]), "+f"(d[7]), "+f"(d[8]), "+f"(d[9]), "+f"(d[10]), "+f"(d[11]), "+f"(d[12]), "+f"(d[13]), "+f"(d[14]), "+f"(d[15]), "+f"(d[16]), "+f"(d[17]), "+f"(d[18]), "+f"(d[19]), "+f"(d[20]), "+f"(d[21]), "+f"(d[22]), "+f"(d[23]), "+f"(d[24]), "+f"(d[25]), "+f"(d[26]), "+f"(d[27]), "+f"(d[28]), "+f"(d[29]), "+f"(d[30]), "+f"(d[31]), "+f"(d[32]), "+f"(d[33]), "+f"(d[34]), "+f"(d[35]), "+f"(d[36]), "+f"(d[37]), "+f"(d[38]), "+f"(d[39]), "+f"(d[40]), "+f"(d[41]), "+f"(d[42]), "+f"(d[43]), "+f"(d[44]), "+f"(d[45]), "+f"(d[46]), "+f"(d[47]), "+f"(d[48]), "+f"(d[49]), "+f"(d[50]), "+f"(d[51]), "+f"(d[52]), "+f"(d[53]), "+f"(d[54]), "+f"(d[55]), "+f"(d[56]), "+f"(d[57]), "+f"(d[58]), "+f"(d[59]), "+f"(d[60]), "+f"(d[61]), "+f"(d[62]), "+f"(d[63]), "+f"(d[64]), "+f"(d[65]), "+f"(d[66]), "+f"(d[67]), "+f"(d[68]), "+f"(d[69]), "+f"(d[70]), "+f"(d[71]), "+f"(d[72]), "+f"(d[73]), "+f"(d[74]), "+f"(d[75]), "+f"(d[76]), "+f"(d[77]), "+f"(d[78]), "+f"(d[79])
    : "l"(da), "l"(db), "r"(sd), "n"(SA));
}
template<int SA>
__device__ __forceinline__ void wgmma_fwd(float (&d)[32], uint64_t da, uint64_t db, int sd) {
  asm volatile("{\n.reg .pred p;\nsetp.ne.b32 p, %34, 0;\n"
    "wgmma.mma_async.sync.aligned.m64n64k16.f32.bf16.bf16 "
    "{%0, %1, %2, %3, %4, %5, %6, %7, %8, %9, %10, %11, %12, %13, %14, %15, %16, %17, %18, %19, %20, %21, %22, %23, %24, %25, %26, %27, %28, %29, %30, %31}, %32, %33, p, %35, 1, 0, 1;\n}\n"
    : "+f"(d[0]), "+f"(d[1]), "+f"(d[2]), "+f"(d[3]), "+f"(d[4]), "+f"(d[5]), "+f"(d[6]), "+f"(d[7]), "+f"(d[8]), "+f"(d[9]), "+f"(d[10]), "+f"(d[11]), "+f"(d[12]), "+f"(d[13]), "+f"(d[14]), "+f"(d[15]), "+f"(d[16]), "+f"(d[17]), "+f"(d[18]), "+f"(d[19]), "+f"(d[20]), "+f"(d[21]), "+f"(d[22]), "+f"(d[23]), "+f"(d[24]), "+f"(d[25]), "+f"(d[26]), "+f"(d[27]), "+f"(d[28]), "+f"(d[29]), "+f"(d[30]), "+f"(d[31])
    : "l"(da), "l"(db), "r"(sd), "n"(SA));
}
template<int SA>
__device__ __forceinline__ void wgmma_inv(float (&d)[28], uint64_t da, uint64_t db, int sd) {
  asm volatile("{\n.reg .pred p;\nsetp.ne.b32 p, %30, 0;\n"
    "wgmma.mma_async.sync.aligned.m64n56k16.f32.bf16.bf16 "
    "{%0, %1, %2, %3, %4, %5, %6, %7, %8, %9, %10, %11, %12, %13, %14, %15, %16, %17, %18, %19, %20, %21, %22, %23, %24, %25, %26, %27}, %28, %29, p, %31, 1, 1, 0;\n}\n"
    : "+f"(d[0]), "+f"(d[1]), "+f"(d[2]), "+f"(d[3]), "+f"(d[4]), "+f"(d[5]), "+f"(d[6]), "+f"(d[7]), "+f"(d[8]), "+f"(d[9]), "+f"(d[10]), "+f"(d[11]), "+f"(d[12]), "+f"(d[13]), "+f"(d[14]), "+f"(d[15]), "+f"(d[16]), "+f"(d[17]), "+f"(d[18]), "+f"(d[19]), "+f"(d[20]), "+f"(d[21]), "+f"(d[22]), "+f"(d[23]), "+f"(d[24]), "+f"(d[25]), "+f"(d[26]), "+f"(d[27])
    : "l"(da), "l"(db), "r"(sd), "n"(SA));
}


__device__ __forceinline__ uint32_t s2u(const void* p) { return (uint32_t)__cvta_generic_to_shared(p); }
__device__ __forceinline__ void mbar_init(uint32_t a, int c) { asm volatile("mbarrier.init.shared::cta.b64 [%0], %1;" ::"r"(a), "r"(c)); }
__device__ __forceinline__ void mbar_expect(uint32_t a, int b) { asm volatile("mbarrier.arrive.expect_tx.shared::cta.b64 _, [%0], %1;" ::"r"(a), "r"(b) : "memory"); }
__device__ __forceinline__ void mbar_arrive(uint32_t a) { asm volatile("mbarrier.arrive.shared::cta.b64 _, [%0];" ::"r"(a) : "memory"); }
__device__ __forceinline__ void mbar_arrive_cluster(uint32_t a, uint32_t cta, uint32_t cnt) {
  asm volatile("{\n.reg .b32 r;\nmapa.shared::cluster.u32 r, %0, %1;\nmbarrier.arrive.shared::cluster.b64 _, [r], %2;\n}" ::"r"(a), "r"(cta), "r"(cnt) : "memory");
}
__device__ __forceinline__ void mbar_wait(uint32_t a, int ph) {
  asm volatile("{\n.reg .pred p;\n.reg .u32 c;\nmov.u32 c, 0;\nWAIT:\n"
               "mbarrier.try_wait.parity.shared::cta.b64 p, [%0], %1;\n@p bra DONE;\n"
               "add.u32 c, c, 1;\nsetp.lt.u32 p, c, 0x400000;\n@p bra WAIT;\ntrap;\nDONE:\n}" ::"r"(a), "r"(ph) : "memory");
}
__device__ __forceinline__ void flag_wait(const unsigned* p, unsigned target) {
  asm volatile("{\n.reg .pred p;\n.reg .u32 c, v;\nmov.u32 c, 0;\nWAIT:\n"
               "ld.acquire.gpu.global.u32 v, [%0];\nsetp.ge.u32 p, v, %1;\n@p bra DONE;\n"
               "add.u32 c, c, 1;\nsetp.lt.u32 p, c, 0x400000;\n@p bra WAIT;\ntrap;\nDONE:\n}" ::"l"(p), "r"(target) : "memory");
}
__device__ __forceinline__ bool elect_one() {
  uint32_t p;
  asm volatile("{\n.reg .pred P;\nelect.sync _|P, 0xffffffff;\nselp.u32 %0, 1, 0, P;\n}" : "=r"(p));
  return p != 0;
}
__device__ __forceinline__ void bulk_ld(uint32_t dst, const void* src, int bytes, uint32_t bar) {
  asm volatile("cp.async.bulk.shared::cluster.global.mbarrier::complete_tx::bytes [%0], [%1], %2, [%3];" ::"r"(dst), "l"(src), "r"(bytes), "r"(bar) : "memory");
}
__device__ __forceinline__ void bulk_ld_mc_h(uint32_t dst, const void* src, int bytes, uint32_t bar, uint16_t mask, uint64_t pol) {
  asm volatile("cp.async.bulk.shared::cluster.global.mbarrier::complete_tx::bytes.multicast::cluster.L2::cache_hint [%0], [%1], %2, [%3], %4, %5;" ::"r"(dst), "l"(src), "r"(bytes), "r"(bar), "h"(mask), "l"(pol) : "memory");
}
__device__ __forceinline__ void tma_ld2(uint32_t dst, const CUtensorMap* tm, int c0, int c1, uint32_t bar) {
  asm volatile("cp.async.bulk.tensor.2d.shared::cluster.global.mbarrier::complete_tx::bytes [%0], [%1, {%3,%4}], [%2];" ::"r"(dst), "l"(tm), "r"(bar), "r"(c0), "r"(c1) : "memory");
}
__device__ __forceinline__ void tma_ld3(uint32_t dst, const CUtensorMap* tm, int c0, int c1, int c2, uint32_t bar) {
  asm volatile("cp.async.bulk.tensor.3d.shared::cluster.global.mbarrier::complete_tx::bytes [%0], [%1, {%3,%4,%5}], [%2];" ::"r"(dst), "l"(tm), "r"(bar), "r"(c0), "r"(c1), "r"(c2) : "memory");
}
__device__ __forceinline__ void tma_ld3h(uint32_t dst, const CUtensorMap* tm, int c0, int c1, int c2, uint32_t bar, uint64_t pol) {
  asm volatile("cp.async.bulk.tensor.3d.shared::cluster.global.mbarrier::complete_tx::bytes.L2::cache_hint [%0], [%1, {%3,%4,%5}], [%2], %6;" ::"r"(dst), "l"(tm), "r"(bar), "r"(c0), "r"(c1), "r"(c2), "l"(pol) : "memory");
}
__device__ __forceinline__ uint64_t policy_evict_first() {
  uint64_t p;
  asm("createpolicy.fractional.L2::evict_first.b64 %0, 1.0;" : "=l"(p));
  return p;
}
__device__ __forceinline__ void tma_st3(const CUtensorMap* tm, uint32_t src, int c0, int c1, int c2) {
  asm volatile("cp.async.bulk.tensor.3d.global.shared::cta.bulk_group [%0, {%2,%3,%4}], [%1];" ::"l"(tm), "r"(src), "r"(c0), "r"(c1), "r"(c2) : "memory");
}
__device__ __forceinline__ void tma_st4(const CUtensorMap* tm, uint32_t src, int c0, int c1, int c2, int c3) {
  asm volatile("cp.async.bulk.tensor.4d.global.shared::cta.bulk_group [%0, {%2,%3,%4,%5}], [%1];" ::"l"(tm), "r"(src), "r"(c0), "r"(c1), "r"(c2), "r"(c3) : "memory");
}
__device__ __forceinline__ void tma_st5(const CUtensorMap* tm, uint32_t src, int c0) {
  asm volatile("cp.async.bulk.tensor.5d.global.shared::cta.bulk_group [%0, {%2,%3,%3,%3,%3}], [%1];" ::"l"(tm), "r"(src), "r"(c0), "r"(0) : "memory");
}
__device__ __forceinline__ void bulk_commit() { asm volatile("cp.async.bulk.commit_group;" ::: "memory"); }
template <int N> __device__ __forceinline__ void bulk_wait_read() { asm volatile("cp.async.bulk.wait_group.read %0;" ::"n"(N) : "memory"); }
template <int N> __device__ __forceinline__ void bulk_wait() { asm volatile("cp.async.bulk.wait_group %0;" ::"n"(N) : "memory"); }
__device__ __forceinline__ void fence_async_smem() { asm volatile("fence.proxy.async.shared::cta;" ::: "memory"); }
__device__ __forceinline__ void wg_fence() { asm volatile("wgmma.fence.sync.aligned;" ::: "memory"); }
__device__ __forceinline__ void wg_commit() { asm volatile("wgmma.commit_group.sync.aligned;" ::: "memory"); }
template <int N> __device__ __forceinline__ void wg_wait() { asm volatile("wgmma.wait_group.sync.aligned %0;" ::"n"(N) : "memory"); }
template <int R> __device__ __forceinline__ void fence_regs(float (&d)[R]) {
#pragma unroll
  for (int i = 0; i < R; i++) asm volatile("" : "+f"(d[i])::"memory");
}
__device__ __forceinline__ uint64_t mk_desc(uint32_t addr) {
  return (uint64_t)((addr & 0x3FFFF) >> 4) | (1ull << 16) | (64ull << 32) | (1ull << 62);
}
__device__ __forceinline__ uint32_t pack2(float lo, float hi) {
  uint32_t r;
  asm("cvt.rn.bf16x2.f32 %0, %1, %2;" : "=r"(r) : "f"(hi), "f"(lo));
  return r;
}
__device__ __forceinline__ void stsm4(uint32_t ad, uint32_t a, uint32_t b, uint32_t c, uint32_t d) {
  asm volatile("stmatrix.sync.aligned.m8n8.x4.shared.b16 [%0], {%1,%2,%3,%4};" ::"r"(ad), "r"(a), "r"(b), "r"(c), "r"(d) : "memory");
}
__device__ __forceinline__ void stsm4t(uint32_t ad, uint32_t a, uint32_t b, uint32_t c, uint32_t d) {
  asm volatile("stmatrix.sync.aligned.m8n8.x4.trans.shared.b16 [%0], {%1,%2,%3,%4};" ::"r"(ad), "r"(a), "r"(b), "r"(c), "r"(d) : "memory");
}

__device__ __forceinline__ void stsm2t(uint32_t ad, uint32_t a, uint32_t b) {
  asm volatile("stmatrix.sync.aligned.m8n8.x2.trans.shared.b16 [%0], {%1,%2};" ::"r"(ad), "r"(a), "r"(b) : "memory");
}
__device__ __forceinline__ void red_add(unsigned* p) { asm volatile("red.relaxed.gpu.global.add.u32 [%0], 1;" ::"l"(p) : "memory"); }
__device__ __forceinline__ void fence_release() { asm volatile("fence.release.gpu;" ::: "memory"); }
__device__ __forceinline__ void fence_async_global() { asm volatile("fence.proxy.async.global;" ::: "memory"); }
__device__ __forceinline__ void tma_pf3(const CUtensorMap* tm, int c0, int c1, int c2) {
  asm volatile("cp.async.bulk.prefetch.tensor.3d.L2.global [%0, {%1,%2,%3}];" ::"l"(tm), "r"(c0), "r"(c1), "r"(c2) : "memory");
}
__device__ __forceinline__ void tma_ld4(uint32_t dst, const CUtensorMap* tm, int c1, uint32_t bar) {
  asm volatile("cp.async.bulk.tensor.4d.shared::cluster.global.mbarrier::complete_tx::bytes [%0], [%1, {%4,%3,%4,%4}], [%2];" ::"r"(dst), "l"(tm), "r"(bar), "r"(c1), "r"(0) : "memory");
}
__device__ __forceinline__ void bulk_ld_mc(uint32_t dst, const void* src, int bytes, uint32_t bar, uint16_t mask) {
  asm volatile("cp.async.bulk.shared::cluster.global.mbarrier::complete_tx::bytes.multicast::cluster [%0], [%1], %2, [%3], %4;" ::"r"(dst), "l"(src), "r"(bytes), "r"(bar), "h"(mask) : "memory");
}

__device__ __forceinline__ unsigned flag_peek(const unsigned* p) {
  unsigned v;
  asm volatile("ld.acquire.gpu.global.u32 %0, [%1];" : "=r"(v) : "l"(p) : "memory");
  return v;
}
__device__ __forceinline__ int lane_id() {
  int l;
  asm volatile("mov.u32 %0, %%laneid;" : "=r"(l));
  return l;
}
__device__ __forceinline__ void poll64x4(const unsigned long long* p, unsigned long long (&v)[4]) {
  asm volatile("{\n.reg .pred p;\n.reg .u32 c;\n.reg .b64 t, u;\nmov.u32 c, 0;\nWAIT:\n"
               "ld.relaxed.gpu.global.u64 %0, [%4];\nld.relaxed.gpu.global.u64 %1, [%4+512];\n"
               "ld.relaxed.gpu.global.u64 %2, [%4+1024];\nld.relaxed.gpu.global.u64 %3, [%4+1536];\n"
               "or.b64 t, %0, %1;\nor.b64 u, %2, %3;\nor.b64 t, t, u;\nsetp.ge.s64 p, t, 0;\n@p bra DONE;\n"
               "add.u32 c, c, 1;\nsetp.lt.u32 p, c, 0x400000;\n@p bra WAIT;\ntrap;\nDONE:\n}"
               : "=l"(v[0]), "=l"(v[1]), "=l"(v[2]), "=l"(v[3]) : "l"(p) : "memory");
}

constexpr int G_STAGE = WBLK + XBLK;
constexpr int OFF_XR = 4 * G_STAGE;
constexpr int OFF_WS = OFF_XR + 6 * 8192;
constexpr int OFF_F = OFF_WS + 2 * 8192;
constexpr int OFF_WRAW = OFF_F + 8192;
constexpr int OFF_BAR = OFF_WRAW + 8192;
constexpr int OFF_GB = OFF_BAR + 1024;
constexpr int SMEM_BYTES = OFF_GB + 512;
constexpr int OFF_H0B = 10 * 8192;
constexpr int OFF_E = OFF_WRAW + 3072;
constexpr int B_RAWX = 0, B_F = 48, B_ROLE = 56, B_H0 = 80, B_H1 = 96, B_YFREE = 120, B_H0C = 136,
              B_EMPTY = 144,
              B_STGX = 192, B_STGW = 240, B_Y = 256, B_OUT = 272, B_YP = 352,
              B_FULL = 432, B_RAWW = 464, B_DONE = 496, S_ROLE = 576, S_PROBE = 592;

static_assert(B_YP == B_OUT + 80, "");
struct Maps { CUtensorMap x, we, wo, xst[2], wst, yld[2], out, xe[2], w30; };

__device__ __forceinline__ int chunk_of(int n) { return n < 16 ? n : 31 - n; }
__device__ __forceinline__ bool has_x2(int id, int n, int g) { return (((id >> 5) ^ n) & 1) == 0 && ((n >> 1) & 1) == g; }
__device__ __forceinline__ int w_row(int id) { return (id & 62) | (id >> 6); }
__device__ __forceinline__ uint32_t x_base(int s, int idx, uint32_t pgmask, int& par) {
  const int page = idx >> 3, o = idx & 7;
  par = (s ^ (pgmask >> page) ^ __popc(o)) & 1;
  return (page << 21) | ((o & 3) << 16) | ((o >> 2) << 19);
}
__device__ __forceinline__ uint32_t spread5(int i) { return (((i >> 1) & 3) << 14) | (((i >> 3) & 1) << 18) | ((i >> 4) << 20) | ((i & 1) << 13); }
__device__ __forceinline__ int y_idx(int half, int dq, int piece) { return (PG_Y + 5 * half) * 8 + (dq * 5 + piece) * 2; }
__device__ __forceinline__ int tail_win(int tr) { return (tr & 1) + 4 * (tr >> 1); }
__device__ __forceinline__ uint32_t read_info(uint32_t bar, int i) {
  uint32_t v;
  mbar_wait(bar + B_ROLE + 8 * i, 0);
  asm volatile("ld.shared.b32 %0, [%1];" : "=r"(v) : "r"(bar + S_ROLE + 4 * i) : "memory");
  return v;
}
__device__ __forceinline__ void send_info(uint32_t bar, int i, uint32_t v) {
#pragma unroll
  for (int r = 0; r < 2; r++)
    asm volatile("{\n.reg .b32 a, m;\nmapa.shared::cluster.u32 a, %0, %2;\nmapa.shared::cluster.u32 m, %1, %2;\n"
                 "st.async.weak.shared::cluster.mbarrier::complete_tx::bytes.b32 [a], %3, [m];\n}"
                 ::"r"(bar + S_ROLE + 4 * i), "r"(bar + B_ROLE + 8 * i), "r"(r), "r"(v) : "memory");
}
__device__ __forceinline__ unsigned probe(uint8_t* p, int lane) {
  if (lane < 2) *(uint4*)(p + lane * 16) = make_uint4(0, 0, 0, 0);
  __syncwarp();
  unsigned v, t0 = 0, t1 = 0;
  if (lane == 0) {
    asm volatile("mov.u32 %0, %%clock;" : "=r"(t0)::"memory");
    asm volatile("atom.relaxed.gpu.global.exch.b32 %0, [%1], 0;" : "=r"(v) : "l"(p) : "memory");
    asm volatile("{\n.reg .pred p;\nsetp.ne.u32 p, %1, 0xffffffff;\nmov.u32 %0, 0;\n@p mov.u32 %0, %%clock;\n}" : "=r"(t1) : "r"(v) : "memory");
  }
  return t1 - t0;
}

template <bool ISX>
__device__ __forceinline__ void t_issue(float (&t)[32], uint32_t sb, uint32_t raw) {
  const uint64_t da = mk_desc(sb + OFF_F), db = mk_desc(raw);
  wg_fence();
#pragma unroll
  for (int kk = 0; kk < (ISX ? 4 : 1); kk++) wgmma_fwd<1>(t, da + 2 * kk, db + 128 * kk, kk);
  wg_commit();
}
template <bool ISX>
__device__ __forceinline__ void t_finish(float (&t)[32], uint32_t dst, uint32_t sbar, int sw, int wg, int w, int lane) {
  fence_regs(t);
  if (ISX) asm volatile("bar.sync %0, 128;" ::"r"(1 + wg) : "memory");
  const int m = lane >> 3, r = lane & 7;
  uint32_t ad = dst + (8 * w + r) * 128;
  if (ISX) ad += ((((m & 1) * 4 + (m >> 1)) ^ sw ^ r) << 4);
  else ad += (m & 1) * 4096 + (((m >> 1) ^ sw ^ r) << 4);
#pragma unroll
  for (int i = 0; i < 4; i++) {
    const uint32_t a = ISX ? ((ad ^ ((i & 1) * 32)) + (i >> 1) * 4096) : (ad ^ (i * 32));
    stsm4(a, pack2(t[8 * i], t[8 * i + 1]), pack2(t[8 * i + 2], t[8 * i + 3]), pack2(t[8 * i + 4], t[8 * i + 5]), pack2(t[8 * i + 6], t[8 * i + 7]));
  }
  __syncwarp();
  if (lane == 0) mbar_arrive(sbar);
}
template <int NT, int K0, int K1>
__device__ __forceinline__ void batch(float (&yr)[80], float (&yi)[80], float (&t)[32], uint32_t st, int wg, int sd, uint32_t fa, uint32_t raw) {
  const uint64_t w0 = mk_desc(st + wg * 8192), x0 = mk_desc(st + WBLK);
  const uint64_t da = mk_desc(fa), db = mk_desc(raw);
  wg_fence();
  if (NT) {
#pragma unroll
    for (int kk = 0; kk < NT; kk++) wgmma_fwd<1>(t, da + 2 * kk, db + 128 * kk, kk);
    wg_commit();
  }
#pragma unroll
  for (int kk = K0; kk < K1; kk++) {
    const uint64_t wr = w0 + kk * 128, wi = wr + 256, xr = x0 + kk * 2, xi = xr + 4;
    wgmma_main<1>(yr, wr, xr, kk ? 1 : sd);
    wgmma_main<1>(yi, wr, xi, kk ? 1 : sd);
    wgmma_main<1>(yr, wi, xi, 1);
    wgmma_main<-1>(yi, wi, xr, 1);
  }
  wg_commit();
}

#define X_WAIT() mbar_wait(bar + B_RAWX + 8 * (wg * 3 + xs), xph)
#define X_ISSUE() t_issue<true>(t, sb, sb + OFF_XR + (wg * 3 + xs) * 8192)
#define X_FINISH(sw) do { t_finish<true>(t, sb + OFF_XR + (wg * 3 + xs) * 8192, bar + B_STGX + 8 * (wg * 3 + xs), sw, wg, w, lane); \
                          if (++xs == 3) { xs = 0; xph ^= 1; } } while (0)
#define W_WAIT(n) mbar_wait(bar + B_RAWW + 8 * (wg * 2 + ((n) & 1)), ((n) >> 1) & 1)
#define WRAW(n) (sb + OFF_WRAW + (wg * 2 + ((n) & 1)) * 2048)
#define W_FINISH() t_finish<false>(t, sb + OFF_WS + wg * 8192, bar + B_STGW + 8 * wg, w_row(id) & 7, wg, w, lane)

__device__ __forceinline__ void gelu_store(float (&hz)[28], uint32_t ad) {
#pragma unroll
  for (int i = 0; i < 28; i++) {
    const float in = hz[i] * fmaf(hz[i] * hz[i], 8.f * 0.044715f * 0.7978845608028654f, 2.f * 0.7978845608028654f);
    float th;
    asm("tanh.approx.f32 %0, %1;" : "=f"(th) : "f"(in));
    hz[i] = fmaf(hz[i], th, hz[i]);
  }
#pragma unroll
  for (int jj = 0; jj < 3; jj++) {
    const float* c = hz + 8 * jj;
    stsm4t(ad + jj * 2048, pack2(c[0], c[1]), pack2(c[2], c[3]), pack2(c[4], c[5]), pack2(c[6], c[7]));
  }
  stsm2t(ad + 3 * 2048, pack2(hz[24], hz[25]), pack2(hz[26], hz[27]));
}

#define ONE(...) do { if (elect_one()) { __VA_ARGS__; } } while (0)
template <int g>
__device__ __forceinline__ void manager(const Maps& tm, const unsigned* ctr, const uint32_t sb, const int id) {
  const uint32_t bar = sb + OFF_BAR, rank = id & 1;
  const uint64_t pol = policy_evict_first();
  const int cl = w_row(id), b = id >> 6, u = (id >> 1) & 31;
  const unsigned* pf = ctr + (C_LOADED + (((cl >> 5) - WR) >> 1)) * 32 + (((cl >> 5) - WR) & 1);
  int li = 0;
  auto refill = [&](int sl, bool wait) {
    const uint32_t fb = bar + B_RAWX + 8 * (g * 3 + sl);
    int row = ((li & 1) ? 128 + (id & 31) : 2 * (id & 63) + g) * MT, col = (li >> 1) * 64;
    asm volatile("" : "+r"(row), "+r"(col));
    ONE(if (li < 32) mbar_expect(fb, 8192);
        if (wait) bulk_wait_read<0>();
        if (li < 32) tma_ld3h(sb + OFF_XR + (g * 3 + sl) * 8192, &tm.x, col, row, b, fb, pol));
    li += (li & 1) || has_x2(id, li >> 1, g) ? 1 : 2;
  };
#pragma unroll 1
  for (int sl = 0; sl < 3; sl++) refill(sl, false);
  int xs = 0, xph = 0, yp = 0;
  int wrow = (cl >> 5) * (WSLOT / 128) + rank * 128 + g * 64 + (cl & 31);
  const uint32_t pgmask = __shfl_sync(0xffffffffu, read_info(bar, 1), 0);
  auto store_y = [&](int half, int piece, uint32_t buf, uint32_t wait_bar, int ph) {
    int par;
    int c = x_base(b, y_idx(half, rank * 2 + g, piece) + (u >> 4), pgmask, par);
    c = (c + (par << 12) + (u & 15) * 256) >> 1;
    const CUtensorMap* m = &tm.xst[par];
    asm volatile("" : "+r"(c), "+l"(m));
    if (wait_bar) mbar_wait(wait_bar, ph);
    ONE(fence_async_smem(); tma_st5(m, buf, c); tma_st5(m, buf + 4096, c + 64));
  };
  mbar_wait(bar + B_STGW + 8 * g, 0);
  ONE(fence_async_smem(); tma_st4(&tm.wst, sb + OFF_WS + g * 8192, 0, 0, 0, wrow); bulk_commit());
#pragma unroll 1
  for (int n = 0; n < 32; n++) {
    unsigned freed = 128;
    if (2 * n + (cl >> 5) >= WR) asm volatile("ld.relaxed.gpu.global.u32 %0, [%1];" : "=r"(freed) : "l"(pf + n * 32) : "memory");
    if (n < 16) {
#pragma unroll 1
      for (int j = 0; j < (has_x2(id, n, g) ? 2 : 1); j++) {
        const int t = j ? 128 + (id & 31) : 2 * (id & 63) + g;
        int par0, par1;
        const uint32_t off0 = x_base(b, n * 10 + (t >> 5), pgmask, par0), off1 = x_base(b, n * 10 + 5 + (t >> 5), pgmask, par1);
        uint32_t buf = sb + OFF_XR + (g * 3 + xs) * 8192;
        int c0 = (off0 + (par0 << 12) + (t & 31) * 128) >> 1, c1 = (off1 + (par1 << 12) + (t & 31) * 128) >> 1;
        const CUtensorMap *m0 = &tm.xst[par0], *m1 = &tm.xst[par1];
        asm volatile("" : "+r"(buf), "+r"(c0), "+r"(c1), "+l"(m0), "+l"(m1));
        mbar_wait(bar + B_STGX + 8 * (g * 3 + xs), xph);
        ONE(fence_async_smem(); tma_st5(m0, buf, c0); tma_st5(m1, buf + 4096, c1); bulk_commit());
        refill(xs, true);
        if (++xs == 3) { xs = 0; xph ^= 1; }
      }
    }
    if (n > 16 + LW && n <= YFLUSH) {
#pragma unroll 1
      do {
        store_y(0, yp, sb + OFF_XR + (g * 3 + (yp < 3 ? yp : yp - 3)) * 8192, (yp == 0 || yp == 3) ? bar + B_Y + 8 * g : 0, yp & 1);
      } while (++yp < 2);
      ONE(bulk_commit(); bulk_wait_read<0>(); if (yp == 2) mbar_arrive(bar + B_YFREE + 8 * g));
    }
    if (__shfl_sync(0xffffffffu, freed, 0) < 128) flag_wait(pf + n * 32, 128);
    const int cp = chunk_of(n + 2) * 64 + cl, sl = g * 2 + (n & 1);
    if (n) mbar_wait(bar + B_STGW + 8 * g, n & 1);
    ONE(if (n) {
          fence_async_smem();
          tma_st4(&tm.wst, sb + OFF_WS + g * 8192, 0, 0, 0, wrow);
          bulk_commit();
        }
        if (n < 30) {
          mbar_expect(bar + B_RAWW + 8 * sl, 2048);
          tma_ld3h(sb + OFF_WRAW + sl * 2048, &tm.we + (cp >> 9), 0, 0, (cp & 511) * 8 + ((n + 2) >> 4) * 4 + rank * 2 + g, bar + B_RAWW + 8 * sl, pol);
        }
        if (n < 4) {
          tma_pf3(&tm.we, 0, 0, ((n + 4) * 64 + cl) * 8 + rank * 2 + g);
          tma_pf3(&tm.wo, 0, 0, (n * 64 + cl) * 8 + rank * 2 + g);
          tma_pf3(&tm.wo, 0, 0, ((n + 4) * 64 + cl) * 8 + rank * 2 + g);
        }
        bulk_wait<0>();
        mbar_arrive(bar + B_DONE + 8 * (n & 7));
        mbar_arrive(bar + B_RAWW + 8 * (sl ^ 1)));
    if (n < 15) {
      const unsigned t0 = clock();
      while ((unsigned)clock() - t0 < 600) {}
    }
    wrow += 2 * WSLOT / 128;
    if (wrow >= WR * WSLOT / 128) wrow -= WR * WSLOT / 128;
  }
  ONE(asm volatile("prefetch.tensormap [%0];" ::"l"(g ? &tm.out : &tm.xst[b]) : "memory"));
  flag_wait(&ctr[(C_LOADED + 31) * 32 + 1], 128);
#pragma unroll 1
  for (int p = 0; p < 5; p++) {
    store_y(1, p, sb + (p * 2 + g) * 8192, bar + B_YP + 8 * (g * 5 + p), 0);
    if (p == YA - 1) ONE(bulk_commit());
  }
  ONE(bulk_commit(); bulk_wait<1>(); mbar_arrive(bar + B_DONE); bulk_wait<0>(); mbar_arrive(bar + B_DONE + 8));
  mbar_wait(bar + B_H1, 0);
#pragma unroll 1
  for (int i = 0; i < 10; i++) {
    const int hf = i >= 5, k = i - 5 * hf;
    const uint32_t buf = sb + (hf ? 0 : k < 4 ? OFF_XR : OFF_H0B - 65536) + (2 * k + g) * 8192;
    mbar_wait(bar + B_OUT + 80 * hf + 8 * (g * 5 + k), hf);
    ONE(fence_async_smem();
        tma_st3(&tm.out, buf, (hf * 4 + rank * 2 + (u & 1)) * 64, (32 * k + tail_win(u >> 1) + 2 * g) * MT, b);
        bulk_commit());
  }
  ONE(bulk_wait_read<0>());
}

__global__ void __cluster_dims__(2, 1, 1) __launch_bounds__(512, 1)
k1_main(uint8_t* xbuf, const void* __restrict__ fimg, const __nv_bfloat16* __restrict__ gamma,
        const __nv_bfloat16* __restrict__ beta, const __grid_constant__ Maps tm) {
  extern __shared__ __align__(1024) uint8_t smem_raw[];
  const uint32_t sb = s2u(smem_raw);
  const uint32_t bar = sb + OFF_BAR;
  const int warp = __shfl_sync(0xffffffffu, threadIdx.x >> 5, 0);
  const int bid = blockIdx.x;
  unsigned* ctr = (unsigned*)(xbuf + CTR_OFF);
  const uint32_t rank = bid & 1;
  if (bid == 0 && threadIdx.x < 4) asm volatile("st.relaxed.gpu.global.u64 [%0], %1;" ::"l"(&ctr[C_REG * 32 + 2 * threadIdx.x]), "l"(1ull << 63) : "memory");
  if (warp >= 12) {
    asm volatile("setmaxnreg.dec.sync.aligned.u32 24;");
    asm volatile("barrier.cluster.arrive.relaxed.aligned;" ::: "memory");
    {
      const int lane = lane_id(), k = bid >> 1;
      if (rank == 0 || k < XPAGES) {
        const uint32_t off = rank ? (k << 21) + 0xb0000 : (XPAGES << 21) + ((k >> 6) << 18) + (((k >> 4) & 3) << 14) + (k & 15) * 128;
        const unsigned lat = probe(xbuf + off + (warp & 1) * 4096 + (warp & 2) * 1024, lane);
        if (lane == 0) asm volatile("st.shared.b32 [%0], %1;" ::"r"(bar + S_PROBE + 4 * (warp & 3)), "r"(lat) : "memory");
      }
      __syncwarp();
      asm volatile("bar.sync 4, 128;" ::: "memory");
      asm volatile("barrier.cluster.wait.aligned;" ::: "memory");
      if (warp == 14 && lane == 0) {
        uint32_t l0, l1, l2, l3;
        asm volatile("ld.shared.v4.b32 {%0, %1, %2, %3}, [%4];" : "=r"(l0), "=r"(l1), "=r"(l2), "=r"(l3) : "r"(bar + S_PROBE) : "memory");
        const int near = min(l1, l3) < min(l0, l2);
        if (rank) {
          send_info(bar, 2, near);
        } else {
          unsigned long long add = 1ull << (8 * near), v, *reg = (unsigned long long*)&ctr[C_REG * 32];
          if (k < XPAGES) add += (unsigned long long)(read_info(bar, 2) ^ near ^ 1) << (16 + k);
          asm volatile("{\n.reg .pred p;\n.reg .u32 c;\nmov.u32 c, 0;\nAGAIN:\n"
                       "atom.relaxed.gpu.global.add.u64 %0, [%1], %2;\nsetp.lt.s64 p, %0, 0;\n@p bra DONE;\n"
                       "add.u32 c, c, 1;\nsetp.lt.u32 p, c, 0x8000;\n@p bra AGAIN;\ntrap;\nDONE:\n}" : "=l"(v) : "l"(reg), "l"(add) : "memory");
          const int ticket = (v >> (8 * near)) & 255;
          if (ticket < 32) send_info(bar, 0, near * 32 + ticket);
          asm volatile("{\n.reg .pred p;\n.reg .u32 c, a, b;\nmov.u32 c, 0;\nWAIT:\n"
                       "ld.relaxed.gpu.global.u64 %0, [%1];\ncvt.u32.u64 a, %0;\nbfe.u32 b, a, 8, 8;\nand.b32 a, a, 255;\nadd.u32 a, a, b;\n"
                       "setp.ge.u32 p, a, 66;\n@p bra DONE;\n"
                       "add.u32 c, c, 1;\nsetp.lt.u32 p, c, 0x400000;\n@p bra WAIT;\ntrap;\nDONE:\n}" : "=l"(v) : "l"(reg) : "memory");
          if (ticket >= 32) {
            const int j = ticket - 32 + (int)((v >> (8 * (near ^ 1))) & 255);
            send_info(bar, 0, j < 32 ? (near ^ 1) * 32 + j : (near == 0 && ticket == 32 && j == 33) ? 64 : 32 + j);
          }
          send_info(bar, 1, (uint32_t)(v >> 16));
        }
      }
      __syncwarp();
      const int role = read_info(bar, 0);
      if (role < 64 && warp - 12 < NFL && elect_one()) {
#pragma unroll 1
        for (int n = warp - 12; n < 34; n += NFL) {
          mbar_wait(bar + B_DONE + 8 * (n & 7), (n >> 3) & 1);
          fence_release();
          if (n < 32) {
            red_add(&ctr[(C_FLAG + n + C_SIDE * ((role >> 5) ^ 1)) * 32]);
            red_add(&ctr[(C_FLAG + n + C_SIDE * (role >> 5)) * 32]);
          } else {
            red_add(&ctr[(C_Y + 2 * (n - 32) + rank + C_SIDE * (role >> 5)) * 32]);
          }
        }
      }
      if (role < 64 && warp == 15 && elect_one()) {
#pragma unroll 1
        for (int v = 0; v < 64; v++) {
          mbar_wait(bar + B_FULL + 8 * (v & 3), (v >> 2) & 1);
          mbar_arrive(bar + B_EMPTY + 8 * (v & 3));
          if (v < 64 - WR || v == 63) {
            red_add(&ctr[(C_LOADED + (v >> 1)) * 32 + (v & 1)]);
            red_add(&ctr[(C_LOADED + (v >> 1) + C_SIDE) * 32 + (v & 1)]);
          }
        }
      }
      __syncwarp();
    }
    asm volatile("barrier.cluster.arrive.relaxed.aligned;\nbarrier.cluster.wait.aligned;" ::: "memory");
    return;
  } else {
    if (elect_one()) {
      if (warp >= 6) asm volatile("prefetch.tensormap [%0];" ::"l"(&tm.x + (warp - 6)) : "memory");
      const int cnt = warp < 3 ? 1 : warp == 3 ? 5 : warp < 9 ? 4 : 2;
#pragma unroll
      for (int i = 0; i < 6; i++) mbar_init(bar + warp * 48 + 8 * i, cnt);
      asm volatile("fence.mbarrier_init.release.cluster;" ::: "memory");
      if (warp == 1) {
        mbar_expect(bar + B_F, 8192);
        bulk_ld(sb + OFF_F, fimg, 8192, bar + B_F);
        mbar_expect(bar + B_ROLE, 4);
        mbar_expect(bar + B_ROLE + 8, 4);
        mbar_expect(bar + B_ROLE + 16, 4);
      }
    }
    __syncwarp();
    asm volatile("bar.sync 0, 384;" ::: "memory");
    asm volatile("barrier.cluster.arrive.relaxed.aligned;" ::: "memory");
    if (bid < 128 && warp < 4 && elect_one()) {
      const int g = warp & 1;
      if (warp < 2) {
        tma_pf3(&tm.x, 0, (2 * (bid & 63) + g) * MT, bid >> 6);
        if (has_x2(bid, 0, g)) tma_pf3(&tm.x, 0, (128 + (bid & 31)) * MT, bid >> 6);
      } else {
        tma_pf3(&tm.we, 0, 0, (bid >> 1) * 8 + rank * 2 + g);
      }
    }
    __syncwarp();
  }
  if (warp >= 8) {
    asm volatile("setmaxnreg.dec.sync.aligned.u32 40;");
    asm volatile("barrier.cluster.wait.aligned;" ::: "memory");
    const int role = __shfl_sync(0xffffffffu, read_info(bar, 0), 0);
    const unsigned* lctr = ctr + (role >> 5) * C_SIDE * 32;
    if (role >= 64) {
    } else if (warp == 9 || warp == 10) {
      asm volatile("barrier.cluster.arrive.relaxed.aligned;" ::: "memory");
      if (warp == 9) manager<0>(tm, lctr, sb, role * 2 + rank); else manager<1>(tm, lctr, sb, role * 2 + rank);
      __syncwarp();
      asm volatile("barrier.cluster.wait.aligned;" ::: "memory");
      return;
    } else if (warp == 11) {
      const uint8_t* ws = xbuf + (PG_W << 21) + ((role & 31) * 2 + rank) * WBLK;
      int slot = 0;
#pragma unroll 1
      for (int v = 0; v < 64; v++) {
        const uint8_t* src = ws + (size_t)slot * WSLOT;
        uint32_t dst = sb + (v & 3) * G_STAGE, fb = bar + B_FULL + 8 * (v & 3);
        asm volatile("" : "+l"(src), "+r"(dst), "+r"(fb));
        if (++slot == WR) slot = 0;
        const unsigned* fp = &lctr[(C_FLAG + (v >> 1)) * 32];
        const bool ready = (v & 1) || __shfl_sync(0xffffffffu, flag_peek(fp), 0) >= 128;
        mbar_wait(bar + B_EMPTY + 8 * (v & 3), ((v >> 2) & 1) ^ 1);
        ONE(mbar_expect(fb, WBLK));
        if (!ready) flag_wait(fp, 128);
        ONE(fence_async_global(); bulk_ld(dst, src, WBLK, fb));
      }
    } else {
      const uint32_t pgmask = __shfl_sync(0xffffffffu, read_info(bar, 1), 0);
      const int b = role >> 5, u = role & 31;
      const uint64_t pef = policy_evict_first();
      const uint8_t* xs = xbuf + spread5(u);
      const int skip = rank * 2048;
#pragma unroll 1
      for (int v = 0; v < 64; v++) {
        const int n = v >> 1;
        uint32_t dst = sb + (v & 3) * G_STAGE + WBLK + rank * 8192, fb = bar + B_FULL + 8 * (v & 3);
        const uint8_t* src[3];
#pragma unroll
        for (int g = 0; g < 3; g++) {
          int par;
          const uint32_t o = x_base(b ^ u, chunk_of(n) * 10 + (v & 1) * 5 + rank * 2 + g, pgmask, par);
          src[g] = xs + o + (par << 12) + (g ? 0 : skip);
        }
        asm volatile("" : "+l"(src[0]), "+l"(src[1]), "+l"(src[2]), "+r"(dst), "+r"(fb));
        const unsigned* fp = &lctr[(C_FLAG + n) * 32];
        const bool ready = (v & 1) || v >= 32 || __shfl_sync(0xffffffffu, flag_peek(fp), 0) >= 128;
        mbar_wait(bar + B_EMPTY + 8 * (v & 3), ((v >> 2) & 1) ^ 1);
        ONE(mbar_expect(fb, XBLK));
        if (!ready) flag_wait(fp, 128);
        ONE(fence_async_global();
            if (n < XKEEP || n >= 16) {
              bulk_ld_mc_h(dst + skip, src[0], 4096 - skip, fb, 3, pef);
              bulk_ld_mc_h(dst + 4096, src[1], 4096, fb, 3, pef);
              bulk_ld_mc_h(dst + 8192, src[2], 2048 + skip, fb, 3, pef);
            } else {
              bulk_ld_mc(dst + skip, src[0], 4096 - skip, fb, 3);
              bulk_ld_mc(dst + 4096, src[1], 4096, fb, 3);
              bulk_ld_mc(dst + 8192, src[2], 2048 + skip, fb, 3);
            });
      }
      const int dq = rank * 2 + (u & 1), t0 = (u >> 1) * 10, tw = tail_win(u >> 1);
      int row[5];
      const CUtensorMap* mp[5];
      auto locate = [&](int half) {
#pragma unroll
        for (int k = 0; k < 5; k++) {
          int par;
          row[k] = x_base(b ^ tw, y_idx(half, dq, k), pgmask, par);
          row[k] = (row[k] + spread5(tw) + (par << 12)) >> 7;
          mp[k] = &tm.yld[par];
          asm volatile("" : "+r"(row[k]), "+l"(mp[k]));
        }
      };
      locate(0);
      flag_wait(&ctr[C_E * 32], 4);
      flag_wait(&lctr[(C_FLAG + YFLUSH) * 32], 128);
      ONE(fence_async_global();
          mbar_expect(bar + B_H0C, 6 * 8192);
          for (int i = 0; i < 3; i++) tma_ld4(sb + OFF_XR + i * 16384, mp[i], row[i], bar + B_H0C));
      static_assert(YFLUSH >= 23, "phase of the B_DONE ring");
      mbar_wait(bar + B_DONE + 8 * 7, 1);
      ONE(mbar_expect(bar + B_H0, 2 * 8192 + 7168 + 5120 + 512);
          bulk_ld(sb + OFF_F, g_Gimg, 7168, bar + B_H0);
          tma_ld4(sb + OFF_WS, mp[3], row[3], bar + B_H0);
          for (int hf = 0; hf < 2; hf++) {
            bulk_ld(sb + OFF_E + hf * 2560, g_E + ((b * 8 + hf * 4 + dq) * NT + t0) * 64, 2560, bar + B_H0);
            bulk_ld(sb + OFF_GB + hf * 256, gamma + (hf * 4 + dq) * 64, 128, bar + B_H0);
            bulk_ld(sb + OFF_GB + hf * 256 + 128, beta + (hf * 4 + dq) * 64, 128, bar + B_H0);
          });
      mbar_wait(bar + B_EMPTY + 8 * 2, 1);
      ONE(mbar_expect(bar + B_H0 + 8, 16384);
          tma_ld4(sb + OFF_H0B, mp[4], row[4], bar + B_H0 + 8);
          for (int i = 0; i < 3; i++) mbar_expect(bar + B_H1 + 8 * i, i < 2 ? 32768 : 16384));
      locate(1);
      flag_wait(&lctr[(C_Y + rank) * 32], 32);
      ONE(fence_async_global();
          for (int i = 0; i < YA; i++) tma_ld4(sb + i * 16384, mp[i], row[i], bar + B_H1 + 8 * (i >> 1)));
      flag_wait(&lctr[(C_Y + 2 + rank) * 32], 32);
      ONE(fence_async_global();
          for (int i = YA; i < 5; i++) tma_ld4(sb + i * 16384, mp[i], row[i], bar + B_H1 + 8 * (i >> 1)));
      const int lane = lane_id();
      unsigned old = 0;
      if (lane == 0) old = atomicAdd(&ctr[C_EXIT * 32], 1);
      if (__shfl_sync(0xffffffffu, old, 0) == 127) {
#pragma unroll
        for (int i = 0; i < 6; i++) *(uint4*)&ctr[((i >> 1) * 128 + (i & 1) * C_SIDE + lane) * 32] = make_uint4(0, 0, 0, 0);
      }
    }
    __syncwarp();
    asm volatile("barrier.cluster.arrive.relaxed.aligned;\nbarrier.cluster.wait.aligned;" ::: "memory");
  } else {
    asm volatile("setmaxnreg.inc.sync.aligned.u32 224;");
    const int wg = warp >> 2, w = warp & 3;
    int lane = lane_id();
    asm volatile("barrier.cluster.wait.aligned;" ::: "memory");
    mbar_wait(bar + B_F, 0);
    const int id = __shfl_sync(0xffffffffu, read_info(bar, 0), 0) * 2 + rank;
    if (id >= 128) {
      float ea[80], eb[80];
      const int b = (id >> 1) & 1;
      constexpr int ES = 32768 + 2 * XBLK;
#pragma unroll 1
      for (int k = -3; k < 8; k++) {
        const int sl = (k + 3) % 3;
        if (k >= 0) {
          mbar_wait(bar + B_RAWX + 8 * sl, (k / 3) & 1);
          const uint64_t da = mk_desc(sb + sl * ES + wg * 16384), db = mk_desc(sb + sl * ES + 32768);
          wg_fence();
#pragma unroll
          for (int kk = 0; kk < 8; kk++) {
            const uint64_t a0 = da + (kk & 3) * 128, b0 = db + (kk & 3) * 2 + (kk >> 2) * (XBLK >> 4);
            wgmma_main<1>(ea, a0, b0, (k | kk) != 0);
            wgmma_main<1>(eb, a0 + 512, b0, (k | kk) != 0);
          }
          wg_commit();
          wg_wait<0>();
          asm volatile("bar.sync 3, 256;" ::: "memory");
        }
        if (k + 3 < 8 && warp == 0 && elect_one()) {
          if (k == -3) {
            for (int i = 0; i < 64; i++) {
              unsigned v;
              asm volatile("ld.relaxed.gpu.global.u32 %0, [%1];" : "=r"(v) : "l"(&ctr[(C_FLAG + 14) * 32]) : "memory");
              if (v >= 128) break;
              __nanosleep(500);
            }
          }
          const uint32_t dst = sb + sl * ES, fb = bar + B_RAWX + 8 * sl;
          mbar_expect(fb, ES);
          for (int q = 0; q < 4; q++) tma_ld2(dst + q * 8192, &tm.w30, rank * 256 + q * 64, (k + 3) * 64, fb);
          for (int q = 0; q < 2; q++) tma_ld3(dst + 32768 + q * XBLK, &tm.xe[q], (k + 3) * 64, 0, b, fb);
        }
        __syncwarp();
      }
      fence_regs(ea);
      fence_regs(eb);
      float* e0 = g_E + ((b * 8 + rank * 4 + wg * 2) * NT + 10 * (lane & 2) + (lane & 1)) * 64 + 16 * w + (lane >> 2);
#pragma unroll
      for (int i = 0; i < 80; i++) {
        const int o = (40 * ((i >> 2) & 3) + 2 * (i >> 4) + 10 * (i & 1)) * 64 + ((i >> 1) & 1) * 8;
        e0[o] = ea[i];
        e0[o + NT * 64] = eb[i];
      }
      asm volatile("bar.sync 3, 256;" ::: "memory");
      if (threadIdx.x == 0) {
        fence_release();
        red_add(&ctr[C_E * 32]);
      }
      __syncwarp();
      asm volatile("barrier.cluster.arrive.relaxed.aligned;\nbarrier.cluster.wait.aligned;" ::: "memory");
      return;
    }
    if (w < 2 && elect_one()) {
      const uint32_t fb = bar + B_RAWW + 8 * (wg * 2 + w);
      mbar_expect(fb, 2048);
      tma_ld3h(sb + OFF_WRAW + (wg * 2 + w) * 2048, &tm.we, 0, 0, (w * 64 + w_row(id)) * 8 + rank * 2 + wg, fb, policy_evict_first());
      if (!w) mbar_arrive(fb);
    }
    __syncwarp();
    {
      float yr[80], yi[80], t[32];
      int xs = 0, xph = 0;
      W_WAIT(0);
      t_issue<false>(t, sb, WRAW(0));
      wg_wait<0>();
      W_FINISH();
#pragma unroll 1
      for (int m = 0; m <= LW; m++) {
        X_WAIT();
        X_ISSUE();
        wg_wait<0>();
        X_FINISH((2 * id + wg) & 7);
        if (has_x2(id, m, wg)) {
          X_WAIT();
          X_ISSUE();
          wg_wait<0>();
          X_FINISH(id & 7);
        }
        if (m < LW && m) {
          W_WAIT(m);
          t_issue<false>(t, sb, WRAW(m));
          wg_wait<0>();
          W_FINISH();
        }
      }
      const int ym = lane >> 3, yr8 = lane & 7;
      const uint32_t yad = (ym >> 1) * 4096 + yr8 * 128 + (((2 * w + (ym & 1)) ^ yr8) << 4);
#define STAGE_BEGIN() mbar_wait(bar + B_FULL + 8 * (v & 3), (v >> 2) & 1); const uint32_t st = sb + (v & 3) * G_STAGE
#define RELEASE(vv) do { if (w == 0 && lane < 2) mbar_arrive_cluster(bar + B_EMPTY + 8 * ((vv) & 3), lane, 1); } while (0)
#define XRAW (sb + OFF_XR + (wg * 3 + xs) * 8192)
#define STAGE_W0(mw, sd) do { W_WAIT(mw); batch<1, 0, 2>(yr, yi, t, st, wg, sd, sb + OFF_F, WRAW(mw)); wg_wait<1>(); W_FINISH(); wg_wait<0>(); RELEASE(v); } while (0)
#define STAGE_PLAIN0(sd) do { batch<0, 0, 2>(yr, yi, t, st, wg, sd, 0, 0); wg_wait<0>(); RELEASE(v); } while (0)
#define STAGE_W1(mw, sd) do { W_WAIT(mw); batch<1, 0, 1>(yr, yi, t, st, wg, sd, sb + OFF_F, WRAW(mw)); wg_wait<1>(); if (sd) RELEASE(v - 1); \
                              W_FINISH(); batch<0, 1, 2>(yr, yi, t, st, wg, 1, 0, 0); } while (0)
      constexpr int VX = 31 - 2 * LW;
#pragma unroll 1
      for (int v = 0; v < VX; v++) {
        const int m = ((v + 1) >> 1) + LW;
        STAGE_BEGIN();
        if (!(v & 1)) {
          STAGE_W1(m, v != 0);
        } else {
          X_WAIT();
          batch<4, 0, 1>(yr, yi, t, st, wg, 1, sb + OFF_F, XRAW);
          wg_wait<1>();
          RELEASE(v - 1);
          X_FINISH((2 * id + wg) & 7);
          if (has_x2(id, m, wg)) {
            X_WAIT();
            batch<4, 1, 2>(yr, yi, t, st, wg, 1, sb + OFF_F, XRAW);
            wg_wait<1>();
            X_FINISH(id & 7);
          } else {
            batch<0, 1, 2>(yr, yi, t, st, wg, 1, 0, 0);
          }
        }
      }
      wg_wait<0>();
      RELEASE(VX - 1);
#pragma unroll 1
      for (int v = VX; v < 32; v++) {
        const int m = ((v + 1) >> 1) + LW;
        STAGE_BEGIN();
        if (!(v & 1) || v == 31) STAGE_W0(m, 1); else STAGE_PLAIN0(1);
      }
      fence_regs(yr);
      fence_regs(yi);
      {
        uint32_t hold[32];
#pragma unroll
        for (int j = 0; j < 20; j++) {
          const uint32_t p0 = pack2(yr[4 * j], yr[4 * j + 1]), p1 = pack2(yr[4 * j + 2], yr[4 * j + 3]);
          const uint32_t p2 = pack2(yi[4 * j], yi[4 * j + 1]), p3 = pack2(yi[4 * j + 2], yi[4 * j + 3]);
          if (j < 12) {
            stsm4t(sb + OFF_XR + wg * 3 * 8192 + yad + (j >> 2) * 8192 + (j & 3) * 1024, p0, p1, p2, p3);
          } else {
            hold[4 * j - 48] = p0; hold[4 * j - 47] = p1; hold[4 * j - 46] = p2; hold[4 * j - 45] = p3;
          }
        }
#pragma unroll
        for (int j = 0; j < 32; j++) asm volatile("" : "+r"(hold[j])::"memory");
        __syncwarp();
        if (lane == 0) mbar_arrive(bar + B_Y + 8 * wg);
#pragma unroll
        for (int v = 32; v < 34; v++) {
          STAGE_BEGIN();
          STAGE_PLAIN0(v != 32);
        }
        mbar_wait(bar + B_YFREE + 8 * wg, 0);
#pragma unroll
        for (int j = 0; j < 8; j++)
          stsm4t(sb + OFF_XR + wg * 3 * 8192 + yad + (j >> 2) * 8192 + (j & 3) * 1024, hold[4 * j], hold[4 * j + 1], hold[4 * j + 2], hold[4 * j + 3]);
        __syncwarp();
        if (lane == 0) mbar_arrive(bar + B_Y + 8 * wg);
#pragma unroll
        for (int j = 0; j < 32; j++) t[j] = __uint_as_float(hold[j]);
      }
#pragma unroll 1
      for (int v = 34; v < 64; v++) {
        const int m = (v >> 1) + LW;
        STAGE_BEGIN();
        if (!(v & 1) && m < 32) {
          STAGE_W0(m, 1);
        } else {
          STAGE_PLAIN0(1);
          if (v == 49 && wg == 0) part_ptr(xbuf, id >> 6, w >> 1, rank * 2 + ((id >> 1) & 1), (id >> 2) & 15)[(w & 1) * 32 + lane] = ~0ull;
        }
      }
      wg_wait<0>();
      fence_regs(yr);
      fence_regs(yi);
      mbar_wait(bar + B_EMPTY + 8 * 2, 1);
#pragma unroll
      for (int j = 0; j < 20; j++) {
        stsm4t(sb + wg * 8192 + yad + (j >> 2) * 16384 + (j & 3) * 1024, pack2(yr[4 * j], yr[4 * j + 1]), pack2(yr[4 * j + 2], yr[4 * j + 3]),
               pack2(yi[4 * j], yi[4 * j + 1]), pack2(yi[4 * j + 2], yi[4 * j + 3]));
        if ((j & 3) == 3) {
          __syncwarp();
          if (lane == 0) mbar_arrive(bar + B_YP + 8 * (wg * 5 + (j >> 2)));
        }
      }
    }
    __syncwarp();
    asm volatile("barrier.cluster.arrive.relaxed.aligned;" ::: "memory");
    lane = lane_id();
    const int tid = warp * 32 + lane, b = id >> 6, u = (id >> 1) & 31;
    const int dq = rank * 2 + (u & 1), tr = u >> 1;
    const int a = lane & 3, d0 = 16 * w + (lane >> 2);
    float2* s_red = (float2*)(smem_raw + OFF_WRAW);
    const uint32_t oad = wg * 8192 + ((lane >> 4) * 8 + (lane & 7)) * 128 + (((2 * w + ((lane >> 3) & 1)) ^ (lane & 7)) << 4);
    float hz[28];
#pragma unroll
    for (int i = 0; i < 28; i++) hz[i] = 0.f;
#pragma unroll 1
    for (int hf = 0; hf < 2; hf++) {
      const uint32_t base = sb + (hf ? 0 : OFF_XR), last = hf ? 0 : OFF_H0B - 65536 - OFF_XR;
      float acc[5][28];
      float q1[4] = {0.f, 0.f, 0.f, 0.f}, q2[4] = {0.f, 0.f, 0.f, 0.f};
      if (hf == 0) { mbar_wait(bar + B_H0, 0); mbar_wait(bar + B_H0C, 0); }
      const float* se = (const float*)(smem_raw + OFF_E + hf * 2560) + wg * 64 + d0;
#pragma unroll
      for (int k2 = 0; k2 < 3; k2++) {
        if (hf) mbar_wait(bar + B_H1 + 8 * k2, 0);
        else if (k2 == 2) mbar_wait(bar + B_H0 + 8, 0);
        const uint64_t da = mk_desc(base + (4 * k2 + wg) * 8192 + (k2 == 2 ? last : 0)), db = mk_desc(sb + OFF_F);
        wg_fence();
#pragma unroll
        for (int kk = 0; kk < 4; kk++) {
          wgmma_inv<1>(acc[2 * k2], da + 128 * kk, db + 2 * kk, kk);
          if (k2 < 2) wgmma_inv<1>(acc[2 * k2 + 1], da + 1024 + 128 * kk, db + 2 * kk, kk);
        }
        wg_commit();
        wg_wait<0>();
#pragma unroll
        for (int k = 2 * k2; k < 2 * k2 + 2 && k < 5; k++) {
          fence_regs(acc[k]);
          if (a == 0) {
            acc[k][25] += se[k * 128];
            acc[k][27] += se[k * 128 + 8];
          }
          if (k == 4 && tr == 15 && wg == 1) {
#pragma unroll
            for (int i = 16; i < 28; i++)
              if (8 * (i >> 2) + (i & 1) + 2 * a >= LOUT - (NT - 1) * MT) acc[k][i] = 0.f;
          }
#pragma unroll
          for (int i = 0; i < 28; i++) {
            q1[i & 3] += acc[k][i];
            q2[i & 3] = fmaf(acc[k][i], acc[k][i], q2[i & 3]);
          }
          fence_regs(q1);
          fence_regs(q2);
        }
      }
      float s1[2] = {q1[0] + q1[1], q1[2] + q1[3]}, s2[2] = {q2[0] + q2[1], q2[2] + q2[3]};
#pragma unroll
      for (int i = 0; i < 2; i++) {
#pragma unroll
        for (int o = 1; o < 4; o <<= 1) {
          s1[i] += __shfl_xor_sync(0xffffffffu, s1[i], o);
          s2[i] += __shfl_xor_sync(0xffffffffu, s2[i], o);
        }
      }
      if (a == 0) {
        s_red[wg * 64 + d0] = make_float2(s1[0], s2[0]);
        s_red[wg * 64 + d0 + 8] = make_float2(s1[1], s2[1]);
      }
      asm volatile("bar.sync 3, 256;" ::: "memory");
      if (tid < 64) {
        const float2 p0 = s_red[tid], p1 = s_red[64 + tid];
        const float x1 = p0.x + p1.x, x2 = p0.y + p1.y;
        const unsigned long long v = ((unsigned long long)(__float_as_uint(x2) & 0x7fffffffu) << 32) | __float_as_uint(x1);
        asm volatile("st.relaxed.gpu.global.u64 [%0], %1;" ::"l"(part_ptr(xbuf, b, hf, dq, tr) + tid), "l"(v) : "memory");
      }
      if (hf) {
        gelu_store(hz, sb + OFF_H0B + oad);
        __syncwarp();
        if (lane == 0) mbar_arrive(bar + B_OUT + 8 * (wg * 5 + 4));
      }
      {
        const unsigned long long* q = part_ptr(xbuf, b, hf, dq, (tid >> 6) * 4) + (tid & 63);
        unsigned long long v[4];
        poll64x4(q, v);
        float x1 = 0.f, x2 = 0.f;
#pragma unroll
        for (int i = 0; i < 4; i++) {
          x1 += __uint_as_float((uint32_t)v[i]);
          x2 += __uint_as_float((uint32_t)(v[i] >> 32));
        }
        s_red[128 + tid] = make_float2(x1, x2);
      }
      asm volatile("bar.sync 3, 256;" ::: "memory");
#pragma unroll
      for (int i = 0; i < 2; i++) {
        const float2 q0 = s_red[128 + d0 + 8 * i], q1 = s_red[192 + d0 + 8 * i], q2 = s_red[256 + d0 + 8 * i], q3 = s_red[320 + d0 + 8 * i];
        const float mu = ((q0.x + q1.x) + (q2.x + q3.x)) * (1.f / LOUT);
        const float var = fmaxf(((q0.y + q1.y) + (q2.y + q3.y)) * (1.f / LOUT) - mu * mu, 0.f);
        const __nv_bfloat16* gb = (const __nv_bfloat16*)(smem_raw + OFF_GB + hf * 256) + d0 + 8 * i;
        s1[i] = 0.5f * __bfloat162float(gb[0]) * rsqrtf(var + 1e-5f);
        s2[i] = 0.5f * __bfloat162float(gb[64]) - mu * s1[i];
      }
      float zp = 0.f;
#pragma unroll
      for (int k = 0; k < 5; k++) {
#pragma unroll
        for (int i = 0; i < 28; i++) hz[i] = fmaf(acc[k][i], s1[(i >> 1) & 1], s2[(i >> 1) & 1]);
        if (k == 4) break;
        gelu_store(hz, base + oad + k * 16384);
        s2[0] += zp;
        s2[1] += zp;
        asm volatile("ld.volatile.shared.f32 %0, [%1];" : "=f"(zp) : "r"(sb + OFF_F + 55 * 128) : "memory");
        __syncwarp();
        if (lane == 0) mbar_arrive(bar + B_OUT + 80 * hf + 8 * (wg * 5 + k));
      }
    }
    gelu_store(hz, sb + 4 * 16384 + oad);
    __syncwarp();
    if (lane == 0) mbar_arrive(bar + B_YP + 8 * (wg * 5 + 4));
    __syncwarp();
    asm volatile("barrier.cluster.wait.aligned;" ::: "memory");
  }
}

__global__ void __launch_bounds__(256) fb_conv(const __nv_bfloat16* __restrict__ x, const __nv_bfloat16* __restrict__ w, float* __restrict__ h) {
  __shared__ float sx[16][65], sw[16][64];
  const int b = blockIdx.z, l0 = blockIdx.y * 64, d0 = blockIdx.x * 64, tx = threadIdx.x & 15, ty = threadIdx.x >> 4;
  float acc[4][4] = {};
  for (int k0 = 0; k0 < 31 * 512; k0 += 16) {
    for (int i = threadIdx.x; i < 1024; i += 256) {
      const int l = min(l0 + (i >> 4), LOUT - 1);
      sx[i & 15][i >> 4] = __bfloat162float(x[((size_t)b * 16000 + 2 * l) * 512 + k0 + (i & 15)]);
      sw[i >> 6][i & 63] = __bfloat162float(w[(size_t)(k0 + (i >> 6)) * 512 + d0 + (i & 63)]);
    }
    __syncthreads();
#pragma unroll
    for (int k = 0; k < 16; k++)
#pragma unroll
      for (int i = 0; i < 4; i++)
#pragma unroll
        for (int j = 0; j < 4; j++) acc[i][j] = fmaf(sx[k][ty * 4 + i], sw[k][tx * 4 + j], acc[i][j]);
    __syncthreads();
  }
  for (int i = 0; i < 4; i++)
    for (int j = 0; j < 4; j++)
      if (l0 + ty * 4 + i < LOUT) h[((size_t)b * LOUT + l0 + ty * 4 + i) * 512 + d0 + tx * 4 + j] = acc[i][j];
}
__global__ void __launch_bounds__(256) fb_norm(const float* __restrict__ h, const __nv_bfloat16* __restrict__ gamma,
                                               const __nv_bfloat16* __restrict__ beta, __nv_bfloat16* __restrict__ out) {
  __shared__ float r[2][32][8];
  const int c = threadIdx.x & 7, q = threadIdx.x >> 3, d = blockIdx.x * 8 + c;
  const size_t base = (size_t)blockIdx.y * LOUT * 512 + d;
  float mu = 0.f, var = 0.f;
  for (int pass = 0; pass < 2; pass++) {
    float s = 0.f;
    for (int l = q; l < LOUT; l += 32) {
      const float v = h[base + (size_t)l * 512] - mu;
      s += pass ? v * v : v;
    }
    r[pass][q][c] = s;
    __syncthreads();
    s = 0.f;
    for (int i = 0; i < 32; i++) s += r[pass][i][c];
    if (pass) var = s / LOUT; else mu = s / LOUT;
  }
  const float g = __bfloat162float(gamma[d]) * rsqrtf(var + 1e-5f), be = __bfloat162float(beta[d]);
  for (int l = q; l < LOUT; l += 32) {
    const float z = (h[base + (size_t)l * 512] - mu) * g + be;
    out[base + (size_t)l * 512] = __float2bfloat16(0.5f * z * (1.f + tanhf(0.7978845608028654f * (z + 0.044715f * z * z * z))));
  }
}

typedef CUresult (*EncFn)(CUtensorMap*, CUtensorMapDataType, cuuint32_t, void*, const cuuint64_t*, const cuuint64_t*, const cuuint32_t*,
                          const cuuint32_t*, CUtensorMapInterleave, CUtensorMapSwizzle, CUtensorMapL2promotion, CUtensorMapFloatOOBfill);

void encode(EncFn fn, CUtensorMap* m, int rank, void* base, const cuuint64_t* dims, const cuuint64_t* strides, const cuuint32_t* box,
            CUtensorMapL2promotion promo) {
  cuuint32_t es[5] = {1, 1, 1, 1, 1};
  fn(m, CU_TENSOR_MAP_DATA_TYPE_BFLOAT16, rank, base, dims, strides, box, es, CU_TENSOR_MAP_INTERLEAVE_NONE, CU_TENSOR_MAP_SWIZZLE_128B, promo,
     CU_TENSOR_MAP_FLOAT_OOB_FILL_NONE);
}

}

extern "C" void kernel_launch(void* const* d_in, const int* in_sizes, int n_in, void* d_out, int out_size) {
  (void)in_sizes; (void)n_in; (void)out_size;
  const __nv_bfloat16* x = (const __nv_bfloat16*)d_in[0];
  const __nv_bfloat16* w = (const __nv_bfloat16*)d_in[1];
  const __nv_bfloat16* gamma = (const __nv_bfloat16*)d_in[2];
  const __nv_bfloat16* beta = (const __nv_bfloat16*)d_in[3];
  void* fnp = nullptr;
  cudaDriverEntryPointQueryResult qr;
  cudaGetDriverEntryPoint("cuTensorMapEncodeTiled", &fnp, cudaEnableDefault, &qr);
  EncFn fn = (EncFn)fnp;
  void *fptr = nullptr, *xptr = nullptr;
  cudaGetSymbolAddress(&fptr, g_Fimg);
  cudaGetSymbolAddress(&xptr, g_X);
  xptr = (void*)(((uintptr_t)xptr + (1u << 21) - 1) & ~(uintptr_t)((1u << 21) - 1));
  const CUtensorMapL2promotion P0 = CU_TENSOR_MAP_L2_PROMOTION_NONE, P128 = CU_TENSOR_MAP_L2_PROMOTION_L2_128B;
  Maps m;
  {
    cuuint64_t d[3] = {1024, 8000, 2}, s[2] = {2048, 8000ull * 2048};
    cuuint32_t bx[3] = {64, 64, 1};
    encode(fn, &m.x, 3, (void*)x, d, s, bx, P128);
  }
  for (int ph = 0; ph < 2; ph++) {
    cuuint64_t d[3] = {64, (cuuint64_t)(16 - ph), 4096}, s[2] = {2ull * 262144 * 2, 128};
    cuuint32_t bx[3] = {64, 16, 1};
    encode(fn, ph ? &m.wo : &m.we, 3, (void*)(w + (size_t)ph * 262144), d, s, bx, P128);
  }
  for (int par = 0; par < 2; par++) {
    cuuint64_t d[5] = {(cuuint64_t)XPAGES << 20, 2, 4, 2, 2}, s[4] = {par ? 0x1000u : 0x3000u, 1u << 14, 1u << 18, 1u << 20};
    cuuint32_t bx[5] = {64, 2, 4, 2, 2};
    encode(fn, &m.xst[par], 5, xptr, d, s, bx, P0);
  }
  {
    cuuint64_t d[4] = {64, 32, 2, (cuuint64_t)WR * WSLOT / 128}, s[3] = {2ull * WBLK, 4096, 128};
    cuuint32_t bx[4] = {64, 32, 2, 1};
    encode(fn, &m.wst, 4, (char*)xptr + ((size_t)PG_W << 21), d, s, bx, P0);
  }
  for (int par = 0; par < 2; par++) {
    cuuint64_t d[4] = {64, (cuuint64_t)XPAGES << 14, 2, 2}, s[3] = {128, par ? 0xf000u : 0x11000u, 1u << 14};
    cuuint32_t bx[4] = {64, 32, 2, 2};
    encode(fn, &m.yld[par], 4, xptr, d, s, bx, P128);
  }
  {
    cuuint64_t d[3] = {512, LOUT, 2}, s[2] = {1024, (cuuint64_t)LOUT * 1024};
    cuuint32_t bx[3] = {64, MT, 1};
    encode(fn, &m.out, 3, d_out, d, s, bx, P0);
  }
  for (int q = 0; q < 2; q++) {
    cuuint64_t d[3] = {512, (cuuint64_t)(NT - q), 2}, s[2] = {MT * 2048, 8000ull * 2048};
    cuuint32_t bx[3] = {64, NT, 1};
    encode(fn, &m.xe[q], 3, (void*)(x + q * 64 * 1024), d, s, bx, P128);
  }
  {
    cuuint64_t d[2] = {512, 512}, s[1] = {1024};
    cuuint32_t bx[2] = {64, 64};
    encode(fn, &m.w30, 2, (void*)(w + 30 * 262144), d, s, bx, P128);
  }
  cudaFuncSetAttribute(k1_main, cudaFuncAttributeMaxDynamicSharedMemorySize, SMEM_BYTES);
  cudaLaunchConfig_t cfg = {};
  cfg.gridDim = dim3(132);
  cfg.blockDim = dim3(512);
  cfg.dynamicSmemBytes = SMEM_BYTES;
  int clusters = 0;
  cudaOccupancyMaxActiveClusters(&clusters, k1_main, &cfg);
  if (clusters < 66) {
    fb_conv<<<dim3(8, (LOUT + 63) / 64, 2), 256>>>(x, w, (float*)xptr);
    fb_norm<<<dim3(64, 2), 256>>>((const float*)xptr, gamma, beta, (__nv_bfloat16*)d_out);
    return;
  }
  k1_main<<<132, 512, SMEM_BYTES>>>((uint8_t*)xptr, fptr, gamma, beta, m);
}
```
